```python
import torch

def _softmax(x, axis=-1):
    return torch.softmax(x, dim=axis)

def _gelu(x):
    return torch.nn.functional.gelu(x, approximate='tanh')

def _silu(x):
    return torch.nn.functional.silu(x)

def _sigmoid(x):
    return torch.sigmoid(x)

def _layernorm(x, axis=-1, eps=1e-05):
    m = x.mean(dim=axis, keepdim=True)
    v = x.var(dim=axis, keepdim=True, unbiased=False)
    return (x - m) / torch.sqrt(v + eps)

def _scatter_add(tgt, idx, src, axis=0):
    return tgt.clone().index_add_(axis, idx, src)

def _segment_sum(src, seg, n):
    out = torch.zeros((n,) + src.shape[1:], dtype=src.dtype)
    return out.index_add_(0, seg, src)

def _pad(x, pw):
    flat = tuple((v for pair in reversed(pw) for v in pair))
    return torch.nn.functional.pad(x, flat)
kernel_name = 'concat_heads__memory_aug_recurrent_mem_tr__spectral_gfnet__prompt'

def setup_inputs():

    _w = lambda a: (lambda t: t.to(torch.bfloat16) if t.is_floating_point() else t)(torch.as_tensor(a))

    def _A_setup():
        B, S, Dm = (1, 2048, 1024)
        H, Dh = (32, 128)
        M, seg = (8, 32)
        seg = min(seg, S)
        S = S // seg * seg
        return {'x': _w((lambda *s: torch.randn(*s, dtype=torch.bfloat16) * 0.05)(B, S, Dm)), 'mem0': _w((lambda *s: torch.randn(*s, dtype=torch.bfloat16) * 0.4)(B, M, Dm)), 'Wq': _w((lambda *s: torch.randn(*s, dtype=torch.bfloat16) * 6.4)(Dm, H, Dh) * Dm ** (-0.5)), 'Wk': _w((lambda *s: torch.randn(*s, dtype=torch.bfloat16) * 6.4)(Dm, H, Dh) * Dm ** (-0.5)), 'Wv': _w((lambda *s: torch.randn(*s, dtype=torch.bfloat16) * 0.4)(Dm, H, Dh) * Dm ** (-0.5)), 'Wo': _w((lambda *s: torch.randn(*s, dtype=torch.bfloat16) * 0.4)(H, Dh, Dm) * (H * Dh) ** (-0.5)), 'seg_len': seg}
    _A_in = _A_setup()

    def _B_setup():
        B, S, D = (1, 2048, 1024)
        Df = D // 2 + 1
        return {'x': _w((lambda *s: torch.randn(*s, dtype=torch.bfloat16) * 0.05)(B, S, D)), 'w_r': _w((lambda *s: torch.randn(*s, dtype=torch.bfloat16) * 3.2)(S, Df) * 0.02), 'w_i': _w((lambda *s: torch.randn(*s, dtype=torch.bfloat16) * 3.2)(S, Df) * 0.02)}
    _B_in = _B_setup()
    return {'A_x': _A_in['x'], 'A_mem0': _A_in['mem0'], 'A_Wq': _A_in['Wq'], 'A_Wk': _A_in['Wk'], 'A_Wv': _A_in['Wv'], 'A_Wo': _A_in['Wo'], 'A_seg_len': _A_in['seg_len'], 'B_x': _B_in['x'], 'B_w_r': _B_in['w_r'], 'B_w_i': _B_in['w_i']}

def reference(A_x, A_mem0, A_Wq, A_Wk, A_Wv, A_Wo, A_seg_len, B_x, B_w_r, B_w_i):

    def _A_ref(x, mem0, Wq, Wk, Wv, Wo, seg_len):
        B, S, Dm = x.shape
        H, Dh = (Wq.shape[1], Wq.shape[2])
        M = mem0.shape[1]
        scale = Dh ** (-0.5)
        n_seg = S // seg_len
        L = M + seg_len
        idx = torch.arange(L)
        mask = (idx[:, None] < M) | (idx[:, None] >= idx[None, :])
        mem = mem0
        outs = []
        for s in range(n_seg):
            xs = x[:, s * seg_len:(s + 1) * seg_len, :].clone()
            h = torch.concatenate([mem, xs], axis=1)
            q = torch.einsum('btd,dhe->bhte', h, Wq)
            k = torch.einsum('btd,dhe->bhte', h, Wk)
            v = torch.einsum('btd,dhe->bhte', h, Wv)
            scores = torch.einsum('bhqe,bhke->bhqk', q, k) * scale
            scores = torch.where(mask[None, None], scores, -1000000000.0)
            p = _softmax(scores, axis=-1)
            o = torch.einsum('bhqk,bhke->bhqe', p, v)
            o = torch.einsum('bhte,hed->btd', o, Wo)
            mem = o[:, :M, :].clone()
            outs.append(o[:, M:, :])
        return torch.concatenate(outs, axis=1)

    def _B_ref(x, w_r, w_i):
        B, S, D = x.shape
        X = (lambda x, axes=(-2, -1): torch.fft.rfft2(x.float(), dim=axes))(x, axes=(-2, -1))
        W = w_r + 1j * w_i
        X = X * W
        y = (lambda x, s, axes=(-2, -1): torch.fft.irfft2(x, s=s, dim=axes).to(torch.bfloat16))(X, (S, D), axes=(-2, -1))
        return y
    a = _A_ref(A_x, A_mem0, A_Wq, A_Wk, A_Wv, A_Wo, A_seg_len)
    b = _B_ref(B_x, B_w_r, B_w_i)
    return torch.concatenate([a, b], axis=-1)
```

```cpp
#include <cuda_runtime.h>
#include <cuda_bf16.h>
#include <cuda.h>
#include <stdint.h>

typedef __nv_bfloat16 bf16;

constexpr int S_LEN = 2048, DM = 1024, NH = 32, DH = 128, MEM = 8, SEG = 32, NSEG = 64;
constexpr int HD = NH * DH;
constexpr int SPIN_LIMIT = 1 << 20;

__device__ __align__(1024) bf16 g_qkv[(size_t)S_LEN * 3 * HD];
__device__ __align__(1024) bf16 g_ox[(size_t)S_LEN * HD];
struct Xchg {
  uint4 A[128][2][32];
  uint4 V[128][32];
  uint4 C[1024];
  uint4 B[128][256];
};
__device__ __align__(4096) Xchg g_x;
__device__ __align__(1024) float2 g_f1[513 * 2048];
__device__ int g_err;
#define TS(i)

__device__ __forceinline__ unsigned clk() { unsigned c; asm volatile("mov.u32 %0, %%clock;" : "=r"(c)); return c; }
__device__ __forceinline__ uint32_t smem_u32(const void* p) { return (uint32_t)__cvta_generic_to_shared(p); }
__device__ __forceinline__ void mbar_init(uint32_t bar, int cnt) { asm volatile("mbarrier.init.shared::cta.b64 [%0], %1;" :: "r"(bar), "r"(cnt) : "memory"); }
__device__ __forceinline__ void mbar_expect_tx(uint32_t bar, int bytes) { asm volatile("mbarrier.arrive.expect_tx.shared::cta.b64 _, [%0], %1;" :: "r"(bar), "r"(bytes) : "memory"); }
__device__ __forceinline__ void mbar_arrive(uint32_t bar) { asm volatile("mbarrier.arrive.shared::cta.b64 _, [%0];" :: "r"(bar) : "memory"); }
__device__ __forceinline__ void mbar_arrive_cluster(uint32_t bar, int cta) {
  asm volatile("{.reg .b32 r; mapa.shared::cluster.u32 r, %0, %1; mbarrier.arrive.release.cluster.shared::cluster.b64 _, [r];}" :: "r"(bar), "r"(cta) : "memory"); }
__device__ __forceinline__ bool mbar_try(uint32_t bar, int par) {
  uint32_t ok; asm volatile("{.reg .pred p; mbarrier.try_wait.parity.shared::cta.b64 p, [%1], %2; selp.u32 %0, 1, 0, p;}" : "=r"(ok) : "r"(bar), "r"(par) : "memory"); return ok; }
__device__ __forceinline__ void mbar_wait(uint32_t bar, int par) {
  int it = 0;
  while (!mbar_try(bar, par)) { if (++it > SPIN_LIMIT) { g_err = 1; break; } }
}
__device__ __forceinline__ void tma2d(uint32_t dst, const CUtensorMap* m, int c0, int c1, uint32_t bar) {
  asm volatile("cp.async.bulk.tensor.2d.shared::cluster.global.mbarrier::complete_tx::bytes [%0], [%1, {%3, %4}], [%2];"
    :: "r"(dst), "l"(m), "r"(bar), "r"(c0), "r"(c1) : "memory"); }
__device__ __forceinline__ void tma2d_mc(uint32_t dst, const CUtensorMap* m, int c0, int c1, uint32_t bar, uint16_t mask) {
  asm volatile("cp.async.bulk.tensor.2d.shared::cluster.global.mbarrier::complete_tx::bytes.multicast::cluster [%0], [%1, {%3, %4}], [%2], %5;"
    :: "r"(dst), "l"(m), "r"(bar), "r"(c0), "r"(c1), "h"(mask) : "memory"); }
__device__ __forceinline__ void tma2d_store(const CUtensorMap* m, uint32_t src, int c0, int c1) {
  asm volatile("cp.async.bulk.tensor.2d.global.shared::cta.bulk_group [%0, {%2, %3}], [%1];" :: "l"(m), "r"(src), "r"(c0), "r"(c1) : "memory"); }
__device__ __forceinline__ void fence_async() { asm volatile("fence.proxy.async.shared::cta;" ::: "memory"); }
__device__ __forceinline__ void bar_sync(int id, int n) { asm volatile("bar.sync %0, %1;" :: "r"(id), "r"(n) : "memory"); }
__device__ __forceinline__ void bar_arrive(int id, int n) { asm volatile("bar.arrive %0, %1;" :: "r"(id), "r"(n) : "memory"); }
__device__ __forceinline__ uint32_t pack2(float lo, float hi) { uint32_t r; asm("cvt.rn.bf16x2.f32 %0, %1, %2;" : "=r"(r) : "f"(hi), "f"(lo)); return r; }
__device__ __forceinline__ uint32_t pack2_tag(float lo, float hi, uint32_t T) {
  uint32_t u = ((__float_as_uint(lo) - T + 0x10000u) & 0xFFFE0000u) + T;
  return __byte_perm(u, pack2(0.f, hi), 0x7632); }
__device__ __forceinline__ void ldsm4(uint32_t (&r)[4], uint32_t a) {
  asm volatile("ldmatrix.sync.aligned.m8n8.x4.shared.b16 {%0,%1,%2,%3}, [%4];" : "=r"(r[0]), "=r"(r[1]), "=r"(r[2]), "=r"(r[3]) : "r"(a) : "memory"); }
__device__ __forceinline__ void ldsm4t(uint32_t (&r)[4], uint32_t a) {
  asm volatile("ldmatrix.sync.aligned.m8n8.x4.trans.shared.b16 {%0,%1,%2,%3}, [%4];" : "=r"(r[0]), "=r"(r[1]), "=r"(r[2]), "=r"(r[3]) : "r"(a) : "memory"); }
__device__ __forceinline__ void stsm4(uint32_t a, uint32_t r0, uint32_t r1, uint32_t r2, uint32_t r3) {
  asm volatile("stmatrix.sync.aligned.m8n8.x4.shared.b16 [%0], {%1,%2,%3,%4};" :: "r"(a), "r"(r0), "r"(r1), "r"(r2), "r"(r3) : "memory"); }
__device__ __forceinline__ void stsm4t(uint32_t a, uint32_t r0, uint32_t r1, uint32_t r2, uint32_t r3) {
  asm volatile("stmatrix.sync.aligned.m8n8.x4.trans.shared.b16 [%0], {%1,%2,%3,%4};" :: "r"(a), "r"(r0), "r"(r1), "r"(r2), "r"(r3) : "memory"); }
__device__ __forceinline__ void lds128(uint32_t (&r)[4], uint32_t a) {
  asm volatile("ld.shared.v4.u32 {%0,%1,%2,%3}, [%4];" : "=r"(r[0]), "=r"(r[1]), "=r"(r[2]), "=r"(r[3]) : "r"(a) : "memory"); }
__device__ __forceinline__ float4 lds128f(uint32_t a) { float4 r;
  asm volatile("ld.shared.v4.f32 {%0,%1,%2,%3}, [%4];" : "=f"(r.x), "=f"(r.y), "=f"(r.z), "=f"(r.w) : "r"(a) : "memory"); return r; }
__device__ __forceinline__ float2 lds64f(uint32_t a) { float2 r;
  asm volatile("ld.shared.v2.f32 {%0,%1}, [%2];" : "=f"(r.x), "=f"(r.y) : "r"(a) : "memory"); return r; }
__device__ __forceinline__ void sts128(uint32_t a, uint32_t r0, uint32_t r1, uint32_t r2, uint32_t r3) {
  asm volatile("st.shared.v4.u32 [%0], {%1,%2,%3,%4};" :: "r"(a), "r"(r0), "r"(r1), "r"(r2), "r"(r3) : "memory"); }
__device__ __forceinline__ void sts64f(uint32_t a, float x, float y) { asm volatile("st.shared.v2.f32 [%0], {%1,%2};" :: "r"(a), "f"(x), "f"(y) : "memory"); }
__device__ __forceinline__ void sts32f(uint32_t a, float x) { asm volatile("st.shared.f32 [%0], %1;" :: "r"(a), "f"(x) : "memory"); }
__device__ __forceinline__ void mma16816(float (&d)[4], uint32_t a0, uint32_t a1, uint32_t a2, uint32_t a3, uint32_t b0, uint32_t b1) {
  asm volatile("mma.sync.aligned.m16n8k16.row.col.f32.bf16.bf16.f32 {%0,%1,%2,%3}, {%4,%5,%6,%7}, {%8,%9}, {%0,%1,%2,%3};"
    : "+f"(d[0]), "+f"(d[1]), "+f"(d[2]), "+f"(d[3]) : "r"(a0), "r"(a1), "r"(a2), "r"(a3), "r"(b0), "r"(b1)); }
__device__ __forceinline__ void mma1688(float (&d)[4], uint32_t a0, uint32_t a1, uint32_t b0) {
  asm volatile("mma.sync.aligned.m16n8k8.row.col.f32.bf16.bf16.f32 {%0,%1,%2,%3}, {%4,%5}, {%6}, {%0,%1,%2,%3};"
    : "+f"(d[0]), "+f"(d[1]), "+f"(d[2]), "+f"(d[3]) : "r"(a0), "r"(a1), "r"(b0)); }
__device__ __forceinline__ void ldx128(uint32_t (&r)[4], const void* p) {
  asm volatile("{.reg .b128 t; .reg .b64 a, b; ld.relaxed.gpu.global.b128 t, [%4]; mov.b128 {a, b}, t; mov.b64 {%0,%1}, a; mov.b64 {%2,%3}, b;}"
    : "=r"(r[0]), "=r"(r[1]), "=r"(r[2]), "=r"(r[3]) : "l"(p) : "memory"); }
__device__ __forceinline__ void ldx2x64(uint32_t (&r)[4], const void* p) {
  asm volatile("{.reg .b64 a, b; ld.relaxed.gpu.global.v2.b64 {a, b}, [%4]; mov.b64 {%0,%1}, a; mov.b64 {%2,%3}, b;}"
    : "=r"(r[0]), "=r"(r[1]), "=r"(r[2]), "=r"(r[3]) : "l"(p) : "memory"); }
__device__ __forceinline__ void stx128(void* p, uint32_t r0, uint32_t r1, uint32_t r2, uint32_t r3) {
  asm volatile("{.reg .b128 t; .reg .b64 a, b; mov.b64 a, {%1,%2}; mov.b64 b, {%3,%4}; mov.b128 t, {a, b}; st.relaxed.gpu.global.b128 [%0], t;}"
    :: "l"(p), "r"(r0), "r"(r1), "r"(r2), "r"(r3) : "memory"); }
__device__ __forceinline__ void stx64(void* p, uint32_t r0, uint32_t r1) {
  asm volatile("{.reg .b64 a; mov.b64 a, {%1,%2}; st.relaxed.gpu.global.b64 [%0], a;}" :: "l"(p), "r"(r0), "r"(r1) : "memory"); }
__device__ __forceinline__ float ex2(float x) { float r; asm("ex2.approx.ftz.f32 %0, %1;" : "=f"(r) : "f"(x)); return r; }
__device__ __forceinline__ void wg_fence() { asm volatile("wgmma.fence.sync.aligned;" ::: "memory"); }
__device__ __forceinline__ void wg_commit() { asm volatile("wgmma.commit_group.sync.aligned;" ::: "memory"); }
template <int N> __device__ __forceinline__ void wg_wait() { asm volatile("wgmma.wait_group.sync.aligned %0;" :: "n"(N) : "memory"); }

__device__ __forceinline__ void wgmma_ss_n256_tb1(float (&d)[128], uint64_t da, uint64_t db, int sc) {
  asm volatile("{.reg .pred p; setp.ne.b32 p, %130, 0;\n"
    "wgmma.mma_async.sync.aligned.m64n256k16.f32.bf16.bf16 {%0,%1,%2,%3,%4,%5,%6,%7,%8,%9,%10,%11,%12,%13,%14,%15,%16,%17,%18,%19,%20,%21,%22,%23,%24,%25,%26,%27,%28,%29,%30,%31,%32,%33,%34,%35,%36,%37,%38,%39,%40,%41,%42,%43,%44,%45,%46,%47,%48,%49,%50,%51,%52,%53,%54,%55,%56,%57,%58,%59,%60,%61,%62,%63,%64,%65,%66,%67,%68,%69,%70,%71,%72,%73,%74,%75,%76,%77,%78,%79,%80,%81,%82,%83,%84,%85,%86,%87,%88,%89,%90,%91,%92,%93,%94,%95,%96,%97,%98,%99,%100,%101,%102,%103,%104,%105,%106,%107,%108,%109,%110,%111,%112,%113,%114,%115,%116,%117,%118,%119,%120,%121,%122,%123,%124,%125,%126,%127}, %128, %129, p, 1, 1, 0, 1;}\n"
    : "+f"(d[0]),"+f"(d[1]),"+f"(d[2]),"+f"(d[3]),"+f"(d[4]),"+f"(d[5]),"+f"(d[6]),"+f"(d[7]),"+f"(d[8]),"+f"(d[9]),"+f"(d[10]),"+f"(d[11]),"+f"(d[12]),"+f"(d[13]),"+f"(d[14]),"+f"(d[15]),"+f"(d[16]),"+f"(d[17]),"+f"(d[18]),"+f"(d[19]),"+f"(d[20]),"+f"(d[21]),"+f"(d[22]),"+f"(d[23]),"+f"(d[24]),"+f"(d[25]),"+f"(d[26]),"+f"(d[27]),"+f"(d[28]),"+f"(d[29]),"+f"(d[30]),"+f"(d[31]),"+f"(d[32]),"+f"(d[33]),"+f"(d[34]),"+f"(d[35]),"+f"(d[36]),"+f"(d[37]),"+f"(d[38]),"+f"(d[39]),"+f"(d[40]),"+f"(d[41]),"+f"(d[42]),"+f"(d[43]),"+f"(d[44]),"+f"(d[45]),"+f"(d[46]),"+f"(d[47]),"+f"(d[48]),"+f"(d[49]),"+f"(d[50]),"+f"(d[51]),"+f"(d[52]),"+f"(d[53]),"+f"(d[54]),"+f"(d[55]),"+f"(d[56]),"+f"(d[57]),"+f"(d[58]),"+f"(d[59]),"+f"(d[60]),"+f"(d[61]),"+f"(d[62]),"+f"(d[63]),"+f"(d[64]),"+f"(d[65]),"+f"(d[66]),"+f"(d[67]),"+f"(d[68]),"+f"(d[69]),"+f"(d[70]),"+f"(d[71]),"+f"(d[72]),"+f"(d[73]),"+f"(d[74]),"+f"(d[75]),"+f"(d[76]),"+f"(d[77]),"+f"(d[78]),"+f"(d[79]),"+f"(d[80]),"+f"(d[81]),"+f"(d[82]),"+f"(d[83]),"+f"(d[84]),"+f"(d[85]),"+f"(d[86]),"+f"(d[87]),"+f"(d[88]),"+f"(d[89]),"+f"(d[90]),"+f"(d[91]),"+f"(d[92]),"+f"(d[93]),"+f"(d[94]),"+f"(d[95]),"+f"(d[96]),"+f"(d[97]),"+f"(d[98]),"+f"(d[99]),"+f"(d[100]),"+f"(d[101]),"+f"(d[102]),"+f"(d[103]),"+f"(d[104]),"+f"(d[105]),"+f"(d[106]),"+f"(d[107]),"+f"(d[108]),"+f"(d[109]),"+f"(d[110]),"+f"(d[111]),"+f"(d[112]),"+f"(d[113]),"+f"(d[114]),"+f"(d[115]),"+f"(d[116]),"+f"(d[117]),"+f"(d[118]),"+f"(d[119]),"+f"(d[120]),"+f"(d[121]),"+f"(d[122]),"+f"(d[123]),"+f"(d[124]),"+f"(d[125]),"+f"(d[126]),"+f"(d[127])
    : "l"(da), "l"(db), "r"(sc));
}

__device__ __forceinline__ void wgmma_ss_n128_tb1(float (&d)[64], uint64_t da, uint64_t db, int sc) {
  asm volatile("{.reg .pred p; setp.ne.b32 p, %66, 0;\n"
    "wgmma.mma_async.sync.aligned.m64n128k16.f32.bf16.bf16 {%0,%1,%2,%3,%4,%5,%6,%7,%8,%9,%10,%11,%12,%13,%14,%15,%16,%17,%18,%19,%20,%21,%22,%23,%24,%25,%26,%27,%28,%29,%30,%31,%32,%33,%34,%35,%36,%37,%38,%39,%40,%41,%42,%43,%44,%45,%46,%47,%48,%49,%50,%51,%52,%53,%54,%55,%56,%57,%58,%59,%60,%61,%62,%63}, %64, %65, p, 1, 1, 0, 1;}\n"
    : "+f"(d[0]),"+f"(d[1]),"+f"(d[2]),"+f"(d[3]),"+f"(d[4]),"+f"(d[5]),"+f"(d[6]),"+f"(d[7]),"+f"(d[8]),"+f"(d[9]),"+f"(d[10]),"+f"(d[11]),"+f"(d[12]),"+f"(d[13]),"+f"(d[14]),"+f"(d[15]),"+f"(d[16]),"+f"(d[17]),"+f"(d[18]),"+f"(d[19]),"+f"(d[20]),"+f"(d[21]),"+f"(d[22]),"+f"(d[23]),"+f"(d[24]),"+f"(d[25]),"+f"(d[26]),"+f"(d[27]),"+f"(d[28]),"+f"(d[29]),"+f"(d[30]),"+f"(d[31]),"+f"(d[32]),"+f"(d[33]),"+f"(d[34]),"+f"(d[35]),"+f"(d[36]),"+f"(d[37]),"+f"(d[38]),"+f"(d[39]),"+f"(d[40]),"+f"(d[41]),"+f"(d[42]),"+f"(d[43]),"+f"(d[44]),"+f"(d[45]),"+f"(d[46]),"+f"(d[47]),"+f"(d[48]),"+f"(d[49]),"+f"(d[50]),"+f"(d[51]),"+f"(d[52]),"+f"(d[53]),"+f"(d[54]),"+f"(d[55]),"+f"(d[56]),"+f"(d[57]),"+f"(d[58]),"+f"(d[59]),"+f"(d[60]),"+f"(d[61]),"+f"(d[62]),"+f"(d[63])
    : "l"(da), "l"(db), "r"(sc));
}

template <int BN> struct WG;
template <> struct WG<256> { static __device__ __forceinline__ void mma(float (&d)[128], uint64_t a, uint64_t b, int sc) { wgmma_ss_n256_tb1(d, a, b, sc); } };
template <> struct WG<128> { static __device__ __forceinline__ void mma(float (&d)[64], uint64_t a, uint64_t b, int sc) { wgmma_ss_n128_tb1(d, a, b, sc); } };

struct GemmMaps { CUtensorMap a, b[3], c; };
template <int BN, int STAGES>
__global__ void __cluster_dims__(2, 1, 1) __launch_bounds__(384, 1)
gemm_kernel(const __grid_constant__ GemmMaps maps, int tilesM, int tilesN, int kblocks, int nPerB, int clearX) {
  extern __shared__ __align__(1024) uint8_t smem_raw[];
  constexpr int STAGE_BYTES = 16384 + BN * 128;
  constexpr int NBOX = BN / 64;
  const uint32_t sbase = (smem_u32(smem_raw) + 1023) & ~1023u;
  const uint32_t sEpi = sbase + STAGES * STAGE_BYTES;
  const uint32_t sBar = sEpi + 32768;
  const int warp = threadIdx.x >> 5, lane = threadIdx.x & 31, wg = warp >> 2;
  uint32_t crank; asm("mov.u32 %0, %%cluster_ctarank;" : "=r"(crank));
  if (threadIdx.x == 0) {
    for (int i = 0; i < STAGES; i++) { mbar_init(sBar + 8 * i, 1); mbar_init(sBar + 8 * (STAGES + i), 4); }
    asm volatile("fence.mbarrier_init.release.cluster;" ::: "memory");
  }
  if (clearX) {
    uint4* p = reinterpret_cast<uint4*>(&g_x);
    for (int i = blockIdx.x * 384 + threadIdx.x; i < (int)(sizeof(Xchg) / 16); i += gridDim.x * 384) p[i] = make_uint4(0, 0, 0, 0);
  }
  asm volatile("barrier.cluster.arrive.release.aligned; barrier.cluster.wait.acquire.aligned;" ::: "memory");
  const int npairs = (tilesM >> 1) * tilesN, pair0 = blockIdx.x >> 1, pstep = gridDim.x >> 1;
  if (wg == 2) {
    asm volatile("setmaxnreg.dec.sync.aligned.u32 40;");
    if (warp == 8 && lane == 0) {
      int st = 0, ph = 1;
      for (int p = pair0; p < npairs; p += pstep) {
        const int tm = (p % (tilesM >> 1)) * 2 + crank, tn = p / (tilesM >> 1);
        const CUtensorMap* mb = &maps.b[tn / nPerB];
        const int n0 = (tn % nPerB) * BN;
        for (int kb = 0; kb < kblocks; kb++) {
          mbar_wait(sBar + 8 * (STAGES + st), ph);
          const uint32_t a = sbase + st * STAGE_BYTES, full = sBar + 8 * st;
          mbar_expect_tx(full, STAGE_BYTES);
          tma2d(a, &maps.a, kb * 64, tm * 128, full);
#pragma unroll
          for (int i = 0; i < NBOX / 2; i++) {
            const int bx = crank * (NBOX / 2) + i;
            tma2d_mc(a + 16384 + bx * 8192, mb, n0 + bx * 64, kb * 64, full, (uint16_t)3);
          }
          if (++st == STAGES) { st = 0; ph ^= 1; }
        }
      }
      for (int i = 0; i < STAGES; i++) { mbar_wait(sBar + 8 * (STAGES + st), ph); if (++st == STAGES) { st = 0; ph ^= 1; } }
    }
  } else {
    asm volatile("setmaxnreg.inc.sync.aligned.u32 232;");
    int st = 0, ph = 0;
    float acc[BN / 2];
    const uint64_t descA0 = (uint64_t)(((sbase + wg * 8192) & 0x3FFFF) >> 4) | (1ull << 16) | (64ull << 32) | (1ull << 62);
    const uint64_t descB0 = (uint64_t)(((sbase + 16384) & 0x3FFFF) >> 4) | (512ull << 16) | (64ull << 32) | (1ull << 62);
    const uint32_t epi = sEpi + wg * 16384;
    for (int p = pair0; p < npairs; p += pstep) {
      const int tm = (p % (tilesM >> 1)) * 2 + crank, tn = p / (tilesM >> 1);
      int prev = -1;
      for (int kb = 0; kb < kblocks; kb++) {
        mbar_wait(sBar + 8 * st, ph);
        wg_fence();
        const uint64_t so = (uint64_t)(st * (STAGE_BYTES >> 4));
#pragma unroll
        for (int k = 0; k < 4; k++) WG<BN>::mma(acc, descA0 + so + k * 2, descB0 + so + k * 128, kb | k);
        wg_commit();
        if (prev >= 0) {
          wg_wait<1>();
          if ((threadIdx.x & 127) < 2) mbar_arrive_cluster(sBar + 8 * (STAGES + prev), threadIdx.x & 1);
        }
        prev = st;
        if (++st == STAGES) { st = 0; ph ^= 1; }
      }
      wg_wait<0>();
      if ((threadIdx.x & 127) < 2) mbar_arrive_cluster(sBar + 8 * (STAGES + prev), threadIdx.x & 1);
#pragma unroll
      for (int r = 0; r < BN / 128; r++) {
        if ((threadIdx.x & 127) == 0) asm volatile("cp.async.bulk.wait_group.read 0;" ::: "memory");
        bar_sync(1 + wg, 128);
        const int row = (warp & 3) * 16 + (lane & 15);
#pragma unroll
        for (int i = 0; i < 8; i++) {
          const int c = 2 * (i & 3) + (lane >> 4);
          const float* q = &acc[r * 64 + i * 8];
          stsm4(epi + (i >> 2) * 8192 + row * 128 + ((c ^ (row & 7)) << 4), pack2(q[0], q[1]), pack2(q[2], q[3]), pack2(q[4], q[5]), pack2(q[6], q[7]));
        }
        fence_async();
        bar_sync(1 + wg, 128);
        if ((threadIdx.x & 127) == 0) {
          tma2d_store(&maps.c, epi, tn * BN + r * 128, tm * 128 + wg * 64);
          tma2d_store(&maps.c, epi + 8192, tn * BN + r * 128 + 64, tm * 128 + wg * 64);
          asm volatile("cp.async.bulk.commit_group;" ::: "memory");
        }
      }
    }
    if ((threadIdx.x & 127) == 0) asm volatile("cp.async.bulk.wait_group 0;" ::: "memory");
  }
}

struct RecMaps { CUtensorMap wq, wk, wv, kv, q; };
constexpr int R_WV = 0, R_WO = 65536, R_MEM = 131072, R_KV = 147456, R_KVSZ = 18432, R_RED = 184320, R_REDV = 188672,
              R_S = 192768, R_O = 195328, R_SUM = 197376, R_OX = 197440, R_BAR = 200000, R_TOTAL = 200064 + 1024;

__device__ __forceinline__ void rec_issue_kv(const RecMaps& maps, uint32_t dst, uint32_t bar, int s, int h, int j) {
  mbar_expect_tx(bar, R_KVSZ);
  tma2d(dst, &maps.kv, HD + h * DH, s * SEG, bar);
  tma2d(dst + 4096, &maps.kv, HD + h * DH + 64, s * SEG, bar);
  tma2d(dst + 16384, &maps.q, h * DH, s * SEG + 8 * j, bar);
  tma2d(dst + 17408, &maps.q, h * DH + 64, s * SEG + 8 * j, bar);
  tma2d(dst + 8192, &maps.kv, 2 * HD + h * DH, s * SEG, bar);
  tma2d(dst + 12288, &maps.kv, 2 * HD + h * DH + 64, s * SEG, bar);
}

__device__ __forceinline__ void score_tile(const uint32_t (&a)[4][4], const uint32_t (&b)[4][4], uint32_t dst) {
  float c0[4] = {0, 0, 0, 0}, c1[4] = {0, 0, 0, 0};
#pragma unroll
  for (int i = 0; i < 4; i++) {
    mma16816(c0, a[i][0], 0, a[i][1], 0, b[i][0], b[i][1]);
    mma16816(c1, a[i][2], 0, a[i][3], 0, b[i][2], b[i][3]);
  }
  sts64f(dst, c0[0] + c1[0], c0[1] + c1[1]);
}

__global__ void __launch_bounds__(256, 1)
rec_kernel(const __grid_constant__ RecMaps maps, const bf16* __restrict__ Wo, const bf16* __restrict__ mem0) {
  extern __shared__ __align__(1024) uint8_t smem_raw[];
  const uint32_t sb = (smem_u32(smem_raw) + 1023) & ~1023u;
  const int tid = threadIdx.x, warp = tid >> 5, lane = tid & 31, wg = warp >> 2, w4 = warp & 3, g = lane >> 2, t = lane & 3;
  const int h = blockIdx.x >> 2, j = blockIdx.x & 3;
  uint32_t wqk[32][4];
  uint32_t wsw[16][4];
  int it = 0;

  if (tid == 0) {
    mbar_init(sb + R_BAR, 1); mbar_init(sb + R_BAR + 8, 1); mbar_init(sb + R_BAR + 16, 1);
    asm volatile("fence.mbarrier_init.release.cluster;" ::: "memory");
    mbar_expect_tx(sb + R_BAR + 16, 3 * 65536);
    for (int i = 0; i < 4; i++) {
      tma2d(sb + R_WO + i * 16384, &maps.wq, h * DH + 32 * j, i * 256, sb + R_BAR + 16);
      tma2d(sb + R_MEM + i * 16384, &maps.wk, h * DH + 32 * j, i * 256, sb + R_BAR + 16);
    }
    for (int i = 0; i < 4; i++) tma2d(sb + R_WV + i * 16384, &maps.wv, h * DH + 32 * j, i * 256, sb + R_BAR + 16);
  }
  {
    const bf16* wp = Wo + (size_t)(h * DH + 2 * t) * DM + 256 * j + 32 * warp + 4 * g;
#pragma unroll
    for (int ks = 0; ks < 8; ks++)
#pragma unroll
      for (int u = 0; u < 2; u++) {
        const uint2 r0 = __ldg(reinterpret_cast<const uint2*>(wp + (size_t)(16 * ks + 8 * u) * DM));
        const uint2 r1 = __ldg(reinterpret_cast<const uint2*>(wp + (size_t)(16 * ks + 8 * u + 1) * DM));
        wsw[2 * ks][2 * u] = __byte_perm(r0.x, r1.x, 0x5410); wsw[2 * ks][2 * u + 1] = __byte_perm(r0.x, r1.x, 0x7632);
        wsw[2 * ks + 1][2 * u] = __byte_perm(r0.y, r1.y, 0x5410); wsw[2 * ks + 1][2 * u + 1] = __byte_perm(r0.y, r1.y, 0x7632);
      }
  }
  __syncthreads();
  mbar_wait(sb + R_BAR + 16, 0);
  const int lrow = (lane & 7) + ((lane >> 4) << 3);
  const uint32_t wofs = lrow * 64 + (((2 * (w4 & 1) + ((lane >> 3) & 1)) ^ ((lrow >> 1) & 3)) << 4);
  {
    const uint32_t a = sb + (w4 < 2 ? R_WO : R_MEM) + wg * 32768 + wofs;
#pragma unroll
    for (int ks = 0; ks < 32; ks++) ldsm4t(wqk[ks], a + ks * 1024);
  }
  __syncthreads();
#pragma unroll
  for (int i = 0; i < 16; i++) sts128(sb + R_WO + i * 4096 + tid * 16, wsw[i][0], wsw[i][1], wsw[i][2], wsw[i][3]);
#pragma unroll
  for (int i = 0; i < 4; i++) {
    const int idx = wg * 512 + i * 128 + (tid & 127);
    const uint4 v = __ldg(reinterpret_cast<const uint4*>(mem0 + (idx & 7) * DM + (idx >> 3) * 8));
    sts128(sb + R_MEM + idx * 16, v.x, v.y, v.z, v.w);
  }
  if (tid == 128) {
    fence_async();
    rec_issue_kv(maps, sb + R_KV, sb + R_BAR, 0, h, j);
  }
  const uint32_t wvaddr = sb + R_WV + (2 * wg + (w4 >> 1)) * 16384 + wofs;
#pragma unroll
  for (int i = 0; i < 16; i++) ldsm4t(wsw[i], wvaddr + i * 1024);

  const float sc = 0.08838834764831845f * 1.4426950408889634f;

#pragma unroll 1
  for (int s = 0; s < NSEG; s++) {
    const uint32_t tag = (s + 1) & 1, T = tag << 16;
    const uint32_t kv = sb + R_KV + (s & 1) * R_KVSZ;
    TS(0);
    if (s > 0) {
      uint32_t v[4][4];
      const uint4* src = &g_x.C[wg * 512 + (tid & 127)];
#pragma unroll
      for (int i = 0; i < 4; i++) ldx2x64(v[i], src + i * 128);
      while (true) {
        uint32_t bad = 0;
#pragma unroll
        for (int i = 0; i < 4; i++) bad |= (v[i][0] ^ s) | (v[i][2] ^ s);
        if (!(bad & 1) || ++it > SPIN_LIMIT) break;
#pragma unroll
        for (int i = 0; i < 4; i++) if (((v[i][0] ^ s) | (v[i][2] ^ s)) & 1) ldx2x64(v[i], src + i * 128);
      }
#pragma unroll
      for (int i = 0; i < 4; i++) sts128(sb + R_MEM + (wg * 512 + i * 128 + (tid & 127)) * 16, v[i][0], v[i][1], v[i][2], v[i][3]);
    }
    bar_sync(1 + wg, 128);
    TS(1);
    {
      float c0[4] = {0, 0, 0, 0}, c1[4] = {0, 0, 0, 0};
      const uint32_t a = sb + R_MEM + wg * 8192 + lane * 16;
#pragma unroll
      for (int i = 0; i < 16; i++) {
        uint32_t b[4]; ldsm4(b, a + i * 512);
        mma16816(c0, wqk[2 * i][0], wqk[2 * i][1], wqk[2 * i][2], wqk[2 * i][3], b[0], b[1]);
        mma16816(c1, wqk[2 * i + 1][0], wqk[2 * i + 1][1], wqk[2 * i + 1][2], wqk[2 * i + 1][3], b[2], b[3]);
      }
      const uint32_t r = sb + R_RED + (wg * 8 * 68 + 2 * t * 68 + 16 * w4 + g) * 4;
      sts32f(r, c0[0] + c1[0]); sts32f(r + 272, c0[1] + c1[1]); sts32f(r + 32, c0[2] + c1[2]); sts32f(r + 304, c0[3] + c1[3]);
    }
    TS(2);
    if (warp < 2) {
      bar_sync(3, 256);
      const uint32_t r = sb + R_RED + ((lane & 7) * 68 + 32 * warp + 8 * (lane >> 3)) * 4;
      const float4 a0 = lds128f(r), a1 = lds128f(r + 16), b0 = lds128f(r + 2176), b1 = lds128f(r + 2192);
      stx128(&g_x.A[blockIdx.x][warp][lane], pack2_tag(a0.x + b0.x, a0.y + b0.y, T), pack2(a0.z + b0.z, a0.w + b0.w),
             pack2(a1.x + b1.x, a1.y + b1.y), pack2(a1.z + b1.z, a1.w + b1.w));
    } else {
      bar_arrive(3, 256);
    }
    TS(3);
    {
      float c0[4] = {0, 0, 0, 0}, c1[4] = {0, 0, 0, 0};
      const uint32_t a = sb + R_MEM + (2 * wg + (w4 >> 1)) * 4096 + lane * 16;
#pragma unroll
      for (int i = 0; i < 8; i++) {
        uint32_t b[4]; ldsm4(b, a + i * 512);
        mma16816(c0, wsw[2 * i][0], wsw[2 * i][1], wsw[2 * i][2], wsw[2 * i][3], b[0], b[1]);
        mma16816(c1, wsw[2 * i + 1][0], wsw[2 * i + 1][1], wsw[2 * i + 1][2], wsw[2 * i + 1][3], b[2], b[3]);
      }
      sts128(sb + R_REDV + warp * 512 + lane * 16, __float_as_uint(c0[0] + c1[0]), __float_as_uint(c0[1] + c1[1]),
             __float_as_uint(c0[2] + c1[2]), __float_as_uint(c0[3] + c1[3]));
    }
    if (warp >= 6) {
      bar_sync(4, 256);
      const uint32_t r = sb + R_REDV + (warp & 1) * 512 + lane * 16;
      const float4 a0 = lds128f(r), a1 = lds128f(r + 1024), a2 = lds128f(r + 2048), a3 = lds128f(r + 3072);
      stx64(reinterpret_cast<uint2*>(&g_x.V[blockIdx.x][lane]) + (warp & 1),
            pack2_tag((a0.x + a1.x) + (a2.x + a3.x), (a0.y + a1.y) + (a2.y + a3.y), T), pack2((a0.z + a1.z) + (a2.z + a3.z), (a0.w + a1.w) + (a2.w + a3.w)));
    } else {
      bar_arrive(4, 256);
    }
    TS(4);
#pragma unroll
    for (int i = 0; i < 16; i++) lds128(wsw[i], sb + R_WO + i * 4096 + tid * 16);
    mbar_wait(sb + R_BAR + 8 * (s & 1), (s >> 1) & 1);
    if (tid == 128 && s + 1 < NSEG) { fence_async(); rec_issue_kv(maps, sb + R_KV + ((s + 1) & 1) * R_KVSZ, sb + R_BAR + 8 * ((s + 1) & 1), s + 1, h, j); }
    {
      uint32_t a[4][4], b[4][4];
#pragma unroll
      for (int i = 0; i < 4; i++) lds128(b[i], kv + (i >> 1) * 4096 + (8 * w4 + g) * 128 + (((4 * (i & 1) + t) ^ g) << 4));
      if (wg == 1) {
#pragma unroll
        for (int i = 0; i < 4; i++) lds128(a[i], kv + 16384 + (i >> 1) * 1024 + g * 128 + (((4 * (i & 1) + t) ^ g) << 4));
        score_tile(a, b, sb + R_S + 1280 + w4 * 256 + lane * 8);
      }
      if (warp < 6) {
        const uint4* src = &g_x.A[4 * h][0][t * 8 + g];
        if (warp < 5) {
#pragma unroll
          for (int i = 0; i < 4; i++) ldx128(a[i], src + i * 64);
        }
        if (warp >= 4) {
#pragma unroll
          for (int i = 0; i < 4; i++) ldx128(b[i], src + i * 64 + 32);
        }
        if (warp < 5) while (true) {
          uint32_t bad = 0;
#pragma unroll
          for (int i = 0; i < 4; i++) bad |= a[i][0] ^ tag;
          if (!(bad & 1) || ++it > SPIN_LIMIT) break;
#pragma unroll
          for (int i = 0; i < 4; i++) if ((a[i][0] ^ tag) & 1) ldx128(a[i], src + i * 64);
        }
        if (warp >= 4) while (true) {
          uint32_t bad = 0;
#pragma unroll
          for (int i = 0; i < 4; i++) bad |= b[i][0] ^ tag;
          if (!(bad & 1) || ++it > SPIN_LIMIT) break;
#pragma unroll
          for (int i = 0; i < 4; i++) if ((b[i][0] ^ tag) & 1) ldx128(b[i], src + i * 64 + 32);
        }
        __syncwarp();
        TS(5);
        score_tile(a, b, sb + R_S + (warp == 5 ? 1280 + 1024 : warp * 256) + lane * 8);
      }
    }
    auto attend = [&](float (&o)[2][4], float (&sum)[4], bool isx) {
      uint32_t vm[4], vf[4][4];
      const uint4* vsrc = &g_x.V[4 * h + w4][lane];
      ldx2x64(vm, vsrc);
#pragma unroll
      for (int i = 0; i < 4; i++) {
        const int row = 16 * (i & 1) + lrow;
        ldsm4t(vf[i], kv + 8192 + (w4 >> 1) * 4096 + row * 128 + (((4 * (w4 & 1) + 2 * (i >> 1) + ((lane >> 3) & 1)) ^ (row & 7)) << 4));
      }
      if (!isx) bar_sync(5, 256);
      TS(6);
      float2 sv[5];
#pragma unroll
      for (int i = 0; i < 5; i++) sv[i] = lds64f(sb + R_S + (isx ? 1280 : 0) + i * 256 + lane * 8);
      if (isx) {
#pragma unroll
        for (int i = 0; i < 4; i++) {
          if (8 * i + 2 * t > 8 * j + g) sv[i].x = -INFINITY;
          if (8 * i + 2 * t + 1 > 8 * j + g) sv[i].y = -INFINITY;
        }
      }
      float m = fmaxf(fmaxf(fmaxf(sv[0].x, sv[0].y), fmaxf(sv[1].x, sv[1].y)), fmaxf(fmaxf(sv[2].x, sv[2].y), fmaxf(sv[3].x, sv[3].y)));
      m = fmaxf(m, fmaxf(sv[4].x, sv[4].y));
      m = fmaxf(m, __shfl_xor_sync(0xffffffffu, m, 1));
      m = fmaxf(m, __shfl_xor_sync(0xffffffffu, m, 2));
      const float ms = -m * sc;
      uint32_t p[5];
#pragma unroll
      for (int i = 0; i < 5; i++) p[i] = pack2(ex2(fmaf(sv[i].x, sc, ms)), ex2(fmaf(sv[i].y, sc, ms)));
      const uint32_t ONE = 0x3F803F80u;
#pragma unroll
      for (int k = 0; k < 2; k++) {
        mma16816(o[0], vf[k][0], vf[k][1], vf[k][2], vf[k][3], p[2 * k], p[2 * k + 1]);
        mma16816(o[1], vf[2 + k][0], vf[2 + k][1], vf[2 + k][2], vf[2 + k][3], p[2 * k], p[2 * k + 1]);
        mma16816(sum, ONE, ONE, ONE, ONE, p[2 * k], p[2 * k + 1]);
      }
      while ((((vm[0] ^ tag) | (vm[2] ^ tag)) & 1) && ++it <= SPIN_LIMIT) ldx2x64(vm, vsrc);
      __syncwarp();
      mma1688(o[0], vm[0], vm[1], p[4]);
      mma1688(o[1], vm[2], vm[3], p[4]);
      mma1688(sum, ONE, ONE, p[4]);
    };
    if (wg == 0) {
      float o[2][4] = {{0, 0, 0, 0}, {0, 0, 0, 0}}, sum[4] = {0, 0, 0, 0};
      attend(o, sum, false);
      stsm4t(sb + R_O + w4 * 512 + lane * 16, pack2(o[0][0], o[0][1]), pack2(o[0][2], o[0][3]), pack2(o[1][0], o[1][1]), pack2(o[1][2], o[1][3]));
      if (tid < 4) sts64f(sb + R_SUM + t * 8, sum[0], sum[1]);
    } else {
      bar_arrive(5, 256);
    }
    TS(7);
    bar_sync(6, 256);
    TS(8);
    if (s + 1 < NSEG) {
      float c0[4] = {0, 0, 0, 0}, c1[4] = {0, 0, 0, 0};
      const float2 sm = lds64f(sb + R_SUM + t * 8);
#pragma unroll
      for (int i = 0; i < 4; i++) {
        uint32_t b[4]; ldsm4(b, sb + R_O + i * 512 + lane * 16);
        mma16816(c0, wsw[4 * i][0], wsw[4 * i][1], wsw[4 * i][2], wsw[4 * i][3], b[0], b[1]);
        mma16816(c1, wsw[4 * i + 1][0], wsw[4 * i + 1][1], wsw[4 * i + 1][2], wsw[4 * i + 1][3], b[0], b[1]);
        mma16816(c0, wsw[4 * i + 2][0], wsw[4 * i + 2][1], wsw[4 * i + 2][2], wsw[4 * i + 2][3], b[2], b[3]);
        mma16816(c1, wsw[4 * i + 3][0], wsw[4 * i + 3][1], wsw[4 * i + 3][2], wsw[4 * i + 3][3], b[2], b[3]);
      }
      const float r0 = __frcp_rn(sm.x), r1 = __frcp_rn(sm.y);
      stx128(&g_x.B[(4 * warp + (g >> 1)) * 4 + j][h * 8 + (lane & 7)], pack2_tag(c0[0] * r0, c0[2] * r0, T), pack2(c1[0] * r0, c1[2] * r0),
             pack2(c0[1] * r1, c0[3] * r1), pack2(c1[1] * r1, c1[3] * r1));
    }
    TS(9);
    if (wg == 1) {
      float o[2][4] = {{0, 0, 0, 0}, {0, 0, 0, 0}}, sum[4] = {0, 0, 0, 0};
      attend(o, sum, true);
      const float r0 = __frcp_rn(sum[0]), r1 = __frcp_rn(sum[1]);
      const uint32_t ox = sb + R_OX + w4 * 640;
      stsm4t(ox + (lane & 7) * 80 + (lane >> 3) * 16, pack2(o[0][0] * r0, o[0][1] * r1), pack2(o[0][2] * r0, o[0][3] * r1),
             pack2(o[1][0] * r0, o[1][1] * r1), pack2(o[1][2] * r0, o[1][3] * r1));
      __syncwarp();
      uint32_t v[4]; lds128(v, ox + g * 80 + t * 16);
      *reinterpret_cast<uint4*>(&g_ox[(size_t)(s * SEG + 8 * j + g) * HD + h * DH + 32 * w4 + 8 * t]) = make_uint4(v[0], v[1], v[2], v[3]);
    }
    if (s + 1 < NSEG) {
      if (warp == 0) {
        const uint4* src = &g_x.B[blockIdx.x][t * 8 + g];
#pragma unroll
        for (int i = 0; i < 8; i++) ldx128(wsw[i], src + i * 32);
        while (true) {
          uint32_t bad = 0;
#pragma unroll
          for (int i = 0; i < 8; i++) bad |= wsw[i][0] ^ tag;
          if (!(bad & 1) || ++it > SPIN_LIMIT) break;
#pragma unroll
          for (int i = 0; i < 8; i++) if ((wsw[i][0] ^ tag) & 1) ldx128(wsw[i], src + i * 32);
        }
        __syncwarp();
        TS(10);
        const uint32_t b0 = g == 0 ? 0x00003F80u : g == 1 ? 0x3F800000u : 0u, b1 = g == 2 ? 0x00003F80u : g == 3 ? 0x3F800000u : 0u;
        float c[4][4];
#pragma unroll
        for (int i = 0; i < 4; i++) { c[i][0] = c[i][1] = c[i][2] = c[i][3] = 0.f; }
#pragma unroll
        for (int i = 0; i < 8; i++) mma16816(c[i & 3], wsw[i][0], wsw[i][1], wsw[i][2], wsw[i][3], b0, b1);
        if (t < 2)
          stx64(reinterpret_cast<uint2*>(&g_x.C[(32 * j + h) * 8 + 2 * (g & 3) + t]) + (g >> 2),
                pack2_tag((c[0][0] + c[1][0]) + (c[2][0] + c[3][0]), (c[0][1] + c[1][1]) + (c[2][1] + c[3][1]), T),
                pack2((c[0][2] + c[1][2]) + (c[2][2] + c[3][2]), (c[0][3] + c[1][3]) + (c[2][3] + c[3][3])));
        TS(11);
      }
#pragma unroll
      for (int i = 0; i < 16; i++) ldsm4t(wsw[i], wvaddr + i * 1024);
    }
  }
  if (it > SPIN_LIMIT) g_err = 2;
}

template <int N, int LOGN, int SIGN>
__device__ __forceinline__ float2* fft_smem(float2* a, float2* b) {
  const int i = threadIdx.x;
#pragma unroll 1
  for (int p = 1; p < N; p <<= 1) {
    __syncthreads();
    const int k = i & (p - 1);
    float sn, cs; sincospif(SIGN * (float)k / (float)p, &sn, &cs);
    const float2 u = a[i], v0 = a[i + N / 2];
    const float2 v = make_float2(v0.x * cs - v0.y * sn, v0.x * sn + v0.y * cs);
    const int o = ((i - k) << 1) + k;
    b[o] = make_float2(u.x + v.x, u.y + v.y); b[o + p] = make_float2(u.x - v.x, u.y - v.y);
    float2* tmp = a; a = b; b = tmp;
  }
  __syncthreads();
  return a;
}
__global__ void __launch_bounds__(512) fft_p1(const bf16* __restrict__ x) {
  __shared__ float2 a[1024], b[1024];
  const int m = blockIdx.x;
  for (int i = threadIdx.x; i < 1024; i += 512) a[i] = make_float2(__bfloat162float(x[m * 1024 + i]), __bfloat162float(x[(m + 1024) * 1024 + i]));
  float2* z = fft_smem<1024, 10, -1>(a, b);
  for (int f = threadIdx.x; f <= 512; f += 512) {
    const float2 p = z[f], q = z[(1024 - f) & 1023];
    g_f1[f * 2048 + m] = make_float2(0.5f * (p.x + q.x), 0.5f * (p.y - q.y));
    g_f1[f * 2048 + m + 1024] = make_float2(0.5f * (p.y + q.y), 0.5f * (q.x - p.x));
  }
}
__global__ void __launch_bounds__(1024) fft_p2(const bf16* __restrict__ wr, const bf16* __restrict__ wi) {
  __shared__ float2 a[2048], b[2048];
  const int f = blockIdx.x;
  for (int i = threadIdx.x; i < 2048; i += 1024) a[i] = g_f1[f * 2048 + i];
  float2* z = fft_smem<2048, 11, -1>(a, b);
  for (int i = threadIdx.x; i < 2048; i += 1024) {
    const float r = __bfloat162float(wr[i * 513 + f]), im = __bfloat162float(wi[i * 513 + f]);
    const float2 v = z[i];
    z[i] = make_float2(v.x * r - v.y * im, v.x * im + v.y * r);
  }
  float2* y = fft_smem<2048, 11, 1>(z, z == a ? b : a);
  for (int i = threadIdx.x; i < 2048; i += 1024) g_f1[f * 2048 + i] = y[i];
}
__global__ void __launch_bounds__(512) fft_p3(bf16* __restrict__ out) {
  __shared__ float2 a[1024], b[1024];
  const int m = blockIdx.x;
  for (int f = threadIdx.x; f <= 512; f += 512) {
    float2 p = g_f1[f * 2048 + m], q = g_f1[f * 2048 + m + 1024];
    if (f == 0 || f == 512) { p.y = 0.f; q.y = 0.f; }
    a[f] = make_float2(p.x - q.y, p.y + q.x);
    if (f != 0 && f != 512) a[1024 - f] = make_float2(p.x + q.y, q.x - p.y);
  }
  float2* z = fft_smem<1024, 10, 1>(a, b);
  const float sc = 1.f / (2048.f * 1024.f);
  for (int i = threadIdx.x; i < 1024; i += 512) {
    out[(size_t)m * 2048 + 1024 + i] = __float2bfloat16(z[i].x * sc);
    out[(size_t)(m + 1024) * 2048 + 1024 + i] = __float2bfloat16(z[i].y * sc);
  }
}

typedef CUresult (*EncodeFn)(CUtensorMap*, CUtensorMapDataType, cuuint32_t, void*, const cuuint64_t*, const cuuint64_t*, const cuuint32_t*,
                             const cuuint32_t*, CUtensorMapInterleave, CUtensorMapSwizzle, CUtensorMapL2promotion, CUtensorMapFloatOOBfill);
static void make_map(EncodeFn fn, CUtensorMap* m, const void* p, uint64_t cols, uint64_t rows, uint64_t pitch, uint32_t bc, uint32_t br, CUtensorMapSwizzle sw) {
  cuuint64_t dims[2] = {cols, rows}, strides[1] = {pitch * 2};
  cuuint32_t box[2] = {bc, br}, es[2] = {1, 1};
  fn(m, CU_TENSOR_MAP_DATA_TYPE_BFLOAT16, 2, const_cast<void*>(p), dims, strides, box, es, CU_TENSOR_MAP_INTERLEAVE_NONE, sw,
     CU_TENSOR_MAP_L2_PROMOTION_L2_256B, CU_TENSOR_MAP_FLOAT_OOB_FILL_NONE);
}

extern "C" void kernel_launch(void* const* d_in, const int* in_sizes, int n_in, void* d_out, int out_size) {
  const bf16* Ax = (const bf16*)d_in[0]; const bf16* mem0 = (const bf16*)d_in[1];
  const bf16* Wq = (const bf16*)d_in[2]; const bf16* Wk = (const bf16*)d_in[3]; const bf16* Wv = (const bf16*)d_in[4];
  const bf16* Wo = (const bf16*)d_in[5];
  const bf16* Bx = (const bf16*)d_in[7]; const bf16* wr = (const bf16*)d_in[8]; const bf16* wi = (const bf16*)d_in[9];
  bf16* out = (bf16*)d_out;

  void* fp = nullptr; cudaDriverEntryPointQueryResult qr;
  cudaGetDriverEntryPoint("cuTensorMapEncodeTiled", &fp, cudaEnableDefault, &qr);
  EncodeFn fn = (EncodeFn)fp;
  void *qkv, *ox;
  cudaGetSymbolAddress(&qkv, g_qkv); cudaGetSymbolAddress(&ox, g_ox);
  const CUtensorMapSwizzle S128 = CU_TENSOR_MAP_SWIZZLE_128B, S64 = CU_TENSOR_MAP_SWIZZLE_64B;

  GemmMaps m1, m3; RecMaps mr;
  make_map(fn, &m1.a, Ax, DM, S_LEN, DM, 64, 128, S128);
  make_map(fn, &m1.b[0], Wq, HD, DM, HD, 64, 64, S128);
  make_map(fn, &m1.b[1], Wk, HD, DM, HD, 64, 64, S128);
  make_map(fn, &m1.b[2], Wv, HD, DM, HD, 64, 64, S128);
  make_map(fn, &m1.c, qkv, 3 * HD, S_LEN, 3 * HD, 64, 64, S128);
  make_map(fn, &m3.a, ox, HD, S_LEN, HD, 64, 128, S128);
  make_map(fn, &m3.b[0], Wo, DM, HD, DM, 64, 64, S128);
  m3.b[1] = m3.b[0]; m3.b[2] = m3.b[0];
  make_map(fn, &m3.c, out, DM, S_LEN, 2 * DM, 64, 64, S128);
  make_map(fn, &mr.wq, Wq, HD, DM, HD, 32, 256, S64);
  make_map(fn, &mr.wk, Wk, HD, DM, HD, 32, 256, S64);
  make_map(fn, &mr.wv, Wv, HD, DM, HD, 32, 256, S64);
  make_map(fn, &mr.kv, qkv, 3 * HD, S_LEN, 3 * HD, 64, 32, S128);
  make_map(fn, &mr.q, qkv, 3 * HD, S_LEN, 3 * HD, 64, 8, S128);

  constexpr int SM1 = 4 * 49152 + 32768 + 256 + 1024, SM3 = 6 * 32768 + 32768 + 256 + 1024;
  cudaFuncSetAttribute(gemm_kernel<256, 4>, cudaFuncAttributeMaxDynamicSharedMemorySize, SM1);
  cudaFuncSetAttribute(gemm_kernel<128, 6>, cudaFuncAttributeMaxDynamicSharedMemorySize, SM3);
  cudaFuncSetAttribute(rec_kernel, cudaFuncAttributeMaxDynamicSharedMemorySize, R_TOTAL);

  cudaStream_t st = cudaStreamPerThread;
  gemm_kernel<256, 4><<<132, 384, SM1, st>>>(m1, 16, 48, 16, 16, 1);
  rec_kernel<<<128, 256, R_TOTAL, st>>>(mr, Wo, mem0);
  gemm_kernel<128, 6><<<128, 384, SM3, st>>>(m3, 16, 8, 64, 8, 0);
  fft_p1<<<1024, 512, 0, st>>>(Bx);
  fft_p2<<<513, 1024, 0, st>>>(wr, wi);
  fft_p3<<<1024, 512, 0, st>>>(out);
}
```

```cpp
#include <cuda_runtime.h>
#include <cuda_bf16.h>
#include <cuda.h>
#include <stdint.h>
#include <stddef.h>

typedef __nv_bfloat16 bf16;

constexpr int S_LEN = 2048, DM = 1024, NH = 32, DH = 128, MEM = 8, SEG = 32, NSEG = 64;
constexpr int HD = NH * DH;
constexpr int SPIN_LIMIT = 1 << 20;

__device__ __align__(1024) bf16 g_qkv[(size_t)S_LEN * 3 * HD];
__device__ __align__(1024) bf16 g_ox[(size_t)S_LEN * HD];
struct Xchg {
  uint4 A[128][3][32];
  uint4 C[1024];
  uint4 B[128][256];
};
__device__ __align__(4096) Xchg g_x;
__device__ __align__(1024) float2 g_f1[513 * 2048];
__device__ int g_err;

__device__ __forceinline__ unsigned clk() { unsigned long long c; asm volatile("mov.u64 %0, %%clock64;" : "=l"(c)); return (unsigned)c; }
__device__ __forceinline__ uint32_t smem_u32(const void* p) { return (uint32_t)__cvta_generic_to_shared(p); }
__device__ __forceinline__ void mbar_init(uint32_t bar, int cnt) { asm volatile("mbarrier.init.shared::cta.b64 [%0], %1;" :: "r"(bar), "r"(cnt) : "memory"); }
__device__ __forceinline__ void mbar_expect_tx(uint32_t bar, int bytes) { asm volatile("mbarrier.arrive.expect_tx.shared::cta.b64 _, [%0], %1;" :: "r"(bar), "r"(bytes) : "memory"); }
__device__ __forceinline__ void mbar_arrive(uint32_t bar) { asm volatile("mbarrier.arrive.shared::cta.b64 _, [%0];" :: "r"(bar) : "memory"); }
__device__ __forceinline__ void mbar_arrive_cluster(uint32_t bar, int cta) {
  asm volatile("{.reg .b32 r; mapa.shared::cluster.u32 r, %0, %1; mbarrier.arrive.shared::cluster.b64 _, [r];}" :: "r"(bar), "r"(cta) : "memory"); }
__device__ __forceinline__ bool mbar_try(uint32_t bar, int par) {
  uint32_t ok; asm volatile("{.reg .pred p; mbarrier.try_wait.parity.shared::cta.b64 p, [%1], %2; selp.u32 %0, 1, 0, p;}" : "=r"(ok) : "r"(bar), "r"(par) : "memory"); return ok; }
__device__ __forceinline__ void mbar_wait(uint32_t bar, int par) {
  int it = 0;
  while (!mbar_try(bar, par)) { if (++it > SPIN_LIMIT) { g_err = 1; break; } }
}
__device__ __forceinline__ void tma2d(uint32_t dst, const CUtensorMap* m, int c0, int c1, uint32_t bar) {
  asm volatile("cp.async.bulk.tensor.2d.shared::cluster.global.mbarrier::complete_tx::bytes [%0], [%1, {%3, %4}], [%2];"
    :: "r"(dst), "l"(m), "r"(bar), "r"(c0), "r"(c1) : "memory"); }
__device__ __forceinline__ void tma2d_mc(uint32_t dst, const CUtensorMap* m, int c0, int c1, uint32_t bar, uint16_t mask) {
  asm volatile("cp.async.bulk.tensor.2d.shared::cluster.global.mbarrier::complete_tx::bytes.multicast::cluster [%0], [%1, {%3, %4}], [%2], %5;"
    :: "r"(dst), "l"(m), "r"(bar), "r"(c0), "r"(c1), "h"(mask) : "memory"); }
__device__ __forceinline__ void tma2d_store(const CUtensorMap* m, uint32_t src, int c0, int c1) {
  asm volatile("cp.async.bulk.tensor.2d.global.shared::cta.bulk_group [%0, {%2, %3}], [%1];" :: "l"(m), "r"(src), "r"(c0), "r"(c1) : "memory"); }
__device__ __forceinline__ void fence_async() { asm volatile("fence.proxy.async.shared::cta;" ::: "memory"); }
__device__ __forceinline__ void bar_sync(int id, int n) { asm volatile("bar.sync %0, %1;" :: "r"(id), "r"(n) : "memory"); }
__device__ __forceinline__ void bar_arrive(int id, int n) { asm volatile("bar.arrive %0, %1;" :: "r"(id), "r"(n) : "memory"); }
__device__ __forceinline__ uint32_t pack2(float lo, float hi) { uint32_t r; asm("cvt.rn.bf16x2.f32 %0, %1, %2;" : "=r"(r) : "f"(hi), "f"(lo)); return r; }
__device__ __forceinline__ uint32_t pack2_tag(float lo, float hi, uint32_t T) {
  uint32_t u = ((__float_as_uint(lo) - T + 0x10000u) & 0xFFFE0000u) + T;
  return __byte_perm(u, pack2(0.f, hi), 0x7632); }
__device__ __forceinline__ void ldsm4(uint32_t (&r)[4], uint32_t a) {
  asm volatile("ldmatrix.sync.aligned.m8n8.x4.shared.b16 {%0,%1,%2,%3}, [%4];" : "=r"(r[0]), "=r"(r[1]), "=r"(r[2]), "=r"(r[3]) : "r"(a) : "memory"); }
__device__ __forceinline__ void ldsm4t(uint32_t (&r)[4], uint32_t a) {
  asm volatile("ldmatrix.sync.aligned.m8n8.x4.trans.shared.b16 {%0,%1,%2,%3}, [%4];" : "=r"(r[0]), "=r"(r[1]), "=r"(r[2]), "=r"(r[3]) : "r"(a) : "memory"); }
__device__ __forceinline__ void stsm4(uint32_t a, uint32_t r0, uint32_t r1, uint32_t r2, uint32_t r3) {
  asm volatile("stmatrix.sync.aligned.m8n8.x4.shared.b16 [%0], {%1,%2,%3,%4};" :: "r"(a), "r"(r0), "r"(r1), "r"(r2), "r"(r3) : "memory"); }
__device__ __forceinline__ void stsm4t(uint32_t a, uint32_t r0, uint32_t r1, uint32_t r2, uint32_t r3) {
  asm volatile("stmatrix.sync.aligned.m8n8.x4.trans.shared.b16 [%0], {%1,%2,%3,%4};" :: "r"(a), "r"(r0), "r"(r1), "r"(r2), "r"(r3) : "memory"); }
__device__ __forceinline__ void lds128(uint32_t (&r)[4], uint32_t a) {
  asm volatile("ld.shared.v4.u32 {%0,%1,%2,%3}, [%4];" : "=r"(r[0]), "=r"(r[1]), "=r"(r[2]), "=r"(r[3]) : "r"(a) : "memory"); }
__device__ __forceinline__ float4 lds128f(uint32_t a) { float4 r;
  asm volatile("ld.shared.v4.f32 {%0,%1,%2,%3}, [%4];" : "=f"(r.x), "=f"(r.y), "=f"(r.z), "=f"(r.w) : "r"(a) : "memory"); return r; }
__device__ __forceinline__ float2 lds64f(uint32_t a) { float2 r;
  asm volatile("ld.shared.v2.f32 {%0,%1}, [%2];" : "=f"(r.x), "=f"(r.y) : "r"(a) : "memory"); return r; }
__device__ __forceinline__ void sts128(uint32_t a, uint32_t r0, uint32_t r1, uint32_t r2, uint32_t r3) {
  asm volatile("st.shared.v4.u32 [%0], {%1,%2,%3,%4};" :: "r"(a), "r"(r0), "r"(r1), "r"(r2), "r"(r3) : "memory"); }
__device__ __forceinline__ void sts64f(uint32_t a, float x, float y) { asm volatile("st.shared.v2.f32 [%0], {%1,%2};" :: "r"(a), "f"(x), "f"(y) : "memory"); }
__device__ __forceinline__ void sts32f(uint32_t a, float x) { asm volatile("st.shared.f32 [%0], %1;" :: "r"(a), "f"(x) : "memory"); }
__device__ __forceinline__ void mma16816(float (&d)[4], uint32_t a0, uint32_t a1, uint32_t a2, uint32_t a3, uint32_t b0, uint32_t b1) {
  asm volatile("mma.sync.aligned.m16n8k16.row.col.f32.bf16.bf16.f32 {%0,%1,%2,%3}, {%4,%5,%6,%7}, {%8,%9}, {%0,%1,%2,%3};"
    : "+f"(d[0]), "+f"(d[1]), "+f"(d[2]), "+f"(d[3]) : "r"(a0), "r"(a1), "r"(a2), "r"(a3), "r"(b0), "r"(b1)); }
__device__ __forceinline__ void mma1688(float (&d)[4], uint32_t a0, uint32_t a1, uint32_t b0) {
  asm volatile("mma.sync.aligned.m16n8k8.row.col.f32.bf16.bf16.f32 {%0,%1,%2,%3}, {%4,%5}, {%6}, {%0,%1,%2,%3};"
    : "+f"(d[0]), "+f"(d[1]), "+f"(d[2]), "+f"(d[3]) : "r"(a0), "r"(a1), "r"(b0)); }
__device__ __forceinline__ void ldx128(uint32_t (&r)[4], const void* p) {
  asm volatile("{.reg .b128 t; .reg .b64 a, b; ld.relaxed.gpu.global.b128 t, [%4]; mov.b128 {a, b}, t; mov.b64 {%0,%1}, a; mov.b64 {%2,%3}, b;}"
    : "=r"(r[0]), "=r"(r[1]), "=r"(r[2]), "=r"(r[3]) : "l"(p) : "memory"); }
__device__ __forceinline__ void ldx2x64(uint32_t (&r)[4], const void* p) {
  asm volatile("{.reg .b64 a, b; ld.relaxed.gpu.global.v2.b64 {a, b}, [%4]; mov.b64 {%0,%1}, a; mov.b64 {%2,%3}, b;}"
    : "=r"(r[0]), "=r"(r[1]), "=r"(r[2]), "=r"(r[3]) : "l"(p) : "memory"); }
__device__ __forceinline__ void stx128(void* p, uint32_t r0, uint32_t r1, uint32_t r2, uint32_t r3) {
  asm volatile("{.reg .b128 t; .reg .b64 a, b; mov.b64 a, {%1,%2}; mov.b64 b, {%3,%4}; mov.b128 t, {a, b}; st.relaxed.gpu.global.b128 [%0], t;}"
    :: "l"(p), "r"(r0), "r"(r1), "r"(r2), "r"(r3) : "memory"); }
__device__ __forceinline__ void stx64(void* p, uint32_t r0, uint32_t r1) {
  asm volatile("{.reg .b64 a; mov.b64 a, {%1,%2}; st.relaxed.gpu.global.b64 [%0], a;}" :: "l"(p), "r"(r0), "r"(r1) : "memory"); }
__device__ __forceinline__ float ex2(float x) { float r; asm("ex2.approx.ftz.f32 %0, %1;" : "=f"(r) : "f"(x)); return r; }
__device__ __forceinline__ void wg_fence() { asm volatile("wgmma.fence.sync.aligned;" ::: "memory"); }
__device__ __forceinline__ void wg_commit() { asm volatile("wgmma.commit_group.sync.aligned;" ::: "memory"); }
template <int N> __device__ __forceinline__ void wg_wait() { asm volatile("wgmma.wait_group.sync.aligned %0;" :: "n"(N) : "memory"); }

__device__ __forceinline__ void wgmma_ss_n256_tb1(float (&d)[128], uint64_t da, uint64_t db, int sc) {
  asm volatile("{.reg .pred p; setp.ne.b32 p, %130, 0;\n"
    "wgmma.mma_async.sync.aligned.m64n256k16.f32.bf16.bf16 {%0,%1,%2,%3,%4,%5,%6,%7,%8,%9,%10,%11,%12,%13,%14,%15,%16,%17,%18,%19,%20,%21,%22,%23,%24,%25,%26,%27,%28,%29,%30,%31,%32,%33,%34,%35,%36,%37,%38,%39,%40,%41,%42,%43,%44,%45,%46,%47,%48,%49,%50,%51,%52,%53,%54,%55,%56,%57,%58,%59,%60,%61,%62,%63,%64,%65,%66,%67,%68,%69,%70,%71,%72,%73,%74,%75,%76,%77,%78,%79,%80,%81,%82,%83,%84,%85,%86,%87,%88,%89,%90,%91,%92,%93,%94,%95,%96,%97,%98,%99,%100,%101,%102,%103,%104,%105,%106,%107,%108,%109,%110,%111,%112,%113,%114,%115,%116,%117,%118,%119,%120,%121,%122,%123,%124,%125,%126,%127}, %128, %129, p, 1, 1, 0, 1;}\n"
    : "+f"(d[0]),"+f"(d[1]),"+f"(d[2]),"+f"(d[3]),"+f"(d[4]),"+f"(d[5]),"+f"(d[6]),"+f"(d[7]),"+f"(d[8]),"+f"(d[9]),"+f"(d[10]),"+f"(d[11]),"+f"(d[12]),"+f"(d[13]),"+f"(d[14]),"+f"(d[15]),"+f"(d[16]),"+f"(d[17]),"+f"(d[18]),"+f"(d[19]),"+f"(d[20]),"+f"(d[21]),"+f"(d[22]),"+f"(d[23]),"+f"(d[24]),"+f"(d[25]),"+f"(d[26]),"+f"(d[27]),"+f"(d[28]),"+f"(d[29]),"+f"(d[30]),"+f"(d[31]),"+f"(d[32]),"+f"(d[33]),"+f"(d[34]),"+f"(d[35]),"+f"(d[36]),"+f"(d[37]),"+f"(d[38]),"+f"(d[39]),"+f"(d[40]),"+f"(d[41]),"+f"(d[42]),"+f"(d[43]),"+f"(d[44]),"+f"(d[45]),"+f"(d[46]),"+f"(d[47]),"+f"(d[48]),"+f"(d[49]),"+f"(d[50]),"+f"(d[51]),"+f"(d[52]),"+f"(d[53]),"+f"(d[54]),"+f"(d[55]),"+f"(d[56]),"+f"(d[57]),"+f"(d[58]),"+f"(d[59]),"+f"(d[60]),"+f"(d[61]),"+f"(d[62]),"+f"(d[63]),"+f"(d[64]),"+f"(d[65]),"+f"(d[66]),"+f"(d[67]),"+f"(d[68]),"+f"(d[69]),"+f"(d[70]),"+f"(d[71]),"+f"(d[72]),"+f"(d[73]),"+f"(d[74]),"+f"(d[75]),"+f"(d[76]),"+f"(d[77]),"+f"(d[78]),"+f"(d[79]),"+f"(d[80]),"+f"(d[81]),"+f"(d[82]),"+f"(d[83]),"+f"(d[84]),"+f"(d[85]),"+f"(d[86]),"+f"(d[87]),"+f"(d[88]),"+f"(d[89]),"+f"(d[90]),"+f"(d[91]),"+f"(d[92]),"+f"(d[93]),"+f"(d[94]),"+f"(d[95]),"+f"(d[96]),"+f"(d[97]),"+f"(d[98]),"+f"(d[99]),"+f"(d[100]),"+f"(d[101]),"+f"(d[102]),"+f"(d[103]),"+f"(d[104]),"+f"(d[105]),"+f"(d[106]),"+f"(d[107]),"+f"(d[108]),"+f"(d[109]),"+f"(d[110]),"+f"(d[111]),"+f"(d[112]),"+f"(d[113]),"+f"(d[114]),"+f"(d[115]),"+f"(d[116]),"+f"(d[117]),"+f"(d[118]),"+f"(d[119]),"+f"(d[120]),"+f"(d[121]),"+f"(d[122]),"+f"(d[123]),"+f"(d[124]),"+f"(d[125]),"+f"(d[126]),"+f"(d[127])
    : "l"(da), "l"(db), "r"(sc));
}

__device__ __forceinline__ void wgmma_ss_n128_tb1(float (&d)[64], uint64_t da, uint64_t db, int sc) {
  asm volatile("{.reg .pred p; setp.ne.b32 p, %66, 0;\n"
    "wgmma.mma_async.sync.aligned.m64n128k16.f32.bf16.bf16 {%0,%1,%2,%3,%4,%5,%6,%7,%8,%9,%10,%11,%12,%13,%14,%15,%16,%17,%18,%19,%20,%21,%22,%23,%24,%25,%26,%27,%28,%29,%30,%31,%32,%33,%34,%35,%36,%37,%38,%39,%40,%41,%42,%43,%44,%45,%46,%47,%48,%49,%50,%51,%52,%53,%54,%55,%56,%57,%58,%59,%60,%61,%62,%63}, %64, %65, p, 1, 1, 0, 1;}\n"
    : "+f"(d[0]),"+f"(d[1]),"+f"(d[2]),"+f"(d[3]),"+f"(d[4]),"+f"(d[5]),"+f"(d[6]),"+f"(d[7]),"+f"(d[8]),"+f"(d[9]),"+f"(d[10]),"+f"(d[11]),"+f"(d[12]),"+f"(d[13]),"+f"(d[14]),"+f"(d[15]),"+f"(d[16]),"+f"(d[17]),"+f"(d[18]),"+f"(d[19]),"+f"(d[20]),"+f"(d[21]),"+f"(d[22]),"+f"(d[23]),"+f"(d[24]),"+f"(d[25]),"+f"(d[26]),"+f"(d[27]),"+f"(d[28]),"+f"(d[29]),"+f"(d[30]),"+f"(d[31]),"+f"(d[32]),"+f"(d[33]),"+f"(d[34]),"+f"(d[35]),"+f"(d[36]),"+f"(d[37]),"+f"(d[38]),"+f"(d[39]),"+f"(d[40]),"+f"(d[41]),"+f"(d[42]),"+f"(d[43]),"+f"(d[44]),"+f"(d[45]),"+f"(d[46]),"+f"(d[47]),"+f"(d[48]),"+f"(d[49]),"+f"(d[50]),"+f"(d[51]),"+f"(d[52]),"+f"(d[53]),"+f"(d[54]),"+f"(d[55]),"+f"(d[56]),"+f"(d[57]),"+f"(d[58]),"+f"(d[59]),"+f"(d[60]),"+f"(d[61]),"+f"(d[62]),"+f"(d[63])
    : "l"(da), "l"(db), "r"(sc));
}

template <int BN> struct WG;
template <> struct WG<256> { static __device__ __forceinline__ void mma(float (&d)[128], uint64_t a, uint64_t b, int sc) { wgmma_ss_n256_tb1(d, a, b, sc); } };
template <> struct WG<128> { static __device__ __forceinline__ void mma(float (&d)[64], uint64_t a, uint64_t b, int sc) { wgmma_ss_n128_tb1(d, a, b, sc); } };

struct GemmMaps { CUtensorMap a, b[3], c; };
template <int BN, int STAGES>
__global__ void __cluster_dims__(2, 1, 1) __launch_bounds__(384, 1)
gemm_kernel(const __grid_constant__ GemmMaps maps, int tilesM, int tilesN, int kblocks, int nPerB, int clearX) {
  extern __shared__ __align__(1024) uint8_t smem_raw[];
  constexpr int STAGE_BYTES = 16384 + BN * 128;
  constexpr int NBOX = BN / 64;
  const uint32_t sbase = (smem_u32(smem_raw) + 1023) & ~1023u;
  const uint32_t sEpi = sbase + STAGES * STAGE_BYTES;
  const uint32_t sBar = sEpi + 32768;
  const int warp = threadIdx.x >> 5, lane = threadIdx.x & 31, wg = warp >> 2;
  uint32_t crank; asm("mov.u32 %0, %%cluster_ctarank;" : "=r"(crank));
  if (threadIdx.x == 0) {
    for (int i = 0; i < STAGES; i++) { mbar_init(sBar + 8 * i, 1); mbar_init(sBar + 8 * (STAGES + i), 4); }
    asm volatile("fence.mbarrier_init.release.cluster;" ::: "memory");
  }
  if (clearX) {
    uint4* p = reinterpret_cast<uint4*>(&g_x);
    for (int i = blockIdx.x * 384 + threadIdx.x; i < (int)(sizeof(Xchg) / 16); i += gridDim.x * 384) p[i] = make_uint4(0, 0, 0, 0);
  }
  asm volatile("barrier.cluster.arrive.release.aligned; barrier.cluster.wait.acquire.aligned;" ::: "memory");
  const int npairs = (tilesM >> 1) * tilesN, pair0 = blockIdx.x >> 1, pstep = gridDim.x >> 1;
  if (wg == 2) {
    asm volatile("setmaxnreg.dec.sync.aligned.u32 40;");
    if (warp == 8 && lane == 0) {
      int st = 0, ph = 1;
      for (int p = pair0; p < npairs; p += pstep) {
        const int tm = (p % (tilesM >> 1)) * 2 + crank, tn = p / (tilesM >> 1);
        const CUtensorMap* mb = &maps.b[tn / nPerB];
        const int n0 = (tn % nPerB) * BN;
        for (int kb = 0; kb < kblocks; kb++) {
          mbar_wait(sBar + 8 * (STAGES + st), ph);
          const uint32_t a = sbase + st * STAGE_BYTES, full = sBar + 8 * st;
          mbar_expect_tx(full, STAGE_BYTES);
          tma2d(a, &maps.a, kb * 64, tm * 128, full);
#pragma unroll
          for (int i = 0; i < NBOX / 2; i++) {
            const int bx = crank * (NBOX / 2) + i;
            tma2d_mc(a + 16384 + bx * 8192, mb, n0 + bx * 64, kb * 64, full, (uint16_t)3);
          }
          if (++st == STAGES) { st = 0; ph ^= 1; }
        }
      }
      for (int i = 0; i < STAGES; i++) { mbar_wait(sBar + 8 * (STAGES + st), ph); if (++st == STAGES) { st = 0; ph ^= 1; } }
    }
  } else {
    asm volatile("setmaxnreg.inc.sync.aligned.u32 232;");
    int st = 0, ph = 0;
    float acc[BN / 2];
    const uint64_t descA0 = (uint64_t)(((sbase + wg * 8192) & 0x3FFFF) >> 4) | (1ull << 16) | (64ull << 32) | (1ull << 62);
    const uint64_t descB0 = (uint64_t)(((sbase + 16384) & 0x3FFFF) >> 4) | (512ull << 16) | (64ull << 32) | (1ull << 62);
    const uint32_t epi = sEpi + wg * 16384;
    for (int p = pair0; p < npairs; p += pstep) {
      const int tm = (p % (tilesM >> 1)) * 2 + crank, tn = p / (tilesM >> 1);
      int prev = -1;
      for (int kb = 0; kb < kblocks; kb++) {
        mbar_wait(sBar + 8 * st, ph);
        wg_fence();
        const uint64_t so = (uint64_t)(st * (STAGE_BYTES >> 4));
#pragma unroll
        for (int k = 0; k < 4; k++) WG<BN>::mma(acc, descA0 + so + k * 2, descB0 + so + k * 128, kb | k);
        wg_commit();
        if (prev >= 0) {
          wg_wait<1>();
          if ((threadIdx.x & 127) < 2) mbar_arrive_cluster(sBar + 8 * (STAGES + prev), threadIdx.x & 1);
        }
        prev = st;
        if (++st == STAGES) { st = 0; ph ^= 1; }
      }
      wg_wait<0>();
      if ((threadIdx.x & 127) < 2) mbar_arrive_cluster(sBar + 8 * (STAGES + prev), threadIdx.x & 1);
#pragma unroll
      for (int r = 0; r < BN / 128; r++) {
        if ((threadIdx.x & 127) == 0) asm volatile("cp.async.bulk.wait_group.read 0;" ::: "memory");
        bar_sync(1 + wg, 128);
        const int row = (warp & 3) * 16 + (lane & 15);
#pragma unroll
        for (int i = 0; i < 8; i++) {
          const int c = 2 * (i & 3) + (lane >> 4);
          const float* q = &acc[r * 64 + i * 8];
          stsm4(epi + (i >> 2) * 8192 + row * 128 + ((c ^ (row & 7)) << 4), pack2(q[0], q[1]), pack2(q[2], q[3]), pack2(q[4], q[5]), pack2(q[6], q[7]));
        }
        fence_async();
        bar_sync(1 + wg, 128);
        if ((threadIdx.x & 127) == 0) {
          tma2d_store(&maps.c, epi, tn * BN + r * 128, tm * 128 + wg * 64);
          tma2d_store(&maps.c, epi + 8192, tn * BN + r * 128 + 64, tm * 128 + wg * 64);
          asm volatile("cp.async.bulk.commit_group;" ::: "memory");
        }
      }
    }
    if ((threadIdx.x & 127) == 0) asm volatile("cp.async.bulk.wait_group 0;" ::: "memory");
  }
}

struct RecMaps { CUtensorMap wq, wk, wv, kv, q; };
constexpr int R_WV = 0, R_WO = 65536, R_MEM = 131072, R_KV = 147456, R_KVSZ = 18432, R_RED = 184320, R_REDV = 186368,
              R_S = 194560, R_O = 198400, R_SUM = 200448, R_OX = 200576, R_BAR = 203136, R_TS = 203200,
              R_TOTAL = R_TS + 1024;
#define TS(i)
#define DLY_A 400
#define DLY_V 450
#define DLY_B 500
#define DLY_C 350
__device__ __forceinline__ float rcp(float x) { float r; asm("rcp.approx.ftz.f32 %0, %1;" : "=f"(r) : "f"(x)); return r; }
__device__ __forceinline__ uint32_t uni(uint32_t x) { return __shfl_sync(0xffffffffu, x, 0); }
__device__ __forceinline__ uint32_t pin(uint32_t x) { return __shfl_sync(0xffffffffu, x, threadIdx.x); }
__device__ __forceinline__ uint32_t movm(uint32_t a) { uint32_t d; asm volatile("movmatrix.sync.aligned.m8n8.trans.b16 %0, %1;" : "=r"(d) : "r"(a)); return d; }
__device__ __forceinline__ void mma_a(float (&d)[4], const uint32_t (&a)[4], uint32_t b0, uint32_t b1) { mma16816(d, a[0], a[1], a[2], a[3], b0, b1); }
__device__ __forceinline__ void tma4d(uint32_t dst, const CUtensorMap* m, int c1, int c2, int c3, uint32_t bar) {
  asm volatile("cp.async.bulk.tensor.4d.shared::cluster.global.mbarrier::complete_tx::bytes [%0], [%1, {0, %3, %4, %5}], [%2];"
    :: "r"(dst), "l"(m), "r"(bar), "r"(c1), "r"(c2), "r"(c3) : "memory"); }
__device__ __forceinline__ void tma4d_pf(const CUtensorMap* m, int c1, int c2, int c3) {
  asm volatile("cp.async.bulk.prefetch.tensor.4d.L2.global [%0, {0, %1, %2, %3}];" :: "l"(m), "r"(c1), "r"(c2), "r"(c3) : "memory"); }

__device__ __forceinline__ void rec_issue_kv(const RecMaps& maps, uint32_t dst, uint32_t bar, int s, int h, int j) {
  mbar_expect_tx(bar, R_KVSZ);
  tma4d(dst, &maps.kv, s * SEG, 2 * h, 1, bar);
  tma4d(dst + 16384, &maps.q, s * SEG + 8 * j, 2 * h, 0, bar);
}

__device__ __forceinline__ void poll1(uint64_t (&v)[1][2], const void* p, uint32_t tag, int& it) {
  asm volatile(
    "{.reg .pred q, p0; .reg .b32 u, lo0, lo1, hi, x0;\n"
    "LOOP:\n"
    "mov.b64 {lo0, hi}, %0; mov.b64 {lo1, hi}, %1; lop3.b32 x0, lo0, lo1, %4, 0x7E;\n"
    "and.b32 u, x0, 1;\n"
    "setp.ne.u32 q, u, 0; vote.sync.any.pred q, q, 0xffffffff; @!q bra.uni DONE;\n"
    "add.s32 %2, %2, 1; setp.gt.s32 q, %2, 1048576; @q bra.uni DONE;\n"
    "and.b32 u, x0, 1; setp.ne.u32 p0, u, 0;\n"
    "@p0 ld.relaxed.gpu.global.v2.b64 {%0, %1}, [%3+0];\n"
    "bra.uni LOOP;\n"
    "DONE: }\n"
    : "+l"(v[0][0]), "+l"(v[0][1]), "+r"(it) : "l"(p), "r"(tag) : "memory");
}

__device__ __forceinline__ void poll4_512(uint64_t (&v)[4][2], const void* p, uint32_t tag, int& it) {
  asm volatile(
    "{.reg .pred q, p0, p1, p2, p3; .reg .b32 u, lo0, lo1, hi, x0, x1, x2, x3;\n"
    "LOOP:\n"
    "mov.b64 {lo0, hi}, %0; mov.b64 {lo1, hi}, %1; lop3.b32 x0, lo0, lo1, %10, 0x7E;\n"
    "mov.b64 {lo0, hi}, %2; mov.b64 {lo1, hi}, %3; lop3.b32 x1, lo0, lo1, %10, 0x7E;\n"
    "mov.b64 {lo0, hi}, %4; mov.b64 {lo1, hi}, %5; lop3.b32 x2, lo0, lo1, %10, 0x7E;\n"
    "mov.b64 {lo0, hi}, %6; mov.b64 {lo1, hi}, %7; lop3.b32 x3, lo0, lo1, %10, 0x7E;\n"
    "lop3.b32 u, x0, x1, x2, 0xFE; lop3.b32 u, u, x3, 1, 0xA8;\n"
    "setp.ne.u32 q, u, 0; vote.sync.any.pred q, q, 0xffffffff; @!q bra.uni DONE;\n"
    "add.s32 %8, %8, 1; setp.gt.s32 q, %8, 1048576; @q bra.uni DONE;\n"
    "and.b32 u, x0, 1; setp.ne.u32 p0, u, 0;\n"
    "and.b32 u, x1, 1; setp.ne.u32 p1, u, 0;\n"
    "and.b32 u, x2, 1; setp.ne.u32 p2, u, 0;\n"
    "and.b32 u, x3, 1; setp.ne.u32 p3, u, 0;\n"
    "@p0 ld.relaxed.gpu.global.v2.b64 {%0, %1}, [%9+0];\n"
    "@p1 ld.relaxed.gpu.global.v2.b64 {%2, %3}, [%9+512];\n"
    "@p2 ld.relaxed.gpu.global.v2.b64 {%4, %5}, [%9+1024];\n"
    "@p3 ld.relaxed.gpu.global.v2.b64 {%6, %7}, [%9+1536];\n"
    "bra.uni LOOP;\n"
    "DONE: }\n"
    : "+l"(v[0][0]), "+l"(v[0][1]), "+l"(v[1][0]), "+l"(v[1][1]), "+l"(v[2][0]), "+l"(v[2][1]), "+l"(v[3][0]), "+l"(v[3][1]), "+r"(it) : "l"(p), "r"(tag) : "memory");
}

__device__ __forceinline__ void poll4_1536(uint64_t (&v)[4][2], const void* p, uint32_t tag, int& it) {
  asm volatile(
    "{.reg .pred q, p0, p1, p2, p3; .reg .b32 u, lo0, lo1, hi, x0, x1, x2, x3;\n"
    "LOOP:\n"
    "mov.b64 {lo0, hi}, %0; mov.b64 {lo1, hi}, %1; lop3.b32 x0, lo0, lo1, %10, 0x7E;\n"
    "mov.b64 {lo0, hi}, %2; mov.b64 {lo1, hi}, %3; lop3.b32 x1, lo0, lo1, %10, 0x7E;\n"
    "mov.b64 {lo0, hi}, %4; mov.b64 {lo1, hi}, %5; lop3.b32 x2, lo0, lo1, %10, 0x7E;\n"
    "mov.b64 {lo0, hi}, %6; mov.b64 {lo1, hi}, %7; lop3.b32 x3, lo0, lo1, %10, 0x7E;\n"
    "lop3.b32 u, x0, x1, x2, 0xFE; lop3.b32 u, u, x3, 1, 0xA8;\n"
    "setp.ne.u32 q, u, 0; vote.sync.any.pred q, q, 0xffffffff; @!q bra.uni DONE;\n"
    "add.s32 %8, %8, 1; setp.gt.s32 q, %8, 1048576; @q bra.uni DONE;\n"
    "and.b32 u, x0, 1; setp.ne.u32 p0, u, 0;\n"
    "and.b32 u, x1, 1; setp.ne.u32 p1, u, 0;\n"
    "and.b32 u, x2, 1; setp.ne.u32 p2, u, 0;\n"
    "and.b32 u, x3, 1; setp.ne.u32 p3, u, 0;\n"
    "@p0 ld.relaxed.gpu.global.v2.b64 {%0, %1}, [%9+0];\n"
    "@p1 ld.relaxed.gpu.global.v2.b64 {%2, %3}, [%9+1536];\n"
    "@p2 ld.relaxed.gpu.global.v2.b64 {%4, %5}, [%9+3072];\n"
    "@p3 ld.relaxed.gpu.global.v2.b64 {%6, %7}, [%9+4608];\n"
    "bra.uni LOOP;\n"
    "DONE: }\n"
    : "+l"(v[0][0]), "+l"(v[0][1]), "+l"(v[1][0]), "+l"(v[1][1]), "+l"(v[2][0]), "+l"(v[2][1]), "+l"(v[3][0]), "+l"(v[3][1]), "+r"(it) : "l"(p), "r"(tag) : "memory");
}

__device__ __forceinline__ void poll8_qk(uint64_t (&v)[8][2], const void* p, uint32_t tag, int& it) {
  asm volatile(
    "{.reg .pred q, p0, p1, p2, p3, p4, p5, p6, p7; .reg .b32 u, lo0, lo1, hi, x0, x1, x2, x3, x4, x5, x6, x7;\n"
    "LOOP:\n"
    "mov.b64 {lo0, hi}, %0; mov.b64 {lo1, hi}, %1; lop3.b32 x0, lo0, lo1, %18, 0x7E;\n"
    "mov.b64 {lo0, hi}, %2; mov.b64 {lo1, hi}, %3; lop3.b32 x1, lo0, lo1, %18, 0x7E;\n"
    "mov.b64 {lo0, hi}, %4; mov.b64 {lo1, hi}, %5; lop3.b32 x2, lo0, lo1, %18, 0x7E;\n"
    "mov.b64 {lo0, hi}, %6; mov.b64 {lo1, hi}, %7; lop3.b32 x3, lo0, lo1, %18, 0x7E;\n"
    "mov.b64 {lo0, hi}, %8; mov.b64 {lo1, hi}, %9; lop3.b32 x4, lo0, lo1, %18, 0x7E;\n"
    "mov.b64 {lo0, hi}, %10; mov.b64 {lo1, hi}, %11; lop3.b32 x5, lo0, lo1, %18, 0x7E;\n"
    "mov.b64 {lo0, hi}, %12; mov.b64 {lo1, hi}, %13; lop3.b32 x6, lo0, lo1, %18, 0x7E;\n"
    "mov.b64 {lo0, hi}, %14; mov.b64 {lo1, hi}, %15; lop3.b32 x7, lo0, lo1, %18, 0x7E;\n"
    "lop3.b32 u, x0, x1, x2, 0xFE; lop3.b32 hi, x3, x4, x5, 0xFE; lop3.b32 u, u, x6, x7, 0xFE; lop3.b32 u, u, hi, 1, 0xA8;\n"
    "setp.ne.u32 q, u, 0; vote.sync.any.pred q, q, 0xffffffff; @!q bra.uni DONE;\n"
    "add.s32 %16, %16, 1; setp.gt.s32 q, %16, 1048576; @q bra.uni DONE;\n"
    "and.b32 u, x0, 1; setp.ne.u32 p0, u, 0;\n"
    "and.b32 u, x1, 1; setp.ne.u32 p1, u, 0;\n"
    "and.b32 u, x2, 1; setp.ne.u32 p2, u, 0;\n"
    "and.b32 u, x3, 1; setp.ne.u32 p3, u, 0;\n"
    "and.b32 u, x4, 1; setp.ne.u32 p4, u, 0;\n"
    "and.b32 u, x5, 1; setp.ne.u32 p5, u, 0;\n"
    "and.b32 u, x6, 1; setp.ne.u32 p6, u, 0;\n"
    "and.b32 u, x7, 1; setp.ne.u32 p7, u, 0;\n"
    "@p0 ld.relaxed.gpu.global.v2.b64 {%0, %1}, [%17+0];\n"
    "@p1 ld.relaxed.gpu.global.v2.b64 {%2, %3}, [%17+1536];\n"
    "@p2 ld.relaxed.gpu.global.v2.b64 {%4, %5}, [%17+3072];\n"
    "@p3 ld.relaxed.gpu.global.v2.b64 {%6, %7}, [%17+4608];\n"
    "@p4 ld.relaxed.gpu.global.v2.b64 {%8, %9}, [%17+512];\n"
    "@p5 ld.relaxed.gpu.global.v2.b64 {%10, %11}, [%17+2048];\n"
    "@p6 ld.relaxed.gpu.global.v2.b64 {%12, %13}, [%17+3584];\n"
    "@p7 ld.relaxed.gpu.global.v2.b64 {%14, %15}, [%17+5120];\n"
    "bra.uni LOOP;\n"
    "DONE: }\n"
    : "+l"(v[0][0]), "+l"(v[0][1]), "+l"(v[1][0]), "+l"(v[1][1]), "+l"(v[2][0]), "+l"(v[2][1]), "+l"(v[3][0]), "+l"(v[3][1]), "+l"(v[4][0]), "+l"(v[4][1]), "+l"(v[5][0]), "+l"(v[5][1]), "+l"(v[6][0]), "+l"(v[6][1]), "+l"(v[7][0]), "+l"(v[7][1]), "+r"(it) : "l"(p), "r"(tag) : "memory");
}

__device__ __forceinline__ void poll8_b128(uint64_t (&v)[8][2], const void* p, uint32_t tag, int& it) {
  asm volatile(
    "{.reg .pred q, p0, p1, p2, p3; .reg .b32 u, lo0, lo1, hi, x0, x1, x2, x3; .reg .b128 t;\n"
    "LOOP:\n"
    "mov.b64 {lo0, hi}, %0; mov.b64 {lo1, hi}, %2; lop3.b32 x0, lo0, lo1, %18, 0x7E;\n"
    "mov.b64 {lo0, hi}, %4; mov.b64 {lo1, hi}, %6; lop3.b32 x1, lo0, lo1, %18, 0x7E;\n"
    "mov.b64 {lo0, hi}, %8; mov.b64 {lo1, hi}, %10; lop3.b32 x2, lo0, lo1, %18, 0x7E;\n"
    "mov.b64 {lo0, hi}, %12; mov.b64 {lo1, hi}, %14; lop3.b32 x3, lo0, lo1, %18, 0x7E;\n"
    "lop3.b32 u, x0, x1, x2, 0xFE; lop3.b32 u, u, x3, 1, 0xA8;\n"
    "setp.ne.u32 q, u, 0; vote.sync.any.pred q, q, 0xffffffff; @!q bra.uni DONE;\n"
    "add.s32 %16, %16, 1; setp.gt.s32 q, %16, 1048576; @q bra.uni DONE;\n"
    "and.b32 u, x0, 1; setp.ne.u32 p0, u, 0;\n"
    "and.b32 u, x1, 1; setp.ne.u32 p1, u, 0;\n"
    "and.b32 u, x2, 1; setp.ne.u32 p2, u, 0;\n"
    "and.b32 u, x3, 1; setp.ne.u32 p3, u, 0;\n"
    "mov.b128 t, {%0, %1}; @p0 ld.relaxed.gpu.global.b128 t, [%17+0]; mov.b128 {%0, %1}, t;\n"
    "mov.b128 t, {%2, %3}; @p0 ld.relaxed.gpu.global.b128 t, [%17+512]; mov.b128 {%2, %3}, t;\n"
    "mov.b128 t, {%4, %5}; @p1 ld.relaxed.gpu.global.b128 t, [%17+1024]; mov.b128 {%4, %5}, t;\n"
    "mov.b128 t, {%6, %7}; @p1 ld.relaxed.gpu.global.b128 t, [%17+1536]; mov.b128 {%6, %7}, t;\n"
    "mov.b128 t, {%8, %9}; @p2 ld.relaxed.gpu.global.b128 t, [%17+2048]; mov.b128 {%8, %9}, t;\n"
    "mov.b128 t, {%10, %11}; @p2 ld.relaxed.gpu.global.b128 t, [%17+2560]; mov.b128 {%10, %11}, t;\n"
    "mov.b128 t, {%12, %13}; @p3 ld.relaxed.gpu.global.b128 t, [%17+3072]; mov.b128 {%12, %13}, t;\n"
    "mov.b128 t, {%14, %15}; @p3 ld.relaxed.gpu.global.b128 t, [%17+3584]; mov.b128 {%14, %15}, t;\n"
    "bra.uni LOOP;\n"
    "DONE: }\n"
    : "+l"(v[0][0]), "+l"(v[0][1]), "+l"(v[1][0]), "+l"(v[1][1]), "+l"(v[2][0]), "+l"(v[2][1]), "+l"(v[3][0]), "+l"(v[3][1]), "+l"(v[4][0]), "+l"(v[4][1]), "+l"(v[5][0]), "+l"(v[5][1]), "+l"(v[6][0]), "+l"(v[6][1]), "+l"(v[7][0]), "+l"(v[7][1]), "+r"(it) : "l"(p), "r"(tag) : "memory");
}

__device__ __forceinline__ uint32_t lo32(uint64_t v) { return (uint32_t)v; }
__device__ __forceinline__ uint32_t hi32(uint64_t v) { return (uint32_t)(v >> 32); }
__device__ __forceinline__ void ldx2(uint64_t (&r)[2], const void* p) { asm volatile("ld.relaxed.gpu.global.v2.b64 {%0, %1}, [%2];" : "=l"(r[0]), "=l"(r[1]) : "l"(p) : "memory"); }
__device__ __forceinline__ void ldxb(uint64_t (&r)[2], const void* p) {
  asm volatile("{.reg .b128 t; ld.relaxed.gpu.global.b128 t, [%2]; mov.b128 {%0, %1}, t;}" : "=l"(r[0]), "=l"(r[1]) : "l"(p) : "memory"); }
__device__ __forceinline__ void lds2(uint64_t (&r)[2], uint32_t a) { asm volatile("ld.shared.v2.b64 {%0, %1}, [%2];" : "=l"(r[0]), "=l"(r[1]) : "r"(a) : "memory"); }
__device__ __forceinline__ void sts2(uint32_t a, const uint64_t (&r)[2]) { asm volatile("st.shared.v2.b64 [%0], {%1, %2};" :: "r"(a), "l"(r[0]), "l"(r[1]) : "memory"); }
__device__ __forceinline__ void mma_b(float (&d)[4], const uint32_t (&a)[4], uint64_t b) { mma16816(d, a[0], a[1], a[2], a[3], lo32(b), hi32(b)); }
__device__ __forceinline__ void mma_bb(float (&d)[4], const uint64_t (&a)[2], uint64_t b) { mma16816(d, lo32(a[0]), hi32(a[0]), lo32(a[1]), hi32(a[1]), lo32(b), hi32(b)); }
__device__ __forceinline__ void ldsm4q(uint64_t (&r)[2], uint32_t a) {
  asm volatile("{.reg .b32 a,b,c,d; ldmatrix.sync.aligned.m8n8.x4.shared.b16 {a,b,c,d}, [%2]; mov.b64 %0, {a,b}; mov.b64 %1, {c,d};}" : "=l"(r[0]), "=l"(r[1]) : "r"(a) : "memory"); }
__device__ __forceinline__ void mbar_spin(uint32_t bar, uint32_t par, int& it) {
  asm volatile("{.reg .pred p;\nLOOP: mbarrier.try_wait.parity.shared::cta.b64 p, [%1], %2; @p bra.uni DONE;\n"
               "add.s32 %0, %0, 1; setp.le.s32 p, %0, 1048576; @p bra.uni LOOP;\nDONE: }" : "+r"(it) : "r"(bar), "r"(par) : "memory"); }
__device__ __forceinline__ void delay_until(unsigned t) {
  asm volatile("{.reg .pred p; .reg .b64 c; .reg .b32 lo, hi;\nLOOP: mov.u64 c, %%clock64; mov.b64 {lo, hi}, c; sub.s32 lo, lo, %0; setp.lt.s32 p, lo, 0; @p bra.uni LOOP;}" :: "r"(t) : "memory"); }
__device__ __forceinline__ void zero(float (&c)[4][4]) {
#pragma unroll
  for (int i = 0; i < 4; i++) c[i][0] = c[i][1] = c[i][2] = c[i][3] = 0.f;
}

template <int W4>
__device__ __forceinline__ void qk_gemm(const uint32_t (&w)[32][4], uint64_t (&own)[4][2], uint32_t a, float (&c)[4][4], uint32_t bar, uint32_t par, int& it) {
#pragma unroll
  for (int i = 0; i < 4; i++) {
    mma_b(c[2 * (i & 1)], w[8 * W4 + 2 * i], own[i][0]);
    mma_b(c[2 * (i & 1) + 1], w[8 * W4 + 2 * i + 1], own[i][1]);
  }
  mbar_spin(bar, par, it);
  uint64_t b[12][2];
#pragma unroll
  for (int i = 0; i < 12; i++) lds2(b[i], a + (((W4 + 1 + (i >> 2)) & 3) - W4) * 512 + (i & 3) * 4096);
#pragma unroll
  for (int i = 0; i < 12; i++) {
    const int p = (4 * W4 + 4 + i) & 15;
    mma_b(c[2 * (i & 1)], w[2 * p], b[i][0]);
    mma_b(c[2 * (i & 1) + 1], w[2 * p + 1], b[i][1]);
  }
}

__global__ void __launch_bounds__(256, 1)
rec_kernel(const __grid_constant__ RecMaps maps, const bf16* __restrict__ Wo, const bf16* __restrict__ mem0) {
  extern __shared__ __align__(1024) uint8_t smem_raw[];
  const uint32_t sb = (smem_u32(smem_raw) + 1023) & ~1023u;
  const int tid = threadIdx.x, warp = uni(tid >> 5), lane = tid & 31, wg = warp >> 2, w4 = warp & 3, g = lane >> 2, t = lane & 3;
  const int h = blockIdx.x >> 2, j = blockIdx.x & 3;
  uint32_t wqk[32][4];
  uint32_t wsw[16][4];
  uint64_t own[4][2];
  int it = 0;

  if (tid == 0) {
    mbar_init(sb + R_BAR, 1); mbar_init(sb + R_BAR + 8, 1); mbar_init(sb + R_BAR + 16, 1);
    mbar_init(sb + R_BAR + 24, 128); mbar_init(sb + R_BAR + 32, 128);
    asm volatile("fence.mbarrier_init.release.cluster;" ::: "memory");
    mbar_expect_tx(sb + R_BAR + 16, 3 * 65536);
    for (int i = 0; i < 4; i++) {
      tma2d(sb + R_WO + i * 16384, &maps.wq, h * DH + 32 * j, i * 256, sb + R_BAR + 16);
      tma2d(sb + R_MEM + i * 16384, &maps.wk, h * DH + 32 * j, i * 256, sb + R_BAR + 16);
    }
    for (int i = 0; i < 4; i++) tma2d(sb + R_WV + i * 16384, &maps.wv, h * DH + 32 * j, i * 256, sb + R_BAR + 16);
  }
  {
    const bf16* wp = Wo + (size_t)(h * DH + 2 * t) * DM + 256 * j + 32 * warp + 16 * (g & 1) + 2 * (g >> 1);
#pragma unroll
    for (int ks = 0; ks < 8; ks++)
#pragma unroll
      for (int u = 0; u < 2; u++)
#pragma unroll
        for (int i = 0; i < 2; i++) {
          const uint32_t r0 = __ldg(reinterpret_cast<const uint32_t*>(wp + (size_t)(16 * ks + 8 * u) * DM + 8 * i));
          const uint32_t r1 = __ldg(reinterpret_cast<const uint32_t*>(wp + (size_t)(16 * ks + 8 * u + 1) * DM + 8 * i));
          wsw[2 * ks + i][2 * u] = __byte_perm(r0, r1, 0x5410); wsw[2 * ks + i][2 * u + 1] = __byte_perm(r0, r1, 0x7632);
        }
#pragma unroll
    for (int i = 0; i < 4; i++)
#pragma unroll
      for (int r = 0; r < 2; r++) {
        const uint32_t* mp = reinterpret_cast<const uint32_t*>(mem0 + g * DM + 128 * warp + 32 * i + 16 * r + 2 * t);
        own[i][r] = (uint64_t)__ldg(mp) | ((uint64_t)__ldg(mp + 4) << 32);
      }
  }
  __syncthreads();
  mbar_spin(sb + R_BAR + 16, 0, it);
  const int lrow = (lane & 7) + ((lane >> 4) << 3), lhi = (lane >> 3) & 1;
  {
    const int chunk = w4 < 2 ? w4 + 2 * lhi : 2 * (w4 & 1) + lhi;
    const uint32_t a = sb + (w4 < 2 ? R_WO : R_MEM) + wg * 32768 + lrow * 64 + ((chunk ^ ((lrow >> 1) & 3)) << 4);
#pragma unroll
    for (int ks = 0; ks < 32; ks++) ldsm4t(wqk[ks], a + ks * 1024);
  }
  __syncthreads();
  const uint32_t L16 = pin(lane * 16);
  const uint32_t uT = uni(sb + warp * 512);
#pragma unroll
  for (int i = 0; i < 16; i++) sts128(uT + L16 + R_WO + i * 4096, wsw[i][0], wsw[i][1], wsw[i][2], wsw[i][3]);
  if (tid == 224) {
    fence_async();
    rec_issue_kv(maps, sb + R_KV, sb + R_BAR, 0, h, j);
    tma4d_pf(&maps.kv, SEG, 2 * h, 1); tma4d_pf(&maps.q, SEG + 8 * j, 2 * h, 0);
  }
  __syncwarp();
  auto load_wv = [&]() {
    const uint32_t a = sb + R_WV + warp * 8192 + lrow * 64 + ((lhi ^ ((lrow >> 1) & 3)) << 4);
#pragma unroll
    for (int i = 0; i < 16; i++) ldsm4t(wsw[i], (a ^ ((i & 1) << 5)) + (i >> 1) * 1024);
  };
  auto load_wo = [&]() {
#pragma unroll
    for (int i = 0; i < 16; i++) lds128(wsw[i], uT + L16 + R_WO + i * 4096);
  };
  load_wv();

  const float sc = 0.08838834764831845f * 1.4426950408889634f;
  uint8_t* const xb = reinterpret_cast<uint8_t*>(&g_x);
  uint8_t* const xa = xb + uni(h * 4 * 1536);
  const uint32_t uAw = uni(j * 1536 + (w4 >> 1) * 512 + (w4 & 1) * 8 + wg * 512);
  const uint32_t uBar = uni(sb + R_BAR + 24 + 8 * wg);
  const uint32_t bofs = pin(offsetof(Xchg, B) + ((4 * warp + t) * 4 + j) * 4096 + (h >> 2) * 512 + (g >> 1) * 128 + (h & 3) * 32 + (g & 1) * 16);

#pragma unroll 1
  for (int s = 0; s < NSEG; s++) {
    const uint32_t tag = (s + 1) & 1, T = tag << 16;
    const uint32_t kv = sb + R_KV + (s & 1) * R_KVSZ;
    TS(0);
#pragma unroll
    for (int i = 0; i < 4; i++) sts2(uT + L16 + R_MEM + i * 4096, own[i]);
    mbar_arrive(uBar);
    float c[4][4];
    zero(c);
#pragma unroll
    for (int i = 0; i < 16; i++) mma_b(c[i & 3], wsw[i], own[i >> 2][(i >> 1) & 1]);
#pragma unroll
    for (int i = 0; i < 2; i++)
      sts128(uT + L16 + R_REDV + i * 4096, __float_as_uint(c[i][0] + c[i + 2][0]), __float_as_uint(c[i][1] + c[i + 2][1]),
             __float_as_uint(c[i][2] + c[i + 2][2]), __float_as_uint(c[i][3] + c[i + 2][3]));
    if (warp < 6) bar_arrive(4, 256);
    TS(1);
    zero(c);
    {
      const uint32_t a = uT + L16 + R_MEM;
      if (w4 < 2) { if (w4 == 0) qk_gemm<0>(wqk, own, a, c, uBar, s & 1, it); else qk_gemm<1>(wqk, own, a, c, uBar, s & 1, it); }
      else { if (w4 == 2) qk_gemm<2>(wqk, own, a, c, uBar, s & 1, it); else qk_gemm<3>(wqk, own, a, c, uBar, s & 1, it); }
    }
#pragma unroll
    for (int i = 0; i < 4; i++) c[0][i] = (c[0][i] + c[1][i]) + (c[2][i] + c[3][i]);

    auto load_v = [&](uint32_t (&vf)[4][4]) {
      const uint32_t va = kv + 8192 + (w4 >> 1) * 4096 + lrow * 128 + (((4 * (w4 & 1) + lhi) ^ (lane & 7)) << 4);
#pragma unroll
      for (int i = 0; i < 4; i++) ldsm4t(vf[i], (va ^ ((i & 1) << 5)) + (i >> 1) * 2048);
    };
    auto attend = [&](float (&o)[2][4], const uint32_t (&vf)[4][4], const uint64_t (&vm)[1][2], uint32_t sa, bool isx) {
      float2 sv[5];
#pragma unroll
      for (int i = 0; i < 5; i++) sv[i] = lds64f(sa + i * 256);
      if (isx) {
#pragma unroll
        for (int i = 0; i < 4; i++) {
          if (8 * i + 2 * t > 8 * j + g) sv[i].x = -INFINITY;
          if (8 * i + 2 * t + 1 > 8 * j + g) sv[i].y = -INFINITY;
        }
      }
      float m = fmaxf(fmaxf(fmaxf(sv[0].x, sv[0].y), fmaxf(sv[1].x, sv[1].y)), fmaxf(fmaxf(sv[2].x, sv[2].y), fmaxf(sv[3].x, sv[3].y)));
      m = fmaxf(m, fmaxf(sv[4].x, sv[4].y));
      m = fmaxf(m, __shfl_xor_sync(0xffffffffu, m, 1));
      m = fmaxf(m, __shfl_xor_sync(0xffffffffu, m, 2));
      const float ms = -m * sc;
#pragma unroll
      for (int i = 4; i >= 0; i--) { sv[i].x = ex2(fmaf(sv[i].x, sc, ms)); sv[i].y = ex2(fmaf(sv[i].y, sc, ms)); }
      float sum = ((sv[0].x + sv[0].y) + (sv[1].x + sv[1].y)) + ((sv[2].x + sv[2].y) + (sv[3].x + sv[3].y) + (sv[4].x + sv[4].y));
      float r = 1.f;
      if (isx) { sum += __shfl_xor_sync(0xffffffffu, sum, 1); sum += __shfl_xor_sync(0xffffffffu, sum, 2); r = rcp(sum); }
      uint32_t p[5];
#pragma unroll
      for (int i = 0; i < 5; i++) p[i] = isx ? pack2(sv[i].x * r, sv[i].y * r) : pack2(sv[i].x, sv[i].y);
      mma1688(o[0], lo32(vm[0][0]), hi32(vm[0][0]), p[4]);
      mma1688(o[1], lo32(vm[0][1]), hi32(vm[0][1]), p[4]);
#pragma unroll
      for (int k = 1; k >= 0; k--) {
        mma_a(o[0], vf[2 * k], p[2 * k], p[2 * k + 1]);
        mma_a(o[1], vf[2 * k + 1], p[2 * k], p[2 * k + 1]);
      }
      if (!isx) sts32f(sb + R_SUM + (L16 >> 2), sum);
    };
    uint64_t vm[1][2];
    if (wg == 0) {
      TS(2);
      bar_sync(8 + w4, 64);
      const float4 o4 = lds128f(uT + L16 + R_RED);
      const uint32_t r0 = movm(pack2(c[0][0] + o4.x, c[0][1] + o4.y)), r1 = movm(pack2(c[0][2] + o4.z, c[0][3] + o4.w));
      stx64(xa + uAw + L16, (r0 & ~1u) | tag, r1);
      const unsigned tpub = clk();
      TS(3);
      load_wo();
      mbar_spin(sb + R_BAR + 8 * (s & 1), (s >> 1) & 1, it);
      uint32_t vf[4][4];
      load_v(vf);
      const uint32_t sa = pin(sb + R_S + (L16 >> 1));
      const uint8_t* vsrc = xa + w4 * 1536 + 1024 + L16;
      delay_until(tpub + DLY_V);
      ldx2(vm[0], vsrc);
      poll1(vm, vsrc, tag, it);
      TS(5);
      bar_sync(5, 256);
      float o[2][4] = {{0, 0, 0, 0}, {0, 0, 0, 0}};
      attend(o, vf, vm, sa, false);
      stsm4t(uT + L16 + R_O, pack2(o[0][0], o[0][1]), pack2(o[0][2], o[0][3]), pack2(o[1][0], o[1][1]), pack2(o[1][2], o[1][3]));
    } else {
      sts128(uT + L16 + R_RED - 2048, __float_as_uint(c[0][0]), __float_as_uint(c[0][1]), __float_as_uint(c[0][2]), __float_as_uint(c[0][3]));
      bar_arrive(8 + w4, 64);
      const unsigned tpub = clk();
      TS(2);
      const uint8_t* asrc = xa + L16;
      const uint32_t qa = kv + 16384 + (lane & 7) * 128 + (((2 * lhi + (lane >> 4)) ^ (lane & 7)) << 4);
      if (warp < 6) {
        mbar_spin(sb + R_BAR + 8 * (s & 1), (s >> 1) & 1, it);
        uint32_t kf[8][4];
        uint64_t q[4][2];
        const uint32_t ka = kv + (16 * w4 + (lane & 15)) * 128 + (((2 * (lane >> 4)) ^ (lane & 7)) << 4);
#pragma unroll
        for (int i = 0; i < 8; i++) ldsm4(kf[i], (ka ^ ((4 * ((i >> 1) & 1) + (i & 1)) << 4)) + (i >> 2) * 4096);
#pragma unroll
        for (int i = 0; i < 4; i++) ldsm4q(q[i], (qa ^ ((i & 1) << 6)) + (i >> 1) * 1024);
        const uint32_t sa = pin(sb + R_S + w4 * 512 + t * 64 + g * 4);
        zero(c);
#pragma unroll
        for (int i = 0; i < 8; i++) mma_b(c[i & 3], kf[i], q[i >> 1][i & 1]);
        delay_until(tpub + DLY_A);
        TS(4);
#pragma unroll
        for (int i = 0; i < 4; i++) ldx2(q[i], asrc + i * 1536);
#pragma unroll
        for (int i = 0; i < 4; i++) sts32f(sa + 1280 + (i & 1) * 32 + (i >> 1) * 256, (c[0][i] + c[1][i]) + (c[2][i] + c[3][i]));
        poll4_1536(q, asrc, tag, it);
        TS(5);
        zero(c);
#pragma unroll
        for (int i = 0; i < 8; i++) mma_b(c[i & 3], kf[i], q[i >> 1][i & 1]);
#pragma unroll
        for (int i = 0; i < 4; i++) sts32f(sa + (i & 1) * 32 + (i >> 1) * 256, (c[0][i] + c[1][i]) + (c[2][i] + c[3][i]));
        bar_sync(5, 256);
      } else {
        const uint32_t r = sb + R_REDV + (warp & 1) * 4096 + L16;
        bar_sync(4, 256);
        float4 a[8];
#pragma unroll
        for (int i = 0; i < 8; i++) a[i] = lds128f(r + i * 512);
#pragma unroll
        for (int k = 4; k > 0; k >>= 1)
#pragma unroll
          for (int i = 0; i < k; i++) { a[i].x += a[i + k].x; a[i].y += a[i + k].y; a[i].z += a[i + k].z; a[i].w += a[i + k].w; }
        stx64(xa + uAw + L16, pack2_tag(a[0].x, a[0].y, T), pack2(a[0].z, a[0].w));
        TS(3);
        if (warp == 6) {
          uint64_t qk[8][2], q[4][2];
          const uint32_t sa = pin(sb + R_S + 1024 + t * 64 + g * 4);
          delay_until(tpub + DLY_A);
          TS(4);
#pragma unroll
          for (int i = 0; i < 8; i++) ldx2(qk[i], asrc + (i & 3) * 1536 + (i >> 2) * 512);
          mbar_spin(sb + R_BAR + 8 * (s & 1), (s >> 1) & 1, it);
#pragma unroll
          for (int i = 0; i < 4; i++) ldsm4q(q[i], (qa ^ ((i & 1) << 6)) + (i >> 1) * 1024);
          poll8_qk(qk, asrc, tag, it);
          TS(5);
          zero(c);
#pragma unroll
          for (int i = 0; i < 8; i++) mma_bb(c[i & 3], qk[4 + (i >> 1)], qk[i >> 1][i & 1]);
#pragma unroll
          for (int i = 0; i < 2; i++) sts32f(sa + i * 32, (c[0][i] + c[1][i + 2]) + (c[2][i] + c[3][i + 2]));
          bar_arrive(5, 256);
          zero(c);
#pragma unroll
          for (int i = 0; i < 8; i++) mma_bb(c[i & 3], qk[4 + (i >> 1)], q[i >> 1][i & 1]);
#pragma unroll
          for (int i = 0; i < 2; i++) sts32f(sa + 1280 + i * 32, (c[0][i] + c[1][i + 2]) + (c[2][i] + c[3][i + 2]));
        } else {
          if (lane == 0) {
            if (s + 2 < NSEG) { tma4d_pf(&maps.kv, (s + 2) * SEG, 2 * h, 1); tma4d_pf(&maps.q, (s + 2) * SEG + 8 * j, 2 * h, 0); }
            fence_async();
          }
          __syncwarp();
          bar_sync(5, 256);
          if (lane == 0 && s + 1 < NSEG) rec_issue_kv(maps, sb + R_KV + ((s + 1) & 1) * R_KVSZ, sb + R_BAR + 8 * ((s + 1) & 1), s + 1, h, j);
          __syncwarp();
        }
      }
      TS(6);
      const uint8_t* vsrc = asrc + w4 * 1536 + 1024;
      ldx2(vm[0], vsrc);
      load_wo();
      poll1(vm, vsrc, tag, it);
    }
    TS(7);
    bar_sync(6, 256);
    if (s + 1 < NSEG) {
      uint64_t b[4][2];
#pragma unroll
      for (int i = 0; i < 4; i++) ldsm4q(b[i], sb + R_O + i * 512 + L16);
      const float4 s0 = lds128f(sb + R_SUM + ((L16 << 1) & 96)), s1 = lds128f(sb + R_SUM + 16 + ((L16 << 1) & 96));
      zero(c);
#pragma unroll
      for (int i = 0; i < 16; i++) mma_b(c[i & 3], wsw[i], b[i >> 2][(i >> 1) & 1]);
      const float r0 = rcp((s0.x + s0.y) + (s0.z + s0.w)), r1 = rcp((s1.x + s1.y) + (s1.z + s1.w));
      stx128(xb + bofs, pack2_tag((c[0][0] + c[2][0]) * r0, (c[0][2] + c[2][2]) * r0, T), pack2((c[1][0] + c[3][0]) * r0, (c[1][2] + c[3][2]) * r0),
             pack2((c[0][1] + c[2][1]) * r1, (c[0][3] + c[2][3]) * r1), pack2((c[1][1] + c[3][1]) * r1, (c[1][3] + c[3][3]) * r1));
    }
    const unsigned tb = clk();
    TS(9);
    if (wg == 1) {
      float o[2][4] = {{0, 0, 0, 0}, {0, 0, 0, 0}};
      uint32_t vf[4][4];
      load_v(vf);
      attend(o, vf, vm, sb + R_S + 1280 + lane * 8, true);
      const uint32_t ox = sb + R_OX + w4 * 640;
      stsm4t(ox + (lane & 7) * 80 + (lane >> 3) * 16, pack2(o[0][0], o[0][1]), pack2(o[0][2], o[0][3]), pack2(o[1][0], o[1][1]), pack2(o[1][2], o[1][3]));
      __syncwarp();
      uint32_t v[4]; lds128(v, ox + g * 80 + t * 16);
      *reinterpret_cast<uint4*>(&g_ox[(size_t)(s * SEG + 8 * j + g) * HD + h * DH + 32 * w4 + 8 * t]) = make_uint4(v[0], v[1], v[2], v[3]);
    }
    if (s + 1 < NSEG) {
      if (warp == 0) {
        const uint8_t* src = xb + offsetof(Xchg, B) + blockIdx.x * 4096 + (g >> 1) * 128 + t * 32 + (g & 1) * 16;
        const uint32_t cofs = pin(offsetof(Xchg, C) + (32 * j + h) * 128 + t * 64 + g * 8);
        const uint64_t bsel = (uint64_t)pin(g == 0 ? 0x00003F80u : g == 1 ? 0x3F800000u : 0u) | ((uint64_t)pin(g == 2 ? 0x00003F80u : g == 3 ? 0x3F800000u : 0u) << 32);
        uint64_t v[8][2];
        delay_until(tb + DLY_B);
        TS(8);
#pragma unroll
        for (int i = 0; i < 8; i++) ldxb(v[i], src + i * 512);
        poll8_b128(v, src, tag, it);
        TS(10);
        zero(c);
#pragma unroll
        for (int i = 0; i < 8; i++) mma_bb(c[i & 3], v[i], bsel);
#pragma unroll
        for (int i = 0; i < 4; i++) c[0][i] = (c[0][i] + c[1][i]) + (c[2][i] + c[3][i]);
        if (!(L16 & 32)) stx64(xb + cofs, pack2_tag(c[0][0], c[0][1], T), pack2(c[0][2], c[0][3]));
        sts32f(sb + R_BAR + 48, __uint_as_float(clk()));
        TS(11);
        bar_arrive(7, 256);
      }
      load_wv();
      if (warp != 0) { TS(11); bar_sync(7, 256); }
      const uint8_t* src = xb + offsetof(Xchg, C) + warp * 2048 + L16;
      uint32_t tc; asm volatile("ld.volatile.shared.u32 %0, [%1];" : "=r"(tc) : "r"(sb + R_BAR + 48) : "memory");
      delay_until(tc + DLY_C);
      TS(12);
#pragma unroll
      for (int i = 0; i < 4; i++) ldx2(own[i], src + i * 512);
      poll4_512(own, src, tag, it);
    }
  }
  if (it > SPIN_LIMIT) g_err = 2;
}

template <int N, int LOGN, int SIGN>
__device__ __forceinline__ float2* fft_smem(float2* a, float2* b) {
  const int i = threadIdx.x;
#pragma unroll 1
  for (int p = 1; p < N; p <<= 1) {
    __syncthreads();
    const int k = i & (p - 1);
    float sn, cs; sincospif(SIGN * (float)k / (float)p, &sn, &cs);
    const float2 u = a[i], v0 = a[i + N / 2];
    const float2 v = make_float2(v0.x * cs - v0.y * sn, v0.x * sn + v0.y * cs);
    const int o = ((i - k) << 1) + k;
    b[o] = make_float2(u.x + v.x, u.y + v.y); b[o + p] = make_float2(u.x - v.x, u.y - v.y);
    float2* tmp = a; a = b; b = tmp;
  }
  __syncthreads();
  return a;
}
__global__ void __launch_bounds__(512) fft_p1(const bf16* __restrict__ x) {
  __shared__ float2 a[1024], b[1024];
  const int m = blockIdx.x;
  for (int i = threadIdx.x; i < 1024; i += 512) a[i] = make_float2(__bfloat162float(x[m * 1024 + i]), __bfloat162float(x[(m + 1024) * 1024 + i]));
  float2* z = fft_smem<1024, 10, -1>(a, b);
  for (int f = threadIdx.x; f <= 512; f += 512) {
    const float2 p = z[f], q = z[(1024 - f) & 1023];
    g_f1[f * 2048 + m] = make_float2(0.5f * (p.x + q.x), 0.5f * (p.y - q.y));
    g_f1[f * 2048 + m + 1024] = make_float2(0.5f * (p.y + q.y), 0.5f * (q.x - p.x));
  }
}
__global__ void __launch_bounds__(1024) fft_p2(const bf16* __restrict__ wr, const bf16* __restrict__ wi) {
  __shared__ float2 a[2048], b[2048];
  const int f = blockIdx.x;
  for (int i = threadIdx.x; i < 2048; i += 1024) a[i] = g_f1[f * 2048 + i];
  float2* z = fft_smem<2048, 11, -1>(a, b);
  for (int i = threadIdx.x; i < 2048; i += 1024) {
    const float r = __bfloat162float(wr[i * 513 + f]), im = __bfloat162float(wi[i * 513 + f]);
    const float2 v = z[i];
    z[i] = make_float2(v.x * r - v.y * im, v.x * im + v.y * r);
  }
  float2* y = fft_smem<2048, 11, 1>(z, z == a ? b : a);
  for (int i = threadIdx.x; i < 2048; i += 1024) g_f1[f * 2048 + i] = y[i];
}
__global__ void __launch_bounds__(512) fft_p3(bf16* __restrict__ out) {
  __shared__ float2 a[1024], b[1024];
  const int m = blockIdx.x;
  for (int f = threadIdx.x; f <= 512; f += 512) {
    float2 p = g_f1[f * 2048 + m], q = g_f1[f * 2048 + m + 1024];
    if (f == 0 || f == 512) { p.y = 0.f; q.y = 0.f; }
    a[f] = make_float2(p.x - q.y, p.y + q.x);
    if (f != 0 && f != 512) a[1024 - f] = make_float2(p.x + q.y, q.x - p.y);
  }
  float2* z = fft_smem<1024, 10, 1>(a, b);
  const float sc = 1.f / (2048.f * 1024.f);
  for (int i = threadIdx.x; i < 1024; i += 512) {
    out[(size_t)m * 2048 + 1024 + i] = __float2bfloat16(z[i].x * sc);
    out[(size_t)(m + 1024) * 2048 + 1024 + i] = __float2bfloat16(z[i].y * sc);
  }
}

typedef CUresult (*EncodeFn)(CUtensorMap*, CUtensorMapDataType, cuuint32_t, void*, const cuuint64_t*, const cuuint64_t*, const cuuint32_t*,
                             const cuuint32_t*, CUtensorMapInterleave, CUtensorMapSwizzle, CUtensorMapL2promotion, CUtensorMapFloatOOBfill);
static void make_map(EncodeFn fn, CUtensorMap* m, const void* p, uint64_t cols, uint64_t rows, uint64_t pitch, uint32_t bc, uint32_t br, CUtensorMapSwizzle sw) {
  cuuint64_t dims[2] = {cols, rows}, strides[1] = {pitch * 2};
  cuuint32_t box[2] = {bc, br}, es[2] = {1, 1};
  fn(m, CU_TENSOR_MAP_DATA_TYPE_BFLOAT16, 2, const_cast<void*>(p), dims, strides, box, es, CU_TENSOR_MAP_INTERLEAVE_NONE, sw,
     CU_TENSOR_MAP_L2_PROMOTION_L2_256B, CU_TENSOR_MAP_FLOAT_OOB_FILL_NONE);
}

extern "C" void kernel_launch(void* const* d_in, const int* in_sizes, int n_in, void* d_out, int out_size) {
  const bf16* Ax = (const bf16*)d_in[0]; const bf16* mem0 = (const bf16*)d_in[1];
  const bf16* Wq = (const bf16*)d_in[2]; const bf16* Wk = (const bf16*)d_in[3]; const bf16* Wv = (const bf16*)d_in[4];
  const bf16* Wo = (const bf16*)d_in[5];
  const bf16* Bx = (const bf16*)d_in[7]; const bf16* wr = (const bf16*)d_in[8]; const bf16* wi = (const bf16*)d_in[9];
  bf16* out = (bf16*)d_out;

  void* fp = nullptr; cudaDriverEntryPointQueryResult qr;
  cudaGetDriverEntryPoint("cuTensorMapEncodeTiled", &fp, cudaEnableDefault, &qr);
  EncodeFn fn = (EncodeFn)fp;
  void *qkv, *ox;
  cudaGetSymbolAddress(&qkv, g_qkv); cudaGetSymbolAddress(&ox, g_ox);
  const CUtensorMapSwizzle S128 = CU_TENSOR_MAP_SWIZZLE_128B, S64 = CU_TENSOR_MAP_SWIZZLE_64B;

  GemmMaps m1, m3; RecMaps mr;
  make_map(fn, &m1.a, Ax, DM, S_LEN, DM, 64, 128, S128);
  make_map(fn, &m1.b[0], Wq, HD, DM, HD, 64, 64, S128);
  make_map(fn, &m1.b[1], Wk, HD, DM, HD, 64, 64, S128);
  make_map(fn, &m1.b[2], Wv, HD, DM, HD, 64, 64, S128);
  make_map(fn, &m1.c, qkv, 3 * HD, S_LEN, 3 * HD, 64, 64, S128);
  make_map(fn, &m3.a, ox, HD, S_LEN, HD, 64, 128, S128);
  make_map(fn, &m3.b[0], Wo, DM, HD, DM, 64, 64, S128);
  m3.b[1] = m3.b[0]; m3.b[2] = m3.b[0];
  make_map(fn, &m3.c, out, DM, S_LEN, 2 * DM, 64, 64, S128);
  make_map(fn, &mr.wq, Wq, HD, DM, HD, 32, 256, S64);
  make_map(fn, &mr.wk, Wk, HD, DM, HD, 32, 256, S64);
  make_map(fn, &mr.wv, Wv, HD, DM, HD, 32, 256, S64);
  for (int i = 0; i < 2; i++) {
    cuuint64_t dims[4] = {64, S_LEN, 2 * NH, 3}, strides[3] = {3 * HD * 2, 128, HD * 2};
    cuuint32_t box[4] = {64, i ? 8u : 32u, 2, i ? 1u : 2u}, es[4] = {1, 1, 1, 1};
    fn(i ? &mr.q : &mr.kv, CU_TENSOR_MAP_DATA_TYPE_BFLOAT16, 4, qkv, dims, strides, box, es, CU_TENSOR_MAP_INTERLEAVE_NONE, S128,
       CU_TENSOR_MAP_L2_PROMOTION_L2_256B, CU_TENSOR_MAP_FLOAT_OOB_FILL_NONE);
  }

  constexpr int SM1 = 4 * 49152 + 32768 + 256 + 1024, SM3 = 6 * 32768 + 32768 + 256 + 1024;
  cudaFuncSetAttribute(gemm_kernel<256, 4>, cudaFuncAttributeMaxDynamicSharedMemorySize, SM1);
  cudaFuncSetAttribute(gemm_kernel<128, 6>, cudaFuncAttributeMaxDynamicSharedMemorySize, SM3);
  cudaFuncSetAttribute(rec_kernel, cudaFuncAttributeMaxDynamicSharedMemorySize, R_TOTAL);

  cudaStream_t st = cudaStreamPerThread;
  gemm_kernel<256, 4><<<132, 384, SM1, st>>>(m1, 16, 48, 16, 16, 1);
  rec_kernel<<<128, 256, R_TOTAL, st>>>(mr, Wo, mem0);
  gemm_kernel<128, 6><<<128, 384, SM3, st>>>(m3, 16, 8, 64, 8, 0);
  fft_p1<<<1024, 512, 0, st>>>(Bx);
  fft_p2<<<513, 1024, 0, st>>>(wr, wi);
  fft_p3<<<1024, 512, 0, st>>>(out);
}
```

```cpp
#include <cuda_runtime.h>
#include <cuda_bf16.h>
#include <cuda.h>
#include <stdint.h>
#include <stddef.h>

typedef __nv_bfloat16 bf16;

constexpr int S_LEN = 2048, DM = 1024, NH = 32, DH = 128, MEM = 8, SEG = 32, NSEG = 64;
constexpr int HD = NH * DH;
constexpr int SPIN_LIMIT = 1 << 20;

__device__ __align__(1024) bf16 g_qkv[(size_t)S_LEN * 3 * HD];
__device__ __align__(1024) bf16 g_ox[(size_t)S_LEN * HD];
struct Xchg {
  uint4 A[128][3][32];
  uint4 C[1024];
  uint4 B[128][256];
  unsigned ctr[32];
};
__device__ __align__(4096) Xchg g_x;
__device__ __align__(1024) uint4 g_y[1024 * 256];
__device__ __align__(1024) uint4 g_wt[513 * 512];
__device__ int g_err;

__device__ __forceinline__ unsigned clk() { unsigned long long c; asm volatile("mov.u64 %0, %%clock64;" : "=l"(c)); return (unsigned)c; }
__device__ __forceinline__ uint32_t smem_u32(const void* p) { return (uint32_t)__cvta_generic_to_shared(p); }
__device__ __forceinline__ void mbar_init(uint32_t bar, int cnt) { asm volatile("mbarrier.init.shared::cta.b64 [%0], %1;" :: "r"(bar), "r"(cnt) : "memory"); }
__device__ __forceinline__ void mbar_expect_tx(uint32_t bar, int bytes) { asm volatile("mbarrier.arrive.expect_tx.shared::cta.b64 _, [%0], %1;" :: "r"(bar), "r"(bytes) : "memory"); }
__device__ __forceinline__ void mbar_arrive(uint32_t bar) { asm volatile("mbarrier.arrive.shared::cta.b64 _, [%0];" :: "r"(bar) : "memory"); }
__device__ __forceinline__ void mbar_arrive_cluster(uint32_t bar, int cta) {
  asm volatile("{.reg .b32 r; mapa.shared::cluster.u32 r, %0, %1; mbarrier.arrive.shared::cluster.b64 _, [r];}" :: "r"(bar), "r"(cta) : "memory"); }
__device__ __forceinline__ bool mbar_try(uint32_t bar, int par) {
  uint32_t ok; asm volatile("{.reg .pred p; mbarrier.try_wait.parity.shared::cta.b64 p, [%1], %2; selp.u32 %0, 1, 0, p;}" : "=r"(ok) : "r"(bar), "r"(par) : "memory"); return ok; }
__device__ __forceinline__ void mbar_wait(uint32_t bar, int par) {
  int it = 0;
  while (!mbar_try(bar, par)) { if (++it > SPIN_LIMIT) { g_err = 1; break; } }
}
__device__ __forceinline__ void tma2d(uint32_t dst, const CUtensorMap* m, int c0, int c1, uint32_t bar) {
  asm volatile("cp.async.bulk.tensor.2d.shared::cluster.global.mbarrier::complete_tx::bytes [%0], [%1, {%3, %4}], [%2];"
    :: "r"(dst), "l"(m), "r"(bar), "r"(c0), "r"(c1) : "memory"); }
__device__ __forceinline__ void tma2d_mc(uint32_t dst, const CUtensorMap* m, int c0, int c1, uint32_t bar, uint16_t mask) {
  asm volatile("cp.async.bulk.tensor.2d.shared::cluster.global.mbarrier::complete_tx::bytes.multicast::cluster [%0], [%1, {%3, %4}], [%2], %5;"
    :: "r"(dst), "l"(m), "r"(bar), "r"(c0), "r"(c1), "h"(mask) : "memory"); }
__device__ __forceinline__ void tma2d_store(const CUtensorMap* m, uint32_t src, int c0, int c1) {
  asm volatile("cp.async.bulk.tensor.2d.global.shared::cta.bulk_group [%0, {%2, %3}], [%1];" :: "l"(m), "r"(src), "r"(c0), "r"(c1) : "memory"); }
__device__ __forceinline__ void fence_async() { asm volatile("fence.proxy.async.shared::cta;" ::: "memory"); }
__device__ __forceinline__ void bar_sync(int id, int n) { asm volatile("bar.sync %0, %1;" :: "r"(id), "r"(n) : "memory"); }
__device__ __forceinline__ void bar_arrive(int id, int n) { asm volatile("bar.arrive %0, %1;" :: "r"(id), "r"(n) : "memory"); }
__device__ __forceinline__ uint32_t pack2(float lo, float hi) { uint32_t r; asm("cvt.rn.bf16x2.f32 %0, %1, %2;" : "=r"(r) : "f"(hi), "f"(lo)); return r; }
__device__ __forceinline__ uint32_t pack2_tag(float lo, float hi, uint32_t T) {
  uint32_t u = ((__float_as_uint(lo) - T + 0x10000u) & 0xFFFE0000u) + T;
  return __byte_perm(u, pack2(0.f, hi), 0x7632); }
__device__ __forceinline__ void ldsm4(uint32_t (&r)[4], uint32_t a) {
  asm volatile("ldmatrix.sync.aligned.m8n8.x4.shared.b16 {%0,%1,%2,%3}, [%4];" : "=r"(r[0]), "=r"(r[1]), "=r"(r[2]), "=r"(r[3]) : "r"(a) : "memory"); }
__device__ __forceinline__ void ldsm4t(uint32_t (&r)[4], uint32_t a) {
  asm volatile("ldmatrix.sync.aligned.m8n8.x4.trans.shared.b16 {%0,%1,%2,%3}, [%4];" : "=r"(r[0]), "=r"(r[1]), "=r"(r[2]), "=r"(r[3]) : "r"(a) : "memory"); }
__device__ __forceinline__ void stsm4(uint32_t a, uint32_t r0, uint32_t r1, uint32_t r2, uint32_t r3) {
  asm volatile("stmatrix.sync.aligned.m8n8.x4.shared.b16 [%0], {%1,%2,%3,%4};" :: "r"(a), "r"(r0), "r"(r1), "r"(r2), "r"(r3) : "memory"); }
__device__ __forceinline__ void stsm4t(uint32_t a, uint32_t r0, uint32_t r1, uint32_t r2, uint32_t r3) {
  asm volatile("stmatrix.sync.aligned.m8n8.x4.trans.shared.b16 [%0], {%1,%2,%3,%4};" :: "r"(a), "r"(r0), "r"(r1), "r"(r2), "r"(r3) : "memory"); }
__device__ __forceinline__ void lds128(uint32_t (&r)[4], uint32_t a) {
  asm volatile("ld.shared.v4.u32 {%0,%1,%2,%3}, [%4];" : "=r"(r[0]), "=r"(r[1]), "=r"(r[2]), "=r"(r[3]) : "r"(a) : "memory"); }
__device__ __forceinline__ float4 lds128f(uint32_t a) { float4 r;
  asm volatile("ld.shared.v4.f32 {%0,%1,%2,%3}, [%4];" : "=f"(r.x), "=f"(r.y), "=f"(r.z), "=f"(r.w) : "r"(a) : "memory"); return r; }
__device__ __forceinline__ float2 lds64f(uint32_t a) { float2 r;
  asm volatile("ld.shared.v2.f32 {%0,%1}, [%2];" : "=f"(r.x), "=f"(r.y) : "r"(a) : "memory"); return r; }
__device__ __forceinline__ void sts128(uint32_t a, uint32_t r0, uint32_t r1, uint32_t r2, uint32_t r3) {
  asm volatile("st.shared.v4.u32 [%0], {%1,%2,%3,%4};" :: "r"(a), "r"(r0), "r"(r1), "r"(r2), "r"(r3) : "memory"); }
__device__ __forceinline__ void sts64f(uint32_t a, float x, float y) { asm volatile("st.shared.v2.f32 [%0], {%1,%2};" :: "r"(a), "f"(x), "f"(y) : "memory"); }
__device__ __forceinline__ void sts32f(uint32_t a, float x) { asm volatile("st.shared.f32 [%0], %1;" :: "r"(a), "f"(x) : "memory"); }
__device__ __forceinline__ void mma16816(float (&d)[4], uint32_t a0, uint32_t a1, uint32_t a2, uint32_t a3, uint32_t b0, uint32_t b1) {
  asm volatile("mma.sync.aligned.m16n8k16.row.col.f32.bf16.bf16.f32 {%0,%1,%2,%3}, {%4,%5,%6,%7}, {%8,%9}, {%0,%1,%2,%3};"
    : "+f"(d[0]), "+f"(d[1]), "+f"(d[2]), "+f"(d[3]) : "r"(a0), "r"(a1), "r"(a2), "r"(a3), "r"(b0), "r"(b1)); }
__device__ __forceinline__ void mma1688(float (&d)[4], uint32_t a0, uint32_t a1, uint32_t b0) {
  asm volatile("mma.sync.aligned.m16n8k8.row.col.f32.bf16.bf16.f32 {%0,%1,%2,%3}, {%4,%5}, {%6}, {%0,%1,%2,%3};"
    : "+f"(d[0]), "+f"(d[1]), "+f"(d[2]), "+f"(d[3]) : "r"(a0), "r"(a1), "r"(b0)); }
__device__ __forceinline__ void ldx128(uint32_t (&r)[4], const void* p) {
  asm volatile("{.reg .b128 t; .reg .b64 a, b; ld.relaxed.gpu.global.b128 t, [%4]; mov.b128 {a, b}, t; mov.b64 {%0,%1}, a; mov.b64 {%2,%3}, b;}"
    : "=r"(r[0]), "=r"(r[1]), "=r"(r[2]), "=r"(r[3]) : "l"(p) : "memory"); }
__device__ __forceinline__ void ldx2x64(uint32_t (&r)[4], const void* p) {
  asm volatile("{.reg .b64 a, b; ld.relaxed.gpu.global.v2.b64 {a, b}, [%4]; mov.b64 {%0,%1}, a; mov.b64 {%2,%3}, b;}"
    : "=r"(r[0]), "=r"(r[1]), "=r"(r[2]), "=r"(r[3]) : "l"(p) : "memory"); }
__device__ __forceinline__ void stx128(void* p, uint32_t r0, uint32_t r1, uint32_t r2, uint32_t r3) {
  asm volatile("{.reg .b128 t; .reg .b64 a, b; mov.b64 a, {%1,%2}; mov.b64 b, {%3,%4}; mov.b128 t, {a, b}; st.relaxed.gpu.global.b128 [%0], t;}"
    :: "l"(p), "r"(r0), "r"(r1), "r"(r2), "r"(r3) : "memory"); }
__device__ __forceinline__ void stx64(void* p, uint32_t r0, uint32_t r1) {
  asm volatile("{.reg .b64 a; mov.b64 a, {%1,%2}; st.relaxed.gpu.global.b64 [%0], a;}" :: "l"(p), "r"(r0), "r"(r1) : "memory"); }
__device__ __forceinline__ uint32_t uni(uint32_t x) { return __shfl_sync(0xffffffffu, x, 0); }
__device__ __forceinline__ uint32_t pin(uint32_t x) { return __shfl_sync(0xffffffffu, x, threadIdx.x); }
__device__ __forceinline__ float ex2(float x) { float r; asm("ex2.approx.ftz.f32 %0, %1;" : "=f"(r) : "f"(x)); return r; }
__device__ __forceinline__ void wg_fence() { asm volatile("wgmma.fence.sync.aligned;" ::: "memory"); }
__device__ __forceinline__ void wg_commit() { asm volatile("wgmma.commit_group.sync.aligned;" ::: "memory"); }
template <int N> __device__ __forceinline__ void wg_wait() { asm volatile("wgmma.wait_group.sync.aligned %0;" :: "n"(N) : "memory"); }

__device__ __forceinline__ void wgmma_ss_n256_tb1(float (&d)[128], uint64_t da, uint64_t db, int sc) {
  asm volatile("{.reg .pred p; setp.ne.b32 p, %130, 0;\n"
    "wgmma.mma_async.sync.aligned.m64n256k16.f32.bf16.bf16 {%0,%1,%2,%3,%4,%5,%6,%7,%8,%9,%10,%11,%12,%13,%14,%15,%16,%17,%18,%19,%20,%21,%22,%23,%24,%25,%26,%27,%28,%29,%30,%31,%32,%33,%34,%35,%36,%37,%38,%39,%40,%41,%42,%43,%44,%45,%46,%47,%48,%49,%50,%51,%52,%53,%54,%55,%56,%57,%58,%59,%60,%61,%62,%63,%64,%65,%66,%67,%68,%69,%70,%71,%72,%73,%74,%75,%76,%77,%78,%79,%80,%81,%82,%83,%84,%85,%86,%87,%88,%89,%90,%91,%92,%93,%94,%95,%96,%97,%98,%99,%100,%101,%102,%103,%104,%105,%106,%107,%108,%109,%110,%111,%112,%113,%114,%115,%116,%117,%118,%119,%120,%121,%122,%123,%124,%125,%126,%127}, %128, %129, p, 1, 1, 0, 1;}\n"
    : "+f"(d[0]),"+f"(d[1]),"+f"(d[2]),"+f"(d[3]),"+f"(d[4]),"+f"(d[5]),"+f"(d[6]),"+f"(d[7]),"+f"(d[8]),"+f"(d[9]),"+f"(d[10]),"+f"(d[11]),"+f"(d[12]),"+f"(d[13]),"+f"(d[14]),"+f"(d[15]),"+f"(d[16]),"+f"(d[17]),"+f"(d[18]),"+f"(d[19]),"+f"(d[20]),"+f"(d[21]),"+f"(d[22]),"+f"(d[23]),"+f"(d[24]),"+f"(d[25]),"+f"(d[26]),"+f"(d[27]),"+f"(d[28]),"+f"(d[29]),"+f"(d[30]),"+f"(d[31]),"+f"(d[32]),"+f"(d[33]),"+f"(d[34]),"+f"(d[35]),"+f"(d[36]),"+f"(d[37]),"+f"(d[38]),"+f"(d[39]),"+f"(d[40]),"+f"(d[41]),"+f"(d[42]),"+f"(d[43]),"+f"(d[44]),"+f"(d[45]),"+f"(d[46]),"+f"(d[47]),"+f"(d[48]),"+f"(d[49]),"+f"(d[50]),"+f"(d[51]),"+f"(d[52]),"+f"(d[53]),"+f"(d[54]),"+f"(d[55]),"+f"(d[56]),"+f"(d[57]),"+f"(d[58]),"+f"(d[59]),"+f"(d[60]),"+f"(d[61]),"+f"(d[62]),"+f"(d[63]),"+f"(d[64]),"+f"(d[65]),"+f"(d[66]),"+f"(d[67]),"+f"(d[68]),"+f"(d[69]),"+f"(d[70]),"+f"(d[71]),"+f"(d[72]),"+f"(d[73]),"+f"(d[74]),"+f"(d[75]),"+f"(d[76]),"+f"(d[77]),"+f"(d[78]),"+f"(d[79]),"+f"(d[80]),"+f"(d[81]),"+f"(d[82]),"+f"(d[83]),"+f"(d[84]),"+f"(d[85]),"+f"(d[86]),"+f"(d[87]),"+f"(d[88]),"+f"(d[89]),"+f"(d[90]),"+f"(d[91]),"+f"(d[92]),"+f"(d[93]),"+f"(d[94]),"+f"(d[95]),"+f"(d[96]),"+f"(d[97]),"+f"(d[98]),"+f"(d[99]),"+f"(d[100]),"+f"(d[101]),"+f"(d[102]),"+f"(d[103]),"+f"(d[104]),"+f"(d[105]),"+f"(d[106]),"+f"(d[107]),"+f"(d[108]),"+f"(d[109]),"+f"(d[110]),"+f"(d[111]),"+f"(d[112]),"+f"(d[113]),"+f"(d[114]),"+f"(d[115]),"+f"(d[116]),"+f"(d[117]),"+f"(d[118]),"+f"(d[119]),"+f"(d[120]),"+f"(d[121]),"+f"(d[122]),"+f"(d[123]),"+f"(d[124]),"+f"(d[125]),"+f"(d[126]),"+f"(d[127])
    : "l"(da), "l"(db), "r"(sc));
}

__device__ __forceinline__ void wgmma_ss_n128_tb1(float (&d)[64], uint64_t da, uint64_t db, int sc) {
  asm volatile("{.reg .pred p; setp.ne.b32 p, %66, 0;\n"
    "wgmma.mma_async.sync.aligned.m64n128k16.f32.bf16.bf16 {%0,%1,%2,%3,%4,%5,%6,%7,%8,%9,%10,%11,%12,%13,%14,%15,%16,%17,%18,%19,%20,%21,%22,%23,%24,%25,%26,%27,%28,%29,%30,%31,%32,%33,%34,%35,%36,%37,%38,%39,%40,%41,%42,%43,%44,%45,%46,%47,%48,%49,%50,%51,%52,%53,%54,%55,%56,%57,%58,%59,%60,%61,%62,%63}, %64, %65, p, 1, 1, 0, 1;}\n"
    : "+f"(d[0]),"+f"(d[1]),"+f"(d[2]),"+f"(d[3]),"+f"(d[4]),"+f"(d[5]),"+f"(d[6]),"+f"(d[7]),"+f"(d[8]),"+f"(d[9]),"+f"(d[10]),"+f"(d[11]),"+f"(d[12]),"+f"(d[13]),"+f"(d[14]),"+f"(d[15]),"+f"(d[16]),"+f"(d[17]),"+f"(d[18]),"+f"(d[19]),"+f"(d[20]),"+f"(d[21]),"+f"(d[22]),"+f"(d[23]),"+f"(d[24]),"+f"(d[25]),"+f"(d[26]),"+f"(d[27]),"+f"(d[28]),"+f"(d[29]),"+f"(d[30]),"+f"(d[31]),"+f"(d[32]),"+f"(d[33]),"+f"(d[34]),"+f"(d[35]),"+f"(d[36]),"+f"(d[37]),"+f"(d[38]),"+f"(d[39]),"+f"(d[40]),"+f"(d[41]),"+f"(d[42]),"+f"(d[43]),"+f"(d[44]),"+f"(d[45]),"+f"(d[46]),"+f"(d[47]),"+f"(d[48]),"+f"(d[49]),"+f"(d[50]),"+f"(d[51]),"+f"(d[52]),"+f"(d[53]),"+f"(d[54]),"+f"(d[55]),"+f"(d[56]),"+f"(d[57]),"+f"(d[58]),"+f"(d[59]),"+f"(d[60]),"+f"(d[61]),"+f"(d[62]),"+f"(d[63])
    : "l"(da), "l"(db), "r"(sc));
}

template <int BN> struct WG;
template <> struct WG<256> { static __device__ __forceinline__ void mma(float (&d)[128], uint64_t a, uint64_t b, int sc) { wgmma_ss_n256_tb1(d, a, b, sc); } };
template <> struct WG<128> { static __device__ __forceinline__ void mma(float (&d)[64], uint64_t a, uint64_t b, int sc) { wgmma_ss_n128_tb1(d, a, b, sc); } };

struct GemmMaps { CUtensorMap a, b[3], c; };
template <int BN, int STAGES>
__global__ void __cluster_dims__(2, 1, 1) __launch_bounds__(384, 1)
gemm_kernel(const __grid_constant__ GemmMaps maps, int tilesM, int tilesN, int kblocks, int nPerB, int clearX) {
  extern __shared__ __align__(1024) uint8_t smem_raw[];
  constexpr int STAGE_BYTES = 16384 + BN * 128;
  constexpr int NBOX = BN / 64;
  const uint32_t sbase = (smem_u32(smem_raw) + 1023) & ~1023u;
  const uint32_t sEpi = sbase + STAGES * STAGE_BYTES;
  const uint32_t sBar = sEpi + 32768;
  const int warp = threadIdx.x >> 5, lane = threadIdx.x & 31, wg = warp >> 2;
  uint32_t crank; asm("mov.u32 %0, %%cluster_ctarank;" : "=r"(crank));
  if (threadIdx.x == 0) {
    for (int i = 0; i < STAGES; i++) { mbar_init(sBar + 8 * i, 1); mbar_init(sBar + 8 * (STAGES + i), 4); }
    asm volatile("fence.mbarrier_init.release.cluster;" ::: "memory");
  }
  if (clearX) {
    uint4* p = reinterpret_cast<uint4*>(&g_x);
    for (int i = blockIdx.x * 384 + threadIdx.x; i < (int)(sizeof(Xchg) / 16); i += gridDim.x * 384) p[i] = make_uint4(0, 0, 0, 0);
  }
  asm volatile("barrier.cluster.arrive.release.aligned; barrier.cluster.wait.acquire.aligned;" ::: "memory");
  const int npairs = (tilesM >> 1) * tilesN, pair0 = blockIdx.x >> 1, pstep = gridDim.x >> 1;
  if (wg == 2) {
    asm volatile("setmaxnreg.dec.sync.aligned.u32 40;");
    if (warp == 8 && lane == 0) {
      int st = 0, ph = 1;
      for (int p = pair0; p < npairs; p += pstep) {
        const int tm = (p % (tilesM >> 1)) * 2 + crank, tn = p / (tilesM >> 1);
        const CUtensorMap* mb = &maps.b[tn / nPerB];
        const int n0 = (tn % nPerB) * BN;
        for (int kb = 0; kb < kblocks; kb++) {
          mbar_wait(sBar + 8 * (STAGES + st), ph);
          const uint32_t a = sbase + st * STAGE_BYTES, full = sBar + 8 * st;
          mbar_expect_tx(full, STAGE_BYTES);
          tma2d(a, &maps.a, kb * 64, tm * 128, full);
#pragma unroll
          for (int i = 0; i < NBOX / 2; i++) {
            const int bx = crank * (NBOX / 2) + i;
            tma2d_mc(a + 16384 + bx * 8192, mb, n0 + bx * 64, kb * 64, full, (uint16_t)3);
          }
          if (++st == STAGES) { st = 0; ph ^= 1; }
        }
      }
      for (int i = 0; i < STAGES; i++) { mbar_wait(sBar + 8 * (STAGES + st), ph); if (++st == STAGES) { st = 0; ph ^= 1; } }
    }
  } else {
    asm volatile("setmaxnreg.inc.sync.aligned.u32 232;");
    int st = 0, ph = 0;
    float acc[BN / 2];
    const uint64_t descA0 = (uint64_t)(((sbase + wg * 8192) & 0x3FFFF) >> 4) | (1ull << 16) | (64ull << 32) | (1ull << 62);
    const uint64_t descB0 = (uint64_t)(((sbase + 16384) & 0x3FFFF) >> 4) | (512ull << 16) | (64ull << 32) | (1ull << 62);
    const uint32_t epi = sEpi + wg * 16384;
    for (int p = pair0; p < npairs; p += pstep) {
      const int tm = (p % (tilesM >> 1)) * 2 + crank, tn = p / (tilesM >> 1);
      int prev = -1;
      for (int kb = 0; kb < kblocks; kb++) {
        mbar_wait(sBar + 8 * st, ph);
        wg_fence();
        const uint64_t so = (uint64_t)(st * (STAGE_BYTES >> 4));
#pragma unroll
        for (int k = 0; k < 4; k++) WG<BN>::mma(acc, descA0 + so + k * 2, descB0 + so + k * 128, kb | k);
        wg_commit();
        if (prev >= 0) {
          wg_wait<1>();
          if ((threadIdx.x & 127) < 2) mbar_arrive_cluster(sBar + 8 * (STAGES + prev), threadIdx.x & 1);
        }
        prev = st;
        if (++st == STAGES) { st = 0; ph ^= 1; }
      }
      wg_wait<0>();
      if ((threadIdx.x & 127) < 2) mbar_arrive_cluster(sBar + 8 * (STAGES + prev), threadIdx.x & 1);
#pragma unroll
      for (int r = 0; r < BN / 128; r++) {
        if ((threadIdx.x & 127) == 0) asm volatile("cp.async.bulk.wait_group.read 0;" ::: "memory");
        bar_sync(1 + wg, 128);
        const int row = (warp & 3) * 16 + (lane & 15);
#pragma unroll
        for (int i = 0; i < 8; i++) {
          const int c = 2 * (i & 3) + (lane >> 4);
          const float* q = &acc[r * 64 + i * 8];
          stsm4(epi + (i >> 2) * 8192 + row * 128 + ((c ^ (row & 7)) << 4), pack2(q[0], q[1]), pack2(q[2], q[3]), pack2(q[4], q[5]), pack2(q[6], q[7]));
        }
        fence_async();
        bar_sync(1 + wg, 128);
        if ((threadIdx.x & 127) == 0) {
          tma2d_store(&maps.c, epi, tn * BN + r * 128, tm * 128 + wg * 64);
          tma2d_store(&maps.c, epi + 8192, tn * BN + r * 128 + 64, tm * 128 + wg * 64);
          asm volatile("cp.async.bulk.commit_group;" ::: "memory");
        }
      }
    }
    if ((threadIdx.x & 127) == 0) asm volatile("cp.async.bulk.wait_group 0;" ::: "memory");
  }
}

struct Dft { uint32_t m[2][2][2][4]; };
template <bool P4> __device__ __forceinline__ int fidx(int tile, int x) { return P4 ? 4 * (x >> 1) + 2 * (tile & 1) + (x & 1) + 16 * (tile >> 1) : x + 8 * tile; }
__device__ __forceinline__ float2 cis(int k, int n) {
  k &= n - 1; if (2 * k > n) k -= n;
  const float a = (float)k * (6.283185307179586f / (float)n);
  return make_float2(__cosf(a), __sinf(a));
}
template <bool OUT4> __device__ __forceinline__ void make_dft(Dft& D, int g, int t) {
#pragma unroll
  for (int q = 0; q < 16; q++) {
    const int b = q >> 3, u = (q >> 2) & 1, r = (q >> 1) & 1, v = q & 1;
    const float2 w = cis(fidx<OUT4>(v, g) * fidx<false>(2 * u + r, 2 * t + b), 32);
    D.m[b][u][0][q & 3] = pack2(w.x, w.y); D.m[b][u][1][q & 3] = pack2(-w.y, w.x);
  }
}
__device__ __forceinline__ void mma_dc(float (&d)[4], uint32_t a0, uint32_t a1, uint32_t a2, uint32_t a3, uint32_t b0, uint32_t b1, const float (&c)[4]) {
  asm("mma.sync.aligned.m16n8k16.row.col.f32.bf16.bf16.f32 {%0,%1,%2,%3}, {%4,%5,%6,%7}, {%8,%9}, {%10,%11,%12,%13};"
    : "=f"(d[0]), "=f"(d[1]), "=f"(d[2]), "=f"(d[3]) : "r"(a0), "r"(a1), "r"(a2), "r"(a3), "r"(b0), "r"(b1), "f"(c[0]), "f"(c[1]), "f"(c[2]), "f"(c[3])); }
__device__ __forceinline__ void dft_b(const Dft& D, const uint32_t (&x)[2][4], float (&o)[2][8]) {
#pragma unroll
  for (int ri = 0; ri < 2; ri++) {
    float z[4] = {0.f, 0.f, 0.f, 0.f}, e[4], p[4];
    mma_dc(e, D.m[0][0][ri][0], D.m[0][0][ri][1], D.m[0][0][ri][2], D.m[0][0][ri][3], x[0][0], x[0][1], z);
    mma_dc(e, D.m[0][1][ri][0], D.m[0][1][ri][1], D.m[0][1][ri][2], D.m[0][1][ri][3], x[0][2], x[0][3], e);
    mma_dc(p, D.m[1][0][ri][0], D.m[1][0][ri][1], D.m[1][0][ri][2], D.m[1][0][ri][3], x[1][0], x[1][1], e);
    mma_dc(p, D.m[1][1][ri][0], D.m[1][1][ri][1], D.m[1][1][ri][2], D.m[1][1][ri][3], x[1][2], x[1][3], p);
#pragma unroll
    for (int q = 0; q < 4; q++) { o[ri][q] = p[q]; o[ri][4 + q] = fmaf(2.f, e[q], -p[q]); }
  }
}
__device__ __forceinline__ void dft_a(const uint32_t (&m)[2][2][4], const uint32_t (&x0)[2][4], const uint32_t (&x1)[2][4], float (&o)[2][8]) {
#pragma unroll
  for (int ri = 0; ri < 2; ri++) {
    float z[4] = {0.f, 0.f, 0.f, 0.f}, e[4], p[4];
    mma_dc(e, x0[0][0], x1[0][0], x0[0][1], x1[0][1], m[0][ri][0], m[0][ri][1], z);
    mma_dc(e, x0[0][2], x1[0][2], x0[0][3], x1[0][3], m[0][ri][2], m[0][ri][3], e);
    mma_dc(p, x0[1][0], x1[1][0], x0[1][1], x1[1][1], m[1][ri][0], m[1][ri][1], e);
    mma_dc(p, x0[1][2], x1[1][2], x0[1][3], x1[1][3], m[1][ri][2], m[1][ri][3], p);
#pragma unroll
    for (int q = 0; q < 4; q++) { o[ri][q] = p[q]; o[ri][4 + q] = fmaf(2.f, e[q], -p[q]); }
  }
}
__device__ __forceinline__ uint32_t twid(float re, float im, float c, float s) { return pack2(fmaf(re, c, im * s), fmaf(im, c, -re * s)); }
__device__ __forceinline__ void cpa16(uint32_t d, const void* s) { asm volatile("cp.async.cg.shared.global [%0], [%1], 16;" :: "r"(d), "l"(s) : "memory"); }
__device__ __forceinline__ void sts32(uint32_t a, uint32_t x) { asm volatile("st.shared.u32 [%0], %1;" :: "r"(a), "r"(x) : "memory"); }
__device__ __forceinline__ void cpa_commit() { asm volatile("cp.async.commit_group;" ::: "memory"); }
template <int N> __device__ __forceinline__ void cpa_wait() { asm volatile("cp.async.wait_group %0;" :: "n"(N) : "memory"); }
__device__ __forceinline__ uint32_t lds32(uint32_t a) { uint32_t r; asm volatile("ld.shared.u32 %0, [%1];" : "=r"(r) : "r"(a) : "memory"); return r; }
constexpr int F_TP = 4112, F_TSZ = 8 * F_TP;

__device__ __forceinline__ void fft_wprep(const bf16* __restrict__ wr, const bf16* __restrict__ wi, int cta, int ncta) {
  const int tid = threadIdx.x;
#pragma unroll 2
  for (int it = cta; it < 256; it += ncta) {
    const int g = (it >> 1) & 7, c = (it >> 4) & 3, i = it >> 6, t = 2 * (it & 1) + (tid & 1);
    const int k0 = g + 8 * i + 32 * (8 * c + 2 * t), l0 = (tid & ~1) + (g & 1);
    uint32_t a[2][4], b[2][4];
#pragma unroll
    for (int q = 0; q < 8; q++) {
      const int o = (k0 + 32 * ((q >> 1) & 1) + 1024 * (q & 1)) * 513 + l0 + 256 * (q >> 2);
      a[q >> 2][q & 3] = __ldg(reinterpret_cast<const uint32_t*>(wr + o));
      b[q >> 2][q & 3] = __ldg(reinterpret_cast<const uint32_t*>(wi + o));
    }
    uint4* dst = g_wt + l0 * 512 + it * 2 + (tid & 1);
#pragma unroll
    for (int q = 0; q < 4; q++) {
      const int hf = q >> 1, l = l0 + 256 * hf + (q & 1);
      const uint32_t sel = (q & 1) ? 0x7632 : 0x5410;
      if (l & 511) dst[(256 * hf + (q & 1)) * 512] = make_uint4(__byte_perm(a[hf][0], b[hf][0], sel), __byte_perm(a[hf][1], b[hf][1], sel),
                                                              __byte_perm(a[hf][2], b[hf][2], sel), __byte_perm(a[hf][3], b[hf][3], sel));
    }
  }
  for (int e = cta * 256 + tid; e < 4096; e += ncta * 256) {
    const int l = (e >> 11) * 512, k = e & 2047, kn = (2048 - k) & 2047, k2 = (k >> 5) & 31;
    const float re = 0.5f * (__bfloat162float(wr[k * 513 + l]) + __bfloat162float(wr[kn * 513 + l]));
    const float im = 0.5f * (__bfloat162float(wi[k * 513 + l]) - __bfloat162float(wi[kn * 513 + l]));
    reinterpret_cast<uint32_t*>(g_wt)[(64 * ((k >> 3) & 3) + 16 * (k2 >> 3) + 2 * (k & 7) + ((k2 >> 2) & 1)) * 8 + l * 2048 + 2 * (k2 & 3) + (k >> 10)] = pack2(re, im);
  }
}

__device__ __forceinline__ void fft_rows_fwd(const bf16* __restrict__ x, uint32_t sb, int cta, int ncta) {
  const int warp = threadIdx.x >> 5, lane = threadIdx.x & 31, g = lane >> 2, t = lane & 3;
  const uint32_t in = sb + warp * 8192, tb = sb + 65536;
  const uint32_t f0 = pin(in + (lane >> 3) * 256 + (((lane & 7) ^ (2 * (lane >> 3))) << 4));
  const uint32_t xo = pin((256 * (warp & 3) + 64 * (warp >> 2)) * 2048 + lane * 8);
  auto fetch = [&](int it, int buf) {
    const bf16* src = x + (xo + (128 * (it & 1) + 32 * ((it >> 4) & 1) + 8 * (it >> 5) + ((it >> 1) & 7)) * 2048);
#pragma unroll
    for (int q = 0; q < 8; q++) cpa16(((f0 + buf * 4096) ^ ((q >> 2) * 144)) + (q & 3) * 1024, src + q * 256);
    cpa_commit();
  };
  fetch(cta, 0);
  Dft D; make_dft<true>(D, g, t);
  float2 tw[4][8];
#pragma unroll
  for (int q = 0; q < 32; q++) tw[q >> 3][q & 7] = cis(fidx<true>((q >> 1) & 3, g) * fidx<false>(q >> 3, 2 * t + (q & 1)), 1024);
  const uint32_t la = pin(in + lane * 128 + ((lane & 7) << 4));
  const uint32_t wa = pin(tb + warp * F_TP + fidx<true>(0, g) * 128 + t * 16), wz = pin((g & 1) ? -64 : 64);
  const uint32_t ra = pin(tb + (lane & 1) * 4 * F_TP + ((lane >> 1) + 16 * (warp ^ ((warp >> 1) & 1))) * 4);
  uint4* dst = g_y + (threadIdx.x >> 1) * 256 + (lane & 1);
  int buf = 0;
  auto drain = [&](int it, int q) {
    const uint32_t r = ra + (buf ^ 1) * F_TSZ + q * 512;
    const uint4 v = make_uint4(lds32(r), lds32(r + F_TP), lds32(r + 2 * F_TP), lds32(r + 3 * F_TP));
    if (it >= 0) dst[it * 2 + q * 32768] = v;
  };
  int it = cta;
#pragma unroll 1
  for (; it < 128; it += ncta, buf ^= 1) {
    cpa_wait<0>(); __syncthreads();
    uint32_t a[4][2][4], y[4][2][4];
#pragma unroll
    for (int q = 0; q < 8; q++) ldsm4t(a[q & 3][q >> 2], (la + buf * 4096) ^ (q << 4));
    if (it + ncta < 128) fetch(it + ncta, buf ^ 1);
    float o[2][8];
#pragma unroll
    for (int i = 0; i < 4; i++) {
      dft_b(D, a[i], o);
      drain(it - ncta, i);
#pragma unroll
      for (int q = 0; q < 8; q++) y[q >> 1][q & 1][i] = twid(o[0][q], o[1][q], tw[i][q].x, tw[i][q].y);
    }
    const uint32_t w0 = wa + buf * F_TSZ + ((g & 1) << 6);
#pragma unroll
    for (int z = 0; z < 2; z++) {
      float o2[2][8];
      dft_b(D, y[2 * z], o); drain(it - ncta, 4 + 2 * z); dft_b(D, y[2 * z + 1], o2); drain(it - ncta, 5 + 2 * z);
#pragma unroll
      for (int i = 0; i < 4; i++) {
        const float sg = i < 2 ? 1.f : -1.f;
        sts128(w0 + z * wz + fidx<true>(i, 0) * 128, pack2(o[0][2 * i], sg * o[1][2 * i]), pack2(o[0][2 * i + 1], sg * o[1][2 * i + 1]),
               pack2(o2[0][2 * i], sg * o2[1][2 * i]), pack2(o2[0][2 * i + 1], sg * o2[1][2 * i + 1]));
      }
    }
  }
  __syncthreads();
#pragma unroll
  for (int q = 0; q < 8; q++) drain(it - ncta, q);
}

__device__ __forceinline__ void fft_cols(uint32_t sb, int cta, int ncta) {
  const int warp = threadIdx.x >> 5, lane = threadIdx.x & 31, g = lane >> 2, t = lane & 3;
  const uint32_t in = sb + warp * 16384 + lane * 16, tab = sb + 131072 + lane * 16;
  auto fetch_y = [&](int l) {
#pragma unroll
    for (int q = 0; q < 16; q++) cpa16(in + q * 512, g_y + (q < 8 ? l : (1024 - l) & 1023) * 256 + (q & 7) * 32 + lane);
  };
  auto fetch_w = [&](int l) {
#pragma unroll
    for (int q = 0; q < 16; q++) cpa16(in + 8192 + q * 512, g_wt + l * 512 + q * 32 + lane);
  };
  const int l0 = cta * 8 + warp, dl = ncta * 8;
  if (l0 <= 512) fetch_y(l0);
  cpa_commit();
  if (l0 <= 512) fetch_w(l0);
  cpa_commit();
  Dft D; make_dft<false>(D, g, t);
#pragma unroll
  for (int q = 2 * warp; q < 2 * warp + 2; q++) {
    const int r = fidx<false>(q & 3, g), c = fidx<false>(q >> 2, 2 * t);
    const float2 w0 = cis(r * c, 1024), w1 = cis(r * c + r, 1024), p0 = cis(r + 32 * c, 2048), p1 = cis(r + 32 * c + 32, 2048);
    sts128(tab + q * 512, __float_as_uint(w0.x), __float_as_uint(w0.y), __float_as_uint(w1.x), __float_as_uint(w1.y));
    sts128(tab + 8192 + q * 512, __float_as_uint(p0.x), __float_as_uint(p0.y), __float_as_uint(p1.x), __float_as_uint(p1.y));
  }
  if (warp == 0) {
#pragma unroll
    for (int q = 0; q < 8; q++) {
      const int v = q >> 2, b = (q >> 1) & 1, ri = q & 1;
      sts128(tab + 16384 + q * 512, D.m[b][0][ri][v], D.m[b][0][ri][v + 2], D.m[b][1][ri][v], D.m[b][1][ri][v + 2]);
    }
  }
  __syncthreads();
#pragma unroll 1
  for (int l = l0; l <= 512; l += dl) {
    uint32_t a[2][4][2][4], y[2][4][2][4];
    float o[2][2][8];
    cpa_wait<1>();
#pragma unroll
    for (int q = 0; q < 16; q++) lds128(a[q >> 3][(q >> 1) & 3][q & 1], in + q * 512);
    if (!(l & 511)) {
      const uint32_t m0 = l ? 0x80000000u : 0u;
#pragma unroll
      for (int q = 0; q < 32; q++) { a[0][q >> 3][(q >> 2) & 1][q & 3] ^= m0; a[1][q >> 3][(q >> 2) & 1][q & 3] ^= m0 ^ 0x80000000u; }
    }
    auto first = [&]() {
#pragma unroll
      for (int i = 0; i < 4; i++) {
        dft_b(D, a[0][i], o[0]); dft_b(D, a[1][i], o[1]);
#pragma unroll
        for (int r = 0; r < 4; r++) {
          const float4 w = lds128f(tab + (4 * i + r) * 512);
#pragma unroll
          for (int s = 0; s < 2; s++) {
            y[s][r][0][i] = twid(o[s][0][2 * r], o[s][1][2 * r], w.x, w.y);
            y[s][r][1][i] = twid(o[s][0][2 * r + 1], o[s][1][2 * r + 1], w.z, w.w);
          }
        }
      }
    };
    first();
    if (l + dl <= 512) fetch_y(l + dl);
    cpa_commit();
    cpa_wait<1>();
#pragma unroll
    for (int zv = 0; zv < 4; zv++) {
      const int z = zv >> 1, v = zv & 1;
      uint32_t m[2][2][4];
#pragma unroll
      for (int q = 0; q < 4; q++) lds128(m[q >> 1][q & 1], tab + 16384 + (4 * v + q) * 512);
      dft_a(m, y[0][2 * z], y[0][2 * z + 1], o[0]); dft_a(m, y[1][2 * z], y[1][2 * z + 1], o[1]);
#pragma unroll
      for (int q = 0; q < 4; q++) {
        const int i = 2 * z + (q & 1), c = v + (q & 2);
        uint32_t w[4]; lds128(w, in + 8192 + (4 * i + c) * 512);
        const float4 ph = lds128f(tab + 8192 + (4 * c + i) * 512);
#pragma unroll
        for (int b = 0; b < 2; b++) {
          const float cs = b ? ph.z : ph.x, sn = b ? ph.w : ph.y;
          const float r1 = __uint_as_float(w[2 * b] << 16), i1 = __uint_as_float(w[2 * b] & 0xFFFF0000u);
          const float r2 = __uint_as_float(w[2 * b + 1] << 16), i2 = __uint_as_float(w[2 * b + 1] & 0xFFFF0000u);
          const float Sr = r1 + r2, Si = i1 + i2, Dr = r1 - r2, Di = i1 - i2;
          const float ar = fmaf(-Dr, sn, Sr), ai = fmaf(-Di, sn, Si), dr = fmaf(Dr, sn, Sr), di = fmaf(Di, sn, Si), br = -Di * cs, bi = Dr * cs;
          const float Ar = o[0][0][2 * q + b], Ai = o[0][1][2 * q + b], Br = o[1][0][2 * q + b], Bi = o[1][1][2 * q + b];
          a[0][i][b][c] = pack2(fmaf(ar, Ai, fmaf(ai, Ar, fmaf(br, Bi, bi * Br))), fmaf(ar, Ar, fmaf(-ai, Ai, fmaf(br, Br, -bi * Bi))));
          a[1][i][b][c] = pack2(fmaf(dr, Bi, fmaf(di, Br, fmaf(-br, Ai, -bi * Ar))), fmaf(dr, Br, fmaf(-di, Bi, fmaf(-br, Ar, bi * Ai))));
        }
      }
    }
    if (l + dl <= 512) fetch_w(l + dl);
    cpa_commit();
    first();
#pragma unroll
    for (int s = 0; s < 2; s++) {
      uint4* dst = g_y + (s ? (1024 - l) & 1023 : l) * 256 + lane;
      const float sg = s ? -1.f : 1.f;
#pragma unroll
      for (int i = 0; i < 4; i++) {
        dft_b(D, y[s][i], o[0]);
#pragma unroll
        for (int b = 0; b < 2; b++)
          dst[(2 * i + b) * 32] = make_uint4(pack2(sg * o[0][0][b], o[0][1][b]), pack2(sg * o[0][0][2 + b], o[0][1][2 + b]),
                                             pack2(sg * o[0][0][4 + b], o[0][1][4 + b]), pack2(sg * o[0][0][6 + b], o[0][1][6 + b]));
      }
    }
  }
}

__device__ __forceinline__ void fft_rows_inv(const CUtensorMap* om, uint32_t sb, int cta, int ncta) {
  const int warp = threadIdx.x >> 5, lane = threadIdx.x & 31, g = lane >> 2, t = lane & 3, wg = warp >> 2, w4 = warp & 3;
  const uint32_t tb = sb + 32768 + wg * 2 * F_TSZ;
  const uint4* src = g_y + pin((256 * ((lane >> 1) & 3) + 64 * (lane >> 3) + 8 * w4) * 256 + (lane & 1));
  const uint32_t wa = pin(tb + (lane & 1) * 4 * F_TP + w4 * 1024 + (lane >> 1) * 4);
  uint4 pf[8];
  auto fetch = [&](int it, int hf) {
#pragma unroll
    for (int q = 0; q < 8; q++) pf[q] = __ldcg(src + (it * 2 + hf * 8192) + q * 256);
  };
  auto put = [&](uint32_t off) {
#pragma unroll
    for (int q = 0; q < 8; q++) {
      sts32(wa + off + q * 64, pf[q].x); sts32(wa + off + q * 64 + F_TP, pf[q].y);
      sts32(wa + off + q * 64 + 2 * F_TP, pf[q].z); sts32(wa + off + q * 64 + 3 * F_TP, pf[q].w);
    }
  };
  const int it0 = 2 * cta + wg;
  if (it0 >= 128) return;
  fetch(it0, 0); put(0); fetch(it0, 1); put(512);
  Dft D; make_dft<false>(D, g, t);
  float2 tw[4][8];
#pragma unroll
  for (int q = 0; q < 32; q++) {
    tw[q >> 3][q & 7] = cis(fidx<false>((q >> 1) & 3, g) * fidx<false>(q >> 3, 2 * t + (q & 1)), 1024);
    tw[q >> 3][q & 7].x *= 1.f / 2097152.f; tw[q >> 3][q & 7].y *= 1.f / 2097152.f;
  }
  const uint32_t la = pin(tb + w4 * F_TP + lane * 16), ob = uni(sb + warp * 4096);
  const uint32_t oa = pin(ob + (lane >> 1) * 128 + (((4 * (lane & 1)) ^ ((lane >> 1) & 7)) << 4));
#pragma unroll 1
  for (int n = 0;; n++) {
    const int it = it0 + (n >> 1) * 2 * ncta, hf = n & 1, buf = (n >> 1) & 1;
    if (it >= 128) break;
    if (!hf) bar_sync(1 + wg, 128);
    uint32_t a[4][2][4], y[4][2][4];
#pragma unroll
    for (int q = 0; q < 8; q++) lds128(a[q >> 1][q & 1], la + buf * F_TSZ + hf * 4 * F_TP + q * 512);
    fetch(min(it + 2 * ncta, 127), hf);
    float o[2][8];
#pragma unroll
    for (int i = 0; i < 4; i++) {
      dft_b(D, a[i], o);
#pragma unroll
      for (int q = 0; q < 8; q++) y[q >> 1][q & 1][i] = twid(o[0][q], o[1][q], tw[i][q].x, tw[i][q].y);
    }
    if (lane == 0) asm volatile("cp.async.bulk.wait_group.read 0;" ::: "memory");
    __syncwarp();
#pragma unroll
    for (int c = 0; c < 4; c++) {
      dft_b(D, y[c], o);
#pragma unroll
      for (int ri = 0; ri < 2; ri++)
        stsm4((oa ^ (c << 4)) + (1 - ri) * 2048, pack2(o[ri][0], o[ri][1]), pack2(o[ri][2], o[ri][3]), pack2(o[ri][4], o[ri][5]), pack2(o[ri][6], o[ri][7]));
    }
    fence_async();
    __syncwarp();
    if (lane == 0) {
      const int m = 256 * w4 + 32 * ((it >> 1) & 7) + 8 * (it >> 5) + 4 * (it & 1) + 2 * hf + ((it >> 4) & 1);
      asm volatile("cp.async.bulk.tensor.3d.global.shared::cta.bulk_group [%0, {0, 0, %2}], [%1];" :: "l"(om), "r"(ob), "r"(2 * m) : "memory");
      asm volatile("cp.async.bulk.commit_group;" ::: "memory");
    }
    put((buf ^ 1) * F_TSZ + hf * 512);
  }
  if (lane == 0) asm volatile("cp.async.bulk.wait_group 0;" ::: "memory");
}
constexpr int F_SMEM = 65536 + 2 * F_TSZ + 1024;
__global__ void __launch_bounds__(256, 1) fft_pre_kernel(const bf16* __restrict__ x, const bf16* __restrict__ wr, const bf16* __restrict__ wi) {
  extern __shared__ __align__(1024) uint8_t smem_raw[];
  const uint32_t sb = (smem_u32(smem_raw) + 1023) & ~1023u;
  fft_wprep(wr, wi, blockIdx.x, gridDim.x);
  fft_rows_fwd(x, sb, blockIdx.x, gridDim.x);
}
__device__ __forceinline__ void grid_arrive(unsigned* ctr) {
  __syncthreads();
  if (threadIdx.x == 0) { __threadfence(); atomicAdd(ctr, 1u); }
}
__device__ __forceinline__ void grid_wait(unsigned* ctr, unsigned n) {
  if (threadIdx.x == 0) {
    int it = 0;
    while (*reinterpret_cast<volatile unsigned*>(ctr) < n) { __nanosleep(200); if (++it > SPIN_LIMIT) { g_err = 3; break; } }
    __threadfence();
  }
  __syncthreads();
}

struct RecMaps { CUtensorMap wq, wk, wv, kv, q, fo; };
constexpr int R_WV = 0, R_WO = 65536, R_MEM = 131072, R_KV = 147456, R_KVSZ = 18432, R_RED = 184320, R_REDV = 186368,
              R_S = 194560, R_O = 198400, R_SUM = 200448, R_OX = 200576, R_BAR = 203136, R_TS = 203200,
              R_TOTAL = R_TS + 1024;
#define TS(i)
#define RECG 132
#define DLY_A 400
#define DLY_V 450
#define DLY_B 500
#define DLY_C 350
__device__ __forceinline__ float rcp(float x) { float r; asm("rcp.approx.ftz.f32 %0, %1;" : "=f"(r) : "f"(x)); return r; }
__device__ __forceinline__ uint32_t movm(uint32_t a) { uint32_t d; asm volatile("movmatrix.sync.aligned.m8n8.trans.b16 %0, %1;" : "=r"(d) : "r"(a)); return d; }
__device__ __forceinline__ void mma_a(float (&d)[4], const uint32_t (&a)[4], uint32_t b0, uint32_t b1) { mma16816(d, a[0], a[1], a[2], a[3], b0, b1); }
__device__ __forceinline__ void tma4d(uint32_t dst, const CUtensorMap* m, int c1, int c2, int c3, uint32_t bar) {
  asm volatile("cp.async.bulk.tensor.4d.shared::cluster.global.mbarrier::complete_tx::bytes [%0], [%1, {0, %3, %4, %5}], [%2];"
    :: "r"(dst), "l"(m), "r"(bar), "r"(c1), "r"(c2), "r"(c3) : "memory"); }
__device__ __forceinline__ void tma4d_pf(const CUtensorMap* m, int c1, int c2, int c3) {
  asm volatile("cp.async.bulk.prefetch.tensor.4d.L2.global [%0, {0, %1, %2, %3}];" :: "l"(m), "r"(c1), "r"(c2), "r"(c3) : "memory"); }

__device__ __forceinline__ void rec_issue_kv(const RecMaps& maps, uint32_t dst, uint32_t bar, int s, int h, int j) {
  mbar_expect_tx(bar, R_KVSZ);
  tma4d(dst, &maps.kv, s * SEG, 2 * h, 1, bar);
  tma4d(dst + 16384, &maps.q, s * SEG + 8 * j, 2 * h, 0, bar);
}

__device__ __forceinline__ void poll1(uint64_t (&v)[1][2], const void* p, uint32_t tag, int& it) {
  asm volatile(
    "{.reg .pred q, p0; .reg .b32 u, lo0, lo1, hi, x0;\n"
    "LOOP:\n"
    "mov.b64 {lo0, hi}, %0; mov.b64 {lo1, hi}, %1; lop3.b32 x0, lo0, lo1, %4, 0x7E;\n"
    "and.b32 u, x0, 1;\n"
    "setp.ne.u32 q, u, 0; vote.sync.any.pred q, q, 0xffffffff; @!q bra.uni DONE;\n"
    "add.s32 %2, %2, 1; setp.gt.s32 q, %2, 1048576; @q bra.uni DONE;\n"
    "and.b32 u, x0, 1; setp.ne.u32 p0, u, 0;\n"
    "@p0 ld.relaxed.gpu.global.v2.b64 {%0, %1}, [%3+0];\n"
    "bra.uni LOOP;\n"
    "DONE: }\n"
    : "+l"(v[0][0]), "+l"(v[0][1]), "+r"(it) : "l"(p), "r"(tag) : "memory");
}

__device__ __forceinline__ void poll4_512(uint64_t (&v)[4][2], const void* p, uint32_t tag, int& it) {
  asm volatile(
    "{.reg .pred q, p0, p1, p2, p3; .reg .b32 u, lo0, lo1, hi, x0, x1, x2, x3;\n"
    "LOOP:\n"
    "mov.b64 {lo0, hi}, %0; mov.b64 {lo1, hi}, %1; lop3.b32 x0, lo0, lo1, %10, 0x7E;\n"
    "mov.b64 {lo0, hi}, %2; mov.b64 {lo1, hi}, %3; lop3.b32 x1, lo0, lo1, %10, 0x7E;\n"
    "mov.b64 {lo0, hi}, %4; mov.b64 {lo1, hi}, %5; lop3.b32 x2, lo0, lo1, %10, 0x7E;\n"
    "mov.b64 {lo0, hi}, %6; mov.b64 {lo1, hi}, %7; lop3.b32 x3, lo0, lo1, %10, 0x7E;\n"
    "lop3.b32 u, x0, x1, x2, 0xFE; lop3.b32 u, u, x3, 1, 0xA8;\n"
    "setp.ne.u32 q, u, 0; vote.sync.any.pred q, q, 0xffffffff; @!q bra.uni DONE;\n"
    "add.s32 %8, %8, 1; setp.gt.s32 q, %8, 1048576; @q bra.uni DONE;\n"
    "and.b32 u, x0, 1; setp.ne.u32 p0, u, 0;\n"
    "and.b32 u, x1, 1; setp.ne.u32 p1, u, 0;\n"
    "and.b32 u, x2, 1; setp.ne.u32 p2, u, 0;\n"
    "and.b32 u, x3, 1; setp.ne.u32 p3, u, 0;\n"
    "@p0 ld.relaxed.gpu.global.v2.b64 {%0, %1}, [%9+0];\n"
    "@p1 ld.relaxed.gpu.global.v2.b64 {%2, %3}, [%9+512];\n"
    "@p2 ld.relaxed.gpu.global.v2.b64 {%4, %5}, [%9+1024];\n"
    "@p3 ld.relaxed.gpu.global.v2.b64 {%6, %7}, [%9+1536];\n"
    "bra.uni LOOP;\n"
    "DONE: }\n"
    : "+l"(v[0][0]), "+l"(v[0][1]), "+l"(v[1][0]), "+l"(v[1][1]), "+l"(v[2][0]), "+l"(v[2][1]), "+l"(v[3][0]), "+l"(v[3][1]), "+r"(it) : "l"(p), "r"(tag) : "memory");
}

__device__ __forceinline__ void poll4_1536(uint64_t (&v)[4][2], const void* p, uint32_t tag, int& it) {
  asm volatile(
    "{.reg .pred q, p0, p1, p2, p3; .reg .b32 u, lo0, lo1, hi, x0, x1, x2, x3;\n"
    "LOOP:\n"
    "mov.b64 {lo0, hi}, %0; mov.b64 {lo1, hi}, %1; lop3.b32 x0, lo0, lo1, %10, 0x7E;\n"
    "mov.b64 {lo0, hi}, %2; mov.b64 {lo1, hi}, %3; lop3.b32 x1, lo0, lo1, %10, 0x7E;\n"
    "mov.b64 {lo0, hi}, %4; mov.b64 {lo1, hi}, %5; lop3.b32 x2, lo0, lo1, %10, 0x7E;\n"
    "mov.b64 {lo0, hi}, %6; mov.b64 {lo1, hi}, %7; lop3.b32 x3, lo0, lo1, %10, 0x7E;\n"
    "lop3.b32 u, x0, x1, x2, 0xFE; lop3.b32 u, u, x3, 1, 0xA8;\n"
    "setp.ne.u32 q, u, 0; vote.sync.any.pred q, q, 0xffffffff; @!q bra.uni DONE;\n"
    "add.s32 %8, %8, 1; setp.gt.s32 q, %8, 1048576; @q bra.uni DONE;\n"
    "and.b32 u, x0, 1; setp.ne.u32 p0, u, 0;\n"
    "and.b32 u, x1, 1; setp.ne.u32 p1, u, 0;\n"
    "and.b32 u, x2, 1; setp.ne.u32 p2, u, 0;\n"
    "and.b32 u, x3, 1; setp.ne.u32 p3, u, 0;\n"
    "@p0 ld.relaxed.gpu.global.v2.b64 {%0, %1}, [%9+0];\n"
    "@p1 ld.relaxed.gpu.global.v2.b64 {%2, %3}, [%9+1536];\n"
    "@p2 ld.relaxed.gpu.global.v2.b64 {%4, %5}, [%9+3072];\n"
    "@p3 ld.relaxed.gpu.global.v2.b64 {%6, %7}, [%9+4608];\n"
    "bra.uni LOOP;\n"
    "DONE: }\n"
    : "+l"(v[0][0]), "+l"(v[0][1]), "+l"(v[1][0]), "+l"(v[1][1]), "+l"(v[2][0]), "+l"(v[2][1]), "+l"(v[3][0]), "+l"(v[3][1]), "+r"(it) : "l"(p), "r"(tag) : "memory");
}

__device__ __forceinline__ void poll8_qk(uint64_t (&v)[8][2], const void* p, uint32_t tag, int& it) {
  asm volatile(
    "{.reg .pred q, p0, p1, p2, p3, p4, p5, p6, p7; .reg .b32 u, lo0, lo1, hi, x0, x1, x2, x3, x4, x5, x6, x7;\n"
    "LOOP:\n"
    "mov.b64 {lo0, hi}, %0; mov.b64 {lo1, hi}, %1; lop3.b32 x0, lo0, lo1, %18, 0x7E;\n"
    "mov.b64 {lo0, hi}, %2; mov.b64 {lo1, hi}, %3; lop3.b32 x1, lo0, lo1, %18, 0x7E;\n"
    "mov.b64 {lo0, hi}, %4; mov.b64 {lo1, hi}, %5; lop3.b32 x2, lo0, lo1, %18, 0x7E;\n"
    "mov.b64 {lo0, hi}, %6; mov.b64 {lo1, hi}, %7; lop3.b32 x3, lo0, lo1, %18, 0x7E;\n"
    "mov.b64 {lo0, hi}, %8; mov.b64 {lo1, hi}, %9; lop3.b32 x4, lo0, lo1, %18, 0x7E;\n"
    "mov.b64 {lo0, hi}, %10; mov.b64 {lo1, hi}, %11; lop3.b32 x5, lo0, lo1, %18, 0x7E;\n"
    "mov.b64 {lo0, hi}, %12; mov.b64 {lo1, hi}, %13; lop3.b32 x6, lo0, lo1, %18, 0x7E;\n"
    "mov.b64 {lo0, hi}, %14; mov.b64 {lo1, hi}, %15; lop3.b32 x7, lo0, lo1, %18, 0x7E;\n"
    "lop3.b32 u, x0, x1, x2, 0xFE; lop3.b32 hi, x3, x4, x5, 0xFE; lop3.b32 u, u, x6, x7, 0xFE; lop3.b32 u, u, hi, 1, 0xA8;\n"
    "setp.ne.u32 q, u, 0; vote.sync.any.pred q, q, 0xffffffff; @!q bra.uni DONE;\n"
    "add.s32 %16, %16, 1; setp.gt.s32 q, %16, 1048576; @q bra.uni DONE;\n"
    "and.b32 u, x0, 1; setp.ne.u32 p0, u, 0;\n"
    "and.b32 u, x1, 1; setp.ne.u32 p1, u, 0;\n"
    "and.b32 u, x2, 1; setp.ne.u32 p2, u, 0;\n"
    "and.b32 u, x3, 1; setp.ne.u32 p3, u, 0;\n"
    "and.b32 u, x4, 1; setp.ne.u32 p4, u, 0;\n"
    "and.b32 u, x5, 1; setp.ne.u32 p5, u, 0;\n"
    "and.b32 u, x6, 1; setp.ne.u32 p6, u, 0;\n"
    "and.b32 u, x7, 1; setp.ne.u32 p7, u, 0;\n"
    "@p0 ld.relaxed.gpu.global.v2.b64 {%0, %1}, [%17+0];\n"
    "@p1 ld.relaxed.gpu.global.v2.b64 {%2, %3}, [%17+1536];\n"
    "@p2 ld.relaxed.gpu.global.v2.b64 {%4, %5}, [%17+3072];\n"
    "@p3 ld.relaxed.gpu.global.v2.b64 {%6, %7}, [%17+4608];\n"
    "@p4 ld.relaxed.gpu.global.v2.b64 {%8, %9}, [%17+512];\n"
    "@p5 ld.relaxed.gpu.global.v2.b64 {%10, %11}, [%17+2048];\n"
    "@p6 ld.relaxed.gpu.global.v2.b64 {%12, %13}, [%17+3584];\n"
    "@p7 ld.relaxed.gpu.global.v2.b64 {%14, %15}, [%17+5120];\n"
    "bra.uni LOOP;\n"
    "DONE: }\n"
    : "+l"(v[0][0]), "+l"(v[0][1]), "+l"(v[1][0]), "+l"(v[1][1]), "+l"(v[2][0]), "+l"(v[2][1]), "+l"(v[3][0]), "+l"(v[3][1]), "+l"(v[4][0]), "+l"(v[4][1]), "+l"(v[5][0]), "+l"(v[5][1]), "+l"(v[6][0]), "+l"(v[6][1]), "+l"(v[7][0]), "+l"(v[7][1]), "+r"(it) : "l"(p), "r"(tag) : "memory");
}

__device__ __forceinline__ void poll8_b128(uint64_t (&v)[8][2], const void* p, uint32_t tag, int& it) {
  asm volatile(
    "{.reg .pred q, p0, p1, p2, p3; .reg .b32 u, lo0, lo1, hi, x0, x1, x2, x3; .reg .b128 t;\n"
    "LOOP:\n"
    "mov.b64 {lo0, hi}, %0; mov.b64 {lo1, hi}, %2; lop3.b32 x0, lo0, lo1, %18, 0x7E;\n"
    "mov.b64 {lo0, hi}, %4; mov.b64 {lo1, hi}, %6; lop3.b32 x1, lo0, lo1, %18, 0x7E;\n"
    "mov.b64 {lo0, hi}, %8; mov.b64 {lo1, hi}, %10; lop3.b32 x2, lo0, lo1, %18, 0x7E;\n"
    "mov.b64 {lo0, hi}, %12; mov.b64 {lo1, hi}, %14; lop3.b32 x3, lo0, lo1, %18, 0x7E;\n"
    "lop3.b32 u, x0, x1, x2, 0xFE; lop3.b32 u, u, x3, 1, 0xA8;\n"
    "setp.ne.u32 q, u, 0; vote.sync.any.pred q, q, 0xffffffff; @!q bra.uni DONE;\n"
    "add.s32 %16, %16, 1; setp.gt.s32 q, %16, 1048576; @q bra.uni DONE;\n"
    "and.b32 u, x0, 1; setp.ne.u32 p0, u, 0;\n"
    "and.b32 u, x1, 1; setp.ne.u32 p1, u, 0;\n"
    "and.b32 u, x2, 1; setp.ne.u32 p2, u, 0;\n"
    "and.b32 u, x3, 1; setp.ne.u32 p3, u, 0;\n"
    "mov.b128 t, {%0, %1}; @p0 ld.relaxed.gpu.global.b128 t, [%17+0]; mov.b128 {%0, %1}, t;\n"
    "mov.b128 t, {%2, %3}; @p0 ld.relaxed.gpu.global.b128 t, [%17+512]; mov.b128 {%2, %3}, t;\n"
    "mov.b128 t, {%4, %5}; @p1 ld.relaxed.gpu.global.b128 t, [%17+1024]; mov.b128 {%4, %5}, t;\n"
    "mov.b128 t, {%6, %7}; @p1 ld.relaxed.gpu.global.b128 t, [%17+1536]; mov.b128 {%6, %7}, t;\n"
    "mov.b128 t, {%8, %9}; @p2 ld.relaxed.gpu.global.b128 t, [%17+2048]; mov.b128 {%8, %9}, t;\n"
    "mov.b128 t, {%10, %11}; @p2 ld.relaxed.gpu.global.b128 t, [%17+2560]; mov.b128 {%10, %11}, t;\n"
    "mov.b128 t, {%12, %13}; @p3 ld.relaxed.gpu.global.b128 t, [%17+3072]; mov.b128 {%12, %13}, t;\n"
    "mov.b128 t, {%14, %15}; @p3 ld.relaxed.gpu.global.b128 t, [%17+3584]; mov.b128 {%14, %15}, t;\n"
    "bra.uni LOOP;\n"
    "DONE: }\n"
    : "+l"(v[0][0]), "+l"(v[0][1]), "+l"(v[1][0]), "+l"(v[1][1]), "+l"(v[2][0]), "+l"(v[2][1]), "+l"(v[3][0]), "+l"(v[3][1]), "+l"(v[4][0]), "+l"(v[4][1]), "+l"(v[5][0]), "+l"(v[5][1]), "+l"(v[6][0]), "+l"(v[6][1]), "+l"(v[7][0]), "+l"(v[7][1]), "+r"(it) : "l"(p), "r"(tag) : "memory");
}

__device__ __forceinline__ uint32_t lo32(uint64_t v) { return (uint32_t)v; }
__device__ __forceinline__ uint32_t hi32(uint64_t v) { return (uint32_t)(v >> 32); }
__device__ __forceinline__ void ldx2(uint64_t (&r)[2], const void* p) { asm volatile("ld.relaxed.gpu.global.v2.b64 {%0, %1}, [%2];" : "=l"(r[0]), "=l"(r[1]) : "l"(p) : "memory"); }
__device__ __forceinline__ void ldxb(uint64_t (&r)[2], const void* p) {
  asm volatile("{.reg .b128 t; ld.relaxed.gpu.global.b128 t, [%2]; mov.b128 {%0, %1}, t;}" : "=l"(r[0]), "=l"(r[1]) : "l"(p) : "memory"); }
__device__ __forceinline__ void lds2(uint64_t (&r)[2], uint32_t a) { asm volatile("ld.shared.v2.b64 {%0, %1}, [%2];" : "=l"(r[0]), "=l"(r[1]) : "r"(a) : "memory"); }
__device__ __forceinline__ void sts2(uint32_t a, const uint64_t (&r)[2]) { asm volatile("st.shared.v2.b64 [%0], {%1, %2};" :: "r"(a), "l"(r[0]), "l"(r[1]) : "memory"); }
__device__ __forceinline__ void mma_b(float (&d)[4], const uint32_t (&a)[4], uint64_t b) { mma16816(d, a[0], a[1], a[2], a[3], lo32(b), hi32(b)); }
__device__ __forceinline__ void mma_bb(float (&d)[4], const uint64_t (&a)[2], uint64_t b) { mma16816(d, lo32(a[0]), hi32(a[0]), lo32(a[1]), hi32(a[1]), lo32(b), hi32(b)); }
__device__ __forceinline__ void ldsm4q(uint64_t (&r)[2], uint32_t a) {
  asm volatile("{.reg .b32 a,b,c,d; ldmatrix.sync.aligned.m8n8.x4.shared.b16 {a,b,c,d}, [%2]; mov.b64 %0, {a,b}; mov.b64 %1, {c,d};}" : "=l"(r[0]), "=l"(r[1]) : "r"(a) : "memory"); }
__device__ __forceinline__ void mbar_spin(uint32_t bar, uint32_t par, int& it) {
  asm volatile("{.reg .pred p;\nLOOP: mbarrier.try_wait.parity.shared::cta.b64 p, [%1], %2; @p bra.uni DONE;\n"
               "add.s32 %0, %0, 1; setp.le.s32 p, %0, 1048576; @p bra.uni LOOP;\nDONE: }" : "+r"(it) : "r"(bar), "r"(par) : "memory"); }
__device__ __forceinline__ void delay_until(unsigned t) {
  asm volatile("{.reg .pred p; .reg .b64 c; .reg .b32 lo, hi;\nLOOP: mov.u64 c, %%clock64; mov.b64 {lo, hi}, c; sub.s32 lo, lo, %0; setp.lt.s32 p, lo, 0; @p bra.uni LOOP;}" :: "r"(t) : "memory"); }
__device__ __forceinline__ void zero(float (&c)[4][4]) {
#pragma unroll
  for (int i = 0; i < 4; i++) c[i][0] = c[i][1] = c[i][2] = c[i][3] = 0.f;
}

template <int W4>
__device__ __forceinline__ void qk_gemm(const uint32_t (&w)[32][4], uint64_t (&own)[4][2], uint32_t a, float (&c)[4][4], uint32_t bar, uint32_t par, int& it) {
#pragma unroll
  for (int i = 0; i < 4; i++) {
    mma_b(c[2 * (i & 1)], w[8 * W4 + 2 * i], own[i][0]);
    mma_b(c[2 * (i & 1) + 1], w[8 * W4 + 2 * i + 1], own[i][1]);
  }
  mbar_spin(bar, par, it);
  uint64_t b[12][2];
#pragma unroll
  for (int i = 0; i < 12; i++) lds2(b[i], a + (((W4 + 1 + (i >> 2)) & 3) - W4) * 512 + (i & 3) * 4096);
#pragma unroll
  for (int i = 0; i < 12; i++) {
    const int p = (4 * W4 + 4 + i) & 15;
    mma_b(c[2 * (i & 1)], w[2 * p], b[i][0]);
    mma_b(c[2 * (i & 1) + 1], w[2 * p + 1], b[i][1]);
  }
}

__global__ void
__launch_bounds__(256, 1)
rec_kernel(const __grid_constant__ RecMaps maps, const bf16* __restrict__ Wo, const bf16* __restrict__ mem0) {
  extern __shared__ __align__(1024) uint8_t smem_raw[];
  const uint32_t sb = (smem_u32(smem_raw) + 1023) & ~1023u;
  if (blockIdx.x >= 128) {
    fft_cols(sb, blockIdx.x - 128, 4);
    grid_arrive(&g_x.ctr[0]); grid_wait(&g_x.ctr[0], 4);
    fft_rows_inv(&maps.fo, sb, blockIdx.x - 128, 4);
    return;
  }
  const int tid = threadIdx.x, warp = uni(tid >> 5), lane = tid & 31, wg = warp >> 2, w4 = warp & 3, g = lane >> 2, t = lane & 3;
  const int h = blockIdx.x >> 2, j = blockIdx.x & 3;
  uint32_t wqk[32][4];
  uint32_t wsw[16][4];
  uint64_t own[4][2];
  int it = 0;

  if (tid == 0) {
    mbar_init(sb + R_BAR, 1); mbar_init(sb + R_BAR + 8, 1); mbar_init(sb + R_BAR + 16, 1);
    mbar_init(sb + R_BAR + 24, 128); mbar_init(sb + R_BAR + 32, 128);
    asm volatile("fence.mbarrier_init.release.cluster;" ::: "memory");
    mbar_expect_tx(sb + R_BAR + 16, 3 * 65536);
    for (int i = 0; i < 4; i++) {
      tma2d(sb + R_WO + i * 16384, &maps.wq, h * DH + 32 * j, i * 256, sb + R_BAR + 16);
      tma2d(sb + R_MEM + i * 16384, &maps.wk, h * DH + 32 * j, i * 256, sb + R_BAR + 16);
    }
    for (int i = 0; i < 4; i++) tma2d(sb + R_WV + i * 16384, &maps.wv, h * DH + 32 * j, i * 256, sb + R_BAR + 16);
  }
  {
    const bf16* wp = Wo + (size_t)(h * DH + 2 * t) * DM + 256 * j + 32 * warp + 16 * (g & 1) + 2 * (g >> 1);
#pragma unroll
    for (int ks = 0; ks < 8; ks++)
#pragma unroll
      for (int u = 0; u < 2; u++)
#pragma unroll
        for (int i = 0; i < 2; i++) {
          const uint32_t r0 = __ldg(reinterpret_cast<const uint32_t*>(wp + (size_t)(16 * ks + 8 * u) * DM + 8 * i));
          const uint32_t r1 = __ldg(reinterpret_cast<const uint32_t*>(wp + (size_t)(16 * ks + 8 * u + 1) * DM + 8 * i));
          wsw[2 * ks + i][2 * u] = __byte_perm(r0, r1, 0x5410); wsw[2 * ks + i][2 * u + 1] = __byte_perm(r0, r1, 0x7632);
        }
#pragma unroll
    for (int i = 0; i < 4; i++)
#pragma unroll
      for (int r = 0; r < 2; r++) {
        const uint32_t* mp = reinterpret_cast<const uint32_t*>(mem0 + g * DM + 128 * warp + 32 * i + 16 * r + 2 * t);
        own[i][r] = (uint64_t)__ldg(mp) | ((uint64_t)__ldg(mp + 4) << 32);
      }
  }
  __syncthreads();
  mbar_spin(sb + R_BAR + 16, 0, it);
  const int lrow = (lane & 7) + ((lane >> 4) << 3), lhi = (lane >> 3) & 1;
  {
    const int chunk = w4 < 2 ? w4 + 2 * lhi : 2 * (w4 & 1) + lhi;
    const uint32_t a = sb + (w4 < 2 ? R_WO : R_MEM) + wg * 32768 + lrow * 64 + ((chunk ^ ((lrow >> 1) & 3)) << 4);
#pragma unroll
    for (int ks = 0; ks < 32; ks++) ldsm4t(wqk[ks], a + ks * 1024);
  }
  __syncthreads();
  const uint32_t L16 = pin(lane * 16);
  const uint32_t uT = uni(sb + warp * 512);
#pragma unroll
  for (int i = 0; i < 16; i++) sts128(uT + L16 + R_WO + i * 4096, wsw[i][0], wsw[i][1], wsw[i][2], wsw[i][3]);
  if (tid == 224) {
    fence_async();
    rec_issue_kv(maps, sb + R_KV, sb + R_BAR, 0, h, j);
    tma4d_pf(&maps.kv, SEG, 2 * h, 1); tma4d_pf(&maps.q, SEG + 8 * j, 2 * h, 0);
  }
  __syncwarp();
  auto load_wv = [&]() {
    const uint32_t a = sb + R_WV + warp * 8192 + lrow * 64 + ((lhi ^ ((lrow >> 1) & 3)) << 4);
#pragma unroll
    for (int i = 0; i < 16; i++) ldsm4t(wsw[i], (a ^ ((i & 1) << 5)) + (i >> 1) * 1024);
  };
  auto load_wo = [&]() {
#pragma unroll
    for (int i = 0; i < 16; i++) lds128(wsw[i], uT + L16 + R_WO + i * 4096);
  };
  load_wv();

  const float sc = 0.08838834764831845f * 1.4426950408889634f;
  uint8_t* const xb = reinterpret_cast<uint8_t*>(&g_x);
  uint8_t* const xa = xb + uni(h * 4 * 1536);
  const uint32_t uAw = uni(j * 1536 + (w4 >> 1) * 512 + (w4 & 1) * 8 + wg * 512);
  const uint32_t uBar = uni(sb + R_BAR + 24 + 8 * wg);
  const uint32_t bofs = pin(offsetof(Xchg, B) + ((4 * warp + t) * 4 + j) * 4096 + (h >> 2) * 512 + (g >> 1) * 128 + (h & 3) * 32 + (g & 1) * 16);

#pragma unroll 1
  for (int s = 0; s < NSEG; s++) {
    const uint32_t tag = (s + 1) & 1, T = tag << 16;
    const uint32_t kv = sb + R_KV + (s & 1) * R_KVSZ;
    TS(0);
#pragma unroll
    for (int i = 0; i < 4; i++) sts2(uT + L16 + R_MEM + i * 4096, own[i]);
    mbar_arrive(uBar);
    float c[4][4];
    zero(c);
#pragma unroll
    for (int i = 0; i < 16; i++) mma_b(c[i & 3], wsw[i], own[i >> 2][(i >> 1) & 1]);
#pragma unroll
    for (int i = 0; i < 2; i++)
      sts128(uT + L16 + R_REDV + i * 4096, __float_as_uint(c[i][0] + c[i + 2][0]), __float_as_uint(c[i][1] + c[i + 2][1]),
             __float_as_uint(c[i][2] + c[i + 2][2]), __float_as_uint(c[i][3] + c[i + 2][3]));
    if (warp < 6) bar_arrive(4, 256);
    TS(1);
    zero(c);
    {
      const uint32_t a = uT + L16 + R_MEM;
      if (w4 < 2) { if (w4 == 0) qk_gemm<0>(wqk, own, a, c, uBar, s & 1, it); else qk_gemm<1>(wqk, own, a, c, uBar, s & 1, it); }
      else { if (w4 == 2) qk_gemm<2>(wqk, own, a, c, uBar, s & 1, it); else qk_gemm<3>(wqk, own, a, c, uBar, s & 1, it); }
    }
#pragma unroll
    for (int i = 0; i < 4; i++) c[0][i] = (c[0][i] + c[1][i]) + (c[2][i] + c[3][i]);

    auto load_v = [&](uint32_t (&vf)[4][4]) {
      const uint32_t va = kv + 8192 + (w4 >> 1) * 4096 + lrow * 128 + (((4 * (w4 & 1) + lhi) ^ (lane & 7)) << 4);
#pragma unroll
      for (int i = 0; i < 4; i++) ldsm4t(vf[i], (va ^ ((i & 1) << 5)) + (i >> 1) * 2048);
    };
    auto attend = [&](float (&o)[2][4], const uint32_t (&vf)[4][4], const uint64_t (&vm)[1][2], uint32_t sa, bool isx) {
      float2 sv[5];
#pragma unroll
      for (int i = 0; i < 5; i++) sv[i] = lds64f(sa + i * 256);
      if (isx) {
#pragma unroll
        for (int i = 0; i < 4; i++) {
          if (8 * i + 2 * t > 8 * j + g) sv[i].x = -INFINITY;
          if (8 * i + 2 * t + 1 > 8 * j + g) sv[i].y = -INFINITY;
        }
      }
      float m = fmaxf(fmaxf(fmaxf(sv[0].x, sv[0].y), fmaxf(sv[1].x, sv[1].y)), fmaxf(fmaxf(sv[2].x, sv[2].y), fmaxf(sv[3].x, sv[3].y)));
      m = fmaxf(m, fmaxf(sv[4].x, sv[4].y));
      m = fmaxf(m, __shfl_xor_sync(0xffffffffu, m, 1));
      m = fmaxf(m, __shfl_xor_sync(0xffffffffu, m, 2));
      const float ms = -m * sc;
#pragma unroll
      for (int i = 4; i >= 0; i--) { sv[i].x = ex2(fmaf(sv[i].x, sc, ms)); sv[i].y = ex2(fmaf(sv[i].y, sc, ms)); }
      float sum = ((sv[0].x + sv[0].y) + (sv[1].x + sv[1].y)) + ((sv[2].x + sv[2].y) + (sv[3].x + sv[3].y) + (sv[4].x + sv[4].y));
      float r = 1.f;
      if (isx) { sum += __shfl_xor_sync(0xffffffffu, sum, 1); sum += __shfl_xor_sync(0xffffffffu, sum, 2); r = rcp(sum); }
      uint32_t p[5];
#pragma unroll
      for (int i = 0; i < 5; i++) p[i] = isx ? pack2(sv[i].x * r, sv[i].y * r) : pack2(sv[i].x, sv[i].y);
      mma1688(o[0], lo32(vm[0][0]), hi32(vm[0][0]), p[4]);
      mma1688(o[1], lo32(vm[0][1]), hi32(vm[0][1]), p[4]);
#pragma unroll
      for (int k = 1; k >= 0; k--) {
        mma_a(o[0], vf[2 * k], p[2 * k], p[2 * k + 1]);
        mma_a(o[1], vf[2 * k + 1], p[2 * k], p[2 * k + 1]);
      }
      if (!isx) sts32f(sb + R_SUM + (L16 >> 2), sum);
    };
    uint64_t vm[1][2];
    if (wg == 0) {
      TS(2);
      bar_sync(8 + w4, 64);
      const float4 o4 = lds128f(uT + L16 + R_RED);
      const uint32_t r0 = movm(pack2(c[0][0] + o4.x, c[0][1] + o4.y)), r1 = movm(pack2(c[0][2] + o4.z, c[0][3] + o4.w));
      stx64(xa + uAw + L16, (r0 & ~1u) | tag, r1);
      const unsigned tpub = clk();
      TS(3);
      load_wo();
      mbar_spin(sb + R_BAR + 8 * (s & 1), (s >> 1) & 1, it);
      uint32_t vf[4][4];
      load_v(vf);
      const uint32_t sa = pin(sb + R_S + (L16 >> 1));
      const uint8_t* vsrc = xa + w4 * 1536 + 1024 + L16;
      delay_until(tpub + DLY_V);
      ldx2(vm[0], vsrc);
      poll1(vm, vsrc, tag, it);
      TS(5);
      bar_sync(5, 256);
      float o[2][4] = {{0, 0, 0, 0}, {0, 0, 0, 0}};
      attend(o, vf, vm, sa, false);
      stsm4t(uT + L16 + R_O, pack2(o[0][0], o[0][1]), pack2(o[0][2], o[0][3]), pack2(o[1][0], o[1][1]), pack2(o[1][2], o[1][3]));
    } else {
      sts128(uT + L16 + R_RED - 2048, __float_as_uint(c[0][0]), __float_as_uint(c[0][1]), __float_as_uint(c[0][2]), __float_as_uint(c[0][3]));
      bar_arrive(8 + w4, 64);
      const unsigned tpub = clk();
      TS(2);
      const uint8_t* asrc = xa + L16;
      const uint32_t qa = kv + 16384 + (lane & 7) * 128 + (((2 * lhi + (lane >> 4)) ^ (lane & 7)) << 4);
      if (warp < 6) {
        mbar_spin(sb + R_BAR + 8 * (s & 1), (s >> 1) & 1, it);
        uint32_t kf[8][4];
        uint64_t q[4][2];
        const uint32_t ka = kv + (16 * w4 + (lane & 15)) * 128 + (((2 * (lane >> 4)) ^ (lane & 7)) << 4);
#pragma unroll
        for (int i = 0; i < 8; i++) ldsm4(kf[i], (ka ^ ((4 * ((i >> 1) & 1) + (i & 1)) << 4)) + (i >> 2) * 4096);
#pragma unroll
        for (int i = 0; i < 4; i++) ldsm4q(q[i], (qa ^ ((i & 1) << 6)) + (i >> 1) * 1024);
        const uint32_t sa = pin(sb + R_S + w4 * 512 + t * 64 + g * 4);
        zero(c);
#pragma unroll
        for (int i = 0; i < 8; i++) mma_b(c[i & 3], kf[i], q[i >> 1][i & 1]);
        delay_until(tpub + DLY_A);
        TS(4);
#pragma unroll
        for (int i = 0; i < 4; i++) ldx2(q[i], asrc + i * 1536);
#pragma unroll
        for (int i = 0; i < 4; i++) sts32f(sa + 1280 + (i & 1) * 32 + (i >> 1) * 256, (c[0][i] + c[1][i]) + (c[2][i] + c[3][i]));
        poll4_1536(q, asrc, tag, it);
        TS(5);
        zero(c);
#pragma unroll
        for (int i = 0; i < 8; i++) mma_b(c[i & 3], kf[i], q[i >> 1][i & 1]);
#pragma unroll
        for (int i = 0; i < 4; i++) sts32f(sa + (i & 1) * 32 + (i >> 1) * 256, (c[0][i] + c[1][i]) + (c[2][i] + c[3][i]));
        bar_sync(5, 256);
      } else {
        const uint32_t r = sb + R_REDV + (warp & 1) * 4096 + L16;
        bar_sync(4, 256);
        float4 a[8];
#pragma unroll
        for (int i = 0; i < 8; i++) a[i] = lds128f(r + i * 512);
#pragma unroll
        for (int k = 4; k > 0; k >>= 1)
#pragma unroll
          for (int i = 0; i < k; i++) { a[i].x += a[i + k].x; a[i].y += a[i + k].y; a[i].z += a[i + k].z; a[i].w += a[i + k].w; }
        stx64(xa + uAw + L16, pack2_tag(a[0].x, a[0].y, T), pack2(a[0].z, a[0].w));
        TS(3);
        if (warp == 6) {
          uint64_t qk[8][2], q[4][2];
          const uint32_t sa = pin(sb + R_S + 1024 + t * 64 + g * 4);
          delay_until(tpub + DLY_A);
          TS(4);
#pragma unroll
          for (int i = 0; i < 8; i++) ldx2(qk[i], asrc + (i & 3) * 1536 + (i >> 2) * 512);
          mbar_spin(sb + R_BAR + 8 * (s & 1), (s >> 1) & 1, it);
#pragma unroll
          for (int i = 0; i < 4; i++) ldsm4q(q[i], (qa ^ ((i & 1) << 6)) + (i >> 1) * 1024);
          poll8_qk(qk, asrc, tag, it);
          TS(5);
          zero(c);
#pragma unroll
          for (int i = 0; i < 8; i++) mma_bb(c[i & 3], qk[4 + (i >> 1)], qk[i >> 1][i & 1]);
#pragma unroll
          for (int i = 0; i < 2; i++) sts32f(sa + i * 32, (c[0][i] + c[1][i + 2]) + (c[2][i] + c[3][i + 2]));
          bar_arrive(5, 256);
          zero(c);
#pragma unroll
          for (int i = 0; i < 8; i++) mma_bb(c[i & 3], qk[4 + (i >> 1)], q[i >> 1][i & 1]);
#pragma unroll
          for (int i = 0; i < 2; i++) sts32f(sa + 1280 + i * 32, (c[0][i] + c[1][i + 2]) + (c[2][i] + c[3][i + 2]));
        } else {
          if (lane == 0) {
            if (s + 2 < NSEG) { tma4d_pf(&maps.kv, (s + 2) * SEG, 2 * h, 1); tma4d_pf(&maps.q, (s + 2) * SEG + 8 * j, 2 * h, 0); }
            fence_async();
          }
          __syncwarp();
          bar_sync(5, 256);
          if (lane == 0 && s + 1 < NSEG) rec_issue_kv(maps, sb + R_KV + ((s + 1) & 1) * R_KVSZ, sb + R_BAR + 8 * ((s + 1) & 1), s + 1, h, j);
          __syncwarp();
        }
      }
      TS(6);
      const uint8_t* vsrc = asrc + w4 * 1536 + 1024;
      ldx2(vm[0], vsrc);
      load_wo();
      poll1(vm, vsrc, tag, it);
    }
    TS(7);
    bar_sync(6, 256);
    if (s + 1 < NSEG) {
      uint64_t b[4][2];
#pragma unroll
      for (int i = 0; i < 4; i++) ldsm4q(b[i], sb + R_O + i * 512 + L16);
      const float4 s0 = lds128f(sb + R_SUM + ((L16 << 1) & 96)), s1 = lds128f(sb + R_SUM + 16 + ((L16 << 1) & 96));
      zero(c);
#pragma unroll
      for (int i = 0; i < 16; i++) mma_b(c[i & 3], wsw[i], b[i >> 2][(i >> 1) & 1]);
      const float r0 = rcp((s0.x + s0.y) + (s0.z + s0.w)), r1 = rcp((s1.x + s1.y) + (s1.z + s1.w));
      stx128(xb + bofs, pack2_tag((c[0][0] + c[2][0]) * r0, (c[0][2] + c[2][2]) * r0, T), pack2((c[1][0] + c[3][0]) * r0, (c[1][2] + c[3][2]) * r0),
             pack2((c[0][1] + c[2][1]) * r1, (c[0][3] + c[2][3]) * r1), pack2((c[1][1] + c[3][1]) * r1, (c[1][3] + c[3][3]) * r1));
    }
    const unsigned tb = clk();
    TS(9);
    if (wg == 1) {
      float o[2][4] = {{0, 0, 0, 0}, {0, 0, 0, 0}};
      uint32_t vf[4][4];
      load_v(vf);
      attend(o, vf, vm, sb + R_S + 1280 + lane * 8, true);
      const uint32_t ox = sb + R_OX + w4 * 640;
      stsm4t(ox + (lane & 7) * 80 + (lane >> 3) * 16, pack2(o[0][0], o[0][1]), pack2(o[0][2], o[0][3]), pack2(o[1][0], o[1][1]), pack2(o[1][2], o[1][3]));
      __syncwarp();
      uint32_t v[4]; lds128(v, ox + g * 80 + t * 16);
      *reinterpret_cast<uint4*>(&g_ox[(size_t)(
      s * SEG +
      8 * j + g) * HD + h * DH + 32 * w4 + 8 * t]) = make_uint4(v[0], v[1], v[2], v[3]);
    }
    if (s + 1 < NSEG) {
      if (warp == 0) {
        const uint8_t* src = xb + offsetof(Xchg, B) + blockIdx.x * 4096 + (g >> 1) * 128 + t * 32 + (g & 1) * 16;
        const uint32_t cofs = pin(offsetof(Xchg, C) + (32 * j + h) * 128 + t * 64 + g * 8);
        const uint64_t bsel = (uint64_t)pin(g == 0 ? 0x00003F80u : g == 1 ? 0x3F800000u : 0u) | ((uint64_t)pin(g == 2 ? 0x00003F80u : g == 3 ? 0x3F800000u : 0u) << 32);
        uint64_t v[8][2];
        delay_until(tb + DLY_B);
        TS(8);
#pragma unroll
        for (int i = 0; i < 8; i++) ldxb(v[i], src + i * 512);
        poll8_b128(v, src, tag, it);
        TS(10);
        zero(c);
#pragma unroll
        for (int i = 0; i < 8; i++) mma_bb(c[i & 3], v[i], bsel);
#pragma unroll
        for (int i = 0; i < 4; i++) c[0][i] = (c[0][i] + c[1][i]) + (c[2][i] + c[3][i]);
        if (!(L16 & 32)) stx64(xb + cofs, pack2_tag(c[0][0], c[0][1], T), pack2(c[0][2], c[0][3]));
        sts32f(sb + R_BAR + 48, __uint_as_float(clk()));
        TS(11);
        bar_arrive(7, 256);
      }
      load_wv();
      if (warp != 0) { TS(11); bar_sync(7, 256); }
      const uint8_t* src = xb + offsetof(Xchg, C) + warp * 2048 + L16;
      uint32_t tc; asm volatile("ld.volatile.shared.u32 %0, [%1];" : "=r"(tc) : "r"(sb + R_BAR + 48) : "memory");
      delay_until(tc + DLY_C);
      TS(12);
#pragma unroll
      for (int i = 0; i < 4; i++) ldx2(own[i], src + i * 512);
      poll4_512(own, src, tag, it);
    }
  }
  if (it > SPIN_LIMIT) g_err = 2;
}

typedef CUresult (*EncodeFn)(CUtensorMap*, CUtensorMapDataType, cuuint32_t, void*, const cuuint64_t*, const cuuint64_t*, const cuuint32_t*,
                             const cuuint32_t*, CUtensorMapInterleave, CUtensorMapSwizzle, CUtensorMapL2promotion, CUtensorMapFloatOOBfill);
static void make_map(EncodeFn fn, CUtensorMap* m, const void* p, uint64_t cols, uint64_t rows, uint64_t pitch, uint32_t bc, uint32_t br, CUtensorMapSwizzle sw) {
  cuuint64_t dims[2] = {cols, rows}, strides[1] = {pitch * 2};
  cuuint32_t box[2] = {bc, br}, es[2] = {1, 1};
  fn(m, CU_TENSOR_MAP_DATA_TYPE_BFLOAT16, 2, const_cast<void*>(p), dims, strides, box, es, CU_TENSOR_MAP_INTERLEAVE_NONE, sw,
     CU_TENSOR_MAP_L2_PROMOTION_L2_256B, CU_TENSOR_MAP_FLOAT_OOB_FILL_NONE);
}

extern "C" void kernel_launch(void* const* d_in, const int* in_sizes, int n_in, void* d_out, int out_size) {
  const bf16* Ax = (const bf16*)d_in[0]; const bf16* mem0 = (const bf16*)d_in[1];
  const bf16* Wq = (const bf16*)d_in[2]; const bf16* Wk = (const bf16*)d_in[3]; const bf16* Wv = (const bf16*)d_in[4];
  const bf16* Wo = (const bf16*)d_in[5];
  const bf16* Bx = (const bf16*)d_in[7]; const bf16* wr = (const bf16*)d_in[8]; const bf16* wi = (const bf16*)d_in[9];
  bf16* out = (bf16*)d_out;

  void* fp = nullptr; cudaDriverEntryPointQueryResult qr;
  cudaGetDriverEntryPoint("cuTensorMapEncodeTiled", &fp, cudaEnableDefault, &qr);
  EncodeFn fn = (EncodeFn)fp;
  void *qkv, *ox;
  cudaGetSymbolAddress(&qkv, g_qkv); cudaGetSymbolAddress(&ox, g_ox);
  const CUtensorMapSwizzle S128 = CU_TENSOR_MAP_SWIZZLE_128B, S64 = CU_TENSOR_MAP_SWIZZLE_64B;

  GemmMaps m1, m3; RecMaps mr;
  make_map(fn, &m1.a, Ax, DM, S_LEN, DM, 64, 128, S128);
  make_map(fn, &m1.b[0], Wq, HD, DM, HD, 64, 64, S128);
  make_map(fn, &m1.b[1], Wk, HD, DM, HD, 64, 64, S128);
  make_map(fn, &m1.b[2], Wv, HD, DM, HD, 64, 64, S128);
  make_map(fn, &m1.c, qkv, 3 * HD, S_LEN, 3 * HD, 64, 64, S128);
  make_map(fn, &m3.a, ox, HD, S_LEN, HD, 64, 128, S128);
  make_map(fn, &m3.b[0], Wo, DM, HD, DM, 64, 64, S128);
  m3.b[1] = m3.b[0]; m3.b[2] = m3.b[0];
  make_map(fn, &m3.c, out, DM, S_LEN, 2 * DM, 64, 64, S128);
  make_map(fn, &mr.wq, Wq, HD, DM, HD, 32, 256, S64);
  make_map(fn, &mr.wk, Wk, HD, DM, HD, 32, 256, S64);
  make_map(fn, &mr.wv, Wv, HD, DM, HD, 32, 256, S64);
  for (int i = 0; i < 2; i++) {
    cuuint64_t dims[4] = {64, S_LEN, 2 * NH, 3}, strides[3] = {3 * HD * 2, 128, HD * 2};
    cuuint32_t box[4] = {64, i ? 8u : 32u, 2, i ? 1u : 2u}, es[4] = {1, 1, 1, 1};
    fn(i ? &mr.q : &mr.kv, CU_TENSOR_MAP_DATA_TYPE_BFLOAT16, 4, qkv, dims, strides, box, es, CU_TENSOR_MAP_INTERLEAVE_NONE, S128,
       CU_TENSOR_MAP_L2_PROMOTION_L2_256B, CU_TENSOR_MAP_FLOAT_OOB_FILL_NONE);
  }

  {
    cuuint64_t dims[3] = {64, 16, S_LEN}, strides[2] = {128, 2 * DM * 2};
    cuuint32_t box[3] = {64, 16, 2}, es[3] = {1, 1, 1};
    fn(&mr.fo, CU_TENSOR_MAP_DATA_TYPE_BFLOAT16, 3, out + DM, dims, strides, box, es, CU_TENSOR_MAP_INTERLEAVE_NONE, S128,
       CU_TENSOR_MAP_L2_PROMOTION_NONE, CU_TENSOR_MAP_FLOAT_OOB_FILL_NONE);
  }
  constexpr int SM1 = 4 * 49152 + 32768 + 256 + 1024, SM3 = 6 * 32768 + 32768 + 256 + 1024;
  cudaFuncSetAttribute(gemm_kernel<256, 4>, cudaFuncAttributeMaxDynamicSharedMemorySize, SM1);
  cudaFuncSetAttribute(gemm_kernel<128, 6>, cudaFuncAttributeMaxDynamicSharedMemorySize, SM3);
  cudaFuncSetAttribute(rec_kernel, cudaFuncAttributeMaxDynamicSharedMemorySize, R_TOTAL);

  cudaStream_t st = cudaStreamPerThread;
  cudaFuncSetAttribute(fft_pre_kernel, cudaFuncAttributeMaxDynamicSharedMemorySize, F_SMEM);
  fft_pre_kernel<<<128, 256, F_SMEM, st>>>(Bx, wr, wi);
  gemm_kernel<256, 4><<<132, 384, SM1, st>>>(m1, 16, 48, 16, 16, 1);
  rec_kernel<<<RECG, 256, R_TOTAL, st>>>(mr, Wo, mem0);
  gemm_kernel<128, 6><<<128, 384, SM3, st>>>(m3, 16, 8, 64, 8, 0);
}
```

```cpp
#include <cuda_runtime.h>
#include <cuda_bf16.h>
#include <cuda.h>
#include <stdint.h>
#include <stddef.h>
#include <type_traits>

typedef __nv_bfloat16 bf16;

constexpr int S_LEN = 2048, DM = 1024, NH = 32, DH = 128, MEM = 8, SEG = 32, NSEG = 64;
constexpr int HD = NH * DH;
constexpr int SPIN_LIMIT = 1 << 20;

__device__ __align__(1024) uint4 g_kqv[2][128][512];
__device__ __align__(1024) bf16 g_ox[(size_t)S_LEN * HD];
struct Xchg {
  uint4 A[32][2][2][256];
  uint4 C[4][2][256];
  uint4 B[128][2][256];
  unsigned ctr[64];
};
__device__ __align__(8192) Xchg g_x;
__device__ __align__(1024) uint4 g_y[1024 * 256];
__device__ __align__(1024) uint4 g_wt[513 * 512];
__device__ int g_err;

__device__ __forceinline__ unsigned clk() { unsigned long long c; asm volatile("mov.u64 %0, %%clock64;" : "=l"(c)); return (unsigned)c; }
__device__ __forceinline__ uint32_t smem_u32(const void* p) { return (uint32_t)__cvta_generic_to_shared(p); }
__device__ __forceinline__ void mbar_init(uint32_t bar, int cnt) { asm volatile("mbarrier.init.shared::cta.b64 [%0], %1;" :: "r"(bar), "r"(cnt) : "memory"); }
__device__ __forceinline__ void mbar_expect_tx(uint32_t bar, int bytes) { asm volatile("mbarrier.arrive.expect_tx.shared::cta.b64 _, [%0], %1;" :: "r"(bar), "r"(bytes) : "memory"); }
__device__ __forceinline__ void mbar_arrive(uint32_t bar) { asm volatile("mbarrier.arrive.shared::cta.b64 _, [%0];" :: "r"(bar) : "memory"); }
__device__ __forceinline__ void mbar_arrive_cluster(uint32_t bar, int cta) {
  asm volatile("{.reg .b32 r; mapa.shared::cluster.u32 r, %0, %1; mbarrier.arrive.shared::cluster.b64 _, [r];}" :: "r"(bar), "r"(cta) : "memory"); }
__device__ __forceinline__ bool mbar_try(uint32_t bar, int par) {
  uint32_t ok; asm volatile("{.reg .pred p; mbarrier.try_wait.parity.shared::cta.b64 p, [%1], %2; selp.u32 %0, 1, 0, p;}" : "=r"(ok) : "r"(bar), "r"(par) : "memory"); return ok; }
__device__ __forceinline__ void mbar_wait(uint32_t bar, int par) {
  int it = 0;
  while (!mbar_try(bar, par)) { if (++it > SPIN_LIMIT) { g_err = 1; break; } }
}
__device__ __forceinline__ void tma2d(uint32_t dst, const CUtensorMap* m, int c0, int c1, uint32_t bar) {
  asm volatile("cp.async.bulk.tensor.2d.shared::cluster.global.mbarrier::complete_tx::bytes [%0], [%1, {%3, %4}], [%2];"
    :: "r"(dst), "l"(m), "r"(bar), "r"(c0), "r"(c1) : "memory"); }
__device__ __forceinline__ void tma2d_mc(uint32_t dst, const CUtensorMap* m, int c0, int c1, uint32_t bar, uint16_t mask) {
  asm volatile("cp.async.bulk.tensor.2d.shared::cluster.global.mbarrier::complete_tx::bytes.multicast::cluster [%0], [%1, {%3, %4}], [%2], %5;"
    :: "r"(dst), "l"(m), "r"(bar), "r"(c0), "r"(c1), "h"(mask) : "memory"); }
__device__ __forceinline__ void tma2d_store(const CUtensorMap* m, uint32_t src, int c0, int c1) {
  asm volatile("cp.async.bulk.tensor.2d.global.shared::cta.bulk_group [%0, {%2, %3}], [%1];" :: "l"(m), "r"(src), "r"(c0), "r"(c1) : "memory"); }
__device__ __forceinline__ void fence_async() { asm volatile("fence.proxy.async.shared::cta;" ::: "memory"); }
__device__ __forceinline__ void bar_sync(int id, int n) { asm volatile("bar.sync %0, %1;" :: "r"(id), "r"(n) : "memory"); }
__device__ __forceinline__ void bar_arrive(int id, int n) { asm volatile("bar.arrive %0, %1;" :: "r"(id), "r"(n) : "memory"); }
__device__ __forceinline__ uint32_t pack2(float lo, float hi) { uint32_t r; asm("cvt.rn.bf16x2.f32 %0, %1, %2;" : "=r"(r) : "f"(hi), "f"(lo)); return r; }
__device__ __forceinline__ uint32_t pack2_tag(float lo, float hi, uint32_t T) {
  uint32_t u = ((__float_as_uint(lo) - T + 0x10000u) & 0xFFFE0000u) + T;
  return __byte_perm(u, pack2(0.f, hi), 0x7632); }
__device__ __forceinline__ void ldsm4(uint32_t (&r)[4], uint32_t a) {
  asm volatile("ldmatrix.sync.aligned.m8n8.x4.shared.b16 {%0,%1,%2,%3}, [%4];" : "=r"(r[0]), "=r"(r[1]), "=r"(r[2]), "=r"(r[3]) : "r"(a) : "memory"); }
__device__ __forceinline__ void ldsm4t(uint32_t (&r)[4], uint32_t a) {
  asm volatile("ldmatrix.sync.aligned.m8n8.x4.trans.shared.b16 {%0,%1,%2,%3}, [%4];" : "=r"(r[0]), "=r"(r[1]), "=r"(r[2]), "=r"(r[3]) : "r"(a) : "memory"); }
__device__ __forceinline__ void stsm4(uint32_t a, uint32_t r0, uint32_t r1, uint32_t r2, uint32_t r3) {
  asm volatile("stmatrix.sync.aligned.m8n8.x4.shared.b16 [%0], {%1,%2,%3,%4};" :: "r"(a), "r"(r0), "r"(r1), "r"(r2), "r"(r3) : "memory"); }
__device__ __forceinline__ void stsm4t(uint32_t a, uint32_t r0, uint32_t r1, uint32_t r2, uint32_t r3) {
  asm volatile("stmatrix.sync.aligned.m8n8.x4.trans.shared.b16 [%0], {%1,%2,%3,%4};" :: "r"(a), "r"(r0), "r"(r1), "r"(r2), "r"(r3) : "memory"); }
__device__ __forceinline__ void lds128(uint32_t (&r)[4], uint32_t a) {
  asm volatile("ld.shared.v4.u32 {%0,%1,%2,%3}, [%4];" : "=r"(r[0]), "=r"(r[1]), "=r"(r[2]), "=r"(r[3]) : "r"(a) : "memory"); }
__device__ __forceinline__ float4 lds128f(uint32_t a) { float4 r;
  asm volatile("ld.shared.v4.f32 {%0,%1,%2,%3}, [%4];" : "=f"(r.x), "=f"(r.y), "=f"(r.z), "=f"(r.w) : "r"(a) : "memory"); return r; }
__device__ __forceinline__ float2 lds64f(uint32_t a) { float2 r;
  asm volatile("ld.shared.v2.f32 {%0,%1}, [%2];" : "=f"(r.x), "=f"(r.y) : "r"(a) : "memory"); return r; }
__device__ __forceinline__ void sts128(uint32_t a, uint32_t r0, uint32_t r1, uint32_t r2, uint32_t r3) {
  asm volatile("st.shared.v4.u32 [%0], {%1,%2,%3,%4};" :: "r"(a), "r"(r0), "r"(r1), "r"(r2), "r"(r3) : "memory"); }
__device__ __forceinline__ void sts64f(uint32_t a, float x, float y) { asm volatile("st.shared.v2.f32 [%0], {%1,%2};" :: "r"(a), "f"(x), "f"(y) : "memory"); }
__device__ __forceinline__ void sts32f(uint32_t a, float x) { asm volatile("st.shared.f32 [%0], %1;" :: "r"(a), "f"(x) : "memory"); }
__device__ __forceinline__ void mma16816(float (&d)[4], uint32_t a0, uint32_t a1, uint32_t a2, uint32_t a3, uint32_t b0, uint32_t b1) {
  asm volatile("mma.sync.aligned.m16n8k16.row.col.f32.bf16.bf16.f32 {%0,%1,%2,%3}, {%4,%5,%6,%7}, {%8,%9}, {%0,%1,%2,%3};"
    : "+f"(d[0]), "+f"(d[1]), "+f"(d[2]), "+f"(d[3]) : "r"(a0), "r"(a1), "r"(a2), "r"(a3), "r"(b0), "r"(b1)); }
__device__ __forceinline__ void mma1688(float (&d)[4], uint32_t a0, uint32_t a1, uint32_t b0) {
  asm volatile("mma.sync.aligned.m16n8k8.row.col.f32.bf16.bf16.f32 {%0,%1,%2,%3}, {%4,%5}, {%6}, {%0,%1,%2,%3};"
    : "+f"(d[0]), "+f"(d[1]), "+f"(d[2]), "+f"(d[3]) : "r"(a0), "r"(a1), "r"(b0)); }
__device__ __forceinline__ void ldx128(uint32_t (&r)[4], const void* p) {
  asm volatile("{.reg .b128 t; .reg .b64 a, b; ld.relaxed.gpu.global.b128 t, [%4]; mov.b128 {a, b}, t; mov.b64 {%0,%1}, a; mov.b64 {%2,%3}, b;}"
    : "=r"(r[0]), "=r"(r[1]), "=r"(r[2]), "=r"(r[3]) : "l"(p) : "memory"); }
__device__ __forceinline__ void ldx2x64(uint32_t (&r)[4], const void* p) {
  asm volatile("{.reg .b64 a, b; ld.relaxed.gpu.global.v2.b64 {a, b}, [%4]; mov.b64 {%0,%1}, a; mov.b64 {%2,%3}, b;}"
    : "=r"(r[0]), "=r"(r[1]), "=r"(r[2]), "=r"(r[3]) : "l"(p) : "memory"); }
__device__ __forceinline__ void stx128(void* p, uint32_t r0, uint32_t r1, uint32_t r2, uint32_t r3) {
  asm volatile("{.reg .b128 t; .reg .b64 a, b; mov.b64 a, {%1,%2}; mov.b64 b, {%3,%4}; mov.b128 t, {a, b}; st.relaxed.gpu.global.b128 [%0], t;}"
    :: "l"(p), "r"(r0), "r"(r1), "r"(r2), "r"(r3) : "memory"); }
__device__ __forceinline__ void stx64(void* p, uint32_t r0, uint32_t r1) {
  asm volatile("{.reg .b64 a; mov.b64 a, {%1,%2}; st.relaxed.gpu.global.b64 [%0], a;}" :: "l"(p), "r"(r0), "r"(r1) : "memory"); }
__device__ __forceinline__ uint32_t uni(uint32_t x) { return __shfl_sync(0xffffffffu, x, 0); }
__device__ __forceinline__ uint32_t pin(uint32_t x) { return __shfl_sync(0xffffffffu, x, threadIdx.x); }
__device__ __forceinline__ float ex2(float x) { float r; asm("ex2.approx.ftz.f32 %0, %1;" : "=f"(r) : "f"(x)); return r; }
__device__ __forceinline__ void wg_fence() { asm volatile("wgmma.fence.sync.aligned;" ::: "memory"); }
__device__ __forceinline__ void wg_commit() { asm volatile("wgmma.commit_group.sync.aligned;" ::: "memory"); }
template <int N> __device__ __forceinline__ void wg_wait() { asm volatile("wgmma.wait_group.sync.aligned %0;" :: "n"(N) : "memory"); }

__device__ __forceinline__ void wgmma_ss_n256_tb1(float (&d)[128], uint64_t da, uint64_t db, int sc) {
  asm volatile("{.reg .pred p; setp.ne.b32 p, %130, 0;\n"
    "wgmma.mma_async.sync.aligned.m64n256k16.f32.bf16.bf16 {%0,%1,%2,%3,%4,%5,%6,%7,%8,%9,%10,%11,%12,%13,%14,%15,%16,%17,%18,%19,%20,%21,%22,%23,%24,%25,%26,%27,%28,%29,%30,%31,%32,%33,%34,%35,%36,%37,%38,%39,%40,%41,%42,%43,%44,%45,%46,%47,%48,%49,%50,%51,%52,%53,%54,%55,%56,%57,%58,%59,%60,%61,%62,%63,%64,%65,%66,%67,%68,%69,%70,%71,%72,%73,%74,%75,%76,%77,%78,%79,%80,%81,%82,%83,%84,%85,%86,%87,%88,%89,%90,%91,%92,%93,%94,%95,%96,%97,%98,%99,%100,%101,%102,%103,%104,%105,%106,%107,%108,%109,%110,%111,%112,%113,%114,%115,%116,%117,%118,%119,%120,%121,%122,%123,%124,%125,%126,%127}, %128, %129, p, 1, 1, 0, 1;}\n"
    : "+f"(d[0]),"+f"(d[1]),"+f"(d[2]),"+f"(d[3]),"+f"(d[4]),"+f"(d[5]),"+f"(d[6]),"+f"(d[7]),"+f"(d[8]),"+f"(d[9]),"+f"(d[10]),"+f"(d[11]),"+f"(d[12]),"+f"(d[13]),"+f"(d[14]),"+f"(d[15]),"+f"(d[16]),"+f"(d[17]),"+f"(d[18]),"+f"(d[19]),"+f"(d[20]),"+f"(d[21]),"+f"(d[22]),"+f"(d[23]),"+f"(d[24]),"+f"(d[25]),"+f"(d[26]),"+f"(d[27]),"+f"(d[28]),"+f"(d[29]),"+f"(d[30]),"+f"(d[31]),"+f"(d[32]),"+f"(d[33]),"+f"(d[34]),"+f"(d[35]),"+f"(d[36]),"+f"(d[37]),"+f"(d[38]),"+f"(d[39]),"+f"(d[40]),"+f"(d[41]),"+f"(d[42]),"+f"(d[43]),"+f"(d[44]),"+f"(d[45]),"+f"(d[46]),"+f"(d[47]),"+f"(d[48]),"+f"(d[49]),"+f"(d[50]),"+f"(d[51]),"+f"(d[52]),"+f"(d[53]),"+f"(d[54]),"+f"(d[55]),"+f"(d[56]),"+f"(d[57]),"+f"(d[58]),"+f"(d[59]),"+f"(d[60]),"+f"(d[61]),"+f"(d[62]),"+f"(d[63]),"+f"(d[64]),"+f"(d[65]),"+f"(d[66]),"+f"(d[67]),"+f"(d[68]),"+f"(d[69]),"+f"(d[70]),"+f"(d[71]),"+f"(d[72]),"+f"(d[73]),"+f"(d[74]),"+f"(d[75]),"+f"(d[76]),"+f"(d[77]),"+f"(d[78]),"+f"(d[79]),"+f"(d[80]),"+f"(d[81]),"+f"(d[82]),"+f"(d[83]),"+f"(d[84]),"+f"(d[85]),"+f"(d[86]),"+f"(d[87]),"+f"(d[88]),"+f"(d[89]),"+f"(d[90]),"+f"(d[91]),"+f"(d[92]),"+f"(d[93]),"+f"(d[94]),"+f"(d[95]),"+f"(d[96]),"+f"(d[97]),"+f"(d[98]),"+f"(d[99]),"+f"(d[100]),"+f"(d[101]),"+f"(d[102]),"+f"(d[103]),"+f"(d[104]),"+f"(d[105]),"+f"(d[106]),"+f"(d[107]),"+f"(d[108]),"+f"(d[109]),"+f"(d[110]),"+f"(d[111]),"+f"(d[112]),"+f"(d[113]),"+f"(d[114]),"+f"(d[115]),"+f"(d[116]),"+f"(d[117]),"+f"(d[118]),"+f"(d[119]),"+f"(d[120]),"+f"(d[121]),"+f"(d[122]),"+f"(d[123]),"+f"(d[124]),"+f"(d[125]),"+f"(d[126]),"+f"(d[127])
    : "l"(da), "l"(db), "r"(sc));
}

__device__ __forceinline__ void wgmma_ss_n128_tb1(float (&d)[64], uint64_t da, uint64_t db, int sc) {
  asm volatile("{.reg .pred p; setp.ne.b32 p, %66, 0;\n"
    "wgmma.mma_async.sync.aligned.m64n128k16.f32.bf16.bf16 {%0,%1,%2,%3,%4,%5,%6,%7,%8,%9,%10,%11,%12,%13,%14,%15,%16,%17,%18,%19,%20,%21,%22,%23,%24,%25,%26,%27,%28,%29,%30,%31,%32,%33,%34,%35,%36,%37,%38,%39,%40,%41,%42,%43,%44,%45,%46,%47,%48,%49,%50,%51,%52,%53,%54,%55,%56,%57,%58,%59,%60,%61,%62,%63}, %64, %65, p, 1, 1, 0, 1;}\n"
    : "+f"(d[0]),"+f"(d[1]),"+f"(d[2]),"+f"(d[3]),"+f"(d[4]),"+f"(d[5]),"+f"(d[6]),"+f"(d[7]),"+f"(d[8]),"+f"(d[9]),"+f"(d[10]),"+f"(d[11]),"+f"(d[12]),"+f"(d[13]),"+f"(d[14]),"+f"(d[15]),"+f"(d[16]),"+f"(d[17]),"+f"(d[18]),"+f"(d[19]),"+f"(d[20]),"+f"(d[21]),"+f"(d[22]),"+f"(d[23]),"+f"(d[24]),"+f"(d[25]),"+f"(d[26]),"+f"(d[27]),"+f"(d[28]),"+f"(d[29]),"+f"(d[30]),"+f"(d[31]),"+f"(d[32]),"+f"(d[33]),"+f"(d[34]),"+f"(d[35]),"+f"(d[36]),"+f"(d[37]),"+f"(d[38]),"+f"(d[39]),"+f"(d[40]),"+f"(d[41]),"+f"(d[42]),"+f"(d[43]),"+f"(d[44]),"+f"(d[45]),"+f"(d[46]),"+f"(d[47]),"+f"(d[48]),"+f"(d[49]),"+f"(d[50]),"+f"(d[51]),"+f"(d[52]),"+f"(d[53]),"+f"(d[54]),"+f"(d[55]),"+f"(d[56]),"+f"(d[57]),"+f"(d[58]),"+f"(d[59]),"+f"(d[60]),"+f"(d[61]),"+f"(d[62]),"+f"(d[63])
    : "l"(da), "l"(db), "r"(sc));
}

template <int BN> struct WG;
template <> struct WG<256> { static __device__ __forceinline__ void mma(float (&d)[128], uint64_t a, uint64_t b, int sc) { wgmma_ss_n256_tb1(d, a, b, sc); } };
template <> struct WG<128> { static __device__ __forceinline__ void mma(float (&d)[64], uint64_t a, uint64_t b, int sc) { wgmma_ss_n128_tb1(d, a, b, sc); } };

struct GemmMaps { CUtensorMap a, b[3], c; };
template <int BN, int STAGES>
__global__ void __cluster_dims__(2, 1, 1) __launch_bounds__(384, 1)
gemm_kernel(const __grid_constant__ GemmMaps maps, int tilesM, int tilesN, int kblocks, int nPerB, int clearX) {
  extern __shared__ __align__(1024) uint8_t smem_raw[];
  constexpr int STAGE_BYTES = 16384 + BN * 128;
  constexpr int NBOX = BN / 64;
  const uint32_t sbase = (smem_u32(smem_raw) + 1023) & ~1023u;
  const uint32_t sEpi = sbase + STAGES * STAGE_BYTES;
  const uint32_t sBar = sEpi + 32768;
  const int warp = threadIdx.x >> 5, lane = threadIdx.x & 31, wg = warp >> 2;
  uint32_t crank; asm("mov.u32 %0, %%cluster_ctarank;" : "=r"(crank));
  if (threadIdx.x == 0) {
    for (int i = 0; i < STAGES; i++) { mbar_init(sBar + 8 * i, 1); mbar_init(sBar + 8 * (STAGES + i), 4); }
    asm volatile("fence.mbarrier_init.release.cluster;" ::: "memory");
  }
  if (clearX) {
    uint4* p = reinterpret_cast<uint4*>(&g_x);
    for (int i = blockIdx.x * 384 + threadIdx.x; i < (int)(sizeof(Xchg) / 16); i += gridDim.x * 384) p[i] = make_uint4(0, 0, 0, 0);
  }
  asm volatile("barrier.cluster.arrive.release.aligned; barrier.cluster.wait.acquire.aligned;" ::: "memory");
  const int npairs = (tilesM >> 1) * tilesN, pair0 = blockIdx.x >> 1, pstep = gridDim.x >> 1;
  if (wg == 2) {
    asm volatile("setmaxnreg.dec.sync.aligned.u32 40;");
    if (warp == 8 && lane == 0) {
      int st = 0, ph = 1;
      for (int p = pair0; p < npairs; p += pstep) {
        const int tm = (p % (tilesM >> 1)) * 2 + crank, tn = p / (tilesM >> 1);
        const CUtensorMap* mb = &maps.b[tn / nPerB];
        const int n0 = (tn % nPerB) * BN;
        for (int kb = 0; kb < kblocks; kb++) {
          mbar_wait(sBar + 8 * (STAGES + st), ph);
          const uint32_t a = sbase + st * STAGE_BYTES, full = sBar + 8 * st;
          mbar_expect_tx(full, STAGE_BYTES);
          tma2d(a, &maps.a, kb * 64, tm * 128, full);
#pragma unroll
          for (int i = 0; i < NBOX / 2; i++) {
            const int bx = crank * (NBOX / 2) + i;
            tma2d_mc(a + 16384 + bx * 8192, mb, n0 + bx * 64, kb * 64, full, (uint16_t)3);
          }
          if (++st == STAGES) { st = 0; ph ^= 1; }
        }
      }
      for (int i = 0; i < STAGES; i++) { mbar_wait(sBar + 8 * (STAGES + st), ph); if (++st == STAGES) { st = 0; ph ^= 1; } }
    }
  } else {
    asm volatile("setmaxnreg.inc.sync.aligned.u32 232;");
    int st = 0, ph = 0;
    float acc[BN / 2];
    const uint64_t descA0 = (uint64_t)(((sbase + wg * 8192) & 0x3FFFF) >> 4) | (1ull << 16) | (64ull << 32) | (1ull << 62);
    const uint64_t descB0 = (uint64_t)(((sbase + 16384) & 0x3FFFF) >> 4) | (512ull << 16) | (64ull << 32) | (1ull << 62);
    const uint32_t epi = sEpi + wg * 16384;
    for (int p = pair0; p < npairs; p += pstep) {
      const int tm = (p % (tilesM >> 1)) * 2 + crank, tn = p / (tilesM >> 1);
      int prev = -1;
      for (int kb = 0; kb < kblocks; kb++) {
        mbar_wait(sBar + 8 * st, ph);
        wg_fence();
        const uint64_t so = (uint64_t)(st * (STAGE_BYTES >> 4));
#pragma unroll
        for (int k = 0; k < 4; k++) WG<BN>::mma(acc, descA0 + so + k * 2, descB0 + so + k * 128, kb | k);
        wg_commit();
        if (prev >= 0) {
          wg_wait<1>();
          if ((threadIdx.x & 127) < 2) mbar_arrive_cluster(sBar + 8 * (STAGES + prev), threadIdx.x & 1);
        }
        prev = st;
        if (++st == STAGES) { st = 0; ph ^= 1; }
      }
      wg_wait<0>();
      if ((threadIdx.x & 127) < 2) mbar_arrive_cluster(sBar + 8 * (STAGES + prev), threadIdx.x & 1);
#pragma unroll
      for (int r = 0; r < BN / 128; r++) {
        if ((threadIdx.x & 127) == 0) asm volatile("cp.async.bulk.wait_group.read 0;" ::: "memory");
        bar_sync(1 + wg, 128);
        const int row = (warp & 3) * 16 + (lane & 15);
#pragma unroll
        for (int i = 0; i < 8; i++) {
          const int c = 2 * (i & 3) + (lane >> 4);
          const float* q = &acc[r * 64 + i * 8];
          stsm4(epi + (i >> 2) * 8192 + row * 128 + ((c ^ (row & 7)) << 4), pack2(q[0], q[1]), pack2(q[2], q[3]), pack2(q[4], q[5]), pack2(q[6], q[7]));
        }
        fence_async();
        bar_sync(1 + wg, 128);
        if ((threadIdx.x & 127) == 0) {
          tma2d_store(&maps.c, epi, tn * BN + r * 128, tm * 128 + wg * 64);
          tma2d_store(&maps.c, epi + 8192, tn * BN + r * 128 + 64, tm * 128 + wg * 64);
          asm volatile("cp.async.bulk.commit_group;" ::: "memory");
        }
      }
    }
    if ((threadIdx.x & 127) == 0) asm volatile("cp.async.bulk.wait_group 0;" ::: "memory");
  }
}

struct Dft { uint32_t m[2][2][2][4]; };
template <bool P4> __device__ __forceinline__ int fidx(int tile, int x) { return P4 ? 4 * (x >> 1) + 2 * (tile & 1) + (x & 1) + 16 * (tile >> 1) : x + 8 * tile; }
__device__ __forceinline__ float2 cis(int k, int n) {
  k &= n - 1; if (2 * k > n) k -= n;
  const float a = (float)k * (6.283185307179586f / (float)n);
  return make_float2(__cosf(a), __sinf(a));
}
template <bool OUT4> __device__ __forceinline__ void make_dft(Dft& D, int g, int t) {
#pragma unroll
  for (int q = 0; q < 16; q++) {
    const int b = q >> 3, u = (q >> 2) & 1, r = (q >> 1) & 1, v = q & 1;
    const float2 w = cis(fidx<OUT4>(v, g) * fidx<false>(2 * u + r, 2 * t + b), 32);
    D.m[b][u][0][q & 3] = pack2(w.x, w.y); D.m[b][u][1][q & 3] = pack2(-w.y, w.x);
  }
}
__device__ __forceinline__ void mma_dc(float (&d)[4], uint32_t a0, uint32_t a1, uint32_t a2, uint32_t a3, uint32_t b0, uint32_t b1, const float (&c)[4]) {
  asm("mma.sync.aligned.m16n8k16.row.col.f32.bf16.bf16.f32 {%0,%1,%2,%3}, {%4,%5,%6,%7}, {%8,%9}, {%10,%11,%12,%13};"
    : "=f"(d[0]), "=f"(d[1]), "=f"(d[2]), "=f"(d[3]) : "r"(a0), "r"(a1), "r"(a2), "r"(a3), "r"(b0), "r"(b1), "f"(c[0]), "f"(c[1]), "f"(c[2]), "f"(c[3])); }
__device__ __forceinline__ void dft_b(const Dft& D, const uint32_t (&x)[2][4], float (&o)[2][8]) {
#pragma unroll
  for (int ri = 0; ri < 2; ri++) {
    float z[4] = {0.f, 0.f, 0.f, 0.f}, e[4], p[4];
    mma_dc(e, D.m[0][0][ri][0], D.m[0][0][ri][1], D.m[0][0][ri][2], D.m[0][0][ri][3], x[0][0], x[0][1], z);
    mma_dc(e, D.m[0][1][ri][0], D.m[0][1][ri][1], D.m[0][1][ri][2], D.m[0][1][ri][3], x[0][2], x[0][3], e);
    mma_dc(p, D.m[1][0][ri][0], D.m[1][0][ri][1], D.m[1][0][ri][2], D.m[1][0][ri][3], x[1][0], x[1][1], e);
    mma_dc(p, D.m[1][1][ri][0], D.m[1][1][ri][1], D.m[1][1][ri][2], D.m[1][1][ri][3], x[1][2], x[1][3], p);
#pragma unroll
    for (int q = 0; q < 4; q++) { o[ri][q] = p[q]; o[ri][4 + q] = fmaf(2.f, e[q], -p[q]); }
  }
}
__device__ __forceinline__ void dft_a(const uint32_t (&m)[2][2][4], const uint32_t (&x0)[2][4], const uint32_t (&x1)[2][4], float (&o)[2][8]) {
#pragma unroll
  for (int ri = 0; ri < 2; ri++) {
    float z[4] = {0.f, 0.f, 0.f, 0.f}, e[4], p[4];
    mma_dc(e, x0[0][0], x1[0][0], x0[0][1], x1[0][1], m[0][ri][0], m[0][ri][1], z);
    mma_dc(e, x0[0][2], x1[0][2], x0[0][3], x1[0][3], m[0][ri][2], m[0][ri][3], e);
    mma_dc(p, x0[1][0], x1[1][0], x0[1][1], x1[1][1], m[1][ri][0], m[1][ri][1], e);
    mma_dc(p, x0[1][2], x1[1][2], x0[1][3], x1[1][3], m[1][ri][2], m[1][ri][3], p);
#pragma unroll
    for (int q = 0; q < 4; q++) { o[ri][q] = p[q]; o[ri][4 + q] = fmaf(2.f, e[q], -p[q]); }
  }
}
__device__ __forceinline__ uint32_t twid(float re, float im, float c, float s) { return pack2(fmaf(re, c, im * s), fmaf(im, c, -re * s)); }
__device__ __forceinline__ void cpa16(uint32_t d, const void* s) { asm volatile("cp.async.cg.shared.global [%0], [%1], 16;" :: "r"(d), "l"(s) : "memory"); }
__device__ __forceinline__ void sts32(uint32_t a, uint32_t x) { asm volatile("st.shared.u32 [%0], %1;" :: "r"(a), "r"(x) : "memory"); }
__device__ __forceinline__ void cpa_commit() { asm volatile("cp.async.commit_group;" ::: "memory"); }
template <int N> __device__ __forceinline__ void cpa_wait() { asm volatile("cp.async.wait_group %0;" :: "n"(N) : "memory"); }
__device__ __forceinline__ uint32_t lds32(uint32_t a) { uint32_t r; asm volatile("ld.shared.u32 %0, [%1];" : "=r"(r) : "r"(a) : "memory"); return r; }
constexpr int F_TP = 4112, F_TSZ = 8 * F_TP;

__device__ __forceinline__ void fft_wprep(const bf16* __restrict__ wr, const bf16* __restrict__ wi, int cta, int ncta) {
  const int tid = threadIdx.x;
#pragma unroll 2
  for (int it = cta; it < 256; it += ncta) {
    const int g = (it >> 1) & 7, c = (it >> 4) & 3, i = it >> 6, t = 2 * (it & 1) + (tid & 1);
    const int k0 = g + 8 * i + 32 * (8 * c + 2 * t), l0 = (tid & ~1) + (g & 1);
    uint32_t a[2][4], b[2][4];
#pragma unroll
    for (int q = 0; q < 8; q++) {
      const int o = (k0 + 32 * ((q >> 1) & 1) + 1024 * (q & 1)) * 513 + l0 + 256 * (q >> 2);
      a[q >> 2][q & 3] = __ldg(reinterpret_cast<const uint32_t*>(wr + o));
      b[q >> 2][q & 3] = __ldg(reinterpret_cast<const uint32_t*>(wi + o));
    }
    uint4* dst = g_wt + l0 * 512 + it * 2 + (tid & 1);
#pragma unroll
    for (int q = 0; q < 4; q++) {
      const int hf = q >> 1, l = l0 + 256 * hf + (q & 1);
      const uint32_t sel = (q & 1) ? 0x7632 : 0x5410;
      if (l & 511) dst[(256 * hf + (q & 1)) * 512] = make_uint4(__byte_perm(a[hf][0], b[hf][0], sel), __byte_perm(a[hf][1], b[hf][1], sel),
                                                              __byte_perm(a[hf][2], b[hf][2], sel), __byte_perm(a[hf][3], b[hf][3], sel));
    }
  }
  for (int e = cta * 256 + tid; e < 4096; e += ncta * 256) {
    const int l = (e >> 11) * 512, k = e & 2047, kn = (2048 - k) & 2047, k2 = (k >> 5) & 31;
    const float re = 0.5f * (__bfloat162float(wr[k * 513 + l]) + __bfloat162float(wr[kn * 513 + l]));
    const float im = 0.5f * (__bfloat162float(wi[k * 513 + l]) - __bfloat162float(wi[kn * 513 + l]));
    reinterpret_cast<uint32_t*>(g_wt)[(64 * ((k >> 3) & 3) + 16 * (k2 >> 3) + 2 * (k & 7) + ((k2 >> 2) & 1)) * 8 + l * 2048 + 2 * (k2 & 3) + (k >> 10)] = pack2(re, im);
  }
}

__device__ __forceinline__ void fft_rows_fwd(const bf16* __restrict__ x, uint32_t sb, int cta, int ncta) {
  const int warp = threadIdx.x >> 5, lane = threadIdx.x & 31, g = lane >> 2, t = lane & 3;
  const uint32_t in = sb + warp * 8192, tb = sb + 65536;
  const uint32_t f0 = pin(in + (lane >> 3) * 256 + (((lane & 7) ^ (2 * (lane >> 3))) << 4));
  const uint32_t xo = pin((256 * (warp & 3) + 64 * (warp >> 2)) * 2048 + lane * 8);
  auto fetch = [&](int it, int buf) {
    const bf16* src = x + (xo + (128 * (it & 1) + 32 * ((it >> 4) & 1) + 8 * (it >> 5) + ((it >> 1) & 7)) * 2048);
#pragma unroll
    for (int q = 0; q < 8; q++) cpa16(((f0 + buf * 4096) ^ ((q >> 2) * 144)) + (q & 3) * 1024, src + q * 256);
    cpa_commit();
  };
  fetch(cta, 0);
  Dft D; make_dft<true>(D, g, t);
  float2 tw[4][8];
#pragma unroll
  for (int q = 0; q < 32; q++) tw[q >> 3][q & 7] = cis(fidx<true>((q >> 1) & 3, g) * fidx<false>(q >> 3, 2 * t + (q & 1)), 1024);
  const uint32_t la = pin(in + lane * 128 + ((lane & 7) << 4));
  const uint32_t wa = pin(tb + warp * F_TP + fidx<true>(0, g) * 128 + t * 16), wz = pin((g & 1) ? -64 : 64);
  const uint32_t ra = pin(tb + (lane & 1) * 4 * F_TP + ((lane >> 1) + 16 * (warp ^ ((warp >> 1) & 1))) * 4);
  uint4* dst = g_y + (threadIdx.x >> 1) * 256 + (lane & 1);
  int buf = 0;
  auto drain = [&](int it, int q) {
    const uint32_t r = ra + (buf ^ 1) * F_TSZ + q * 512;
    const uint4 v = make_uint4(lds32(r), lds32(r + F_TP), lds32(r + 2 * F_TP), lds32(r + 3 * F_TP));
    if (it >= 0) dst[it * 2 + q * 32768] = v;
  };
  int it = cta;
#pragma unroll 1
  for (; it < 128; it += ncta, buf ^= 1) {
    cpa_wait<0>(); __syncthreads();
    uint32_t a[4][2][4], y[4][2][4];
#pragma unroll
    for (int q = 0; q < 8; q++) ldsm4t(a[q & 3][q >> 2], (la + buf * 4096) ^ (q << 4));
    if (it + ncta < 128) fetch(it + ncta, buf ^ 1);
    float o[2][8];
#pragma unroll
    for (int i = 0; i < 4; i++) {
      dft_b(D, a[i], o);
      drain(it - ncta, i);
#pragma unroll
      for (int q = 0; q < 8; q++) y[q >> 1][q & 1][i] = twid(o[0][q], o[1][q], tw[i][q].x, tw[i][q].y);
    }
    const uint32_t w0 = wa + buf * F_TSZ + ((g & 1) << 6);
#pragma unroll
    for (int z = 0; z < 2; z++) {
      float o2[2][8];
      dft_b(D, y[2 * z], o); drain(it - ncta, 4 + 2 * z); dft_b(D, y[2 * z + 1], o2); drain(it - ncta, 5 + 2 * z);
#pragma unroll
      for (int i = 0; i < 4; i++) {
        const float sg = i < 2 ? 1.f : -1.f;
        sts128(w0 + z * wz + fidx<true>(i, 0) * 128, pack2(o[0][2 * i], sg * o[1][2 * i]), pack2(o[0][2 * i + 1], sg * o[1][2 * i + 1]),
               pack2(o2[0][2 * i], sg * o2[1][2 * i]), pack2(o2[0][2 * i + 1], sg * o2[1][2 * i + 1]));
      }
    }
  }
  __syncthreads();
#pragma unroll
  for (int q = 0; q < 8; q++) drain(it - ncta, q);
}

__device__ __forceinline__ void fft_cols(uint32_t sb, int cta, int ncta) {
  const int warp = threadIdx.x >> 5, lane = threadIdx.x & 31, g = lane >> 2, t = lane & 3;
  const uint32_t in = sb + warp * 16384 + lane * 16, tab = sb + 131072 + lane * 16;
  auto fetch_y = [&](int l) {
#pragma unroll
    for (int q = 0; q < 16; q++) cpa16(in + q * 512, g_y + (q < 8 ? l : (1024 - l) & 1023) * 256 + (q & 7) * 32 + lane);
  };
  auto fetch_w = [&](int l) {
#pragma unroll
    for (int q = 0; q < 16; q++) cpa16(in + 8192 + q * 512, g_wt + l * 512 + q * 32 + lane);
  };
  const int l0 = cta * 8 + warp, dl = ncta * 8;
  if (l0 <= 512) fetch_y(l0);
  cpa_commit();
  if (l0 <= 512) fetch_w(l0);
  cpa_commit();
  Dft D; make_dft<false>(D, g, t);
#pragma unroll
  for (int q = 2 * warp; q < 2 * warp + 2; q++) {
    const int r = fidx<false>(q & 3, g), c = fidx<false>(q >> 2, 2 * t);
    const float2 w0 = cis(r * c, 1024), w1 = cis(r * c + r, 1024), p0 = cis(r + 32 * c, 2048), p1 = cis(r + 32 * c + 32, 2048);
    sts128(tab + q * 512, __float_as_uint(w0.x), __float_as_uint(w0.y), __float_as_uint(w1.x), __float_as_uint(w1.y));
    sts128(tab + 8192 + q * 512, __float_as_uint(p0.x), __float_as_uint(p0.y), __float_as_uint(p1.x), __float_as_uint(p1.y));
  }
  if (warp == 0) {
#pragma unroll
    for (int q = 0; q < 8; q++) {
      const int v = q >> 2, b = (q >> 1) & 1, ri = q & 1;
      sts128(tab + 16384 + q * 512, D.m[b][0][ri][v], D.m[b][0][ri][v + 2], D.m[b][1][ri][v], D.m[b][1][ri][v + 2]);
    }
  }
  __syncthreads();
#pragma unroll 1
  for (int l = l0; l <= 512; l += dl) {
    uint32_t a[2][4][2][4], y[2][4][2][4];
    float o[2][2][8];
    cpa_wait<1>();
#pragma unroll
    for (int q = 0; q < 16; q++) lds128(a[q >> 3][(q >> 1) & 3][q & 1], in + q * 512);
    if (!(l & 511)) {
      const uint32_t m0 = l ? 0x80000000u : 0u;
#pragma unroll
      for (int q = 0; q < 32; q++) { a[0][q >> 3][(q >> 2) & 1][q & 3] ^= m0; a[1][q >> 3][(q >> 2) & 1][q & 3] ^= m0 ^ 0x80000000u; }
    }
    auto first = [&]() {
#pragma unroll
      for (int i = 0; i < 4; i++) {
        dft_b(D, a[0][i], o[0]); dft_b(D, a[1][i], o[1]);
#pragma unroll
        for (int r = 0; r < 4; r++) {
          const float4 w = lds128f(tab + (4 * i + r) * 512);
#pragma unroll
          for (int s = 0; s < 2; s++) {
            y[s][r][0][i] = twid(o[s][0][2 * r], o[s][1][2 * r], w.x, w.y);
            y[s][r][1][i] = twid(o[s][0][2 * r + 1], o[s][1][2 * r + 1], w.z, w.w);
          }
        }
      }
    };
    first();
    if (l + dl <= 512) fetch_y(l + dl);
    cpa_commit();
    cpa_wait<1>();
#pragma unroll
    for (int zv = 0; zv < 4; zv++) {
      const int z = zv >> 1, v = zv & 1;
      uint32_t m[2][2][4];
#pragma unroll
      for (int q = 0; q < 4; q++) lds128(m[q >> 1][q & 1], tab + 16384 + (4 * v + q) * 512);
      dft_a(m, y[0][2 * z], y[0][2 * z + 1], o[0]); dft_a(m, y[1][2 * z], y[1][2 * z + 1], o[1]);
#pragma unroll
      for (int q = 0; q < 4; q++) {
        const int i = 2 * z + (q & 1), c = v + (q & 2);
        uint32_t w[4]; lds128(w, in + 8192 + (4 * i + c) * 512);
        const float4 ph = lds128f(tab + 8192 + (4 * c + i) * 512);
#pragma unroll
        for (int b = 0; b < 2; b++) {
          const float cs = b ? ph.z : ph.x, sn = b ? ph.w : ph.y;
          const float r1 = __uint_as_float(w[2 * b] << 16), i1 = __uint_as_float(w[2 * b] & 0xFFFF0000u);
          const float r2 = __uint_as_float(w[2 * b + 1] << 16), i2 = __uint_as_float(w[2 * b + 1] & 0xFFFF0000u);
          const float Sr = r1 + r2, Si = i1 + i2, Dr = r1 - r2, Di = i1 - i2;
          const float ar = fmaf(-Dr, sn, Sr), ai = fmaf(-Di, sn, Si), dr = fmaf(Dr, sn, Sr), di = fmaf(Di, sn, Si), br = -Di * cs, bi = Dr * cs;
          const float Ar = o[0][0][2 * q + b], Ai = o[0][1][2 * q + b], Br = o[1][0][2 * q + b], Bi = o[1][1][2 * q + b];
          a[0][i][b][c] = pack2(fmaf(ar, Ai, fmaf(ai, Ar, fmaf(br, Bi, bi * Br))), fmaf(ar, Ar, fmaf(-ai, Ai, fmaf(br, Br, -bi * Bi))));
          a[1][i][b][c] = pack2(fmaf(dr, Bi, fmaf(di, Br, fmaf(-br, Ai, -bi * Ar))), fmaf(dr, Br, fmaf(-di, Bi, fmaf(-br, Ar, bi * Ai))));
        }
      }
    }
    if (l + dl <= 512) fetch_w(l + dl);
    cpa_commit();
    first();
#pragma unroll
    for (int s = 0; s < 2; s++) {
      uint4* dst = g_y + (s ? (1024 - l) & 1023 : l) * 256 + lane;
      const float sg = s ? -1.f : 1.f;
#pragma unroll
      for (int i = 0; i < 4; i++) {
        dft_b(D, y[s][i], o[0]);
#pragma unroll
        for (int b = 0; b < 2; b++)
          dst[(2 * i + b) * 32] = make_uint4(pack2(sg * o[0][0][b], o[0][1][b]), pack2(sg * o[0][0][2 + b], o[0][1][2 + b]),
                                             pack2(sg * o[0][0][4 + b], o[0][1][4 + b]), pack2(sg * o[0][0][6 + b], o[0][1][6 + b]));
      }
    }
  }
}

__device__ __forceinline__ void fft_rows_inv(const CUtensorMap* om, uint32_t sb, int cta, int ncta) {
  const int warp = threadIdx.x >> 5, lane = threadIdx.x & 31, g = lane >> 2, t = lane & 3, wg = warp >> 2, w4 = warp & 3;
  const uint32_t tb = sb + 32768 + wg * 2 * F_TSZ;
  const uint4* src = g_y + pin((256 * ((lane >> 1) & 3) + 64 * (lane >> 3) + 8 * w4) * 256 + (lane & 1));
  const uint32_t wa = pin(tb + (lane & 1) * 4 * F_TP + w4 * 1024 + (lane >> 1) * 4);
  uint4 pf[8];
  auto fetch = [&](int it, int hf) {
#pragma unroll
    for (int q = 0; q < 8; q++) pf[q] = __ldcg(src + (it * 2 + hf * 8192) + q * 256);
  };
  auto put = [&](uint32_t off) {
#pragma unroll
    for (int q = 0; q < 8; q++) {
      sts32(wa + off + q * 64, pf[q].x); sts32(wa + off + q * 64 + F_TP, pf[q].y);
      sts32(wa + off + q * 64 + 2 * F_TP, pf[q].z); sts32(wa + off + q * 64 + 3 * F_TP, pf[q].w);
    }
  };
  const int it0 = 2 * cta + wg;
  if (it0 >= 128) return;
  fetch(it0, 0); put(0); fetch(it0, 1); put(512);
  Dft D; make_dft<false>(D, g, t);
  float2 tw[4][8];
#pragma unroll
  for (int q = 0; q < 32; q++) {
    tw[q >> 3][q & 7] = cis(fidx<false>((q >> 1) & 3, g) * fidx<false>(q >> 3, 2 * t + (q & 1)), 1024);
    tw[q >> 3][q & 7].x *= 1.f / 2097152.f; tw[q >> 3][q & 7].y *= 1.f / 2097152.f;
  }
  const uint32_t la = pin(tb + w4 * F_TP + lane * 16), ob = uni(sb + warp * 4096);
  const uint32_t oa = pin(ob + (lane >> 1) * 128 + (((4 * (lane & 1)) ^ ((lane >> 1) & 7)) << 4));
#pragma unroll 1
  for (int n = 0;; n++) {
    const int it = it0 + (n >> 1) * 2 * ncta, hf = n & 1, buf = (n >> 1) & 1;
    if (it >= 128) break;
    if (!hf) bar_sync(1 + wg, 128);
    uint32_t a[4][2][4], y[4][2][4];
#pragma unroll
    for (int q = 0; q < 8; q++) lds128(a[q >> 1][q & 1], la + buf * F_TSZ + hf * 4 * F_TP + q * 512);
    fetch(min(it + 2 * ncta, 127), hf);
    float o[2][8];
#pragma unroll
    for (int i = 0; i < 4; i++) {
      dft_b(D, a[i], o);
#pragma unroll
      for (int q = 0; q < 8; q++) y[q >> 1][q & 1][i] = twid(o[0][q], o[1][q], tw[i][q].x, tw[i][q].y);
    }
    if (lane == 0) asm volatile("cp.async.bulk.wait_group.read 0;" ::: "memory");
    __syncwarp();
#pragma unroll
    for (int c = 0; c < 4; c++) {
      dft_b(D, y[c], o);
#pragma unroll
      for (int ri = 0; ri < 2; ri++)
        stsm4((oa ^ (c << 4)) + (1 - ri) * 2048, pack2(o[ri][0], o[ri][1]), pack2(o[ri][2], o[ri][3]), pack2(o[ri][4], o[ri][5]), pack2(o[ri][6], o[ri][7]));
    }
    fence_async();
    __syncwarp();
    if (lane == 0) {
      const int m = 256 * w4 + 32 * ((it >> 1) & 7) + 8 * (it >> 5) + 4 * (it & 1) + 2 * hf + ((it >> 4) & 1);
      asm volatile("cp.async.bulk.tensor.3d.global.shared::cta.bulk_group [%0, {0, 0, %2}], [%1];" :: "l"(om), "r"(ob), "r"(2 * m) : "memory");
      asm volatile("cp.async.bulk.commit_group;" ::: "memory");
    }
    put((buf ^ 1) * F_TSZ + hf * 512);
  }
  if (lane == 0) asm volatile("cp.async.bulk.wait_group 0;" ::: "memory");
}
constexpr int F_SMEM = 65536 + 2 * F_TSZ + 1024;
__global__ void __launch_bounds__(256, 1) fft_pre_kernel(const bf16* __restrict__ x, const bf16* __restrict__ wr, const bf16* __restrict__ wi) {
  extern __shared__ __align__(1024) uint8_t smem_raw[];
  const uint32_t sb = (smem_u32(smem_raw) + 1023) & ~1023u;
  fft_wprep(wr, wi, blockIdx.x, gridDim.x);
  fft_rows_fwd(x, sb, blockIdx.x, gridDim.x);
}
__device__ __forceinline__ void grid_arrive(unsigned* ctr) {
  __syncthreads();
  if (threadIdx.x == 0) { __threadfence(); atomicAdd(ctr, 1u); }
}
__device__ __forceinline__ void grid_wait(unsigned* ctr, unsigned n) {
  if (threadIdx.x == 0) {
    int it = 0;
    while (*reinterpret_cast<volatile unsigned*>(ctr) < n) { __nanosleep(200); if (++it > SPIN_LIMIT) { g_err = 3; break; } }
    __threadfence();
  }
  __syncthreads();
}

struct RecMaps { CUtensorMap wq, wk, wv, wo, x, k, q, v, fo; };
constexpr int R_WV = 0, R_WO = 65536, R_X = 131072, R_K = 196608, R_Q = 204800, R_V = 206848, R_S = 223232, R_O = 225792,
              R_SUM = 227840, R_BAR = 227968, R_TS = 228096,
              R_TOTAL = R_TS;
#define TS(i)
constexpr int B_KQ = R_BAR, B_V = R_BAR + 8, B_W = R_BAR + 16, B_MEM = R_BAR + 24, B_X = R_BAR + 40, B_TC = R_BAR + 56;
#define DLY_A 400
#define DLY_V 350
#define DLY_B 500
#define DLY_C 350
#define DLY_K 800
__device__ __forceinline__ float rcp(float x) { float r; asm("rcp.approx.ftz.f32 %0, %1;" : "=f"(r) : "f"(x)); return r; }
__device__ __forceinline__ uint32_t movm(uint32_t a) { uint32_t d; asm volatile("movmatrix.sync.aligned.m8n8.trans.b16 %0, %1;" : "=r"(d) : "r"(a)); return d; }
__device__ __forceinline__ uint32_t hadd2(uint32_t a, uint32_t b) { uint32_t d; asm("add.rn.bf16x2 %0, %1, %2;" : "=r"(d) : "r"(a), "r"(b)); return d; }
__device__ __forceinline__ void mma_a(float (&d)[4], const uint32_t (&a)[4], uint32_t b0, uint32_t b1) { mma16816(d, a[0], a[1], a[2], a[3], b0, b1); }
__device__ __forceinline__ void tma3d(uint32_t dst, const CUtensorMap* m, int c1, int c2, uint32_t bar) {
  asm volatile("cp.async.bulk.tensor.3d.shared::cluster.global.mbarrier::complete_tx::bytes [%0], [%1, {0, %3, %4}], [%2];"
    :: "r"(dst), "l"(m), "r"(bar), "r"(c1), "r"(c2) : "memory"); }
__device__ __forceinline__ void tma4d(uint32_t dst, const CUtensorMap* m, int c1, int c2, uint32_t bar) {
  asm volatile("cp.async.bulk.tensor.4d.shared::cluster.global.mbarrier::complete_tx::bytes [%0], [%1, {0, %3, %4, 0}], [%2];"
    :: "r"(dst), "l"(m), "r"(bar), "r"(c1), "r"(c2) : "memory"); }
template <int OFF, int ACC>
__device__ __forceinline__ void wg_rs32(float (&d)[16], const uint32_t (&a)[4], uint32_t db) {
  if (ACC)
    asm volatile("{.reg .b64 db; .reg .b32 lo; add.u32 lo, %20, %21; mov.b64 db, {lo, 0x40000040};\n"
      "wgmma.mma_async.sync.aligned.m64n32k16.f32.bf16.bf16 {%0,%1,%2,%3,%4,%5,%6,%7,%8,%9,%10,%11,%12,%13,%14,%15}, {%16,%17,%18,%19}, db, 1, 1, 1, 0;}"
      : "+f"(d[0]), "+f"(d[1]), "+f"(d[2]), "+f"(d[3]), "+f"(d[4]), "+f"(d[5]), "+f"(d[6]), "+f"(d[7]), "+f"(d[8]), "+f"(d[9]), "+f"(d[10]), "+f"(d[11]), "+f"(d[12]), "+f"(d[13]), "+f"(d[14]), "+f"(d[15])
      : "r"(a[0]), "r"(a[1]), "r"(a[2]), "r"(a[3]), "r"(db), "n"(OFF));
  else
    asm volatile("{.reg .b64 db; .reg .b32 lo; add.u32 lo, %20, %21; mov.b64 db, {lo, 0x40000040};\n"
      "wgmma.mma_async.sync.aligned.m64n32k16.f32.bf16.bf16 {%0,%1,%2,%3,%4,%5,%6,%7,%8,%9,%10,%11,%12,%13,%14,%15}, {%16,%17,%18,%19}, db, 0, 1, 1, 0;}"
      : "=f"(d[0]), "=f"(d[1]), "=f"(d[2]), "=f"(d[3]), "=f"(d[4]), "=f"(d[5]), "=f"(d[6]), "=f"(d[7]), "=f"(d[8]), "=f"(d[9]), "=f"(d[10]), "=f"(d[11]), "=f"(d[12]), "=f"(d[13]), "=f"(d[14]), "=f"(d[15])
      : "r"(a[0]), "r"(a[1]), "r"(a[2]), "r"(a[3]), "r"(db), "n"(OFF));
}
template <int I, int N, class F> __device__ __forceinline__ void sfor(F&& f) {
  if constexpr (I < N) { f(std::integral_constant<int, I>{}); sfor<I + 1, N>(f); }
}
__device__ __forceinline__ void keep(float (&d)[16]) {
  asm volatile("" : "+f"(d[0]), "+f"(d[1]), "+f"(d[2]), "+f"(d[3]), "+f"(d[4]), "+f"(d[5]), "+f"(d[6]), "+f"(d[7]),
      "+f"(d[8]), "+f"(d[9]), "+f"(d[10]), "+f"(d[11]), "+f"(d[12]), "+f"(d[13]), "+f"(d[14]), "+f"(d[15]) :: "memory");
}

__device__ __forceinline__ void poll2(uint64_t (&v)[2][2], const void* p, uint32_t tag, int& it) {
  asm volatile(
    "{.reg .pred q, p0, p1; .reg .b32 u, lo0, lo1, hi, x0, x1;\n"
    "LOOP:\n"
    "mov.b64 {lo0, hi}, %0; mov.b64 {lo1, hi}, %1; lop3.b32 x0, lo0, lo1, %6, 0x7E;\n"
    "mov.b64 {lo0, hi}, %2; mov.b64 {lo1, hi}, %3; lop3.b32 x1, lo0, lo1, %6, 0x7E;\n"
    "lop3.b32 u, x0, x1, 1, 0xA8;\n"
    "setp.ne.u32 q, u, 0; vote.sync.any.pred q, q, 0xffffffff; @!q bra.uni DONE;\n"
    "add.s32 %4, %4, 1; setp.gt.s32 q, %4, 1048576; @q bra.uni DONE;\n"
    "and.b32 u, x0, 1; setp.ne.u32 p0, u, 0;\n"
    "and.b32 u, x1, 1; setp.ne.u32 p1, u, 0;\n"
    "@p0 ld.relaxed.gpu.global.v2.b64 {%0, %1}, [%5+0];\n"
    "@p1 ld.relaxed.gpu.global.v2.b64 {%2, %3}, [%5+512];\n"
    "bra.uni LOOP;\n"
    "DONE: }\n"
    : "+l"(v[0][0]), "+l"(v[0][1]), "+l"(v[1][0]), "+l"(v[1][1]), "+r"(it) : "l"(p), "r"(tag) : "memory");
}

__device__ __forceinline__ void poll4(uint64_t (&v)[4][2], const void* p, uint32_t tag, int& it) {
  asm volatile(
    "{.reg .pred q, p0, p1, p2, p3; .reg .b32 u, lo0, lo1, hi, x0, x1, x2, x3;\n"
    "LOOP:\n"
    "mov.b64 {lo0, hi}, %0; mov.b64 {lo1, hi}, %1; lop3.b32 x0, lo0, lo1, %10, 0x7E;\n"
    "mov.b64 {lo0, hi}, %2; mov.b64 {lo1, hi}, %3; lop3.b32 x1, lo0, lo1, %10, 0x7E;\n"
    "mov.b64 {lo0, hi}, %4; mov.b64 {lo1, hi}, %5; lop3.b32 x2, lo0, lo1, %10, 0x7E;\n"
    "mov.b64 {lo0, hi}, %6; mov.b64 {lo1, hi}, %7; lop3.b32 x3, lo0, lo1, %10, 0x7E;\n"
    "lop3.b32 u, x0, x1, x2, 0xFE; lop3.b32 u, u, x3, 1, 0xA8;\n"
    "setp.ne.u32 q, u, 0; vote.sync.any.pred q, q, 0xffffffff; @!q bra.uni DONE;\n"
    "add.s32 %8, %8, 1; setp.gt.s32 q, %8, 1048576; @q bra.uni DONE;\n"
    "and.b32 u, x0, 1; setp.ne.u32 p0, u, 0;\n"
    "and.b32 u, x1, 1; setp.ne.u32 p1, u, 0;\n"
    "and.b32 u, x2, 1; setp.ne.u32 p2, u, 0;\n"
    "and.b32 u, x3, 1; setp.ne.u32 p3, u, 0;\n"
    "@p0 ld.relaxed.gpu.global.v2.b64 {%0, %1}, [%9+0];\n"
    "@p1 ld.relaxed.gpu.global.v2.b64 {%2, %3}, [%9+512];\n"
    "@p2 ld.relaxed.gpu.global.v2.b64 {%4, %5}, [%9+1024];\n"
    "@p3 ld.relaxed.gpu.global.v2.b64 {%6, %7}, [%9+1536];\n"
    "bra.uni LOOP;\n"
    "DONE: }\n"
    : "+l"(v[0][0]), "+l"(v[0][1]), "+l"(v[1][0]), "+l"(v[1][1]), "+l"(v[2][0]), "+l"(v[2][1]), "+l"(v[3][0]), "+l"(v[3][1]), "+r"(it) : "l"(p), "r"(tag) : "memory");
}

__device__ __forceinline__ void poll8(uint64_t (&v)[8][2], const void* p, uint32_t tag, int& it) {
  asm volatile(
    "{.reg .pred q, p0, p1, p2, p3, p4, p5, p6, p7; .reg .b32 u, lo0, lo1, hi, x0, x1, x2, x3, x4, x5, x6, x7;\n"
    "LOOP:\n"
    "mov.b64 {lo0, hi}, %0; mov.b64 {lo1, hi}, %1; lop3.b32 x0, lo0, lo1, %18, 0x7E;\n"
    "mov.b64 {lo0, hi}, %2; mov.b64 {lo1, hi}, %3; lop3.b32 x1, lo0, lo1, %18, 0x7E;\n"
    "mov.b64 {lo0, hi}, %4; mov.b64 {lo1, hi}, %5; lop3.b32 x2, lo0, lo1, %18, 0x7E;\n"
    "mov.b64 {lo0, hi}, %6; mov.b64 {lo1, hi}, %7; lop3.b32 x3, lo0, lo1, %18, 0x7E;\n"
    "mov.b64 {lo0, hi}, %8; mov.b64 {lo1, hi}, %9; lop3.b32 x4, lo0, lo1, %18, 0x7E;\n"
    "mov.b64 {lo0, hi}, %10; mov.b64 {lo1, hi}, %11; lop3.b32 x5, lo0, lo1, %18, 0x7E;\n"
    "mov.b64 {lo0, hi}, %12; mov.b64 {lo1, hi}, %13; lop3.b32 x6, lo0, lo1, %18, 0x7E;\n"
    "mov.b64 {lo0, hi}, %14; mov.b64 {lo1, hi}, %15; lop3.b32 x7, lo0, lo1, %18, 0x7E;\n"
    "lop3.b32 u, x0, x1, x2, 0xFE; lop3.b32 hi, x3, x4, x5, 0xFE; lop3.b32 u, u, x6, x7, 0xFE; lop3.b32 u, u, hi, 1, 0xA8;\n"
    "setp.ne.u32 q, u, 0; vote.sync.any.pred q, q, 0xffffffff; @!q bra.uni DONE;\n"
    "add.s32 %16, %16, 1; setp.gt.s32 q, %16, 1048576; @q bra.uni DONE;\n"
    "and.b32 u, x0, 1; setp.ne.u32 p0, u, 0;\n"
    "and.b32 u, x1, 1; setp.ne.u32 p1, u, 0;\n"
    "and.b32 u, x2, 1; setp.ne.u32 p2, u, 0;\n"
    "and.b32 u, x3, 1; setp.ne.u32 p3, u, 0;\n"
    "and.b32 u, x4, 1; setp.ne.u32 p4, u, 0;\n"
    "and.b32 u, x5, 1; setp.ne.u32 p5, u, 0;\n"
    "and.b32 u, x6, 1; setp.ne.u32 p6, u, 0;\n"
    "and.b32 u, x7, 1; setp.ne.u32 p7, u, 0;\n"
    "@p0 ld.relaxed.gpu.global.v2.b64 {%0, %1}, [%17+0];\n"
    "@p1 ld.relaxed.gpu.global.v2.b64 {%2, %3}, [%17+512];\n"
    "@p2 ld.relaxed.gpu.global.v2.b64 {%4, %5}, [%17+1024];\n"
    "@p3 ld.relaxed.gpu.global.v2.b64 {%6, %7}, [%17+1536];\n"
    "@p4 ld.relaxed.gpu.global.v2.b64 {%8, %9}, [%17+2048];\n"
    "@p5 ld.relaxed.gpu.global.v2.b64 {%10, %11}, [%17+2560];\n"
    "@p6 ld.relaxed.gpu.global.v2.b64 {%12, %13}, [%17+3072];\n"
    "@p7 ld.relaxed.gpu.global.v2.b64 {%14, %15}, [%17+3584];\n"
    "bra.uni LOOP;\n"
    "DONE: }\n"
    : "+l"(v[0][0]), "+l"(v[0][1]), "+l"(v[1][0]), "+l"(v[1][1]), "+l"(v[2][0]), "+l"(v[2][1]), "+l"(v[3][0]), "+l"(v[3][1]), "+l"(v[4][0]), "+l"(v[4][1]), "+l"(v[5][0]), "+l"(v[5][1]), "+l"(v[6][0]), "+l"(v[6][1]), "+l"(v[7][0]), "+l"(v[7][1]), "+r"(it) : "l"(p), "r"(tag) : "memory");
}

__device__ __forceinline__ void poll4_b128(uint64_t (&v)[4][2], const void* p, uint32_t tag, int& it) {
  asm volatile(
    "{.reg .pred q, p0, p1; .reg .b32 u, lo0, lo1, hi, x0, x1; .reg .b128 t;\n"
    "LOOP:\n"
    "mov.b64 {lo0, hi}, %0; mov.b64 {lo1, hi}, %2; lop3.b32 x0, lo0, lo1, %10, 0x7E;\n"
    "mov.b64 {lo0, hi}, %4; mov.b64 {lo1, hi}, %6; lop3.b32 x1, lo0, lo1, %10, 0x7E;\n"
    "lop3.b32 u, x0, x1, 1, 0xA8;\n"
    "setp.ne.u32 q, u, 0; vote.sync.any.pred q, q, 0xffffffff; @!q bra.uni DONE;\n"
    "add.s32 %8, %8, 1; setp.gt.s32 q, %8, 1048576; @q bra.uni DONE;\n"
    "and.b32 u, x0, 1; setp.ne.u32 p0, u, 0;\n"
    "and.b32 u, x1, 1; setp.ne.u32 p1, u, 0;\n"
    "mov.b128 t, {%0, %1}; @p0 ld.relaxed.gpu.global.b128 t, [%9+0]; mov.b128 {%0, %1}, t;\n"
    "mov.b128 t, {%2, %3}; @p0 ld.relaxed.gpu.global.b128 t, [%9+512]; mov.b128 {%2, %3}, t;\n"
    "mov.b128 t, {%4, %5}; @p1 ld.relaxed.gpu.global.b128 t, [%9+1024]; mov.b128 {%4, %5}, t;\n"
    "mov.b128 t, {%6, %7}; @p1 ld.relaxed.gpu.global.b128 t, [%9+1536]; mov.b128 {%6, %7}, t;\n"
    "bra.uni LOOP;\n"
    "DONE: }\n"
    : "+l"(v[0][0]), "+l"(v[0][1]), "+l"(v[1][0]), "+l"(v[1][1]), "+l"(v[2][0]), "+l"(v[2][1]), "+l"(v[3][0]), "+l"(v[3][1]), "+r"(it) : "l"(p), "r"(tag) : "memory");
}

__device__ __forceinline__ void poll8_w(uint32_t (&v)[8], const void* p, uint32_t tag, uint32_t mask, int& it) {
  asm volatile(
    "{.reg .pred q; .reg .b32 u, x0, x1, x2, x3;\n"
    "LOOP:\n"
    "lop3.b32 x0, %0, %1, %10, 0x7E; lop3.b32 x1, %2, %3, %10, 0x7E; lop3.b32 x2, %4, %5, %10, 0x7E; lop3.b32 x3, %6, %7, %10, 0x7E;\n"
    "lop3.b32 u, x0, x1, x2, 0xFE; lop3.b32 u, u, x3, %11, 0xA8;\n"
    "setp.ne.u32 q, u, 0; vote.sync.any.pred q, q, 0xffffffff; @!q bra.uni DONE;\n"
    "add.s32 %8, %8, 1; setp.gt.s32 q, %8, 1048576; @q bra.uni DONE;\n"
    "ld.relaxed.gpu.global.b32 %0, [%9+0];\n"
    "ld.relaxed.gpu.global.b32 %1, [%9+128];\n"
    "ld.relaxed.gpu.global.b32 %2, [%9+256];\n"
    "ld.relaxed.gpu.global.b32 %3, [%9+384];\n"
    "ld.relaxed.gpu.global.b32 %4, [%9+512];\n"
    "ld.relaxed.gpu.global.b32 %5, [%9+640];\n"
    "ld.relaxed.gpu.global.b32 %6, [%9+768];\n"
    "ld.relaxed.gpu.global.b32 %7, [%9+896];\n"
    "bra.uni LOOP;\n"
    "DONE: }\n"
    : "+r"(v[0]), "+r"(v[1]), "+r"(v[2]), "+r"(v[3]), "+r"(v[4]), "+r"(v[5]), "+r"(v[6]), "+r"(v[7]), "+r"(it) : "l"(p), "r"(tag), "r"(mask) : "memory");
}

__device__ __forceinline__ uint32_t lo32(uint64_t v) { return (uint32_t)v; }
__device__ __forceinline__ uint32_t hi32(uint64_t v) { return (uint32_t)(v >> 32); }
__device__ __forceinline__ void ldx2(uint64_t (&r)[2], const void* p) { asm volatile("ld.relaxed.gpu.global.v2.b64 {%0, %1}, [%2];" : "=l"(r[0]), "=l"(r[1]) : "l"(p) : "memory"); }
__device__ __forceinline__ void ldxb(uint64_t (&r)[2], const void* p) {
  asm volatile("{.reg .b128 t; ld.relaxed.gpu.global.b128 t, [%2]; mov.b128 {%0, %1}, t;}" : "=l"(r[0]), "=l"(r[1]) : "l"(p) : "memory"); }
__device__ __forceinline__ void lds2(uint64_t (&r)[2], uint32_t a) { asm volatile("ld.shared.v2.b64 {%0, %1}, [%2];" : "=l"(r[0]), "=l"(r[1]) : "r"(a) : "memory"); }
__device__ __forceinline__ void sts2(uint32_t a, const uint64_t (&r)[2]) { asm volatile("st.shared.v2.b64 [%0], {%1, %2};" :: "r"(a), "l"(r[0]), "l"(r[1]) : "memory"); }
__device__ __forceinline__ void mma_b(float (&d)[4], const uint32_t (&a)[4], uint64_t b) { mma16816(d, a[0], a[1], a[2], a[3], lo32(b), hi32(b)); }
__device__ __forceinline__ void mma_bb(float (&d)[4], const uint64_t (&a)[2], uint64_t b) { mma16816(d, lo32(a[0]), hi32(a[0]), lo32(a[1]), hi32(a[1]), lo32(b), hi32(b)); }
__device__ __forceinline__ void ldsm4q(uint64_t (&r)[2], uint32_t a) {
  asm volatile("{.reg .b32 a,b,c,d; ldmatrix.sync.aligned.m8n8.x4.shared.b16 {a,b,c,d}, [%2]; mov.b64 %0, {a,b}; mov.b64 %1, {c,d};}" : "=l"(r[0]), "=l"(r[1]) : "r"(a) : "memory"); }
__device__ __forceinline__ void mbar_spin(uint32_t bar, uint32_t par, int& it) {
  asm volatile("{.reg .pred p; .reg .b32 par; mov.b32 par, %2;\nLOOP: mbarrier.try_wait.parity.shared::cta.b64 p, [%1], par; @p bra.uni DONE;\n"
               "add.s32 %0, %0, 1; setp.le.s32 p, %0, 1048576; @p bra.uni LOOP;\nDONE: }" : "+r"(it) : "r"(bar), "r"(par) : "memory"); }
__device__ __forceinline__ void delay_until(unsigned t) {
  asm volatile("{.reg .pred p; .reg .b64 c; .reg .b32 lo, hi;\nLOOP: mov.u64 c, %%clock64; mov.b64 {lo, hi}, c; sub.s32 lo, lo, %0; setp.lt.s32 p, lo, 0; @p bra.uni LOOP;}" :: "r"(t) : "memory"); }
__device__ __forceinline__ void zero(float (&c)[4][4]) {
#pragma unroll
  for (int i = 0; i < 4; i++) c[i][0] = c[i][1] = c[i][2] = c[i][3] = 0.f;
}

template <int W4>
__device__ __forceinline__ void qk_gemm(const uint32_t (&w)[32][4], uint64_t (&own)[4][2], uint32_t a, float (&c)[4][4], uint32_t bar, uint32_t par, int& it) {
#pragma unroll
  for (int i = 0; i < 4; i++) {
    mma_b(c[2 * (i & 1)], w[8 * W4 + 2 * i], own[i][0]);
    mma_b(c[2 * (i & 1) + 1], w[8 * W4 + 2 * i + 1], own[i][1]);
  }
  mbar_spin(bar, par, it);
  uint64_t b[12][2];
#pragma unroll
  for (int i = 0; i < 12; i++) lds2(b[i], a + (((W4 + 1 + (i >> 2)) & 3) - W4) * 512 + (i & 3) * 4096);
#pragma unroll
  for (int i = 0; i < 12; i++) {
    const int p = (4 * W4 + 4 + i) & 15;
    mma_b(c[2 * (i & 1)], w[2 * p], b[i][0]);
    mma_b(c[2 * (i & 1) + 1], w[2 * p + 1], b[i][1]);
  }
}

__global__ void __launch_bounds__(256, 1)
rec_kernel(const __grid_constant__ RecMaps maps, const bf16* __restrict__ xin, const bf16* __restrict__ mem0) {
  extern __shared__ __align__(1024) uint8_t smem_raw[];
  const uint32_t sb = smem_u32(smem_raw);
  int role = blockIdx.x;
  {
    uint32_t smid, nsm; asm volatile("mov.u32 %0, %%smid;" : "=r"(smid)); asm volatile("mov.u32 %0, %%nsmid;" : "=r"(nsm));
    const int p = smid >> 1, u = p - 32;
    if (nsm == gridDim.x)
      role = (smid & 1) + (p < 32 ? 4 * ((p & 7) + 8 * (p >> 4)) + 2 * ((p >> 3) & 1) : p < 60 ? 4 * (16 + u % 7 + 7 * (u / 14)) + 2 * ((u / 7) & 1)
                         : p < 62 ? 2 * p + 8 : 2 * p - 4);
    role = uni(role);
  }
  if (role >= 128) {
    fft_cols(sb, role - 128, 4);
    grid_arrive(&g_x.ctr[32]); grid_wait(&g_x.ctr[32], 4);
    fft_rows_inv(&maps.fo, sb, role - 128, 4);
    return;
  }
  const int tid = threadIdx.x, warp = uni(tid >> 5), lane = tid & 31, wg = warp >> 2, w4 = warp & 3, g = lane >> 2, t = lane & 3;
  const int h = role >> 2, j = role & 3, jh = j & 1;
  uint32_t wqk[32][4];
  uint32_t wsw[16][4];
  uint64_t own[4][2];
  float aq[16], av[16];
  int it = 0;

  if (tid == 224) {
    mbar_init(sb + B_KQ, 1); mbar_init(sb + B_V, 1); mbar_init(sb + B_W, 1); mbar_init(sb + B_X, 1); mbar_init(sb + B_X + 8, 1);
    mbar_init(sb + B_MEM, 128); mbar_init(sb + B_MEM + 8, 128);
    asm volatile("fence.mbarrier_init.release.cluster;" ::: "memory");
    mbar_expect_tx(sb + B_W, 3 * 65536);
    for (int i = 0; i < 4; i++) {
      tma2d(sb + R_X + i * 16384, &maps.wq, h * DH + 32 * j, i * 256, sb + B_W);
      tma2d(sb + R_WO + i * 16384, &maps.wk, h * DH + 32 * j, i * 256, sb + B_W);
    }
    for (int i = 0; i < 2; i++) tma2d(sb + R_WV + i * 32768, &maps.wv, h * DH + 64 * (j >> 1), jh * 512 + i * 256, sb + B_W);
    for (int i = 0; i < 4; i++) asm volatile("cp.async.bulk.prefetch.L2.global [%0], 8192;" :: "l"(xin + role * 16384 + i * 4096) : "memory");
    for (int i = 0; i < 4; i++)
      asm volatile("cp.async.bulk.prefetch.tensor.2d.L2.global [%0, {%1, %2}];" :: "l"(&maps.wo), "r"(256 * j + 64 * i), "r"(h * DH) : "memory");
  }
  const int kq = 2 * ((w4 >> 1) ^ jh) + wg;
#pragma unroll
  for (int i = 0; i < 4; i++)
#pragma unroll
    for (int r = 0; r < 2; r++) {
      const uint32_t* mp = reinterpret_cast<const uint32_t*>(mem0 + g * DM + 256 * kq + 128 * (w4 & 1) + 32 * i + 16 * r + 2 * t);
      own[i][r] = (uint64_t)__ldg(mp) | ((uint64_t)__ldg(mp + 4) << 32);
    }
  __syncthreads();
  mbar_spin(sb + B_W, 0, it);
  const int lrow = (lane & 7) + ((lane >> 4) << 3), lhi = (lane >> 3) & 1;
  {
    const int chunk = w4 < 2 ? w4 + 2 * lhi : 2 * (w4 & 1) + lhi;
    const uint32_t a = sb + (w4 < 2 ? R_X : R_WO) + wg * 16384 + lrow * 64 + ((chunk ^ ((lrow >> 1) & 3)) << 4);
#pragma unroll
    for (int ks = 0; ks < 32; ks++) ldsm4t(wqk[ks], a + ((ks >> 4) ^ jh) * 32768 + (ks & 15) * 1024);
  }
  const uint32_t L16 = pin(lane * 16);
  const uint32_t aWv = pin(sb + R_WV + wg * 32768 + lrow * 128 + (((2 * w4 + lhi) ^ (lane & 7)) << 4));
  const uint32_t aWo = pin(sb + R_WO + (warp >> 1) * 16384 + lrow * 128 + (((4 * (warp & 1) + lhi) ^ (lane & 7)) << 4));
  const uint32_t uMem = uni(sb + R_X + 32768 + jh * 16384 + warp * 512);
  const uint32_t uPark = uni(sb + R_X + (1 - jh) * 16384 + w4 * 512);
  const uint32_t uStage = uni(sb + R_X + 32768 + (1 - jh) * 16384);
  const uint32_t dB = uni(((sb + R_X + wg * 32768 + jh * 16384) >> 4) | 0x10000u);
  const uint32_t uBx = uni(sb + B_X + 8 * wg);
  auto load_wo = [&]() {
#pragma unroll
    for (int i = 0; i < 16; i++) ldsm4t(wsw[i], (aWo ^ ((i & 1) << 5)) + (i >> 1) * 2048);
  };
  auto issue_x = [&](int n) {
    for (int i = 0; i < 2; i++) { mbar_expect_tx(sb + B_X + 8 * i, 32768); tma4d(sb + R_X + i * 32768, &maps.x, n * SEG, 4 * i, sb + B_X + 8 * i); }
  };
  auto store_stage = [&](int n) {
    asm volatile("cp.async.bulk.global.shared::cta.bulk_group [%0], [%1], 8192; cp.async.bulk.commit_group;" :: "l"(g_kqv[n & 1][role]), "r"(uStage) : "memory");
  };
  auto issue_kqv = [&](int n) {
    const int p = (n & 1) * 128 + 4 * h;
    mbar_expect_tx(sb + B_KQ, 10240); tma3d(sb + R_K, &maps.k, 0, p, sb + B_KQ); tma3d(sb + R_Q, &maps.q, 8 + 2 * j, p, sb + B_KQ);
    mbar_expect_tx(sb + B_V, 16384); tma3d(sb + R_V, &maps.v, 16, p, sb + B_V);
  };
  auto load_wv = [&]() {
#pragma unroll
    for (int i = 0; i < 16; i++) ldsm4t(wsw[i], aWv + i * 2048);
  };
  auto x_qk = [&](int n) {
    mbar_spin(uBx, n & 1, it);
    wg_fence();
    sfor<0, 32>([&](auto I) {
      constexpr int i = decltype(I)::value;
      wg_rs32<((i & 15) >> 2) * 256 + (i & 3) * 2, (i > 0)>(aq, wqk[i ^ 16], i < 16 ? dB ^ 1024 : dB);
    });
    wg_commit();
  };
  auto x_v = [&]() {
    wg_fence();
    sfor<0, 16>([&](auto I) { constexpr int i = decltype(I)::value; wg_rs32<(i >> 2) * 256 + (i & 3) * 2, (i > 0)>(av, wsw[i], dB); });
    wg_commit();
  };
  auto park = [&](const float (&a)[16], int off) {
#pragma unroll
    for (int i = 0; i < 4; i++)
      sts128(uPark + L16 + off + i * 2048, __float_as_uint(a[4 * i]), __float_as_uint(a[4 * i + 1]), __float_as_uint(a[4 * i + 2]), __float_as_uint(a[4 * i + 3]));
  };
  auto fin_qk = [&]() {
    uint32_t r[2][4];
#pragma unroll
    for (int i = 0; i < 4; i++) {
      const float4 p = lds128f(uPark + L16 + i * 2048);
      r[0][i] = pack2(aq[4 * i] + p.x, aq[4 * i + 1] + p.y); r[1][i] = pack2(aq[4 * i + 2] + p.z, aq[4 * i + 3] + p.w);
    }
    const uint32_t a = uStage + (w4 < 2 ? 2048 + w4 * 128 : (w4 & 1) * 256) + (L16 & 112) + (L16 >> 7) * 512;
    stsm4t(a, r[0][0], r[0][1], r[0][2], r[0][3]);
    stsm4t(a + (w4 < 2 ? 256 : 128), r[1][0], r[1][1], r[1][2], r[1][3]);
  };
  auto fin_v = [&]() {
#pragma unroll
    for (int a = 0; a < 2; a++) {
      const float4 p = lds128f(uPark + L16 + 8192 + a * 4096), q = lds128f(uPark + L16 + 8192 + a * 4096 + 2048);
      sts128(uStage + 4096 + w4 * 1024 + a * 512 + L16, pack2(av[8 * a] + p.x, av[8 * a + 1] + p.y), pack2(av[8 * a + 2] + p.z, av[8 * a + 3] + p.w),
             pack2(av[8 * a + 4] + q.x, av[8 * a + 5] + q.y), pack2(av[8 * a + 6] + q.z, av[8 * a + 7] + q.w));
    }
  };
  __syncthreads();
  if (tid == 224) {
    fence_async();
    issue_x(0);
    mbar_expect_tx(sb + B_W, 65536);
    for (int i = 0; i < 4; i++) tma2d(sb + R_WO + i * 16384, &maps.wo, 256 * j + 64 * i, h * DH, sb + B_W);
  }
  __syncwarp();
  load_wv();
#pragma unroll 1
  for (int n = 0; n < 2; n++) {
    x_qk(n); x_v();
    wg_wait<0>(); keep(aq); keep(av);
    __syncthreads();
    if (wg == 0) park(aq, 0); else park(av, 8192);
    __syncthreads();
    if (wg == 0) fin_v(); else fin_qk();
    fence_async();
    __syncthreads();
    if (tid == 224) {
      store_stage(n);
      if (n == 0) {
        asm volatile("cp.async.bulk.wait_group.read 0;" ::: "memory");
        issue_x(1);
        asm volatile("cp.async.bulk.wait_group 0;" ::: "memory");
        __threadfence(); atomicAdd(&g_x.ctr[h], 1u);
      } else {
        for (int k = 0; *reinterpret_cast<volatile unsigned*>(&g_x.ctr[h]) < 4 && k < SPIN_LIMIT; k++) {}
        __threadfence(); asm volatile("fence.proxy.async;" ::: "memory");
        issue_kqv(0);
      }
    }
    __syncwarp();
  }
  mbar_spin(sb + B_W, 1, it);

  const float sc = 0.08838834764831845f * 1.4426950408889634f;
  uint8_t* const xb = reinterpret_cast<uint8_t*>(&g_x);
  uint8_t* const xa = xb + uni(h * 16384);
  const uint32_t uAq = uni((w4 >> 1) * 2048 + j * 512 + (w4 & 1) * 8), uAv = uni(8192 + (4 * (j >> 1) + w4) * 512 + jh * 8);
  const uint32_t uBar = uni(sb + B_MEM + 8 * wg);
  const uint32_t uRed = uni(uStage + 8192 + w4 * 512), uKw = uni(sb + R_K + w4 * 2048);
  const uint32_t bofs = pin(offsetof(Xchg, B) + ((4 * warp + t) * 4 + j) * 8192 + (g >> 1) * 1024 + h * 32 + (g & 1) * 16);
  const uint32_t uC = uni(offsetof(Xchg, C) + kq * 8192 + (w4 & 1) * 2048);

#pragma unroll 1
  for (int s = 0;; s++) {
    const uint32_t tag = (s + 1) & 1, T = tag << 16;
    TS(0);
#pragma unroll
    for (int i = 0; i < 4; i++) sts2(uMem + L16 + i * 4096, own[i]);
    mbar_arrive(uBar);
    float c[4][4];
    zero(c);
    {
      const uint32_t a = uMem + L16;
      if (w4 < 2) { if (w4 == 0) qk_gemm<0>(wqk, own, a, c, uBar, s & 1, it); else qk_gemm<1>(wqk, own, a, c, uBar, s & 1, it); }
      else { if (w4 == 2) qk_gemm<2>(wqk, own, a, c, uBar, s & 1, it); else qk_gemm<3>(wqk, own, a, c, uBar, s & 1, it); }
    }
#pragma unroll
    for (int i = 0; i < 4; i++) c[0][i] = (c[0][i] + c[1][i]) + (c[2][i] + c[3][i]);
    TS(1);
    if (wg == 0) {
      bar_sync(8 + w4, 64);
      const float4 o4 = lds128f(uRed + L16);
      const uint32_t r0 = movm(pack2(c[0][0] + o4.x, c[0][1] + o4.y)), r1 = movm(pack2(c[0][2] + o4.z, c[0][3] + o4.w));
      stx64(xa + uAq + L16, (r0 & ~1u) | tag, r1);
    } else {
      sts128(uRed + L16, __float_as_uint(c[0][0]), __float_as_uint(c[0][1]), __float_as_uint(c[0][2]), __float_as_uint(c[0][3]));
      bar_arrive(8 + w4, 64);
    }
    unsigned tpub = clk();
    TS(2);
    {
      uint64_t b[8][2];
#pragma unroll
      for (int i = 0; i < 8; i++) lds2(b[i], uMem - w4 * 512 + L16 + (i >> 2) * 512 + (i & 3) * 4096);
      zero(c);
#pragma unroll
      for (int i = 0; i < 16; i++) mma_b(c[i & 3], wsw[i], b[i >> 1][i & 1]);
#pragma unroll
      for (int i = 0; i < 4; i++) c[0][i] = (c[0][i] + c[1][i]) + (c[2][i] + c[3][i]);
    }

    auto load_v = [&](uint32_t (&vf)[4][4]) {
      const uint32_t va = sb + R_V + (w4 >> 1) * 8192 + (w4 & 1) * 2048 + L16;
#pragma unroll
      for (int i = 0; i < 4; i++) {
        uint32_t p[4]; lds128(vf[i], va + i * 512); lds128(p, va + 4096 + i * 512);
#pragma unroll
        for (int e = 0; e < 4; e++) vf[i][e] = hadd2(vf[i][e], p[e]);
      }
    };
    auto attend = [&](uint32_t (&o)[4], const uint32_t (&vf)[4][4], const uint64_t (&vm)[2][2], uint32_t sa, bool isx) {
      float2 sv[5];
#pragma unroll
      for (int i = 0; i < 5; i++) sv[i] = lds64f(sa + i * 256);
      if (isx) {
#pragma unroll
        for (int i = 0; i < 4; i++) {
          if (8 * i + 2 * t > 8 * j + g) sv[i].x = -INFINITY;
          if (8 * i + 2 * t + 1 > 8 * j + g) sv[i].y = -INFINITY;
        }
      } else { sts2(uKw + L16, vm[0]); sts2(uKw + 512 + L16, vm[1]); }
      float m = fmaxf(fmaxf(fmaxf(sv[0].x, sv[0].y), fmaxf(sv[1].x, sv[1].y)), fmaxf(fmaxf(sv[2].x, sv[2].y), fmaxf(sv[3].x, sv[3].y)));
      m = fmaxf(m, fmaxf(sv[4].x, sv[4].y));
      m = fmaxf(m, __shfl_xor_sync(0xffffffffu, m, 1));
      m = fmaxf(m, __shfl_xor_sync(0xffffffffu, m, 2));
      const float ms = -m * sc;
#pragma unroll
      for (int i = 4; i >= 0; i--) { sv[i].x = ex2(fmaf(sv[i].x, sc, ms)); sv[i].y = ex2(fmaf(sv[i].y, sc, ms)); }
      float sum = ((sv[0].x + sv[0].y) + (sv[1].x + sv[1].y)) + ((sv[2].x + sv[2].y) + (sv[3].x + sv[3].y) + (sv[4].x + sv[4].y));
      float r = 1.f;
      if (isx) { sum += __shfl_xor_sync(0xffffffffu, sum, 1); sum += __shfl_xor_sync(0xffffffffu, sum, 2); r = rcp(sum); }
      uint32_t p[5];
#pragma unroll
      for (int i = 0; i < 5; i++) p[i] = isx ? pack2(sv[i].x * r, sv[i].y * r) : pack2(sv[i].x, sv[i].y);
      zero(c);
#pragma unroll
      for (int i = 0; i < 2; i++) mma16816(c[i], lo32(vm[i][0]), hi32(vm[i][0]), lo32(vm[i][1]), hi32(vm[i][1]), p[4], p[4]);
#pragma unroll
      for (int i = 0; i < 2; i++) mma_a(c[2 + i], vf[2 * i + 1], p[2], p[3]);
#pragma unroll
      for (int i = 0; i < 2; i++) mma_a(c[i], vf[2 * i], p[0], p[1]);
      if (!isx) sts32f(sb + R_SUM + (L16 >> 2), sum);
#pragma unroll
      for (int i = 0; i < 4; i++) o[i] = pack2(c[i >> 1][2 * (i & 1)] + c[2 + (i >> 1)][2 * (i & 1)], c[i >> 1][2 * (i & 1) + 1] + c[2 + (i >> 1)][2 * (i & 1) + 1]);
    };
    if (wg == 0) {
      bar_sync(12 + w4, 64);
      const float4 o4 = lds128f(uRed + 2048 + L16);
      stx64(xa + uAv + L16, pack2_tag(c[0][0] + o4.x, c[0][1] + o4.y, T), pack2(c[0][2] + o4.z, c[0][3] + o4.w));
      tpub = clk();
      TS(3);
      uint32_t vf[4][4];
      mbar_spin(sb + B_V, s & 1, it);
      load_v(vf);
      load_wo();
      const uint32_t sa = pin(sb + R_S + (L16 >> 1));
      const uint8_t* vsrc = xa + 8192 + w4 * 1024 + L16;
      uint64_t vm[2][2];
      delay_until(tpub + DLY_V);
      TS(4);
      ldx2(vm[0], vsrc); ldx2(vm[1], vsrc + 512);
      poll2(vm, vsrc, tag, it);
      TS(5);
      bar_sync(5, 256);
      uint32_t o[4];
      attend(o, vf, vm, sa, false);
      stsm4t(sb + R_O + w4 * 512 + L16, o[0], o[1], o[2], o[3]);
    } else {
      sts128(uRed + 2048 + L16, __float_as_uint(c[0][0]), __float_as_uint(c[0][1]), __float_as_uint(c[0][2]), __float_as_uint(c[0][3]));
      bar_arrive(12 + w4, 64);
      TS(3);
      const uint8_t* asrc = xa + L16;
      const uint32_t qa = sb + R_Q + (L16 & 112) + (L16 & 128) * 2 + (L16 >> 8) * 128;
      if (warp < 6) {
        mbar_spin(sb + B_KQ, s & 1, it);
        uint32_t kf[8][4];
        uint64_t q[4][2];
        const uint32_t ka = sb + R_K + w4 * 1024 + (L16 & 112) + (L16 & 128) * 4 + (L16 & 256);
#pragma unroll
        for (int i = 0; i < 8; i++) ldsm4(kf[i], ka + (i >> 1) * 2048 + (i & 1) * 128);
#pragma unroll
        for (int i = 0; i < 4; i++) ldsm4q(q[i], qa + i * 512);
        const uint32_t sa = pin(sb + R_S + w4 * 512 + t * 64 + g * 4);
        zero(c);
#pragma unroll
        for (int i = 0; i < 8; i++) mma_b(c[i & 3], kf[i], q[i >> 1][i & 1]);
        delay_until(tpub + DLY_A);
        TS(4);
#pragma unroll
        for (int i = 0; i < 4; i++) ldx2(q[i], asrc + i * 512);
#pragma unroll
        for (int i = 0; i < 4; i++) sts32f(sa + 1280 + (i & 1) * 32 + (i >> 1) * 256, (c[0][i] + c[1][i]) + (c[2][i] + c[3][i]));
        poll4(q, asrc, tag, it);
        TS(5);
        zero(c);
#pragma unroll
        for (int i = 0; i < 8; i++) mma_b(c[i & 3], kf[i], q[i >> 1][i & 1]);
#pragma unroll
        for (int i = 0; i < 4; i++) sts32f(sa + (i & 1) * 32 + (i >> 1) * 256, (c[0][i] + c[1][i]) + (c[2][i] + c[3][i]));
        bar_arrive(5, 256);
      } else if (warp == 6) {
        uint64_t qk[8][2], q[4][2];
        const uint32_t sa = pin(sb + R_S + 1024 + t * 64 + g * 4);
        delay_until(tpub + DLY_A);
        TS(4);
#pragma unroll
        for (int i = 0; i < 8; i++) ldx2(qk[i], asrc + i * 512);
        mbar_spin(sb + B_KQ, s & 1, it);
#pragma unroll
        for (int i = 0; i < 4; i++) ldsm4q(q[i], qa + i * 512);
        poll8(qk, asrc, tag, it);
        TS(5);
        zero(c);
#pragma unroll
        for (int i = 0; i < 8; i++) mma_bb(c[i & 3], qk[4 + (i >> 1)], qk[i >> 1][i & 1]);
#pragma unroll
        for (int i = 0; i < 2; i++) sts32f(sa + i * 32, (c[0][i] + c[1][i + 2]) + (c[2][i] + c[3][i + 2]));
        bar_arrive(5, 256);
        zero(c);
#pragma unroll
        for (int i = 0; i < 8; i++) mma_bb(c[i & 3], qk[4 + (i >> 1)], q[i >> 1][i & 1]);
#pragma unroll
        for (int i = 0; i < 2; i++) sts32f(sa + 1280 + i * 32, (c[0][i] + c[1][i + 2]) + (c[2][i] + c[3][i + 2]));
      }
      TS(6);
      load_wo();
      if (warp == 7) {
        if (lane == 0) { asm volatile("cp.async.bulk.wait_group 0;" ::: "memory"); fence_async(); }
        __syncwarp();
        bar_sync(5, 256);
        if (lane == 0 && s + 1 < NSEG) issue_x(s + 2);
        __syncwarp();
      }
    }
    TS(7);
    bar_sync(6, 256);
    if (s + 1 < NSEG) {
      uint64_t b[4][2];
#pragma unroll
      for (int i = 0; i < 4; i++) ldsm4q(b[i], sb + R_O + i * 512 + L16);
      const float4 s0 = lds128f(sb + R_SUM + ((L16 << 1) & 96)), s1 = lds128f(sb + R_SUM + 16 + ((L16 << 1) & 96));
      zero(c);
#pragma unroll
      for (int i = 0; i < 16; i++) mma_b(c[i & 3], wsw[i], b[i >> 2][(i >> 1) & 1]);
      const float r0 = rcp((s0.x + s0.y) + (s0.z + s0.w)), r1 = rcp((s1.x + s1.y) + (s1.z + s1.w));
      stx128(xb + bofs, pack2_tag((c[0][0] + c[2][0]) * r0, (c[0][1] + c[2][1]) * r1, T), pack2((c[0][2] + c[2][2]) * r0, (c[0][3] + c[2][3]) * r1),
             pack2((c[1][0] + c[3][0]) * r0, (c[1][1] + c[3][1]) * r1), pack2((c[1][2] + c[3][2]) * r0, (c[1][3] + c[3][3]) * r1));
    }
    const unsigned tb = clk();
    TS(8);
    if (wg == 1) {
      uint32_t vf[4][4], o[4];
      uint64_t vm[2][2];
      load_v(vf);
      lds2(vm[0], uKw + L16); lds2(vm[1], uKw + 512 + L16);
      attend(o, vf, vm, sb + R_S + 1280 + (L16 >> 1), true);
      stsm4t(uKw + 1024 + (lane & 7) * 80 + (lane >> 3) * 16, o[0], o[1], o[2], o[3]);
      __syncwarp();
      uint32_t v[4]; lds128(v, uKw + 1024 + g * 80 + t * 16);
      load_wv();
      *reinterpret_cast<uint4*>(&g_ox[(size_t)(s * SEG + 8 * j + g) * HD + h * DH + 32 * w4 + 8 * t]) = make_uint4(v[0], v[1], v[2], v[3]);
    }
    if (s + 1 == NSEG) break;
    TS(9);
    x_qk(s);
    TS(10);
    const uint8_t* src = xb + uC + L16;
    auto gather = [&](uint32_t tc) {
      delay_until(tc + DLY_C);
      TS(14);
#pragma unroll
      for (int i = 0; i < 4; i++) ldxb(own[i], src + i * 512);
      bar_sync(3, 256);
    };
    if (wg == 0) {
      uint32_t bv[8];
      const uint8_t* bsrc = xb + uni(offsetof(Xchg, B) + role * 8192 + w4 * 1024) + (L16 >> 2);
      delay_until(tb + DLY_B);
#pragma unroll
      for (int i = 0; i < 8; i++) asm volatile("ld.relaxed.gpu.global.b32 %0, [%1];" : "=r"(bv[i]) : "l"(bsrc + i * 128) : "memory");
      wg_wait<0>(); keep(aq);
      bar_sync(2, 128);
      park(aq, 0);
      load_wv();
      const uint32_t cofs = pin(offsetof(Xchg, C) + j * 8192 + (L16 >> 8) * 4096 + h * 128 + (L16 & 128) / 2 + w4 * 16 + (L16 & 48) / 4 + (L16 & 64) / 32);
      const uint32_t first = pin((L16 & 112) == 0);
      TS(11);
      poll8_w(bv, bsrc, tag, (L16 & 48) == 0, it);
      TS(12);
      float lo[8], hi[8];
#pragma unroll
      for (int i = 0; i < 8; i++) { lo[i] = __uint_as_float(bv[i] << 16); hi[i] = __uint_as_float(bv[i] & 0xFFFF0000u); }
      const float l = ((lo[0] + lo[1]) + (lo[2] + lo[3])) + ((lo[4] + lo[5]) + (lo[6] + lo[7]));
      const float u = ((hi[0] + hi[1]) + (hi[2] + hi[3])) + ((hi[4] + hi[5]) + (hi[6] + hi[7]));
      float r = ((L16 & 128) ? u : l) + __shfl_xor_sync(0xffffffffu, (L16 & 128) ? l : u, 8);
      r += __shfl_xor_sync(0xffffffffu, r, 16);
      const uint32_t e = ((__float_as_uint(r) + (first ? 0x10000u - T : 0x8000u)) >> 16 & ~first) | (tag & first);
      asm volatile("st.relaxed.gpu.global.b16 [%0], %1;" :: "l"(xb + cofs), "h"((uint16_t)e) : "memory");
      const uint32_t tc = clk();
      sts32(sb + B_TC, tc);
      bar_arrive(7, 256);
      TS(13);
      x_v();
      gather(tc);
      wg_wait<0>(); keep(av);
      fin_v();
      bar_arrive(1, 160);
    } else {
      x_v();
      TS(11);
      wg_wait<1>(); keep(aq);
      bar_sync(7, 256);
      const uint32_t tc = lds32(sb + B_TC);
      fin_qk();
      wg_wait<0>(); keep(av);
      park(av, 8192);
      TS(13);
      gather(tc);
      if (warp == 7) {
        bar_sync(1, 160);
        delay_until(tc + DLY_K);
        if (lane == 0) { issue_kqv(s + 1); fence_async(); store_stage(s); }
        __syncwarp();
      }
    }
    TS(15);
    poll4_b128(own, src, tag, it);
  }
  if (it > SPIN_LIMIT) g_err = 2;
}

typedef CUresult (*EncodeFn)(CUtensorMap*, CUtensorMapDataType, cuuint32_t, void*, const cuuint64_t*, const cuuint64_t*, const cuuint32_t*,
                             const cuuint32_t*, CUtensorMapInterleave, CUtensorMapSwizzle, CUtensorMapL2promotion, CUtensorMapFloatOOBfill);
static void make_map(EncodeFn fn, CUtensorMap* m, const void* p, uint64_t cols, uint64_t rows, uint64_t pitch, uint32_t bc, uint32_t br, CUtensorMapSwizzle sw) {
  cuuint64_t dims[2] = {cols, rows}, strides[1] = {pitch * 2};
  cuuint32_t box[2] = {bc, br}, es[2] = {1, 1};
  fn(m, CU_TENSOR_MAP_DATA_TYPE_BFLOAT16, 2, const_cast<void*>(p), dims, strides, box, es, CU_TENSOR_MAP_INTERLEAVE_NONE, sw,
     CU_TENSOR_MAP_L2_PROMOTION_L2_256B, CU_TENSOR_MAP_FLOAT_OOB_FILL_NONE);
}

extern "C" void kernel_launch(void* const* d_in, const int* in_sizes, int n_in, void* d_out, int out_size) {
  const bf16* Ax = (const bf16*)d_in[0]; const bf16* mem0 = (const bf16*)d_in[1];
  const bf16* Wq = (const bf16*)d_in[2]; const bf16* Wk = (const bf16*)d_in[3]; const bf16* Wv = (const bf16*)d_in[4];
  const bf16* Wo = (const bf16*)d_in[5];
  const bf16* Bx = (const bf16*)d_in[7]; const bf16* wr = (const bf16*)d_in[8]; const bf16* wi = (const bf16*)d_in[9];
  bf16* out = (bf16*)d_out;

  void* fp = nullptr; cudaDriverEntryPointQueryResult qr;
  cudaGetDriverEntryPoint("cuTensorMapEncodeTiled", &fp, cudaEnableDefault, &qr);
  EncodeFn fn = (EncodeFn)fp;
  void *kqv, *ox;
  cudaGetSymbolAddress(&kqv, g_kqv); cudaGetSymbolAddress(&ox, g_ox);
  const CUtensorMapSwizzle S128 = CU_TENSOR_MAP_SWIZZLE_128B, S64 = CU_TENSOR_MAP_SWIZZLE_64B;

  GemmMaps m3; RecMaps mr;
  make_map(fn, &m3.a, ox, HD, S_LEN, HD, 64, 128, S128);
  make_map(fn, &m3.b[0], Wo, DM, HD, DM, 64, 64, S128);
  m3.b[1] = m3.b[0]; m3.b[2] = m3.b[0];
  make_map(fn, &m3.c, out, DM, S_LEN, 2 * DM, 64, 64, S128);
  make_map(fn, &mr.wq, Wq, HD, DM, HD, 32, 256, S64);
  make_map(fn, &mr.wk, Wk, HD, DM, HD, 32, 256, S64);
  make_map(fn, &mr.wv, Wv, HD, DM, HD, 64, 256, S128);
  make_map(fn, &mr.wo, Wo, DM, HD, DM, 64, 128, S128);
  {
    cuuint64_t dims[4] = {64, S_LEN, 8, 2}, strides[3] = {DM * 2, 128, 1024};
    cuuint32_t box[4] = {64, 32, 4, 2}, es[4] = {1, 1, 1, 1};
    fn(&mr.x, CU_TENSOR_MAP_DATA_TYPE_BFLOAT16, 4, const_cast<bf16*>(Ax), dims, strides, box, es, CU_TENSOR_MAP_INTERLEAVE_NONE, S128,
       CU_TENSOR_MAP_L2_PROMOTION_L2_256B, CU_TENSOR_MAP_FLOAT_OOB_FILL_NONE);
  }
  for (int i = 0; i < 3; i++) {
    cuuint64_t dims[3] = {128, 32, 256}, strides[2] = {256, 8192};
    cuuint32_t box[3] = {128, i == 0 ? 8u : i == 1 ? 2u : 16u, 4}, es[3] = {1, 1, 1};
    fn(i == 0 ? &mr.k : i == 1 ? &mr.q : &mr.v, CU_TENSOR_MAP_DATA_TYPE_BFLOAT16, 3, kqv, dims, strides, box, es, CU_TENSOR_MAP_INTERLEAVE_NONE,
       CU_TENSOR_MAP_SWIZZLE_NONE, CU_TENSOR_MAP_L2_PROMOTION_L2_256B, CU_TENSOR_MAP_FLOAT_OOB_FILL_NONE);
  }
  {
    cuuint64_t dims[3] = {64, 16, S_LEN}, strides[2] = {128, 2 * DM * 2};
    cuuint32_t box[3] = {64, 16, 2}, es[3] = {1, 1, 1};
    fn(&mr.fo, CU_TENSOR_MAP_DATA_TYPE_BFLOAT16, 3, out + DM, dims, strides, box, es, CU_TENSOR_MAP_INTERLEAVE_NONE, S128,
       CU_TENSOR_MAP_L2_PROMOTION_NONE, CU_TENSOR_MAP_FLOAT_OOB_FILL_NONE);
  }
  constexpr int SM3 = 6 * 32768 + 32768 + 256 + 1024;
  cudaFuncSetAttribute(gemm_kernel<128, 6>, cudaFuncAttributeMaxDynamicSharedMemorySize, SM3);
  cudaFuncSetAttribute(rec_kernel, cudaFuncAttributeMaxDynamicSharedMemorySize, R_TOTAL);

  cudaStream_t st = cudaStreamPerThread;
  cudaFuncSetAttribute(fft_pre_kernel, cudaFuncAttributeMaxDynamicSharedMemorySize, F_SMEM);
  fft_pre_kernel<<<128, 256, F_SMEM, st>>>(Bx, wr, wi);
  rec_kernel<<<132, 256, R_TOTAL, st>>>(mr, Ax, mem0);
  gemm_kernel<128, 6><<<128, 384, SM3, st>>>(m3, 16, 8, 64, 8, 1);
}
```

```cpp
#include <cuda_runtime.h>
#include <cuda_bf16.h>
#include <cuda.h>
#include <stdint.h>
#include <stddef.h>
#include <type_traits>

typedef __nv_bfloat16 bf16;

constexpr int S_LEN = 2048, DM = 1024, NH = 32, DH = 128, MEM = 8, SEG = 32, NSEG = 64;
constexpr int HD = NH * DH;
constexpr int SPIN_LIMIT = 1 << 20;

__device__ __align__(1024) uint4 g_kqv[4][128][512];
__device__ __align__(1024) bf16 g_ox[(size_t)S_LEN * HD];
struct Xchg {
  uint4 A[32][2][2][256];
  uint4 C[4][2][256];
  uint4 B[128][2][256];
  unsigned ctr[64];
};
__device__ __align__(8192) Xchg g_x;
__device__ __align__(1024) uint4 g_y[1024 * 256];
__device__ __align__(1024) uint4 g_wt[513 * 512];
__device__ int g_err;

__device__ __forceinline__ unsigned clk() { unsigned long long c; asm volatile("mov.u64 %0, %%clock64;" : "=l"(c)); return (unsigned)c; }
__device__ __forceinline__ uint32_t smem_u32(const void* p) { return (uint32_t)__cvta_generic_to_shared(p); }
__device__ __forceinline__ void mbar_init(uint32_t bar, int cnt) { asm volatile("mbarrier.init.shared::cta.b64 [%0], %1;" :: "r"(bar), "r"(cnt) : "memory"); }
__device__ __forceinline__ void mbar_expect_tx(uint32_t bar, int bytes) { asm volatile("mbarrier.arrive.expect_tx.shared::cta.b64 _, [%0], %1;" :: "r"(bar), "r"(bytes) : "memory"); }
__device__ __forceinline__ void mbar_arrive(uint32_t bar) { asm volatile("mbarrier.arrive.shared::cta.b64 _, [%0];" :: "r"(bar) : "memory"); }
__device__ __forceinline__ void mbar_arrive_cluster(uint32_t bar, int cta) {
  asm volatile("{.reg .b32 r; mapa.shared::cluster.u32 r, %0, %1; mbarrier.arrive.shared::cluster.b64 _, [r];}" :: "r"(bar), "r"(cta) : "memory"); }
__device__ __forceinline__ bool mbar_try(uint32_t bar, int par) {
  uint32_t ok; asm volatile("{.reg .pred p; mbarrier.try_wait.parity.shared::cta.b64 p, [%1], %2; selp.u32 %0, 1, 0, p;}" : "=r"(ok) : "r"(bar), "r"(par) : "memory"); return ok; }
__device__ __forceinline__ void mbar_wait(uint32_t bar, int par) {
  int it = 0;
  while (!mbar_try(bar, par)) { if (++it > SPIN_LIMIT) { g_err = 1; break; } }
}
__device__ __forceinline__ void tma2d(uint32_t dst, const CUtensorMap* m, int c0, int c1, uint32_t bar) {
  asm volatile("cp.async.bulk.tensor.2d.shared::cluster.global.mbarrier::complete_tx::bytes [%0], [%1, {%3, %4}], [%2];"
    :: "r"(dst), "l"(m), "r"(bar), "r"(c0), "r"(c1) : "memory"); }
__device__ __forceinline__ void tma2d_mc(uint32_t dst, const CUtensorMap* m, int c0, int c1, uint32_t bar, uint16_t mask) {
  asm volatile("cp.async.bulk.tensor.2d.shared::cluster.global.mbarrier::complete_tx::bytes.multicast::cluster [%0], [%1, {%3, %4}], [%2], %5;"
    :: "r"(dst), "l"(m), "r"(bar), "r"(c0), "r"(c1), "h"(mask) : "memory"); }
__device__ __forceinline__ void tma2d_store(const CUtensorMap* m, uint32_t src, int c0, int c1) {
  asm volatile("cp.async.bulk.tensor.2d.global.shared::cta.bulk_group [%0, {%2, %3}], [%1];" :: "l"(m), "r"(src), "r"(c0), "r"(c1) : "memory"); }
__device__ __forceinline__ void fence_async() { asm volatile("fence.proxy.async.shared::cta;" ::: "memory"); }
__device__ __forceinline__ void bar_sync(int id, int n) { asm volatile("bar.sync %0, %1;" :: "r"(id), "r"(n) : "memory"); }
__device__ __forceinline__ void bar_arrive(int id, int n) { asm volatile("bar.arrive %0, %1;" :: "r"(id), "r"(n) : "memory"); }
__device__ __forceinline__ uint32_t pack2(float lo, float hi) { uint32_t r; asm("cvt.rn.bf16x2.f32 %0, %1, %2;" : "=r"(r) : "f"(hi), "f"(lo)); return r; }
__device__ __forceinline__ uint32_t pack2_tag(float lo, float hi, uint32_t T) {
  uint32_t u = ((__float_as_uint(lo) - T + 0x10000u) & 0xFFFE0000u) + T;
  return __byte_perm(u, pack2(0.f, hi), 0x7632); }
__device__ __forceinline__ void ldsm4(uint32_t (&r)[4], uint32_t a) {
  asm volatile("ldmatrix.sync.aligned.m8n8.x4.shared.b16 {%0,%1,%2,%3}, [%4];" : "=r"(r[0]), "=r"(r[1]), "=r"(r[2]), "=r"(r[3]) : "r"(a) : "memory"); }
__device__ __forceinline__ void ldsm4t(uint32_t (&r)[4], uint32_t a) {
  asm volatile("ldmatrix.sync.aligned.m8n8.x4.trans.shared.b16 {%0,%1,%2,%3}, [%4];" : "=r"(r[0]), "=r"(r[1]), "=r"(r[2]), "=r"(r[3]) : "r"(a) : "memory"); }
__device__ __forceinline__ void stsm4(uint32_t a, uint32_t r0, uint32_t r1, uint32_t r2, uint32_t r3) {
  asm volatile("stmatrix.sync.aligned.m8n8.x4.shared.b16 [%0], {%1,%2,%3,%4};" :: "r"(a), "r"(r0), "r"(r1), "r"(r2), "r"(r3) : "memory"); }
__device__ __forceinline__ void stsm4t(uint32_t a, uint32_t r0, uint32_t r1, uint32_t r2, uint32_t r3) {
  asm volatile("stmatrix.sync.aligned.m8n8.x4.trans.shared.b16 [%0], {%1,%2,%3,%4};" :: "r"(a), "r"(r0), "r"(r1), "r"(r2), "r"(r3) : "memory"); }
__device__ __forceinline__ void lds128(uint32_t (&r)[4], uint32_t a) {
  asm volatile("ld.shared.v4.u32 {%0,%1,%2,%3}, [%4];" : "=r"(r[0]), "=r"(r[1]), "=r"(r[2]), "=r"(r[3]) : "r"(a) : "memory"); }
__device__ __forceinline__ float4 lds128f(uint32_t a) { float4 r;
  asm volatile("ld.shared.v4.f32 {%0,%1,%2,%3}, [%4];" : "=f"(r.x), "=f"(r.y), "=f"(r.z), "=f"(r.w) : "r"(a) : "memory"); return r; }
__device__ __forceinline__ float2 lds64f(uint32_t a) { float2 r;
  asm volatile("ld.shared.v2.f32 {%0,%1}, [%2];" : "=f"(r.x), "=f"(r.y) : "r"(a) : "memory"); return r; }
__device__ __forceinline__ void sts128(uint32_t a, uint32_t r0, uint32_t r1, uint32_t r2, uint32_t r3) {
  asm volatile("st.shared.v4.u32 [%0], {%1,%2,%3,%4};" :: "r"(a), "r"(r0), "r"(r1), "r"(r2), "r"(r3) : "memory"); }
__device__ __forceinline__ void sts64f(uint32_t a, float x, float y) { asm volatile("st.shared.v2.f32 [%0], {%1,%2};" :: "r"(a), "f"(x), "f"(y) : "memory"); }
__device__ __forceinline__ void sts32f(uint32_t a, float x) { asm volatile("st.shared.f32 [%0], %1;" :: "r"(a), "f"(x) : "memory"); }
__device__ __forceinline__ void mma16816(float (&d)[4], uint32_t a0, uint32_t a1, uint32_t a2, uint32_t a3, uint32_t b0, uint32_t b1) {
  asm volatile("mma.sync.aligned.m16n8k16.row.col.f32.bf16.bf16.f32 {%0,%1,%2,%3}, {%4,%5,%6,%7}, {%8,%9}, {%0,%1,%2,%3};"
    : "+f"(d[0]), "+f"(d[1]), "+f"(d[2]), "+f"(d[3]) : "r"(a0), "r"(a1), "r"(a2), "r"(a3), "r"(b0), "r"(b1)); }
__device__ __forceinline__ void mma1688(float (&d)[4], uint32_t a0, uint32_t a1, uint32_t b0) {
  asm volatile("mma.sync.aligned.m16n8k8.row.col.f32.bf16.bf16.f32 {%0,%1,%2,%3}, {%4,%5}, {%6}, {%0,%1,%2,%3};"
    : "+f"(d[0]), "+f"(d[1]), "+f"(d[2]), "+f"(d[3]) : "r"(a0), "r"(a1), "r"(b0)); }
__device__ __forceinline__ void ldx128(uint32_t (&r)[4], const void* p) {
  asm volatile("{.reg .b128 t; .reg .b64 a, b; ld.relaxed.gpu.global.b128 t, [%4]; mov.b128 {a, b}, t; mov.b64 {%0,%1}, a; mov.b64 {%2,%3}, b;}"
    : "=r"(r[0]), "=r"(r[1]), "=r"(r[2]), "=r"(r[3]) : "l"(p) : "memory"); }
__device__ __forceinline__ void ldx2x64(uint32_t (&r)[4], const void* p) {
  asm volatile("{.reg .b64 a, b; ld.relaxed.gpu.global.v2.b64 {a, b}, [%4]; mov.b64 {%0,%1}, a; mov.b64 {%2,%3}, b;}"
    : "=r"(r[0]), "=r"(r[1]), "=r"(r[2]), "=r"(r[3]) : "l"(p) : "memory"); }
__device__ __forceinline__ void stx128(void* p, uint32_t r0, uint32_t r1, uint32_t r2, uint32_t r3) {
  asm volatile("{.reg .b128 t; .reg .b64 a, b; mov.b64 a, {%1,%2}; mov.b64 b, {%3,%4}; mov.b128 t, {a, b}; st.relaxed.gpu.global.b128 [%0], t;}"
    :: "l"(p), "r"(r0), "r"(r1), "r"(r2), "r"(r3) : "memory"); }
__device__ __forceinline__ void stx64(void* p, uint32_t r0, uint32_t r1) {
  asm volatile("{.reg .b64 a; mov.b64 a, {%1,%2}; st.relaxed.gpu.global.b64 [%0], a;}" :: "l"(p), "r"(r0), "r"(r1) : "memory"); }
__device__ __forceinline__ uint32_t uni(uint32_t x) { return __shfl_sync(0xffffffffu, x, 0); }
__device__ __forceinline__ uint32_t pin(uint32_t x) { return __shfl_xor_sync(0xffffffffu, x, 0); }
__device__ __forceinline__ float ex2(float x) { float r; asm("ex2.approx.ftz.f32 %0, %1;" : "=f"(r) : "f"(x)); return r; }
__device__ __forceinline__ void wg_fence() { asm volatile("wgmma.fence.sync.aligned;" ::: "memory"); }
__device__ __forceinline__ void wg_commit() { asm volatile("wgmma.commit_group.sync.aligned;" ::: "memory"); }
template <int N> __device__ __forceinline__ void wg_wait() { asm volatile("wgmma.wait_group.sync.aligned %0;" :: "n"(N) : "memory"); }

__device__ __forceinline__ void wgmma_ss_n256_tb1(float (&d)[128], uint64_t da, uint64_t db, int sc) {
  asm volatile("{.reg .pred p; setp.ne.b32 p, %130, 0;\n"
    "wgmma.mma_async.sync.aligned.m64n256k16.f32.bf16.bf16 {%0,%1,%2,%3,%4,%5,%6,%7,%8,%9,%10,%11,%12,%13,%14,%15,%16,%17,%18,%19,%20,%21,%22,%23,%24,%25,%26,%27,%28,%29,%30,%31,%32,%33,%34,%35,%36,%37,%38,%39,%40,%41,%42,%43,%44,%45,%46,%47,%48,%49,%50,%51,%52,%53,%54,%55,%56,%57,%58,%59,%60,%61,%62,%63,%64,%65,%66,%67,%68,%69,%70,%71,%72,%73,%74,%75,%76,%77,%78,%79,%80,%81,%82,%83,%84,%85,%86,%87,%88,%89,%90,%91,%92,%93,%94,%95,%96,%97,%98,%99,%100,%101,%102,%103,%104,%105,%106,%107,%108,%109,%110,%111,%112,%113,%114,%115,%116,%117,%118,%119,%120,%121,%122,%123,%124,%125,%126,%127}, %128, %129, p, 1, 1, 0, 1;}\n"
    : "+f"(d[0]),"+f"(d[1]),"+f"(d[2]),"+f"(d[3]),"+f"(d[4]),"+f"(d[5]),"+f"(d[6]),"+f"(d[7]),"+f"(d[8]),"+f"(d[9]),"+f"(d[10]),"+f"(d[11]),"+f"(d[12]),"+f"(d[13]),"+f"(d[14]),"+f"(d[15]),"+f"(d[16]),"+f"(d[17]),"+f"(d[18]),"+f"(d[19]),"+f"(d[20]),"+f"(d[21]),"+f"(d[22]),"+f"(d[23]),"+f"(d[24]),"+f"(d[25]),"+f"(d[26]),"+f"(d[27]),"+f"(d[28]),"+f"(d[29]),"+f"(d[30]),"+f"(d[31]),"+f"(d[32]),"+f"(d[33]),"+f"(d[34]),"+f"(d[35]),"+f"(d[36]),"+f"(d[37]),"+f"(d[38]),"+f"(d[39]),"+f"(d[40]),"+f"(d[41]),"+f"(d[42]),"+f"(d[43]),"+f"(d[44]),"+f"(d[45]),"+f"(d[46]),"+f"(d[47]),"+f"(d[48]),"+f"(d[49]),"+f"(d[50]),"+f"(d[51]),"+f"(d[52]),"+f"(d[53]),"+f"(d[54]),"+f"(d[55]),"+f"(d[56]),"+f"(d[57]),"+f"(d[58]),"+f"(d[59]),"+f"(d[60]),"+f"(d[61]),"+f"(d[62]),"+f"(d[63]),"+f"(d[64]),"+f"(d[65]),"+f"(d[66]),"+f"(d[67]),"+f"(d[68]),"+f"(d[69]),"+f"(d[70]),"+f"(d[71]),"+f"(d[72]),"+f"(d[73]),"+f"(d[74]),"+f"(d[75]),"+f"(d[76]),"+f"(d[77]),"+f"(d[78]),"+f"(d[79]),"+f"(d[80]),"+f"(d[81]),"+f"(d[82]),"+f"(d[83]),"+f"(d[84]),"+f"(d[85]),"+f"(d[86]),"+f"(d[87]),"+f"(d[88]),"+f"(d[89]),"+f"(d[90]),"+f"(d[91]),"+f"(d[92]),"+f"(d[93]),"+f"(d[94]),"+f"(d[95]),"+f"(d[96]),"+f"(d[97]),"+f"(d[98]),"+f"(d[99]),"+f"(d[100]),"+f"(d[101]),"+f"(d[102]),"+f"(d[103]),"+f"(d[104]),"+f"(d[105]),"+f"(d[106]),"+f"(d[107]),"+f"(d[108]),"+f"(d[109]),"+f"(d[110]),"+f"(d[111]),"+f"(d[112]),"+f"(d[113]),"+f"(d[114]),"+f"(d[115]),"+f"(d[116]),"+f"(d[117]),"+f"(d[118]),"+f"(d[119]),"+f"(d[120]),"+f"(d[121]),"+f"(d[122]),"+f"(d[123]),"+f"(d[124]),"+f"(d[125]),"+f"(d[126]),"+f"(d[127])
    : "l"(da), "l"(db), "r"(sc));
}

__device__ __forceinline__ void wgmma_ss_n128_tb1(float (&d)[64], uint64_t da, uint64_t db, int sc) {
  asm volatile("{.reg .pred p; setp.ne.b32 p, %66, 0;\n"
    "wgmma.mma_async.sync.aligned.m64n128k16.f32.bf16.bf16 {%0,%1,%2,%3,%4,%5,%6,%7,%8,%9,%10,%11,%12,%13,%14,%15,%16,%17,%18,%19,%20,%21,%22,%23,%24,%25,%26,%27,%28,%29,%30,%31,%32,%33,%34,%35,%36,%37,%38,%39,%40,%41,%42,%43,%44,%45,%46,%47,%48,%49,%50,%51,%52,%53,%54,%55,%56,%57,%58,%59,%60,%61,%62,%63}, %64, %65, p, 1, 1, 0, 1;}\n"
    : "+f"(d[0]),"+f"(d[1]),"+f"(d[2]),"+f"(d[3]),"+f"(d[4]),"+f"(d[5]),"+f"(d[6]),"+f"(d[7]),"+f"(d[8]),"+f"(d[9]),"+f"(d[10]),"+f"(d[11]),"+f"(d[12]),"+f"(d[13]),"+f"(d[14]),"+f"(d[15]),"+f"(d[16]),"+f"(d[17]),"+f"(d[18]),"+f"(d[19]),"+f"(d[20]),"+f"(d[21]),"+f"(d[22]),"+f"(d[23]),"+f"(d[24]),"+f"(d[25]),"+f"(d[26]),"+f"(d[27]),"+f"(d[28]),"+f"(d[29]),"+f"(d[30]),"+f"(d[31]),"+f"(d[32]),"+f"(d[33]),"+f"(d[34]),"+f"(d[35]),"+f"(d[36]),"+f"(d[37]),"+f"(d[38]),"+f"(d[39]),"+f"(d[40]),"+f"(d[41]),"+f"(d[42]),"+f"(d[43]),"+f"(d[44]),"+f"(d[45]),"+f"(d[46]),"+f"(d[47]),"+f"(d[48]),"+f"(d[49]),"+f"(d[50]),"+f"(d[51]),"+f"(d[52]),"+f"(d[53]),"+f"(d[54]),"+f"(d[55]),"+f"(d[56]),"+f"(d[57]),"+f"(d[58]),"+f"(d[59]),"+f"(d[60]),"+f"(d[61]),"+f"(d[62]),"+f"(d[63])
    : "l"(da), "l"(db), "r"(sc));
}

template <int BN> struct WG;
template <> struct WG<256> { static __device__ __forceinline__ void mma(float (&d)[128], uint64_t a, uint64_t b, int sc) { wgmma_ss_n256_tb1(d, a, b, sc); } };
template <> struct WG<128> { static __device__ __forceinline__ void mma(float (&d)[64], uint64_t a, uint64_t b, int sc) { wgmma_ss_n128_tb1(d, a, b, sc); } };

struct GemmMaps { CUtensorMap a, b[3], c; };
template <int BN, int STAGES>
__global__ void __cluster_dims__(2, 1, 1) __launch_bounds__(384, 1)
gemm_kernel(const __grid_constant__ GemmMaps maps, int tilesM, int tilesN, int kblocks, int nPerB, int clearX) {
  extern __shared__ __align__(1024) uint8_t smem_raw[];
  constexpr int STAGE_BYTES = 16384 + BN * 128;
  constexpr int NBOX = BN / 64;
  const uint32_t sbase = (smem_u32(smem_raw) + 1023) & ~1023u;
  const uint32_t sEpi = sbase + STAGES * STAGE_BYTES;
  const uint32_t sBar = sEpi + 32768;
  const int warp = threadIdx.x >> 5, lane = threadIdx.x & 31, wg = warp >> 2;
  uint32_t crank; asm("mov.u32 %0, %%cluster_ctarank;" : "=r"(crank));
  if (threadIdx.x == 0) {
    for (int i = 0; i < STAGES; i++) { mbar_init(sBar + 8 * i, 1); mbar_init(sBar + 8 * (STAGES + i), 4); }
    asm volatile("fence.mbarrier_init.release.cluster;" ::: "memory");
  }
  if (clearX) {
    uint4* p = reinterpret_cast<uint4*>(&g_x);
    for (int i = blockIdx.x * 384 + threadIdx.x; i < (int)(sizeof(Xchg) / 16); i += gridDim.x * 384) p[i] = make_uint4(0, 0, 0, 0);
  }
  asm volatile("barrier.cluster.arrive.release.aligned; barrier.cluster.wait.acquire.aligned;" ::: "memory");
  const int npairs = (tilesM >> 1) * tilesN, pair0 = blockIdx.x >> 1, pstep = gridDim.x >> 1;
  if (wg == 2) {
    asm volatile("setmaxnreg.dec.sync.aligned.u32 40;");
    if (warp == 8 && lane == 0) {
      int st = 0, ph = 1;
      for (int p = pair0; p < npairs; p += pstep) {
        const int tm = (p % (tilesM >> 1)) * 2 + crank, tn = p / (tilesM >> 1);
        const CUtensorMap* mb = &maps.b[tn / nPerB];
        const int n0 = (tn % nPerB) * BN;
        for (int kb = 0; kb < kblocks; kb++) {
          mbar_wait(sBar + 8 * (STAGES + st), ph);
          const uint32_t a = sbase + st * STAGE_BYTES, full = sBar + 8 * st;
          mbar_expect_tx(full, STAGE_BYTES);
          tma2d(a, &maps.a, kb * 64, tm * 128, full);
#pragma unroll
          for (int i = 0; i < NBOX / 2; i++) {
            const int bx = crank * (NBOX / 2) + i;
            tma2d_mc(a + 16384 + bx * 8192, mb, n0 + bx * 64, kb * 64, full, (uint16_t)3);
          }
          if (++st == STAGES) { st = 0; ph ^= 1; }
        }
      }
      for (int i = 0; i < STAGES; i++) { mbar_wait(sBar + 8 * (STAGES + st), ph); if (++st == STAGES) { st = 0; ph ^= 1; } }
    }
  } else {
    asm volatile("setmaxnreg.inc.sync.aligned.u32 232;");
    int st = 0, ph = 0;
    float acc[BN / 2];
    const uint64_t descA0 = (uint64_t)(((sbase + wg * 8192) & 0x3FFFF) >> 4) | (1ull << 16) | (64ull << 32) | (1ull << 62);
    const uint64_t descB0 = (uint64_t)(((sbase + 16384) & 0x3FFFF) >> 4) | (512ull << 16) | (64ull << 32) | (1ull << 62);
    const uint32_t epi = sEpi + wg * 16384;
    for (int p = pair0; p < npairs; p += pstep) {
      const int tm = (p % (tilesM >> 1)) * 2 + crank, tn = p / (tilesM >> 1);
      int prev = -1;
      for (int kb = 0; kb < kblocks; kb++) {
        mbar_wait(sBar + 8 * st, ph);
        wg_fence();
        const uint64_t so = (uint64_t)(st * (STAGE_BYTES >> 4));
#pragma unroll
        for (int k = 0; k < 4; k++) WG<BN>::mma(acc, descA0 + so + k * 2, descB0 + so + k * 128, kb | k);
        wg_commit();
        if (prev >= 0) {
          wg_wait<1>();
          if ((threadIdx.x & 127) < 2) mbar_arrive_cluster(sBar + 8 * (STAGES + prev), threadIdx.x & 1);
        }
        prev = st;
        if (++st == STAGES) { st = 0; ph ^= 1; }
      }
      wg_wait<0>();
      if ((threadIdx.x & 127) < 2) mbar_arrive_cluster(sBar + 8 * (STAGES + prev), threadIdx.x & 1);
#pragma unroll
      for (int r = 0; r < BN / 128; r++) {
        if ((threadIdx.x & 127) == 0) asm volatile("cp.async.bulk.wait_group.read 0;" ::: "memory");
        bar_sync(1 + wg, 128);
        const int row = (warp & 3) * 16 + (lane & 15);
#pragma unroll
        for (int i = 0; i < 8; i++) {
          const int c = 2 * (i & 3) + (lane >> 4);
          const float* q = &acc[r * 64 + i * 8];
          stsm4(epi + (i >> 2) * 8192 + row * 128 + ((c ^ (row & 7)) << 4), pack2(q[0], q[1]), pack2(q[2], q[3]), pack2(q[4], q[5]), pack2(q[6], q[7]));
        }
        fence_async();
        bar_sync(1 + wg, 128);
        if ((threadIdx.x & 127) == 0) {
          tma2d_store(&maps.c, epi, tn * BN + r * 128, tm * 128 + wg * 64);
          tma2d_store(&maps.c, epi + 8192, tn * BN + r * 128 + 64, tm * 128 + wg * 64);
          asm volatile("cp.async.bulk.commit_group;" ::: "memory");
        }
      }
    }
    if ((threadIdx.x & 127) == 0) asm volatile("cp.async.bulk.wait_group 0;" ::: "memory");
  }
}

struct Dft { uint32_t m[2][2][2][4]; };
template <bool P4> __device__ __forceinline__ int fidx(int tile, int x) { return P4 ? 4 * (x >> 1) + 2 * (tile & 1) + (x & 1) + 16 * (tile >> 1) : x + 8 * tile; }
__device__ __forceinline__ float2 cis(int k, int n) {
  k &= n - 1; if (2 * k > n) k -= n;
  const float a = (float)k * (6.283185307179586f / (float)n);
  return make_float2(__cosf(a), __sinf(a));
}
template <bool OUT4> __device__ __forceinline__ void make_dft(Dft& D, int g, int t) {
#pragma unroll
  for (int q = 0; q < 16; q++) {
    const int b = q >> 3, u = (q >> 2) & 1, r = (q >> 1) & 1, v = q & 1;
    const float2 w = cis(fidx<OUT4>(v, g) * fidx<false>(2 * u + r, 2 * t + b), 32);
    D.m[b][u][0][q & 3] = pack2(w.x, w.y); D.m[b][u][1][q & 3] = pack2(-w.y, w.x);
  }
}
__device__ __forceinline__ void mma_dc(float (&d)[4], uint32_t a0, uint32_t a1, uint32_t a2, uint32_t a3, uint32_t b0, uint32_t b1, const float (&c)[4]) {
  asm("mma.sync.aligned.m16n8k16.row.col.f32.bf16.bf16.f32 {%0,%1,%2,%3}, {%4,%5,%6,%7}, {%8,%9}, {%10,%11,%12,%13};"
    : "=f"(d[0]), "=f"(d[1]), "=f"(d[2]), "=f"(d[3]) : "r"(a0), "r"(a1), "r"(a2), "r"(a3), "r"(b0), "r"(b1), "f"(c[0]), "f"(c[1]), "f"(c[2]), "f"(c[3])); }
__device__ __forceinline__ void dft_b(const Dft& D, const uint32_t (&x)[2][4], float (&o)[2][8]) {
#pragma unroll
  for (int ri = 0; ri < 2; ri++) {
    float z[4] = {0.f, 0.f, 0.f, 0.f}, e[4], p[4];
    mma_dc(e, D.m[0][0][ri][0], D.m[0][0][ri][1], D.m[0][0][ri][2], D.m[0][0][ri][3], x[0][0], x[0][1], z);
    mma_dc(e, D.m[0][1][ri][0], D.m[0][1][ri][1], D.m[0][1][ri][2], D.m[0][1][ri][3], x[0][2], x[0][3], e);
    mma_dc(p, D.m[1][0][ri][0], D.m[1][0][ri][1], D.m[1][0][ri][2], D.m[1][0][ri][3], x[1][0], x[1][1], e);
    mma_dc(p, D.m[1][1][ri][0], D.m[1][1][ri][1], D.m[1][1][ri][2], D.m[1][1][ri][3], x[1][2], x[1][3], p);
#pragma unroll
    for (int q = 0; q < 4; q++) { o[ri][q] = p[q]; o[ri][4 + q] = fmaf(2.f, e[q], -p[q]); }
  }
}
__device__ __forceinline__ void dft_a(const uint32_t (&m)[2][2][4], const uint32_t (&x0)[2][4], const uint32_t (&x1)[2][4], float (&o)[2][8]) {
#pragma unroll
  for (int ri = 0; ri < 2; ri++) {
    float z[4] = {0.f, 0.f, 0.f, 0.f}, e[4], p[4];
    mma_dc(e, x0[0][0], x1[0][0], x0[0][1], x1[0][1], m[0][ri][0], m[0][ri][1], z);
    mma_dc(e, x0[0][2], x1[0][2], x0[0][3], x1[0][3], m[0][ri][2], m[0][ri][3], e);
    mma_dc(p, x0[1][0], x1[1][0], x0[1][1], x1[1][1], m[1][ri][0], m[1][ri][1], e);
    mma_dc(p, x0[1][2], x1[1][2], x0[1][3], x1[1][3], m[1][ri][2], m[1][ri][3], p);
#pragma unroll
    for (int q = 0; q < 4; q++) { o[ri][q] = p[q]; o[ri][4 + q] = fmaf(2.f, e[q], -p[q]); }
  }
}
__device__ __forceinline__ uint32_t twid(float re, float im, float c, float s) { return pack2(fmaf(re, c, im * s), fmaf(im, c, -re * s)); }
__device__ __forceinline__ void cpa16(uint32_t d, const void* s) { asm volatile("cp.async.cg.shared.global [%0], [%1], 16;" :: "r"(d), "l"(s) : "memory"); }
__device__ __forceinline__ void sts32(uint32_t a, uint32_t x) { asm volatile("st.shared.u32 [%0], %1;" :: "r"(a), "r"(x) : "memory"); }
__device__ __forceinline__ void cpa_commit() { asm volatile("cp.async.commit_group;" ::: "memory"); }
template <int N> __device__ __forceinline__ void cpa_wait() { asm volatile("cp.async.wait_group %0;" :: "n"(N) : "memory"); }
__device__ __forceinline__ uint32_t lds32(uint32_t a) { uint32_t r; asm volatile("ld.shared.u32 %0, [%1];" : "=r"(r) : "r"(a) : "memory"); return r; }
constexpr int F_TP = 4112, F_TSZ = 8 * F_TP;

__device__ __forceinline__ void fft_wprep(const bf16* __restrict__ wr, const bf16* __restrict__ wi, int cta, int ncta) {
  const int tid = threadIdx.x;
#pragma unroll 2
  for (int it = cta; it < 256; it += ncta) {
    const int g = (it >> 1) & 7, c = (it >> 4) & 3, i = it >> 6, t = 2 * (it & 1) + (tid & 1);
    const int k0 = g + 8 * i + 32 * (8 * c + 2 * t), l0 = (tid & ~1) + (g & 1);
    uint32_t a[2][4], b[2][4];
#pragma unroll
    for (int q = 0; q < 8; q++) {
      const int o = (k0 + 32 * ((q >> 1) & 1) + 1024 * (q & 1)) * 513 + l0 + 256 * (q >> 2);
      a[q >> 2][q & 3] = __ldg(reinterpret_cast<const uint32_t*>(wr + o));
      b[q >> 2][q & 3] = __ldg(reinterpret_cast<const uint32_t*>(wi + o));
    }
    uint4* dst = g_wt + l0 * 512 + it * 2 + (tid & 1);
#pragma unroll
    for (int q = 0; q < 4; q++) {
      const int hf = q >> 1, l = l0 + 256 * hf + (q & 1);
      const uint32_t sel = (q & 1) ? 0x7632 : 0x5410;
      if (l & 511) dst[(256 * hf + (q & 1)) * 512] = make_uint4(__byte_perm(a[hf][0], b[hf][0], sel), __byte_perm(a[hf][1], b[hf][1], sel),
                                                              __byte_perm(a[hf][2], b[hf][2], sel), __byte_perm(a[hf][3], b[hf][3], sel));
    }
  }
  for (int e = cta * 256 + tid; e < 4096; e += ncta * 256) {
    const int l = (e >> 11) * 512, k = e & 2047, kn = (2048 - k) & 2047, k2 = (k >> 5) & 31;
    const float re = 0.5f * (__bfloat162float(wr[k * 513 + l]) + __bfloat162float(wr[kn * 513 + l]));
    const float im = 0.5f * (__bfloat162float(wi[k * 513 + l]) - __bfloat162float(wi[kn * 513 + l]));
    reinterpret_cast<uint32_t*>(g_wt)[(64 * ((k >> 3) & 3) + 16 * (k2 >> 3) + 2 * (k & 7) + ((k2 >> 2) & 1)) * 8 + l * 2048 + 2 * (k2 & 3) + (k >> 10)] = pack2(re, im);
  }
}

__device__ __forceinline__ void fft_rows_fwd(const bf16* __restrict__ x, uint32_t sb, int cta, int ncta) {
  const int warp = threadIdx.x >> 5, lane = threadIdx.x & 31, g = lane >> 2, t = lane & 3;
  const uint32_t in = sb + warp * 8192, tb = sb + 65536;
  const uint32_t f0 = pin(in + (lane >> 3) * 256 + (((lane & 7) ^ (2 * (lane >> 3))) << 4));
  const uint32_t xo = pin((256 * (warp & 3) + 64 * (warp >> 2)) * 2048 + lane * 8);
  auto fetch = [&](int it, int buf) {
    const bf16* src = x + (xo + (128 * (it & 1) + 32 * ((it >> 4) & 1) + 8 * (it >> 5) + ((it >> 1) & 7)) * 2048);
#pragma unroll
    for (int q = 0; q < 8; q++) cpa16(((f0 + buf * 4096) ^ ((q >> 2) * 144)) + (q & 3) * 1024, src + q * 256);
    cpa_commit();
  };
  fetch(cta, 0);
  Dft D; make_dft<true>(D, g, t);
  float2 tw[4][8];
#pragma unroll
  for (int q = 0; q < 32; q++) tw[q >> 3][q & 7] = cis(fidx<true>((q >> 1) & 3, g) * fidx<false>(q >> 3, 2 * t + (q & 1)), 1024);
  const uint32_t la = pin(in + lane * 128 + ((lane & 7) << 4));
  const uint32_t wa = pin(tb + warp * F_TP + fidx<true>(0, g) * 128 + t * 16), wz = pin((g & 1) ? -64 : 64);
  const uint32_t ra = pin(tb + (lane & 1) * 4 * F_TP + ((lane >> 1) + 16 * (warp ^ ((warp >> 1) & 1))) * 4);
  uint4* dst = g_y + (threadIdx.x >> 1) * 256 + (lane & 1);
  int buf = 0;
  auto drain = [&](int it, int q) {
    const uint32_t r = ra + (buf ^ 1) * F_TSZ + q * 512;
    const uint4 v = make_uint4(lds32(r), lds32(r + F_TP), lds32(r + 2 * F_TP), lds32(r + 3 * F_TP));
    if (it >= 0) dst[it * 2 + q * 32768] = v;
  };
  int it = cta;
#pragma unroll 1
  for (; it < 128; it += ncta, buf ^= 1) {
    cpa_wait<0>(); __syncthreads();
    uint32_t a[4][2][4], y[4][2][4];
#pragma unroll
    for (int q = 0; q < 8; q++) ldsm4t(a[q & 3][q >> 2], (la + buf * 4096) ^ (q << 4));
    if (it + ncta < 128) fetch(it + ncta, buf ^ 1);
    float o[2][8];
#pragma unroll
    for (int i = 0; i < 4; i++) {
      dft_b(D, a[i], o);
      drain(it - ncta, i);
#pragma unroll
      for (int q = 0; q < 8; q++) y[q >> 1][q & 1][i] = twid(o[0][q], o[1][q], tw[i][q].x, tw[i][q].y);
    }
    const uint32_t w0 = wa + buf * F_TSZ + ((g & 1) << 6);
#pragma unroll
    for (int z = 0; z < 2; z++) {
      float o2[2][8];
      dft_b(D, y[2 * z], o); drain(it - ncta, 4 + 2 * z); dft_b(D, y[2 * z + 1], o2); drain(it - ncta, 5 + 2 * z);
#pragma unroll
      for (int i = 0; i < 4; i++) {
        const float sg = i < 2 ? 1.f : -1.f;
        sts128(w0 + z * wz + fidx<true>(i, 0) * 128, pack2(o[0][2 * i], sg * o[1][2 * i]), pack2(o[0][2 * i + 1], sg * o[1][2 * i + 1]),
               pack2(o2[0][2 * i], sg * o2[1][2 * i]), pack2(o2[0][2 * i + 1], sg * o2[1][2 * i + 1]));
      }
    }
  }
  __syncthreads();
#pragma unroll
  for (int q = 0; q < 8; q++) drain(it - ncta, q);
}

__device__ __forceinline__ void fft_cols(uint32_t sb, int cta, int ncta) {
  const int warp = threadIdx.x >> 5, lane = threadIdx.x & 31, g = lane >> 2, t = lane & 3;
  const uint32_t in = sb + warp * 16384 + lane * 16, tab = sb + 131072 + lane * 16;
  auto fetch_y = [&](int l) {
#pragma unroll
    for (int q = 0; q < 16; q++) cpa16(in + q * 512, g_y + (q < 8 ? l : (1024 - l) & 1023) * 256 + (q & 7) * 32 + lane);
  };
  auto fetch_w = [&](int l) {
#pragma unroll
    for (int q = 0; q < 16; q++) cpa16(in + 8192 + q * 512, g_wt + l * 512 + q * 32 + lane);
  };
  const int l0 = cta * 8 + warp, dl = ncta * 8;
  if (l0 <= 512) fetch_y(l0);
  cpa_commit();
  if (l0 <= 512) fetch_w(l0);
  cpa_commit();
  Dft D; make_dft<false>(D, g, t);
#pragma unroll
  for (int q = 2 * warp; q < 2 * warp + 2; q++) {
    const int r = fidx<false>(q & 3, g), c = fidx<false>(q >> 2, 2 * t);
    const float2 w0 = cis(r * c, 1024), w1 = cis(r * c + r, 1024), p0 = cis(r + 32 * c, 2048), p1 = cis(r + 32 * c + 32, 2048);
    sts128(tab + q * 512, __float_as_uint(w0.x), __float_as_uint(w0.y), __float_as_uint(w1.x), __float_as_uint(w1.y));
    sts128(tab + 8192 + q * 512, __float_as_uint(p0.x), __float_as_uint(p0.y), __float_as_uint(p1.x), __float_as_uint(p1.y));
  }
  if (warp == 0) {
#pragma unroll
    for (int q = 0; q < 8; q++) {
      const int v = q >> 2, b = (q >> 1) & 1, ri = q & 1;
      sts128(tab + 16384 + q * 512, D.m[b][0][ri][v], D.m[b][0][ri][v + 2], D.m[b][1][ri][v], D.m[b][1][ri][v + 2]);
    }
  }
  __syncthreads();
#pragma unroll 1
  for (int l = l0; l <= 512; l += dl) {
    uint32_t a[2][4][2][4], y[2][4][2][4];
    float o[2][2][8];
    cpa_wait<1>();
#pragma unroll
    for (int q = 0; q < 16; q++) lds128(a[q >> 3][(q >> 1) & 3][q & 1], in + q * 512);
    if (!(l & 511)) {
      const uint32_t m0 = l ? 0x80000000u : 0u;
#pragma unroll
      for (int q = 0; q < 32; q++) { a[0][q >> 3][(q >> 2) & 1][q & 3] ^= m0; a[1][q >> 3][(q >> 2) & 1][q & 3] ^= m0 ^ 0x80000000u; }
    }
    auto first = [&]() {
#pragma unroll
      for (int i = 0; i < 4; i++) {
        dft_b(D, a[0][i], o[0]); dft_b(D, a[1][i], o[1]);
#pragma unroll
        for (int r = 0; r < 4; r++) {
          const float4 w = lds128f(tab + (4 * i + r) * 512);
#pragma unroll
          for (int s = 0; s < 2; s++) {
            y[s][r][0][i] = twid(o[s][0][2 * r], o[s][1][2 * r], w.x, w.y);
            y[s][r][1][i] = twid(o[s][0][2 * r + 1], o[s][1][2 * r + 1], w.z, w.w);
          }
        }
      }
    };
    first();
    if (l + dl <= 512) fetch_y(l + dl);
    cpa_commit();
    cpa_wait<1>();
#pragma unroll
    for (int zv = 0; zv < 4; zv++) {
      const int z = zv >> 1, v = zv & 1;
      uint32_t m[2][2][4];
#pragma unroll
      for (int q = 0; q < 4; q++) lds128(m[q >> 1][q & 1], tab + 16384 + (4 * v + q) * 512);
      dft_a(m, y[0][2 * z], y[0][2 * z + 1], o[0]); dft_a(m, y[1][2 * z], y[1][2 * z + 1], o[1]);
#pragma unroll
      for (int q = 0; q < 4; q++) {
        const int i = 2 * z + (q & 1), c = v + (q & 2);
        uint32_t w[4]; lds128(w, in + 8192 + (4 * i + c) * 512);
        const float4 ph = lds128f(tab + 8192 + (4 * c + i) * 512);
#pragma unroll
        for (int b = 0; b < 2; b++) {
          const float cs = b ? ph.z : ph.x, sn = b ? ph.w : ph.y;
          const float r1 = __uint_as_float(w[2 * b] << 16), i1 = __uint_as_float(w[2 * b] & 0xFFFF0000u);
          const float r2 = __uint_as_float(w[2 * b + 1] << 16), i2 = __uint_as_float(w[2 * b + 1] & 0xFFFF0000u);
          const float Sr = r1 + r2, Si = i1 + i2, Dr = r1 - r2, Di = i1 - i2;
          const float ar = fmaf(-Dr, sn, Sr), ai = fmaf(-Di, sn, Si), dr = fmaf(Dr, sn, Sr), di = fmaf(Di, sn, Si), br = -Di * cs, bi = Dr * cs;
          const float Ar = o[0][0][2 * q + b], Ai = o[0][1][2 * q + b], Br = o[1][0][2 * q + b], Bi = o[1][1][2 * q + b];
          a[0][i][b][c] = pack2(fmaf(ar, Ai, fmaf(ai, Ar, fmaf(br, Bi, bi * Br))), fmaf(ar, Ar, fmaf(-ai, Ai, fmaf(br, Br, -bi * Bi))));
          a[1][i][b][c] = pack2(fmaf(dr, Bi, fmaf(di, Br, fmaf(-br, Ai, -bi * Ar))), fmaf(dr, Br, fmaf(-di, Bi, fmaf(-br, Ar, bi * Ai))));
        }
      }
    }
    if (l + dl <= 512) fetch_w(l + dl);
    cpa_commit();
    first();
#pragma unroll
    for (int s = 0; s < 2; s++) {
      uint4* dst = g_y + (s ? (1024 - l) & 1023 : l) * 256 + lane;
      const float sg = s ? -1.f : 1.f;
#pragma unroll
      for (int i = 0; i < 4; i++) {
        dft_b(D, y[s][i], o[0]);
#pragma unroll
        for (int b = 0; b < 2; b++)
          dst[(2 * i + b) * 32] = make_uint4(pack2(sg * o[0][0][b], o[0][1][b]), pack2(sg * o[0][0][2 + b], o[0][1][2 + b]),
                                             pack2(sg * o[0][0][4 + b], o[0][1][4 + b]), pack2(sg * o[0][0][6 + b], o[0][1][6 + b]));
      }
    }
  }
}

__device__ __forceinline__ void fft_rows_inv(const CUtensorMap* om, uint32_t sb, int cta, int ncta) {
  const int warp = threadIdx.x >> 5, lane = threadIdx.x & 31, g = lane >> 2, t = lane & 3, wg = warp >> 2, w4 = warp & 3;
  const uint32_t tb = sb + 32768 + wg * 2 * F_TSZ;
  const uint4* src = g_y + pin((256 * ((lane >> 1) & 3) + 64 * (lane >> 3) + 8 * w4) * 256 + (lane & 1));
  const uint32_t wa = pin(tb + (lane & 1) * 4 * F_TP + w4 * 1024 + (lane >> 1) * 4);
  uint4 pf[8];
  auto fetch = [&](int it, int hf) {
#pragma unroll
    for (int q = 0; q < 8; q++) pf[q] = __ldcg(src + (it * 2 + hf * 8192) + q * 256);
  };
  auto put = [&](uint32_t off) {
#pragma unroll
    for (int q = 0; q < 8; q++) {
      sts32(wa + off + q * 64, pf[q].x); sts32(wa + off + q * 64 + F_TP, pf[q].y);
      sts32(wa + off + q * 64 + 2 * F_TP, pf[q].z); sts32(wa + off + q * 64 + 3 * F_TP, pf[q].w);
    }
  };
  const int it0 = 2 * cta + wg;
  if (it0 >= 128) return;
  fetch(it0, 0); put(0); fetch(it0, 1); put(512);
  Dft D; make_dft<false>(D, g, t);
  float2 tw[4][8];
#pragma unroll
  for (int q = 0; q < 32; q++) {
    tw[q >> 3][q & 7] = cis(fidx<false>((q >> 1) & 3, g) * fidx<false>(q >> 3, 2 * t + (q & 1)), 1024);
    tw[q >> 3][q & 7].x *= 1.f / 2097152.f; tw[q >> 3][q & 7].y *= 1.f / 2097152.f;
  }
  const uint32_t la = pin(tb + w4 * F_TP + lane * 16), ob = uni(sb + warp * 4096);
  const uint32_t oa = pin(ob + (lane >> 1) * 128 + (((4 * (lane & 1)) ^ ((lane >> 1) & 7)) << 4));
#pragma unroll 1
  for (int n = 0;; n++) {
    const int it = it0 + (n >> 1) * 2 * ncta, hf = n & 1, buf = (n >> 1) & 1;
    if (it >= 128) break;
    if (!hf) bar_sync(1 + wg, 128);
    uint32_t a[4][2][4], y[4][2][4];
#pragma unroll
    for (int q = 0; q < 8; q++) lds128(a[q >> 1][q & 1], la + buf * F_TSZ + hf * 4 * F_TP + q * 512);
    fetch(min(it + 2 * ncta, 127), hf);
    float o[2][8];
#pragma unroll
    for (int i = 0; i < 4; i++) {
      dft_b(D, a[i], o);
#pragma unroll
      for (int q = 0; q < 8; q++) y[q >> 1][q & 1][i] = twid(o[0][q], o[1][q], tw[i][q].x, tw[i][q].y);
    }
    if (lane == 0) asm volatile("cp.async.bulk.wait_group.read 0;" ::: "memory");
    __syncwarp();
#pragma unroll
    for (int c = 0; c < 4; c++) {
      dft_b(D, y[c], o);
#pragma unroll
      for (int ri = 0; ri < 2; ri++)
        stsm4((oa ^ (c << 4)) + (1 - ri) * 2048, pack2(o[ri][0], o[ri][1]), pack2(o[ri][2], o[ri][3]), pack2(o[ri][4], o[ri][5]), pack2(o[ri][6], o[ri][7]));
    }
    fence_async();
    __syncwarp();
    if (lane == 0) {
      const int m = 256 * w4 + 32 * ((it >> 1) & 7) + 8 * (it >> 5) + 4 * (it & 1) + 2 * hf + ((it >> 4) & 1);
      asm volatile("cp.async.bulk.tensor.3d.global.shared::cta.bulk_group [%0, {0, 0, %2}], [%1];" :: "l"(om), "r"(ob), "r"(2 * m) : "memory");
      asm volatile("cp.async.bulk.commit_group;" ::: "memory");
    }
    put((buf ^ 1) * F_TSZ + hf * 512);
  }
  if (lane == 0) asm volatile("cp.async.bulk.wait_group 0;" ::: "memory");
}
constexpr int F_SMEM = 65536 + 2 * F_TSZ + 1024;
__global__ void __launch_bounds__(256, 1) fft_pre_kernel(const bf16* __restrict__ x, const bf16* __restrict__ wr, const bf16* __restrict__ wi) {
  extern __shared__ __align__(1024) uint8_t smem_raw[];
  const uint32_t sb = (smem_u32(smem_raw) + 1023) & ~1023u;
  fft_wprep(wr, wi, blockIdx.x, gridDim.x);
  fft_rows_fwd(x, sb, blockIdx.x, gridDim.x);
}
__device__ __forceinline__ void grid_arrive(unsigned* ctr) {
  __syncthreads();
  if (threadIdx.x == 0) { __threadfence(); atomicAdd(ctr, 1u); }
}
__device__ __forceinline__ void grid_wait(unsigned* ctr, unsigned n) {
  if (threadIdx.x == 0) {
    int it = 0;
    while (*reinterpret_cast<volatile unsigned*>(ctr) < n) { __nanosleep(200); if (++it > SPIN_LIMIT) { g_err = 3; break; } }
    __threadfence();
  }
  __syncthreads();
}

struct RecMaps { CUtensorMap wq, wk, wv, wo, x, k, q, v, fo; };
#define NSW0 10
#define NSW1 6
#define NP0 2
constexpr int R_WO = 0, R_X = 65536, R_MEM = 131072, R_RED = 147456, R_WVC = 155648, R_STAGE = 188416, R_K = 196608, R_Q = 204800, R_V = 206848,
              R_S = 223232, R_O = 225792, R_SUM = 227840, R_BAR = 227968, R_TS = 228096,
              R_TOTAL = R_TS;
#define TS(i)
constexpr int B_KQ = R_BAR, B_V = R_BAR + 8, B_W = R_BAR + 16, B_MEM = R_BAR + 24, B_X = R_BAR + 40, B_TC = R_BAR + 56;
#define DLY_A 400
#define DLY_V 350
#define DLY_B 500
#define DLY_C 350
#define DLY_K 0
__device__ __forceinline__ float rcp(float x) { float r; asm("rcp.approx.ftz.f32 %0, %1;" : "=f"(r) : "f"(x)); return r; }
__device__ __forceinline__ uint32_t movm(uint32_t a) { uint32_t d; asm volatile("movmatrix.sync.aligned.m8n8.trans.b16 %0, %1;" : "=r"(d) : "r"(a)); return d; }
__device__ __forceinline__ uint32_t hadd2(uint32_t a, uint32_t b) { uint32_t d; asm("add.rn.bf16x2 %0, %1, %2;" : "=r"(d) : "r"(a), "r"(b)); return d; }
__device__ __forceinline__ void mma_a(float (&d)[4], const uint32_t (&a)[4], uint32_t b0, uint32_t b1) { mma16816(d, a[0], a[1], a[2], a[3], b0, b1); }
__device__ __forceinline__ void tma3d(uint32_t dst, const CUtensorMap* m, int c1, int c2, uint32_t bar) {
  asm volatile("cp.async.bulk.tensor.3d.shared::cluster.global.mbarrier::complete_tx::bytes [%0], [%1, {0, %3, %4}], [%2];"
    :: "r"(dst), "l"(m), "r"(bar), "r"(c1), "r"(c2) : "memory"); }
__device__ __forceinline__ void tma4d(uint32_t dst, const CUtensorMap* m, int c1, int c2, uint32_t bar) {
  asm volatile("cp.async.bulk.tensor.4d.shared::cluster.global.mbarrier::complete_tx::bytes [%0], [%1, {0, %3, %4, 0}], [%2];"
    :: "r"(dst), "l"(m), "r"(bar), "r"(c1), "r"(c2) : "memory"); }
template <int OFF, int ACC>
__device__ __forceinline__ void wg_rs32(float (&d)[16], const uint32_t (&a)[4], uint32_t db) {
  if (ACC)
    asm volatile("{.reg .b64 db; .reg .b32 lo; add.u32 lo, %20, %21; mov.b64 db, {lo, 0x40000040};\n"
      "wgmma.mma_async.sync.aligned.m64n32k16.f32.bf16.bf16 {%0,%1,%2,%3,%4,%5,%6,%7,%8,%9,%10,%11,%12,%13,%14,%15}, {%16,%17,%18,%19}, db, 1, 1, 1, 0;}"
      : "+f"(d[0]), "+f"(d[1]), "+f"(d[2]), "+f"(d[3]), "+f"(d[4]), "+f"(d[5]), "+f"(d[6]), "+f"(d[7]), "+f"(d[8]), "+f"(d[9]), "+f"(d[10]), "+f"(d[11]), "+f"(d[12]), "+f"(d[13]), "+f"(d[14]), "+f"(d[15])
      : "r"(a[0]), "r"(a[1]), "r"(a[2]), "r"(a[3]), "r"(db), "n"(OFF));
  else
    asm volatile("{.reg .b64 db; .reg .b32 lo; add.u32 lo, %20, %21; mov.b64 db, {lo, 0x40000040};\n"
      "wgmma.mma_async.sync.aligned.m64n32k16.f32.bf16.bf16 {%0,%1,%2,%3,%4,%5,%6,%7,%8,%9,%10,%11,%12,%13,%14,%15}, {%16,%17,%18,%19}, db, 0, 1, 1, 0;}"
      : "=f"(d[0]), "=f"(d[1]), "=f"(d[2]), "=f"(d[3]), "=f"(d[4]), "=f"(d[5]), "=f"(d[6]), "=f"(d[7]), "=f"(d[8]), "=f"(d[9]), "=f"(d[10]), "=f"(d[11]), "=f"(d[12]), "=f"(d[13]), "=f"(d[14]), "=f"(d[15])
      : "r"(a[0]), "r"(a[1]), "r"(a[2]), "r"(a[3]), "r"(db), "n"(OFF));
}
template <int I, int N, class F> __device__ __forceinline__ void sfor(F&& f) {
  if constexpr (I < N) { f(std::integral_constant<int, I>{}); sfor<I + 1, N>(f); }
}
__device__ __forceinline__ void keep(float (&d)[16]) {
  asm volatile("" : "+f"(d[0]), "+f"(d[1]), "+f"(d[2]), "+f"(d[3]), "+f"(d[4]), "+f"(d[5]), "+f"(d[6]), "+f"(d[7]),
      "+f"(d[8]), "+f"(d[9]), "+f"(d[10]), "+f"(d[11]), "+f"(d[12]), "+f"(d[13]), "+f"(d[14]), "+f"(d[15]) :: "memory");
}

__device__ __forceinline__ void poll2(uint64_t (&v)[2][2], const void* p, uint32_t tag, int& it) {
  asm volatile(
    "{.reg .pred q, p0, p1; .reg .b32 u, lo0, lo1, hi, x0, x1;\n"
    "LOOP:\n"
    "mov.b64 {lo0, hi}, %0; mov.b64 {lo1, hi}, %1; lop3.b32 x0, lo0, lo1, %6, 0x7E;\n"
    "mov.b64 {lo0, hi}, %2; mov.b64 {lo1, hi}, %3; lop3.b32 x1, lo0, lo1, %6, 0x7E;\n"
    "lop3.b32 u, x0, x1, 1, 0xA8;\n"
    "setp.ne.u32 q, u, 0; vote.sync.any.pred q, q, 0xffffffff; @!q bra.uni DONE;\n"
    "add.s32 %4, %4, 1; setp.gt.s32 q, %4, 1048576; @q bra.uni DONE;\n"
    "and.b32 u, x0, 1; setp.ne.u32 p0, u, 0;\n"
    "and.b32 u, x1, 1; setp.ne.u32 p1, u, 0;\n"
    "@p0 ld.relaxed.gpu.global.v2.b64 {%0, %1}, [%5+0];\n"
    "@p1 ld.relaxed.gpu.global.v2.b64 {%2, %3}, [%5+512];\n"
    "bra.uni LOOP;\n"
    "DONE: }\n"
    : "+l"(v[0][0]), "+l"(v[0][1]), "+l"(v[1][0]), "+l"(v[1][1]), "+r"(it) : "l"(p), "r"(tag) : "memory");
}

__device__ __forceinline__ void poll4(uint64_t (&v)[4][2], const void* p, uint32_t tag, int& it) {
  asm volatile(
    "{.reg .pred q, p0, p1, p2, p3; .reg .b32 u, lo0, lo1, hi, x0, x1, x2, x3;\n"
    "LOOP:\n"
    "mov.b64 {lo0, hi}, %0; mov.b64 {lo1, hi}, %1; lop3.b32 x0, lo0, lo1, %10, 0x7E;\n"
    "mov.b64 {lo0, hi}, %2; mov.b64 {lo1, hi}, %3; lop3.b32 x1, lo0, lo1, %10, 0x7E;\n"
    "mov.b64 {lo0, hi}, %4; mov.b64 {lo1, hi}, %5; lop3.b32 x2, lo0, lo1, %10, 0x7E;\n"
    "mov.b64 {lo0, hi}, %6; mov.b64 {lo1, hi}, %7; lop3.b32 x3, lo0, lo1, %10, 0x7E;\n"
    "lop3.b32 u, x0, x1, x2, 0xFE; lop3.b32 u, u, x3, 1, 0xA8;\n"
    "setp.ne.u32 q, u, 0; vote.sync.any.pred q, q, 0xffffffff; @!q bra.uni DONE;\n"
    "add.s32 %8, %8, 1; setp.gt.s32 q, %8, 1048576; @q bra.uni DONE;\n"
    "and.b32 u, x0, 1; setp.ne.u32 p0, u, 0;\n"
    "and.b32 u, x1, 1; setp.ne.u32 p1, u, 0;\n"
    "and.b32 u, x2, 1; setp.ne.u32 p2, u, 0;\n"
    "and.b32 u, x3, 1; setp.ne.u32 p3, u, 0;\n"
    "@p0 ld.relaxed.gpu.global.v2.b64 {%0, %1}, [%9+0];\n"
    "@p1 ld.relaxed.gpu.global.v2.b64 {%2, %3}, [%9+512];\n"
    "@p2 ld.relaxed.gpu.global.v2.b64 {%4, %5}, [%9+1024];\n"
    "@p3 ld.relaxed.gpu.global.v2.b64 {%6, %7}, [%9+1536];\n"
    "bra.uni LOOP;\n"
    "DONE: }\n"
    : "+l"(v[0][0]), "+l"(v[0][1]), "+l"(v[1][0]), "+l"(v[1][1]), "+l"(v[2][0]), "+l"(v[2][1]), "+l"(v[3][0]), "+l"(v[3][1]), "+r"(it) : "l"(p), "r"(tag) : "memory");
}

__device__ __forceinline__ void poll8(uint64_t (&v)[8][2], const void* p, uint32_t tag, int& it) {
  asm volatile(
    "{.reg .pred q, p0, p1, p2, p3, p4, p5, p6, p7; .reg .b32 u, lo0, lo1, hi, x0, x1, x2, x3, x4, x5, x6, x7;\n"
    "LOOP:\n"
    "mov.b64 {lo0, hi}, %0; mov.b64 {lo1, hi}, %1; lop3.b32 x0, lo0, lo1, %18, 0x7E;\n"
    "mov.b64 {lo0, hi}, %2; mov.b64 {lo1, hi}, %3; lop3.b32 x1, lo0, lo1, %18, 0x7E;\n"
    "mov.b64 {lo0, hi}, %4; mov.b64 {lo1, hi}, %5; lop3.b32 x2, lo0, lo1, %18, 0x7E;\n"
    "mov.b64 {lo0, hi}, %6; mov.b64 {lo1, hi}, %7; lop3.b32 x3, lo0, lo1, %18, 0x7E;\n"
    "mov.b64 {lo0, hi}, %8; mov.b64 {lo1, hi}, %9; lop3.b32 x4, lo0, lo1, %18, 0x7E;\n"
    "mov.b64 {lo0, hi}, %10; mov.b64 {lo1, hi}, %11; lop3.b32 x5, lo0, lo1, %18, 0x7E;\n"
    "mov.b64 {lo0, hi}, %12; mov.b64 {lo1, hi}, %13; lop3.b32 x6, lo0, lo1, %18, 0x7E;\n"
    "mov.b64 {lo0, hi}, %14; mov.b64 {lo1, hi}, %15; lop3.b32 x7, lo0, lo1, %18, 0x7E;\n"
    "lop3.b32 u, x0, x1, x2, 0xFE; lop3.b32 hi, x3, x4, x5, 0xFE; lop3.b32 u, u, x6, x7, 0xFE; lop3.b32 u, u, hi, 1, 0xA8;\n"
    "setp.ne.u32 q, u, 0; vote.sync.any.pred q, q, 0xffffffff; @!q bra.uni DONE;\n"
    "add.s32 %16, %16, 1; setp.gt.s32 q, %16, 1048576; @q bra.uni DONE;\n"
    "and.b32 u, x0, 1; setp.ne.u32 p0, u, 0;\n"
    "and.b32 u, x1, 1; setp.ne.u32 p1, u, 0;\n"
    "and.b32 u, x2, 1; setp.ne.u32 p2, u, 0;\n"
    "and.b32 u, x3, 1; setp.ne.u32 p3, u, 0;\n"
    "and.b32 u, x4, 1; setp.ne.u32 p4, u, 0;\n"
    "and.b32 u, x5, 1; setp.ne.u32 p5, u, 0;\n"
    "and.b32 u, x6, 1; setp.ne.u32 p6, u, 0;\n"
    "and.b32 u, x7, 1; setp.ne.u32 p7, u, 0;\n"
    "@p0 ld.relaxed.gpu.global.v2.b64 {%0, %1}, [%17+0];\n"
    "@p1 ld.relaxed.gpu.global.v2.b64 {%2, %3}, [%17+512];\n"
    "@p2 ld.relaxed.gpu.global.v2.b64 {%4, %5}, [%17+1024];\n"
    "@p3 ld.relaxed.gpu.global.v2.b64 {%6, %7}, [%17+1536];\n"
    "@p4 ld.relaxed.gpu.global.v2.b64 {%8, %9}, [%17+2048];\n"
    "@p5 ld.relaxed.gpu.global.v2.b64 {%10, %11}, [%17+2560];\n"
    "@p6 ld.relaxed.gpu.global.v2.b64 {%12, %13}, [%17+3072];\n"
    "@p7 ld.relaxed.gpu.global.v2.b64 {%14, %15}, [%17+3584];\n"
    "bra.uni LOOP;\n"
    "DONE: }\n"
    : "+l"(v[0][0]), "+l"(v[0][1]), "+l"(v[1][0]), "+l"(v[1][1]), "+l"(v[2][0]), "+l"(v[2][1]), "+l"(v[3][0]), "+l"(v[3][1]), "+l"(v[4][0]), "+l"(v[4][1]), "+l"(v[5][0]), "+l"(v[5][1]), "+l"(v[6][0]), "+l"(v[6][1]), "+l"(v[7][0]), "+l"(v[7][1]), "+r"(it) : "l"(p), "r"(tag) : "memory");
}

__device__ __forceinline__ void poll4_b128(uint64_t (&v)[4][2], const void* p, uint32_t tag, int& it) {
  asm volatile(
    "{.reg .pred q, p0, p1; .reg .b32 u, lo0, lo1, hi, x0, x1; .reg .b128 t;\n"
    "LOOP:\n"
    "mov.b64 {lo0, hi}, %0; mov.b64 {lo1, hi}, %2; lop3.b32 x0, lo0, lo1, %10, 0x7E;\n"
    "mov.b64 {lo0, hi}, %4; mov.b64 {lo1, hi}, %6; lop3.b32 x1, lo0, lo1, %10, 0x7E;\n"
    "lop3.b32 u, x0, x1, 1, 0xA8;\n"
    "setp.ne.u32 q, u, 0; vote.sync.any.pred q, q, 0xffffffff; @!q bra.uni DONE;\n"
    "add.s32 %8, %8, 1; setp.gt.s32 q, %8, 1048576; @q bra.uni DONE;\n"
    "and.b32 u, x0, 1; setp.ne.u32 p0, u, 0;\n"
    "and.b32 u, x1, 1; setp.ne.u32 p1, u, 0;\n"
    "mov.b128 t, {%0, %1}; @p0 ld.relaxed.gpu.global.b128 t, [%9+0]; mov.b128 {%0, %1}, t;\n"
    "mov.b128 t, {%2, %3}; @p0 ld.relaxed.gpu.global.b128 t, [%9+512]; mov.b128 {%2, %3}, t;\n"
    "mov.b128 t, {%4, %5}; @p1 ld.relaxed.gpu.global.b128 t, [%9+1024]; mov.b128 {%4, %5}, t;\n"
    "mov.b128 t, {%6, %7}; @p1 ld.relaxed.gpu.global.b128 t, [%9+1536]; mov.b128 {%6, %7}, t;\n"
    "bra.uni LOOP;\n"
    "DONE: }\n"
    : "+l"(v[0][0]), "+l"(v[0][1]), "+l"(v[1][0]), "+l"(v[1][1]), "+l"(v[2][0]), "+l"(v[2][1]), "+l"(v[3][0]), "+l"(v[3][1]), "+r"(it) : "l"(p), "r"(tag) : "memory");
}

__device__ __forceinline__ void poll8_w(uint32_t (&v)[8], const void* p, uint32_t tag, uint32_t mask, int& it) {
  asm volatile(
    "{.reg .pred q; .reg .b32 u, x0, x1, x2, x3;\n"
    "lop3.b32 x0, %0, %1, %10, 0x7E; lop3.b32 x1, %2, %3, %10, 0x7E; lop3.b32 x2, %4, %5, %10, 0x7E; lop3.b32 x3, %6, %7, %10, 0x7E;\n"
    "lop3.b32 u, x0, x1, x2, 0xFE; lop3.b32 u, u, x3, %11, 0xA8;\n"
    "setp.ne.u32 q, u, 0; vote.sync.any.pred q, q, 0xffffffff;\n"
    "@!q bra.uni DONE;\n"
    "LOOP:\n"
    "ld.relaxed.gpu.global.b32 %0, [%9+0];\n"
    "ld.relaxed.gpu.global.b32 %1, [%9+128];\n"
    "ld.relaxed.gpu.global.b32 %2, [%9+256];\n"
    "ld.relaxed.gpu.global.b32 %3, [%9+384];\n"
    "ld.relaxed.gpu.global.b32 %4, [%9+512];\n"
    "ld.relaxed.gpu.global.b32 %5, [%9+640];\n"
    "ld.relaxed.gpu.global.b32 %6, [%9+768];\n"
    "ld.relaxed.gpu.global.b32 %7, [%9+896];\n"
    "lop3.b32 x0, %0, %1, %10, 0x7E; lop3.b32 x1, %2, %3, %10, 0x7E; lop3.b32 x2, %4, %5, %10, 0x7E; lop3.b32 x3, %6, %7, %10, 0x7E;\n"
    "lop3.b32 u, x0, x1, x2, 0xFE; lop3.b32 u, u, x3, %11, 0xA8;\n"
    "setp.ne.u32 q, u, 0; vote.sync.any.pred q, q, 0xffffffff;\n"
    "add.s32 %8, %8, 1; setp.le.and.s32 q, %8, 1048576, q; @q bra.uni LOOP;\n"
    "DONE: }\n"
    : "+r"(v[0]), "+r"(v[1]), "+r"(v[2]), "+r"(v[3]), "+r"(v[4]), "+r"(v[5]), "+r"(v[6]), "+r"(v[7]), "+r"(it) : "l"(p), "r"(tag), "r"(mask) : "memory");
}

__device__ __forceinline__ uint32_t lo32(uint64_t v) { return (uint32_t)v; }
__device__ __forceinline__ uint32_t hi32(uint64_t v) { return (uint32_t)(v >> 32); }
__device__ __forceinline__ void ldx2(uint64_t (&r)[2], const void* p) { asm volatile("ld.relaxed.gpu.global.v2.b64 {%0, %1}, [%2];" : "=l"(r[0]), "=l"(r[1]) : "l"(p) : "memory"); }
__device__ __forceinline__ void ldxb(uint64_t (&r)[2], const void* p) {
  asm volatile("{.reg .b128 t; ld.relaxed.gpu.global.b128 t, [%2]; mov.b128 {%0, %1}, t;}" : "=l"(r[0]), "=l"(r[1]) : "l"(p) : "memory"); }
__device__ __forceinline__ void lds2(uint64_t (&r)[2], uint32_t a) { asm volatile("ld.shared.v2.b64 {%0, %1}, [%2];" : "=l"(r[0]), "=l"(r[1]) : "r"(a) : "memory"); }
__device__ __forceinline__ void sts2(uint32_t a, const uint64_t (&r)[2]) { asm volatile("st.shared.v2.b64 [%0], {%1, %2};" :: "r"(a), "l"(r[0]), "l"(r[1]) : "memory"); }
__device__ __forceinline__ void mma_b(float (&d)[4], const uint32_t (&a)[4], uint64_t b) { mma16816(d, a[0], a[1], a[2], a[3], lo32(b), hi32(b)); }
__device__ __forceinline__ void mma_bb(float (&d)[4], const uint64_t (&a)[2], uint64_t b) { mma16816(d, lo32(a[0]), hi32(a[0]), lo32(a[1]), hi32(a[1]), lo32(b), hi32(b)); }
__device__ __forceinline__ void ldsm4q(uint64_t (&r)[2], uint32_t a) {
  asm volatile("{.reg .b32 a,b,c,d; ldmatrix.sync.aligned.m8n8.x4.shared.b16 {a,b,c,d}, [%2]; mov.b64 %0, {a,b}; mov.b64 %1, {c,d};}" : "=l"(r[0]), "=l"(r[1]) : "r"(a) : "memory"); }
__device__ __forceinline__ void mbar_spin(uint32_t bar, uint32_t par, int& it) {
  asm volatile("{.reg .pred p; .reg .b32 par; mov.b32 par, %2;\nLOOP: mbarrier.try_wait.parity.shared::cta.b64 p, [%1], par; @p bra.uni DONE;\n"
               "add.s32 %0, %0, 1; setp.le.s32 p, %0, 1048576; @p bra.uni LOOP;\nDONE: }" : "+r"(it) : "r"(bar), "r"(par) : "memory"); }
__device__ __forceinline__ void delay_until(unsigned t) {
  asm volatile("{.reg .pred p; .reg .b64 c; .reg .b32 lo, hi;\nLOOP: mov.u64 c, %%clock64; mov.b64 {lo, hi}, c; sub.s32 lo, lo, %0; setp.lt.s32 p, lo, 0; @p bra.uni LOOP;}" :: "r"(t) : "memory"); }
__device__ __forceinline__ void zero(float (&c)[4][4]) {
#pragma unroll
  for (int i = 0; i < 4; i++) c[i][0] = c[i][1] = c[i][2] = c[i][3] = 0.f;
}

template <int W4>
__device__ __forceinline__ void qk_gemm(const uint32_t (&w)[32][4], uint64_t (&own)[4][2], uint64_t (&be)[8][2], uint32_t a, float (&r)[4],
                                        uint32_t bar, uint32_t par, int& it) {
  float c[4][4];
  zero(c);
#pragma unroll
  for (int i = 0; i < 4; i++) {
    mma_b(c[2 * (i & 1)], w[8 * W4 + 2 * i], own[i][0]);
    mma_b(c[2 * (i & 1) + 1], w[8 * W4 + 2 * i + 1], own[i][1]);
    if (W4 < 2) { be[4 * W4 + i][0] = own[i][0]; be[4 * W4 + i][1] = own[i][1]; }
  }
  mbar_spin(bar, par, it);
  uint64_t b[8][2];
#pragma unroll
  for (int q = 0; q < 16; q++) {
    const int p = q ^ 8;
    if ((p >> 2) != W4) lds2(p < 8 ? be[p & 7] : b[p & 7], a + ((p >> 2) - W4) * 512 + (p & 3) * 4096);
  }
#pragma unroll
  for (int q = 0; q < 16; q++) {
    const int p = q ^ 8;
    if ((p >> 2) != W4) {
      mma_b(c[2 * (p & 1)], w[2 * p], p < 8 ? be[p & 7][0] : b[p & 7][0]);
      mma_b(c[2 * (p & 1) + 1], w[2 * p + 1], p < 8 ? be[p & 7][1] : b[p & 7][1]);
    }
  }
#pragma unroll
  for (int i = 0; i < 4; i++) { r[i] = (c[0][i] + c[1][i]) + (c[2][i] + c[3][i]); asm volatile("" : "+f"(r[i])); }
}

__global__ void __launch_bounds__(256, 1)
rec_kernel(const __grid_constant__ RecMaps maps, const bf16* __restrict__ xin, const bf16* __restrict__ mem0) {
  extern __shared__ __align__(1024) uint8_t smem_raw[];
  const uint32_t sb = smem_u32(smem_raw);
  int role = blockIdx.x;
  {
    uint32_t smid, nsm; asm volatile("mov.u32 %0, %%smid;" : "=r"(smid)); asm volatile("mov.u32 %0, %%nsmid;" : "=r"(nsm));
    const int p = smid >> 1, u = p - 32;
    if (nsm == gridDim.x)
      role = (smid & 1) + (p < 32 ? 4 * ((p & 7) + 8 * (p >> 4)) + 2 * ((p >> 3) & 1) : p < 60 ? 4 * (16 + u % 7 + 7 * (u / 14)) + 2 * ((u / 7) & 1)
                         : p < 62 ? 2 * p + 8 : 2 * p - 4);
    role = uni(role);
  }
  if (role >= 128) {
    fft_cols(sb, role - 128, 4);
    grid_arrive(&g_x.ctr[32]); grid_wait(&g_x.ctr[32], 4);
    fft_rows_inv(&maps.fo, sb, role - 128, 4);
    return;
  }
  const int tid = threadIdx.x, warp = uni(tid >> 5), lane = tid & 31, wg = warp >> 2, w4 = warp & 3, g = lane >> 2, t = lane & 3;
  const int h = role >> 2, j = role & 3, jh = j & 1;
  uint32_t wqk[32][4];
  uint32_t wv[16][4];
  uint64_t own[4][2];
  float aq[16], av[16];
  int it = 0;

  if (tid == 224) {
    mbar_init(sb + B_KQ, 1); mbar_init(sb + B_V, 1); mbar_init(sb + B_W, 1); mbar_init(sb + B_X, 1); mbar_init(sb + B_X + 8, 1);
    mbar_init(sb + B_MEM, 128); mbar_init(sb + B_MEM + 8, 128);
    asm volatile("fence.mbarrier_init.release.cluster;" ::: "memory");
    mbar_expect_tx(sb + B_W, 3 * 65536);
    for (int i = 0; i < 4; i++) {
      tma2d(sb + R_X + i * 16384, &maps.wq, h * DH + 32 * j, i * 256, sb + B_W);
      tma2d(sb + R_MEM + i * 16384, &maps.wk, h * DH + 32 * j, i * 256, sb + B_W);
    }
    for (int i = 0; i < 2; i++) tma2d(sb + R_WO + i * 32768, &maps.wv, h * DH + 64 * (j >> 1), jh * 512 + i * 256, sb + B_W);
    for (int i = 0; i < 4; i++) asm volatile("cp.async.bulk.prefetch.L2.global [%0], 8192;" :: "l"(xin + role * 16384 + i * 4096) : "memory");
    for (int i = 0; i < 4; i++)
      asm volatile("cp.async.bulk.prefetch.tensor.2d.L2.global [%0, {%1, %2}];" :: "l"(&maps.wo), "r"(256 * j + 64 * i), "r"(h * DH) : "memory");
  }
  const int kq = 2 * ((w4 >> 1) ^ jh) + wg;
  if (tid < 128) asm volatile("prefetch.global.L2 [%0];" :: "l"(mem0 + tid * 64));
  __syncthreads();
  mbar_spin(sb + B_W, 0, it);
  const int lrow = (lane & 7) + ((lane >> 4) << 3), lhi = (lane >> 3) & 1;
  {
    const int chunk = w4 < 2 ? w4 + 2 * lhi : 2 * (w4 & 1) + lhi;
    const uint32_t a = sb + (w4 < 2 ? R_X : R_MEM) + wg * 16384 + lrow * 64 + ((chunk ^ ((lrow >> 1) & 3)) << 4);
#pragma unroll
    for (int ks = 0; ks < 32; ks++) ldsm4t(wqk[ks], a + ((ks >> 4) ^ jh) * 32768 + (ks & 15) * 1024);
  }
  uint32_t L16 = pin(lane * 16), LW = pin(lrow * 128 + ((lhi ^ (lane & 7)) << 4));
#pragma unroll
  for (int i = 0; i < 16; i++) ldsm4t(wv[i], sb + R_WO + wg * 32768 + (LW ^ (w4 << 5)) + i * 2048);
  const uint32_t uWo = uni(sb + R_WO + (warp >> 1) * 16384), uWvc = uni(sb + R_WVC + wg * (NSW0 * 2048) + w4 * 512);
  const uint32_t uMem = uni(sb + R_MEM + warp * 512), uRed = uni(sb + R_RED + w4 * 2048);
  const uint32_t dB = uni(((sb + R_X + wg * 32768 + jh * 16384) >> 4) | 0x10000u);
  const uint32_t uBx = uni(sb + B_X + 8 * wg);
  auto load_wo = [&](uint32_t (&d)[4], int i) { ldsm4t(d, uWo + (LW ^ (((warp & 1) << 6) + ((i & 1) << 5))) + (i >> 1) * 2048); };
  auto issue_x = [&](int n, int i) { mbar_expect_tx(sb + B_X + 8 * i, 32768); tma4d(sb + R_X + i * 32768, &maps.x, n * SEG, 4 * i, sb + B_X + 8 * i); };
  auto store_stage = [&](int n) {
    fence_async();
    asm volatile("cp.async.bulk.global.shared::cta.bulk_group [%0], [%1], 8192; cp.async.bulk.commit_group;" :: "l"(g_kqv[n & 3][role]), "r"(sb + R_STAGE) : "memory");
  };
  auto issue_kqv = [&](int n) {
    const int p = (n & 3) * 128 + 4 * h;
    mbar_expect_tx(sb + B_KQ, 10240); tma3d(sb + R_K, &maps.k, 0, p, sb + B_KQ); tma3d(sb + R_Q, &maps.q, 8 + 2 * j, p, sb + B_KQ);
    mbar_expect_tx(sb + B_V, 16384); tma3d(sb + R_V, &maps.v, 16, p, sb + B_V);
  };
  auto project = [&](int n) {
    mbar_spin(uBx, n & 1, it);
    wg_fence();
    sfor<0, 32>([&](auto I) {
      constexpr int i = decltype(I)::value;
      wg_rs32<((i & 15) >> 2) * 256 + (i & 3) * 2, (i > 0)>(aq, wqk[i ^ 16], i < 16 ? dB ^ 1024 : dB);
    });
    wg_commit();
    wg_fence();
    sfor<0, 16>([&](auto I) { constexpr int i = decltype(I)::value; wg_rs32<(i >> 2) * 256 + (i & 3) * 2, (i > 0)>(av, wv[i], dB); });
    wg_commit();
  };
  auto park = [&]() {
#pragma unroll
    for (int i = 0; i < 4; i++) {
      sts128(uMem + 2048 + L16 + i * 4096, __float_as_uint(aq[4 * i]), __float_as_uint(aq[4 * i + 1]), __float_as_uint(aq[4 * i + 2]), __float_as_uint(aq[4 * i + 3]));
      sts128(uRed + L16 + i * 512, __float_as_uint(av[4 * i]), __float_as_uint(av[4 * i + 1]), __float_as_uint(av[4 * i + 2]), __float_as_uint(av[4 * i + 3]));
    }
  };
  auto fin_qk = [&]() {
    uint32_t r[2][4];
#pragma unroll
    for (int i = 0; i < 4; i++) {
      const float4 p = lds128f(uMem + L16 + i * 4096);
      r[0][i] = pack2(aq[4 * i] + p.x, aq[4 * i + 1] + p.y); r[1][i] = pack2(aq[4 * i + 2] + p.z, aq[4 * i + 3] + p.w);
    }
    const uint32_t a = sb + R_STAGE + (w4 < 2 ? 2048 + w4 * 128 : (w4 & 1) * 256) + (L16 & 112) + (L16 >> 7) * 512;
    stsm4t(a, r[0][0], r[0][1], r[0][2], r[0][3]);
    stsm4t(a + (w4 < 2 ? 256 : 128), r[1][0], r[1][1], r[1][2], r[1][3]);
  };
  auto fin_v = [&]() {
#pragma unroll
    for (int a = 0; a < 2; a++) {
      const float4 p = lds128f(uRed + L16 + a * 1024), q = lds128f(uRed + L16 + a * 1024 + 512);
      sts128(sb + R_STAGE + 4096 + w4 * 1024 + a * 512 + L16, pack2(av[8 * a] + p.x, av[8 * a + 1] + p.y), pack2(av[8 * a + 2] + p.z, av[8 * a + 3] + p.w),
             pack2(av[8 * a + 4] + q.x, av[8 * a + 5] + q.y), pack2(av[8 * a + 6] + q.z, av[8 * a + 7] + q.w));
    }
  };
  __syncthreads();
  if (tid == 224) {
    issue_x(0, 0); issue_x(0, 1);
    mbar_expect_tx(sb + B_W, 65536);
    for (int i = 0; i < 4; i++) tma2d(sb + R_WO + i * 16384, &maps.wo, 256 * j + 64 * i, h * DH, sb + B_W);
  }
  __syncwarp();
#pragma unroll
  for (int i = 0; i < NSW0; i++)
    if (i < NSW1 || wg == 0) sts128(uWvc + L16 + i * 2048, wv[i][0], wv[i][1], wv[i][2], wv[i][3]);
#pragma unroll 1
  for (int n = 0; n < 2; n++) {
    project(n);
    wg_wait<0>(); keep(aq); keep(av);
    if (wg == 0) park();
    if (tid == 224) asm volatile("cp.async.bulk.wait_group 0;" ::: "memory");
    __syncthreads();
    if (tid == 0) { issue_x(n + 1, 0); issue_x(n + 1, 1); }
    if (tid == 32 && n == 1) {
      __threadfence(); atomicAdd(&g_x.ctr[h], 1u);
      for (int k = 0; *reinterpret_cast<volatile unsigned*>(&g_x.ctr[h]) < 4 && k < SPIN_LIMIT; k++) {}
      __threadfence(); asm volatile("fence.proxy.async;" ::: "memory");
      issue_kqv(0);
    }
    if (wg == 1) { fin_qk(); fin_v(); }
    __syncthreads();
    if (tid == 224) store_stage(n);
    __syncwarp();
  }
#pragma unroll
  for (int i = 0; i < 4; i++)
#pragma unroll
    for (int r = 0; r < 2; r++) {
      const uint32_t* mp = reinterpret_cast<const uint32_t*>(mem0 + g * DM + 256 * kq + 128 * (w4 & 1) + 32 * i + 16 * r + 2 * t);
      own[i][r] = (uint64_t)__ldg(mp) | ((uint64_t)__ldg(mp + 4) << 32);
    }
  mbar_spin(sb + B_W, 1, it);

  const float sc = 0.08838834764831845f * 1.4426950408889634f;
  uint8_t* const xb = reinterpret_cast<uint8_t*>(&g_x);
  uint8_t* const xa = xb + uni(h * 16384);
  const uint32_t uAq = uni((w4 >> 1) * 2048 + j * 512 + (w4 & 1) * 8), uAv = uni(8192 + (4 * (j >> 1) + w4) * 512 + jh * 8);
  const uint32_t uBar = uni(sb + B_MEM + 8 * wg);
  uint32_t bofs = pin(offsetof(Xchg, B) + ((4 * warp + t) * 4 + j) * 8192 + (g >> 1) * 1024 + h * 32 + (g & 1) * 16);
  const uint32_t uC = uni(offsetof(Xchg, C) + kq * 8192 + (w4 & 1) * 2048);

#pragma unroll 1
  for (int s = 0;; s++) {
    const uint32_t tag = (s + 1) & 1, T = tag << 16;
    { const uint32_t z = (uint32_t)it >> 31; L16 += z; LW += z; bofs += z; }
    TS(0);
#pragma unroll
    for (int i = 0; i < 4; i++) sts2(uMem + L16 + i * 4096, own[i]);
    mbar_arrive(uBar);
    float c[4][4], r4[4];
    uint64_t be[8][2];
    {
      const uint32_t a = uMem + L16;
      if (w4 < 2) { if (w4 == 0) qk_gemm<0>(wqk, own, be, a, r4, uBar, s & 1, it); else qk_gemm<1>(wqk, own, be, a, r4, uBar, s & 1, it); }
      else { if (w4 == 2) qk_gemm<2>(wqk, own, be, a, r4, uBar, s & 1, it); else qk_gemm<3>(wqk, own, be, a, r4, uBar, s & 1, it); }
    }
    auto fold = [&]() {
#pragma unroll
      for (int i = 0; i < 4; i++) r4[i] = (c[0][i] + c[1][i]) + (c[2][i] + c[3][i]);
    };
    auto v_gemm = [&](int i0, int i1) {
#pragma unroll
      for (int i = i0; i < i1; i++) mma_b(c[i & 3], wv[i], be[i >> 1][i & 1]);
    };
    auto expo = [&](float2 (&sv)[5]) {
      float m = fmaxf(fmaxf(fmaxf(sv[0].x, sv[0].y), fmaxf(sv[1].x, sv[1].y)), fmaxf(fmaxf(sv[2].x, sv[2].y), fmaxf(sv[3].x, sv[3].y)));
      m = fmaxf(m, fmaxf(sv[4].x, sv[4].y));
      m = fmaxf(m, __shfl_xor_sync(0xffffffffu, m, 1));
      m = fmaxf(m, __shfl_xor_sync(0xffffffffu, m, 2));
      const float ms = -m * sc;
#pragma unroll
      for (int i = 0; i < 5; i++) { sv[i].x = ex2(fmaf(sv[i].x, sc, ms)); sv[i].y = ex2(fmaf(sv[i].y, sc, ms)); }
      return ((sv[0].x + sv[0].y) + (sv[1].x + sv[1].y)) + ((sv[2].x + sv[2].y) + (sv[3].x + sv[3].y) + (sv[4].x + sv[4].y));
    };
    auto publish_b = [&]() {
      const float4 s0 = lds128f(sb + R_SUM + ((L16 << 1) & 96)), s1 = lds128f(sb + R_SUM + 16 + ((L16 << 1) & 96));
      const float r0 = rcp((s0.x + s0.y) + (s0.z + s0.w)), r1 = rcp((s1.x + s1.y) + (s1.z + s1.w));
      stx128(xb + bofs, pack2_tag((c[0][0] + c[2][0]) * r0, (c[0][1] + c[2][1]) * r1, T), pack2((c[0][2] + c[2][2]) * r0, (c[0][3] + c[2][3]) * r1),
             pack2((c[1][0] + c[3][0]) * r0, (c[1][1] + c[3][1]) * r1), pack2((c[1][2] + c[3][2]) * r0, (c[1][3] + c[3][3]) * r1));
    };
    zero(c);
    TS(1);
    unsigned tb;
    if (wg == 0) {
      v_gemm(0, 4);
      bar_sync(8 + w4, 64);
      float4 o4 = lds128f(uRed + L16);
      v_gemm(4, 8);
      const uint32_t r0 = movm(pack2(r4[0] + o4.x, r4[1] + o4.y)), r1 = movm(pack2(r4[2] + o4.z, r4[3] + o4.w));
      v_gemm(8, 12);
      stx64(xa + uAq + L16, (r0 & ~1u) | tag, r1);
      TS(2);
      v_gemm(12, 16);
      bar_sync(12 + w4, 64);
      o4 = lds128f(uRed + 512 + L16);
      fold();
      stx64(xa + uAv + L16, pack2_tag(r4[0] + o4.x, r4[1] + o4.y, T), pack2(r4[2] + o4.z, r4[3] + o4.w));
      const unsigned tpub = clk();
      TS(3);
      uint32_t vf[4][4], wt[16 - NSW0][4];
      mbar_spin(sb + B_V, s & 1, it);
      const uint32_t va = sb + R_V + (w4 >> 1) * 8192 + (w4 & 1) * 2048 + L16;
#pragma unroll
      for (int i = 0; i < 4; i++) {
        uint32_t p[4]; lds128(vf[i], va + i * 512); lds128(p, va + 4096 + i * 512);
#pragma unroll
        for (int e = 0; e < 4; e++) vf[i][e] = hadd2(vf[i][e], p[e]);
      }
#pragma unroll
      for (int i = 0; i < NSW0 + NP0; i++) load_wo(i < NSW0 ? wv[i] : wt[i < NSW0 ? 0 : i - NSW0], i);
      const uint32_t sa = pin(sb + R_S + (L16 >> 1));
      const uint8_t* vsrc = xa + 8192 + w4 * 1024 + L16;
      uint64_t vm[2][2];
      delay_until(tpub + DLY_V);
      TS(4);
      ldx2(vm[0], vsrc); ldx2(vm[1], vsrc + 512);
      bar_sync(5, 224);
      TS(5);
      float2 sv[5];
#pragma unroll
      for (int i = 0; i < 5; i++) sv[i] = lds64f(sa + i * 256);
      const float sum = expo(sv);
      uint32_t p[5];
      auto pv_x = [&]() {
        zero(c);
#pragma unroll
        for (int i = 0; i < 4; i++) mma_a(c[i & 1], vf[2 * (i & 1) + (i >> 1)], p[i & 2], p[(i & 2) + 1]);
      };
      auto pv_m = [&](uint32_t (&o)[4]) {
#pragma unroll
        for (int i = 0; i < 2; i++) mma16816(c[i], lo32(vm[i][0]), hi32(vm[i][0]), lo32(vm[i][1]), hi32(vm[i][1]), p[4], p[4]);
#pragma unroll
        for (int i = 0; i < 4; i++) o[i] = pack2(c[i >> 1][2 * (i & 1)], c[i >> 1][2 * (i & 1) + 1]);
      };
#pragma unroll
      for (int i = 0; i < 5; i++) p[i] = pack2(sv[i].x, sv[i].y);
      pv_x();
      sts32f(sb + R_SUM + (L16 >> 2), sum);
      poll2(vm, vsrc, tag, it);
      TS(6);
      uint32_t o[4];
      pv_m(o);
      stsm4t(sb + R_O + w4 * 512 + L16, o[0], o[1], o[2], o[3]);
      TS(7);
      bar_sync(6, 256);
      uint64_t b[4][2];
      { uint32_t q[4]; lds128(q, sb + R_S + 1280 + L16); p[0] = q[0]; p[1] = q[1]; p[2] = q[2]; p[3] = q[3]; p[4] = lds32(sb + R_S + 1792 + (L16 >> 2)); }
#pragma unroll
      for (int i = 0; i < 4; i++) ldsm4q(b[i], sb + R_O + i * 512 + L16);
      pv_x(); pv_m(o);
#pragma unroll
      for (int i = NSW0 + NP0; i < 16; i++) load_wo(wt[i - NSW0], i);
      zero(c);
#pragma unroll
      for (int i = 0; i < 16; i++) mma_b(c[i & 3], i < NSW0 ? wv[i] : wt[i < NSW0 ? 0 : i - NSW0], b[i >> 2][(i >> 1) & 1]);
      publish_b();
      tb = clk();
      TS(8);
#pragma unroll
      for (int i = 0; i < NSW0; i++) lds128(wv[i], uWvc + L16 + i * 2048);
      stsm4t(sb + R_STAGE + 4096 + w4 * 1024 + (L16 & 112) * 4 + (((L16 >> 3) ^ (L16 >> 1)) & 48), o[0], o[1], o[2], o[3]);
      if (s + 1 == NSEG) { bar_arrive(2, 256); break; }
    } else {
      sts128(uRed + L16, __float_as_uint(r4[0]), __float_as_uint(r4[1]), __float_as_uint(r4[2]), __float_as_uint(r4[3]));
      bar_arrive(8 + w4, 64);
      const unsigned tpub = clk();
      TS(2);
      v_gemm(0, 16);
      if (warp == 7) {
        if (L16 == 0) asm volatile("cp.async.bulk.wait_group 0;" ::: "memory");
        __syncwarp();
      }
      fold();
      sts128(uRed + 512 + L16, __float_as_uint(r4[0]), __float_as_uint(r4[1]), __float_as_uint(r4[2]), __float_as_uint(r4[3]));
      bar_arrive(12 + w4, 64);
      TS(3);
      const uint8_t* asrc = xa + L16;
      const uint32_t qa = sb + R_Q + (L16 & 112) + (L16 & 128) * 2 + (L16 >> 8) * 128;
      uint32_t wt[16 - NSW1][4];
      if (warp < 6) {
        mbar_spin(sb + B_KQ, s & 1, it);
        uint32_t kf[8][4];
        uint64_t q[4][2];
        const uint32_t ka = sb + R_K + w4 * 1024 + (L16 & 112) + (L16 & 128) * 4 + (L16 & 256);
#pragma unroll
        for (int i = 0; i < 8; i++) ldsm4(kf[i], ka + (i >> 1) * 2048 + (i & 1) * 128);
#pragma unroll
        for (int i = 0; i < 4; i++) ldsm4q(q[i], qa + i * 512);
        const uint32_t sa = pin(sb + R_S + w4 * 512 + (L16 & 48) * 4 + (L16 >> 6) * 4);
        zero(c);
#pragma unroll
        for (int i = 0; i < 8; i++) mma_b(c[i & 3], kf[i], q[i >> 1][i & 1]);
        delay_until(tpub + DLY_A);
        TS(4);
#pragma unroll
        for (int i = 0; i < 4; i++) ldx2(q[i], asrc + i * 512);
        fold();
#pragma unroll
        for (int i = 0; i < 4; i++) sts32f(sa + 1280 + (i & 1) * 32 + (i >> 1) * 256, r4[i]);
        bar_arrive(4, 96);
#pragma unroll
        for (int i = 0; i < 4; i++) load_wo(wv[i], i);
        poll4(q, asrc, tag, it);
        TS(5);
        zero(c);
#pragma unroll
        for (int i = 0; i < 8; i++) mma_b(c[i & 3], kf[i], q[i >> 1][i & 1]);
        fold();
#pragma unroll
        for (int i = 0; i < 4; i++) sts32f(sa + (i & 1) * 32 + (i >> 1) * 256, r4[i]);
        bar_arrive(5, 224);
      } else if (warp == 6) {
        uint64_t qk[8][2];
        delay_until(tpub + DLY_A);
        TS(4);
#pragma unroll
        for (int i = 0; i < 8; i++) ldx2(qk[i], asrc + i * 512);
#pragma unroll
        for (int i = 0; i < 4; i++) load_wo(wv[i], i);
        poll8(qk, asrc, tag, it);
        TS(5);
        zero(c);
#pragma unroll
        for (int i = 0; i < 8; i++) mma_bb(c[i & 3], qk[i >> 1], qk[4 + (i >> 1)][i & 1]);
        sts64f(sb + R_S + 1024 + (L16 >> 1), (c[0][0] + c[1][2]) + (c[2][0] + c[3][2]), (c[0][1] + c[1][3]) + (c[2][1] + c[3][3]));
        bar_arrive(5, 224);
      } else {
        uint64_t q[4][2], k[4][2];
        mbar_spin(sb + B_KQ, s & 1, it);
#pragma unroll
        for (int i = 0; i < 4; i++) ldsm4q(q[i], qa + i * 512);
        delay_until(tpub + DLY_A);
        TS(4);
#pragma unroll
        for (int i = 0; i < 4; i++) ldx2(k[i], asrc + 2048 + i * 512);
#pragma unroll
        for (int i = 0; i < 4; i++) load_wo(wv[i], i);
        bar_sync(4, 96);
        float2 sv[5];
        const int d = (int)(L16 >> 6) - (int)((L16 >> 3) & 6) + 8 * j;
#pragma unroll
        for (int i = 0; i < 4; i++) {
          sv[i] = lds64f(sb + R_S + 1280 + (L16 >> 1) + i * 256);
          if (8 * i > d) sv[i].x = -INFINITY;
          if (8 * i + 1 > d) sv[i].y = -INFINITY;
        }
        poll4(k, asrc + 2048, tag, it);
        TS(5);
        zero(c);
#pragma unroll
        for (int i = 0; i < 8; i++) mma_bb(c[i & 3], q[i >> 1], k[i >> 1][i & 1]);
        sv[4] = make_float2((c[0][0] + c[1][2]) + (c[2][0] + c[3][2]), (c[0][1] + c[1][3]) + (c[2][1] + c[3][3]));
        float sum = expo(sv);
        sum += __shfl_xor_sync(0xffffffffu, sum, 1); sum += __shfl_xor_sync(0xffffffffu, sum, 2);
        const float r = rcp(sum);
        sts128(sb + R_S + 1280 + L16, pack2(sv[0].x * r, sv[0].y * r), pack2(sv[1].x * r, sv[1].y * r), pack2(sv[2].x * r, sv[2].y * r), pack2(sv[3].x * r, sv[3].y * r));
        sts32(sb + R_S + 1792 + (L16 >> 2), pack2(sv[4].x * r, sv[4].y * r));
      }
      TS(6);
#pragma unroll
      for (int i = 4; i < 16; i++) load_wo(i < NSW1 ? wv[i] : wt[i < NSW1 ? 0 : i - NSW1], i);
      TS(7);
      bar_sync(6, 256);
      uint64_t b[4][2];
#pragma unroll
      for (int i = 0; i < 4; i++) ldsm4q(b[i], sb + R_O + i * 512 + L16);
      zero(c);
#pragma unroll
      for (int i = 0; i < 16; i++) mma_b(c[i & 3], i < NSW1 ? wv[i] : wt[i < NSW1 ? 0 : i - NSW1], b[i >> 2][(i >> 1) & 1]);
      publish_b();
      tb = clk();
      TS(8);
#pragma unroll
      for (int i = 0; i < NSW1; i++) lds128(wv[i], uWvc + L16 + i * 2048);
      if (warp == 7) {
        delay_until(tb + DLY_K);
        if (L16 == 0 && s + 1 < NSEG) issue_kqv(s + 1);
        __syncwarp();
      }
      bar_sync(2, 256);
      uint32_t v[4]; lds128(v, sb + R_STAGE + 4096 + w4 * 1024 + (L16 ^ ((L16 >> 3) & 48)));
      *reinterpret_cast<uint4*>(reinterpret_cast<uint8_t*>(g_ox) + (((s * SEG + 8 * j) * HD + h * DH + 32 * w4) * 2 + (L16 >> 6) * (HD * 2) + (L16 & 48))) = make_uint4(v[0], v[1], v[2], v[3]);
      if (s + 1 == NSEG) break;
    }
    TS(9);
    project(s);
    TS(10);
    const uint8_t* src = xb + uC + L16;
    auto gather = [&](uint32_t tc) {
      delay_until(tc + DLY_C);
      TS(14);
#pragma unroll
      for (int i = 0; i < 4; i++) ldxb(own[i], src + i * 512);
    };
    if (wg == 0) {
      bar_arrive(2, 256);
      uint32_t bv[8];
      const uint8_t* bsrc = xb + uni(offsetof(Xchg, B) + role * 8192 + w4 * 1024) + (L16 >> 2);
      delay_until(tb + DLY_B);
#pragma unroll
      for (int i = 0; i < 8; i++) asm volatile("ld.relaxed.gpu.global.b32 %0, [%1];" : "=r"(bv[i]) : "l"(bsrc + i * 128) : "memory");
      __syncwarp();
      wg_wait<0>(); keep(aq); keep(av);
      const uint32_t cofs = pin(offsetof(Xchg, C) + j * 8192 + (L16 >> 8) * 4096 + h * 128 + (L16 & 128) / 2 + w4 * 16 + (L16 & 48) / 4 + (L16 & 64) / 32);
      const uint32_t first = pin((L16 & 112) == 0);
      park();
      if (warp == 0) {
        bar_sync(3, 128);
        if (L16 == 0 && s < NSEG - 2) issue_x(s + 3, 0);
        __syncwarp();
      } else bar_arrive(3, 128);
      TS(11);
      poll8_w(bv, bsrc, tag, (L16 & 48) == 0, it);
      TS(12);
      float lo[8], hi[8];
#pragma unroll
      for (int i = 0; i < 8; i++) { lo[i] = __uint_as_float(bv[i] << 16); hi[i] = __uint_as_float(bv[i] & 0xFFFF0000u); }
      const float l = ((lo[0] + lo[1]) + (lo[2] + lo[3])) + ((lo[4] + lo[5]) + (lo[6] + lo[7]));
      const float u = ((hi[0] + hi[1]) + (hi[2] + hi[3])) + ((hi[4] + hi[5]) + (hi[6] + hi[7]));
      float r = ((L16 & 128) ? u : l) + __shfl_xor_sync(0xffffffffu, (L16 & 128) ? l : u, 8);
      r += __shfl_xor_sync(0xffffffffu, r, 16);
      const uint32_t e = ((__float_as_uint(r) + (first ? 0x10000u - T : 0x8000u)) >> 16 & ~first) | (tag & first);
      asm volatile("st.relaxed.gpu.global.b16 [%0], %1;" :: "l"(xb + cofs), "h"((uint16_t)e) : "memory");
      const uint32_t tc = clk();
      sts32(sb + B_TC, tc);
      bar_arrive(7, 256);
      TS(13);
      gather(tc);
    } else {
      bar_sync(7, 256);
      const uint32_t tc = lds32(sb + B_TC);
      TS(11);
      wg_wait<1>(); keep(aq);
      fin_qk();
      TS(12);
      gather(tc);
      __syncwarp();
      wg_wait<0>(); keep(av);
      fin_v();
      TS(13);
      if (warp == 7) {
        bar_sync(1, 128);
        if (L16 == 0) { store_stage(s + 2); if (s < NSEG - 2) issue_x(s + 3, 1); }
        __syncwarp();
      } else bar_arrive(1, 128);
    }
    TS(15);
    poll4_b128(own, src, tag, it);
  }
  if (it > SPIN_LIMIT) g_err = 2;
}

typedef CUresult (*EncodeFn)(CUtensorMap*, CUtensorMapDataType, cuuint32_t, void*, const cuuint64_t*, const cuuint64_t*, const cuuint32_t*,
                             const cuuint32_t*, CUtensorMapInterleave, CUtensorMapSwizzle, CUtensorMapL2promotion, CUtensorMapFloatOOBfill);
static void make_map(EncodeFn fn, CUtensorMap* m, const void* p, uint64_t cols, uint64_t rows, uint64_t pitch, uint32_t bc, uint32_t br, CUtensorMapSwizzle sw) {
  cuuint64_t dims[2] = {cols, rows}, strides[1] = {pitch * 2};
  cuuint32_t box[2] = {bc, br}, es[2] = {1, 1};
  fn(m, CU_TENSOR_MAP_DATA_TYPE_BFLOAT16, 2, const_cast<void*>(p), dims, strides, box, es, CU_TENSOR_MAP_INTERLEAVE_NONE, sw,
     CU_TENSOR_MAP_L2_PROMOTION_L2_256B, CU_TENSOR_MAP_FLOAT_OOB_FILL_NONE);
}

extern "C" void kernel_launch(void* const* d_in, const int* in_sizes, int n_in, void* d_out, int out_size) {
  const bf16* Ax = (const bf16*)d_in[0]; const bf16* mem0 = (const bf16*)d_in[1];
  const bf16* Wq = (const bf16*)d_in[2]; const bf16* Wk = (const bf16*)d_in[3]; const bf16* Wv = (const bf16*)d_in[4];
  const bf16* Wo = (const bf16*)d_in[5];
  const bf16* Bx = (const bf16*)d_in[7]; const bf16* wr = (const bf16*)d_in[8]; const bf16* wi = (const bf16*)d_in[9];
  bf16* out = (bf16*)d_out;

  void* fp = nullptr; cudaDriverEntryPointQueryResult qr;
  cudaGetDriverEntryPoint("cuTensorMapEncodeTiled", &fp, cudaEnableDefault, &qr);
  EncodeFn fn = (EncodeFn)fp;
  void *kqv, *ox;
  cudaGetSymbolAddress(&kqv, g_kqv); cudaGetSymbolAddress(&ox, g_ox);
  const CUtensorMapSwizzle S128 = CU_TENSOR_MAP_SWIZZLE_128B, S64 = CU_TENSOR_MAP_SWIZZLE_64B;

  GemmMaps m3; RecMaps mr;
  make_map(fn, &m3.a, ox, HD, S_LEN, HD, 64, 128, S128);
  make_map(fn, &m3.b[0], Wo, DM, HD, DM, 64, 64, S128);
  m3.b[1] = m3.b[0]; m3.b[2] = m3.b[0];
  make_map(fn, &m3.c, out, DM, S_LEN, 2 * DM, 64, 64, S128);
  make_map(fn, &mr.wq, Wq, HD, DM, HD, 32, 256, S64);
  make_map(fn, &mr.wk, Wk, HD, DM, HD, 32, 256, S64);
  make_map(fn, &mr.wv, Wv, HD, DM, HD, 64, 256, S128);
  make_map(fn, &mr.wo, Wo, DM, HD, DM, 64, 128, S128);
  {
    cuuint64_t dims[4] = {64, S_LEN, 8, 2}, strides[3] = {DM * 2, 128, 1024};
    cuuint32_t box[4] = {64, 32, 4, 2}, es[4] = {1, 1, 1, 1};
    fn(&mr.x, CU_TENSOR_MAP_DATA_TYPE_BFLOAT16, 4, const_cast<bf16*>(Ax), dims, strides, box, es, CU_TENSOR_MAP_INTERLEAVE_NONE, S128,
       CU_TENSOR_MAP_L2_PROMOTION_L2_256B, CU_TENSOR_MAP_FLOAT_OOB_FILL_NONE);
  }
  for (int i = 0; i < 3; i++) {
    cuuint64_t dims[3] = {128, 32, 512}, strides[2] = {256, 8192};
    cuuint32_t box[3] = {128, i == 0 ? 8u : i == 1 ? 2u : 16u, 4}, es[3] = {1, 1, 1};
    fn(i == 0 ? &mr.k : i == 1 ? &mr.q : &mr.v, CU_TENSOR_MAP_DATA_TYPE_BFLOAT16, 3, kqv, dims, strides, box, es, CU_TENSOR_MAP_INTERLEAVE_NONE,
       CU_TENSOR_MAP_SWIZZLE_NONE, CU_TENSOR_MAP_L2_PROMOTION_L2_256B, CU_TENSOR_MAP_FLOAT_OOB_FILL_NONE);
  }
  {
    cuuint64_t dims[3] = {64, 16, S_LEN}, strides[2] = {128, 2 * DM * 2};
    cuuint32_t box[3] = {64, 16, 2}, es[3] = {1, 1, 1};
    fn(&mr.fo, CU_TENSOR_MAP_DATA_TYPE_BFLOAT16, 3, out + DM, dims, strides, box, es, CU_TENSOR_MAP_INTERLEAVE_NONE, S128,
       CU_TENSOR_MAP_L2_PROMOTION_NONE, CU_TENSOR_MAP_FLOAT_OOB_FILL_NONE);
  }
  constexpr int SM3 = 6 * 32768 + 32768 + 256 + 1024;
  cudaFuncSetAttribute(gemm_kernel<128, 6>, cudaFuncAttributeMaxDynamicSharedMemorySize, SM3);
  cudaFuncSetAttribute(rec_kernel, cudaFuncAttributeMaxDynamicSharedMemorySize, R_TOTAL);

  cudaStream_t st = cudaStreamPerThread;
  cudaFuncSetAttribute(fft_pre_kernel, cudaFuncAttributeMaxDynamicSharedMemorySize, F_SMEM);
  fft_pre_kernel<<<128, 256, F_SMEM, st>>>(Bx, wr, wi);
  rec_kernel<<<132, 256, R_TOTAL, st>>>(mr, Ax, mem0);
  gemm_kernel<128, 6><<<128, 384, SM3, st>>>(m3, 16, 8, 64, 8, 1);
}
```

```cpp
#include <cuda_runtime.h>
#include <cuda_bf16.h>
#include <cuda.h>
#include <stdint.h>
#include <stddef.h>
#include <type_traits>

typedef __nv_bfloat16 bf16;

constexpr int S_LEN = 2048, DM = 1024, NH = 32, DH = 128, MEM = 8, SEG = 32, NSEG = 64;
constexpr int HD = NH * DH;
constexpr int SPIN_LIMIT = 1 << 20, INC_A = 1, INC_B = 1;

__device__ __align__(1024) uint4 g_kqv[4][128][512];
__device__ __align__(1024) bf16 g_ox[(size_t)S_LEN * HD];
struct Xchg {
  uint4 A[32][2][2][256];
  uint4 C[4][2][256];
  uint4 B[128][2][256];
  unsigned ctr[64];
};
__device__ __align__(8192) Xchg g_x;
__device__ __align__(1024) uint4 g_y[1024 * 256];
__device__ __align__(1024) uint4 g_wt[513 * 512];
__device__ int g_err;

__device__ __forceinline__ unsigned clk() { unsigned long long c; asm volatile("mov.u64 %0, %%clock64;" : "=l"(c)); return (unsigned)c; }
__device__ __forceinline__ uint32_t smem_u32(const void* p) { return (uint32_t)__cvta_generic_to_shared(p); }
__device__ __forceinline__ void mbar_init(uint32_t bar, int cnt) { asm volatile("mbarrier.init.shared::cta.b64 [%0], %1;" :: "r"(bar), "r"(cnt) : "memory"); }
__device__ __forceinline__ void mbar_expect_tx(uint32_t bar, int bytes) { asm volatile("mbarrier.arrive.expect_tx.shared::cta.b64 _, [%0], %1;" :: "r"(bar), "r"(bytes) : "memory"); }
__device__ __forceinline__ void mbar_arrive(uint32_t bar) { asm volatile("mbarrier.arrive.shared::cta.b64 _, [%0];" :: "r"(bar) : "memory"); }
__device__ __forceinline__ void mbar_arrive_cluster(uint32_t bar, int cta) {
  asm volatile("{.reg .b32 r; mapa.shared::cluster.u32 r, %0, %1; mbarrier.arrive.shared::cluster.b64 _, [r];}" :: "r"(bar), "r"(cta) : "memory"); }
__device__ __forceinline__ bool mbar_try(uint32_t bar, int par) {
  uint32_t ok; asm volatile("{.reg .pred p; mbarrier.try_wait.parity.shared::cta.b64 p, [%1], %2; selp.u32 %0, 1, 0, p;}" : "=r"(ok) : "r"(bar), "r"(par) : "memory"); return ok; }
__device__ __forceinline__ void mbar_wait(uint32_t bar, int par) {
  int it = 0;
  while (!mbar_try(bar, par)) { if (++it > SPIN_LIMIT) { g_err = 1; break; } }
}
__device__ __forceinline__ void tma2d(uint32_t dst, const CUtensorMap* m, int c0, int c1, uint32_t bar) {
  asm volatile("cp.async.bulk.tensor.2d.shared::cluster.global.mbarrier::complete_tx::bytes [%0], [%1, {%3, %4}], [%2];"
    :: "r"(dst), "l"(m), "r"(bar), "r"(c0), "r"(c1) : "memory"); }
__device__ __forceinline__ void tma2d_mc(uint32_t dst, const CUtensorMap* m, int c0, int c1, uint32_t bar, uint16_t mask) {
  asm volatile("cp.async.bulk.tensor.2d.shared::cluster.global.mbarrier::complete_tx::bytes.multicast::cluster [%0], [%1, {%3, %4}], [%2], %5;"
    :: "r"(dst), "l"(m), "r"(bar), "r"(c0), "r"(c1), "h"(mask) : "memory"); }
__device__ __forceinline__ void tma2d_store(const CUtensorMap* m, uint32_t src, int c0, int c1) {
  asm volatile("cp.async.bulk.tensor.2d.global.shared::cta.bulk_group [%0, {%2, %3}], [%1];" :: "l"(m), "r"(src), "r"(c0), "r"(c1) : "memory"); }
__device__ __forceinline__ void fence_async() { asm volatile("fence.proxy.async.shared::cta;" ::: "memory"); }
__device__ __forceinline__ void bar_sync(int id, int n) { asm volatile("bar.sync %0, %1;" :: "r"(id), "r"(n) : "memory"); }
__device__ __forceinline__ void bar_arrive(int id, int n) { asm volatile("bar.arrive %0, %1;" :: "r"(id), "r"(n) : "memory"); }
__device__ __forceinline__ uint32_t pack2(float lo, float hi) { uint32_t r; asm("cvt.rn.bf16x2.f32 %0, %1, %2;" : "=r"(r) : "f"(hi), "f"(lo)); return r; }
__device__ __forceinline__ uint32_t pack2_tag(float lo, float hi, uint32_t T) {
  uint32_t u = ((__float_as_uint(lo) - T + 0x10000u) & 0xFFFE0000u) + T;
  return __byte_perm(u, pack2(0.f, hi), 0x7632); }
__device__ __forceinline__ void ldsm4(uint32_t (&r)[4], uint32_t a) {
  asm volatile("ldmatrix.sync.aligned.m8n8.x4.shared.b16 {%0,%1,%2,%3}, [%4];" : "=r"(r[0]), "=r"(r[1]), "=r"(r[2]), "=r"(r[3]) : "r"(a) : "memory"); }
__device__ __forceinline__ void ldsm4t(uint32_t (&r)[4], uint32_t a) {
  asm volatile("ldmatrix.sync.aligned.m8n8.x4.trans.shared.b16 {%0,%1,%2,%3}, [%4];" : "=r"(r[0]), "=r"(r[1]), "=r"(r[2]), "=r"(r[3]) : "r"(a) : "memory"); }
__device__ __forceinline__ void stsm4(uint32_t a, uint32_t r0, uint32_t r1, uint32_t r2, uint32_t r3) {
  asm volatile("stmatrix.sync.aligned.m8n8.x4.shared.b16 [%0], {%1,%2,%3,%4};" :: "r"(a), "r"(r0), "r"(r1), "r"(r2), "r"(r3) : "memory"); }
__device__ __forceinline__ void stsm4t(uint32_t a, uint32_t r0, uint32_t r1, uint32_t r2, uint32_t r3) {
  asm volatile("stmatrix.sync.aligned.m8n8.x4.trans.shared.b16 [%0], {%1,%2,%3,%4};" :: "r"(a), "r"(r0), "r"(r1), "r"(r2), "r"(r3) : "memory"); }
__device__ __forceinline__ void lds128(uint32_t (&r)[4], uint32_t a) {
  asm volatile("ld.shared.v4.u32 {%0,%1,%2,%3}, [%4];" : "=r"(r[0]), "=r"(r[1]), "=r"(r[2]), "=r"(r[3]) : "r"(a) : "memory"); }
__device__ __forceinline__ float4 lds128f(uint32_t a) { float4 r;
  asm volatile("ld.shared.v4.f32 {%0,%1,%2,%3}, [%4];" : "=f"(r.x), "=f"(r.y), "=f"(r.z), "=f"(r.w) : "r"(a) : "memory"); return r; }
__device__ __forceinline__ float2 lds64f(uint32_t a) { float2 r;
  asm volatile("ld.shared.v2.f32 {%0,%1}, [%2];" : "=f"(r.x), "=f"(r.y) : "r"(a) : "memory"); return r; }
__device__ __forceinline__ void sts128(uint32_t a, uint32_t r0, uint32_t r1, uint32_t r2, uint32_t r3) {
  asm volatile("st.shared.v4.u32 [%0], {%1,%2,%3,%4};" :: "r"(a), "r"(r0), "r"(r1), "r"(r2), "r"(r3) : "memory"); }
__device__ __forceinline__ void sts64f(uint32_t a, float x, float y) { asm volatile("st.shared.v2.f32 [%0], {%1,%2};" :: "r"(a), "f"(x), "f"(y) : "memory"); }
__device__ __forceinline__ void sts32f(uint32_t a, float x) { asm volatile("st.shared.f32 [%0], %1;" :: "r"(a), "f"(x) : "memory"); }
__device__ __forceinline__ void mma16816(float (&d)[4], uint32_t a0, uint32_t a1, uint32_t a2, uint32_t a3, uint32_t b0, uint32_t b1) {
  asm volatile("mma.sync.aligned.m16n8k16.row.col.f32.bf16.bf16.f32 {%0,%1,%2,%3}, {%4,%5,%6,%7}, {%8,%9}, {%0,%1,%2,%3};"
    : "+f"(d[0]), "+f"(d[1]), "+f"(d[2]), "+f"(d[3]) : "r"(a0), "r"(a1), "r"(a2), "r"(a3), "r"(b0), "r"(b1)); }
__device__ __forceinline__ void mma1688(float (&d)[4], uint32_t a0, uint32_t a1, uint32_t b0) {
  asm volatile("mma.sync.aligned.m16n8k8.row.col.f32.bf16.bf16.f32 {%0,%1,%2,%3}, {%4,%5}, {%6}, {%0,%1,%2,%3};"
    : "+f"(d[0]), "+f"(d[1]), "+f"(d[2]), "+f"(d[3]) : "r"(a0), "r"(a1), "r"(b0)); }
__device__ __forceinline__ void ldx128(uint32_t (&r)[4], const void* p) {
  asm volatile("{.reg .b128 t; .reg .b64 a, b; ld.relaxed.gpu.global.b128 t, [%4]; mov.b128 {a, b}, t; mov.b64 {%0,%1}, a; mov.b64 {%2,%3}, b;}"
    : "=r"(r[0]), "=r"(r[1]), "=r"(r[2]), "=r"(r[3]) : "l"(p) : "memory"); }
__device__ __forceinline__ void ldx2x64(uint32_t (&r)[4], const void* p) {
  asm volatile("{.reg .b64 a, b; ld.relaxed.gpu.global.v2.b64 {a, b}, [%4]; mov.b64 {%0,%1}, a; mov.b64 {%2,%3}, b;}"
    : "=r"(r[0]), "=r"(r[1]), "=r"(r[2]), "=r"(r[3]) : "l"(p) : "memory"); }
__device__ __forceinline__ void stx128(void* p, uint32_t r0, uint32_t r1, uint32_t r2, uint32_t r3) {
  asm volatile("{.reg .b128 t; .reg .b64 a, b; mov.b64 a, {%1,%2}; mov.b64 b, {%3,%4}; mov.b128 t, {a, b}; st.relaxed.gpu.global.b128 [%0], t;}"
    :: "l"(p), "r"(r0), "r"(r1), "r"(r2), "r"(r3) : "memory"); }
__device__ __forceinline__ void stx64(void* p, uint32_t r0, uint32_t r1) {
  asm volatile("{.reg .b64 a; mov.b64 a, {%1,%2}; st.relaxed.gpu.global.b64 [%0], a;}" :: "l"(p), "r"(r0), "r"(r1) : "memory"); }
__device__ __forceinline__ uint32_t uni(uint32_t x) { return __shfl_sync(0xffffffffu, x, 0); }
__device__ __forceinline__ uint32_t pin(uint32_t x) { return __shfl_xor_sync(0xffffffffu, x, 0); }
__device__ __forceinline__ float ex2(float x) { float r; asm("ex2.approx.ftz.f32 %0, %1;" : "=f"(r) : "f"(x)); return r; }
__device__ __forceinline__ void wg_fence() { asm volatile("wgmma.fence.sync.aligned;" ::: "memory"); }
__device__ __forceinline__ void wg_commit() { asm volatile("wgmma.commit_group.sync.aligned;" ::: "memory"); }
template <int N> __device__ __forceinline__ void wg_wait() { asm volatile("wgmma.wait_group.sync.aligned %0;" :: "n"(N) : "memory"); }

__device__ __forceinline__ void wgmma_ss_n256_tb1(float (&d)[128], uint64_t da, uint64_t db, int sc) {
  asm volatile("{.reg .pred p; setp.ne.b32 p, %130, 0;\n"
    "wgmma.mma_async.sync.aligned.m64n256k16.f32.bf16.bf16 {%0,%1,%2,%3,%4,%5,%6,%7,%8,%9,%10,%11,%12,%13,%14,%15,%16,%17,%18,%19,%20,%21,%22,%23,%24,%25,%26,%27,%28,%29,%30,%31,%32,%33,%34,%35,%36,%37,%38,%39,%40,%41,%42,%43,%44,%45,%46,%47,%48,%49,%50,%51,%52,%53,%54,%55,%56,%57,%58,%59,%60,%61,%62,%63,%64,%65,%66,%67,%68,%69,%70,%71,%72,%73,%74,%75,%76,%77,%78,%79,%80,%81,%82,%83,%84,%85,%86,%87,%88,%89,%90,%91,%92,%93,%94,%95,%96,%97,%98,%99,%100,%101,%102,%103,%104,%105,%106,%107,%108,%109,%110,%111,%112,%113,%114,%115,%116,%117,%118,%119,%120,%121,%122,%123,%124,%125,%126,%127}, %128, %129, p, 1, 1, 0, 1;}\n"
    : "+f"(d[0]),"+f"(d[1]),"+f"(d[2]),"+f"(d[3]),"+f"(d[4]),"+f"(d[5]),"+f"(d[6]),"+f"(d[7]),"+f"(d[8]),"+f"(d[9]),"+f"(d[10]),"+f"(d[11]),"+f"(d[12]),"+f"(d[13]),"+f"(d[14]),"+f"(d[15]),"+f"(d[16]),"+f"(d[17]),"+f"(d[18]),"+f"(d[19]),"+f"(d[20]),"+f"(d[21]),"+f"(d[22]),"+f"(d[23]),"+f"(d[24]),"+f"(d[25]),"+f"(d[26]),"+f"(d[27]),"+f"(d[28]),"+f"(d[29]),"+f"(d[30]),"+f"(d[31]),"+f"(d[32]),"+f"(d[33]),"+f"(d[34]),"+f"(d[35]),"+f"(d[36]),"+f"(d[37]),"+f"(d[38]),"+f"(d[39]),"+f"(d[40]),"+f"(d[41]),"+f"(d[42]),"+f"(d[43]),"+f"(d[44]),"+f"(d[45]),"+f"(d[46]),"+f"(d[47]),"+f"(d[48]),"+f"(d[49]),"+f"(d[50]),"+f"(d[51]),"+f"(d[52]),"+f"(d[53]),"+f"(d[54]),"+f"(d[55]),"+f"(d[56]),"+f"(d[57]),"+f"(d[58]),"+f"(d[59]),"+f"(d[60]),"+f"(d[61]),"+f"(d[62]),"+f"(d[63]),"+f"(d[64]),"+f"(d[65]),"+f"(d[66]),"+f"(d[67]),"+f"(d[68]),"+f"(d[69]),"+f"(d[70]),"+f"(d[71]),"+f"(d[72]),"+f"(d[73]),"+f"(d[74]),"+f"(d[75]),"+f"(d[76]),"+f"(d[77]),"+f"(d[78]),"+f"(d[79]),"+f"(d[80]),"+f"(d[81]),"+f"(d[82]),"+f"(d[83]),"+f"(d[84]),"+f"(d[85]),"+f"(d[86]),"+f"(d[87]),"+f"(d[88]),"+f"(d[89]),"+f"(d[90]),"+f"(d[91]),"+f"(d[92]),"+f"(d[93]),"+f"(d[94]),"+f"(d[95]),"+f"(d[96]),"+f"(d[97]),"+f"(d[98]),"+f"(d[99]),"+f"(d[100]),"+f"(d[101]),"+f"(d[102]),"+f"(d[103]),"+f"(d[104]),"+f"(d[105]),"+f"(d[106]),"+f"(d[107]),"+f"(d[108]),"+f"(d[109]),"+f"(d[110]),"+f"(d[111]),"+f"(d[112]),"+f"(d[113]),"+f"(d[114]),"+f"(d[115]),"+f"(d[116]),"+f"(d[117]),"+f"(d[118]),"+f"(d[119]),"+f"(d[120]),"+f"(d[121]),"+f"(d[122]),"+f"(d[123]),"+f"(d[124]),"+f"(d[125]),"+f"(d[126]),"+f"(d[127])
    : "l"(da), "l"(db), "r"(sc));
}

__device__ __forceinline__ void wgmma_ss_n128_tb1(float (&d)[64], uint64_t da, uint64_t db, int sc) {
  asm volatile("{.reg .pred p; setp.ne.b32 p, %66, 0;\n"
    "wgmma.mma_async.sync.aligned.m64n128k16.f32.bf16.bf16 {%0,%1,%2,%3,%4,%5,%6,%7,%8,%9,%10,%11,%12,%13,%14,%15,%16,%17,%18,%19,%20,%21,%22,%23,%24,%25,%26,%27,%28,%29,%30,%31,%32,%33,%34,%35,%36,%37,%38,%39,%40,%41,%42,%43,%44,%45,%46,%47,%48,%49,%50,%51,%52,%53,%54,%55,%56,%57,%58,%59,%60,%61,%62,%63}, %64, %65, p, 1, 1, 0, 1;}\n"
    : "+f"(d[0]),"+f"(d[1]),"+f"(d[2]),"+f"(d[3]),"+f"(d[4]),"+f"(d[5]),"+f"(d[6]),"+f"(d[7]),"+f"(d[8]),"+f"(d[9]),"+f"(d[10]),"+f"(d[11]),"+f"(d[12]),"+f"(d[13]),"+f"(d[14]),"+f"(d[15]),"+f"(d[16]),"+f"(d[17]),"+f"(d[18]),"+f"(d[19]),"+f"(d[20]),"+f"(d[21]),"+f"(d[22]),"+f"(d[23]),"+f"(d[24]),"+f"(d[25]),"+f"(d[26]),"+f"(d[27]),"+f"(d[28]),"+f"(d[29]),"+f"(d[30]),"+f"(d[31]),"+f"(d[32]),"+f"(d[33]),"+f"(d[34]),"+f"(d[35]),"+f"(d[36]),"+f"(d[37]),"+f"(d[38]),"+f"(d[39]),"+f"(d[40]),"+f"(d[41]),"+f"(d[42]),"+f"(d[43]),"+f"(d[44]),"+f"(d[45]),"+f"(d[46]),"+f"(d[47]),"+f"(d[48]),"+f"(d[49]),"+f"(d[50]),"+f"(d[51]),"+f"(d[52]),"+f"(d[53]),"+f"(d[54]),"+f"(d[55]),"+f"(d[56]),"+f"(d[57]),"+f"(d[58]),"+f"(d[59]),"+f"(d[60]),"+f"(d[61]),"+f"(d[62]),"+f"(d[63])
    : "l"(da), "l"(db), "r"(sc));
}

template <int BN> struct WG;
template <> struct WG<256> { static __device__ __forceinline__ void mma(float (&d)[128], uint64_t a, uint64_t b, int sc) { wgmma_ss_n256_tb1(d, a, b, sc); } };
template <> struct WG<128> { static __device__ __forceinline__ void mma(float (&d)[64], uint64_t a, uint64_t b, int sc) { wgmma_ss_n128_tb1(d, a, b, sc); } };

struct GemmMaps { CUtensorMap a, b[3], c; };
template <int BN, int STAGES>
__global__ void __cluster_dims__(2, 1, 1) __launch_bounds__(384, 1)
gemm_kernel(const __grid_constant__ GemmMaps maps, int tilesM, int tilesN, int kblocks, int nPerB, int clearX) {
  extern __shared__ __align__(1024) uint8_t smem_raw[];
  constexpr int STAGE_BYTES = 16384 + BN * 128;
  constexpr int NBOX = BN / 64;
  const uint32_t sbase = (smem_u32(smem_raw) + 1023) & ~1023u;
  const uint32_t sEpi = sbase + STAGES * STAGE_BYTES;
  const uint32_t sBar = sEpi + 32768;
  const int warp = threadIdx.x >> 5, lane = threadIdx.x & 31, wg = warp >> 2;
  uint32_t crank; asm("mov.u32 %0, %%cluster_ctarank;" : "=r"(crank));
  if (threadIdx.x == 0) {
    for (int i = 0; i < STAGES; i++) { mbar_init(sBar + 8 * i, 1); mbar_init(sBar + 8 * (STAGES + i), 4); }
    asm volatile("fence.mbarrier_init.release.cluster;" ::: "memory");
  }
  if (clearX) {
    uint4* p = reinterpret_cast<uint4*>(&g_x);
    for (int i = blockIdx.x * 384 + threadIdx.x; i < (int)(sizeof(Xchg) / 16); i += gridDim.x * 384) p[i] = make_uint4(0, 0, 0, 0);
  }
  asm volatile("barrier.cluster.arrive.release.aligned; barrier.cluster.wait.acquire.aligned;" ::: "memory");
  const int npairs = (tilesM >> 1) * tilesN, pair0 = blockIdx.x >> 1, pstep = gridDim.x >> 1;
  if (wg == 2) {
    asm volatile("setmaxnreg.dec.sync.aligned.u32 40;");
    if (warp == 8 && lane == 0) {
      int st = 0, ph = 1;
      for (int p = pair0; p < npairs; p += pstep) {
        const int tm = (p % (tilesM >> 1)) * 2 + crank, tn = p / (tilesM >> 1);
        const CUtensorMap* mb = &maps.b[tn / nPerB];
        const int n0 = (tn % nPerB) * BN;
        for (int kb = 0; kb < kblocks; kb++) {
          mbar_wait(sBar + 8 * (STAGES + st), ph);
          const uint32_t a = sbase + st * STAGE_BYTES, full = sBar + 8 * st;
          mbar_expect_tx(full, STAGE_BYTES);
          tma2d(a, &maps.a, kb * 64, tm * 128, full);
#pragma unroll
          for (int i = 0; i < NBOX / 2; i++) {
            const int bx = crank * (NBOX / 2) + i;
            tma2d_mc(a + 16384 + bx * 8192, mb, n0 + bx * 64, kb * 64, full, (uint16_t)3);
          }
          if (++st == STAGES) { st = 0; ph ^= 1; }
        }
      }
      for (int i = 0; i < STAGES; i++) { mbar_wait(sBar + 8 * (STAGES + st), ph); if (++st == STAGES) { st = 0; ph ^= 1; } }
    }
  } else {
    asm volatile("setmaxnreg.inc.sync.aligned.u32 232;");
    int st = 0, ph = 0;
    float acc[BN / 2];
    const uint64_t descA0 = (uint64_t)(((sbase + wg * 8192) & 0x3FFFF) >> 4) | (1ull << 16) | (64ull << 32) | (1ull << 62);
    const uint64_t descB0 = (uint64_t)(((sbase + 16384) & 0x3FFFF) >> 4) | (512ull << 16) | (64ull << 32) | (1ull << 62);
    const uint32_t epi = sEpi + wg * 16384;
    for (int p = pair0; p < npairs; p += pstep) {
      const int tm = (p % (tilesM >> 1)) * 2 + crank, tn = p / (tilesM >> 1);
      int prev = -1;
      for (int kb = 0; kb < kblocks; kb++) {
        mbar_wait(sBar + 8 * st, ph);
        wg_fence();
        const uint64_t so = (uint64_t)(st * (STAGE_BYTES >> 4));
#pragma unroll
        for (int k = 0; k < 4; k++) WG<BN>::mma(acc, descA0 + so + k * 2, descB0 + so + k * 128, kb | k);
        wg_commit();
        if (prev >= 0) {
          wg_wait<1>();
          if ((threadIdx.x & 127) < 2) mbar_arrive_cluster(sBar + 8 * (STAGES + prev), threadIdx.x & 1);
        }
        prev = st;
        if (++st == STAGES) { st = 0; ph ^= 1; }
      }
      wg_wait<0>();
      if ((threadIdx.x & 127) < 2) mbar_arrive_cluster(sBar + 8 * (STAGES + prev), threadIdx.x & 1);
#pragma unroll
      for (int r = 0; r < BN / 128; r++) {
        if ((threadIdx.x & 127) == 0) asm volatile("cp.async.bulk.wait_group.read 0;" ::: "memory");
        bar_sync(1 + wg, 128);
        const int row = (warp & 3) * 16 + (lane & 15);
#pragma unroll
        for (int i = 0; i < 8; i++) {
          const int c = 2 * (i & 3) + (lane >> 4);
          const float* q = &acc[r * 64 + i * 8];
          stsm4(epi + (i >> 2) * 8192 + row * 128 + ((c ^ (row & 7)) << 4), pack2(q[0], q[1]), pack2(q[2], q[3]), pack2(q[4], q[5]), pack2(q[6], q[7]));
        }
        fence_async();
        bar_sync(1 + wg, 128);
        if ((threadIdx.x & 127) == 0) {
          tma2d_store(&maps.c, epi, tn * BN + r * 128, tm * 128 + wg * 64);
          tma2d_store(&maps.c, epi + 8192, tn * BN + r * 128 + 64, tm * 128 + wg * 64);
          asm volatile("cp.async.bulk.commit_group;" ::: "memory");
        }
      }
    }
    if ((threadIdx.x & 127) == 0) asm volatile("cp.async.bulk.wait_group 0;" ::: "memory");
  }
}

struct Dft { uint32_t m[2][2][2][4]; };
template <bool P4> __device__ __forceinline__ int fidx(int tile, int x) { return P4 ? 4 * (x >> 1) + 2 * (tile & 1) + (x & 1) + 16 * (tile >> 1) : x + 8 * tile; }
__device__ __forceinline__ float2 cis(int k, int n) {
  k &= n - 1; if (2 * k > n) k -= n;
  const float a = (float)k * (6.283185307179586f / (float)n);
  return make_float2(__cosf(a), __sinf(a));
}
template <bool OUT4> __device__ __forceinline__ void make_dft(Dft& D, int g, int t) {
#pragma unroll
  for (int q = 0; q < 16; q++) {
    const int b = q >> 3, u = (q >> 2) & 1, r = (q >> 1) & 1, v = q & 1;
    const float2 w = cis(fidx<OUT4>(v, g) * fidx<false>(2 * u + r, 2 * t + b), 32);
    D.m[b][u][0][q & 3] = pack2(w.x, w.y); D.m[b][u][1][q & 3] = pack2(-w.y, w.x);
  }
}
__device__ __forceinline__ void mma_dc(float (&d)[4], uint32_t a0, uint32_t a1, uint32_t a2, uint32_t a3, uint32_t b0, uint32_t b1, const float (&c)[4]) {
  asm("mma.sync.aligned.m16n8k16.row.col.f32.bf16.bf16.f32 {%0,%1,%2,%3}, {%4,%5,%6,%7}, {%8,%9}, {%10,%11,%12,%13};"
    : "=f"(d[0]), "=f"(d[1]), "=f"(d[2]), "=f"(d[3]) : "r"(a0), "r"(a1), "r"(a2), "r"(a3), "r"(b0), "r"(b1), "f"(c[0]), "f"(c[1]), "f"(c[2]), "f"(c[3])); }
__device__ __forceinline__ void dft_b(const Dft& D, const uint32_t (&x)[2][4], float (&o)[2][8]) {
#pragma unroll
  for (int ri = 0; ri < 2; ri++) {
    float z[4] = {0.f, 0.f, 0.f, 0.f}, e[4], p[4];
    mma_dc(e, D.m[0][0][ri][0], D.m[0][0][ri][1], D.m[0][0][ri][2], D.m[0][0][ri][3], x[0][0], x[0][1], z);
    mma_dc(e, D.m[0][1][ri][0], D.m[0][1][ri][1], D.m[0][1][ri][2], D.m[0][1][ri][3], x[0][2], x[0][3], e);
    mma_dc(p, D.m[1][0][ri][0], D.m[1][0][ri][1], D.m[1][0][ri][2], D.m[1][0][ri][3], x[1][0], x[1][1], e);
    mma_dc(p, D.m[1][1][ri][0], D.m[1][1][ri][1], D.m[1][1][ri][2], D.m[1][1][ri][3], x[1][2], x[1][3], p);
#pragma unroll
    for (int q = 0; q < 4; q++) { o[ri][q] = p[q]; o[ri][4 + q] = fmaf(2.f, e[q], -p[q]); }
  }
}
__device__ __forceinline__ void dft_a(const uint32_t (&m)[2][2][4], const uint32_t (&x0)[2][4], const uint32_t (&x1)[2][4], float (&o)[2][8]) {
#pragma unroll
  for (int ri = 0; ri < 2; ri++) {
    float z[4] = {0.f, 0.f, 0.f, 0.f}, e[4], p[4];
    mma_dc(e, x0[0][0], x1[0][0], x0[0][1], x1[0][1], m[0][ri][0], m[0][ri][1], z);
    mma_dc(e, x0[0][2], x1[0][2], x0[0][3], x1[0][3], m[0][ri][2], m[0][ri][3], e);
    mma_dc(p, x0[1][0], x1[1][0], x0[1][1], x1[1][1], m[1][ri][0], m[1][ri][1], e);
    mma_dc(p, x0[1][2], x1[1][2], x0[1][3], x1[1][3], m[1][ri][2], m[1][ri][3], p);
#pragma unroll
    for (int q = 0; q < 4; q++) { o[ri][q] = p[q]; o[ri][4 + q] = fmaf(2.f, e[q], -p[q]); }
  }
}
__device__ __forceinline__ uint32_t twid(float re, float im, float c, float s) { return pack2(fmaf(re, c, im * s), fmaf(im, c, -re * s)); }
__device__ __forceinline__ void cpa16(uint32_t d, const void* s) { asm volatile("cp.async.cg.shared.global [%0], [%1], 16;" :: "r"(d), "l"(s) : "memory"); }
__device__ __forceinline__ void sts32(uint32_t a, uint32_t x) { asm volatile("st.shared.u32 [%0], %1;" :: "r"(a), "r"(x) : "memory"); }
__device__ __forceinline__ void cpa_commit() { asm volatile("cp.async.commit_group;" ::: "memory"); }
template <int N> __device__ __forceinline__ void cpa_wait() { asm volatile("cp.async.wait_group %0;" :: "n"(N) : "memory"); }
__device__ __forceinline__ uint32_t lds32(uint32_t a) { uint32_t r; asm volatile("ld.shared.u32 %0, [%1];" : "=r"(r) : "r"(a) : "memory"); return r; }
constexpr int F_TP = 4112, F_TSZ = 8 * F_TP;

__device__ __forceinline__ void fft_wprep(const bf16* __restrict__ wr, const bf16* __restrict__ wi, int cta, int ncta) {
  const int tid = threadIdx.x;
#pragma unroll 2
  for (int it = cta; it < 256; it += ncta) {
    const int g = (it >> 1) & 7, c = (it >> 4) & 3, i = it >> 6, t = 2 * (it & 1) + (tid & 1);
    const int k0 = g + 8 * i + 32 * (8 * c + 2 * t), l0 = (tid & ~1) + (g & 1);
    uint32_t a[2][4], b[2][4];
#pragma unroll
    for (int q = 0; q < 8; q++) {
      const int o = (k0 + 32 * ((q >> 1) & 1) + 1024 * (q & 1)) * 513 + l0 + 256 * (q >> 2);
      a[q >> 2][q & 3] = __ldg(reinterpret_cast<const uint32_t*>(wr + o));
      b[q >> 2][q & 3] = __ldg(reinterpret_cast<const uint32_t*>(wi + o));
    }
    uint4* dst = g_wt + l0 * 512 + it * 2 + (tid & 1);
#pragma unroll
    for (int q = 0; q < 4; q++) {
      const int hf = q >> 1, l = l0 + 256 * hf + (q & 1);
      const uint32_t sel = (q & 1) ? 0x7632 : 0x5410;
      if (l & 511) dst[(256 * hf + (q & 1)) * 512] = make_uint4(__byte_perm(a[hf][0], b[hf][0], sel), __byte_perm(a[hf][1], b[hf][1], sel),
                                                              __byte_perm(a[hf][2], b[hf][2], sel), __byte_perm(a[hf][3], b[hf][3], sel));
    }
  }
  for (int e = cta * 256 + tid; e < 4096; e += ncta * 256) {
    const int l = (e >> 11) * 512, k = e & 2047, kn = (2048 - k) & 2047, k2 = (k >> 5) & 31;
    const float re = 0.5f * (__bfloat162float(wr[k * 513 + l]) + __bfloat162float(wr[kn * 513 + l]));
    const float im = 0.5f * (__bfloat162float(wi[k * 513 + l]) - __bfloat162float(wi[kn * 513 + l]));
    reinterpret_cast<uint32_t*>(g_wt)[(64 * ((k >> 3) & 3) + 16 * (k2 >> 3) + 2 * (k & 7) + ((k2 >> 2) & 1)) * 8 + l * 2048 + 2 * (k2 & 3) + (k >> 10)] = pack2(re, im);
  }
}

__device__ __forceinline__ void fft_rows_fwd(const bf16* __restrict__ x, uint32_t sb, int cta, int ncta) {
  const int warp = threadIdx.x >> 5, lane = threadIdx.x & 31, g = lane >> 2, t = lane & 3;
  const uint32_t in = sb + warp * 8192, tb = sb + 65536;
  const uint32_t f0 = pin(in + (lane >> 3) * 256 + (((lane & 7) ^ (2 * (lane >> 3))) << 4));
  const uint32_t xo = pin((256 * (warp & 3) + 64 * (warp >> 2)) * 2048 + lane * 8);
  auto fetch = [&](int it, int buf) {
    const bf16* src = x + (xo + (128 * (it & 1) + 32 * ((it >> 4) & 1) + 8 * (it >> 5) + ((it >> 1) & 7)) * 2048);
#pragma unroll
    for (int q = 0; q < 8; q++) cpa16(((f0 + buf * 4096) ^ ((q >> 2) * 144)) + (q & 3) * 1024, src + q * 256);
    cpa_commit();
  };
  fetch(cta, 0);
  Dft D; make_dft<true>(D, g, t);
  float2 tw[4][8];
#pragma unroll
  for (int q = 0; q < 32; q++) tw[q >> 3][q & 7] = cis(fidx<true>((q >> 1) & 3, g) * fidx<false>(q >> 3, 2 * t + (q & 1)), 1024);
  const uint32_t la = pin(in + lane * 128 + ((lane & 7) << 4));
  const uint32_t wa = pin(tb + warp * F_TP + fidx<true>(0, g) * 128 + t * 16), wz = pin((g & 1) ? -64 : 64);
  const uint32_t ra = pin(tb + (lane & 1) * 4 * F_TP + ((lane >> 1) + 16 * (warp ^ ((warp >> 1) & 1))) * 4);
  uint4* dst = g_y + (threadIdx.x >> 1) * 256 + (lane & 1);
  int buf = 0;
  auto drain = [&](int it, int q) {
    const uint32_t r = ra + (buf ^ 1) * F_TSZ + q * 512;
    const uint4 v = make_uint4(lds32(r), lds32(r + F_TP), lds32(r + 2 * F_TP), lds32(r + 3 * F_TP));
    if (it >= 0) dst[it * 2 + q * 32768] = v;
  };
  int it = cta;
#pragma unroll 1
  for (; it < 128; it += ncta, buf ^= 1) {
    cpa_wait<0>(); __syncthreads();
    uint32_t a[4][2][4], y[4][2][4];
#pragma unroll
    for (int q = 0; q < 8; q++) ldsm4t(a[q & 3][q >> 2], (la + buf * 4096) ^ (q << 4));
    if (it + ncta < 128) fetch(it + ncta, buf ^ 1);
    float o[2][8];
#pragma unroll
    for (int i = 0; i < 4; i++) {
      dft_b(D, a[i], o);
      drain(it - ncta, i);
#pragma unroll
      for (int q = 0; q < 8; q++) y[q >> 1][q & 1][i] = twid(o[0][q], o[1][q], tw[i][q].x, tw[i][q].y);
    }
    const uint32_t w0 = wa + buf * F_TSZ + ((g & 1) << 6);
#pragma unroll
    for (int z = 0; z < 2; z++) {
      float o2[2][8];
      dft_b(D, y[2 * z], o); drain(it - ncta, 4 + 2 * z); dft_b(D, y[2 * z + 1], o2); drain(it - ncta, 5 + 2 * z);
#pragma unroll
      for (int i = 0; i < 4; i++) {
        const float sg = i < 2 ? 1.f : -1.f;
        sts128(w0 + z * wz + fidx<true>(i, 0) * 128, pack2(o[0][2 * i], sg * o[1][2 * i]), pack2(o[0][2 * i + 1], sg * o[1][2 * i + 1]),
               pack2(o2[0][2 * i], sg * o2[1][2 * i]), pack2(o2[0][2 * i + 1], sg * o2[1][2 * i + 1]));
      }
    }
  }
  __syncthreads();
#pragma unroll
  for (int q = 0; q < 8; q++) drain(it - ncta, q);
}

__device__ __forceinline__ void fft_cols(uint32_t sb, int cta, int ncta) {
  const int warp = threadIdx.x >> 5, lane = threadIdx.x & 31, g = lane >> 2, t = lane & 3;
  const uint32_t in = sb + warp * 16384 + lane * 16, tab = sb + 131072 + lane * 16;
  auto fetch_y = [&](int l) {
#pragma unroll
    for (int q = 0; q < 16; q++) cpa16(in + q * 512, g_y + (q < 8 ? l : (1024 - l) & 1023) * 256 + (q & 7) * 32 + lane);
  };
  auto fetch_w = [&](int l) {
#pragma unroll
    for (int q = 0; q < 16; q++) cpa16(in + 8192 + q * 512, g_wt + l * 512 + q * 32 + lane);
  };
  const int l0 = cta * 8 + warp, dl = ncta * 8;
  if (l0 <= 512) fetch_y(l0);
  cpa_commit();
  if (l0 <= 512) fetch_w(l0);
  cpa_commit();
  Dft D; make_dft<false>(D, g, t);
#pragma unroll
  for (int q = 2 * warp; q < 2 * warp + 2; q++) {
    const int r = fidx<false>(q & 3, g), c = fidx<false>(q >> 2, 2 * t);
    const float2 w0 = cis(r * c, 1024), w1 = cis(r * c + r, 1024), p0 = cis(r + 32 * c, 2048), p1 = cis(r + 32 * c + 32, 2048);
    sts128(tab + q * 512, __float_as_uint(w0.x), __float_as_uint(w0.y), __float_as_uint(w1.x), __float_as_uint(w1.y));
    sts128(tab + 8192 + q * 512, __float_as_uint(p0.x), __float_as_uint(p0.y), __float_as_uint(p1.x), __float_as_uint(p1.y));
  }
  if (warp == 0) {
#pragma unroll
    for (int q = 0; q < 8; q++) {
      const int v = q >> 2, b = (q >> 1) & 1, ri = q & 1;
      sts128(tab + 16384 + q * 512, D.m[b][0][ri][v], D.m[b][0][ri][v + 2], D.m[b][1][ri][v], D.m[b][1][ri][v + 2]);
    }
  }
  __syncthreads();
#pragma unroll 1
  for (int l = l0; l <= 512; l += dl) {
    uint32_t a[2][4][2][4], y[2][4][2][4];
    float o[2][2][8];
    cpa_wait<1>();
#pragma unroll
    for (int q = 0; q < 16; q++) lds128(a[q >> 3][(q >> 1) & 3][q & 1], in + q * 512);
    if (!(l & 511)) {
      const uint32_t m0 = l ? 0x80000000u : 0u;
#pragma unroll
      for (int q = 0; q < 32; q++) { a[0][q >> 3][(q >> 2) & 1][q & 3] ^= m0; a[1][q >> 3][(q >> 2) & 1][q & 3] ^= m0 ^ 0x80000000u; }
    }
    auto first = [&]() {
#pragma unroll
      for (int i = 0; i < 4; i++) {
        dft_b(D, a[0][i], o[0]); dft_b(D, a[1][i], o[1]);
#pragma unroll
        for (int r = 0; r < 4; r++) {
          const float4 w = lds128f(tab + (4 * i + r) * 512);
#pragma unroll
          for (int s = 0; s < 2; s++) {
            y[s][r][0][i] = twid(o[s][0][2 * r], o[s][1][2 * r], w.x, w.y);
            y[s][r][1][i] = twid(o[s][0][2 * r + 1], o[s][1][2 * r + 1], w.z, w.w);
          }
        }
      }
    };
    first();
    if (l + dl <= 512) fetch_y(l + dl);
    cpa_commit();
    cpa_wait<1>();
#pragma unroll
    for (int zv = 0; zv < 4; zv++) {
      const int z = zv >> 1, v = zv & 1;
      uint32_t m[2][2][4];
#pragma unroll
      for (int q = 0; q < 4; q++) lds128(m[q >> 1][q & 1], tab + 16384 + (4 * v + q) * 512);
      dft_a(m, y[0][2 * z], y[0][2 * z + 1], o[0]); dft_a(m, y[1][2 * z], y[1][2 * z + 1], o[1]);
#pragma unroll
      for (int q = 0; q < 4; q++) {
        const int i = 2 * z + (q & 1), c = v + (q & 2);
        uint32_t w[4]; lds128(w, in + 8192 + (4 * i + c) * 512);
        const float4 ph = lds128f(tab + 8192 + (4 * c + i) * 512);
#pragma unroll
        for (int b = 0; b < 2; b++) {
          const float cs = b ? ph.z : ph.x, sn = b ? ph.w : ph.y;
          const float r1 = __uint_as_float(w[2 * b] << 16), i1 = __uint_as_float(w[2 * b] & 0xFFFF0000u);
          const float r2 = __uint_as_float(w[2 * b + 1] << 16), i2 = __uint_as_float(w[2 * b + 1] & 0xFFFF0000u);
          const float Sr = r1 + r2, Si = i1 + i2, Dr = r1 - r2, Di = i1 - i2;
          const float ar = fmaf(-Dr, sn, Sr), ai = fmaf(-Di, sn, Si), dr = fmaf(Dr, sn, Sr), di = fmaf(Di, sn, Si), br = -Di * cs, bi = Dr * cs;
          const float Ar = o[0][0][2 * q + b], Ai = o[0][1][2 * q + b], Br = o[1][0][2 * q + b], Bi = o[1][1][2 * q + b];
          a[0][i][b][c] = pack2(fmaf(ar, Ai, fmaf(ai, Ar, fmaf(br, Bi, bi * Br))), fmaf(ar, Ar, fmaf(-ai, Ai, fmaf(br, Br, -bi * Bi))));
          a[1][i][b][c] = pack2(fmaf(dr, Bi, fmaf(di, Br, fmaf(-br, Ai, -bi * Ar))), fmaf(dr, Br, fmaf(-di, Bi, fmaf(-br, Ar, bi * Ai))));
        }
      }
    }
    if (l + dl <= 512) fetch_w(l + dl);
    cpa_commit();
    first();
#pragma unroll
    for (int s = 0; s < 2; s++) {
      uint4* dst = g_y + (s ? (1024 - l) & 1023 : l) * 256 + lane;
      const float sg = s ? -1.f : 1.f;
#pragma unroll
      for (int i = 0; i < 4; i++) {
        dft_b(D, y[s][i], o[0]);
#pragma unroll
        for (int b = 0; b < 2; b++)
          dst[(2 * i + b) * 32] = make_uint4(pack2(sg * o[0][0][b], o[0][1][b]), pack2(sg * o[0][0][2 + b], o[0][1][2 + b]),
                                             pack2(sg * o[0][0][4 + b], o[0][1][4 + b]), pack2(sg * o[0][0][6 + b], o[0][1][6 + b]));
      }
    }
  }
}

__device__ __forceinline__ void fft_rows_inv(const CUtensorMap* om, uint32_t sb, int cta, int ncta) {
  const int warp = threadIdx.x >> 5, lane = threadIdx.x & 31, g = lane >> 2, t = lane & 3, wg = warp >> 2, w4 = warp & 3;
  const uint32_t tb = sb + 32768 + wg * 2 * F_TSZ;
  const uint4* src = g_y + pin((256 * ((lane >> 1) & 3) + 64 * (lane >> 3) + 8 * w4) * 256 + (lane & 1));
  const uint32_t wa = pin(tb + (lane & 1) * 4 * F_TP + w4 * 1024 + (lane >> 1) * 4);
  uint4 pf[8];
  auto fetch = [&](int it, int hf) {
#pragma unroll
    for (int q = 0; q < 8; q++) pf[q] = __ldcg(src + (it * 2 + hf * 8192) + q * 256);
  };
  auto put = [&](uint32_t off) {
#pragma unroll
    for (int q = 0; q < 8; q++) {
      sts32(wa + off + q * 64, pf[q].x); sts32(wa + off + q * 64 + F_TP, pf[q].y);
      sts32(wa + off + q * 64 + 2 * F_TP, pf[q].z); sts32(wa + off + q * 64 + 3 * F_TP, pf[q].w);
    }
  };
  const int it0 = 2 * cta + wg;
  if (it0 >= 128) return;
  fetch(it0, 0); put(0); fetch(it0, 1); put(512);
  Dft D; make_dft<false>(D, g, t);
  float2 tw[4][8];
#pragma unroll
  for (int q = 0; q < 32; q++) {
    tw[q >> 3][q & 7] = cis(fidx<false>((q >> 1) & 3, g) * fidx<false>(q >> 3, 2 * t + (q & 1)), 1024);
    tw[q >> 3][q & 7].x *= 1.f / 2097152.f; tw[q >> 3][q & 7].y *= 1.f / 2097152.f;
  }
  const uint32_t la = pin(tb + w4 * F_TP + lane * 16), ob = uni(sb + warp * 4096);
  const uint32_t oa = pin(ob + (lane >> 1) * 128 + (((4 * (lane & 1)) ^ ((lane >> 1) & 7)) << 4));
#pragma unroll 1
  for (int n = 0;; n++) {
    const int it = it0 + (n >> 1) * 2 * ncta, hf = n & 1, buf = (n >> 1) & 1;
    if (it >= 128) break;
    if (!hf) bar_sync(1 + wg, 128);
    uint32_t a[4][2][4], y[4][2][4];
#pragma unroll
    for (int q = 0; q < 8; q++) lds128(a[q >> 1][q & 1], la + buf * F_TSZ + hf * 4 * F_TP + q * 512);
    fetch(min(it + 2 * ncta, 127), hf);
    float o[2][8];
#pragma unroll
    for (int i = 0; i < 4; i++) {
      dft_b(D, a[i], o);
#pragma unroll
      for (int q = 0; q < 8; q++) y[q >> 1][q & 1][i] = twid(o[0][q], o[1][q], tw[i][q].x, tw[i][q].y);
    }
    if (lane == 0) asm volatile("cp.async.bulk.wait_group.read 0;" ::: "memory");
    __syncwarp();
#pragma unroll
    for (int c = 0; c < 4; c++) {
      dft_b(D, y[c], o);
#pragma unroll
      for (int ri = 0; ri < 2; ri++)
        stsm4((oa ^ (c << 4)) + (1 - ri) * 2048, pack2(o[ri][0], o[ri][1]), pack2(o[ri][2], o[ri][3]), pack2(o[ri][4], o[ri][5]), pack2(o[ri][6], o[ri][7]));
    }
    fence_async();
    __syncwarp();
    if (lane == 0) {
      const int m = 256 * w4 + 32 * ((it >> 1) & 7) + 8 * (it >> 5) + 4 * (it & 1) + 2 * hf + ((it >> 4) & 1);
      asm volatile("cp.async.bulk.tensor.3d.global.shared::cta.bulk_group [%0, {0, 0, %2}], [%1];" :: "l"(om), "r"(ob), "r"(2 * m) : "memory");
      asm volatile("cp.async.bulk.commit_group;" ::: "memory");
    }
    put((buf ^ 1) * F_TSZ + hf * 512);
  }
  if (lane == 0) asm volatile("cp.async.bulk.wait_group 0;" ::: "memory");
}
constexpr int F_SMEM = 65536 + 2 * F_TSZ + 1024;
__global__ void __launch_bounds__(256, 1) fft_pre_kernel(const bf16* __restrict__ x, const bf16* __restrict__ wr, const bf16* __restrict__ wi) {
  extern __shared__ __align__(1024) uint8_t smem_raw[];
  const uint32_t sb = (smem_u32(smem_raw) + 1023) & ~1023u;
  fft_wprep(wr, wi, blockIdx.x, gridDim.x);
  fft_rows_fwd(x, sb, blockIdx.x, gridDim.x);
}
__device__ __forceinline__ void grid_arrive(unsigned* ctr) {
  __syncthreads();
  if (threadIdx.x == 0) { __threadfence(); atomicAdd(ctr, 1u); }
}
__device__ __forceinline__ void grid_wait(unsigned* ctr, unsigned n) {
  if (threadIdx.x == 0) {
    int it = 0;
    while (*reinterpret_cast<volatile unsigned*>(ctr) < n) { __nanosleep(200); if (++it > SPIN_LIMIT) { g_err = 3; break; } }
    __threadfence();
  }
  __syncthreads();
}

struct RecMaps { CUtensorMap wq, wk, wv, wo, x, k, q, v, fo; };
#define NSW0 12
#define NSW1 6
#define EXP 0
#define CPOS 30
#define NE0 4
#define NA0 12
#define NB0 14
#define NE1 2
#define NB1 15
#define NR0 7
constexpr int R_WO = 0, R_X = 65536, R_MEM = 131072, R_RED = 147456, R_WVC = 151552, R_STAGE = 188416, R_K = 196608, R_Q = 204800, R_V = 206848,
              R_S = 223232, R_O = 225792, R_SUM = 227840, R_BAR = 227968, R_TS = 228096,
              R_TOTAL = R_TS;
#define TS(i)
constexpr int B_KV = R_BAR, B_W = R_BAR + 8, B_X = R_BAR + 16, B_TC = R_BAR + 32;
#define DLY_A 450
#define DLY_V 400
#define DLY_B 650
#define DLY_C 500
#define DLY_W 180
#define DLY_L 90
__device__ __forceinline__ float rcp(float x) { float r; asm("rcp.approx.ftz.f32 %0, %1;" : "=f"(r) : "f"(x)); return r; }
__device__ __forceinline__ uint32_t movm(uint32_t a) { uint32_t d; asm volatile("movmatrix.sync.aligned.m8n8.trans.b16 %0, %1;" : "=r"(d) : "r"(a)); return d; }
__device__ __forceinline__ uint32_t hadd2(uint32_t a, uint32_t b) { uint32_t d; asm("add.rn.bf16x2 %0, %1, %2;" : "=r"(d) : "r"(a), "r"(b)); return d; }
__device__ __forceinline__ void mma_a(float (&d)[4], const uint32_t (&a)[4], uint32_t b0, uint32_t b1) { mma16816(d, a[0], a[1], a[2], a[3], b0, b1); }
__device__ __forceinline__ bool elect() {
  uint32_t p; asm volatile("{.reg .pred p; elect.sync _|p, 0xffffffff; selp.u32 %0, 1, 0, p;}" : "=r"(p)); return p; }
__device__ __forceinline__ void tma3d(uint32_t dst, const CUtensorMap* m, int c1, int c2, uint32_t bar) {
  asm volatile("cp.async.bulk.tensor.3d.shared::cluster.global.mbarrier::complete_tx::bytes [%0], [%1, {0, %3, %4}], [%2];"
    :: "r"(dst), "l"(m), "r"(bar), "r"(c1), "r"(c2) : "memory"); }
__device__ __forceinline__ void tma4d(uint32_t dst, const CUtensorMap* m, int c1, int c2, uint32_t bar) {
  asm volatile("cp.async.bulk.tensor.4d.shared::cluster.global.mbarrier::complete_tx::bytes [%0], [%1, {0, %3, %4, 0}], [%2];"
    :: "r"(dst), "l"(m), "r"(bar), "r"(c1), "r"(c2) : "memory"); }
template <int OFF, int ACC>
__device__ __forceinline__ void wg_rs32(float (&d)[16], const uint32_t (&a)[4], uint32_t db) {
  if (ACC)
    asm volatile("{.reg .b64 db; .reg .b32 lo; add.u32 lo, %20, %21; mov.b64 db, {lo, 0x40000040};\n"
      "wgmma.mma_async.sync.aligned.m64n32k16.f32.bf16.bf16 {%0,%1,%2,%3,%4,%5,%6,%7,%8,%9,%10,%11,%12,%13,%14,%15}, {%16,%17,%18,%19}, db, 1, 1, 1, 0;}"
      : "+f"(d[0]), "+f"(d[1]), "+f"(d[2]), "+f"(d[3]), "+f"(d[4]), "+f"(d[5]), "+f"(d[6]), "+f"(d[7]), "+f"(d[8]), "+f"(d[9]), "+f"(d[10]), "+f"(d[11]), "+f"(d[12]), "+f"(d[13]), "+f"(d[14]), "+f"(d[15])
      : "r"(a[0]), "r"(a[1]), "r"(a[2]), "r"(a[3]), "r"(db), "n"(OFF));
  else
    asm volatile("{.reg .b64 db; .reg .b32 lo; add.u32 lo, %20, %21; mov.b64 db, {lo, 0x40000040};\n"
      "wgmma.mma_async.sync.aligned.m64n32k16.f32.bf16.bf16 {%0,%1,%2,%3,%4,%5,%6,%7,%8,%9,%10,%11,%12,%13,%14,%15}, {%16,%17,%18,%19}, db, 0, 1, 1, 0;}"
      : "=f"(d[0]), "=f"(d[1]), "=f"(d[2]), "=f"(d[3]), "=f"(d[4]), "=f"(d[5]), "=f"(d[6]), "=f"(d[7]), "=f"(d[8]), "=f"(d[9]), "=f"(d[10]), "=f"(d[11]), "=f"(d[12]), "=f"(d[13]), "=f"(d[14]), "=f"(d[15])
      : "r"(a[0]), "r"(a[1]), "r"(a[2]), "r"(a[3]), "r"(db), "n"(OFF));
}
template <int I, int N, class F> __device__ __forceinline__ void sfor(F&& f) {
  if constexpr (I < N) { f(std::integral_constant<int, I>{}); sfor<I + 1, N>(f); }
}
__device__ __forceinline__ void keep(float (&d)[16]) {
  asm volatile("" : "+f"(d[0]), "+f"(d[1]), "+f"(d[2]), "+f"(d[3]), "+f"(d[4]), "+f"(d[5]), "+f"(d[6]), "+f"(d[7]),
      "+f"(d[8]), "+f"(d[9]), "+f"(d[10]), "+f"(d[11]), "+f"(d[12]), "+f"(d[13]), "+f"(d[14]), "+f"(d[15]) :: "memory");
}

template <int N> __device__ __forceinline__ void ldx(uint32_t (&v)[N][4], const uint8_t* p) {
#pragma unroll
  for (int i = 0; i < N; i++)
    asm volatile("ld.relaxed.gpu.global.v4.b32 {%0,%1,%2,%3}, [%4];" : "=r"(v[i][0]), "=r"(v[i][1]), "=r"(v[i][2]), "=r"(v[i][3]) : "l"(p + i * 512) : "memory");
}
__device__ __forceinline__ uint32_t dif2(uint32_t a, uint32_t b, uint32_t tag) { uint32_t r; asm("lop3.b32 %0, %1, %2, %3, 0x7e;" : "=r"(r) : "r"(a), "r"(b), "r"(tag)); return r; }
__device__ __forceinline__ uint32_t or3(uint32_t a, uint32_t b, uint32_t c) { uint32_t r; asm("lop3.b32 %0, %1, %2, %3, 0xfe;" : "=r"(r) : "r"(a), "r"(b), "r"(c)); return r; }
template <int W, int N> __device__ __forceinline__ uint32_t dif(const uint32_t (&v)[N][4], uint32_t tag) {
  if (W == 4) return dif2(v[0][0], v[1][0], tag) | dif2(v[2 % N][0], v[3 % N][0], tag);
  if (N == 2) return dif2(v[0][0], v[0][2], tag) | dif2(v[1][0], v[1][2], tag);
  uint32_t x = or3(dif2(v[0][0], v[0][2], tag), dif2(v[1][0], v[1][2], tag), dif2(v[2 % N][0], v[2 % N][2], tag));
  if (N == 8) x = or3(or3(x, dif2(v[3 % N][0], v[3 % N][2], tag), dif2(v[4 % N][0], v[4 % N][2], tag)), dif2(v[5 % N][0], v[5 % N][2], tag), dif2(v[6 % N][0], v[6 % N][2], tag));
  return x | dif2(v[N - 1][0], v[N - 1][2], tag);
}
template <int W, int N> __device__ __forceinline__ bool stale(const uint32_t (&v)[N][4], uint32_t tag, uint32_t mask = 1) {
  return __any_sync(0xffffffffu, dif<W>(v, tag) & mask);
}
template <int W, int N> __device__ __forceinline__ void retry(uint32_t (&v)[N][4], const uint8_t* p, uint32_t tag, int& it) {
#pragma unroll 1
  do {
#pragma unroll
    for (int i = 0; i < N; i++)
      asm volatile("{.reg .pred p; setp.ne.u32 p, %5, 0; @p ld.relaxed.gpu.global.v4.b32 {%0,%1,%2,%3}, [%4];}"
        : "+r"(v[i][0]), "+r"(v[i][1]), "+r"(v[i][2]), "+r"(v[i][3]) : "l"(p + i * 512), "r"(dif2(v[i][0], v[i][W & 2], tag) & 1) : "memory");
    it += W == 2 ? INC_A : 1;
  } while (stale<W>(v, tag) && it < SPIN_LIMIT);
}
__device__ __forceinline__ void mma_h(float (&d)[4], const uint32_t (&a)[4], const uint32_t (&b)[4], int hf) { mma16816(d, a[0], a[1], a[2], a[3], b[2 * hf], b[2 * hf + 1]); }
__device__ __forceinline__ void sts128(uint32_t a, const uint32_t (&r)[4]) { sts128(a, r[0], r[1], r[2], r[3]); }
__device__ __forceinline__ void sts128f(uint32_t a, const float* r) { sts128(a, __float_as_uint(r[0]), __float_as_uint(r[1]), __float_as_uint(r[2]), __float_as_uint(r[3])); }
__device__ __forceinline__ void mbar_spin(uint32_t bar, uint32_t par, int& it) {
  asm volatile("{.reg .pred p; .reg .b32 par; mov.b32 par, %2;\nLOOP: mbarrier.try_wait.parity.shared::cta.b64 p, [%1], par; @p bra.uni DONE;\n"
               "add.s32 %0, %0, 1; setp.le.s32 p, %0, %3; @p bra.uni LOOP;\nDONE: }" : "+r"(it) : "r"(bar), "r"(par), "n"(SPIN_LIMIT) : "memory"); }
__device__ __forceinline__ void delay_until(unsigned t) {
  asm volatile("{.reg .pred p; .reg .b64 c; .reg .b32 lo, hi;\nLOOP: mov.u64 c, %%clock64; mov.b64 {lo, hi}, c; sub.s32 lo, lo, %0; setp.lt.s32 p, lo, 0; @p bra.uni LOOP;}" :: "r"(t) : "memory"); }
__device__ __forceinline__ void cut(int it) { asm volatile("{.reg .pred p; setp.lt.s32 p, %0, 0;\nL: @p st.volatile.shared.u32 [%0], %0; @p bra.uni L;}" :: "r"(it) : "memory"); }
__device__ __forceinline__ void zero(float (&c)[4][4]) {
#pragma unroll
  for (int i = 0; i < 4; i++) c[i][0] = c[i][1] = c[i][2] = c[i][3] = 0.f;
}

template <int W4>
__device__ __forceinline__ void qk_gemm(const uint32_t (&w)[32][4], uint32_t (&own)[4][4], uint32_t (&be)[8][4], uint32_t a, float (&r)[4],
                                        const uint8_t* src, int s, int bar, int& it, uint32_t tsa) {
#pragma unroll
  for (int i = 0; i < 4; i++) sts128(a + i * 4096, own[i]);
  TS(13);
  if (stale<4>(own, s & 1, s > 0)) {
    retry<4>(own, src, s & 1, it);
#pragma unroll
    for (int i = 0; i < 4; i++) sts128(a + i * 4096, own[i]);
  }
  TS(1);
  bar_sync(bar, 128);
  float c[4][4];
  zero(c);
#pragma unroll
  for (int i = 0; i < 8; i++) mma_h(c[i & 3], w[8 * W4 + i], own[i >> 1], i & 1);
  uint32_t b[8][4];
#pragma unroll
  for (int q = 0; q < 16; q++) {
    const int p = q ^ 8;
    if ((p >> 2) != W4) { lds128(p < 8 ? be[p & 7] : b[p & 7], a + ((p >> 2) - W4) * 512 + (p & 3) * 4096); if (q & 1) __syncwarp(); }
  }
  if (W4 < 2) {
#pragma unroll
    for (int i = 0; i < 4; i++) lds128(be[4 * W4 + i], a + i * 4096);
  }
#pragma unroll
  for (int q = 0; q < 32; q++) {
    const int p = (q >> 1) ^ 8;
    if ((p >> 2) != W4) mma_h(c[q & 3], w[q ^ 16], p < 8 ? be[p & 7] : b[p & 7], q & 1);
  }
#pragma unroll
  for (int i = 0; i < 4; i++) { r[i] = (c[0][i] + c[1][i]) + (c[2][i] + c[3][i]); asm volatile("" : "+f"(r[i])); }
}

__global__ void __launch_bounds__(256, 1)
rec_kernel(const __grid_constant__ RecMaps maps, const bf16* __restrict__ xin, const bf16* __restrict__ mem0) {
  extern __shared__ __align__(1024) uint8_t smem_raw[];
  const uint32_t sb = smem_u32(smem_raw);
  int role = blockIdx.x;
  {
    uint32_t smid, nsm; asm volatile("mov.u32 %0, %%smid;" : "=r"(smid)); asm volatile("mov.u32 %0, %%nsmid;" : "=r"(nsm));
    const int p = smid >> 1, u = p - 32;
    if (nsm == gridDim.x)
      role = (smid & 1) + (p < 32 ? 4 * ((p & 7) + 8 * (p >> 4)) + 2 * ((p >> 3) & 1) : p < 60 ? 4 * (16 + u % 7 + 7 * (u / 14)) + 2 * ((u / 7) & 1)
                         : p < 62 ? 2 * p + 8 : 2 * p - 4);
    role = uni(role);
  }
  if (role >= 128) {
    fft_cols(sb, role - 128, 4);
    grid_arrive(&g_x.ctr[32]); grid_wait(&g_x.ctr[32], 4);
    fft_rows_inv(&maps.fo, sb, role - 128, 4);
    return;
  }
  const int tid = threadIdx.x, warp = uni(tid >> 5), lane = tid & 31, wg = warp >> 2, w4 = warp & 3, g = lane >> 2, t = lane & 3;
  const int h = role >> 2, j = role & 3, jh = j & 1;
  uint32_t wqk[32][4];
  uint32_t wv[16][4];
  uint32_t own[4][4];
  float aq[16], av[16];
  int it = 0;

  if (tid == 224) {
    mbar_init(sb + B_KV, 1); mbar_init(sb + B_W, 1); mbar_init(sb + B_X, 1); mbar_init(sb + B_X + 8, 1);
    asm volatile("fence.mbarrier_init.release.cluster;" ::: "memory");
    mbar_expect_tx(sb + B_W, 3 * 65536);
    for (int i = 0; i < 4; i++) {
      tma2d(sb + R_X + i * 16384, &maps.wq, h * DH + 32 * j, i * 256, sb + B_W);
      tma2d(sb + R_MEM + i * 16384, &maps.wk, h * DH + 32 * j, i * 256, sb + B_W);
    }
    for (int i = 0; i < 2; i++) tma2d(sb + R_WO + i * 32768, &maps.wv, h * DH + 64 * (j >> 1), jh * 512 + i * 256, sb + B_W);
    for (int i = 0; i < 4; i++) asm volatile("cp.async.bulk.prefetch.L2.global [%0], 8192;" :: "l"(xin + role * 16384 + i * 4096) : "memory");
    for (int i = 0; i < 4; i++)
      asm volatile("cp.async.bulk.prefetch.tensor.2d.L2.global [%0, {%1, %2}];" :: "l"(&maps.wo), "r"(256 * j + 64 * i), "r"(h * DH) : "memory");
  }
  const int kq = 2 * ((w4 >> 1) ^ jh) + wg;
  if (tid < 128) asm volatile("prefetch.global.L2 [%0];" :: "l"(mem0 + tid * 64));
  __syncthreads();
  mbar_spin(sb + B_W, 0, it);
  const int lrow = (lane & 7) + ((lane >> 4) << 3), lhi = (lane >> 3) & 1;
  {
    const int chunk = w4 < 2 ? w4 + 2 * lhi : 2 * (w4 & 1) + lhi;
    const uint32_t a = sb + (w4 < 2 ? R_X : R_MEM) + wg * 16384 + lrow * 64 + ((chunk ^ ((lrow >> 1) & 3)) << 4);
#pragma unroll
    for (int ks = 0; ks < 32; ks++) ldsm4t(wqk[ks], a + ((ks >> 4) ^ jh) * 32768 + (ks & 15) * 1024);
  }
  uint32_t L16 = pin(lane * 16);
  const uint32_t LW = lrow * 128 + ((lhi ^ (lane & 7)) << 4);
#pragma unroll
  for (int i = 0; i < 16; i++) ldsm4t(wv[i], sb + R_WO + wg * 32768 + (LW ^ (w4 << 5)) + i * 2048);
  const uint32_t uWo = uni(sb + R_WO + (warp >> 1) * 16384 + (warp & 1) * 1024), uWvc = uni(sb + R_WVC + wg * (NSW0 * 2048) + w4 * 512);
  const uint32_t uMem = uni(sb + R_MEM + warp * 512), uRed = uni(sb + R_RED + w4 * 1024);
  const uint32_t dB = uni(((sb + R_X + wg * 32768 + jh * 16384) >> 4) | 0x10000u);
  const uint32_t uBx = uni(sb + B_X + 8 * wg);
  auto load_wo = [&](uint32_t (&d)[16][4], int i0, int i1) {
#pragma unroll
    for (int i = i0; i < i1; i++) lds128(d[i], uWo + L16 + (i & 1) * 512 + (i >> 1) * 2048);
  };
  auto load_wv = [&](int i0, int i1) {
#pragma unroll
    for (int i = i0; i < i1; i++) lds128(wv[i], uWvc + L16 + i * 2048);
  };
  auto issue_x = [&](int n, int i) { mbar_expect_tx(sb + B_X + 8 * i, 32768); tma4d(sb + R_X + i * 32768, &maps.x, n * SEG, 4 * i, sb + B_X + 8 * i); };
  auto store_stage = [&](int n) {
    fence_async();
    asm volatile("cp.async.bulk.global.shared::cta.bulk_group [%0], [%1], 8192; cp.async.bulk.commit_group;" :: "l"(g_kqv[n & 3][role]), "r"(sb + R_STAGE) : "memory");
  };
  auto issue_kqv = [&](int n) {
    const int p = (n & 3) * 128 + 4 * h;
    mbar_expect_tx(sb + B_KV, 26624);
    tma3d(sb + R_K, &maps.k, 0, p, sb + B_KV); tma3d(sb + R_Q, &maps.q, 8 + 2 * j, p, sb + B_KV); tma3d(sb + R_V, &maps.v, 16, p, sb + B_KV);
  };
  auto wait_x = [&](int n) { if (!(EXP & 1) || n < 3) mbar_spin(uBx, n & 1, it); };
  auto project = [&](auto acc, auto&& mid) {
    wg_fence();
    sfor<0, 32>([&](auto I) {
      constexpr int i = decltype(I)::value;
      mid(i);
      wg_rs32<((i & 15) >> 2) * 256 + (i & 3) * 2, (i > 0 || decltype(acc)::value)>(aq, wqk[i ^ 16], i < 16 ? dB ^ 1024 : dB);
    });
    wg_commit();
    sfor<0, 16>([&](auto I) {
      constexpr int i = decltype(I)::value;
      mid(i + 32);
      wg_rs32<0x10000 + (i >> 2) * 256 + (i & 3) * 2, (i > 0 || decltype(acc)::value)>(av, wv[i], dB);
    });
    wg_commit();
    mid(48);
  };
  auto park = [&]() {
#pragma unroll
    for (int i = 0; i < 4; i++) { sts128f(uMem - 2048 + L16 + i * 4096, aq + 4 * i); sts128f(uMem + L16 + i * 4096, av + 4 * i); }
  };
  auto unpark = [&]() {
#pragma unroll
    for (int i = 0; i < 8; i++) {
      const float4 p = lds128f(uMem + (i >> 2) * 2048 + L16 + (i & 3) * 4096);
      float* d = (i < 4 ? aq : av) + 4 * (i & 3);
      d[0] = p.x; d[1] = p.y; d[2] = p.z; d[3] = p.w;
    }
  };
  auto fin_qk = [&]() {
    const uint32_t a = sb + R_STAGE + (w4 < 2 ? 2048 + w4 * 128 : (w4 & 1) * 256) + (L16 & 112) + (L16 >> 7) * 512;
    stsm4t(a, pack2(aq[0], aq[1]), pack2(aq[4], aq[5]), pack2(aq[8], aq[9]), pack2(aq[12], aq[13]));
    stsm4t(a + (w4 < 2 ? 256 : 128), pack2(aq[2], aq[3]), pack2(aq[6], aq[7]), pack2(aq[10], aq[11]), pack2(aq[14], aq[15]));
  };
  auto fin_v = [&]() {
#pragma unroll
    for (int a = 0; a < 2; a++)
      sts128(sb + R_STAGE + 4096 + w4 * 1024 + a * 512 + L16, pack2(av[8 * a], av[8 * a + 1]), pack2(av[8 * a + 2], av[8 * a + 3]),
             pack2(av[8 * a + 4], av[8 * a + 5]), pack2(av[8 * a + 6], av[8 * a + 7]));
  };
  __syncthreads();
  if (tid == 224) {
    issue_x(0, 1); issue_x(0, 0);
    mbar_expect_tx(sb + B_W, 65536);
    for (int i = 0; i < 4; i++) tma2d(sb + R_WO + i * 16384, &maps.wo, 256 * j + 64 * i, h * DH, sb + B_W);
  }
  __syncwarp();
#pragma unroll
  for (int i = 0; i < NSW0; i++)
    if (i < NSW1 || wg == 0) sts128(uWvc + L16 + i * 2048, wv[i]);
#pragma unroll 1
  for (int n = 0; n < 2; n++) {
    wait_x(n);
    if (wg == 0) { bar_sync(1, 256); unpark(); }
    else {
#pragma unroll
      for (int i = 0; i < 16; i++) aq[i] = av[i] = 0.f;
    }
    project(std::true_type{}, [](int) {});
    wg_wait<0>(); keep(aq); keep(av);
    if (wg == 1) {
      park();
      if (warp == 7) asm volatile("cp.async.bulk.wait_group 0;" ::: "memory");
      bar_sync(1, 256);
      if (tid == 128) issue_x(n + 1, 1);
      if (tid == 160 && n == 1) {
        __threadfence(); atomicAdd(&g_x.ctr[h], 1u);
        for (int k = 0; *reinterpret_cast<volatile unsigned*>(&g_x.ctr[h]) < 4 && k < SPIN_LIMIT; k++) {}
        __threadfence(); asm volatile("fence.proxy.async;" ::: "memory");
        issue_kqv(0);
      }
    } else { fin_qk(); fin_v(); }
    __syncthreads();
    if (warp == 7 && elect()) store_stage(n);
    if (tid == 0) issue_x(n + 1, 0);
    __syncwarp();
  }
#pragma unroll
  for (int i = 0; i < 16; i++)
    own[i >> 2][i & 3] = __ldg(reinterpret_cast<const uint32_t*>(mem0 + g * DM + 256 * kq + 128 * (w4 & 1) + 8 * i + 2 * t));
  mbar_spin(sb + B_W, 1, it);
#pragma unroll
  for (int i = 0; i < 4; i++) {
    uint32_t f[4][4];
    const uint32_t a = sb + R_WO + warp * 8192 + i * 2048;
#pragma unroll
    for (int q = 0; q < 4; q++) ldsm4t(f[q], a + (LW ^ (q << 5)));
    __syncwarp();
#pragma unroll
    for (int q = 0; q < 4; q++) sts128(a + q * 512 + L16, f[q]);
  }
  mbar_spin(sb + B_KV, 0, it);

  const float sc = 0.08838834764831845f * 1.4426950408889634f;
  uint8_t* const xb = reinterpret_cast<uint8_t*>(&g_x);
  uint8_t* const xa = xb + uni(h * 16384);
  const uint32_t uAq = uni((w4 >> 1) * 2048 + j * 512 + (w4 & 1) * 8), uAv = uni(8192 + (4 * (j >> 1) + w4) * 512 + jh * 8);
  const uint32_t uB = uni(offsetof(Xchg, B) + (16 * warp + j) * 8192 + h * 32);
  const uint32_t uC = uni(offsetof(Xchg, C) + kq * 8192 + (w4 & 1) * 2048);

#pragma unroll 1
  for (int s = 0;; s++) {
    const uint32_t tag = (s + 1) & 1;
    auto fresh = [&]() { L16 += (uint32_t)it >> 31; };
    const uint32_t tsa = 0;
    float c[4][4], r4[4];
    uint32_t be[8][4], wo[16][4];
    {
      const uint32_t a = uMem + L16;
      const uint8_t* src = xb + uC + L16;
      if (w4 < 2) { if (w4 == 0) qk_gemm<0>(wqk, own, be, a, r4, src, s, 4 - wg, it, tsa); else qk_gemm<1>(wqk, own, be, a, r4, src, s, 4 - wg, it, tsa); }
      else { if (w4 == 2) qk_gemm<2>(wqk, own, be, a, r4, src, s, 4 - wg, it, tsa); else qk_gemm<3>(wqk, own, be, a, r4, src, s, 4 - wg, it, tsa); }
    }
    auto fold = [&]() {
#pragma unroll
      for (int i = 0; i < 4; i++) r4[i] = (c[0][i] + c[1][i]) + (c[2][i] + c[3][i]);
    };
    auto v_gemm = [&]() {
      zero(c);
#pragma unroll
      for (int i = 0; i < 16; i++) mma_h(c[i & 3], wv[i], be[i >> 1], i & 1);
    };
    auto expo = [&](float2 (&sv)[5]) {
      float m = fmaxf(fmaxf(fmaxf(sv[0].x, sv[0].y), fmaxf(sv[1].x, sv[1].y)), fmaxf(fmaxf(sv[2].x, sv[2].y), fmaxf(sv[3].x, sv[3].y)));
      m = fmaxf(m, fmaxf(sv[4].x, sv[4].y));
      const float m1 = __shfl_xor_sync(0xffffffffu, m, 1), m2 = __shfl_xor_sync(0xffffffffu, m, 2), m3 = __shfl_xor_sync(0xffffffffu, m, 3);
      const float ms = -fmaxf(fmaxf(m, m1), fmaxf(m2, m3)) * sc;
#pragma unroll
      for (int i = 0; i < 5; i++) { sv[i].x = ex2(fmaf(sv[i].x, sc, ms)); sv[i].y = ex2(fmaf(sv[i].y, sc, ms)); }
      return (((sv[0].x + sv[0].y) + (sv[1].x + sv[1].y)) + ((sv[2].x + sv[2].y) + (sv[3].x + sv[3].y))) + (sv[4].x + sv[4].y);
    };
    auto out_proj = [&](int nb, auto&& more) {
      fresh();
      uint8_t* const dst = xb + uB + (((L16 >> 2) * 0x2021u) & 0x18C10u);
      bar_sync(6, 256);
      uint32_t b[4][4];
#pragma unroll
      for (int i = 0; i < 4; i++) { ldsm4(b[i], sb + R_O + i * 512 + L16); __syncwarp(); }
      load_wo(wo, nb, 16);
      zero(c);
#pragma unroll
      for (int i = 0; i < 16; i++) mma_h(c[i & 3], wo[i], b[i >> 2], (i >> 1) & 1);
      more();
      __syncwarp();
      stx128(dst, (pack2(c[0][0] + c[2][0], c[0][1] + c[2][1]) & ~1u) | tag, pack2(c[0][2] + c[2][2], c[0][3] + c[2][3]),
             pack2(c[1][0] + c[3][0], c[1][1] + c[3][1]), pack2(c[1][2] + c[3][2], c[1][3] + c[3][3]));
    };
    TS(0);
    if (wg == 0) {
      bar_sync(8 + w4, 64);
      float4 o4 = lds128f(uRed + L16);
      const uint32_t r0 = movm(pack2(r4[0] + o4.x, r4[1] + o4.y)), r1 = movm(pack2(r4[2] + o4.z, r4[3] + o4.w));
      stx64(xa + uAq + L16, (r0 & ~1u) | tag, r1);
      cut(it);
      TS(2);
      load_wo(wo, 0, NE0);
      v_gemm();
      bar_sync(12 + w4, 64);
      o4 = lds128f(uRed + 512 + L16);
      fold();
      stx64(xa + uAv + L16, (pack2(r4[0] + o4.x, r4[1] + o4.y) & ~1u) | tag, pack2(r4[2] + o4.z, r4[3] + o4.w));
      const unsigned tpub = clk();
      TS(3);
      const uint32_t sa = pin(sb + R_S + (L16 >> 1));
      delay_until(tpub + DLY_W);
      uint32_t vf[4][4], vm[2][4];
      const uint32_t va = sb + R_V + (w4 >> 1) * 8192 + (w4 & 1) * 2048 + L16;
#pragma unroll
      for (int i = 0; i < 4; i++) {
        uint32_t p[4]; lds128(vf[i], va + i * 512); lds128(p, va + 4096 + i * 512);
#pragma unroll
        for (int e = 0; e < 4; e++) vf[i][e] = hadd2(vf[i][e], p[e]);
      }
      load_wo(wo, NE0, NA0);
      const uint8_t* vsrc = xa + 8192 + w4 * 1024 + L16;
      delay_until(tpub + DLY_V);
      TS(4);
      ldx(vm, vsrc);
      bar_sync(5, 256);
      float2 sv[5];
#pragma unroll
      for (int i = 0; i < 5; i++) sv[i] = lds64f(sa + i * 256);
      const float sum = expo(sv);
      uint32_t p[5];
#pragma unroll
      for (int i = 0; i < 5; i++) p[i] = pack2(sv[i].x, sv[i].y);
      zero(c);
#pragma unroll
      for (int i = 0; i < 4; i++) mma_a(c[i & 1], vf[2 * (i & 1) + (i >> 1)], p[i & 2], p[(i & 2) + 1]);
      float rs[4] = {0.f, 0.f, 0.f, 0.f};
      { const float hi = __uint_as_float(__float_as_uint(sum) & 0xFFFF0000u); mma1688(rs, 0x3F803F80u, 0x3F803F80u, pack2(hi, sum - hi)); }
      mma_a(c[2], vm[0], p[4], p[4]); mma_a(c[3], vm[1], p[4], p[4]);
      if (stale<2>(vm, tag)) {
        retry<2>(vm, vsrc, tag, it);
#pragma unroll
        for (int i = 0; i < 8; i++) c[2 + (i >> 2)][i & 3] = 0.f;
        mma_a(c[2], vm[0], p[4], p[4]); mma_a(c[3], vm[1], p[4], p[4]);
      }
      TS(6);
      const float n0 = rcp(rs[0]), n1 = rcp(rs[1]);
      stsm4t(sb + R_O + w4 * 512 + L16, pack2((c[0][0] + c[2][0]) * n0, (c[0][1] + c[2][1]) * n1), pack2((c[0][2] + c[2][2]) * n0, (c[0][3] + c[2][3]) * n1),
             pack2((c[1][0] + c[3][0]) * n0, (c[1][1] + c[3][1]) * n1), pack2((c[1][2] + c[3][2]) * n0, (c[1][3] + c[3][3]) * n1));
      __syncwarp();
      load_wo(wo, NA0, NB0);
      TS(7);
      out_proj(NB0, [&]() {
        uint32_t q[4]; lds128(q, sb + R_S + 1280 + L16); p[0] = q[0]; p[1] = q[1]; p[2] = q[2]; p[3] = q[3]; p[4] = lds32(sb + R_S + 1792 + (L16 >> 2));
      });
      const unsigned tb = clk();
      cut(it);
      TS(8);
      float d[2][4] = {};
      zero(c);
      mma_a(d[0], vm[0], p[4], p[4]); mma_a(d[1], vm[1], p[4], p[4]);
#pragma unroll
      for (int i = 0; i < 4; i++) mma_a(c[i], vf[i], p[2 * (i & 1)], p[2 * (i & 1) + 1]);
      bar_arrive(2, 256);
      uint32_t o[4];
#pragma unroll
      for (int i = 0; i < 4; i++) {
        const int m = i >> 1, e = 2 * (i & 1);
        o[i] = pack2(d[m][e] + c[2 * m][e] + c[2 * m + 1][e], d[m][e + 1] + c[2 * m][e + 1] + c[2 * m + 1][e + 1]);
      }
      const uint32_t ob = uni(sb + R_STAGE + 4096 + w4 * 1024);
      stsm4t(ob + (L16 & 112) * 4 + (((L16 >> 3) ^ (L16 >> 1)) & 48), o[0], o[1], o[2], o[3]);
      if (!(EXP & 2) && warp == 0 && s + 1 < NSEG && elect()) issue_kqv(s + 1);
      __syncwarp();
      lds128(o, ob + (L16 ^ ((L16 >> 3) & 48)));
      load_wv(0, NR0);
      *reinterpret_cast<uint4*>(reinterpret_cast<uint8_t*>(g_ox) + (((s * SEG + 8 * j) * HD + h * DH + 32 * w4) * 2 + (L16 >> 6) * (HD * 2) + (L16 & 48))) = make_uint4(o[0], o[1], o[2], o[3]);
      if (s + 1 == NSEG) break;
      const uint8_t* bsrc = xb + uni(offsetof(Xchg, B) + role * 8192 + w4 * 1024) + (L16 >> 2);
      const uint32_t cofs = pin(offsetof(Xchg, C) + j * 8192 + h * 128 + (L16 & 128) / 2 + w4 * 16 + (L16 & 48) / 4 + (L16 & 64) / 32);
      const uint32_t first = pin((L16 & 112) == 0), rnd = pin(first ? 0x10000u - (tag << 16) : 0x8000u);
      wait_x(s + 2);
      fresh();
      delay_until(tb + DLY_B);
      TS(9);
      uint32_t bv[8];
      auto load_b = [&]() {
#pragma unroll
        for (int i = 0; i < 8; i++) asm volatile("ld.relaxed.gpu.global.b32 %0, [%1];" : "=r"(bv[i]) : "l"(bsrc + i * 128) : "memory");
      };
      auto stale_b = [&]() {
        const uint32_t x = or3(dif2(bv[0], bv[1], tag), dif2(bv[2], bv[3], tag), dif2(bv[4], bv[5], tag)) | dif2(bv[6], bv[7], tag);
        return __any_sync(0xffffffffu, x & ((L16 & 48) == 0));
      };
      auto sum_b = [&]() {
        float lo[8], hi[8];
#pragma unroll
        for (int i = 0; i < 8; i++) { lo[i] = __uint_as_float(bv[i] << 16); hi[i] = __uint_as_float(bv[i] & 0xFFFF0000u); }
        const float l = ((lo[0] + lo[1]) + (lo[2] + lo[3])) + ((lo[4] + lo[5]) + (lo[6] + lo[7]));
        const float u = ((hi[0] + hi[1]) + (hi[2] + hi[3])) + ((hi[4] + hi[5]) + (hi[6] + hi[7]));
        return ((L16 & 128) ? u : l) + __shfl_xor_sync(0xffffffffu, (L16 & 128) ? l : u, 8);
      };
      load_b();
      __syncwarp();
      load_wv(NR0, NSW0);
      bar_sync(0, 256);
      unpark();
      __syncwarp();
      TS(10);
      float r = sum_b();
      if (stale_b()) {
#pragma unroll 1
        do { load_b(); it += INC_B; } while (stale_b() && it < SPIN_LIMIT);
        r = sum_b();
      }
      r += __shfl_xor_sync(0xffffffffu, r, 16);
      const uint32_t e = ((__float_as_uint(r) + rnd) >> 16 & ~first) | (tag & first);
      if (L16 < 256) asm volatile("st.relaxed.gpu.global.b16 [%0], %1;" :: "l"(xb + cofs), "h"((uint16_t)e) : "memory");
      bar_arrive(7, 256);
      TS(11);
      const uint8_t* src = xb + uC + L16;
      project(std::true_type{}, [&](int n) {
        if (n == CPOS) { __syncwarp(); ldx(own, src); __syncwarp(); }
      });
      TS(12);
      wg_wait<1>(); keep(aq);
      fin_qk();
      wg_wait<0>(); keep(av);
      fin_v();
      bar_arrive(1, 256);
      TS(15);
    } else {
      sts128f(uRed + L16, r4);
      bar_sync(8 + w4, 64);
      load_wo(wo, 0, NE1);
      __syncwarp();
      const unsigned tpub = clk();
      TS(2);
      v_gemm();
      fold();
      if (warp == 7) asm volatile("cp.async.bulk.wait_group 0;" ::: "memory");
      sts128f(uRed + 512 + L16, r4);
      bar_arrive(12 + w4, 64);
      TS(3);
      const uint8_t* asrc = xa + L16;
      const uint32_t qa = sb + R_Q + (L16 & 112) + (L16 & 128) * 2 + (L16 >> 8) * 128;
      if (warp < 6) {
        uint32_t kf[8][4], q[4][4];
        const uint32_t ka = sb + R_K + w4 * 1024 + (L16 & 112) + (L16 & 128) * 4 + (L16 & 256);
#pragma unroll
        for (int i = 0; i < 8; i++) ldsm4(kf[i], ka + (i >> 1) * 2048 + (i & 1) * 128);
#pragma unroll
        for (int i = 0; i < 4; i++) ldsm4(q[i], qa + i * 512);
        const uint32_t sa = pin(sb + R_S + w4 * 512 + (L16 & 48) * 4 + (L16 >> 6) * 4);
        auto score = [&]() {
          zero(c);
#pragma unroll
          for (int i = 0; i < 8; i++) mma_h(c[i & 3], kf[i], q[i >> 1], i & 1);
        };
        score();
        fold();
#pragma unroll
        for (int i = 0; i < 4; i++) sts32f(sa + 1280 + (i & 1) * 32 + (i >> 1) * 256, r4[i]);
        delay_until(tpub + DLY_A);
        TS(4);
        ldx(q, asrc);
        score();
        if (stale<2>(q, tag)) { retry<2>(q, asrc, tag, it); score(); }
        TS(5);
        fold();
#pragma unroll
        for (int i = 0; i < 4; i++) sts32f(sa + (i & 1) * 32 + (i >> 1) * 256, r4[i]);
        bar_sync(5, 256);
        delay_until(clk() + DLY_L);
        load_wo(wo, NE1, NB1);
      } else {
        uint32_t qk[8][4];
        uint32_t (&q)[4][4] = reinterpret_cast<uint32_t (&)[4][4]>(qk[0]), (&k)[4][4] = reinterpret_cast<uint32_t (&)[4][4]>(qk[4]);
        load_wo(wo, NE1, NE1 + 4);
        auto score = [&]() {
          zero(c);
#pragma unroll
          for (int i = 0; i < 8; i++) mma_h(c[i & 3], q[i >> 1], k[i >> 1], i & 1);
        };
        if (warp == 6) {
          delay_until(tpub + DLY_A);
          TS(4);
          ldx(qk, asrc);
          score();
          if (stale<2>(qk, tag)) { retry<2>(qk, asrc, tag, it); score(); }
          TS(5);
          sts64f(sb + R_S + 1024 + (L16 >> 1), (c[0][0] + c[1][2]) + (c[2][0] + c[3][2]), (c[0][1] + c[1][3]) + (c[2][1] + c[3][3]));
          bar_sync(5, 256);
          delay_until(clk() + DLY_L);
        } else {
#pragma unroll
          for (int i = 0; i < 4; i++) ldsm4(q[i], qa + i * 512);
          delay_until(tpub + DLY_A);
          TS(4);
          ldx(k, asrc + 2048);
          score();
          if (stale<2>(k, tag)) { retry<2>(k, asrc + 2048, tag, it); score(); }
          TS(5);
          bar_sync(5, 256);
          float2 sv[5];
          const int dq = (int)(L16 >> 6) - (int)((L16 >> 3) & 6) + 8 * j;
#pragma unroll
          for (int i = 0; i < 4; i++) {
            sv[i] = lds64f(sb + R_S + 1280 + (L16 >> 1) + i * 256);
            if (8 * i > dq) sv[i].x = -INFINITY;
            if (8 * i + 1 > dq) sv[i].y = -INFINITY;
          }
          sv[4] = make_float2((c[0][0] + c[1][2]) + (c[2][0] + c[3][2]), (c[0][1] + c[1][3]) + (c[2][1] + c[3][3]));
          const float sum = expo(sv);
          const float s1 = __shfl_xor_sync(0xffffffffu, sum, 1), s2 = __shfl_xor_sync(0xffffffffu, sum, 2), s3 = __shfl_xor_sync(0xffffffffu, sum, 3);
          const float r = rcp((sum + s1) + (s2 + s3));
          sts128(sb + R_S + 1280 + L16, pack2(sv[0].x * r, sv[0].y * r), pack2(sv[1].x * r, sv[1].y * r), pack2(sv[2].x * r, sv[2].y * r), pack2(sv[3].x * r, sv[3].y * r));
          sts32(sb + R_S + 1792 + (L16 >> 2), pack2(sv[4].x * r, sv[4].y * r));
        }
        load_wo(wo, NE1 + 4, NB1);
      }
      TS(7);
      out_proj(NB1, [&]() { load_wv(0, NSW1); });
      TS(8);
      if (s + 1 == NSEG) { bar_sync(2, 256); break; }
      wait_x(s + 2);
      bar_sync(2, 256);
      TS(9);
      project(std::false_type{}, [](int) {});
      TS(10);
      wg_wait<0>(); keep(aq); keep(av);
      park();
      if (warp == 5) {
        bar_sync(0, 256);
        if (!(EXP & 1) && s < NSEG - 2 && elect()) issue_x(s + 3, 1);
        __syncwarp();
      } else bar_arrive(0, 256);
      TS(11);
      if (!(EXP & 2)) mbar_spin(sb + B_KV, tag, it);
      fresh();
      const uint8_t* src = xb + uC + L16;
      bar_sync(7, 256);
      cut(it);
      delay_until(clk() + DLY_C);
      TS(14);
      ldx(own, src);
      bar_sync(1, 256);
      if (!(EXP & 4) && warp == 7 && elect()) store_stage(s + 2);
      if (!(EXP & 1) && warp == 6 && s < NSEG - 2 && elect()) issue_x(s + 3, 0);
      __syncwarp();
      TS(15);
    }
  }
  if (it >= SPIN_LIMIT) g_err = 2;
}

typedef CUresult (*EncodeFn)(CUtensorMap*, CUtensorMapDataType, cuuint32_t, void*, const cuuint64_t*, const cuuint64_t*, const cuuint32_t*,
                             const cuuint32_t*, CUtensorMapInterleave, CUtensorMapSwizzle, CUtensorMapL2promotion, CUtensorMapFloatOOBfill);
static void make_map(EncodeFn fn, CUtensorMap* m, const void* p, uint64_t cols, uint64_t rows, uint64_t pitch, uint32_t bc, uint32_t br, CUtensorMapSwizzle sw) {
  cuuint64_t dims[2] = {cols, rows}, strides[1] = {pitch * 2};
  cuuint32_t box[2] = {bc, br}, es[2] = {1, 1};
  fn(m, CU_TENSOR_MAP_DATA_TYPE_BFLOAT16, 2, const_cast<void*>(p), dims, strides, box, es, CU_TENSOR_MAP_INTERLEAVE_NONE, sw,
     CU_TENSOR_MAP_L2_PROMOTION_L2_256B, CU_TENSOR_MAP_FLOAT_OOB_FILL_NONE);
}

extern "C" void kernel_launch(void* const* d_in, const int* in_sizes, int n_in, void* d_out, int out_size) {
  const bf16* Ax = (const bf16*)d_in[0]; const bf16* mem0 = (const bf16*)d_in[1];
  const bf16* Wq = (const bf16*)d_in[2]; const bf16* Wk = (const bf16*)d_in[3]; const bf16* Wv = (const bf16*)d_in[4];
  const bf16* Wo = (const bf16*)d_in[5];
  const bf16* Bx = (const bf16*)d_in[7]; const bf16* wr = (const bf16*)d_in[8]; const bf16* wi = (const bf16*)d_in[9];
  bf16* out = (bf16*)d_out;

  void* fp = nullptr; cudaDriverEntryPointQueryResult qr;
  cudaGetDriverEntryPoint("cuTensorMapEncodeTiled", &fp, cudaEnableDefault, &qr);
  EncodeFn fn = (EncodeFn)fp;
  void *kqv, *ox;
  cudaGetSymbolAddress(&kqv, g_kqv); cudaGetSymbolAddress(&ox, g_ox);
  const CUtensorMapSwizzle S128 = CU_TENSOR_MAP_SWIZZLE_128B, S64 = CU_TENSOR_MAP_SWIZZLE_64B;

  GemmMaps m3; RecMaps mr;
  make_map(fn, &m3.a, ox, HD, S_LEN, HD, 64, 128, S128);
  make_map(fn, &m3.b[0], Wo, DM, HD, DM, 64, 64, S128);
  m3.b[1] = m3.b[0]; m3.b[2] = m3.b[0];
  make_map(fn, &m3.c, out, DM, S_LEN, 2 * DM, 64, 64, S128);
  make_map(fn, &mr.wq, Wq, HD, DM, HD, 32, 256, S64);
  make_map(fn, &mr.wk, Wk, HD, DM, HD, 32, 256, S64);
  make_map(fn, &mr.wv, Wv, HD, DM, HD, 64, 256, S128);
  make_map(fn, &mr.wo, Wo, DM, HD, DM, 64, 128, S128);
  {
    cuuint64_t dims[4] = {64, S_LEN, 8, 2}, strides[3] = {DM * 2, 128, 1024};
    cuuint32_t box[4] = {64, 32, 4, 2}, es[4] = {1, 1, 1, 1};
    fn(&mr.x, CU_TENSOR_MAP_DATA_TYPE_BFLOAT16, 4, const_cast<bf16*>(Ax), dims, strides, box, es, CU_TENSOR_MAP_INTERLEAVE_NONE, S128,
       CU_TENSOR_MAP_L2_PROMOTION_L2_256B, CU_TENSOR_MAP_FLOAT_OOB_FILL_NONE);
  }
  for (int i = 0; i < 3; i++) {
    cuuint64_t dims[3] = {128, 32, 512}, strides[2] = {256, 8192};
    cuuint32_t box[3] = {128, i == 0 ? 8u : i == 1 ? 2u : 16u, 4}, es[3] = {1, 1, 1};
    fn(i == 0 ? &mr.k : i == 1 ? &mr.q : &mr.v, CU_TENSOR_MAP_DATA_TYPE_BFLOAT16, 3, kqv, dims, strides, box, es, CU_TENSOR_MAP_INTERLEAVE_NONE,
       CU_TENSOR_MAP_SWIZZLE_NONE, CU_TENSOR_MAP_L2_PROMOTION_L2_256B, CU_TENSOR_MAP_FLOAT_OOB_FILL_NONE);
  }
  {
    cuuint64_t dims[3] = {64, 16, S_LEN}, strides[2] = {128, 2 * DM * 2};
    cuuint32_t box[3] = {64, 16, 2}, es[3] = {1, 1, 1};
    fn(&mr.fo, CU_TENSOR_MAP_DATA_TYPE_BFLOAT16, 3, out + DM, dims, strides, box, es, CU_TENSOR_MAP_INTERLEAVE_NONE, S128,
       CU_TENSOR_MAP_L2_PROMOTION_NONE, CU_TENSOR_MAP_FLOAT_OOB_FILL_NONE);
  }
  constexpr int SM3 = 6 * 32768 + 32768 + 256 + 1024;
  cudaFuncSetAttribute(gemm_kernel<128, 6>, cudaFuncAttributeMaxDynamicSharedMemorySize, SM3);
  cudaFuncSetAttribute(rec_kernel, cudaFuncAttributeMaxDynamicSharedMemorySize, R_TOTAL);

  cudaStream_t st = cudaStreamPerThread;
  cudaFuncSetAttribute(fft_pre_kernel, cudaFuncAttributeMaxDynamicSharedMemorySize, F_SMEM);
  fft_pre_kernel<<<128, 256, F_SMEM, st>>>(Bx, wr, wi);
  rec_kernel<<<132, 256, R_TOTAL, st>>>(mr, Ax, mem0);
  gemm_kernel<128, 6><<<128, 384, SM3, st>>>(m3, 16, 8, 64, 8, 1);
}
```

```cpp
#include <cuda_runtime.h>
#include <cuda_bf16.h>
#include <cuda.h>
#include <stdint.h>
#include <stddef.h>
#include <type_traits>

typedef __nv_bfloat16 bf16;

constexpr int S_LEN = 2048, DM = 1024, NH = 32, DH = 128, MEM = 8, SEG = 32, NSEG = 64;
constexpr int HD = NH * DH;
constexpr int SPIN_LIMIT = 1 << 20, INC_A = 1, INC_B = 1;

__device__ __align__(1024) uint4 g_kqv[4][128][512];
__device__ __align__(1024) bf16 g_ox[(size_t)S_LEN * HD];
struct Xchg {
  uint4 A[32][2][2][256];
  uint4 C[2][4][256];
  uint4 B[128][2][256];
  uint32_t T[32][32];
  unsigned ctr[64];
};
__device__ __align__(8192) Xchg g_x;
__device__ __align__(1024) uint4 g_y[1024 * 256];
__device__ __align__(1024) uint4 g_wt[513 * 512];
__device__ int g_err;

__device__ __forceinline__ unsigned clk() { unsigned long long c; asm volatile("mov.u64 %0, %%clock64;" : "=l"(c)); return (unsigned)c; }
__device__ __forceinline__ uint32_t smem_u32(const void* p) { return (uint32_t)__cvta_generic_to_shared(p); }
__device__ __forceinline__ void mbar_init(uint32_t bar, int cnt) { asm volatile("mbarrier.init.shared::cta.b64 [%0], %1;" :: "r"(bar), "r"(cnt) : "memory"); }
__device__ __forceinline__ void mbar_expect_tx(uint32_t bar, int bytes) { asm volatile("mbarrier.arrive.expect_tx.shared::cta.b64 _, [%0], %1;" :: "r"(bar), "r"(bytes) : "memory"); }
__device__ __forceinline__ void mbar_arrive(uint32_t bar) { asm volatile("mbarrier.arrive.shared::cta.b64 _, [%0];" :: "r"(bar) : "memory"); }
__device__ __forceinline__ void mbar_arrive_cluster(uint32_t bar, int cta) {
  asm volatile("{.reg .b32 r; mapa.shared::cluster.u32 r, %0, %1; mbarrier.arrive.shared::cluster.b64 _, [r];}" :: "r"(bar), "r"(cta) : "memory"); }
__device__ __forceinline__ bool mbar_try(uint32_t bar, int par) {
  uint32_t ok; asm volatile("{.reg .pred p; mbarrier.try_wait.parity.shared::cta.b64 p, [%1], %2; selp.u32 %0, 1, 0, p;}" : "=r"(ok) : "r"(bar), "r"(par) : "memory"); return ok; }
__device__ __forceinline__ void mbar_wait(uint32_t bar, int par) {
  int it = 0;
  while (!mbar_try(bar, par)) { if (++it > SPIN_LIMIT) { g_err = 1; break; } }
}
__device__ __forceinline__ void tma2d(uint32_t dst, const CUtensorMap* m, int c0, int c1, uint32_t bar) {
  asm volatile("cp.async.bulk.tensor.2d.shared::cluster.global.mbarrier::complete_tx::bytes [%0], [%1, {%3, %4}], [%2];"
    :: "r"(dst), "l"(m), "r"(bar), "r"(c0), "r"(c1) : "memory"); }
__device__ __forceinline__ void tma2d_mc(uint32_t dst, const CUtensorMap* m, int c0, int c1, uint32_t bar, uint16_t mask) {
  asm volatile("cp.async.bulk.tensor.2d.shared::cluster.global.mbarrier::complete_tx::bytes.multicast::cluster [%0], [%1, {%3, %4}], [%2], %5;"
    :: "r"(dst), "l"(m), "r"(bar), "r"(c0), "r"(c1), "h"(mask) : "memory"); }
__device__ __forceinline__ void tma2d_store(const CUtensorMap* m, uint32_t src, int c0, int c1) {
  asm volatile("cp.async.bulk.tensor.2d.global.shared::cta.bulk_group [%0, {%2, %3}], [%1];" :: "l"(m), "r"(src), "r"(c0), "r"(c1) : "memory"); }
__device__ __forceinline__ void fence_async() { asm volatile("fence.proxy.async.shared::cta;" ::: "memory"); }
__device__ __forceinline__ void bar_sync(int id, int n) { asm volatile("bar.sync %0, %1;" :: "r"(id), "r"(n) : "memory"); }
__device__ __forceinline__ void bar_arrive(int id, int n) { asm volatile("bar.arrive %0, %1;" :: "r"(id), "r"(n) : "memory"); }
__device__ __forceinline__ uint32_t pack2(float lo, float hi) { uint32_t r; asm("cvt.rn.bf16x2.f32 %0, %1, %2;" : "=r"(r) : "f"(hi), "f"(lo)); return r; }
__device__ __forceinline__ uint32_t pack2_tag(float lo, float hi, uint32_t T) {
  uint32_t u = ((__float_as_uint(lo) - T + 0x10000u) & 0xFFFE0000u) + T;
  return __byte_perm(u, pack2(0.f, hi), 0x7632); }
__device__ __forceinline__ void ldsm4(uint32_t (&r)[4], uint32_t a) {
  asm volatile("ldmatrix.sync.aligned.m8n8.x4.shared.b16 {%0,%1,%2,%3}, [%4];" : "=r"(r[0]), "=r"(r[1]), "=r"(r[2]), "=r"(r[3]) : "r"(a) : "memory"); }
__device__ __forceinline__ void ldsm4t(uint32_t (&r)[4], uint32_t a) {
  asm volatile("ldmatrix.sync.aligned.m8n8.x4.trans.shared.b16 {%0,%1,%2,%3}, [%4];" : "=r"(r[0]), "=r"(r[1]), "=r"(r[2]), "=r"(r[3]) : "r"(a) : "memory"); }
__device__ __forceinline__ void stsm4(uint32_t a, uint32_t r0, uint32_t r1, uint32_t r2, uint32_t r3) {
  asm volatile("stmatrix.sync.aligned.m8n8.x4.shared.b16 [%0], {%1,%2,%3,%4};" :: "r"(a), "r"(r0), "r"(r1), "r"(r2), "r"(r3) : "memory"); }
__device__ __forceinline__ void stsm4t(uint32_t a, uint32_t r0, uint32_t r1, uint32_t r2, uint32_t r3) {
  asm volatile("stmatrix.sync.aligned.m8n8.x4.trans.shared.b16 [%0], {%1,%2,%3,%4};" :: "r"(a), "r"(r0), "r"(r1), "r"(r2), "r"(r3) : "memory"); }
__device__ __forceinline__ void lds128(uint32_t (&r)[4], uint32_t a) {
  asm volatile("ld.shared.v4.u32 {%0,%1,%2,%3}, [%4];" : "=r"(r[0]), "=r"(r[1]), "=r"(r[2]), "=r"(r[3]) : "r"(a) : "memory"); }
__device__ __forceinline__ float4 lds128f(uint32_t a) { float4 r;
  asm volatile("ld.shared.v4.f32 {%0,%1,%2,%3}, [%4];" : "=f"(r.x), "=f"(r.y), "=f"(r.z), "=f"(r.w) : "r"(a) : "memory"); return r; }
__device__ __forceinline__ float2 lds64f(uint32_t a) { float2 r;
  asm volatile("ld.shared.v2.f32 {%0,%1}, [%2];" : "=f"(r.x), "=f"(r.y) : "r"(a) : "memory"); return r; }
__device__ __forceinline__ void sts128(uint32_t a, uint32_t r0, uint32_t r1, uint32_t r2, uint32_t r3) {
  asm volatile("st.shared.v4.u32 [%0], {%1,%2,%3,%4};" :: "r"(a), "r"(r0), "r"(r1), "r"(r2), "r"(r3) : "memory"); }
__device__ __forceinline__ void sts64f(uint32_t a, float x, float y) { asm volatile("st.shared.v2.f32 [%0], {%1,%2};" :: "r"(a), "f"(x), "f"(y) : "memory"); }
__device__ __forceinline__ void sts32f(uint32_t a, float x) { asm volatile("st.shared.f32 [%0], %1;" :: "r"(a), "f"(x) : "memory"); }
__device__ __forceinline__ void mma16816(float (&d)[4], uint32_t a0, uint32_t a1, uint32_t a2, uint32_t a3, uint32_t b0, uint32_t b1) {
  asm volatile("mma.sync.aligned.m16n8k16.row.col.f32.bf16.bf16.f32 {%0,%1,%2,%3}, {%4,%5,%6,%7}, {%8,%9}, {%0,%1,%2,%3};"
    : "+f"(d[0]), "+f"(d[1]), "+f"(d[2]), "+f"(d[3]) : "r"(a0), "r"(a1), "r"(a2), "r"(a3), "r"(b0), "r"(b1)); }
__device__ __forceinline__ void mma1688(float (&d)[4], uint32_t a0, uint32_t a1, uint32_t b0) {
  asm volatile("mma.sync.aligned.m16n8k8.row.col.f32.bf16.bf16.f32 {%0,%1,%2,%3}, {%4,%5}, {%6}, {%0,%1,%2,%3};"
    : "+f"(d[0]), "+f"(d[1]), "+f"(d[2]), "+f"(d[3]) : "r"(a0), "r"(a1), "r"(b0)); }
__device__ __forceinline__ void ldx128(uint32_t (&r)[4], const void* p) {
  asm volatile("{.reg .b128 t; .reg .b64 a, b; ld.relaxed.gpu.global.b128 t, [%4]; mov.b128 {a, b}, t; mov.b64 {%0,%1}, a; mov.b64 {%2,%3}, b;}"
    : "=r"(r[0]), "=r"(r[1]), "=r"(r[2]), "=r"(r[3]) : "l"(p) : "memory"); }
__device__ __forceinline__ void ldx2x64(uint32_t (&r)[4], const void* p) {
  asm volatile("{.reg .b64 a, b; ld.relaxed.gpu.global.v2.b64 {a, b}, [%4]; mov.b64 {%0,%1}, a; mov.b64 {%2,%3}, b;}"
    : "=r"(r[0]), "=r"(r[1]), "=r"(r[2]), "=r"(r[3]) : "l"(p) : "memory"); }
__device__ __forceinline__ void stx128(void* p, uint32_t r0, uint32_t r1, uint32_t r2, uint32_t r3) {
  asm volatile("{.reg .b128 t; .reg .b64 a, b; mov.b64 a, {%1,%2}; mov.b64 b, {%3,%4}; mov.b128 t, {a, b}; st.relaxed.gpu.global.b128 [%0], t;}"
    :: "l"(p), "r"(r0), "r"(r1), "r"(r2), "r"(r3) : "memory"); }
__device__ __forceinline__ void stx64(void* p, uint32_t r0, uint32_t r1) {
  asm volatile("{.reg .b64 a; mov.b64 a, {%1,%2}; st.relaxed.gpu.global.b64 [%0], a;}" :: "l"(p), "r"(r0), "r"(r1) : "memory"); }
__device__ __forceinline__ uint32_t uni(uint32_t x) { return __shfl_sync(0xffffffffu, x, 0); }
__device__ __forceinline__ uint32_t pin(uint32_t x) { return __shfl_xor_sync(0xffffffffu, x, 0); }
__device__ __forceinline__ float ex2(float x) { float r; asm("ex2.approx.ftz.f32 %0, %1;" : "=f"(r) : "f"(x)); return r; }
__device__ __forceinline__ void wg_fence() { asm volatile("wgmma.fence.sync.aligned;" ::: "memory"); }
__device__ __forceinline__ void wg_commit() { asm volatile("wgmma.commit_group.sync.aligned;" ::: "memory"); }
template <int N> __device__ __forceinline__ void wg_wait() { asm volatile("wgmma.wait_group.sync.aligned %0;" :: "n"(N) : "memory"); }

__device__ __forceinline__ void wgmma_ss_n256_tb1(float (&d)[128], uint64_t da, uint64_t db, int sc) {
  asm volatile("{.reg .pred p; setp.ne.b32 p, %130, 0;\n"
    "wgmma.mma_async.sync.aligned.m64n256k16.f32.bf16.bf16 {%0,%1,%2,%3,%4,%5,%6,%7,%8,%9,%10,%11,%12,%13,%14,%15,%16,%17,%18,%19,%20,%21,%22,%23,%24,%25,%26,%27,%28,%29,%30,%31,%32,%33,%34,%35,%36,%37,%38,%39,%40,%41,%42,%43,%44,%45,%46,%47,%48,%49,%50,%51,%52,%53,%54,%55,%56,%57,%58,%59,%60,%61,%62,%63,%64,%65,%66,%67,%68,%69,%70,%71,%72,%73,%74,%75,%76,%77,%78,%79,%80,%81,%82,%83,%84,%85,%86,%87,%88,%89,%90,%91,%92,%93,%94,%95,%96,%97,%98,%99,%100,%101,%102,%103,%104,%105,%106,%107,%108,%109,%110,%111,%112,%113,%114,%115,%116,%117,%118,%119,%120,%121,%122,%123,%124,%125,%126,%127}, %128, %129, p, 1, 1, 0, 1;}\n"
    : "+f"(d[0]),"+f"(d[1]),"+f"(d[2]),"+f"(d[3]),"+f"(d[4]),"+f"(d[5]),"+f"(d[6]),"+f"(d[7]),"+f"(d[8]),"+f"(d[9]),"+f"(d[10]),"+f"(d[11]),"+f"(d[12]),"+f"(d[13]),"+f"(d[14]),"+f"(d[15]),"+f"(d[16]),"+f"(d[17]),"+f"(d[18]),"+f"(d[19]),"+f"(d[20]),"+f"(d[21]),"+f"(d[22]),"+f"(d[23]),"+f"(d[24]),"+f"(d[25]),"+f"(d[26]),"+f"(d[27]),"+f"(d[28]),"+f"(d[29]),"+f"(d[30]),"+f"(d[31]),"+f"(d[32]),"+f"(d[33]),"+f"(d[34]),"+f"(d[35]),"+f"(d[36]),"+f"(d[37]),"+f"(d[38]),"+f"(d[39]),"+f"(d[40]),"+f"(d[41]),"+f"(d[42]),"+f"(d[43]),"+f"(d[44]),"+f"(d[45]),"+f"(d[46]),"+f"(d[47]),"+f"(d[48]),"+f"(d[49]),"+f"(d[50]),"+f"(d[51]),"+f"(d[52]),"+f"(d[53]),"+f"(d[54]),"+f"(d[55]),"+f"(d[56]),"+f"(d[57]),"+f"(d[58]),"+f"(d[59]),"+f"(d[60]),"+f"(d[61]),"+f"(d[62]),"+f"(d[63]),"+f"(d[64]),"+f"(d[65]),"+f"(d[66]),"+f"(d[67]),"+f"(d[68]),"+f"(d[69]),"+f"(d[70]),"+f"(d[71]),"+f"(d[72]),"+f"(d[73]),"+f"(d[74]),"+f"(d[75]),"+f"(d[76]),"+f"(d[77]),"+f"(d[78]),"+f"(d[79]),"+f"(d[80]),"+f"(d[81]),"+f"(d[82]),"+f"(d[83]),"+f"(d[84]),"+f"(d[85]),"+f"(d[86]),"+f"(d[87]),"+f"(d[88]),"+f"(d[89]),"+f"(d[90]),"+f"(d[91]),"+f"(d[92]),"+f"(d[93]),"+f"(d[94]),"+f"(d[95]),"+f"(d[96]),"+f"(d[97]),"+f"(d[98]),"+f"(d[99]),"+f"(d[100]),"+f"(d[101]),"+f"(d[102]),"+f"(d[103]),"+f"(d[104]),"+f"(d[105]),"+f"(d[106]),"+f"(d[107]),"+f"(d[108]),"+f"(d[109]),"+f"(d[110]),"+f"(d[111]),"+f"(d[112]),"+f"(d[113]),"+f"(d[114]),"+f"(d[115]),"+f"(d[116]),"+f"(d[117]),"+f"(d[118]),"+f"(d[119]),"+f"(d[120]),"+f"(d[121]),"+f"(d[122]),"+f"(d[123]),"+f"(d[124]),"+f"(d[125]),"+f"(d[126]),"+f"(d[127])
    : "l"(da), "l"(db), "r"(sc));
}

__device__ __forceinline__ void wgmma_ss_n128_tb1(float (&d)[64], uint64_t da, uint64_t db, int sc) {
  asm volatile("{.reg .pred p; setp.ne.b32 p, %66, 0;\n"
    "wgmma.mma_async.sync.aligned.m64n128k16.f32.bf16.bf16 {%0,%1,%2,%3,%4,%5,%6,%7,%8,%9,%10,%11,%12,%13,%14,%15,%16,%17,%18,%19,%20,%21,%22,%23,%24,%25,%26,%27,%28,%29,%30,%31,%32,%33,%34,%35,%36,%37,%38,%39,%40,%41,%42,%43,%44,%45,%46,%47,%48,%49,%50,%51,%52,%53,%54,%55,%56,%57,%58,%59,%60,%61,%62,%63}, %64, %65, p, 1, 1, 0, 1;}\n"
    : "+f"(d[0]),"+f"(d[1]),"+f"(d[2]),"+f"(d[3]),"+f"(d[4]),"+f"(d[5]),"+f"(d[6]),"+f"(d[7]),"+f"(d[8]),"+f"(d[9]),"+f"(d[10]),"+f"(d[11]),"+f"(d[12]),"+f"(d[13]),"+f"(d[14]),"+f"(d[15]),"+f"(d[16]),"+f"(d[17]),"+f"(d[18]),"+f"(d[19]),"+f"(d[20]),"+f"(d[21]),"+f"(d[22]),"+f"(d[23]),"+f"(d[24]),"+f"(d[25]),"+f"(d[26]),"+f"(d[27]),"+f"(d[28]),"+f"(d[29]),"+f"(d[30]),"+f"(d[31]),"+f"(d[32]),"+f"(d[33]),"+f"(d[34]),"+f"(d[35]),"+f"(d[36]),"+f"(d[37]),"+f"(d[38]),"+f"(d[39]),"+f"(d[40]),"+f"(d[41]),"+f"(d[42]),"+f"(d[43]),"+f"(d[44]),"+f"(d[45]),"+f"(d[46]),"+f"(d[47]),"+f"(d[48]),"+f"(d[49]),"+f"(d[50]),"+f"(d[51]),"+f"(d[52]),"+f"(d[53]),"+f"(d[54]),"+f"(d[55]),"+f"(d[56]),"+f"(d[57]),"+f"(d[58]),"+f"(d[59]),"+f"(d[60]),"+f"(d[61]),"+f"(d[62]),"+f"(d[63])
    : "l"(da), "l"(db), "r"(sc));
}

template <int BN> struct WG;
template <> struct WG<256> { static __device__ __forceinline__ void mma(float (&d)[128], uint64_t a, uint64_t b, int sc) { wgmma_ss_n256_tb1(d, a, b, sc); } };
template <> struct WG<128> { static __device__ __forceinline__ void mma(float (&d)[64], uint64_t a, uint64_t b, int sc) { wgmma_ss_n128_tb1(d, a, b, sc); } };

struct GemmMaps { CUtensorMap a, b[3], c; };
template <int BN, int STAGES>
__global__ void __cluster_dims__(2, 1, 1) __launch_bounds__(384, 1)
gemm_kernel(const __grid_constant__ GemmMaps maps, int tilesM, int tilesN, int kblocks, int nPerB, int clearX) {
  extern __shared__ __align__(1024) uint8_t smem_raw[];
  constexpr int STAGE_BYTES = 16384 + BN * 128;
  constexpr int NBOX = BN / 64;
  const uint32_t sbase = (smem_u32(smem_raw) + 1023) & ~1023u;
  const uint32_t sEpi = sbase + STAGES * STAGE_BYTES;
  const uint32_t sBar = sEpi + 32768;
  const int warp = threadIdx.x >> 5, lane = threadIdx.x & 31, wg = warp >> 2;
  uint32_t crank; asm("mov.u32 %0, %%cluster_ctarank;" : "=r"(crank));
  if (threadIdx.x == 0) {
    for (int i = 0; i < STAGES; i++) { mbar_init(sBar + 8 * i, 1); mbar_init(sBar + 8 * (STAGES + i), 4); }
    asm volatile("fence.mbarrier_init.release.cluster;" ::: "memory");
  }
  if (clearX) {
    uint4* p = reinterpret_cast<uint4*>(&g_x);
    for (int i = blockIdx.x * 384 + threadIdx.x; i < (int)(sizeof(Xchg) / 16); i += gridDim.x * 384) p[i] = make_uint4(0, 0, 0, 0);
  }
  asm volatile("barrier.cluster.arrive.release.aligned; barrier.cluster.wait.acquire.aligned;" ::: "memory");
  const int npairs = (tilesM >> 1) * tilesN, pair0 = blockIdx.x >> 1, pstep = gridDim.x >> 1;
  if (wg == 2) {
    asm volatile("setmaxnreg.dec.sync.aligned.u32 40;");
    if (warp == 8 && lane == 0) {
      int st = 0, ph = 1;
      for (int p = pair0; p < npairs; p += pstep) {
        const int tm = (p % (tilesM >> 1)) * 2 + crank, tn = p / (tilesM >> 1);
        const CUtensorMap* mb = &maps.b[tn / nPerB];
        const int n0 = (tn % nPerB) * BN;
        for (int kb = 0; kb < kblocks; kb++) {
          mbar_wait(sBar + 8 * (STAGES + st), ph);
          const uint32_t a = sbase + st * STAGE_BYTES, full = sBar + 8 * st;
          mbar_expect_tx(full, STAGE_BYTES);
          tma2d(a, &maps.a, kb * 64, tm * 128, full);
#pragma unroll
          for (int i = 0; i < NBOX / 2; i++) {
            const int bx = crank * (NBOX / 2) + i;
            tma2d_mc(a + 16384 + bx * 8192, mb, n0 + bx * 64, kb * 64, full, (uint16_t)3);
          }
          if (++st == STAGES) { st = 0; ph ^= 1; }
        }
      }
      for (int i = 0; i < STAGES; i++) { mbar_wait(sBar + 8 * (STAGES + st), ph); if (++st == STAGES) { st = 0; ph ^= 1; } }
    }
  } else {
    asm volatile("setmaxnreg.inc.sync.aligned.u32 232;");
    int st = 0, ph = 0;
    float acc[BN / 2];
    const uint64_t descA0 = (uint64_t)(((sbase + wg * 8192) & 0x3FFFF) >> 4) | (1ull << 16) | (64ull << 32) | (1ull << 62);
    const uint64_t descB0 = (uint64_t)(((sbase + 16384) & 0x3FFFF) >> 4) | (512ull << 16) | (64ull << 32) | (1ull << 62);
    const uint32_t epi = sEpi + wg * 16384;
    for (int p = pair0; p < npairs; p += pstep) {
      const int tm = (p % (tilesM >> 1)) * 2 + crank, tn = p / (tilesM >> 1);
      int prev = -1;
      for (int kb = 0; kb < kblocks; kb++) {
        mbar_wait(sBar + 8 * st, ph);
        wg_fence();
        const uint64_t so = (uint64_t)(st * (STAGE_BYTES >> 4));
#pragma unroll
        for (int k = 0; k < 4; k++) WG<BN>::mma(acc, descA0 + so + k * 2, descB0 + so + k * 128, kb | k);
        wg_commit();
        if (prev >= 0) {
          wg_wait<1>();
          if ((threadIdx.x & 127) < 2) mbar_arrive_cluster(sBar + 8 * (STAGES + prev), threadIdx.x & 1);
        }
        prev = st;
        if (++st == STAGES) { st = 0; ph ^= 1; }
      }
      wg_wait<0>();
      if ((threadIdx.x & 127) < 2) mbar_arrive_cluster(sBar + 8 * (STAGES + prev), threadIdx.x & 1);
#pragma unroll
      for (int r = 0; r < BN / 128; r++) {
        if ((threadIdx.x & 127) == 0) asm volatile("cp.async.bulk.wait_group.read 0;" ::: "memory");
        bar_sync(1 + wg, 128);
        const int row = (warp & 3) * 16 + (lane & 15);
#pragma unroll
        for (int i = 0; i < 8; i++) {
          const int c = 2 * (i & 3) + (lane >> 4);
          const float* q = &acc[r * 64 + i * 8];
          stsm4(epi + (i >> 2) * 8192 + row * 128 + ((c ^ (row & 7)) << 4), pack2(q[0], q[1]), pack2(q[2], q[3]), pack2(q[4], q[5]), pack2(q[6], q[7]));
        }
        fence_async();
        bar_sync(1 + wg, 128);
        if ((threadIdx.x & 127) == 0) {
          tma2d_store(&maps.c, epi, tn * BN + r * 128, tm * 128 + wg * 64);
          tma2d_store(&maps.c, epi + 8192, tn * BN + r * 128 + 64, tm * 128 + wg * 64);
          asm volatile("cp.async.bulk.commit_group;" ::: "memory");
        }
      }
    }
    if ((threadIdx.x & 127) == 0) asm volatile("cp.async.bulk.wait_group 0;" ::: "memory");
  }
}

struct Dft { uint32_t m[2][2][2][4]; };
template <bool P4> __device__ __forceinline__ int fidx(int tile, int x) { return P4 ? 4 * (x >> 1) + 2 * (tile & 1) + (x & 1) + 16 * (tile >> 1) : x + 8 * tile; }
__device__ __forceinline__ float2 cis(int k, int n) {
  k &= n - 1; if (2 * k > n) k -= n;
  const float a = (float)k * (6.283185307179586f / (float)n);
  return make_float2(__cosf(a), __sinf(a));
}
template <bool OUT4> __device__ __forceinline__ void make_dft(Dft& D, int g, int t) {
#pragma unroll
  for (int q = 0; q < 16; q++) {
    const int b = q >> 3, u = (q >> 2) & 1, r = (q >> 1) & 1, v = q & 1;
    const float2 w = cis(fidx<OUT4>(v, g) * fidx<false>(2 * u + r, 2 * t + b), 32);
    D.m[b][u][0][q & 3] = pack2(w.x, w.y); D.m[b][u][1][q & 3] = pack2(-w.y, w.x);
  }
}
__device__ __forceinline__ void mma_dc(float (&d)[4], uint32_t a0, uint32_t a1, uint32_t a2, uint32_t a3, uint32_t b0, uint32_t b1, const float (&c)[4]) {
  asm("mma.sync.aligned.m16n8k16.row.col.f32.bf16.bf16.f32 {%0,%1,%2,%3}, {%4,%5,%6,%7}, {%8,%9}, {%10,%11,%12,%13};"
    : "=f"(d[0]), "=f"(d[1]), "=f"(d[2]), "=f"(d[3]) : "r"(a0), "r"(a1), "r"(a2), "r"(a3), "r"(b0), "r"(b1), "f"(c[0]), "f"(c[1]), "f"(c[2]), "f"(c[3])); }
__device__ __forceinline__ void dft_b(const Dft& D, const uint32_t (&x)[2][4], float (&o)[2][8]) {
#pragma unroll
  for (int ri = 0; ri < 2; ri++) {
    float z[4] = {0.f, 0.f, 0.f, 0.f}, e[4], p[4];
    mma_dc(e, D.m[0][0][ri][0], D.m[0][0][ri][1], D.m[0][0][ri][2], D.m[0][0][ri][3], x[0][0], x[0][1], z);
    mma_dc(e, D.m[0][1][ri][0], D.m[0][1][ri][1], D.m[0][1][ri][2], D.m[0][1][ri][3], x[0][2], x[0][3], e);
    mma_dc(p, D.m[1][0][ri][0], D.m[1][0][ri][1], D.m[1][0][ri][2], D.m[1][0][ri][3], x[1][0], x[1][1], e);
    mma_dc(p, D.m[1][1][ri][0], D.m[1][1][ri][1], D.m[1][1][ri][2], D.m[1][1][ri][3], x[1][2], x[1][3], p);
#pragma unroll
    for (int q = 0; q < 4; q++) { o[ri][q] = p[q]; o[ri][4 + q] = fmaf(2.f, e[q], -p[q]); }
  }
}
__device__ __forceinline__ void dft_a(const uint32_t (&m)[2][2][4], const uint32_t (&x0)[2][4], const uint32_t (&x1)[2][4], float (&o)[2][8]) {
#pragma unroll
  for (int ri = 0; ri < 2; ri++) {
    float z[4] = {0.f, 0.f, 0.f, 0.f}, e[4], p[4];
    mma_dc(e, x0[0][0], x1[0][0], x0[0][1], x1[0][1], m[0][ri][0], m[0][ri][1], z);
    mma_dc(e, x0[0][2], x1[0][2], x0[0][3], x1[0][3], m[0][ri][2], m[0][ri][3], e);
    mma_dc(p, x0[1][0], x1[1][0], x0[1][1], x1[1][1], m[1][ri][0], m[1][ri][1], e);
    mma_dc(p, x0[1][2], x1[1][2], x0[1][3], x1[1][3], m[1][ri][2], m[1][ri][3], p);
#pragma unroll
    for (int q = 0; q < 4; q++) { o[ri][q] = p[q]; o[ri][4 + q] = fmaf(2.f, e[q], -p[q]); }
  }
}
__device__ __forceinline__ uint32_t twid(float re, float im, float c, float s) { return pack2(fmaf(re, c, im * s), fmaf(im, c, -re * s)); }
__device__ __forceinline__ void cpa16(uint32_t d, const void* s) { asm volatile("cp.async.cg.shared.global [%0], [%1], 16;" :: "r"(d), "l"(s) : "memory"); }
__device__ __forceinline__ void sts32(uint32_t a, uint32_t x) { asm volatile("st.shared.u32 [%0], %1;" :: "r"(a), "r"(x) : "memory"); }
__device__ __forceinline__ void cpa_commit() { asm volatile("cp.async.commit_group;" ::: "memory"); }
template <int N> __device__ __forceinline__ void cpa_wait() { asm volatile("cp.async.wait_group %0;" :: "n"(N) : "memory"); }
__device__ __forceinline__ uint32_t lds32(uint32_t a) { uint32_t r; asm volatile("ld.shared.u32 %0, [%1];" : "=r"(r) : "r"(a) : "memory"); return r; }
constexpr int F_TP = 4112, F_TSZ = 8 * F_TP;

__device__ __forceinline__ void fft_wprep(const bf16* __restrict__ wr, const bf16* __restrict__ wi, int cta, int ncta) {
  const int tid = threadIdx.x;
#pragma unroll 2
  for (int it = cta; it < 256; it += ncta) {
    const int g = (it >> 1) & 7, c = (it >> 4) & 3, i = it >> 6, t = 2 * (it & 1) + (tid & 1);
    const int k0 = g + 8 * i + 32 * (8 * c + 2 * t), l0 = (tid & ~1) + (g & 1);
    uint32_t a[2][4], b[2][4];
#pragma unroll
    for (int q = 0; q < 8; q++) {
      const int o = (k0 + 32 * ((q >> 1) & 1) + 1024 * (q & 1)) * 513 + l0 + 256 * (q >> 2);
      a[q >> 2][q & 3] = __ldg(reinterpret_cast<const uint32_t*>(wr + o));
      b[q >> 2][q & 3] = __ldg(reinterpret_cast<const uint32_t*>(wi + o));
    }
    uint4* dst = g_wt + l0 * 512 + it * 2 + (tid & 1);
#pragma unroll
    for (int q = 0; q < 4; q++) {
      const int hf = q >> 1, l = l0 + 256 * hf + (q & 1);
      const uint32_t sel = (q & 1) ? 0x7632 : 0x5410;
      if (l & 511) dst[(256 * hf + (q & 1)) * 512] = make_uint4(__byte_perm(a[hf][0], b[hf][0], sel), __byte_perm(a[hf][1], b[hf][1], sel),
                                                              __byte_perm(a[hf][2], b[hf][2], sel), __byte_perm(a[hf][3], b[hf][3], sel));
    }
  }
  for (int e = cta * 256 + tid; e < 4096; e += ncta * 256) {
    const int l = (e >> 11) * 512, k = e & 2047, kn = (2048 - k) & 2047, k2 = (k >> 5) & 31;
    const float re = 0.5f * (__bfloat162float(wr[k * 513 + l]) + __bfloat162float(wr[kn * 513 + l]));
    const float im = 0.5f * (__bfloat162float(wi[k * 513 + l]) - __bfloat162float(wi[kn * 513 + l]));
    reinterpret_cast<uint32_t*>(g_wt)[(64 * ((k >> 3) & 3) + 16 * (k2 >> 3) + 2 * (k & 7) + ((k2 >> 2) & 1)) * 8 + l * 2048 + 2 * (k2 & 3) + (k >> 10)] = pack2(re, im);
  }
}

__device__ __forceinline__ void fft_rows_fwd(const bf16* __restrict__ x, uint32_t sb, int cta, int ncta) {
  const int warp = threadIdx.x >> 5, lane = threadIdx.x & 31, g = lane >> 2, t = lane & 3;
  const uint32_t in = sb + warp * 8192, tb = sb + 65536;
  const uint32_t f0 = pin(in + (lane >> 3) * 256 + (((lane & 7) ^ (2 * (lane >> 3))) << 4));
  const uint32_t xo = pin((256 * (warp & 3) + 64 * (warp >> 2)) * 2048 + lane * 8);
  auto fetch = [&](int it, int buf) {
    const bf16* src = x + (xo + (128 * (it & 1) + 32 * ((it >> 4) & 1) + 8 * (it >> 5) + ((it >> 1) & 7)) * 2048);
#pragma unroll
    for (int q = 0; q < 8; q++) cpa16(((f0 + buf * 4096) ^ ((q >> 2) * 144)) + (q & 3) * 1024, src + q * 256);
    cpa_commit();
  };
  fetch(cta, 0);
  Dft D; make_dft<true>(D, g, t);
  float2 tw[4][8];
#pragma unroll
  for (int q = 0; q < 32; q++) tw[q >> 3][q & 7] = cis(fidx<true>((q >> 1) & 3, g) * fidx<false>(q >> 3, 2 * t + (q & 1)), 1024);
  const uint32_t la = pin(in + lane * 128 + ((lane & 7) << 4));
  const uint32_t wa = pin(tb + warp * F_TP + fidx<true>(0, g) * 128 + t * 16), wz = pin((g & 1) ? -64 : 64);
  const uint32_t ra = pin(tb + (lane & 1) * 4 * F_TP + ((lane >> 1) + 16 * (warp ^ ((warp >> 1) & 1))) * 4);
  uint4* dst = g_y + (threadIdx.x >> 1) * 256 + (lane & 1);
  int buf = 0;
  auto drain = [&](int it, int q) {
    const uint32_t r = ra + (buf ^ 1) * F_TSZ + q * 512;
    const uint4 v = make_uint4(lds32(r), lds32(r + F_TP), lds32(r + 2 * F_TP), lds32(r + 3 * F_TP));
    if (it >= 0) dst[it * 2 + q * 32768] = v;
  };
  int it = cta;
#pragma unroll 1
  for (; it < 128; it += ncta, buf ^= 1) {
    cpa_wait<0>(); __syncthreads();
    uint32_t a[4][2][4], y[4][2][4];
#pragma unroll
    for (int q = 0; q < 8; q++) ldsm4t(a[q & 3][q >> 2], (la + buf * 4096) ^ (q << 4));
    if (it + ncta < 128) fetch(it + ncta, buf ^ 1);
    float o[2][8];
#pragma unroll
    for (int i = 0; i < 4; i++) {
      dft_b(D, a[i], o);
      drain(it - ncta, i);
#pragma unroll
      for (int q = 0; q < 8; q++) y[q >> 1][q & 1][i] = twid(o[0][q], o[1][q], tw[i][q].x, tw[i][q].y);
    }
    const uint32_t w0 = wa + buf * F_TSZ + ((g & 1) << 6);
#pragma unroll
    for (int z = 0; z < 2; z++) {
      float o2[2][8];
      dft_b(D, y[2 * z], o); drain(it - ncta, 4 + 2 * z); dft_b(D, y[2 * z + 1], o2); drain(it - ncta, 5 + 2 * z);
#pragma unroll
      for (int i = 0; i < 4; i++) {
        const float sg = i < 2 ? 1.f : -1.f;
        sts128(w0 + z * wz + fidx<true>(i, 0) * 128, pack2(o[0][2 * i], sg * o[1][2 * i]), pack2(o[0][2 * i + 1], sg * o[1][2 * i + 1]),
               pack2(o2[0][2 * i], sg * o2[1][2 * i]), pack2(o2[0][2 * i + 1], sg * o2[1][2 * i + 1]));
      }
    }
  }
  __syncthreads();
#pragma unroll
  for (int q = 0; q < 8; q++) drain(it - ncta, q);
}

__device__ __forceinline__ void fft_cols(uint32_t sb, int cta, int ncta) {
  const int warp = threadIdx.x >> 5, lane = threadIdx.x & 31, g = lane >> 2, t = lane & 3;
  const uint32_t in = sb + warp * 16384 + lane * 16, tab = sb + 131072 + lane * 16;
  auto fetch_y = [&](int l) {
#pragma unroll
    for (int q = 0; q < 16; q++) cpa16(in + q * 512, g_y + (q < 8 ? l : (1024 - l) & 1023) * 256 + (q & 7) * 32 + lane);
  };
  auto fetch_w = [&](int l) {
#pragma unroll
    for (int q = 0; q < 16; q++) cpa16(in + 8192 + q * 512, g_wt + l * 512 + q * 32 + lane);
  };
  const int l0 = cta * 8 + warp, dl = ncta * 8;
  if (l0 <= 512) fetch_y(l0);
  cpa_commit();
  if (l0 <= 512) fetch_w(l0);
  cpa_commit();
  Dft D; make_dft<false>(D, g, t);
#pragma unroll
  for (int q = 2 * warp; q < 2 * warp + 2; q++) {
    const int r = fidx<false>(q & 3, g), c = fidx<false>(q >> 2, 2 * t);
    const float2 w0 = cis(r * c, 1024), w1 = cis(r * c + r, 1024), p0 = cis(r + 32 * c, 2048), p1 = cis(r + 32 * c + 32, 2048);
    sts128(tab + q * 512, __float_as_uint(w0.x), __float_as_uint(w0.y), __float_as_uint(w1.x), __float_as_uint(w1.y));
    sts128(tab + 8192 + q * 512, __float_as_uint(p0.x), __float_as_uint(p0.y), __float_as_uint(p1.x), __float_as_uint(p1.y));
  }
  if (warp == 0) {
#pragma unroll
    for (int q = 0; q < 8; q++) {
      const int v = q >> 2, b = (q >> 1) & 1, ri = q & 1;
      sts128(tab + 16384 + q * 512, D.m[b][0][ri][v], D.m[b][0][ri][v + 2], D.m[b][1][ri][v], D.m[b][1][ri][v + 2]);
    }
  }
  __syncthreads();
#pragma unroll 1
  for (int l = l0; l <= 512; l += dl) {
    uint32_t a[2][4][2][4], y[2][4][2][4];
    float o[2][2][8];
    cpa_wait<1>();
#pragma unroll
    for (int q = 0; q < 16; q++) lds128(a[q >> 3][(q >> 1) & 3][q & 1], in + q * 512);
    if (!(l & 511)) {
      const uint32_t m0 = l ? 0x80000000u : 0u;
#pragma unroll
      for (int q = 0; q < 32; q++) { a[0][q >> 3][(q >> 2) & 1][q & 3] ^= m0; a[1][q >> 3][(q >> 2) & 1][q & 3] ^= m0 ^ 0x80000000u; }
    }
    auto first = [&]() {
#pragma unroll
      for (int i = 0; i < 4; i++) {
        dft_b(D, a[0][i], o[0]); dft_b(D, a[1][i], o[1]);
#pragma unroll
        for (int r = 0; r < 4; r++) {
          const float4 w = lds128f(tab + (4 * i + r) * 512);
#pragma unroll
          for (int s = 0; s < 2; s++) {
            y[s][r][0][i] = twid(o[s][0][2 * r], o[s][1][2 * r], w.x, w.y);
            y[s][r][1][i] = twid(o[s][0][2 * r + 1], o[s][1][2 * r + 1], w.z, w.w);
          }
        }
      }
    };
    first();
    if (l + dl <= 512) fetch_y(l + dl);
    cpa_commit();
    cpa_wait<1>();
#pragma unroll
    for (int zv = 0; zv < 4; zv++) {
      const int z = zv >> 1, v = zv & 1;
      uint32_t m[2][2][4];
#pragma unroll
      for (int q = 0; q < 4; q++) lds128(m[q >> 1][q & 1], tab + 16384 + (4 * v + q) * 512);
      dft_a(m, y[0][2 * z], y[0][2 * z + 1], o[0]); dft_a(m, y[1][2 * z], y[1][2 * z + 1], o[1]);
#pragma unroll
      for (int q = 0; q < 4; q++) {
        const int i = 2 * z + (q & 1), c = v + (q & 2);
        uint32_t w[4]; lds128(w, in + 8192 + (4 * i + c) * 512);
        const float4 ph = lds128f(tab + 8192 + (4 * c + i) * 512);
#pragma unroll
        for (int b = 0; b < 2; b++) {
          const float cs = b ? ph.z : ph.x, sn = b ? ph.w : ph.y;
          const float r1 = __uint_as_float(w[2 * b] << 16), i1 = __uint_as_float(w[2 * b] & 0xFFFF0000u);
          const float r2 = __uint_as_float(w[2 * b + 1] << 16), i2 = __uint_as_float(w[2 * b + 1] & 0xFFFF0000u);
          const float Sr = r1 + r2, Si = i1 + i2, Dr = r1 - r2, Di = i1 - i2;
          const float ar = fmaf(-Dr, sn, Sr), ai = fmaf(-Di, sn, Si), dr = fmaf(Dr, sn, Sr), di = fmaf(Di, sn, Si), br = -Di * cs, bi = Dr * cs;
          const float Ar = o[0][0][2 * q + b], Ai = o[0][1][2 * q + b], Br = o[1][0][2 * q + b], Bi = o[1][1][2 * q + b];
          a[0][i][b][c] = pack2(fmaf(ar, Ai, fmaf(ai, Ar, fmaf(br, Bi, bi * Br))), fmaf(ar, Ar, fmaf(-ai, Ai, fmaf(br, Br, -bi * Bi))));
          a[1][i][b][c] = pack2(fmaf(dr, Bi, fmaf(di, Br, fmaf(-br, Ai, -bi * Ar))), fmaf(dr, Br, fmaf(-di, Bi, fmaf(-br, Ar, bi * Ai))));
        }
      }
    }
    if (l + dl <= 512) fetch_w(l + dl);
    cpa_commit();
    first();
#pragma unroll
    for (int s = 0; s < 2; s++) {
      uint4* dst = g_y + (s ? (1024 - l) & 1023 : l) * 256 + lane;
      const float sg = s ? -1.f : 1.f;
#pragma unroll
      for (int i = 0; i < 4; i++) {
        dft_b(D, y[s][i], o[0]);
#pragma unroll
        for (int b = 0; b < 2; b++)
          dst[(2 * i + b) * 32] = make_uint4(pack2(sg * o[0][0][b], o[0][1][b]), pack2(sg * o[0][0][2 + b], o[0][1][2 + b]),
                                             pack2(sg * o[0][0][4 + b], o[0][1][4 + b]), pack2(sg * o[0][0][6 + b], o[0][1][6 + b]));
      }
    }
  }
}

__device__ __forceinline__ void fft_rows_inv(const CUtensorMap* om, uint32_t sb, int cta, int ncta) {
  const int warp = threadIdx.x >> 5, lane = threadIdx.x & 31, g = lane >> 2, t = lane & 3, wg = warp >> 2, w4 = warp & 3;
  const uint32_t tb = sb + 32768 + wg * 2 * F_TSZ;
  const uint4* src = g_y + pin((256 * ((lane >> 1) & 3) + 64 * (lane >> 3) + 8 * w4) * 256 + (lane & 1));
  const uint32_t wa = pin(tb + (lane & 1) * 4 * F_TP + w4 * 1024 + (lane >> 1) * 4);
  uint4 pf[8];
  auto fetch = [&](int it, int hf) {
#pragma unroll
    for (int q = 0; q < 8; q++) pf[q] = __ldcg(src + (it * 2 + hf * 8192) + q * 256);
  };
  auto put = [&](uint32_t off) {
#pragma unroll
    for (int q = 0; q < 8; q++) {
      sts32(wa + off + q * 64, pf[q].x); sts32(wa + off + q * 64 + F_TP, pf[q].y);
      sts32(wa + off + q * 64 + 2 * F_TP, pf[q].z); sts32(wa + off + q * 64 + 3 * F_TP, pf[q].w);
    }
  };
  const int it0 = 2 * cta + wg;
  if (it0 >= 128) return;
  fetch(it0, 0); put(0); fetch(it0, 1); put(512);
  Dft D; make_dft<false>(D, g, t);
  float2 tw[4][8];
#pragma unroll
  for (int q = 0; q < 32; q++) {
    tw[q >> 3][q & 7] = cis(fidx<false>((q >> 1) & 3, g) * fidx<false>(q >> 3, 2 * t + (q & 1)), 1024);
    tw[q >> 3][q & 7].x *= 1.f / 2097152.f; tw[q >> 3][q & 7].y *= 1.f / 2097152.f;
  }
  const uint32_t la = pin(tb + w4 * F_TP + lane * 16), ob = uni(sb + warp * 4096);
  const uint32_t oa = pin(ob + (lane >> 1) * 128 + (((4 * (lane & 1)) ^ ((lane >> 1) & 7)) << 4));
#pragma unroll 1
  for (int n = 0;; n++) {
    const int it = it0 + (n >> 1) * 2 * ncta, hf = n & 1, buf = (n >> 1) & 1;
    if (it >= 128) break;
    if (!hf) bar_sync(1 + wg, 128);
    uint32_t a[4][2][4], y[4][2][4];
#pragma unroll
    for (int q = 0; q < 8; q++) lds128(a[q >> 1][q & 1], la + buf * F_TSZ + hf * 4 * F_TP + q * 512);
    fetch(min(it + 2 * ncta, 127), hf);
    float o[2][8];
#pragma unroll
    for (int i = 0; i < 4; i++) {
      dft_b(D, a[i], o);
#pragma unroll
      for (int q = 0; q < 8; q++) y[q >> 1][q & 1][i] = twid(o[0][q], o[1][q], tw[i][q].x, tw[i][q].y);
    }
    if (lane == 0) asm volatile("cp.async.bulk.wait_group.read 0;" ::: "memory");
    __syncwarp();
#pragma unroll
    for (int c = 0; c < 4; c++) {
      dft_b(D, y[c], o);
#pragma unroll
      for (int ri = 0; ri < 2; ri++)
        stsm4((oa ^ (c << 4)) + (1 - ri) * 2048, pack2(o[ri][0], o[ri][1]), pack2(o[ri][2], o[ri][3]), pack2(o[ri][4], o[ri][5]), pack2(o[ri][6], o[ri][7]));
    }
    fence_async();
    __syncwarp();
    if (lane == 0) {
      const int m = 256 * w4 + 32 * ((it >> 1) & 7) + 8 * (it >> 5) + 4 * (it & 1) + 2 * hf + ((it >> 4) & 1);
      asm volatile("cp.async.bulk.tensor.3d.global.shared::cta.bulk_group [%0, {0, 0, %2}], [%1];" :: "l"(om), "r"(ob), "r"(2 * m) : "memory");
      asm volatile("cp.async.bulk.commit_group;" ::: "memory");
    }
    put((buf ^ 1) * F_TSZ + hf * 512);
  }
  if (lane == 0) asm volatile("cp.async.bulk.wait_group 0;" ::: "memory");
}
constexpr int F_SMEM = 65536 + 2 * F_TSZ + 1024;
__global__ void __launch_bounds__(256, 1) fft_pre_kernel(const bf16* __restrict__ x, const bf16* __restrict__ wr, const bf16* __restrict__ wi) {
  extern __shared__ __align__(1024) uint8_t smem_raw[];
  const uint32_t sb = (smem_u32(smem_raw) + 1023) & ~1023u;
  fft_wprep(wr, wi, blockIdx.x, gridDim.x);
  fft_rows_fwd(x, sb, blockIdx.x, gridDim.x);
}
__device__ __forceinline__ void grid_arrive(unsigned* ctr) {
  __syncthreads();
  if (threadIdx.x == 0) { __threadfence(); atomicAdd(ctr, 1u); }
}
__device__ __forceinline__ void grid_wait(unsigned* ctr, unsigned n) {
  if (threadIdx.x == 0) {
    int it = 0;
    while (*reinterpret_cast<volatile unsigned*>(ctr) < n) { __nanosleep(200); if (++it > SPIN_LIMIT) { g_err = 3; break; } }
    __threadfence();
  }
  __syncthreads();
}

struct RecMaps { CUtensorMap wq, wk, wv, wo, x, k, q, v, fo; };
#define NSW 16
#define EXP 0
#define PD1 4
#define NE4 0
#define NE6 2
#define NA4 9
#define NA6 16
#define NB1 24
#define OXPOS 28
#define KVPOS 1
#define NK0 4
#define FLPOS 24
#define NPRE 0
#define UNP 8
#define XCD 1
#define XB 2
#define XA 4
constexpr int R_WO = 0, R_X = 65536, R_MEM = 131072, R_WC = 147456, R_RED = R_WC + NSW * 2048, R_O = R_RED + 2048, R_S = R_O + 2048, R_STAGE = R_S + 3072,
              R_K = R_STAGE + 8192, R_Q = R_K + 8192, R_V = R_Q + 2048, R_BAR = R_V + 16384, R_TS = R_BAR + 128,
              R_TOTAL = R_TS;
#define TS(i)
#define LOG(i, v)
constexpr int B_KV = R_BAR, B_W = R_BAR + 8, B_X = R_BAR + 16, B_C = R_BAR + 32, B_B = R_BAR + 40, B_DUE = R_BAR + 48;
#define DLY_A 150
#define DLY_V 150
#define DLY_C 100
#define DLY_L 90
#define NS_B 1280
#define NS_C 1920
#define NS_P 3008
#define NS_V 160
#define NS_M 64
#define NS_PEN 576
__device__ __forceinline__ float rcp(float x) { float r; asm("rcp.approx.ftz.f32 %0, %1;" : "=f"(r) : "f"(x)); return r; }
__device__ __forceinline__ uint32_t movm(uint32_t a) { uint32_t d; asm volatile("movmatrix.sync.aligned.m8n8.trans.b16 %0, %1;" : "=r"(d) : "r"(a)); return d; }
__device__ __forceinline__ uint32_t hadd2(uint32_t a, uint32_t b) { uint32_t d; asm("add.rn.bf16x2 %0, %1, %2;" : "=r"(d) : "r"(a), "r"(b)); return d; }
__device__ __forceinline__ void mma_a(float (&d)[4], const uint32_t (&a)[4], uint32_t b0, uint32_t b1) { mma16816(d, a[0], a[1], a[2], a[3], b0, b1); }
__device__ __forceinline__ bool elect() {
  uint32_t p; asm volatile("{.reg .pred p; elect.sync _|p, 0xffffffff; selp.u32 %0, 1, 0, p;}" : "=r"(p)); return p; }
__device__ __forceinline__ void tma3d(uint32_t dst, const CUtensorMap* m, int c1, int c2, uint32_t bar) {
  asm volatile("cp.async.bulk.tensor.3d.shared::cluster.global.mbarrier::complete_tx::bytes [%0], [%1, {0, %3, %4}], [%2];"
    :: "r"(dst), "l"(m), "r"(bar), "r"(c1), "r"(c2) : "memory"); }
__device__ __forceinline__ void tma4d(uint32_t dst, const CUtensorMap* m, int c1, int c2, uint32_t bar) {
  asm volatile("cp.async.bulk.tensor.4d.shared::cluster.global.mbarrier::complete_tx::bytes [%0], [%1, {0, %3, %4, 0}], [%2];"
    :: "r"(dst), "l"(m), "r"(bar), "r"(c1), "r"(c2) : "memory"); }
template <int OFF, int ACC>
__device__ __forceinline__ void wg_rs32(float (&d)[16], const uint32_t (&a)[4], uint32_t db) {
  if (ACC)
    asm volatile("{.reg .b64 db; .reg .b32 lo; add.u32 lo, %20, %21; mov.b64 db, {lo, 0x40000040};\n"
      "wgmma.mma_async.sync.aligned.m64n32k16.f32.bf16.bf16 {%0,%1,%2,%3,%4,%5,%6,%7,%8,%9,%10,%11,%12,%13,%14,%15}, {%16,%17,%18,%19}, db, 1, 1, 1, 0;}"
      : "+f"(d[0]), "+f"(d[1]), "+f"(d[2]), "+f"(d[3]), "+f"(d[4]), "+f"(d[5]), "+f"(d[6]), "+f"(d[7]), "+f"(d[8]), "+f"(d[9]), "+f"(d[10]), "+f"(d[11]), "+f"(d[12]), "+f"(d[13]), "+f"(d[14]), "+f"(d[15])
      : "r"(a[0]), "r"(a[1]), "r"(a[2]), "r"(a[3]), "r"(db), "n"(OFF));
  else
    asm volatile("{.reg .b64 db; .reg .b32 lo; add.u32 lo, %20, %21; mov.b64 db, {lo, 0x40000040};\n"
      "wgmma.mma_async.sync.aligned.m64n32k16.f32.bf16.bf16 {%0,%1,%2,%3,%4,%5,%6,%7,%8,%9,%10,%11,%12,%13,%14,%15}, {%16,%17,%18,%19}, db, 0, 1, 1, 0;}"
      : "=f"(d[0]), "=f"(d[1]), "=f"(d[2]), "=f"(d[3]), "=f"(d[4]), "=f"(d[5]), "=f"(d[6]), "=f"(d[7]), "=f"(d[8]), "=f"(d[9]), "=f"(d[10]), "=f"(d[11]), "=f"(d[12]), "=f"(d[13]), "=f"(d[14]), "=f"(d[15])
      : "r"(a[0]), "r"(a[1]), "r"(a[2]), "r"(a[3]), "r"(db), "n"(OFF));
}
template <int I> using IC = std::integral_constant<int, I>;
template <int I, int N, class F> __device__ __forceinline__ void sfor(F&& f) {
  if constexpr (I < N) { f(std::integral_constant<int, I>{}); sfor<I + 1, N>(f); }
}
__device__ __forceinline__ void keep(float (&d)[16]) {
  asm volatile("" : "+f"(d[0]), "+f"(d[1]), "+f"(d[2]), "+f"(d[3]), "+f"(d[4]), "+f"(d[5]), "+f"(d[6]), "+f"(d[7]),
      "+f"(d[8]), "+f"(d[9]), "+f"(d[10]), "+f"(d[11]), "+f"(d[12]), "+f"(d[13]), "+f"(d[14]), "+f"(d[15]) :: "memory");
}

template <int N, int S2 = 1024> __device__ __forceinline__ void ldx(uint32_t (&v)[N][4], const uint8_t* p) {
#pragma unroll
  for (int i = 0; i < 2 * N; i++)
    asm volatile("ld.relaxed.gpu.global.v2.b32 {%0,%1}, [%2];" : "=r"(v[i >> 1][2 * (i & 1)]), "=r"(v[i >> 1][2 * (i & 1) + 1]) : "l"(p + (i & 3) * 256 + (i >> 2) * S2) : "memory");
}
__device__ __forceinline__ uint32_t dif2(uint32_t a, uint32_t b, uint32_t tag) { uint32_t r; asm("lop3.b32 %0, %1, %2, %3, 0x7e;" : "=r"(r) : "r"(a), "r"(b), "r"(tag)); return r; }
__device__ __forceinline__ uint32_t or3(uint32_t a, uint32_t b, uint32_t c) { uint32_t r; asm("lop3.b32 %0, %1, %2, %3, 0xfe;" : "=r"(r) : "r"(a), "r"(b), "r"(c)); return r; }
__device__ __forceinline__ bool any_bit(uint32_t a, uint32_t b, uint32_t m) {
  uint32_t r; asm("lop3.b32 %0, %1, %2, %3, 0xa8;" : "=r"(r) : "r"(a), "r"(b), "r"(m)); return __any_sync(0xffffffffu, r); }
template <int W, int N> __device__ __forceinline__ bool stale(const uint32_t (&v)[N][4], uint32_t tag) {
  uint32_t x = dif2(v[0][0], v[0][2], tag);
  if (N == 4) x = or3(x, dif2(v[1][0], v[1][2], tag), dif2(v[2 % N][0], v[2 % N][2], tag));
  return any_bit(x, dif2(v[N - 1][0], v[N - 1][2], tag), 1);
}
template <int W, int N, int S2 = 1024> __device__ __forceinline__ void retry(uint32_t (&v)[N][4], const uint8_t* p, uint32_t tag, int& it) {
#pragma unroll 1
  do { ldx<N, S2>(v, p); it += INC_A; } while (stale<W>(v, tag) && it < SPIN_LIMIT);
}
__device__ __forceinline__ void mma_h(float (&d)[4], const uint32_t (&a)[4], const uint32_t (&b)[4], int hf) { mma16816(d, a[0], a[1], a[2], a[3], b[2 * hf], b[2 * hf + 1]); }
__device__ __forceinline__ void sts128(uint32_t a, const uint32_t (&r)[4]) { sts128(a, r[0], r[1], r[2], r[3]); }
__device__ __forceinline__ void sts128f(uint32_t a, const float* r) { sts128(a, __float_as_uint(r[0]), __float_as_uint(r[1]), __float_as_uint(r[2]), __float_as_uint(r[3])); }
__device__ __forceinline__ void mbar_spin(uint32_t bar, uint32_t par, int& it) {
  asm volatile("{.reg .pred p; .reg .b32 par; mov.b32 par, %2;\nLOOP: mbarrier.try_wait.parity.shared::cta.b64 p, [%1], par; @p bra.uni DONE;\n"
               "add.s32 %0, %0, 1; setp.le.s32 p, %0, %3; @p bra.uni LOOP;\nDONE: }" : "+r"(it) : "r"(bar), "r"(par), "n"(SPIN_LIMIT) : "memory"); }
__device__ __forceinline__ void delay_until(unsigned t) {
  asm volatile("{.reg .pred p; .reg .b64 c; .reg .b32 lo, hi;\nLOOP: mov.u64 c, %%clock64; mov.b64 {lo, hi}, c; sub.s32 lo, lo, %0; setp.lt.s32 p, lo, 0; @p bra.uni LOOP;}" :: "r"(t) : "memory"); }
__device__ __forceinline__ void cut(int it) { asm volatile("{.reg .pred p; setp.lt.s32 p, %0, 0;\nL: @p st.volatile.shared.u32 [%0], %0; @p bra.uni L;}" :: "r"(it) : "memory"); }
__device__ __forceinline__ void zero(float (&c)[4][4]) {
#pragma unroll
  for (int i = 0; i < 4; i++) c[i][0] = c[i][1] = c[i][2] = c[i][3] = 0.f;
}

__device__ __forceinline__ void sched() { asm volatile("griddepcontrol.launch_dependents;" ::: "memory"); }
__device__ __forceinline__ const uint8_t* pinp(const uint8_t* p) { return reinterpret_cast<const uint8_t*>(__shfl_xor_sync(0xffffffffu, reinterpret_cast<unsigned long long>(p), 0)); }
__device__ __forceinline__ uint32_t bar_or(int id, uint32_t x) {
  uint32_t r; asm volatile("{.reg .pred p, q; setp.ne.u32 p, %2, 0; bar.red.or.pred q, %1, 256, p; selp.u32 %0, 1, 0, q;}" : "=r"(r) : "r"(id), "r"(x) : "memory"); return r; }
__device__ __forceinline__ uint32_t gtime() { uint32_t g; asm volatile("mov.u32 %0, %%globaltimer_lo;" : "=r"(g) :: "memory"); return g; }
template <int N> __device__ __forceinline__ void wait_time(uint32_t t) {
  asm volatile("{.reg .pred p; .reg .b32 g, n; mov.b32 n, 0;\nLOOP: mov.u32 g, %%globaltimer_lo; add.s32 n, n, 1; sub.s32 g, g, %0; setp.lt.s32 p, n, %1;\n"
               "setp.lt.and.s32 p, g, 0, p; @p bra.uni LOOP;}" :: "r"(t), "n"(N) : "memory"); }
__device__ __forceinline__ uint32_t ldx32(const void* p) { uint32_t v; asm volatile("ld.relaxed.gpu.global.b32 %0, [%1];" : "=r"(v) : "l"(p) : "memory"); return v; }
__device__ __forceinline__ void stx32(const void* p, uint32_t v) { asm volatile("st.relaxed.gpu.global.b32 [%0], %1;" :: "l"(p), "r"(v) : "memory"); }

__global__ void __launch_bounds__(256, 1)
rec_kernel(const __grid_constant__ RecMaps maps, const bf16* __restrict__ xin, const bf16* __restrict__ mem0) {
  extern __shared__ __align__(1024) uint8_t smem_raw[];
  const uint32_t sb = smem_u32(smem_raw);
  int role = blockIdx.x;
  {
    uint32_t smid, nsm; asm volatile("mov.u32 %0, %%smid;" : "=r"(smid)); asm volatile("mov.u32 %0, %%nsmid;" : "=r"(nsm));
    const int p = smid >> 1, u = p - 32;
    if (nsm == gridDim.x)
      role = (smid & 1) + (p < 32 ? 4 * ((p & 7) + 8 * (p >> 4)) + 2 * ((p >> 3) & 1) : p < 60 ? 4 * (16 + u % 7 + 7 * (u / 14)) + 2 * ((u / 7) & 1)
                         : p < 62 ? 2 * p + 8 : 2 * p - 4);
    role = uni(role);
  }
  if (role >= 128) {
    fft_cols(sb, role - 128, 4);
    grid_arrive(&g_x.ctr[32]); grid_wait(&g_x.ctr[32], 4);
    fft_rows_inv(&maps.fo, sb, role - 128, 4);
    return;
  }
  const int tid = threadIdx.x, warp = uni(tid >> 5), lane = tid & 31, wg = warp >> 2, w4 = warp & 3, g = lane >> 2, t = lane & 3;
  const int h = role >> 2, j = role & 3, jh = j & 1;
  uint32_t w[48][4];
  float aq[16], av[16];
  int it = 0;

  if (tid == 224) {
    mbar_init(sb + B_KV, 1); mbar_init(sb + B_W, 1); mbar_init(sb + B_X, 1); mbar_init(sb + B_X + 8, 3); mbar_init(sb + B_C, 4); mbar_init(sb + B_B, 1);
    asm volatile("fence.mbarrier_init.release.cluster;" ::: "memory");
    mbar_expect_tx(sb + B_W, 3 * 65536);
    for (int i = 0; i < 4; i++) {
      tma2d(sb + R_X + i * 16384, &maps.wq, h * DH + 32 * j, i * 256, sb + B_W);
      tma2d(sb + R_MEM + i * 16384, &maps.wk, h * DH + 32 * j, i * 256, sb + B_W);
    }
    for (int i = 0; i < 2; i++) tma2d(sb + R_WO + i * 32768, &maps.wv, h * DH + 64 * (j >> 1), jh * 512 + i * 256, sb + B_W);
    for (int i = 0; i < 4; i++) asm volatile("cp.async.bulk.prefetch.L2.global [%0], 8192;" :: "l"(xin + role * 16384 + i * 4096) : "memory");
    for (int i = 0; i < 4; i++)
      asm volatile("cp.async.bulk.prefetch.tensor.2d.L2.global [%0, {%1, %2}];" :: "l"(&maps.wo), "r"(256 * j + 64 * i), "r"(h * DH) : "memory");
  }
  if (tid < 128) asm volatile("prefetch.global.L2 [%0];" :: "l"(mem0 + tid * 64));
  __syncthreads();
  mbar_spin(sb + B_W, 0, it);
  const int lrow = (lane & 7) + ((lane >> 4) << 3), lhi = (lane >> 3) & 1;
  const int kq = wg ? 1 - jh : 3 * jh;
  const uint32_t LW = lrow * 128 + ((lhi ^ (lane & 7)) << 4);
  {
    const int chunk = w4 < 2 ? w4 + 2 * lhi : 2 * (w4 & 1) + lhi;
    uint32_t a = sb + (w4 < 2 ? R_X : R_MEM) + kq * 16384 + lrow * 64 + ((chunk ^ ((lrow >> 1) & 3)) << 4);
#pragma unroll
    for (int i = 0; i < 16; i++) ldsm4t(w[i], a + i * 1024);
    const uint32_t st = wg ? 1024 : 2048, av0 = sb + R_WO + (LW ^ (w4 << 5));
    const uint32_t a1 = wg ? a + 16384 : av0 + jh * 32768, a2 = wg ? a + 32768 : av0 + (1 - jh) * 32768;
#pragma unroll
    for (int i = 0; i < 16; i++) { ldsm4t(w[16 + i], a1 + i * st); ldsm4t(w[32 + i], a2 + i * st); }
  }
  uint32_t L16 = pin(lane * 16);
  uint8_t* const xb = reinterpret_cast<uint8_t*>(&g_x);
  const uint32_t uW = uni(sb + w4 * 512), uWo = uni(sb + R_WO + w4 * 16384), uMem = uni(sb + R_MEM + kq * 4096);
  const uint32_t dX = uni(((sb + R_X + kq * 16384) >> 4) | 0x10000u);
  auto load_wo = [&](uint32_t (&d)[32][4], int i0, int i1) {
#pragma unroll
    for (int i = i0; i < i1; i++) lds128(d[i], uWo + L16 + (i & 1) * 512 + (i >> 4) * 1024 + ((i >> 1) & 7) * 2048);
  };
  auto issue_x = [&](int n, int q, int k) {
    const uint32_t bar = sb + B_X + 8 * k;
    mbar_expect_tx(bar, 16384); tma3d(sb + R_X + q * 16384, &maps.x, n * SEG, 4 * q, bar);
  };
  auto store_stage = [&](int n) {
    fence_async();
    asm volatile("cp.async.bulk.global.shared::cta.bulk_group [%0], [%1], 8192; cp.async.bulk.commit_group;"
                 :: "l"(g_kqv[n & 3][role]), "r"(sb + R_STAGE) : "memory");
  };
  auto issue_kqv = [&](int n) {
    const int p = (n & 3) * 128 + 4 * h;
    mbar_expect_tx(sb + B_KV, 26624);
    tma3d(sb + R_K, &maps.k, 0, p, sb + B_KV); tma3d(sb + R_Q, &maps.q, 8 + 2 * j, p, sb + B_KV); tma3d(sb + R_V, &maps.v, 16, p, sb + B_KV);
  };
  auto fetch4k = [&](uint32_t dst, uint32_t off, uint32_t bar) {
    mbar_expect_tx(bar, 4096);
    asm volatile("cp.async.bulk.shared::cluster.global.mbarrier::complete_tx::bytes [%0], [%1], 4096, [%2];" :: "r"(dst), "l"(xb + off), "r"(bar) : "memory");
  };
  auto issue_c = [&]() { fetch4k(sb + R_MEM + w4 * 4096, offsetof(Xchg, C) + (j >> 1) * 16384 + w4 * 4096, sb + B_C); };
  auto wait_x = [&](int n, int i) { if (!(EXP & 1) || n < 2) mbar_spin(sb + B_X + 8 * i, n & 1, it); };
  auto project_v = [&](auto I0, auto I1, auto&& mid) {
    wg_fence();
    sfor<decltype(I0)::value, decltype(I1)::value>([&](auto I) {
      constexpr int i = decltype(I)::value;
      mid(i);
      wg_rs32<((i >> 2) & 3) * 256 + (i & 3) * 2, (i > 0)>(av, w[16 + i], i < 16 ? dX : dX ^ 1024);
    });
    wg_commit();
  };
  auto project_qk = [&](auto N, auto&& mid) {
    const uint32_t dQ = dX + ((uint32_t)it >> 31);
    wg_fence();
    sfor<0, decltype(N)::value>([&](auto I) {
      constexpr int i = decltype(I)::value;
      mid(i);
      wg_rs32<(i >> 2) * 256 + (i & 3) * 2, (i > 0 || decltype(N)::value == 16)>(aq, w[i], dQ);
    });
    wg_commit();
  };
  const uint32_t uP = uni(sb + R_X + (2 - 2 * jh) * 16384 + w4 * 512);
  auto park = [&]() {
    bar_sync(1, 128);
#pragma unroll
    for (int i = 0; i < 4; i++) sts128f(uP + L16 + i * 2048, aq + 4 * i);
    bar_arrive(2, 256);
  };
  auto unpark = [&]() {
#pragma unroll
    for (int i = 0; i < 4; i++) {
      const float4 p = lds128f(uP + L16 + i * 2048);
      aq[4 * i] = p.x; aq[4 * i + 1] = p.y; aq[4 * i + 2] = p.z; aq[4 * i + 3] = p.w;
    }
  };
  auto fin_qk = [&]() {
    const uint32_t a = sb + R_STAGE + (w4 < 2 ? 2048 + w4 * 128 : (w4 & 1) * 256) + (L16 & 112) + (L16 >> 7) * 512;
    stsm4t(a, pack2(aq[0], aq[1]), pack2(aq[4], aq[5]), pack2(aq[8], aq[9]), pack2(aq[12], aq[13]));
    stsm4t(a + (w4 < 2 ? 256 : 128), pack2(aq[2], aq[3]), pack2(aq[6], aq[7]), pack2(aq[10], aq[11]), pack2(aq[14], aq[15]));
  };
  auto fin_v = [&]() {
#pragma unroll
    for (int a = 0; a < 2; a++)
      sts128(sb + R_STAGE + 4096 + w4 * 1024 + a * 512 + L16, pack2(av[8 * a], av[8 * a + 1]), pack2(av[8 * a + 2], av[8 * a + 3]),
             pack2(av[8 * a + 4], av[8 * a + 5]), pack2(av[8 * a + 6], av[8 * a + 7]));
  };
  __syncthreads();
  if (tid == 224) {
#pragma unroll 1
    for (int i = 0; i < 4; i++) issue_x(0, i, i != 3 * jh);
    mbar_expect_tx(sb + B_W, 65536);
    for (int i = 0; i < 4; i++) tma2d(sb + R_WO + i * 16384, &maps.wo, 256 * j + 64 * i, h * DH, sb + B_W);
  }
  __syncwarp();
  if (wg) {
#pragma unroll
    for (int i = 0; i < NSW; i++) sts128(uW + R_WC + L16 + i * 2048, w[i]);
  }
#pragma unroll
  for (int i = 0; i < 4; i++) {
    const uint32_t* p = reinterpret_cast<const uint32_t*>(mem0 + g * DM + 128 * warp + 32 * i + 2 * t);
    sts128(sb + R_MEM + warp * 2048 + i * 512 + (g >> 1) * 128 + t * 32 + (g & 1) * 16, __ldg(p), __ldg(p + 4), __ldg(p + 8), __ldg(p + 12));
  }
#pragma unroll 1
  for (int n = 0; n < 2; n++) {
    wait_x(n, 1);
    if (wg == 0) {
      wait_x(n, 0);
      project_v(IC<0>{}, IC<32>{}, [](int) {});
      if (tid == 96 && n == 1) {
        asm volatile("cp.async.bulk.wait_group 0;" ::: "memory");
        __threadfence(); atomicAdd(&g_x.ctr[h], 1u);
      }
      __syncwarp();
      bar_sync(2, 256);
      unpark();
      project_qk(IC<16>{}, [](int) {});
      wg_wait<0>(); keep(aq); keep(av);
      fin_v(); fin_qk();
    } else {
      project_qk(IC<48>{}, [](int) {});
      wg_wait<0>(); keep(aq);
      park();
      if (tid == 128 && n == 1) {
        for (int k = 0; *reinterpret_cast<volatile unsigned*>(&g_x.ctr[h]) < 4 && k < SPIN_LIMIT; k++) {}
        __threadfence(); asm volatile("fence.proxy.async;" ::: "memory");
        issue_kqv(0);
      }
    }
    __syncthreads();
    if (tid == 96 && n == 0) store_stage(0);
    if (tid == 128 && n == 0) {
#pragma unroll 1
      for (int i = 0; i < 4; i++) issue_x(1, i, i != 3 * jh);
    }
    __syncwarp();
  }
  mbar_spin(sb + B_W, 1, it);
#pragma unroll
  for (int i = 0; i < 4; i++) {
    uint32_t f[4][4];
    const uint32_t a = sb + R_WO + warp * 8192 + i * 2048;
#pragma unroll
    for (int q = 0; q < 4; q++) ldsm4t(f[q], a + (LW ^ (q << 5)));
    __syncwarp();
#pragma unroll
    for (int q = 0; q < 4; q++) sts128(a + q * 512 + L16, f[q]);
  }
  mbar_spin(sb + B_KV, 0, it);
  if (tid == 0) sts32(sb + B_DUE, (gtime() & ~31u) - NS_P);
  __syncthreads();

  const float sc = 0.08838834764831845f * 1.4426950408889634f;
  uint8_t* const xa = xb + uni(h * 16384);
  const uint32_t uA = uni(wg ? (w4 >> 1) * 2048 + j * 512 + (w4 & 1) * 256 : 8192 + (4 * (j >> 1) + w4) * 512 + jh * 256);
  const uint32_t uB = uni(offsetof(Xchg, B) + (32 * w4 + j) * 8192 + h * 128);
  uint32_t nc = 1;

#pragma unroll 1
  for (int s = 0;; nc++) {
    const uint32_t tag = (s + 1) & 1;
    auto fresh = [&]() { L16 += (uint32_t)it >> 31; };
    float c[4][4], r4[4];
    auto fold = [&]() {
#pragma unroll
      for (int i = 0; i < 4; i++) r4[i] = (c[0][i] + c[1][i]) + (c[2][i] + c[3][i]);
    };
    auto xpos = [&](int pos, int wp) {
      if (!(EXP & 1) && (pos == XCD || pos == XB || pos == XA) && warp == wp && s + 1 < NSEG && elect()) {
        const int z = (uint32_t)it >> 31, jz = jh + z;
        if (pos == XCD) { issue_x(s + 2, 2 - 2 * jz, 1 + z); issue_x(s + 2, 3 - 2 * jz, 1 + z); }
        if (pos == XB) issue_x(s + 2, 1 + jz, 1 + z);
        if (pos == XA) issue_x(s + 2, 3 * jz, z);
      }
      __syncwarp();
    };
    if (wg == 0) {
      const uint32_t ma = pin(uMem + (L16 & 384) + (L16 & 48) * 2 + (L16 & 64) / 4), ta = pin(sb + R_MEM + w4 * 4096 + L16 * 2 + (L16 >> 6) * 4);
      mbar_spin(sb + B_C, nc & 1, it);
      TS(13);
      uint32_t b[16][4], tg[4];
#pragma unroll
      for (int i = 0; i < 8; i++) { lds128(b[i], ma + i * 512); __syncwarp(); }
#pragma unroll
      for (int i = 0; i < 4; i++) tg[i] = lds32(ta + i * 1024);
      sched();
      zero(c);
#pragma unroll
      for (int i = 0; i < 16; i++) mma_h(c[i & 3], w[i], b[i >> 1], i & 1);
      fold();
      sts128f(uW + R_RED + L16, r4);
      TS(1);
      fresh();
      uint8_t* adst;
      if (__any_sync(0xffffffffu, bar_or(4, (dif2(tg[0], tg[1], s) | dif2(tg[2], tg[3], s)) & (s > 0))) && nc < 65536) {
        bar_sync(3, 256);
        if (elect()) issue_c();
        __syncwarp();
        continue;
      }
#pragma unroll
      for (int i = 0; i < 2; i++) lds128(b[8 + i], (ma ^ 4096) + i * 512);
      sched();
      TS(0);
      zero(c);
#pragma unroll
      for (int i = 0; i < 16; i++) {
        mma_h(c[(2 * i) & 3], w[16 + 2 * i], b[i], 0); mma_h(c[(2 * i + 1) & 3], w[17 + 2 * i], b[i], 1);
        if (i >= 1 && i < 7) { lds128(b[9 + i], (ma ^ 4096) + (i + 1) * 512); sched(); }
        if (i == 9) { sched(); adst = const_cast<uint8_t*>(pinp(xa + uA + L16 / 2)); sched(); }
      }
      fold();
      stx64(adst, (pack2(r4[0], r4[1]) & ~1u) | tag, pack2(r4[2], r4[3]));
      sched();
      const unsigned tpub = clk();
      TS(3);
      xpos(0, 0);
      const uint32_t due = lds32(sb + B_DUE);
      uint32_t vf[4][4], vm[2][4], p[5], o[4];
      const uint32_t va = sb + R_V + (w4 >> 1) * 8192 + (w4 & 1) * 2048 + L16;
#pragma unroll
      for (int i = 0; i < 4; i++) {
        uint32_t q[4]; lds128(vf[i], va + i * 512); lds128(q, va + 4096 + i * 512);
#pragma unroll
        for (int e = 0; e < 4; e++) vf[i][e] = hadd2(vf[i][e], q[e]);
      }
      const uint32_t sa = pin(sb + R_S + (L16 >> 1));
      const uint8_t* vsrc = pinp(xa + 8192 + w4 * 1024 + L16 / 2);
      float rs[2][4];
      auto attend = [&](uint32_t a, bool causal) {
        float2 sv[6];
#pragma unroll
        for (int i = 0; i < 6; i++) { sv[i] = lds64f(a + ((i + 4) % 6) * 256); __syncwarp(); }
        sv[1].x += sv[0].x; sv[1].y += sv[0].y;
        if (causal) {
          const int dq = (int)(L16 >> 6) - (int)((L16 >> 3) & 6) + 8 * j;
#pragma unroll
          for (int i = 0; i < 4; i++) {
            if (8 * i > dq) sv[2 + i].x = -INFINITY;
            if (8 * i + 1 > dq) sv[2 + i].y = -INFINITY;
          }
        }
        const float m = fmaxf(fmaxf(fmaxf(fmaxf(sv[1].x, sv[1].y), fmaxf(sv[2].x, sv[2].y)), fmaxf(sv[3].x, sv[3].y)), fmaxf(fmaxf(sv[4].x, sv[4].y), fmaxf(sv[5].x, sv[5].y)));
        const float m1 = __shfl_xor_sync(0xffffffffu, m, 1), m2 = __shfl_xor_sync(0xffffffffu, m, 2), m3 = __shfl_xor_sync(0xffffffffu, m, 3);
        if (!causal) { sched(); bar_arrive(7, 256); }
        const float ms = -fmaxf(fmaxf(m, m1), fmaxf(m2, m3)) * sc;
        zero(c);
#pragma unroll
        for (int i = 0; i < 8; i++) rs[i >> 2][i & 3] = 0.f;
        float2 e[5];
#pragma unroll
        for (int i = 0; i < 7; i++) {
          if (i < 5) { const float2 v = sv[i < 4 ? i + 2 : 1]; e[i].x = ex2(fmaf(v.x, sc, ms)); e[i].y = ex2(fmaf(v.y, sc, ms)); }
          if (i >= 1 && i < 6) p[i - 1] = pack2(e[i - 1].x, e[i - 1].y);
          if (i >= 2) mma1688(rs[i & 1], 0x3F803F80u, 0x3F803F80u, p[i - 2]);
          if (i == 3 || i == 5) { mma_a(c[0], vf[(i - 3) >> 1], p[i - 3], p[i - 2]); mma_a(c[1], vf[2 + ((i - 3) >> 1)], p[i - 3], p[i - 2]); }
          if (i < 6) sched();
        }
        mma_a(c[2], vm[0], p[4], p[4]); mma_a(c[3], vm[1], p[4], p[4]);
      };
      auto norm = [&]() {
        const float n0 = rcp(rs[0][0] + rs[1][0]), n1 = rcp(rs[0][1] + rs[1][1]);
#pragma unroll
        for (int i = 0; i < 4; i++) { const int m = i >> 1, e = 2 * (i & 1); o[i] = pack2((c[m][e] + c[m + 2][e]) * n0, (c[m][e + 1] + c[m + 2][e + 1]) * n1); }
      };
      delay_until(tpub + DLY_V);
      wait_time<512>(due + (NS_P + NS_V));
      TS(4);
      ldx(vm, vsrc);
      if (warp == 0) cpa16(sb + R_RED + L16, xb + offsetof(Xchg, T) + L16 * 8);
      sched();
      bar_sync(5, 256);
      attend(sa, false);
      if (stale<2>(vm, tag)) {
        retry<2>(vm, vsrc, tag, it);
#pragma unroll
        for (int i = 0; i < 8; i++) c[2 + (i >> 2)][i & 3] = 0.f;
        mma_a(c[2], vm[0], p[4], p[4]); mma_a(c[3], vm[1], p[4], p[4]);
      }
      TS(6);
      norm();
      stsm4t(uW + R_O + L16, o[0], o[1], o[2], o[3]);
      bar_sync(6, 256);
      TS(7);
      xpos(3, 1);
      attend(sa + 1536, true);
      TS(8);
      if (warp == 0 && s + 1 < NSEG) {
        uint32_t tq[4];
        asm volatile("cp.async.wait_all;" ::: "memory");
        lds128(tq, sb + R_RED + L16);
        const uint32_t ref = lds32(sb + B_DUE);
#pragma unroll 1
        while (any_bit(or3(tq[0] - s - 1, tq[1] - s - 1, tq[2] - s - 1), tq[3] - s - 1, 30) && ++it < SPIN_LIMIT) ldx128(tq, xb + offsetof(Xchg, T) + L16 * 8);
        const int d = max(max((int)(tq[0] - ref), (int)(tq[1] - ref)), max((int)(tq[2] - ref), (int)(tq[3] - ref)));
        const uint32_t last = (ref + __reduce_max_sync(0xffffffffu, d)) & ~31u;
        TS(2);
        wait_time<512>(last + NS_B);
        if (elect()) fetch4k(sb + R_MEM, offsetof(Xchg, B) + role * 8192, sb + B_B);
        __syncwarp();
        TS(5);
        sts32(sb + B_DUE, last);
        xpos(5, 0);
        LOG(9, last);
        LOG(13, tl - last);
      }
      norm();
      const uint32_t ob = uni(sb + R_MEM + 4096 + w4 * 1024);
      stsm4t(ob + (L16 & 112) * 4 + (((L16 >> 3) ^ (L16 >> 1)) & 48), o[0], o[1], o[2], o[3]);
      __syncwarp();
      lds128(o, ob + (L16 ^ ((L16 >> 3) & 48)));
      auto put_o = [&]() {
        *reinterpret_cast<uint4*>(reinterpret_cast<uint8_t*>(g_ox) + (((s * SEG + 8 * j) * HD + h * DH + 32 * w4) * 2 + (L16 >> 6) * (HD * 2) + (L16 & 48))) = make_uint4(o[0], o[1], o[2], o[3]);
      };
      if (s + 1 == NSEG) { put_o(); break; }
      if (OXPOS < 0) put_o();
      fresh();
      const uint32_t ba = pin(sb + R_MEM + (L16 & 112) * 8 + (L16 >> 8) * 1024 + ((w4 * 32 + ((L16 >> 3) & 16)) ^ (L16 & 112)));
      if (NPRE) { wait_x(s + 2, 0); bar_sync(2, 256); project_v(IC<0>{}, IC<NPRE>{}, [](int) {}); }
      TS(9);
      mbar_spin(sb + B_B, s & 1, it);
      TS(10);
      uint32_t bq[2][4];
      auto sum_b = [&]() {
        ldsm4t(bq[0], ba); ldsm4t(bq[1], ba + 2048);
        sched();
#pragma unroll
        for (int i = 0; i < 8; i++) c[i >> 2][i & 3] = 0.f;
        mma_a(c[0], bq[0], 0x3F803F80u, 0x3F803F80u); mma_a(c[1], bq[1], 0x3F803F80u, 0x3F803F80u);
        const uint32_t t2 = tag * 0x10001u;
        const bool old = any_bit(or3(dif2(bq[0][0], bq[0][1], t2), dif2(bq[0][2], bq[0][3], t2), dif2(bq[1][0], bq[1][1], t2)), dif2(bq[1][2], bq[1][3], t2), L16 < 64 ? 0x10001u : 0u);
        const uint8_t* cdst = xb + (offsetof(Xchg, C) + j * 4096 + h * 128 + w4 * 32 + (L16 & 16) * 1024 + (L16 & 64) / 4 + (L16 >> 7) * 4);
        const uint32_t msk = (L16 >> 6) == (h & 3) * 2 + ((h >> 2) & 1) ? 0xFFFE0000u : 0xFFFFFFFFu;
        const uint32_t T = (tag << 16) & ~msk, u = ((__float_as_uint(c[0][0] + c[1][0]) + ((0x10000u & ~msk) - T)) & msk) | T;
        asm volatile("{.reg .pred p; setp.eq.u32 p, %2, 0; @p st.relaxed.gpu.global.b32 [%0], %1;}"
                     :: "l"(cdst), "r"(pack2(__uint_as_float(u), c[0][2] + c[1][2])), "r"((uint32_t)(old || (L16 & 32))) : "memory");
        return old;
      };
      if (sum_b()) {
#pragma unroll 1
        do {
          const uint8_t* p = xb + (offsetof(Xchg, B) + role * 8192 + (ba - sb - R_MEM));
          ldx128(bq[0], p); ldx128(bq[1], p + 2048);
          sts128(ba, bq[0]); sts128(ba + 2048, bq[1]);
          __syncwarp();
          it += INC_B;
        } while (sum_b() && it < SPIN_LIMIT);
      }
      sched();
      TS(11);
      bar_arrive(0, 256);
      if (!NPRE) { wait_x(s + 2, 0); bar_sync(2, 256); }
      fresh();
      if (EXP & 8) { if (OXPOS >= 0) put_o(); unpark(); for (int i = 0; i < 16; i++) av[i] = 0; } else {
      project_v(IC<NPRE>{}, IC<32>{}, [&](int n) {
        if (n == OXPOS) { __syncwarp(); put_o(); __syncwarp(); }
        if (n == UNP) unpark();
      });
      project_qk(IC<16>{}, [](int) {});
      }
      TS(12);
      LOG(warp, it);
      wg_wait<1>(); keep(av);
      fin_v();
      wg_wait<0>(); keep(aq);
      fin_qk();
      TS(15);
    } else {
      const uint32_t ma = pin(uMem + (L16 & 384) + (L16 & 48) * 2 + (L16 & 64) / 4);
      const uint8_t* adst = pinp(xa + uA + L16 / 2);
      const uint8_t* asrc = pinp(xa + (warp == 7) * 1024 + L16 / 2);
      const uint32_t due = lds32(sb + B_DUE) + NS_P;
      mbar_spin(sb + B_C, nc & 1, it);
      TS(13);
      float4 o4;
      uint32_t old;
      {
        uint32_t b[24][4];
#pragma unroll
        for (int i = 0; i < PD1; i++) { lds128(b[i], ma + i * 512); __syncwarp(); }
        sched();
        zero(c);
#pragma unroll
        for (int i = 0; i < 24; i++) {
          if (i + PD1 < 24) lds128(b[i + PD1], ma + (i + PD1) * 512);
          if (i == 21) old = bar_or(4, 0);
          mma_h(c[(2 * i) & 3], w[2 * i], b[i], 0); mma_h(c[(2 * i + 1) & 3], w[2 * i + 1], b[i], 1);
          if (i < 21) sched();
        }
        o4 = lds128f(uW + R_RED + L16);
      }
      fresh();
      fold();
      TS(0);
      const uint32_t r0 = movm(pack2(r4[0] + o4.x, r4[1] + o4.y)), r1 = movm(pack2(r4[2] + o4.z, r4[3] + o4.w));
      asm volatile("{.reg .pred p; setp.eq.u32 p, %3, 0; @p st.relaxed.gpu.global.v2.b32 [%0], {%1,%2};}" :: "l"(adst), "r"((r0 & ~1u) | tag), "r"(r1), "r"(old) : "memory");
      sched();
      const unsigned tpub = clk(), now = gtime();
      if (__any_sync(0xffffffffu, old) && nc < 65536) { bar_sync(3, 256); continue; }
      TS(2);
      uint32_t wo[32][4];
      const uint32_t qa = sb + R_Q + (L16 & 112) + (L16 & 128) * 2 + (L16 >> 8) * 128;
      if (warp < 6) {
        uint32_t kf[8][4], qx[4][4], q[4][4];
        const uint32_t ka = sb + R_K + w4 * 1024 + (L16 & 112) + (L16 & 128) * 4 + (L16 & 256);
#pragma unroll
        for (int i = 0; i < NK0; i++) ldsm4(kf[i], ka + (i >> 1) * 2048 + (i & 1) * 128);
        auto score = [&](const uint32_t (&q)[4][4]) {
          zero(c);
#pragma unroll
          for (int i = 0; i < 8; i++) mma_h(c[i & 3], kf[i], q[i >> 1], i & 1);
        };
        auto put = [&](uint32_t a) {
          fold();
#pragma unroll
          for (int i = 0; i < 4; i++) sts32f(a + (i & 1) * 32 + (i >> 1) * 256, r4[i]);
        };
        delay_until(tpub + DLY_A);
        wait_time<512>(due);
        TS(4);
        ldx(q, asrc);
        sched();
#pragma unroll
        for (int i = NK0; i < 8; i++) ldsm4(kf[i], ka + (i >> 1) * 2048 + (i & 1) * 128);
#pragma unroll
        for (int i = 0; i < 4; i++) ldsm4(qx[i], qa + i * 512);
        const uint32_t sa = pin(sb + R_S + w4 * 512 + (L16 & 48) * 4 + (L16 >> 6) * 4);
        sched();
        load_wo(wo, 0, NA4);
        score(qx);
        put(sa + 1536);
        sched();
        score(q);
        if (stale<2>(q, tag)) { retry<2>(q, asrc, tag, it); score(q); }
        TS(5);
        put(sa);
        bar_arrive(5, 256);
        bar_sync(7, 256);
        load_wo(wo, NA4, NB1);
      } else {
        uint32_t qx[2][4], q[4][4];
        if (warp == 6) {
          const uint32_t t1 = (now & ~31u) + NS_M;
          LOG(10, now - due);
          if (elect()) stx32(&g_x.T[h][j], ((int)(t1 - due) > 0 ? t1 + NS_PEN : due) | ((s + 1) & 31));
          __syncwarp();
        }
#pragma unroll
        for (int i = 0; i < 2; i++) ldsm4(qx[i], qa + (w4 & 1) * 1024 + i * 512);
        load_wo(wo, 0, NE6);
        auto score = [&](const uint32_t (&a0)[4], const uint32_t (&a1)[4]) {
          zero(c);
#pragma unroll
          for (int i = 0; i < 4; i++) mma_h(c[i], i < 2 ? a0 : a1, q[2 + (i >> 1)], i & 1);
        };
        auto put = [&](uint32_t a) { sts64f(a, (c[0][0] + c[1][2]) + (c[2][0] + c[3][2]), (c[0][1] + c[1][3]) + (c[2][1] + c[3][3])); };
        delay_until(tpub + DLY_A);
        wait_time<512>(due);
        TS(4);
        ldx<4, 2048>(q, asrc);
        sched();
        const uint32_t sa = pin(sb + R_S + 512 + w4 * 256 + (L16 >> 1));
        load_wo(wo, NE6, NA6);
        xpos(1, 7);
        score(q[0], q[1]);
        if (stale<2>(q, tag)) { retry<2, 4, 2048>(q, asrc, tag, it); score(q[0], q[1]); }
        TS(5);
        put(sa);
        bar_sync(5, 256);
        score(qx[0], qx[1]);
        put(sa + 1536);
        sched();
        if (!(EXP & 4) && warp == 6 && s + 1 < NSEG && elect()) store_stage(s + 1);
        xpos(2, 7);
        bar_sync(7, 256);
        load_wo(wo, NA6, NB1);
      }
      fresh();
      uint8_t* const dst = const_cast<uint8_t*>(pinp(xb + uB + ((((L16 >> 2) * 0x2001u) & 0x18070u) ^ ((h & 7) << 4))));
      TS(7);
      bar_sync(6, 256);
      {
        uint32_t b[4][4];
        float d[4][4];
#pragma unroll
        for (int i = 0; i < 4; i++) { ldsm4(b[i], sb + R_O + i * 512 + L16); __syncwarp(); }
        sched();
        zero(c); zero(d);
#pragma unroll
        for (int i = 0; i < 22; i++) {
          mma_h(i < 16 ? c[i & 3] : d[i & 3], wo[i], b[(i >> 2) & 3], (i >> 1) & 1);
          if (i >= 5 && NB1 + i - 5 < 32) load_wo(wo, NB1 + i - 5, NB1 + i - 4);
          if (i >= 3) sched();
        }
        stx128(dst, (pack2(c[0][0] + c[2][0], c[0][1] + c[2][1]) & ~1u) | tag, pack2(c[0][2] + c[2][2], c[0][3] + c[2][3]),
               pack2(c[1][0] + c[3][0], c[1][1] + c[3][1]), pack2(c[1][2] + c[3][2], c[1][3] + c[3][3]));
#pragma unroll
        for (int i = 22; i < 32; i++) { mma_h(d[i & 3], wo[i], b[(i >> 2) & 3], (i >> 1) & 1); if (i == 25) sched(); }
        sched();
        stx128(dst + 131072, (pack2(d[0][0] + d[2][0], d[0][1] + d[2][1]) & ~1u) | tag, pack2(d[0][2] + d[2][2], d[0][3] + d[2][3]),
               pack2(d[1][0] + d[3][0], d[1][1] + d[3][1]), pack2(d[1][2] + d[3][2], d[1][3] + d[3][3]));
        sched();
      }
      TS(8);
      if (s + 1 == NSEG) break;
      if (warp == 6) {
        asm volatile("cp.async.bulk.wait_group 0;" ::: "memory");
        if (elect()) stx32(xa + 4096 + j * 4, s + 1);
        __syncwarp();
      }
#pragma unroll
      for (int i = 0; i < NSW; i++) lds128(w[i], uW + R_WC + L16 + i * 2048);
      if (warp == 4) LOG(12, tb);
      xpos(4, 7);
      wait_x(s + 2, 1);
      TS(9);
      const uint8_t* fsrc = xa + 4096 + ((L16 >> 2) & 12);
      uint32_t fl;
      auto next_kqv = [&]() {
        if (warp == 5) {
#pragma unroll 1
          while (__any_sync(0xffffffffu, fl != s + 1) && !(EXP & 4) && it < SPIN_LIMIT) { fl = ldx32(fsrc); it++; }
          if (!(EXP & 2) && elect()) issue_kqv(s + 1);
          __syncwarp();
        }
      };
      project_qk(IC<48>{}, [&](int n) {
        if (n == FLPOS) {
          __syncwarp();
          asm volatile("{.reg .pred p; setp.eq.u32 p, %2, 5; mov.b32 %0, 0; @p ld.relaxed.gpu.global.b32 %0, [%1];}" : "=r"(fl) : "l"(fsrc), "r"(warp) : "memory");
          __syncwarp();
        }
      });
      TS(10);
      if (KVPOS == 1) next_kqv();
      wg_wait<0>(); keep(aq);
      park();
      if (KVPOS == 2) next_kqv();
      TS(11);
      LOG(warp, it);
      if (warp == 4) LOG(8, nc);
      bar_sync(0, 256);
      const uint32_t cdue = lds32(sb + B_DUE) + NS_C;
      sched();
      delay_until(clk() + DLY_C);
      TS(12);
      if (warp == 7) LOG(11, gtime() - cdue);
      wait_time<512>(cdue);
      if (elect()) issue_c();
      __syncwarp();
      TS(14);
      if (!(EXP & 2)) mbar_spin(sb + B_KV, tag, it);
      TS(15);
    }
    s++;
  }
  if (it >= SPIN_LIMIT || nc >= 65536) g_err = 2;
}

typedef CUresult (*EncodeFn)(CUtensorMap*, CUtensorMapDataType, cuuint32_t, void*, const cuuint64_t*, const cuuint64_t*, const cuuint32_t*,
                             const cuuint32_t*, CUtensorMapInterleave, CUtensorMapSwizzle, CUtensorMapL2promotion, CUtensorMapFloatOOBfill);
static void make_map(EncodeFn fn, CUtensorMap* m, const void* p, uint64_t cols, uint64_t rows, uint64_t pitch, uint32_t bc, uint32_t br, CUtensorMapSwizzle sw) {
  cuuint64_t dims[2] = {cols, rows}, strides[1] = {pitch * 2};
  cuuint32_t box[2] = {bc, br}, es[2] = {1, 1};
  fn(m, CU_TENSOR_MAP_DATA_TYPE_BFLOAT16, 2, const_cast<void*>(p), dims, strides, box, es, CU_TENSOR_MAP_INTERLEAVE_NONE, sw,
     CU_TENSOR_MAP_L2_PROMOTION_L2_256B, CU_TENSOR_MAP_FLOAT_OOB_FILL_NONE);
}

extern "C" void kernel_launch(void* const* d_in, const int* in_sizes, int n_in, void* d_out, int out_size) {
  const bf16* Ax = (const bf16*)d_in[0]; const bf16* mem0 = (const bf16*)d_in[1];
  const bf16* Wq = (const bf16*)d_in[2]; const bf16* Wk = (const bf16*)d_in[3]; const bf16* Wv = (const bf16*)d_in[4];
  const bf16* Wo = (const bf16*)d_in[5];
  const bf16* Bx = (const bf16*)d_in[7]; const bf16* wr = (const bf16*)d_in[8]; const bf16* wi = (const bf16*)d_in[9];
  bf16* out = (bf16*)d_out;

  void* fp = nullptr; cudaDriverEntryPointQueryResult qr;
  cudaGetDriverEntryPoint("cuTensorMapEncodeTiled", &fp, cudaEnableDefault, &qr);
  EncodeFn fn = (EncodeFn)fp;
  void *kqv, *ox;
  cudaGetSymbolAddress(&kqv, g_kqv); cudaGetSymbolAddress(&ox, g_ox);
  const CUtensorMapSwizzle S128 = CU_TENSOR_MAP_SWIZZLE_128B, S64 = CU_TENSOR_MAP_SWIZZLE_64B;

  GemmMaps m3; RecMaps mr;
  make_map(fn, &m3.a, ox, HD, S_LEN, HD, 64, 128, S128);
  make_map(fn, &m3.b[0], Wo, DM, HD, DM, 64, 64, S128);
  m3.b[1] = m3.b[0]; m3.b[2] = m3.b[0];
  make_map(fn, &m3.c, out, DM, S_LEN, 2 * DM, 64, 64, S128);
  make_map(fn, &mr.wq, Wq, HD, DM, HD, 32, 256, S64);
  make_map(fn, &mr.wk, Wk, HD, DM, HD, 32, 256, S64);
  make_map(fn, &mr.wv, Wv, HD, DM, HD, 64, 256, S128);
  make_map(fn, &mr.wo, Wo, DM, HD, DM, 64, 128, S128);
  {
    cuuint64_t dims[3] = {64, S_LEN, 16}, strides[2] = {DM * 2, 128};
    cuuint32_t box[3] = {64, 32, 4}, es[3] = {1, 1, 1};
    fn(&mr.x, CU_TENSOR_MAP_DATA_TYPE_BFLOAT16, 3, const_cast<bf16*>(Ax), dims, strides, box, es, CU_TENSOR_MAP_INTERLEAVE_NONE, S128,
       CU_TENSOR_MAP_L2_PROMOTION_L2_256B, CU_TENSOR_MAP_FLOAT_OOB_FILL_NONE);
  }
  for (int i = 0; i < 3; i++) {
    cuuint64_t dims[3] = {128, 32, 512}, strides[2] = {256, 8192};
    cuuint32_t box[3] = {128, i == 0 ? 8u : i == 1 ? 2u : 16u, 4}, es[3] = {1, 1, 1};
    fn(i == 0 ? &mr.k : i == 1 ? &mr.q : &mr.v, CU_TENSOR_MAP_DATA_TYPE_BFLOAT16, 3, kqv, dims, strides, box, es, CU_TENSOR_MAP_INTERLEAVE_NONE,
       CU_TENSOR_MAP_SWIZZLE_NONE, CU_TENSOR_MAP_L2_PROMOTION_L2_256B, CU_TENSOR_MAP_FLOAT_OOB_FILL_NONE);
  }
  {
    cuuint64_t dims[3] = {64, 16, S_LEN}, strides[2] = {128, 2 * DM * 2};
    cuuint32_t box[3] = {64, 16, 2}, es[3] = {1, 1, 1};
    fn(&mr.fo, CU_TENSOR_MAP_DATA_TYPE_BFLOAT16, 3, out + DM, dims, strides, box, es, CU_TENSOR_MAP_INTERLEAVE_NONE, S128,
       CU_TENSOR_MAP_L2_PROMOTION_NONE, CU_TENSOR_MAP_FLOAT_OOB_FILL_NONE);
  }
  constexpr int SM3 = 6 * 32768 + 32768 + 256 + 1024;
  cudaFuncSetAttribute(gemm_kernel<128, 6>, cudaFuncAttributeMaxDynamicSharedMemorySize, SM3);
  cudaFuncSetAttribute(rec_kernel, cudaFuncAttributeMaxDynamicSharedMemorySize, R_TOTAL);

  cudaStream_t st = cudaStreamPerThread;
  cudaFuncSetAttribute(fft_pre_kernel, cudaFuncAttributeMaxDynamicSharedMemorySize, F_SMEM);
  fft_pre_kernel<<<128, 256, F_SMEM, st>>>(Bx, wr, wi);
  rec_kernel<<<132, 256, R_TOTAL, st>>>(mr, Ax, mem0);
  gemm_kernel<128, 6><<<128, 384, SM3, st>>>(m3, 16, 8, 64, 8, 1);
}
```

```cpp
#include <cuda_runtime.h>
#include <cuda_bf16.h>
#include <cuda.h>
#include <stdint.h>
#include <stddef.h>
#include <type_traits>

typedef __nv_bfloat16 bf16;

constexpr int S_LEN = 2048, DM = 1024, NH = 32, DH = 128, MEM = 8, SEG = 32, NSEG = 64;
constexpr int HD = NH * DH;
#define SPIN 20
constexpr int SPIN_LIMIT = 1 << SPIN, INC_A = 1, INC_B = 1;

constexpr unsigned NC_MAX = 4096;
__device__ __align__(1024) uint4 g_kqv[4][128][512];
__device__ __align__(1024) bf16 g_ox[(size_t)S_LEN * HD];
struct Xchg {
  uint4 A[32][2][2][256];
  uint4 C[2][4][256];
  uint4 B[128][2][256];
  uint32_t T[32][32];
  unsigned ctr[64];
};
__device__ __align__(8192) Xchg g_x;
__device__ __align__(1024) uint4 g_y[1024 * 256];
__device__ __align__(1024) uint4 g_wt[513 * 512];
__device__ int g_err;

__device__ __forceinline__ unsigned clk() { unsigned long long c; asm volatile("mov.u64 %0, %%clock64;" : "=l"(c)); return (unsigned)c; }
__device__ __forceinline__ uint32_t smem_u32(const void* p) { return (uint32_t)__cvta_generic_to_shared(p); }
__device__ __forceinline__ void mbar_init(uint32_t bar, int cnt) { asm volatile("mbarrier.init.shared::cta.b64 [%0], %1;" :: "r"(bar), "r"(cnt) : "memory"); }
__device__ __forceinline__ void mbar_expect_tx(uint32_t bar, int bytes) { asm volatile("mbarrier.arrive.expect_tx.shared::cta.b64 _, [%0], %1;" :: "r"(bar), "r"(bytes) : "memory"); }
__device__ __forceinline__ void mbar_arrive(uint32_t bar) { asm volatile("mbarrier.arrive.shared::cta.b64 _, [%0];" :: "r"(bar) : "memory"); }
__device__ __forceinline__ void mbar_arrive_cluster(uint32_t bar, int cta) {
  asm volatile("{.reg .b32 r; mapa.shared::cluster.u32 r, %0, %1; mbarrier.arrive.shared::cluster.b64 _, [r];}" :: "r"(bar), "r"(cta) : "memory"); }
__device__ __forceinline__ bool mbar_try(uint32_t bar, int par) {
  uint32_t ok; asm volatile("{.reg .pred p; mbarrier.try_wait.parity.shared::cta.b64 p, [%1], %2; selp.u32 %0, 1, 0, p;}" : "=r"(ok) : "r"(bar), "r"(par) : "memory"); return ok; }
__device__ __forceinline__ bool mbar_test(uint32_t bar, int par) {
  uint32_t ok; asm volatile("{.reg .pred p; mbarrier.test_wait.parity.shared::cta.b64 p, [%1], %2; selp.u32 %0, 1, 0, p;}" : "=r"(ok) : "r"(bar), "r"(par) : "memory"); return ok; }
__device__ __forceinline__ void mbar_wait(uint32_t bar, int par) {
  int it = 0;
  while (!mbar_try(bar, par)) { if (++it > SPIN_LIMIT) { g_err = 1; break; } }
}
__device__ __forceinline__ void tma2d(uint32_t dst, const CUtensorMap* m, int c0, int c1, uint32_t bar) {
  asm volatile("cp.async.bulk.tensor.2d.shared::cluster.global.mbarrier::complete_tx::bytes [%0], [%1, {%3, %4}], [%2];"
    :: "r"(dst), "l"(m), "r"(bar), "r"(c0), "r"(c1) : "memory"); }
__device__ __forceinline__ void tma2d_mc(uint32_t dst, const CUtensorMap* m, int c0, int c1, uint32_t bar, uint16_t mask) {
  asm volatile("cp.async.bulk.tensor.2d.shared::cluster.global.mbarrier::complete_tx::bytes.multicast::cluster [%0], [%1, {%3, %4}], [%2], %5;"
    :: "r"(dst), "l"(m), "r"(bar), "r"(c0), "r"(c1), "h"(mask) : "memory"); }
__device__ __forceinline__ void tma2d_store(const CUtensorMap* m, uint32_t src, int c0, int c1) {
  asm volatile("cp.async.bulk.tensor.2d.global.shared::cta.bulk_group [%0, {%2, %3}], [%1];" :: "l"(m), "r"(src), "r"(c0), "r"(c1) : "memory"); }
__device__ __forceinline__ void fence_async() { asm volatile("fence.proxy.async.shared::cta;" ::: "memory"); }
__device__ __forceinline__ void bar_sync(int id, int n) { asm volatile("bar.sync %0, %1;" :: "r"(id), "r"(n) : "memory"); }
__device__ __forceinline__ void bar_arrive(int id, int n) { asm volatile("bar.arrive %0, %1;" :: "r"(id), "r"(n) : "memory"); }
__device__ __forceinline__ uint32_t pack2(float lo, float hi) { uint32_t r; asm("cvt.rn.bf16x2.f32 %0, %1, %2;" : "=r"(r) : "f"(hi), "f"(lo)); return r; }
__device__ __forceinline__ uint32_t pack2_tag(float lo, float hi, uint32_t T) {
  uint32_t u = ((__float_as_uint(lo) - T + 0x10000u) & 0xFFFE0000u) + T;
  return __byte_perm(u, pack2(0.f, hi), 0x7632); }
__device__ __forceinline__ void ldsm4(uint32_t (&r)[4], uint32_t a) {
  asm volatile("ldmatrix.sync.aligned.m8n8.x4.shared.b16 {%0,%1,%2,%3}, [%4];" : "=r"(r[0]), "=r"(r[1]), "=r"(r[2]), "=r"(r[3]) : "r"(a) : "memory"); }
__device__ __forceinline__ void ldsm4t(uint32_t (&r)[4], uint32_t a) {
  asm volatile("ldmatrix.sync.aligned.m8n8.x4.trans.shared.b16 {%0,%1,%2,%3}, [%4];" : "=r"(r[0]), "=r"(r[1]), "=r"(r[2]), "=r"(r[3]) : "r"(a) : "memory"); }
__device__ __forceinline__ void stsm4(uint32_t a, uint32_t r0, uint32_t r1, uint32_t r2, uint32_t r3) {
  asm volatile("stmatrix.sync.aligned.m8n8.x4.shared.b16 [%0], {%1,%2,%3,%4};" :: "r"(a), "r"(r0), "r"(r1), "r"(r2), "r"(r3) : "memory"); }
__device__ __forceinline__ void stsm4t(uint32_t a, uint32_t r0, uint32_t r1, uint32_t r2, uint32_t r3) {
  asm volatile("stmatrix.sync.aligned.m8n8.x4.trans.shared.b16 [%0], {%1,%2,%3,%4};" :: "r"(a), "r"(r0), "r"(r1), "r"(r2), "r"(r3) : "memory"); }
__device__ __forceinline__ void lds128(uint32_t (&r)[4], uint32_t a) {
  asm volatile("ld.shared.v4.u32 {%0,%1,%2,%3}, [%4];" : "=r"(r[0]), "=r"(r[1]), "=r"(r[2]), "=r"(r[3]) : "r"(a) : "memory"); }
__device__ __forceinline__ float4 lds128f(uint32_t a) { float4 r;
  asm volatile("ld.shared.v4.f32 {%0,%1,%2,%3}, [%4];" : "=f"(r.x), "=f"(r.y), "=f"(r.z), "=f"(r.w) : "r"(a) : "memory"); return r; }
__device__ __forceinline__ float2 lds64f(uint32_t a) { float2 r;
  asm volatile("ld.shared.v2.f32 {%0,%1}, [%2];" : "=f"(r.x), "=f"(r.y) : "r"(a) : "memory"); return r; }
__device__ __forceinline__ void sts128(uint32_t a, uint32_t r0, uint32_t r1, uint32_t r2, uint32_t r3) {
  asm volatile("st.shared.v4.u32 [%0], {%1,%2,%3,%4};" :: "r"(a), "r"(r0), "r"(r1), "r"(r2), "r"(r3) : "memory"); }
__device__ __forceinline__ void sts64f(uint32_t a, float x, float y) { asm volatile("st.shared.v2.f32 [%0], {%1,%2};" :: "r"(a), "f"(x), "f"(y) : "memory"); }
__device__ __forceinline__ void sts32f(uint32_t a, float x) { asm volatile("st.shared.f32 [%0], %1;" :: "r"(a), "f"(x) : "memory"); }
__device__ __forceinline__ void mma16816(float (&d)[4], uint32_t a0, uint32_t a1, uint32_t a2, uint32_t a3, uint32_t b0, uint32_t b1) {
  asm volatile("mma.sync.aligned.m16n8k16.row.col.f32.bf16.bf16.f32 {%0,%1,%2,%3}, {%4,%5,%6,%7}, {%8,%9}, {%0,%1,%2,%3};"
    : "+f"(d[0]), "+f"(d[1]), "+f"(d[2]), "+f"(d[3]) : "r"(a0), "r"(a1), "r"(a2), "r"(a3), "r"(b0), "r"(b1)); }
__device__ __forceinline__ void mma1688(float (&d)[4], uint32_t a0, uint32_t a1, uint32_t b0) {
  asm volatile("mma.sync.aligned.m16n8k8.row.col.f32.bf16.bf16.f32 {%0,%1,%2,%3}, {%4,%5}, {%6}, {%0,%1,%2,%3};"
    : "+f"(d[0]), "+f"(d[1]), "+f"(d[2]), "+f"(d[3]) : "r"(a0), "r"(a1), "r"(b0)); }
__device__ __forceinline__ void ldx128(uint32_t (&r)[4], const void* p) {
  asm volatile("{.reg .b128 t; .reg .b64 a, b; ld.relaxed.gpu.global.b128 t, [%4]; mov.b128 {a, b}, t; mov.b64 {%0,%1}, a; mov.b64 {%2,%3}, b;}"
    : "=r"(r[0]), "=r"(r[1]), "=r"(r[2]), "=r"(r[3]) : "l"(p) : "memory"); }
__device__ __forceinline__ void ldx2x64(uint32_t (&r)[4], const void* p) {
  asm volatile("{.reg .b64 a, b; ld.relaxed.gpu.global.v2.b64 {a, b}, [%4]; mov.b64 {%0,%1}, a; mov.b64 {%2,%3}, b;}"
    : "=r"(r[0]), "=r"(r[1]), "=r"(r[2]), "=r"(r[3]) : "l"(p) : "memory"); }
__device__ __forceinline__ void stx128(void* p, uint32_t r0, uint32_t r1, uint32_t r2, uint32_t r3) {
  asm volatile("{.reg .b128 t; .reg .b64 a, b; mov.b64 a, {%1,%2}; mov.b64 b, {%3,%4}; mov.b128 t, {a, b}; st.relaxed.gpu.global.b128 [%0], t;}"
    :: "l"(p), "r"(r0), "r"(r1), "r"(r2), "r"(r3) : "memory"); }
__device__ __forceinline__ void stx64(void* p, uint32_t r0, uint32_t r1) {
  asm volatile("{.reg .b64 a; mov.b64 a, {%1,%2}; st.relaxed.gpu.global.b64 [%0], a;}" :: "l"(p), "r"(r0), "r"(r1) : "memory"); }
__device__ __forceinline__ uint32_t uni(uint32_t x) { return __shfl_sync(0xffffffffu, x, 0); }
__device__ __forceinline__ uint32_t pin(uint32_t x) { return __shfl_xor_sync(0xffffffffu, x, 0); }
__device__ __forceinline__ float ex2(float x) { float r; asm("ex2.approx.ftz.f32 %0, %1;" : "=f"(r) : "f"(x)); return r; }
__device__ __forceinline__ void wg_fence() { asm volatile("wgmma.fence.sync.aligned;" ::: "memory"); }
__device__ __forceinline__ void wg_commit() { asm volatile("wgmma.commit_group.sync.aligned;" ::: "memory"); }
template <int N> __device__ __forceinline__ void wg_wait() { asm volatile("wgmma.wait_group.sync.aligned %0;" :: "n"(N) : "memory"); }

__device__ __forceinline__ void wgmma_ss_n256_tb1(float (&d)[128], uint64_t da, uint64_t db, int sc) {
  asm volatile("{.reg .pred p; setp.ne.b32 p, %130, 0;\n"
    "wgmma.mma_async.sync.aligned.m64n256k16.f32.bf16.bf16 {%0,%1,%2,%3,%4,%5,%6,%7,%8,%9,%10,%11,%12,%13,%14,%15,%16,%17,%18,%19,%20,%21,%22,%23,%24,%25,%26,%27,%28,%29,%30,%31,%32,%33,%34,%35,%36,%37,%38,%39,%40,%41,%42,%43,%44,%45,%46,%47,%48,%49,%50,%51,%52,%53,%54,%55,%56,%57,%58,%59,%60,%61,%62,%63,%64,%65,%66,%67,%68,%69,%70,%71,%72,%73,%74,%75,%76,%77,%78,%79,%80,%81,%82,%83,%84,%85,%86,%87,%88,%89,%90,%91,%92,%93,%94,%95,%96,%97,%98,%99,%100,%101,%102,%103,%104,%105,%106,%107,%108,%109,%110,%111,%112,%113,%114,%115,%116,%117,%118,%119,%120,%121,%122,%123,%124,%125,%126,%127}, %128, %129, p, 1, 1, 0, 1;}\n"
    : "+f"(d[0]),"+f"(d[1]),"+f"(d[2]),"+f"(d[3]),"+f"(d[4]),"+f"(d[5]),"+f"(d[6]),"+f"(d[7]),"+f"(d[8]),"+f"(d[9]),"+f"(d[10]),"+f"(d[11]),"+f"(d[12]),"+f"(d[13]),"+f"(d[14]),"+f"(d[15]),"+f"(d[16]),"+f"(d[17]),"+f"(d[18]),"+f"(d[19]),"+f"(d[20]),"+f"(d[21]),"+f"(d[22]),"+f"(d[23]),"+f"(d[24]),"+f"(d[25]),"+f"(d[26]),"+f"(d[27]),"+f"(d[28]),"+f"(d[29]),"+f"(d[30]),"+f"(d[31]),"+f"(d[32]),"+f"(d[33]),"+f"(d[34]),"+f"(d[35]),"+f"(d[36]),"+f"(d[37]),"+f"(d[38]),"+f"(d[39]),"+f"(d[40]),"+f"(d[41]),"+f"(d[42]),"+f"(d[43]),"+f"(d[44]),"+f"(d[45]),"+f"(d[46]),"+f"(d[47]),"+f"(d[48]),"+f"(d[49]),"+f"(d[50]),"+f"(d[51]),"+f"(d[52]),"+f"(d[53]),"+f"(d[54]),"+f"(d[55]),"+f"(d[56]),"+f"(d[57]),"+f"(d[58]),"+f"(d[59]),"+f"(d[60]),"+f"(d[61]),"+f"(d[62]),"+f"(d[63]),"+f"(d[64]),"+f"(d[65]),"+f"(d[66]),"+f"(d[67]),"+f"(d[68]),"+f"(d[69]),"+f"(d[70]),"+f"(d[71]),"+f"(d[72]),"+f"(d[73]),"+f"(d[74]),"+f"(d[75]),"+f"(d[76]),"+f"(d[77]),"+f"(d[78]),"+f"(d[79]),"+f"(d[80]),"+f"(d[81]),"+f"(d[82]),"+f"(d[83]),"+f"(d[84]),"+f"(d[85]),"+f"(d[86]),"+f"(d[87]),"+f"(d[88]),"+f"(d[89]),"+f"(d[90]),"+f"(d[91]),"+f"(d[92]),"+f"(d[93]),"+f"(d[94]),"+f"(d[95]),"+f"(d[96]),"+f"(d[97]),"+f"(d[98]),"+f"(d[99]),"+f"(d[100]),"+f"(d[101]),"+f"(d[102]),"+f"(d[103]),"+f"(d[104]),"+f"(d[105]),"+f"(d[106]),"+f"(d[107]),"+f"(d[108]),"+f"(d[109]),"+f"(d[110]),"+f"(d[111]),"+f"(d[112]),"+f"(d[113]),"+f"(d[114]),"+f"(d[115]),"+f"(d[116]),"+f"(d[117]),"+f"(d[118]),"+f"(d[119]),"+f"(d[120]),"+f"(d[121]),"+f"(d[122]),"+f"(d[123]),"+f"(d[124]),"+f"(d[125]),"+f"(d[126]),"+f"(d[127])
    : "l"(da), "l"(db), "r"(sc));
}

__device__ __forceinline__ void wgmma_ss_n128_tb1(float (&d)[64], uint64_t da, uint64_t db, int sc) {
  asm volatile("{.reg .pred p; setp.ne.b32 p, %66, 0;\n"
    "wgmma.mma_async.sync.aligned.m64n128k16.f32.bf16.bf16 {%0,%1,%2,%3,%4,%5,%6,%7,%8,%9,%10,%11,%12,%13,%14,%15,%16,%17,%18,%19,%20,%21,%22,%23,%24,%25,%26,%27,%28,%29,%30,%31,%32,%33,%34,%35,%36,%37,%38,%39,%40,%41,%42,%43,%44,%45,%46,%47,%48,%49,%50,%51,%52,%53,%54,%55,%56,%57,%58,%59,%60,%61,%62,%63}, %64, %65, p, 1, 1, 0, 1;}\n"
    : "+f"(d[0]),"+f"(d[1]),"+f"(d[2]),"+f"(d[3]),"+f"(d[4]),"+f"(d[5]),"+f"(d[6]),"+f"(d[7]),"+f"(d[8]),"+f"(d[9]),"+f"(d[10]),"+f"(d[11]),"+f"(d[12]),"+f"(d[13]),"+f"(d[14]),"+f"(d[15]),"+f"(d[16]),"+f"(d[17]),"+f"(d[18]),"+f"(d[19]),"+f"(d[20]),"+f"(d[21]),"+f"(d[22]),"+f"(d[23]),"+f"(d[24]),"+f"(d[25]),"+f"(d[26]),"+f"(d[27]),"+f"(d[28]),"+f"(d[29]),"+f"(d[30]),"+f"(d[31]),"+f"(d[32]),"+f"(d[33]),"+f"(d[34]),"+f"(d[35]),"+f"(d[36]),"+f"(d[37]),"+f"(d[38]),"+f"(d[39]),"+f"(d[40]),"+f"(d[41]),"+f"(d[42]),"+f"(d[43]),"+f"(d[44]),"+f"(d[45]),"+f"(d[46]),"+f"(d[47]),"+f"(d[48]),"+f"(d[49]),"+f"(d[50]),"+f"(d[51]),"+f"(d[52]),"+f"(d[53]),"+f"(d[54]),"+f"(d[55]),"+f"(d[56]),"+f"(d[57]),"+f"(d[58]),"+f"(d[59]),"+f"(d[60]),"+f"(d[61]),"+f"(d[62]),"+f"(d[63])
    : "l"(da), "l"(db), "r"(sc));
}

template <int BN> struct WG;
template <> struct WG<256> { static __device__ __forceinline__ void mma(float (&d)[128], uint64_t a, uint64_t b, int sc) { wgmma_ss_n256_tb1(d, a, b, sc); } };
template <> struct WG<128> { static __device__ __forceinline__ void mma(float (&d)[64], uint64_t a, uint64_t b, int sc) { wgmma_ss_n128_tb1(d, a, b, sc); } };

struct GemmMaps { CUtensorMap a, b[3], c; };
template <int BN, int STAGES>
__global__ void __cluster_dims__(2, 1, 1) __launch_bounds__(384, 1)
gemm_kernel(const __grid_constant__ GemmMaps maps, int tilesM, int tilesN, int kblocks, int nPerB, int clearX) {
  extern __shared__ __align__(1024) uint8_t smem_raw[];
  constexpr int STAGE_BYTES = 16384 + BN * 128;
  constexpr int NBOX = BN / 64;
  const uint32_t sbase = (smem_u32(smem_raw) + 1023) & ~1023u;
  const uint32_t sEpi = sbase + STAGES * STAGE_BYTES;
  const uint32_t sBar = sEpi + 32768;
  const int warp = threadIdx.x >> 5, lane = threadIdx.x & 31, wg = warp >> 2;
  uint32_t crank; asm("mov.u32 %0, %%cluster_ctarank;" : "=r"(crank));
  if (threadIdx.x == 0) {
    for (int i = 0; i < STAGES; i++) { mbar_init(sBar + 8 * i, 1); mbar_init(sBar + 8 * (STAGES + i), 4); }
    asm volatile("fence.mbarrier_init.release.cluster;" ::: "memory");
  }
  if (clearX) {
    uint4* p = reinterpret_cast<uint4*>(&g_x);
    for (int i = blockIdx.x * 384 + threadIdx.x; i < (int)(sizeof(Xchg) / 16); i += gridDim.x * 384) p[i] = make_uint4(0, 0, 0, 0);
  }
  asm volatile("barrier.cluster.arrive.release.aligned; barrier.cluster.wait.acquire.aligned;" ::: "memory");
  const int npairs = (tilesM >> 1) * tilesN, pair0 = blockIdx.x >> 1, pstep = gridDim.x >> 1;
  if (wg == 2) {
    asm volatile("setmaxnreg.dec.sync.aligned.u32 40;");
    if (warp == 8 && lane == 0) {
      int st = 0, ph = 1;
      for (int p = pair0; p < npairs; p += pstep) {
        const int tm = (p % (tilesM >> 1)) * 2 + crank, tn = p / (tilesM >> 1);
        const CUtensorMap* mb = &maps.b[tn / nPerB];
        const int n0 = (tn % nPerB) * BN;
        for (int kb = 0; kb < kblocks; kb++) {
          mbar_wait(sBar + 8 * (STAGES + st), ph);
          const uint32_t a = sbase + st * STAGE_BYTES, full = sBar + 8 * st;
          mbar_expect_tx(full, STAGE_BYTES);
          tma2d(a, &maps.a, kb * 64, tm * 128, full);
#pragma unroll
          for (int i = 0; i < NBOX / 2; i++) {
            const int bx = crank * (NBOX / 2) + i;
            tma2d_mc(a + 16384 + bx * 8192, mb, n0 + bx * 64, kb * 64, full, (uint16_t)3);
          }
          if (++st == STAGES) { st = 0; ph ^= 1; }
        }
      }
      for (int i = 0; i < STAGES; i++) { mbar_wait(sBar + 8 * (STAGES + st), ph); if (++st == STAGES) { st = 0; ph ^= 1; } }
    }
  } else {
    asm volatile("setmaxnreg.inc.sync.aligned.u32 232;");
    int st = 0, ph = 0;
    float acc[BN / 2];
    const uint64_t descA0 = (uint64_t)(((sbase + wg * 8192) & 0x3FFFF) >> 4) | (1ull << 16) | (64ull << 32) | (1ull << 62);
    const uint64_t descB0 = (uint64_t)(((sbase + 16384) & 0x3FFFF) >> 4) | (512ull << 16) | (64ull << 32) | (1ull << 62);
    const uint32_t epi = sEpi + wg * 16384;
    for (int p = pair0; p < npairs; p += pstep) {
      const int tm = (p % (tilesM >> 1)) * 2 + crank, tn = p / (tilesM >> 1);
      int prev = -1;
      for (int kb = 0; kb < kblocks; kb++) {
        mbar_wait(sBar + 8 * st, ph);
        wg_fence();
        const uint64_t so = (uint64_t)(st * (STAGE_BYTES >> 4));
#pragma unroll
        for (int k = 0; k < 4; k++) WG<BN>::mma(acc, descA0 + so + k * 2, descB0 + so + k * 128, kb | k);
        wg_commit();
        if (prev >= 0) {
          wg_wait<1>();
          if ((threadIdx.x & 127) < 2) mbar_arrive_cluster(sBar + 8 * (STAGES + prev), threadIdx.x & 1);
        }
        prev = st;
        if (++st == STAGES) { st = 0; ph ^= 1; }
      }
      wg_wait<0>();
      if ((threadIdx.x & 127) < 2) mbar_arrive_cluster(sBar + 8 * (STAGES + prev), threadIdx.x & 1);
#pragma unroll
      for (int r = 0; r < BN / 128; r++) {
        if ((threadIdx.x & 127) == 0) asm volatile("cp.async.bulk.wait_group.read 0;" ::: "memory");
        bar_sync(1 + wg, 128);
        const int row = (warp & 3) * 16 + (lane & 15);
#pragma unroll
        for (int i = 0; i < 8; i++) {
          const int c = 2 * (i & 3) + (lane >> 4);
          const float* q = &acc[r * 64 + i * 8];
          stsm4(epi + (i >> 2) * 8192 + row * 128 + ((c ^ (row & 7)) << 4), pack2(q[0], q[1]), pack2(q[2], q[3]), pack2(q[4], q[5]), pack2(q[6], q[7]));
        }
        fence_async();
        bar_sync(1 + wg, 128);
        if ((threadIdx.x & 127) == 0) {
          tma2d_store(&maps.c, epi, tn * BN + r * 128, tm * 128 + wg * 64);
          tma2d_store(&maps.c, epi + 8192, tn * BN + r * 128 + 64, tm * 128 + wg * 64);
          asm volatile("cp.async.bulk.commit_group;" ::: "memory");
        }
      }
    }
    if ((threadIdx.x & 127) == 0) asm volatile("cp.async.bulk.wait_group 0;" ::: "memory");
  }
}

struct Dft { uint32_t m[2][2][2][4]; };
template <bool P4> __device__ __forceinline__ int fidx(int tile, int x) { return P4 ? 4 * (x >> 1) + 2 * (tile & 1) + (x & 1) + 16 * (tile >> 1) : x + 8 * tile; }
__device__ __forceinline__ float2 cis(int k, int n) {
  k &= n - 1; if (2 * k > n) k -= n;
  const float a = (float)k * (6.283185307179586f / (float)n);
  return make_float2(__cosf(a), __sinf(a));
}
template <bool OUT4> __device__ __forceinline__ void make_dft(Dft& D, int g, int t) {
#pragma unroll
  for (int q = 0; q < 16; q++) {
    const int b = q >> 3, u = (q >> 2) & 1, r = (q >> 1) & 1, v = q & 1;
    const float2 w = cis(fidx<OUT4>(v, g) * fidx<false>(2 * u + r, 2 * t + b), 32);
    D.m[b][u][0][q & 3] = pack2(w.x, w.y); D.m[b][u][1][q & 3] = pack2(-w.y, w.x);
  }
}
__device__ __forceinline__ void mma_dc(float (&d)[4], uint32_t a0, uint32_t a1, uint32_t a2, uint32_t a3, uint32_t b0, uint32_t b1, const float (&c)[4]) {
  asm("mma.sync.aligned.m16n8k16.row.col.f32.bf16.bf16.f32 {%0,%1,%2,%3}, {%4,%5,%6,%7}, {%8,%9}, {%10,%11,%12,%13};"
    : "=f"(d[0]), "=f"(d[1]), "=f"(d[2]), "=f"(d[3]) : "r"(a0), "r"(a1), "r"(a2), "r"(a3), "r"(b0), "r"(b1), "f"(c[0]), "f"(c[1]), "f"(c[2]), "f"(c[3])); }
__device__ __forceinline__ void dft_b(const Dft& D, const uint32_t (&x)[2][4], float (&o)[2][8]) {
#pragma unroll
  for (int ri = 0; ri < 2; ri++) {
    float z[4] = {0.f, 0.f, 0.f, 0.f}, e[4], p[4];
    mma_dc(e, D.m[0][0][ri][0], D.m[0][0][ri][1], D.m[0][0][ri][2], D.m[0][0][ri][3], x[0][0], x[0][1], z);
    mma_dc(e, D.m[0][1][ri][0], D.m[0][1][ri][1], D.m[0][1][ri][2], D.m[0][1][ri][3], x[0][2], x[0][3], e);
    mma_dc(p, D.m[1][0][ri][0], D.m[1][0][ri][1], D.m[1][0][ri][2], D.m[1][0][ri][3], x[1][0], x[1][1], e);
    mma_dc(p, D.m[1][1][ri][0], D.m[1][1][ri][1], D.m[1][1][ri][2], D.m[1][1][ri][3], x[1][2], x[1][3], p);
#pragma unroll
    for (int q = 0; q < 4; q++) { o[ri][q] = p[q]; o[ri][4 + q] = fmaf(2.f, e[q], -p[q]); }
  }
}
__device__ __forceinline__ void dft_a(const uint32_t (&m)[2][2][4], const uint32_t (&x0)[2][4], const uint32_t (&x1)[2][4], float (&o)[2][8]) {
#pragma unroll
  for (int ri = 0; ri < 2; ri++) {
    float z[4] = {0.f, 0.f, 0.f, 0.f}, e[4], p[4];
    mma_dc(e, x0[0][0], x1[0][0], x0[0][1], x1[0][1], m[0][ri][0], m[0][ri][1], z);
    mma_dc(e, x0[0][2], x1[0][2], x0[0][3], x1[0][3], m[0][ri][2], m[0][ri][3], e);
    mma_dc(p, x0[1][0], x1[1][0], x0[1][1], x1[1][1], m[1][ri][0], m[1][ri][1], e);
    mma_dc(p, x0[1][2], x1[1][2], x0[1][3], x1[1][3], m[1][ri][2], m[1][ri][3], p);
#pragma unroll
    for (int q = 0; q < 4; q++) { o[ri][q] = p[q]; o[ri][4 + q] = fmaf(2.f, e[q], -p[q]); }
  }
}
__device__ __forceinline__ uint32_t twid(float re, float im, float c, float s) { return pack2(fmaf(re, c, im * s), fmaf(im, c, -re * s)); }
__device__ __forceinline__ void cpa16(uint32_t d, const void* s) { asm volatile("cp.async.cg.shared.global [%0], [%1], 16;" :: "r"(d), "l"(s) : "memory"); }
__device__ __forceinline__ void sts32(uint32_t a, uint32_t x) { asm volatile("st.shared.u32 [%0], %1;" :: "r"(a), "r"(x) : "memory"); }
__device__ __forceinline__ void cpa_commit() { asm volatile("cp.async.commit_group;" ::: "memory"); }
template <int N> __device__ __forceinline__ void cpa_wait() { asm volatile("cp.async.wait_group %0;" :: "n"(N) : "memory"); }
__device__ __forceinline__ uint32_t lds32(uint32_t a) { uint32_t r; asm volatile("ld.shared.u32 %0, [%1];" : "=r"(r) : "r"(a) : "memory"); return r; }
constexpr int F_TP = 4112, F_TSZ = 8 * F_TP;

__device__ __forceinline__ void fft_wprep(const bf16* __restrict__ wr, const bf16* __restrict__ wi, int cta, int ncta) {
  const int tid = threadIdx.x;
#pragma unroll 2
  for (int it = cta; it < 256; it += ncta) {
    const int g = (it >> 1) & 7, c = (it >> 4) & 3, i = it >> 6, t = 2 * (it & 1) + (tid & 1);
    const int k0 = g + 8 * i + 32 * (8 * c + 2 * t), l0 = (tid & ~1) + (g & 1);
    uint32_t a[2][4], b[2][4];
#pragma unroll
    for (int q = 0; q < 8; q++) {
      const int o = (k0 + 32 * ((q >> 1) & 1) + 1024 * (q & 1)) * 513 + l0 + 256 * (q >> 2);
      a[q >> 2][q & 3] = __ldg(reinterpret_cast<const uint32_t*>(wr + o));
      b[q >> 2][q & 3] = __ldg(reinterpret_cast<const uint32_t*>(wi + o));
    }
    uint4* dst = g_wt + l0 * 512 + it * 2 + (tid & 1);
#pragma unroll
    for (int q = 0; q < 4; q++) {
      const int hf = q >> 1, l = l0 + 256 * hf + (q & 1);
      const uint32_t sel = (q & 1) ? 0x7632 : 0x5410;
      if (l & 511) dst[(256 * hf + (q & 1)) * 512] = make_uint4(__byte_perm(a[hf][0], b[hf][0], sel), __byte_perm(a[hf][1], b[hf][1], sel),
                                                              __byte_perm(a[hf][2], b[hf][2], sel), __byte_perm(a[hf][3], b[hf][3], sel));
    }
  }
  for (int e = cta * 256 + tid; e < 4096; e += ncta * 256) {
    const int l = (e >> 11) * 512, k = e & 2047, kn = (2048 - k) & 2047, k2 = (k >> 5) & 31;
    const float re = 0.5f * (__bfloat162float(wr[k * 513 + l]) + __bfloat162float(wr[kn * 513 + l]));
    const float im = 0.5f * (__bfloat162float(wi[k * 513 + l]) - __bfloat162float(wi[kn * 513 + l]));
    reinterpret_cast<uint32_t*>(g_wt)[(64 * ((k >> 3) & 3) + 16 * (k2 >> 3) + 2 * (k & 7) + ((k2 >> 2) & 1)) * 8 + l * 2048 + 2 * (k2 & 3) + (k >> 10)] = pack2(re, im);
  }
}

__device__ __forceinline__ void fft_rows_fwd(const bf16* __restrict__ x, uint32_t sb, int cta, int ncta) {
  const int warp = threadIdx.x >> 5, lane = threadIdx.x & 31, g = lane >> 2, t = lane & 3;
  const uint32_t in = sb + warp * 8192, tb = sb + 65536;
  const uint32_t f0 = pin(in + (lane >> 3) * 256 + (((lane & 7) ^ (2 * (lane >> 3))) << 4));
  const uint32_t xo = pin((256 * (warp & 3) + 64 * (warp >> 2)) * 2048 + lane * 8);
  auto fetch = [&](int it, int buf) {
    const bf16* src = x + (xo + (128 * (it & 1) + 32 * ((it >> 4) & 1) + 8 * (it >> 5) + ((it >> 1) & 7)) * 2048);
#pragma unroll
    for (int q = 0; q < 8; q++) cpa16(((f0 + buf * 4096) ^ ((q >> 2) * 144)) + (q & 3) * 1024, src + q * 256);
    cpa_commit();
  };
  fetch(cta, 0);
  Dft D; make_dft<true>(D, g, t);
  float2 tw[4][8];
#pragma unroll
  for (int q = 0; q < 32; q++) tw[q >> 3][q & 7] = cis(fidx<true>((q >> 1) & 3, g) * fidx<false>(q >> 3, 2 * t + (q & 1)), 1024);
  const uint32_t la = pin(in + lane * 128 + ((lane & 7) << 4));
  const uint32_t wa = pin(tb + warp * F_TP + fidx<true>(0, g) * 128 + t * 16), wz = pin((g & 1) ? -64 : 64);
  const uint32_t ra = pin(tb + (lane & 1) * 4 * F_TP + ((lane >> 1) + 16 * (warp ^ ((warp >> 1) & 1))) * 4);
  uint4* dst = g_y + (threadIdx.x >> 1) * 256 + (lane & 1);
  int buf = 0;
  auto drain = [&](int it, int q) {
    const uint32_t r = ra + (buf ^ 1) * F_TSZ + q * 512;
    const uint4 v = make_uint4(lds32(r), lds32(r + F_TP), lds32(r + 2 * F_TP), lds32(r + 3 * F_TP));
    if (it >= 0) dst[it * 2 + q * 32768] = v;
  };
  int it = cta;
#pragma unroll 1
  for (; it < 128; it += ncta, buf ^= 1) {
    cpa_wait<0>(); __syncthreads();
    uint32_t a[4][2][4], y[4][2][4];
#pragma unroll
    for (int q = 0; q < 8; q++) ldsm4t(a[q & 3][q >> 2], (la + buf * 4096) ^ (q << 4));
    if (it + ncta < 128) fetch(it + ncta, buf ^ 1);
    float o[2][8];
#pragma unroll
    for (int i = 0; i < 4; i++) {
      dft_b(D, a[i], o);
      drain(it - ncta, i);
#pragma unroll
      for (int q = 0; q < 8; q++) y[q >> 1][q & 1][i] = twid(o[0][q], o[1][q], tw[i][q].x, tw[i][q].y);
    }
    const uint32_t w0 = wa + buf * F_TSZ + ((g & 1) << 6);
#pragma unroll
    for (int z = 0; z < 2; z++) {
      float o2[2][8];
      dft_b(D, y[2 * z], o); drain(it - ncta, 4 + 2 * z); dft_b(D, y[2 * z + 1], o2); drain(it - ncta, 5 + 2 * z);
#pragma unroll
      for (int i = 0; i < 4; i++) {
        const float sg = i < 2 ? 1.f : -1.f;
        sts128(w0 + z * wz + fidx<true>(i, 0) * 128, pack2(o[0][2 * i], sg * o[1][2 * i]), pack2(o[0][2 * i + 1], sg * o[1][2 * i + 1]),
               pack2(o2[0][2 * i], sg * o2[1][2 * i]), pack2(o2[0][2 * i + 1], sg * o2[1][2 * i + 1]));
      }
    }
  }
  __syncthreads();
#pragma unroll
  for (int q = 0; q < 8; q++) drain(it - ncta, q);
}

__device__ __forceinline__ void fft_cols(uint32_t sb, int cta, int ncta) {
  const int warp = threadIdx.x >> 5, lane = threadIdx.x & 31, g = lane >> 2, t = lane & 3;
  const uint32_t in = sb + warp * 16384 + lane * 16, tab = sb + 131072 + lane * 16;
  auto fetch_y = [&](int l) {
#pragma unroll
    for (int q = 0; q < 16; q++) cpa16(in + q * 512, g_y + (q < 8 ? l : (1024 - l) & 1023) * 256 + (q & 7) * 32 + lane);
  };
  auto fetch_w = [&](int l) {
#pragma unroll
    for (int q = 0; q < 16; q++) cpa16(in + 8192 + q * 512, g_wt + l * 512 + q * 32 + lane);
  };
  const int l0 = cta * 8 + warp, dl = ncta * 8;
  if (l0 <= 512) fetch_y(l0);
  cpa_commit();
  if (l0 <= 512) fetch_w(l0);
  cpa_commit();
  Dft D; make_dft<false>(D, g, t);
#pragma unroll
  for (int q = 2 * warp; q < 2 * warp + 2; q++) {
    const int r = fidx<false>(q & 3, g), c = fidx<false>(q >> 2, 2 * t);
    const float2 w0 = cis(r * c, 1024), w1 = cis(r * c + r, 1024), p0 = cis(r + 32 * c, 2048), p1 = cis(r + 32 * c + 32, 2048);
    sts128(tab + q * 512, __float_as_uint(w0.x), __float_as_uint(w0.y), __float_as_uint(w1.x), __float_as_uint(w1.y));
    sts128(tab + 8192 + q * 512, __float_as_uint(p0.x), __float_as_uint(p0.y), __float_as_uint(p1.x), __float_as_uint(p1.y));
  }
  if (warp == 0) {
#pragma unroll
    for (int q = 0; q < 8; q++) {
      const int v = q >> 2, b = (q >> 1) & 1, ri = q & 1;
      sts128(tab + 16384 + q * 512, D.m[b][0][ri][v], D.m[b][0][ri][v + 2], D.m[b][1][ri][v], D.m[b][1][ri][v + 2]);
    }
  }
  __syncthreads();
#pragma unroll 1
  for (int l = l0; l <= 512; l += dl) {
    uint32_t a[2][4][2][4], y[2][4][2][4];
    float o[2][2][8];
    cpa_wait<1>();
#pragma unroll
    for (int q = 0; q < 16; q++) lds128(a[q >> 3][(q >> 1) & 3][q & 1], in + q * 512);
    if (!(l & 511)) {
      const uint32_t m0 = l ? 0x80000000u : 0u;
#pragma unroll
      for (int q = 0; q < 32; q++) { a[0][q >> 3][(q >> 2) & 1][q & 3] ^= m0; a[1][q >> 3][(q >> 2) & 1][q & 3] ^= m0 ^ 0x80000000u; }
    }
    auto first = [&]() {
#pragma unroll
      for (int i = 0; i < 4; i++) {
        dft_b(D, a[0][i], o[0]); dft_b(D, a[1][i], o[1]);
#pragma unroll
        for (int r = 0; r < 4; r++) {
          const float4 w = lds128f(tab + (4 * i + r) * 512);
#pragma unroll
          for (int s = 0; s < 2; s++) {
            y[s][r][0][i] = twid(o[s][0][2 * r], o[s][1][2 * r], w.x, w.y);
            y[s][r][1][i] = twid(o[s][0][2 * r + 1], o[s][1][2 * r + 1], w.z, w.w);
          }
        }
      }
    };
    first();
    if (l + dl <= 512) fetch_y(l + dl);
    cpa_commit();
    cpa_wait<1>();
#pragma unroll
    for (int zv = 0; zv < 4; zv++) {
      const int z = zv >> 1, v = zv & 1;
      uint32_t m[2][2][4];
#pragma unroll
      for (int q = 0; q < 4; q++) lds128(m[q >> 1][q & 1], tab + 16384 + (4 * v + q) * 512);
      dft_a(m, y[0][2 * z], y[0][2 * z + 1], o[0]); dft_a(m, y[1][2 * z], y[1][2 * z + 1], o[1]);
#pragma unroll
      for (int q = 0; q < 4; q++) {
        const int i = 2 * z + (q & 1), c = v + (q & 2);
        uint32_t w[4]; lds128(w, in + 8192 + (4 * i + c) * 512);
        const float4 ph = lds128f(tab + 8192 + (4 * c + i) * 512);
#pragma unroll
        for (int b = 0; b < 2; b++) {
          const float cs = b ? ph.z : ph.x, sn = b ? ph.w : ph.y;
          const float r1 = __uint_as_float(w[2 * b] << 16), i1 = __uint_as_float(w[2 * b] & 0xFFFF0000u);
          const float r2 = __uint_as_float(w[2 * b + 1] << 16), i2 = __uint_as_float(w[2 * b + 1] & 0xFFFF0000u);
          const float Sr = r1 + r2, Si = i1 + i2, Dr = r1 - r2, Di = i1 - i2;
          const float ar = fmaf(-Dr, sn, Sr), ai = fmaf(-Di, sn, Si), dr = fmaf(Dr, sn, Sr), di = fmaf(Di, sn, Si), br = -Di * cs, bi = Dr * cs;
          const float Ar = o[0][0][2 * q + b], Ai = o[0][1][2 * q + b], Br = o[1][0][2 * q + b], Bi = o[1][1][2 * q + b];
          a[0][i][b][c] = pack2(fmaf(ar, Ai, fmaf(ai, Ar, fmaf(br, Bi, bi * Br))), fmaf(ar, Ar, fmaf(-ai, Ai, fmaf(br, Br, -bi * Bi))));
          a[1][i][b][c] = pack2(fmaf(dr, Bi, fmaf(di, Br, fmaf(-br, Ai, -bi * Ar))), fmaf(dr, Br, fmaf(-di, Bi, fmaf(-br, Ar, bi * Ai))));
        }
      }
    }
    if (l + dl <= 512) fetch_w(l + dl);
    cpa_commit();
    first();
#pragma unroll
    for (int s = 0; s < 2; s++) {
      uint4* dst = g_y + (s ? (1024 - l) & 1023 : l) * 256 + lane;
      const float sg = s ? -1.f : 1.f;
#pragma unroll
      for (int i = 0; i < 4; i++) {
        dft_b(D, y[s][i], o[0]);
#pragma unroll
        for (int b = 0; b < 2; b++)
          dst[(2 * i + b) * 32] = make_uint4(pack2(sg * o[0][0][b], o[0][1][b]), pack2(sg * o[0][0][2 + b], o[0][1][2 + b]),
                                             pack2(sg * o[0][0][4 + b], o[0][1][4 + b]), pack2(sg * o[0][0][6 + b], o[0][1][6 + b]));
      }
    }
  }
}

__device__ __forceinline__ void fft_rows_inv(const CUtensorMap* om, uint32_t sb, int cta, int ncta) {
  const int warp = threadIdx.x >> 5, lane = threadIdx.x & 31, g = lane >> 2, t = lane & 3, wg = warp >> 2, w4 = warp & 3;
  const uint32_t tb = sb + 32768 + wg * 2 * F_TSZ;
  const uint4* src = g_y + pin((256 * ((lane >> 1) & 3) + 64 * (lane >> 3) + 8 * w4) * 256 + (lane & 1));
  const uint32_t wa = pin(tb + (lane & 1) * 4 * F_TP + w4 * 1024 + (lane >> 1) * 4);
  uint4 pf[8];
  auto fetch = [&](int it, int hf) {
#pragma unroll
    for (int q = 0; q < 8; q++) pf[q] = __ldcg(src + (it * 2 + hf * 8192) + q * 256);
  };
  auto put = [&](uint32_t off) {
#pragma unroll
    for (int q = 0; q < 8; q++) {
      sts32(wa + off + q * 64, pf[q].x); sts32(wa + off + q * 64 + F_TP, pf[q].y);
      sts32(wa + off + q * 64 + 2 * F_TP, pf[q].z); sts32(wa + off + q * 64 + 3 * F_TP, pf[q].w);
    }
  };
  const int it0 = 2 * cta + wg;
  if (it0 >= 128) return;
  fetch(it0, 0); put(0); fetch(it0, 1); put(512);
  Dft D; make_dft<false>(D, g, t);
  float2 tw[4][8];
#pragma unroll
  for (int q = 0; q < 32; q++) {
    tw[q >> 3][q & 7] = cis(fidx<false>((q >> 1) & 3, g) * fidx<false>(q >> 3, 2 * t + (q & 1)), 1024);
    tw[q >> 3][q & 7].x *= 1.f / 2097152.f; tw[q >> 3][q & 7].y *= 1.f / 2097152.f;
  }
  const uint32_t la = pin(tb + w4 * F_TP + lane * 16), ob = uni(sb + warp * 4096);
  const uint32_t oa = pin(ob + (lane >> 1) * 128 + (((4 * (lane & 1)) ^ ((lane >> 1) & 7)) << 4));
#pragma unroll 1
  for (int n = 0;; n++) {
    const int it = it0 + (n >> 1) * 2 * ncta, hf = n & 1, buf = (n >> 1) & 1;
    if (it >= 128) break;
    if (!hf) bar_sync(1 + wg, 128);
    uint32_t a[4][2][4], y[4][2][4];
#pragma unroll
    for (int q = 0; q < 8; q++) lds128(a[q >> 1][q & 1], la + buf * F_TSZ + hf * 4 * F_TP + q * 512);
    fetch(min(it + 2 * ncta, 127), hf);
    float o[2][8];
#pragma unroll
    for (int i = 0; i < 4; i++) {
      dft_b(D, a[i], o);
#pragma unroll
      for (int q = 0; q < 8; q++) y[q >> 1][q & 1][i] = twid(o[0][q], o[1][q], tw[i][q].x, tw[i][q].y);
    }
    if (lane == 0) asm volatile("cp.async.bulk.wait_group.read 0;" ::: "memory");
    __syncwarp();
#pragma unroll
    for (int c = 0; c < 4; c++) {
      dft_b(D, y[c], o);
#pragma unroll
      for (int ri = 0; ri < 2; ri++)
        stsm4((oa ^ (c << 4)) + (1 - ri) * 2048, pack2(o[ri][0], o[ri][1]), pack2(o[ri][2], o[ri][3]), pack2(o[ri][4], o[ri][5]), pack2(o[ri][6], o[ri][7]));
    }
    fence_async();
    __syncwarp();
    if (lane == 0) {
      const int m = 256 * w4 + 32 * ((it >> 1) & 7) + 8 * (it >> 5) + 4 * (it & 1) + 2 * hf + ((it >> 4) & 1);
      asm volatile("cp.async.bulk.tensor.3d.global.shared::cta.bulk_group [%0, {0, 0, %2}], [%1];" :: "l"(om), "r"(ob), "r"(2 * m) : "memory");
      asm volatile("cp.async.bulk.commit_group;" ::: "memory");
    }
    put((buf ^ 1) * F_TSZ + hf * 512);
  }
  if (lane == 0) asm volatile("cp.async.bulk.wait_group 0;" ::: "memory");
}
constexpr int F_SMEM = 65536 + 2 * F_TSZ + 1024;
__global__ void __launch_bounds__(256, 1) fft_pre_kernel(const bf16* __restrict__ x, const bf16* __restrict__ wr, const bf16* __restrict__ wi) {
  extern __shared__ __align__(1024) uint8_t smem_raw[];
  const uint32_t sb = (smem_u32(smem_raw) + 1023) & ~1023u;
  fft_wprep(wr, wi, blockIdx.x, gridDim.x);
  fft_rows_fwd(x, sb, blockIdx.x, gridDim.x);
}
__device__ __forceinline__ void grid_arrive(unsigned* ctr) {
  __syncthreads();
  if (threadIdx.x == 0) { __threadfence(); atomicAdd(ctr, 1u); }
}
__device__ __forceinline__ void grid_wait(unsigned* ctr, unsigned n) {
  if (threadIdx.x == 0) {
    int it = 0;
    while (*reinterpret_cast<volatile unsigned*>(ctr) < n) { __nanosleep(200); if (++it > SPIN_LIMIT) { g_err = 3; break; } }
    __threadfence();
  }
  __syncthreads();
}

struct RecMaps { CUtensorMap wq, wk, wv, wo, x, k, q, v, fo; };
#define NSW 16
#define EXP 0
#define PD1 4
#define NE4 6
#define NE6 0
#define NA4 14
#define NA6 18
#define NB1 24
#define OXPOS 28
#define KVPOS 2
#define NK0 0
#define FLPOS 1
#define XWPOS 10
#define FSPOS 28
#define RL0 4
#define RLS 6
#define RLB 4
#define VL0 3
#define RI 10
#define RJ 8
#define NPRE 0
#define UNP 16
#define XC 2
#define XD 2
#define SPOS 2
#ifndef NV0
#define NV0 1
#endif
#define TGP 3
#define FENP 0
#define LW0 8
#define XB 2
#define XA 4
constexpr int R_WO = 0, R_X = 65536, R_MEM = 131072, R_WC = 147456, R_RED = R_WC + NSW * 2048, R_O = R_RED + 2048, R_S = R_O + 2048, R_P = R_S + 3072, R_STAGE = R_P + 2048,
              R_K = R_STAGE + 8192, R_Q = R_K + 8192, R_V = R_Q + 2048, R_ID = R_V + 16384, R_T = R_ID + 512, R_BAR = R_T + 512, R_TS = R_BAR + 128,
              R_TOTAL = R_TS;
#define TS(i)
#define LOG(i, v)
constexpr int B_KV = R_BAR, B_W = R_BAR + 8, B_X = R_BAR + 80, B_PK = R_BAR + 24, B_C = R_BAR + 32, B_B = R_BAR + 40, B_DUE = R_BAR + 48, B_ONE = R_BAR + 64;
#define DLY_A 150
#define DLY_V 150
#define DLY_C 100
#define DLY_L 90
#define NS_B 1280
#define NS_C 1920
#define NS_P 3008
#define NS_V 128
#define NS_F (NS_B - 192)
#define NS_K 128
#define NS_M 64
#define NS_PEN 896
__device__ __forceinline__ float rcp(float x) { float r; asm("rcp.approx.ftz.f32 %0, %1;" : "=f"(r) : "f"(x)); return r; }
__device__ __forceinline__ uint32_t movm(uint32_t a) { uint32_t d; asm volatile("movmatrix.sync.aligned.m8n8.trans.b16 %0, %1;" : "=r"(d) : "r"(a)); return d; }
__device__ __forceinline__ uint32_t hadd2(uint32_t a, uint32_t b) { uint32_t d; asm("add.rn.bf16x2 %0, %1, %2;" : "=r"(d) : "r"(a), "r"(b)); return d; }
__device__ __forceinline__ void mma_a(float (&d)[4], const uint32_t (&a)[4], uint32_t b0, uint32_t b1) { mma16816(d, a[0], a[1], a[2], a[3], b0, b1); }
__device__ __forceinline__ bool elect() {
  uint32_t p; asm volatile("{.reg .pred p; elect.sync _|p, 0xffffffff; selp.u32 %0, 1, 0, p;}" : "=r"(p)); return p; }
__device__ __forceinline__ void tma3d(uint32_t dst, const CUtensorMap* m, int c1, int c2, uint32_t bar) {
  asm volatile("cp.async.bulk.tensor.3d.shared::cluster.global.mbarrier::complete_tx::bytes [%0], [%1, {0, %3, %4}], [%2];"
    :: "r"(dst), "l"(m), "r"(bar), "r"(c1), "r"(c2) : "memory"); }
__device__ __forceinline__ void tma4d(uint32_t dst, const CUtensorMap* m, int c1, int c2, uint32_t bar) {
  asm volatile("cp.async.bulk.tensor.4d.shared::cluster.global.mbarrier::complete_tx::bytes [%0], [%1, {0, %3, %4, 0}], [%2];"
    :: "r"(dst), "l"(m), "r"(bar), "r"(c1), "r"(c2) : "memory"); }
template <int OFF, int ACC>
__device__ __forceinline__ void wg_rs32(float (&d)[16], const uint32_t (&a)[4], uint32_t db) {
  if (ACC)
    asm volatile("{.reg .b64 db; .reg .b32 lo; add.u32 lo, %20, %21; mov.b64 db, {lo, 0x40000040};\n"
      "wgmma.mma_async.sync.aligned.m64n32k16.f32.bf16.bf16 {%0,%1,%2,%3,%4,%5,%6,%7,%8,%9,%10,%11,%12,%13,%14,%15}, {%16,%17,%18,%19}, db, 1, 1, 1, 0;}"
      : "+f"(d[0]), "+f"(d[1]), "+f"(d[2]), "+f"(d[3]), "+f"(d[4]), "+f"(d[5]), "+f"(d[6]), "+f"(d[7]), "+f"(d[8]), "+f"(d[9]), "+f"(d[10]), "+f"(d[11]), "+f"(d[12]), "+f"(d[13]), "+f"(d[14]), "+f"(d[15])
      : "r"(a[0]), "r"(a[1]), "r"(a[2]), "r"(a[3]), "r"(db), "n"(OFF));
  else
    asm volatile("{.reg .b64 db; .reg .b32 lo; add.u32 lo, %20, %21; mov.b64 db, {lo, 0x40000040};\n"
      "wgmma.mma_async.sync.aligned.m64n32k16.f32.bf16.bf16 {%0,%1,%2,%3,%4,%5,%6,%7,%8,%9,%10,%11,%12,%13,%14,%15}, {%16,%17,%18,%19}, db, 0, 1, 1, 0;}"
      : "=f"(d[0]), "=f"(d[1]), "=f"(d[2]), "=f"(d[3]), "=f"(d[4]), "=f"(d[5]), "=f"(d[6]), "=f"(d[7]), "=f"(d[8]), "=f"(d[9]), "=f"(d[10]), "=f"(d[11]), "=f"(d[12]), "=f"(d[13]), "=f"(d[14]), "=f"(d[15])
      : "r"(a[0]), "r"(a[1]), "r"(a[2]), "r"(a[3]), "r"(db), "n"(OFF));
}
template <int I> using IC = std::integral_constant<int, I>;
template <int I, int N, class F> __device__ __forceinline__ void sfor(F&& f) {
  if constexpr (I < N) { f(std::integral_constant<int, I>{}); sfor<I + 1, N>(f); }
}
__device__ __forceinline__ void keep(float (&d)[16]) {
  asm volatile("" : "+f"(d[0]), "+f"(d[1]), "+f"(d[2]), "+f"(d[3]), "+f"(d[4]), "+f"(d[5]), "+f"(d[6]), "+f"(d[7]),
      "+f"(d[8]), "+f"(d[9]), "+f"(d[10]), "+f"(d[11]), "+f"(d[12]), "+f"(d[13]), "+f"(d[14]), "+f"(d[15]) :: "memory");
}

template <int N, int S2 = 1024> __device__ __forceinline__ void ldx(uint32_t (&v)[N][4], const uint8_t* p) {
#pragma unroll
  for (int i = 0; i < 2 * N; i++)
    asm volatile("ld.relaxed.gpu.global.v2.b32 {%0,%1}, [%2];" : "=r"(v[i >> 1][2 * (i & 1)]), "=r"(v[i >> 1][2 * (i & 1) + 1]) : "l"(p + (i & 3) * 256 + (i >> 2) * S2) : "memory");
}
__device__ __forceinline__ uint32_t dif2(uint32_t a, uint32_t b, uint32_t tag) { uint32_t r; asm("lop3.b32 %0, %1, %2, %3, 0x7e;" : "=r"(r) : "r"(a), "r"(b), "r"(tag)); return r; }
__device__ __forceinline__ uint32_t dif2v(uint32_t a, uint32_t b, uint32_t tag) { uint32_t r; asm volatile("lop3.b32 %0, %1, %2, %3, 0x7e;" : "=r"(r) : "r"(a), "r"(b), "r"(tag)); return r; }
__device__ __forceinline__ uint32_t or3(uint32_t a, uint32_t b, uint32_t c) { uint32_t r; asm("lop3.b32 %0, %1, %2, %3, 0xfe;" : "=r"(r) : "r"(a), "r"(b), "r"(c)); return r; }
__device__ __forceinline__ uint32_t after(uint32_t x, float f, uint32_t z) { uint32_t r; asm("lop3.b32 %0, %1, %2, %3, 0xea;" : "=r"(r) : "r"(__float_as_uint(f)), "r"(z), "r"(x)); return r; }
__device__ __forceinline__ bool any_bit(uint32_t a, uint32_t b, uint32_t m) {
  uint32_t r; asm("lop3.b32 %0, %1, %2, %3, 0xa8;" : "=r"(r) : "r"(a), "r"(b), "r"(m)); return __any_sync(0xffffffffu, r); }
template <int W, int N> __device__ __forceinline__ bool stale(const uint32_t (&v)[N][4], uint32_t tag) {
  uint32_t x = dif2(v[0][0], v[0][2], tag);
  if (N == 4) x = or3(x, dif2(v[1][0], v[1][2], tag), dif2(v[2 % N][0], v[2 % N][2], tag));
  return any_bit(x, dif2(v[N - 1][0], v[N - 1][2], tag), 1);
}
template <int W, int N, int S2 = 1024> __device__ __forceinline__ void retry(uint32_t (&v)[N][4], const uint8_t* p, uint32_t tag, int& it) {
#pragma unroll 1
  do { ldx<N, S2>(v, p); it += INC_A; } while (stale<W>(v, tag) && it < SPIN_LIMIT);
}
__device__ __forceinline__ void mma_h(float (&d)[4], const uint32_t (&a)[4], const uint32_t (&b)[4], int hf) { mma16816(d, a[0], a[1], a[2], a[3], b[2 * hf], b[2 * hf + 1]); }
__device__ __forceinline__ void sts128(uint32_t a, const uint32_t (&r)[4]) { sts128(a, r[0], r[1], r[2], r[3]); }
__device__ __forceinline__ void sts128f(uint32_t a, const float* r) { sts128(a, __float_as_uint(r[0]), __float_as_uint(r[1]), __float_as_uint(r[2]), __float_as_uint(r[3])); }
__device__ __forceinline__ void mbar_spin(uint32_t bar, uint32_t par, int& it) {
  asm volatile("{.reg .pred p; .reg .b32 par; mov.b32 par, %2;\nLOOP: mbarrier.try_wait.parity.shared::cta.b64 p, [%1], par; @p bra.uni DONE;\n"
               "add.s32 %0, %0, 1; setp.le.s32 p, %0, %3; @p bra.uni LOOP;\nDONE: }" : "+r"(it) : "r"(bar), "r"(par), "n"(SPIN_LIMIT) : "memory"); }
__device__ __forceinline__ void warp_arrive(uint32_t bar) {
  __syncwarp(); asm volatile("{.reg .pred p; elect.sync _|p, 0xffffffff; @p mbarrier.arrive.shared::cta.b64 _, [%0];}" :: "r"(bar) : "memory"); }
__device__ __forceinline__ void delay_until(unsigned t) {
  asm volatile("{.reg .pred p; .reg .b64 c; .reg .b32 lo, hi;\nLOOP: mov.u64 c, %%clock64; mov.b64 {lo, hi}, c; sub.s32 lo, lo, %0; setp.lt.s32 p, lo, 0; @p bra.uni LOOP;}" :: "r"(t) : "memory"); }
__device__ __forceinline__ void cut(int it) { asm volatile("{.reg .pred p; setp.lt.s32 p, %0, 0;\nL: @p st.volatile.shared.u32 [%0], %0; @p bra.uni L;}" :: "r"(it) : "memory"); }
__device__ __forceinline__ void zero(float (&c)[4][4]) {
#pragma unroll
  for (int i = 0; i < 4; i++) c[i][0] = c[i][1] = c[i][2] = c[i][3] = 0.f;
}

__device__ __forceinline__ void sched() { asm volatile("griddepcontrol.launch_dependents;" ::: "memory"); }
__device__ __forceinline__ const uint8_t* pinp(const uint8_t* p) { return reinterpret_cast<const uint8_t*>(__shfl_xor_sync(0xffffffffu, reinterpret_cast<unsigned long long>(p), 0)); }
__device__ __forceinline__ uint32_t bar_or(int id, uint32_t x) {
  uint32_t r; asm volatile("{.reg .pred p, q; setp.ne.u32 p, %2, 0; bar.red.or.pred q, %1, 256, p; selp.u32 %0, 1, 0, q;}" : "=r"(r) : "r"(id), "r"(x) : "memory"); return r; }
__device__ __forceinline__ void bar_sync_unless(int id, bool x) { asm volatile("{.reg .pred p; setp.eq.u32 p, %1, 0; @p bar.sync %0, 256;}" :: "r"(id), "r"((uint32_t)x) : "memory"); }
__device__ __forceinline__ void bar_arrive_unless(int id, bool x) { asm volatile("{.reg .pred p; setp.eq.u32 p, %1, 0; @p bar.arrive %0, 256;}" :: "r"(id), "r"((uint32_t)x) : "memory"); }
__device__ __forceinline__ void stsm2t(uint32_t a, uint32_t r0, uint32_t r1) {
  asm volatile("stmatrix.sync.aligned.m8n8.x2.trans.shared.b16 [%0], {%1,%2};" :: "r"(a), "r"(r0), "r"(r1) : "memory"); }
#define rare(x) __builtin_expect(!!(x), 0)
__device__ __forceinline__ uint32_t gtime() { unsigned long long g; asm volatile("mov.u64 %0, %%globaltimer;" : "=l"(g) :: "memory"); return (uint32_t)g; }
__device__ __forceinline__ void wait_time(uint32_t t) {
  asm volatile("{.reg .pred p; .reg .b32 g; .reg .b64 c;\nLOOP: mov.u64 c, %%globaltimer; cvt.u32.u64 g, c; sub.s32 g, %0, g; setp.lt.u32 p, g, 16384; @p bra.uni LOOP;}" :: "r"(t - 1) : "memory"); }
__device__ __forceinline__ uint32_t ldx32(const void* p) { uint32_t v; asm volatile("ld.relaxed.gpu.global.b32 %0, [%1];" : "=r"(v) : "l"(p) : "memory"); return v; }
__device__ __forceinline__ void stx32(const void* p, uint32_t v) { asm volatile("st.relaxed.gpu.global.b32 [%0], %1;" :: "l"(p), "r"(v) : "memory"); }

__global__ void __launch_bounds__(256, 1)
rec_kernel(const __grid_constant__ RecMaps maps, const bf16* __restrict__ xin, const bf16* __restrict__ mem0) {
  extern __shared__ __align__(1024) uint8_t smem_raw[];
  const uint32_t sb = smem_u32(smem_raw);
  int role = blockIdx.x;
  {
    uint32_t smid, nsm; asm volatile("mov.u32 %0, %%smid;" : "=r"(smid)); asm volatile("mov.u32 %0, %%nsmid;" : "=r"(nsm));
    const int p = smid >> 1, u = p - 32;
    if (nsm == gridDim.x)
      role = (smid & 1) + (p < 32 ? 4 * ((p & 7) + 8 * (p >> 4)) + 2 * ((p >> 3) & 1) : p < 60 ? 4 * (16 + u % 7 + 7 * (u / 14)) + 2 * ((u / 7) & 1)
                         : p < 62 ? 2 * p + 8 : 2 * p - 4);
    role = uni(role);
  }
  if (role >= 128) {
    fft_cols(sb, role - 128, 4);
    grid_arrive(&g_x.ctr[32]); grid_wait(&g_x.ctr[32], 4);
    fft_rows_inv(&maps.fo, sb, role - 128, 4);
    return;
  }
  const int tid = threadIdx.x, warp = uni(tid >> 5), lane = tid & 31, wg = warp >> 2, w4 = warp & 3, g = lane >> 2, t = lane & 3;
  const int h = role >> 2, j = role & 3, jh = j & 1;
  uint32_t w[48][4];
  float aq[16], av[16];
  int it = 0;

  if (tid == 224) {
    mbar_init(sb + B_KV, 1); mbar_init(sb + B_W, 1); mbar_init(sb + B_X, 1); mbar_init(sb + B_X + 8, 1); mbar_init(sb + B_X + 16, 1); mbar_init(sb + B_X + 24, 1); mbar_init(sb + B_C, 4); mbar_init(sb + B_PK, 4); mbar_init(sb + B_B, 1);
    asm volatile("fence.mbarrier_init.release.cluster;" ::: "memory");
    mbar_expect_tx(sb + B_W, 3 * 65536);
    for (int i = 0; i < 4; i++) {
      tma2d(sb + R_X + i * 16384, &maps.wq, h * DH + 32 * j, i * 256, sb + B_W);
      tma2d(sb + R_MEM + i * 16384, &maps.wk, h * DH + 32 * j, i * 256, sb + B_W);
    }
    for (int i = 0; i < 2; i++) tma2d(sb + R_WO + i * 32768, &maps.wv, h * DH + 64 * (j >> 1), jh * 512 + i * 256, sb + B_W);
    for (int i = 0; i < 4; i++) asm volatile("cp.async.bulk.prefetch.L2.global [%0], 8192;" :: "l"(xin + role * 16384 + i * 4096) : "memory");
    for (int i = 0; i < 4; i++)
      asm volatile("cp.async.bulk.prefetch.tensor.2d.L2.global [%0, {%1, %2}];" :: "l"(&maps.wo), "r"(256 * j + 64 * i), "r"(h * DH) : "memory");
  }
  if (tid < 128) asm volatile("prefetch.global.L2 [%0];" :: "l"(mem0 + tid * 64));
  __syncthreads();
  mbar_spin(sb + B_W, 0, it);
  const int lrow = (lane & 7) + ((lane >> 4) << 3), lhi = (lane >> 3) & 1;
  const int kq = wg ? 1 - jh : 3 * jh;
  const uint32_t LW = lrow * 128 + ((lhi ^ (lane & 7)) << 4);
  {
    const int chunk = w4 < 2 ? w4 + 2 * lhi : 2 * (w4 & 1) + lhi;
    uint32_t a = sb + (w4 < 2 ? R_X : R_MEM) + kq * 16384 + lrow * 64 + ((chunk ^ ((lrow >> 1) & 3)) << 4);
#pragma unroll
    for (int i = 0; i < 16; i++) ldsm4t(w[i], a + i * 1024);
    const uint32_t st = wg ? 1024 : 2048, av0 = sb + R_WO + (LW ^ (w4 << 5));
    const uint32_t a1 = wg ? a + 16384 : av0 + jh * 32768, a2 = wg ? a + 32768 : av0 + (1 - jh) * 32768;
#pragma unroll
    for (int i = 0; i < 16; i++) { ldsm4t(w[16 + i], a1 + i * st); ldsm4t(w[32 + i], a2 + i * st); }
  }
  uint32_t L16 = pin(lane * 16);
  uint8_t* const xb = reinterpret_cast<uint8_t*>(&g_x);
  const uint32_t uW = uni(sb + w4 * 512), uWo = uni(sb + R_WO + w4 * 16384), uMem = uni(sb + R_MEM + kq * 4096);
  const uint32_t dX = uni(((sb + R_X + kq * 16384) >> 4) | 0x10000u);
  auto load_wo = [&](uint32_t (&d)[32][4], int i0, int i1) {
#pragma unroll
    for (int i = i0; i < i1; i++) lds128(d[i], uWo + L16 + (i & 1) * 512 + (i >> 4) * 1024 + (i & 14) * 1024);
  };
  auto issue_x = [&](int n, int k) {
    const uint32_t bar = sb + B_X + 8 * k, q = (k - jh) & 3;
    mbar_expect_tx(bar, 16384); tma3d(sb + R_X + q * 16384, &maps.x, n * SEG, 4 * q, bar);
  };
  auto store_stage = [&](int n) {
    asm volatile("cp.async.bulk.global.shared::cta.bulk_group [%0], [%1], 8192; cp.async.bulk.commit_group;"
                 :: "l"(g_kqv[n & 3][role]), "r"(sb + R_STAGE) : "memory");
  };
  auto issue_kqv = [&](int n) {
    const int p = (n & 3) * 128 + 4 * h;
    mbar_expect_tx(sb + B_KV, 26624);
    tma3d(sb + R_K, &maps.k, 0, p, sb + B_KV); tma3d(sb + R_Q, &maps.q, 8 + 2 * j, p, sb + B_KV); tma3d(sb + R_V, &maps.v, 16, p, sb + B_KV);
  };
  auto fetch4k = [&](uint32_t dst, uint32_t off, uint32_t bar, uint32_t t) {
    asm volatile("{.reg .pred p, q; .reg .b32 g; .reg .b64 c; elect.sync _|q, 0xffffffff; @q mbarrier.arrive.expect_tx.shared::cta.b64 _, [%2], 4096;\n"
                 "LOOP: mov.u64 c, %%globaltimer; cvt.u32.u64 g, c; sub.s32 g, %3, g; setp.lt.u32 p, g, 16384; @p bra.uni LOOP;\n"
                 "@q cp.async.bulk.shared::cluster.global.mbarrier::complete_tx::bytes [%0], [%1], 4096, [%2];}" :: "r"(dst), "l"(xb + off), "r"(bar), "r"(t - 1) : "memory");
  };
  auto issue_c = [&](uint32_t t) { fetch4k(sb + R_MEM + w4 * 4096, offsetof(Xchg, C) + (j >> 1) * 16384 + w4 * 4096, sb + B_C, t); };
  auto wait_x = [&](int n, int i) { if (!(EXP & 1) || n < 2) mbar_spin(sb + B_X + 8 * i, n & 1, it); };
  auto project_v = [&](auto I0, auto I1, auto&& mid) {
    wg_fence();
    sfor<decltype(I0)::value, decltype(I1)::value>([&](auto I) {
      constexpr int i = decltype(I)::value;
      mid(i);
      wg_rs32<((i >> 2) & 3) * 256 + (i & 3) * 2, (i > 0)>(av, w[16 + i], i < 16 ? dX : dX ^ 1024);
    });
    wg_commit();
  };
  auto project_qk = [&](auto I0, auto I1, auto&& mid) {
    const uint32_t dQ = dX + ((uint32_t)it >> 31);
    wg_fence();
    sfor<decltype(I0)::value, decltype(I1)::value>([&](auto I) {
      constexpr int i = decltype(I)::value;
      mid(i);
      wg_rs32<(i >> 2) * 256 + (i & 3) * 2, i != 16>(aq, w[i], dQ);
    });
    wg_commit();
  };
  const uint32_t uP = uni(sb + R_X + (2 - 2 * jh) * 16384 + w4 * 512);
  auto park = [&]() {
    bar_sync(1, 128);
#pragma unroll
    for (int i = 0; i < 4; i++) sts128f(uP + L16 + i * 2048, aq + 4 * i);
    warp_arrive(sb + B_PK);
  };
  auto unpark = [&]() {
#pragma unroll
    for (int i = 0; i < 4; i++) {
      const float4 p = lds128f(uP + L16 + i * 2048);
      aq[4 * i] = p.x; aq[4 * i + 1] = p.y; aq[4 * i + 2] = p.z; aq[4 * i + 3] = p.w;
    }
  };
  auto fin_qk = [&]() {
    const uint32_t a = sb + R_STAGE + (w4 < 2 ? 2048 + w4 * 128 : (w4 & 1) * 256) + (L16 & 112) + (L16 >> 7) * 512;
    stsm4t(a, pack2(aq[0], aq[1]), pack2(aq[4], aq[5]), pack2(aq[8], aq[9]), pack2(aq[12], aq[13]));
    stsm4t(a + (w4 < 2 ? 256 : 128), pack2(aq[2], aq[3]), pack2(aq[6], aq[7]), pack2(aq[10], aq[11]), pack2(aq[14], aq[15]));
  };
  auto fin_v = [&]() {
#pragma unroll
    for (int a = 0; a < 2; a++)
      sts128(sb + R_STAGE + 4096 + w4 * 1024 + a * 512 + L16, pack2(av[8 * a], av[8 * a + 1]), pack2(av[8 * a + 2], av[8 * a + 3]),
             pack2(av[8 * a + 4], av[8 * a + 5]), pack2(av[8 * a + 6], av[8 * a + 7]));
  };
  __syncthreads();
  if (tid == 224) {
#pragma unroll 1
    for (int i = 0; i < 4; i++) issue_x(0, i);
    mbar_expect_tx(sb + B_W, 65536);
    for (int i = 0; i < 4; i++) tma2d(sb + R_WO + i * 16384, &maps.wo, 256 * j + 64 * i, h * DH, sb + B_W);
  }
  __syncwarp();
  if (wg) {
#pragma unroll
    for (int i = 0; i < NSW; i++) sts128(uW + R_WC + L16 + i * 2048, w[i]);
  }
#pragma unroll
  for (int i = 0; i < 4; i++) {
    const uint32_t* p = reinterpret_cast<const uint32_t*>(mem0 + g * DM + 128 * warp + 32 * i + 2 * t);
    sts128(sb + R_MEM + warp * 2048 + i * 512 + (g >> 1) * 128 + t * 32 + (g & 1) * 16, __ldg(p), __ldg(p + 4), __ldg(p + 8), __ldg(p + 12));
  }
#pragma unroll 1
  for (int n = 0; n < 2; n++) {
    wait_x(n, 1); wait_x(n, 2); wait_x(n, 3);
    if (wg == 0) {
      wait_x(n, 0);
      project_v(IC<0>{}, IC<32>{}, [](int) {});
      if (tid == 96 && n == 1) {
        asm volatile("cp.async.bulk.wait_group 0;" ::: "memory");
        __threadfence(); atomicAdd(&g_x.ctr[h], 1u);
      }
      __syncwarp();
      mbar_spin(sb + B_PK, n, it);
      unpark();
      project_qk(IC<0>{}, IC<16>{}, [](int) {});
      wg_wait<0>(); keep(aq); keep(av);
      fin_v(); fin_qk();
      fence_async();
    } else {
      project_qk(IC<16>{}, IC<48>{}, [](int) {});
      project_qk(IC<0>{}, IC<16>{}, [](int) {});
      wg_wait<0>(); keep(aq);
      park();
      if (tid == 128 && n == 1) {
        for (int k = 0; *reinterpret_cast<volatile unsigned*>(&g_x.ctr[h]) < 4 && k < SPIN_LIMIT; k++) {}
        __threadfence(); asm volatile("fence.proxy.async;" ::: "memory");
        issue_kqv(0);
      }
    }
    __syncthreads();
    if (tid == 96 && n == 0) store_stage(0);
    if (tid == 128 && n == 0) {
#pragma unroll 1
      for (int i = 0; i < 4; i++) issue_x(1, i);
    }
    __syncwarp();
  }
  mbar_spin(sb + B_W, 1, it);
#pragma unroll
  for (int i = 0; i < 4; i++) {
    uint32_t f[4][4];
    const uint32_t a = sb + R_WO + warp * 8192 + i * 2048;
#pragma unroll
    for (int q = 0; q < 4; q++) ldsm4t(f[q], a + (LW ^ (q << 5)));
    __syncwarp();
#pragma unroll
    for (int q = 0; q < 4; q++) sts128(a + q * 512 + L16, f[q]);
  }
  mbar_spin(sb + B_KV, 0, it);
  if (tid == 0) sts32(sb + B_DUE, (gtime() & ~31u) - NS_P);
  if (tid < 4) sts32(sb + B_ONE + tid * 4, 0x3F803F80u);
  if (warp == 1) { const uint32_t e = g >> 1 == t ? 0x3F80u << (16 * (g & 1)) : 0u; sts128(sb + R_ID + L16, e, 0, 0, e); }
  __syncthreads();

  const float sc = 0.08838834764831845f * 1.4426950408889634f;
  uint8_t* const xa = xb + uni(h * 16384);
  const uint32_t uA = uni(wg ? (w4 >> 1) * 2048 + j * 512 + (w4 & 1) * 256 : 8192 + (4 * (j >> 1) + w4) * 512 + jh * 256);
  const uint32_t uB = uni(offsetof(Xchg, B) + (32 * w4 + j) * 8192 + h * 128);
  const uint32_t uP2 = uni(sb + R_P + w4 * 256);
  uint32_t nc = 1;
  uint32_t ma;
  auto pin_mem = [&]() { ma = pin(uMem + (L16 & 384) + (L16 & 48) * 2 + (L16 & 64) / 4); };
  pin_mem();

#pragma unroll 1
  for (int s = 0;; nc++) {
    const uint32_t tag = (s + 1) & 1;
    auto fresh = [&]() { L16 += (uint32_t)it >> 31; };
    float c[4][4], r4[4];
    auto fold = [&]() {
#pragma unroll
      for (int i = 0; i < 4; i++) r4[i] = ((c[0][i] + c[1][i]) + c[2][i]) + c[3][i];
    };
    auto mma4 = [&](int n, const uint32_t (&b0)[4], const uint32_t (&b1)[4]) {
      mma_h(c[0], w[n + 2], b1, 0); mma_h(c[1], w[n + 3], b1, 1); mma_h(c[2], w[n], b0, 0); mma_h(c[3], w[n + 1], b0, 1);
    };
    auto xpos = [&](int pos, int wp) {
      if (!(EXP & 1) && (pos == XC || pos == XD || pos == XB || pos == XA) && warp == wp && s + 1 < NSEG && elect()) {
        const int z = (uint32_t)it >> 31;
        if (pos == XC) issue_x(s + 2, 2 + z);
        if (pos == XD) issue_x(s + 2, 3 + z);
        if (pos == XB) issue_x(s + 2, 1 + z);
        if (pos == XA) issue_x(s + 2, z);
      }
      __syncwarp();
    };
    if (wg == 0) {
      mbar_spin(sb + B_C, nc & 1, it);
      TS(13);
      uint32_t b[16][4], tg[4];
#pragma unroll
      for (int i = 0; i < 8; i++) { lds128(b[i], ma + i * 512); __syncwarp(); }
      sched();
      zero(c);
#pragma unroll
      for (int i = 0; i < 8; i++) {
        const int k = i ^ 1;
        mma_h(c[0], w[2 * k], b[k], 0); mma_h(c[1], w[2 * k + 1], b[k], 1);
        if (i < 2 * NV0) { mma_h(c[2], w[16 + 2 * k], b[k], 0); mma_h(c[3], w[17 + 2 * k], b[k], 1); }
        sched();
        if (i == TGP) {
          fresh();
#pragma unroll
          for (int k = 0; k < 4; k++) tg[k] = lds32((uW * 4 + L16) * 2 + (L16 >> 6) * 4 + (R_MEM + k * 1024 - 7 * sb));
          sched();
        }
      }
#pragma unroll
      for (int i = 0; i < 4; i++) { r4[i] = c[0][i] + c[1][i]; c[0][i] = c[1][i] = 0.f; }
      sts128f(uW + R_RED + L16, r4);
      TS(1);
      const uint32_t old = bar_or(4, (dif2(tg[0], tg[1], s) | dif2(tg[2], tg[3], s)) & (s > 0));
      TS(0);
      uint8_t* adst;
#pragma unroll
      for (int i = 0; i < 2 * NV0; i++) { lds128(b[8 + i], (ma ^ 4096) + i * 512); __syncwarp(); }
      sched();
#pragma unroll
      for (int i = NV0; i < 8; i++) {
        mma4(16 + 4 * i, b[2 * i], b[2 * i + 1]);
        if (i < 7) sched();
        if (i < 4) { lds128(b[8 + 2 * i], (ma ^ 4096) + i * 1024); __syncwarp(); lds128(b[9 + 2 * i], (ma ^ 4096) + i * 1024 + 512); sched(); }
        if (i == 4) { adst = const_cast<uint8_t*>(pinp(xa + uA + L16 / 2)); sched(); }
      }
      fold();
      asm volatile("{.reg .pred p; setp.eq.u32 p, %3, 0; @p st.relaxed.gpu.global.v2.b32 [%0], {%1,%2};}" :: "l"(adst), "r"((pack2(r4[0], r4[1]) & ~1u) | tag), "r"(pack2(r4[2], r4[3])), "r"(old) : "memory");
      sched();
      const unsigned tpub = clk();
      if (__any_sync(0xffffffffu, old) && nc < NC_MAX) {
        bar_sync(3, 256);
        issue_c(gtime());
        continue;
      }
      TS(3);
      xpos(0, 0);
      const uint32_t due = lds32(sb + B_DUE);
      uint32_t vf[4][4], vm[2][4], p[4], pm, o[4];
      const uint32_t va = sb + R_V + (w4 >> 1) * 8192 + (w4 & 1) * 2048 + L16;
#pragma unroll
      for (int i = 0; i < 4; i++) {
        uint32_t q[4]; lds128(vf[i], va + i * 512); lds128(q, va + 4096 + i * 512);
#pragma unroll
        for (int e = 0; e < 4; e++) vf[i][e] = hadd2(vf[i][e], q[e]);
      }
      const uint32_t pa = pin(sb + R_P + (L16 >> 1));
      const uint8_t* vsrc = pinp(xa + 8192 + w4 * 1024 + L16 / 2);
      const uint8_t* tsrc = pinp(xb + offsetof(Xchg, T) + L16 * 8);
      uint32_t one[4];
      lds128(one, sb + B_ONE);
      auto pv_x = [&]() {
        zero(c);
        mma_a(c[2], one, p[0], p[1]);
        mma_a(c[0], vf[0], p[0], p[1]); mma_a(c[1], vf[2], p[0], p[1]);
        sched();
        mma_a(c[2], one, p[2], p[3]);
        mma_a(c[0], vf[1], p[2], p[3]); mma_a(c[1], vf[3], p[2], p[3]);
        sched();
      };
      auto pv_m = [&]() {
        mma1688(c[2], one[0], one[1], pm);
        mma_a(c[0], vm[0], pm, pm);
        sched();
        mma_a(c[1], vm[1], pm, pm);
      };
      auto norm = [&]() {
        const float n0 = rcp(c[2][0]), n1 = rcp(c[2][1]);
#pragma unroll
        for (int i = 0; i < 4; i++) o[i] = pack2(c[i >> 1][2 * (i & 1)] * n0, c[i >> 1][2 * (i & 1) + 1] * n1);
        return ((__float_as_uint(c[2][0]) - 0x1F800000u) | (__float_as_uint(c[2][1]) - 0x1F800000u)) >> 30;
      };
      auto load_m = [&](int x) { const float2 e0 = lds64f(pa + 512 + x * 1024), e1 = lds64f(pa + 768 + x * 1024); pm = pack2(e0.x * e1.x, e0.y * e1.y); };
      auto attend_max = [&](int x) {
        float2 sv[6];
#pragma unroll
        for (int i = 0; i < 6; i++) sv[i] = lds64f(pa - 3072 + x * 1536 + i * 256);
        sv[4].x += sv[5].x; sv[4].y += sv[5].y;
        const int dq = (int)(L16 >> 6) - (int)((L16 >> 3) & 6) + 8 * j;
        float m = fmaxf(sv[4].x, sv[4].y);
#pragma unroll
        for (int i = 0; i < 4; i++) {
          if (x && 8 * i > dq) sv[i].x = -INFINITY;
          if (x && 8 * i + 1 > dq) sv[i].y = -INFINITY;
          m = fmaxf(m, fmaxf(sv[i].x, sv[i].y));
        }
        m = fmaxf(m, __shfl_xor_sync(0xffffffffu, m, 1));
        m = fmaxf(m, __shfl_xor_sync(0xffffffffu, m, 2));
#pragma unroll
        for (int i = 0; i < 5; i++) (i < 4 ? p[i] : pm) = pack2(ex2(sv[i].x - m), ex2(sv[i].y - m));
        pv_x(); pv_m(); norm();
      };
      delay_until(tpub + DLY_V);
      wait_time(due + (NS_P + NS_V));
      TS(4);
      ldx(vm, vsrc);
      sched();
      asm volatile("{.reg .pred p; setp.eq.u32 p, %2, 0; @p cp.async.cg.shared.global [%0], [%1], 16;}" :: "r"(sb + R_T + L16), "l"(tsrc), "r"(warp) : "memory");
      cpa_commit();
      xpos(2, 2);
      auto store_kqv = [&]() {
        fence_async();
        if (!(EXP & 4))
          asm volatile("{.reg .pred p; elect.sync _|p, 0xffffffff; @p cp.async.bulk.global.shared::cta.bulk_group [%0], [%1], 2048; cp.async.bulk.commit_group;}"
                       :: "l"(g_kqv[(s + 1) & 3][role] + w4 * 128), "r"(sb + R_STAGE + w4 * 2048) : "memory");
      };
      if (SPOS == 2) store_kqv();
      sched();
      bar_sync(5, 256);
      ldsm4(p, sb + R_P + L16);
      load_m(0);
      pv_x();
      ldsm4(p, sb + R_P + 1024 + L16);
      pv_m();
      const uint32_t r = norm(), tl = after(tag, c[2][0], (uint32_t)it >> 31);
      const bool redo = __any_sync(0xffffffffu, r | ((dif2(vm[0][0], vm[0][2], tl) | dif2(vm[1][0], vm[1][2], tl)) & 1));
      TS(6);
      stsm4t(uW + R_O + L16, o[0], o[1], o[2], o[3]);
      bar_arrive_unless(6, redo);
      sched();
      TS(7);
      pv_x();
      bar_sync(8, 256);
      load_m(1);
      pv_m();
      if (rare(__any_sync(0xffffffffu, norm()) || redo)) {
        fresh();
        retry<2>(vm, xa + 8192 + w4 * 1024 + L16 / 2, tag, it);
#pragma unroll 1
        for (int x = !redo; x < 2; x++) {
          attend_max(x);
          if (x == 0) { stsm4t(uW + R_O + L16, o[0], o[1], o[2], o[3]); bar_arrive(6, 256); }
        }
      }
      TS(8);
      if (SPOS == 4) store_kqv();
      xpos(4, 2);
      asm volatile("cp.async.bulk.wait_group 0;" ::: "memory");
      if (elect()) stx32(xa + 4096 + j * 16 + w4 * 4, s + 1);
      __syncwarp();
      if (warp == 0 && s + 1 < NSEG) {
        uint32_t tq[4];
        cpa_wait<0>();
        lds128(tq, sb + R_T + L16);
        const uint32_t ref = gtime();
#pragma unroll 1
        while (any_bit(or3(tq[0] - s - 1, tq[1] - s - 1, tq[2] - s - 1), tq[3] - s - 1, 30) && ++it < SPIN_LIMIT) ldx128(tq, xb + offsetof(Xchg, T) + L16 * 8);
        const int d = max(max((int)(tq[0] - ref), (int)(tq[1] - ref)), max((int)(tq[2] - ref), (int)(tq[3] - ref)));
        const uint32_t last = (ref + __reduce_max_sync(0xffffffffu, d)) & ~31u;
        TS(2);
        fetch4k(sb + R_MEM, offsetof(Xchg, B) + role * 8192, sb + B_B, last + NS_B);
        TS(5);
        sts32(sb + B_DUE, last);
        xpos(5, 0);
        LOG(9, last);
        LOG(13, tl - last);
      }
      fresh();
      const uint32_t ob = uni(sb + R_MEM + 4096 + w4 * 1024);
      stsm4t(ob + (L16 & 112) * 4 + (((L16 >> 3) ^ (L16 >> 1)) & 48), o[0], o[1], o[2], o[3]);
      __syncwarp();
      lds128(o, ob + (L16 ^ ((L16 >> 3) & 48)));
      auto put_o = [&]() {
        *reinterpret_cast<uint4*>(reinterpret_cast<uint8_t*>(g_ox) + (((s * SEG + 8 * j) * HD + h * DH + 32 * w4) * 2 + (L16 >> 6) * (HD * 2) + (L16 & 48))) = make_uint4(o[0], o[1], o[2], o[3]);
      };
      if (s + 1 == NSEG) { put_o(); break; }
      if (OXPOS < 0) put_o();
      fresh();
      const uint32_t ba = pin(sb + R_MEM + (L16 & 112) * 8 + (L16 >> 8) * 1024 + ((w4 * 32 + ((L16 >> 3) & 16)) ^ (L16 & 112)));
      const uint8_t* cdst = pinp(xb + (offsetof(Xchg, C) + j * 4096 + h * 128 + w4 * 32 + (L16 & 16) * 1024 + (L16 & 64) / 4 + (L16 >> 7) * 4));
      const uint32_t msk = pin((L16 >> 6) == (h & 3) * 2 + ((h >> 2) & 1) ? 0xFFFE0000u : 0xFFFFFFFFu);
      if (warp == 1) {
        wait_time(due + (NS_P + NS_F));
#pragma unroll 1
        while (__any_sync(0xffffffffu, ldx32(xa + 4096 + ((L16 >> 2) & 60)) != s + 1) && !(EXP & 4) && ++it < SPIN_LIMIT) {}
        wait_time(due + (NS_P + NS_B + NS_K));
        if (!(EXP & 2) && elect()) issue_kqv(s + 1);
        __syncwarp();
      }
      TS(9);
      mbar_spin(sb + B_B, s & 1, it);
      TS(10);
      uint32_t bq[2][4];
      auto sum_b = [&]() {
        ldsm4t(bq[0], ba); ldsm4t(bq[1], ba + 2048);
        sched();
#pragma unroll
        for (int i = 0; i < 8; i++) c[i >> 2][i & 3] = 0.f;
        mma_a(c[0], bq[0], 0x3F803F80u, 0x3F803F80u); mma_a(c[1], bq[1], 0x3F803F80u, 0x3F803F80u);
        const uint32_t t2 = tag * 0x10001u;
        const bool old = any_bit(or3(dif2(bq[0][0], bq[0][1], t2), dif2(bq[0][2], bq[0][3], t2), dif2(bq[1][0], bq[1][1], t2)), dif2(bq[1][2], bq[1][3], t2), L16 < 64 ? 0x10001u : 0u);
        const uint32_t T = (tag << 16) & ~msk, u = ((__float_as_uint(c[0][0] + c[1][0]) + ((0x10000u & ~msk) - T)) & msk) | T;
        asm volatile("{.reg .pred p; setp.eq.u32 p, %2, 0; @p st.relaxed.gpu.global.b32 [%0], %1;}"
                     :: "l"(cdst), "r"(pack2(__uint_as_float(u), c[0][2] + c[1][2])), "r"((uint32_t)(old || (L16 & 32))) : "memory");
        return old;
      };
      if (rare(sum_b())) {
#pragma unroll 1
        do {
          const uint8_t* p = xb + (offsetof(Xchg, B) + role * 8192 + (ba - sb - R_MEM));
          ldx128(bq[0], p); ldx128(bq[1], p + 2048);
          sts128(ba, bq[0]); sts128(ba + 2048, bq[1]);
          __syncwarp();
          it += INC_B;
        } while (sum_b() && it < SPIN_LIMIT);
      }
      sched();
      TS(11);
      bar_arrive(0, 256);
      wait_x(s + 2, 0); wait_x(s + 2, 1 + 2 * jh);
      fresh();
      auto mid = [&](int n) { if (n == OXPOS) { __syncwarp(); put_o(); __syncwarp(); } };
      project_v(IC<0>{}, IC<UNP>{}, mid);
      mbar_spin(sb + B_PK, s & 1, it);
      unpark();
      project_v(IC<UNP>{}, IC<32>{}, mid);
      project_qk(IC<0>{}, IC<16>{}, [](int) {});
      TS(12);
      LOG(warp, it);
      pin_mem();
      wg_wait<1>(); keep(av);
      fin_v();
      wg_wait<0>(); keep(aq);
      fin_qk();
      TS(15);
    } else {
      uint32_t kf[8][4];
      auto load_k = [&]() {
        const uint32_t ka = sb + R_K + w4 * 1024 + (L16 & 112) + (L16 & 128) * 4 + (L16 & 256);
#pragma unroll
        for (int i = 0; i < 8; i++) ldsm4(kf[i], ka + (i >> 1) * 2048 + (i & 1) * 128);
      };
      auto put_p = [&](int x) {
        float e[4];
        const int dq = (int)((L16 >> 3) & 6) + 8 * j - (int)(L16 >> 6) - 16 * w4;
#pragma unroll
        for (int i = 0; i < 4; i++) { r4[i] = fmaf(c[3][i], sc, fmaf(c[2][i], sc, (c[0][i] + c[1][i]) * sc)); e[i] = x && dq + (i & 1) < 8 * (i >> 1) ? 0.f : ex2(r4[i]); }
        stsm2t(uP2 + x * 1024 + L16, pack2(e[0], e[1]), pack2(e[2], e[3]));
      };
      auto put_s = [&](int x) {
#pragma unroll
        for (int i = 0; i < 4; i++) sts32f(uW + R_S + x * 1536 + (L16 & 48) * 4 + (L16 >> 6) * 4 + (i & 1) * 32 + (i >> 1) * 256, r4[i]);
      };
      auto load_q = [&](uint32_t (&q)[4], uint32_t off) { ldsm4(q, sb + R_Q + (L16 & 112) + (L16 & 128) * 2 + (L16 >> 8) * 128 + off); };
      const uint8_t* adst = pinp(xa + uA + L16 / 2);
      uint32_t due;
      mbar_spin(sb + B_C, nc & 1, it);
      TS(13);
      float4 o4;
      uint32_t id[4], old;
      {
        uint32_t b[24][4];
#pragma unroll
        for (int i = 0; i < 2 * PD1; i++) { lds128(b[i], ma + i * 512); __syncwarp(); }
        sched();
        zero(c);
#pragma unroll
        for (int i = 0; i < 12; i++) {
          mma4(4 * i, b[2 * i], b[2 * i + 1]);
          if (i < 11) sched();
          if (i + PD1 < 12) { lds128(b[2 * (i + PD1)], ma + (i + PD1) * 1024); __syncwarp(); lds128(b[2 * (i + PD1) + 1], ma + (i + PD1) * 1024 + 512); sched(); }
          if (i == RJ) { lds128(id, sb + R_ID + L16); due = lds32(sb + B_DUE) + NS_P; sched(); }
          if (i == RI) { old = bar_or(4, 0); o4 = lds128f(uW + R_RED + L16); sched(); }
        }
      }
      TS(0);
      {
        float e[4] = {o4.x, o4.y, o4.z, o4.w};
#pragma unroll
        for (int i = 0; i < 4; i++) { r4[i] = (((e[i] + c[0][i]) + c[1][i]) + c[2][i]) + c[3][i]; e[i] = 0.f; }
        mma_a(e, id, pack2(r4[0], r4[1]), pack2(r4[2], r4[3]));
        asm volatile("{.reg .pred p; setp.eq.u32 p, %3, 0; @p st.relaxed.gpu.global.v2.b32 [%0], {%1,%2};}" :: "l"(adst),
                     "r"((__byte_perm(__float_as_uint(e[0]), __float_as_uint(e[1]), 0x7632) & ~1u) | tag), "r"(__byte_perm(__float_as_uint(e[2]), __float_as_uint(e[3]), 0x7632)), "r"(old) : "memory");
        sched();
      }
      const unsigned tpub = clk(), now = gtime();
      if (__any_sync(0xffffffffu, old) && nc < NC_MAX) { bar_sync(3, 256); continue; }
      TS(2);
      const uint8_t* asrc = pinp(adst + ((warp == 7) * 1024 - (int)uA));
      fresh();
      uint32_t wo[32][4];
      uint8_t* dst;
      bool xok;
      auto pin_dst = [&]() { dst = const_cast<uint8_t*>(pinp(xb + uB + ((((L16 >> 2) * 0x2001u) & 0x18070u) ^ ((h & 7) << 4)))); sched(); };
      auto out_proj = [&]() {
        uint32_t b[4][4];
        float d[4][4];
        pin_dst();
        TS(7);
        bar_sync(6, 256);
#pragma unroll
        for (int i = 0; i < 4; i++) { ldsm4(b[i], sb + R_O + i * 512 + L16); __syncwarp(); }
        sched();
        auto put_b = [&](uint8_t* a, const float (&e)[4][4]) {
          stx128(a, (pack2(e[0][0] + e[2][0], e[0][1] + e[2][1]) & ~1u) | tag, pack2(e[0][2] + e[2][2], e[0][3] + e[2][3]),
                 pack2(e[1][0] + e[3][0], e[1][1] + e[3][1]), pack2(e[1][2] + e[3][2], e[1][3] + e[3][3]));
        };
        zero(c); zero(d);
#pragma unroll
        for (int i = 0; i < 32; i++) {
          mma_h(i < 16 ? c[i & 3] : d[i & 3], wo[i], b[(i >> 2) & 3], (i >> 1) & 1);
          if (i >= LW0 && NB1 + i - LW0 < 32) { load_wo(wo, (NB1 + i - LW0) ^ 1, ((NB1 + i - LW0) ^ 1) + 1); __syncwarp(); }
          if (i == 22) put_b(dst, c);
          if ((i & 1) && (i < 20 || i > 22)) sched();
        }
        put_b(dst + 131072, d);
        sched();
      };
      if (warp < 6) {
        delay_until(tpub + DLY_A);
        bool redo;
#pragma unroll 1
        do {
          uint32_t q[4][4], y[4];
          float d[4][4];
          wait_time(due);
          TS(4);
          ldx(q, asrc);
          sched();
          load_k();
          uint32_t qx[4][4];
#pragma unroll
          for (int i = 0; i < 4; i++) load_q(qx[i], i * 512);
          sched();
          load_wo(wo, 0, NE4);
          sched();
          zero(c);
#pragma unroll
          for (int i = 0; i < 8; i++) mma_h(c[i & 3], kf[i], qx[i >> 1], i & 1);
          put_p(1); put_s(1);
          sched();
          load_wo(wo, NE4, NA4);
          sched();
          zero(c); zero(d);
#pragma unroll
          for (int i = 0; i < 8; i++) {
            if (i == 0) { y[0] = dif2v(q[0][0], q[0][2], q[1][0]); sched(); }
            if (i == 3) { y[1] = dif2v(q[1][2], q[2][0], q[2][2]); sched(); }
            if (i == 6) { y[2] = dif2v(q[3][0], q[3][2], tag); sched(); }
            mma_h(i % 6 < 2 ? c[2 + i % 6] : d[i - 2], kf[i], q[i >> 1], i & 1);
            if (i == 4) y[3] = dif2(q[0][0], q[2][0], tag);
            if (i == 2 || i == 5 || i == 7) sched();
          }
          redo = any_bit(or3(y[0], y[1], y[3]), y[2], it < SPIN_LIMIT);
#pragma unroll
          for (int i = 0; i < 4; i++) { c[0][i] = d[0][i] + d[1][i]; c[1][i] = d[2][i] + d[3][i]; }
          put_p(0);
          TS(5);
          bar_sync_unless(5, redo);
          it += INC_A;
        } while (redo);
        it -= INC_A;
        put_s(0);
        bar_arrive(8, 256);
        load_wo(wo, NA4, NB1);
        out_proj();
      } else {
        uint32_t qx[2][4], q[4][4];
        if (warp == 6) {
          const uint32_t t1 = (now & ~31u) + NS_M;
          LOG(10, now - due);
          if (elect()) stx32(&g_x.T[h][j], ((int)(t1 - due) > 0 ? t1 + NS_PEN : due) | ((s + 1) & 31));
          __syncwarp();
        }
        auto score = [&](const uint32_t (&a0)[4], const uint32_t (&a1)[4]) {
          zero(c);
#pragma unroll
          for (int i = 0; i < 4; i++) mma_h(c[i], i < 2 ? a0 : a1, q[2 + (i >> 1)], i & 1);
        };
        auto put_m = [&](uint32_t a) {
#pragma unroll
          for (int i = 0; i < 2; i++) { r4[i] = fmaf(c[3][2 + i], sc, ((c[0][i] + c[1][2 + i]) + c[2][i]) * sc); r4[2 + i] = fmaf(r4[i] * 0x1p122f, 0.f, ex2(r4[i])); }
          sts64f(a, r4[2], r4[3]);
        };
        delay_until(tpub + DLY_A);
        const uint32_t sa = sb + R_S + 512 + w4 * 256 + (L16 >> 1);
        bool redo;
#pragma unroll 1
        do {
          wait_time(due);
          TS(4);
          ldx<4, 2048>(q, asrc);
          sched();
          load_q(qx[0], (w4 & 1) * 1024); load_q(qx[1], (w4 & 1) * 1024 + 512);
          load_wo(wo, 0, NA6);
          sched();
          score(q[0], q[1]);
          const uint32_t tl = after(tag, c[0][0], (uint32_t)it >> 31);
          redo = any_bit(or3(dif2(q[0][0], q[0][2], tl), dif2(q[1][0], q[1][2], tl), dif2(q[2][0], q[2][2], tl)), dif2(q[3][0], q[3][2], tl), it < SPIN_LIMIT);
          put_m(sa + 2560);
          TS(5);
          bar_arrive_unless(5, redo);
          it += INC_A;
        } while (redo);
        it -= INC_A;
        sts64f(sa, r4[0], r4[1]);
        score(qx[0], qx[1]);
        put_m(sa + 3584);
        sts64f(sa + 1536, r4[0], r4[1]);
        bar_arrive(8, 256);
        load_wo(wo, NA6, NB1);
        out_proj();
      }
      TS(8);
      if (s + 1 == NSEG) break;
      if (warp == 4) LOG(12, tb);
      wait_x(s + 2, 2);
      TS(9);
      fresh();
      auto mid = [&](int n) {
        if (n >= 16 + RL0 && (n - 16 - RL0) % RLS == 0) {
#pragma unroll
          for (int i = (n - 16 - RL0) / RLS * RLB; i < (n - 16 - RL0) / RLS * RLB + RLB && i < NSW; i++) lds128(w[i], uW + R_WC + L16 + i * 2048);
          __syncwarp();
        }
        if (n >= 16 && (n & 15) == XWPOS) { __syncwarp(); xok = mbar_test(sb + B_X + (n < 32 ? 24 : 8), s & 1); __syncwarp(); }
      };
      project_qk(IC<16>{}, IC<32>{}, mid);
      if (rare(!xok)) wait_x(s + 2, 3);
      project_qk(IC<32>{}, IC<48>{}, mid);
      if (rare(!xok)) wait_x(s + 2, 1);
      project_qk(IC<0>{}, IC<16>{}, mid);
      TS(10);
      wg_wait<0>(); keep(aq);
      TS(1);
      park();
      TS(11);
      LOG(warp, it);
      if (warp == 4) LOG(8, nc);
      bar_sync(0, 256);
      const uint32_t cdue = lds32(sb + B_DUE) + NS_C;
      sched();
      delay_until(clk() + DLY_C);
      TS(12);
      if (warp == 7) LOG(11, gtime() - cdue);
      issue_c(cdue);
      TS(14);
      fresh();
      pin_mem();
      if (!(EXP & 2)) mbar_spin(sb + B_KV, tag, it);
      TS(15);
    }
    s++;
  }
  if (it >= SPIN_LIMIT || nc >= NC_MAX) g_err = 2;
}

typedef CUresult (*EncodeFn)(CUtensorMap*, CUtensorMapDataType, cuuint32_t, void*, const cuuint64_t*, const cuuint64_t*, const cuuint32_t*,
                             const cuuint32_t*, CUtensorMapInterleave, CUtensorMapSwizzle, CUtensorMapL2promotion, CUtensorMapFloatOOBfill);
static void make_map(EncodeFn fn, CUtensorMap* m, const void* p, uint64_t cols, uint64_t rows, uint64_t pitch, uint32_t bc, uint32_t br, CUtensorMapSwizzle sw) {
  cuuint64_t dims[2] = {cols, rows}, strides[1] = {pitch * 2};
  cuuint32_t box[2] = {bc, br}, es[2] = {1, 1};
  fn(m, CU_TENSOR_MAP_DATA_TYPE_BFLOAT16, 2, const_cast<void*>(p), dims, strides, box, es, CU_TENSOR_MAP_INTERLEAVE_NONE, sw,
     CU_TENSOR_MAP_L2_PROMOTION_L2_256B, CU_TENSOR_MAP_FLOAT_OOB_FILL_NONE);
}

extern "C" void kernel_launch(void* const* d_in, const int* in_sizes, int n_in, void* d_out, int out_size) {
  const bf16* Ax = (const bf16*)d_in[0]; const bf16* mem0 = (const bf16*)d_in[1];
  const bf16* Wq = (const bf16*)d_in[2]; const bf16* Wk = (const bf16*)d_in[3]; const bf16* Wv = (const bf16*)d_in[4];
  const bf16* Wo = (const bf16*)d_in[5];
  const bf16* Bx = (const bf16*)d_in[7]; const bf16* wr = (const bf16*)d_in[8]; const bf16* wi = (const bf16*)d_in[9];
  bf16* out = (bf16*)d_out;

  void* fp = nullptr; cudaDriverEntryPointQueryResult qr;
  cudaGetDriverEntryPoint("cuTensorMapEncodeTiled", &fp, cudaEnableDefault, &qr);
  EncodeFn fn = (EncodeFn)fp;
  void *kqv, *ox;
  cudaGetSymbolAddress(&kqv, g_kqv); cudaGetSymbolAddress(&ox, g_ox);
  const CUtensorMapSwizzle S128 = CU_TENSOR_MAP_SWIZZLE_128B, S64 = CU_TENSOR_MAP_SWIZZLE_64B;

  GemmMaps m3; RecMaps mr;
  make_map(fn, &m3.a, ox, HD, S_LEN, HD, 64, 128, S128);
  make_map(fn, &m3.b[0], Wo, DM, HD, DM, 64, 64, S128);
  m3.b[1] = m3.b[0]; m3.b[2] = m3.b[0];
  make_map(fn, &m3.c, out, DM, S_LEN, 2 * DM, 64, 64, S128);
  make_map(fn, &mr.wq, Wq, HD, DM, HD, 32, 256, S64);
  make_map(fn, &mr.wk, Wk, HD, DM, HD, 32, 256, S64);
  make_map(fn, &mr.wv, Wv, HD, DM, HD, 64, 256, S128);
  make_map(fn, &mr.wo, Wo, DM, HD, DM, 64, 128, S128);
  {
    cuuint64_t dims[3] = {64, S_LEN, 16}, strides[2] = {DM * 2, 128};
    cuuint32_t box[3] = {64, 32, 4}, es[3] = {1, 1, 1};
    fn(&mr.x, CU_TENSOR_MAP_DATA_TYPE_BFLOAT16, 3, const_cast<bf16*>(Ax), dims, strides, box, es, CU_TENSOR_MAP_INTERLEAVE_NONE, S128,
       CU_TENSOR_MAP_L2_PROMOTION_L2_256B, CU_TENSOR_MAP_FLOAT_OOB_FILL_NONE);
  }
  for (int i = 0; i < 3; i++) {
    cuuint64_t dims[3] = {128, 32, 512}, strides[2] = {256, 8192};
    cuuint32_t box[3] = {128, i == 0 ? 8u : i == 1 ? 2u : 16u, 4}, es[3] = {1, 1, 1};
    fn(i == 0 ? &mr.k : i == 1 ? &mr.q : &mr.v, CU_TENSOR_MAP_DATA_TYPE_BFLOAT16, 3, kqv, dims, strides, box, es, CU_TENSOR_MAP_INTERLEAVE_NONE,
       CU_TENSOR_MAP_SWIZZLE_NONE, CU_TENSOR_MAP_L2_PROMOTION_L2_256B, CU_TENSOR_MAP_FLOAT_OOB_FILL_NONE);
  }
  {
    cuuint64_t dims[3] = {64, 16, S_LEN}, strides[2] = {128, 2 * DM * 2};
    cuuint32_t box[3] = {64, 16, 2}, es[3] = {1, 1, 1};
    fn(&mr.fo, CU_TENSOR_MAP_DATA_TYPE_BFLOAT16, 3, out + DM, dims, strides, box, es, CU_TENSOR_MAP_INTERLEAVE_NONE, S128,
       CU_TENSOR_MAP_L2_PROMOTION_NONE, CU_TENSOR_MAP_FLOAT_OOB_FILL_NONE);
  }
  constexpr int SM3 = 6 * 32768 + 32768 + 256 + 1024;
  cudaFuncSetAttribute(gemm_kernel<128, 6>, cudaFuncAttributeMaxDynamicSharedMemorySize, SM3);
  cudaFuncSetAttribute(rec_kernel, cudaFuncAttributeMaxDynamicSharedMemorySize, R_TOTAL);

  cudaStream_t st = cudaStreamPerThread;
  cudaFuncSetAttribute(fft_pre_kernel, cudaFuncAttributeMaxDynamicSharedMemorySize, F_SMEM);
  fft_pre_kernel<<<128, 256, F_SMEM, st>>>(Bx, wr, wi);
  rec_kernel<<<132, 256, R_TOTAL, st>>>(mr, Ax, mem0);
  gemm_kernel<128, 6><<<128, 384, SM3, st>>>(m3, 16, 8, 64, 8, 1);
}
```

```cpp
#include <cuda_runtime.h>
#include <cuda_bf16.h>
#include <cuda.h>
#include <stdint.h>
#include <stddef.h>
#include <type_traits>

typedef __nv_bfloat16 bf16;

constexpr int S_LEN = 2048, DM = 1024, NH = 32, DH = 128, MEM = 8, SEG = 32, NSEG = 64;
constexpr int HD = NH * DH;
#define SPIN 20
constexpr int SPIN_LIMIT = 1 << SPIN, INC_A = 1, INC_B = 1;

constexpr unsigned NC_MAX = 4096;
__device__ __align__(1024) uint4 g_kqv[4][128][512];
__device__ __align__(1024) bf16 g_ox[(size_t)S_LEN * HD];
struct Xchg {
  uint4 A[32][2][2][256];
  uint4 C[2][4][256];
  uint4 B[128][2][256];
  uint32_t T[32][32];
  unsigned ctr[64];
};
__device__ __align__(8192) Xchg g_x;
__device__ __align__(1024) uint4 g_y[1024 * 256];
__device__ __align__(1024) uint4 g_wt[513 * 512];
__device__ int g_err;

__device__ __forceinline__ unsigned clk() { unsigned long long c; asm volatile("mov.u64 %0, %%clock64;" : "=l"(c)); return (unsigned)c; }
__device__ __forceinline__ uint32_t smem_u32(const void* p) { return (uint32_t)__cvta_generic_to_shared(p); }
__device__ __forceinline__ void mbar_init(uint32_t bar, int cnt) { asm volatile("mbarrier.init.shared::cta.b64 [%0], %1;" :: "r"(bar), "r"(cnt) : "memory"); }
__device__ __forceinline__ void mbar_expect_tx(uint32_t bar, int bytes) { asm volatile("mbarrier.arrive.expect_tx.shared::cta.b64 _, [%0], %1;" :: "r"(bar), "r"(bytes) : "memory"); }
__device__ __forceinline__ void mbar_arrive(uint32_t bar) { asm volatile("mbarrier.arrive.shared::cta.b64 _, [%0];" :: "r"(bar) : "memory"); }
__device__ __forceinline__ void mbar_arrive_cluster(uint32_t bar, int cta) {
  asm volatile("{.reg .b32 r; mapa.shared::cluster.u32 r, %0, %1; mbarrier.arrive.shared::cluster.b64 _, [r];}" :: "r"(bar), "r"(cta) : "memory"); }
__device__ __forceinline__ bool mbar_try(uint32_t bar, int par) {
  uint32_t ok; asm volatile("{.reg .pred p; mbarrier.try_wait.parity.shared::cta.b64 p, [%1], %2; selp.u32 %0, 1, 0, p;}" : "=r"(ok) : "r"(bar), "r"(par) : "memory"); return ok; }
__device__ __forceinline__ bool mbar_test(uint32_t bar, int par) {
  uint32_t ok; asm volatile("{.reg .pred p; mbarrier.test_wait.parity.shared::cta.b64 p, [%1], %2; selp.u32 %0, 1, 0, p;}" : "=r"(ok) : "r"(bar), "r"(par) : "memory"); return ok; }
__device__ __forceinline__ void mbar_wait(uint32_t bar, int par) {
  int it = 0;
  while (!mbar_try(bar, par)) { if (++it > SPIN_LIMIT) { g_err = 1; break; } }
}
__device__ __forceinline__ void tma2d(uint32_t dst, const CUtensorMap* m, int c0, int c1, uint32_t bar) {
  asm volatile("cp.async.bulk.tensor.2d.shared::cluster.global.mbarrier::complete_tx::bytes [%0], [%1, {%3, %4}], [%2];"
    :: "r"(dst), "l"(m), "r"(bar), "r"(c0), "r"(c1) : "memory"); }
__device__ __forceinline__ void tma2d_mc(uint32_t dst, const CUtensorMap* m, int c0, int c1, uint32_t bar, uint16_t mask) {
  asm volatile("cp.async.bulk.tensor.2d.shared::cluster.global.mbarrier::complete_tx::bytes.multicast::cluster [%0], [%1, {%3, %4}], [%2], %5;"
    :: "r"(dst), "l"(m), "r"(bar), "r"(c0), "r"(c1), "h"(mask) : "memory"); }
__device__ __forceinline__ void tma2d_store(const CUtensorMap* m, uint32_t src, int c0, int c1) {
  asm volatile("cp.async.bulk.tensor.2d.global.shared::cta.bulk_group [%0, {%2, %3}], [%1];" :: "l"(m), "r"(src), "r"(c0), "r"(c1) : "memory"); }
__device__ __forceinline__ void fence_async() { asm volatile("fence.proxy.async.shared::cta;" ::: "memory"); }
__device__ __forceinline__ void bar_sync(int id, int n) { asm volatile("bar.sync %0, %1;" :: "r"(id), "r"(n) : "memory"); }
__device__ __forceinline__ void bar_arrive(int id, int n) { asm volatile("bar.arrive %0, %1;" :: "r"(id), "r"(n) : "memory"); }
__device__ __forceinline__ uint32_t pack2(float lo, float hi) { uint32_t r; asm("cvt.rn.bf16x2.f32 %0, %1, %2;" : "=r"(r) : "f"(hi), "f"(lo)); return r; }
__device__ __forceinline__ uint32_t pack2_tag(float lo, float hi, uint32_t T) {
  uint32_t u = ((__float_as_uint(lo) - T + 0x10000u) & 0xFFFE0000u) + T;
  return __byte_perm(u, pack2(0.f, hi), 0x7632); }
__device__ __forceinline__ void ldsm4(uint32_t (&r)[4], uint32_t a) {
  asm volatile("ldmatrix.sync.aligned.m8n8.x4.shared.b16 {%0,%1,%2,%3}, [%4];" : "=r"(r[0]), "=r"(r[1]), "=r"(r[2]), "=r"(r[3]) : "r"(a) : "memory"); }
__device__ __forceinline__ void ldsm4t(uint32_t (&r)[4], uint32_t a) {
  asm volatile("ldmatrix.sync.aligned.m8n8.x4.trans.shared.b16 {%0,%1,%2,%3}, [%4];" : "=r"(r[0]), "=r"(r[1]), "=r"(r[2]), "=r"(r[3]) : "r"(a) : "memory"); }
__device__ __forceinline__ void stsm4(uint32_t a, uint32_t r0, uint32_t r1, uint32_t r2, uint32_t r3) {
  asm volatile("stmatrix.sync.aligned.m8n8.x4.shared.b16 [%0], {%1,%2,%3,%4};" :: "r"(a), "r"(r0), "r"(r1), "r"(r2), "r"(r3) : "memory"); }
__device__ __forceinline__ void stsm4t(uint32_t a, uint32_t r0, uint32_t r1, uint32_t r2, uint32_t r3) {
  asm volatile("stmatrix.sync.aligned.m8n8.x4.trans.shared.b16 [%0], {%1,%2,%3,%4};" :: "r"(a), "r"(r0), "r"(r1), "r"(r2), "r"(r3) : "memory"); }
__device__ __forceinline__ void lds128(uint32_t (&r)[4], uint32_t a) {
  asm volatile("ld.shared.v4.u32 {%0,%1,%2,%3}, [%4];" : "=r"(r[0]), "=r"(r[1]), "=r"(r[2]), "=r"(r[3]) : "r"(a) : "memory"); }
__device__ __forceinline__ float4 lds128f(uint32_t a) { float4 r;
  asm volatile("ld.shared.v4.f32 {%0,%1,%2,%3}, [%4];" : "=f"(r.x), "=f"(r.y), "=f"(r.z), "=f"(r.w) : "r"(a) : "memory"); return r; }
__device__ __forceinline__ float2 lds64f(uint32_t a) { float2 r;
  asm volatile("ld.shared.v2.f32 {%0,%1}, [%2];" : "=f"(r.x), "=f"(r.y) : "r"(a) : "memory"); return r; }
__device__ __forceinline__ void sts128(uint32_t a, uint32_t r0, uint32_t r1, uint32_t r2, uint32_t r3) {
  asm volatile("st.shared.v4.u32 [%0], {%1,%2,%3,%4};" :: "r"(a), "r"(r0), "r"(r1), "r"(r2), "r"(r3) : "memory"); }
__device__ __forceinline__ void sts64f(uint32_t a, float x, float y) { asm volatile("st.shared.v2.f32 [%0], {%1,%2};" :: "r"(a), "f"(x), "f"(y) : "memory"); }
__device__ __forceinline__ void sts32f(uint32_t a, float x) { asm volatile("st.shared.f32 [%0], %1;" :: "r"(a), "f"(x) : "memory"); }
__device__ __forceinline__ void mma16816(float (&d)[4], uint32_t a0, uint32_t a1, uint32_t a2, uint32_t a3, uint32_t b0, uint32_t b1) {
  asm volatile("mma.sync.aligned.m16n8k16.row.col.f32.bf16.bf16.f32 {%0,%1,%2,%3}, {%4,%5,%6,%7}, {%8,%9}, {%0,%1,%2,%3};"
    : "+f"(d[0]), "+f"(d[1]), "+f"(d[2]), "+f"(d[3]) : "r"(a0), "r"(a1), "r"(a2), "r"(a3), "r"(b0), "r"(b1)); }
__device__ __forceinline__ void mma1688(float (&d)[4], uint32_t a0, uint32_t a1, uint32_t b0) {
  asm volatile("mma.sync.aligned.m16n8k8.row.col.f32.bf16.bf16.f32 {%0,%1,%2,%3}, {%4,%5}, {%6}, {%0,%1,%2,%3};"
    : "+f"(d[0]), "+f"(d[1]), "+f"(d[2]), "+f"(d[3]) : "r"(a0), "r"(a1), "r"(b0)); }
__device__ __forceinline__ void ldx128(uint32_t (&r)[4], const void* p) {
  asm volatile("{.reg .b128 t; .reg .b64 a, b; ld.relaxed.gpu.global.b128 t, [%4]; mov.b128 {a, b}, t; mov.b64 {%0,%1}, a; mov.b64 {%2,%3}, b;}"
    : "=r"(r[0]), "=r"(r[1]), "=r"(r[2]), "=r"(r[3]) : "l"(p) : "memory"); }
__device__ __forceinline__ void ldx2x64(uint32_t (&r)[4], const void* p) {
  asm volatile("{.reg .b64 a, b; ld.relaxed.gpu.global.v2.b64 {a, b}, [%4]; mov.b64 {%0,%1}, a; mov.b64 {%2,%3}, b;}"
    : "=r"(r[0]), "=r"(r[1]), "=r"(r[2]), "=r"(r[3]) : "l"(p) : "memory"); }
__device__ __forceinline__ void stx128(void* p, uint32_t r0, uint32_t r1, uint32_t r2, uint32_t r3) {
  asm volatile("{.reg .b128 t; .reg .b64 a, b; mov.b64 a, {%1,%2}; mov.b64 b, {%3,%4}; mov.b128 t, {a, b}; st.relaxed.gpu.global.b128 [%0], t;}"
    :: "l"(p), "r"(r0), "r"(r1), "r"(r2), "r"(r3) : "memory"); }
__device__ __forceinline__ void stx64(void* p, uint32_t r0, uint32_t r1) {
  asm volatile("{.reg .b64 a; mov.b64 a, {%1,%2}; st.relaxed.gpu.global.b64 [%0], a;}" :: "l"(p), "r"(r0), "r"(r1) : "memory"); }
__device__ __forceinline__ uint32_t uni(uint32_t x) { return __shfl_sync(0xffffffffu, x, 0); }
__device__ __forceinline__ uint32_t pin(uint32_t x) { return __shfl_xor_sync(0xffffffffu, x, 0); }
__device__ __forceinline__ float ex2(float x) { float r; asm("ex2.approx.ftz.f32 %0, %1;" : "=f"(r) : "f"(x)); return r; }
__device__ __forceinline__ void wg_fence() { asm volatile("wgmma.fence.sync.aligned;" ::: "memory"); }
__device__ __forceinline__ void wg_commit() { asm volatile("wgmma.commit_group.sync.aligned;" ::: "memory"); }
template <int N> __device__ __forceinline__ void wg_wait() { asm volatile("wgmma.wait_group.sync.aligned %0;" :: "n"(N) : "memory"); }

__device__ __forceinline__ void wgmma_ss_n256_tb1(float (&d)[128], uint64_t da, uint64_t db, int sc) {
  asm volatile("{.reg .pred p; setp.ne.b32 p, %130, 0;\n"
    "wgmma.mma_async.sync.aligned.m64n256k16.f32.bf16.bf16 {%0,%1,%2,%3,%4,%5,%6,%7,%8,%9,%10,%11,%12,%13,%14,%15,%16,%17,%18,%19,%20,%21,%22,%23,%24,%25,%26,%27,%28,%29,%30,%31,%32,%33,%34,%35,%36,%37,%38,%39,%40,%41,%42,%43,%44,%45,%46,%47,%48,%49,%50,%51,%52,%53,%54,%55,%56,%57,%58,%59,%60,%61,%62,%63,%64,%65,%66,%67,%68,%69,%70,%71,%72,%73,%74,%75,%76,%77,%78,%79,%80,%81,%82,%83,%84,%85,%86,%87,%88,%89,%90,%91,%92,%93,%94,%95,%96,%97,%98,%99,%100,%101,%102,%103,%104,%105,%106,%107,%108,%109,%110,%111,%112,%113,%114,%115,%116,%117,%118,%119,%120,%121,%122,%123,%124,%125,%126,%127}, %128, %129, p, 1, 1, 0, 1;}\n"
    : "+f"(d[0]),"+f"(d[1]),"+f"(d[2]),"+f"(d[3]),"+f"(d[4]),"+f"(d[5]),"+f"(d[6]),"+f"(d[7]),"+f"(d[8]),"+f"(d[9]),"+f"(d[10]),"+f"(d[11]),"+f"(d[12]),"+f"(d[13]),"+f"(d[14]),"+f"(d[15]),"+f"(d[16]),"+f"(d[17]),"+f"(d[18]),"+f"(d[19]),"+f"(d[20]),"+f"(d[21]),"+f"(d[22]),"+f"(d[23]),"+f"(d[24]),"+f"(d[25]),"+f"(d[26]),"+f"(d[27]),"+f"(d[28]),"+f"(d[29]),"+f"(d[30]),"+f"(d[31]),"+f"(d[32]),"+f"(d[33]),"+f"(d[34]),"+f"(d[35]),"+f"(d[36]),"+f"(d[37]),"+f"(d[38]),"+f"(d[39]),"+f"(d[40]),"+f"(d[41]),"+f"(d[42]),"+f"(d[43]),"+f"(d[44]),"+f"(d[45]),"+f"(d[46]),"+f"(d[47]),"+f"(d[48]),"+f"(d[49]),"+f"(d[50]),"+f"(d[51]),"+f"(d[52]),"+f"(d[53]),"+f"(d[54]),"+f"(d[55]),"+f"(d[56]),"+f"(d[57]),"+f"(d[58]),"+f"(d[59]),"+f"(d[60]),"+f"(d[61]),"+f"(d[62]),"+f"(d[63]),"+f"(d[64]),"+f"(d[65]),"+f"(d[66]),"+f"(d[67]),"+f"(d[68]),"+f"(d[69]),"+f"(d[70]),"+f"(d[71]),"+f"(d[72]),"+f"(d[73]),"+f"(d[74]),"+f"(d[75]),"+f"(d[76]),"+f"(d[77]),"+f"(d[78]),"+f"(d[79]),"+f"(d[80]),"+f"(d[81]),"+f"(d[82]),"+f"(d[83]),"+f"(d[84]),"+f"(d[85]),"+f"(d[86]),"+f"(d[87]),"+f"(d[88]),"+f"(d[89]),"+f"(d[90]),"+f"(d[91]),"+f"(d[92]),"+f"(d[93]),"+f"(d[94]),"+f"(d[95]),"+f"(d[96]),"+f"(d[97]),"+f"(d[98]),"+f"(d[99]),"+f"(d[100]),"+f"(d[101]),"+f"(d[102]),"+f"(d[103]),"+f"(d[104]),"+f"(d[105]),"+f"(d[106]),"+f"(d[107]),"+f"(d[108]),"+f"(d[109]),"+f"(d[110]),"+f"(d[111]),"+f"(d[112]),"+f"(d[113]),"+f"(d[114]),"+f"(d[115]),"+f"(d[116]),"+f"(d[117]),"+f"(d[118]),"+f"(d[119]),"+f"(d[120]),"+f"(d[121]),"+f"(d[122]),"+f"(d[123]),"+f"(d[124]),"+f"(d[125]),"+f"(d[126]),"+f"(d[127])
    : "l"(da), "l"(db), "r"(sc));
}

__device__ __forceinline__ void wgmma_ss_n128_tb1(float (&d)[64], uint64_t da, uint64_t db, int sc) {
  asm volatile("{.reg .pred p; setp.ne.b32 p, %66, 0;\n"
    "wgmma.mma_async.sync.aligned.m64n128k16.f32.bf16.bf16 {%0,%1,%2,%3,%4,%5,%6,%7,%8,%9,%10,%11,%12,%13,%14,%15,%16,%17,%18,%19,%20,%21,%22,%23,%24,%25,%26,%27,%28,%29,%30,%31,%32,%33,%34,%35,%36,%37,%38,%39,%40,%41,%42,%43,%44,%45,%46,%47,%48,%49,%50,%51,%52,%53,%54,%55,%56,%57,%58,%59,%60,%61,%62,%63}, %64, %65, p, 1, 1, 0, 1;}\n"
    : "+f"(d[0]),"+f"(d[1]),"+f"(d[2]),"+f"(d[3]),"+f"(d[4]),"+f"(d[5]),"+f"(d[6]),"+f"(d[7]),"+f"(d[8]),"+f"(d[9]),"+f"(d[10]),"+f"(d[11]),"+f"(d[12]),"+f"(d[13]),"+f"(d[14]),"+f"(d[15]),"+f"(d[16]),"+f"(d[17]),"+f"(d[18]),"+f"(d[19]),"+f"(d[20]),"+f"(d[21]),"+f"(d[22]),"+f"(d[23]),"+f"(d[24]),"+f"(d[25]),"+f"(d[26]),"+f"(d[27]),"+f"(d[28]),"+f"(d[29]),"+f"(d[30]),"+f"(d[31]),"+f"(d[32]),"+f"(d[33]),"+f"(d[34]),"+f"(d[35]),"+f"(d[36]),"+f"(d[37]),"+f"(d[38]),"+f"(d[39]),"+f"(d[40]),"+f"(d[41]),"+f"(d[42]),"+f"(d[43]),"+f"(d[44]),"+f"(d[45]),"+f"(d[46]),"+f"(d[47]),"+f"(d[48]),"+f"(d[49]),"+f"(d[50]),"+f"(d[51]),"+f"(d[52]),"+f"(d[53]),"+f"(d[54]),"+f"(d[55]),"+f"(d[56]),"+f"(d[57]),"+f"(d[58]),"+f"(d[59]),"+f"(d[60]),"+f"(d[61]),"+f"(d[62]),"+f"(d[63])
    : "l"(da), "l"(db), "r"(sc));
}

template <int BN> struct WG;
template <> struct WG<256> { static __device__ __forceinline__ void mma(float (&d)[128], uint64_t a, uint64_t b, int sc) { wgmma_ss_n256_tb1(d, a, b, sc); } };
template <> struct WG<128> { static __device__ __forceinline__ void mma(float (&d)[64], uint64_t a, uint64_t b, int sc) { wgmma_ss_n128_tb1(d, a, b, sc); } };

struct GemmMaps { CUtensorMap a, b[3], c; };
template <int BN, int STAGES>
__global__ void __cluster_dims__(2, 1, 1) __launch_bounds__(384, 1)
gemm_kernel(const __grid_constant__ GemmMaps maps, int tilesM, int tilesN, int kblocks, int nPerB, int clearX) {
  extern __shared__ __align__(1024) uint8_t smem_raw[];
  constexpr int STAGE_BYTES = 16384 + BN * 128;
  constexpr int NBOX = BN / 64;
  const uint32_t sbase = (smem_u32(smem_raw) + 1023) & ~1023u;
  const uint32_t sEpi = sbase + STAGES * STAGE_BYTES;
  const uint32_t sBar = sEpi + 32768;
  const int warp = threadIdx.x >> 5, lane = threadIdx.x & 31, wg = warp >> 2;
  uint32_t crank; asm("mov.u32 %0, %%cluster_ctarank;" : "=r"(crank));
  if (threadIdx.x == 0) {
    for (int i = 0; i < STAGES; i++) { mbar_init(sBar + 8 * i, 1); mbar_init(sBar + 8 * (STAGES + i), 4); }
    asm volatile("fence.mbarrier_init.release.cluster;" ::: "memory");
  }
  if (clearX) {
    uint4* p = reinterpret_cast<uint4*>(&g_x);
    for (int i = blockIdx.x * 384 + threadIdx.x; i < (int)(sizeof(Xchg) / 16); i += gridDim.x * 384) p[i] = make_uint4(0, 0, 0, 0);
  }
  asm volatile("barrier.cluster.arrive.release.aligned; barrier.cluster.wait.acquire.aligned;" ::: "memory");
  const int npairs = (tilesM >> 1) * tilesN, pair0 = blockIdx.x >> 1, pstep = gridDim.x >> 1;
  if (wg == 2) {
    asm volatile("setmaxnreg.dec.sync.aligned.u32 40;");
    if (warp == 8 && lane == 0) {
      int st = 0, ph = 1;
      for (int p = pair0; p < npairs; p += pstep) {
        const int tm = (p % (tilesM >> 1)) * 2 + crank, tn = p / (tilesM >> 1);
        const CUtensorMap* mb = &maps.b[tn / nPerB];
        const int n0 = (tn % nPerB) * BN;
        for (int kb = 0; kb < kblocks; kb++) {
          mbar_wait(sBar + 8 * (STAGES + st), ph);
          const uint32_t a = sbase + st * STAGE_BYTES, full = sBar + 8 * st;
          mbar_expect_tx(full, STAGE_BYTES);
          tma2d(a, &maps.a, kb * 64, tm * 128, full);
#pragma unroll
          for (int i = 0; i < NBOX / 2; i++) {
            const int bx = crank * (NBOX / 2) + i;
            tma2d_mc(a + 16384 + bx * 8192, mb, n0 + bx * 64, kb * 64, full, (uint16_t)3);
          }
          if (++st == STAGES) { st = 0; ph ^= 1; }
        }
      }
      for (int i = 0; i < STAGES; i++) { mbar_wait(sBar + 8 * (STAGES + st), ph); if (++st == STAGES) { st = 0; ph ^= 1; } }
    }
  } else {
    asm volatile("setmaxnreg.inc.sync.aligned.u32 232;");
    int st = 0, ph = 0;
    float acc[BN / 2];
    const uint64_t descA0 = (uint64_t)(((sbase + wg * 8192) & 0x3FFFF) >> 4) | (1ull << 16) | (64ull << 32) | (1ull << 62);
    const uint64_t descB0 = (uint64_t)(((sbase + 16384) & 0x3FFFF) >> 4) | (512ull << 16) | (64ull << 32) | (1ull << 62);
    const uint32_t epi = sEpi + wg * 16384;
    for (int p = pair0; p < npairs; p += pstep) {
      const int tm = (p % (tilesM >> 1)) * 2 + crank, tn = p / (tilesM >> 1);
      int prev = -1;
      for (int kb = 0; kb < kblocks; kb++) {
        mbar_wait(sBar + 8 * st, ph);
        wg_fence();
        const uint64_t so = (uint64_t)(st * (STAGE_BYTES >> 4));
#pragma unroll
        for (int k = 0; k < 4; k++) WG<BN>::mma(acc, descA0 + so + k * 2, descB0 + so + k * 128, kb | k);
        wg_commit();
        if (prev >= 0) {
          wg_wait<1>();
          if ((threadIdx.x & 127) < 2) mbar_arrive_cluster(sBar + 8 * (STAGES + prev), threadIdx.x & 1);
        }
        prev = st;
        if (++st == STAGES) { st = 0; ph ^= 1; }
      }
      wg_wait<0>();
      if ((threadIdx.x & 127) < 2) mbar_arrive_cluster(sBar + 8 * (STAGES + prev), threadIdx.x & 1);
#pragma unroll
      for (int r = 0; r < BN / 128; r++) {
        if ((threadIdx.x & 127) == 0) asm volatile("cp.async.bulk.wait_group.read 0;" ::: "memory");
        bar_sync(1 + wg, 128);
        const int row = (warp & 3) * 16 + (lane & 15);
#pragma unroll
        for (int i = 0; i < 8; i++) {
          const int c = 2 * (i & 3) + (lane >> 4);
          const float* q = &acc[r * 64 + i * 8];
          stsm4(epi + (i >> 2) * 8192 + row * 128 + ((c ^ (row & 7)) << 4), pack2(q[0], q[1]), pack2(q[2], q[3]), pack2(q[4], q[5]), pack2(q[6], q[7]));
        }
        fence_async();
        bar_sync(1 + wg, 128);
        if ((threadIdx.x & 127) == 0) {
          tma2d_store(&maps.c, epi, tn * BN + r * 128, tm * 128 + wg * 64);
          tma2d_store(&maps.c, epi + 8192, tn * BN + r * 128 + 64, tm * 128 + wg * 64);
          asm volatile("cp.async.bulk.commit_group;" ::: "memory");
        }
      }
    }
    if ((threadIdx.x & 127) == 0) asm volatile("cp.async.bulk.wait_group 0;" ::: "memory");
  }
}

struct Dft { uint32_t m[2][2][2][4]; };
template <bool P4> __device__ __forceinline__ int fidx(int tile, int x) { return P4 ? 4 * (x >> 1) + 2 * (tile & 1) + (x & 1) + 16 * (tile >> 1) : x + 8 * tile; }
__device__ __forceinline__ float2 cis(int k, int n) {
  k &= n - 1; if (2 * k > n) k -= n;
  const float a = (float)k * (6.283185307179586f / (float)n);
  return make_float2(__cosf(a), __sinf(a));
}
template <bool OUT4> __device__ __forceinline__ void make_dft(Dft& D, int g, int t) {
#pragma unroll
  for (int q = 0; q < 16; q++) {
    const int b = q >> 3, u = (q >> 2) & 1, r = (q >> 1) & 1, v = q & 1;
    const float2 w = cis(fidx<OUT4>(v, g) * fidx<false>(2 * u + r, 2 * t + b), 32);
    D.m[b][u][0][q & 3] = pack2(w.x, w.y); D.m[b][u][1][q & 3] = pack2(-w.y, w.x);
  }
}
__device__ __forceinline__ void mma_dc(float (&d)[4], uint32_t a0, uint32_t a1, uint32_t a2, uint32_t a3, uint32_t b0, uint32_t b1, const float (&c)[4]) {
  asm("mma.sync.aligned.m16n8k16.row.col.f32.bf16.bf16.f32 {%0,%1,%2,%3}, {%4,%5,%6,%7}, {%8,%9}, {%10,%11,%12,%13};"
    : "=f"(d[0]), "=f"(d[1]), "=f"(d[2]), "=f"(d[3]) : "r"(a0), "r"(a1), "r"(a2), "r"(a3), "r"(b0), "r"(b1), "f"(c[0]), "f"(c[1]), "f"(c[2]), "f"(c[3])); }
__device__ __forceinline__ void dft_b(const Dft& D, const uint32_t (&x)[2][4], float (&o)[2][8]) {
#pragma unroll
  for (int ri = 0; ri < 2; ri++) {
    float z[4] = {0.f, 0.f, 0.f, 0.f}, e[4], p[4];
    mma_dc(e, D.m[0][0][ri][0], D.m[0][0][ri][1], D.m[0][0][ri][2], D.m[0][0][ri][3], x[0][0], x[0][1], z);
    mma_dc(e, D.m[0][1][ri][0], D.m[0][1][ri][1], D.m[0][1][ri][2], D.m[0][1][ri][3], x[0][2], x[0][3], e);
    mma_dc(p, D.m[1][0][ri][0], D.m[1][0][ri][1], D.m[1][0][ri][2], D.m[1][0][ri][3], x[1][0], x[1][1], e);
    mma_dc(p, D.m[1][1][ri][0], D.m[1][1][ri][1], D.m[1][1][ri][2], D.m[1][1][ri][3], x[1][2], x[1][3], p);
#pragma unroll
    for (int q = 0; q < 4; q++) { o[ri][q] = p[q]; o[ri][4 + q] = fmaf(2.f, e[q], -p[q]); }
  }
}
__device__ __forceinline__ void dft_a(const uint32_t (&m)[2][2][4], const uint32_t (&x0)[2][4], const uint32_t (&x1)[2][4], float (&o)[2][8]) {
#pragma unroll
  for (int ri = 0; ri < 2; ri++) {
    float z[4] = {0.f, 0.f, 0.f, 0.f}, e[4], p[4];
    mma_dc(e, x0[0][0], x1[0][0], x0[0][1], x1[0][1], m[0][ri][0], m[0][ri][1], z);
    mma_dc(e, x0[0][2], x1[0][2], x0[0][3], x1[0][3], m[0][ri][2], m[0][ri][3], e);
    mma_dc(p, x0[1][0], x1[1][0], x0[1][1], x1[1][1], m[1][ri][0], m[1][ri][1], e);
    mma_dc(p, x0[1][2], x1[1][2], x0[1][3], x1[1][3], m[1][ri][2], m[1][ri][3], p);
#pragma unroll
    for (int q = 0; q < 4; q++) { o[ri][q] = p[q]; o[ri][4 + q] = fmaf(2.f, e[q], -p[q]); }
  }
}
__device__ __forceinline__ uint32_t twid(float re, float im, float c, float s) { return pack2(fmaf(re, c, im * s), fmaf(im, c, -re * s)); }
__device__ __forceinline__ void cpa16(uint32_t d, const void* s) { asm volatile("cp.async.cg.shared.global [%0], [%1], 16;" :: "r"(d), "l"(s) : "memory"); }
__device__ __forceinline__ void sts32(uint32_t a, uint32_t x) { asm volatile("st.shared.u32 [%0], %1;" :: "r"(a), "r"(x) : "memory"); }
__device__ __forceinline__ void cpa_commit() { asm volatile("cp.async.commit_group;" ::: "memory"); }
template <int N> __device__ __forceinline__ void cpa_wait() { asm volatile("cp.async.wait_group %0;" :: "n"(N) : "memory"); }
__device__ __forceinline__ uint32_t lds32(uint32_t a) { uint32_t r; asm volatile("ld.shared.u32 %0, [%1];" : "=r"(r) : "r"(a) : "memory"); return r; }
constexpr int F_TP = 4112, F_TSZ = 8 * F_TP;

__device__ __forceinline__ void fft_wprep(const bf16* __restrict__ wr, const bf16* __restrict__ wi, int cta, int ncta) {
  const int tid = threadIdx.x;
#pragma unroll 2
  for (int it = cta; it < 256; it += ncta) {
    const int g = (it >> 1) & 7, c = (it >> 4) & 3, i = it >> 6, t = 2 * (it & 1) + (tid & 1);
    const int k0 = g + 8 * i + 32 * (8 * c + 2 * t), l0 = (tid & ~1) + (g & 1);
    uint32_t a[2][4], b[2][4];
#pragma unroll
    for (int q = 0; q < 8; q++) {
      const int o = (k0 + 32 * ((q >> 1) & 1) + 1024 * (q & 1)) * 513 + l0 + 256 * (q >> 2);
      a[q >> 2][q & 3] = __ldg(reinterpret_cast<const uint32_t*>(wr + o));
      b[q >> 2][q & 3] = __ldg(reinterpret_cast<const uint32_t*>(wi + o));
    }
    uint4* dst = g_wt + l0 * 512 + it * 2 + (tid & 1);
#pragma unroll
    for (int q = 0; q < 4; q++) {
      const int hf = q >> 1, l = l0 + 256 * hf + (q & 1);
      const uint32_t sel = (q & 1) ? 0x7632 : 0x5410;
      if (l & 511) dst[(256 * hf + (q & 1)) * 512] = make_uint4(__byte_perm(a[hf][0], b[hf][0], sel), __byte_perm(a[hf][1], b[hf][1], sel),
                                                              __byte_perm(a[hf][2], b[hf][2], sel), __byte_perm(a[hf][3], b[hf][3], sel));
    }
  }
  for (int e = cta * 256 + tid; e < 4096; e += ncta * 256) {
    const int l = (e >> 11) * 512, k = e & 2047, kn = (2048 - k) & 2047, k2 = (k >> 5) & 31;
    const float re = 0.5f * (__bfloat162float(wr[k * 513 + l]) + __bfloat162float(wr[kn * 513 + l]));
    const float im = 0.5f * (__bfloat162float(wi[k * 513 + l]) - __bfloat162float(wi[kn * 513 + l]));
    reinterpret_cast<uint32_t*>(g_wt)[(64 * ((k >> 3) & 3) + 16 * (k2 >> 3) + 2 * (k & 7) + ((k2 >> 2) & 1)) * 8 + l * 2048 + 2 * (k2 & 3) + (k >> 10)] = pack2(re, im);
  }
}

__device__ __forceinline__ void fft_rows_fwd(const bf16* __restrict__ x, uint32_t sb, int cta, int ncta) {
  const int warp = threadIdx.x >> 5, lane = threadIdx.x & 31, g = lane >> 2, t = lane & 3;
  const uint32_t in = sb + warp * 8192, tb = sb + 65536;
  const uint32_t f0 = pin(in + (lane >> 3) * 256 + (((lane & 7) ^ (2 * (lane >> 3))) << 4));
  const uint32_t xo = pin((256 * (warp & 3) + 64 * (warp >> 2)) * 2048 + lane * 8);
  auto fetch = [&](int it, int buf) {
    const bf16* src = x + (xo + (128 * (it & 1) + 32 * ((it >> 4) & 1) + 8 * (it >> 5) + ((it >> 1) & 7)) * 2048);
#pragma unroll
    for (int q = 0; q < 8; q++) cpa16(((f0 + buf * 4096) ^ ((q >> 2) * 144)) + (q & 3) * 1024, src + q * 256);
    cpa_commit();
  };
  fetch(cta, 0);
  Dft D; make_dft<true>(D, g, t);
  float2 tw[4][8];
#pragma unroll
  for (int q = 0; q < 32; q++) tw[q >> 3][q & 7] = cis(fidx<true>((q >> 1) & 3, g) * fidx<false>(q >> 3, 2 * t + (q & 1)), 1024);
  const uint32_t la = pin(in + lane * 128 + ((lane & 7) << 4));
  const uint32_t wa = pin(tb + warp * F_TP + fidx<true>(0, g) * 128 + t * 16), wz = pin((g & 1) ? -64 : 64);
  const uint32_t ra = pin(tb + (lane & 1) * 4 * F_TP + ((lane >> 1) + 16 * (warp ^ ((warp >> 1) & 1))) * 4);
  uint4* dst = g_y + (threadIdx.x >> 1) * 256 + (lane & 1);
  int buf = 0;
  auto drain = [&](int it, int q) {
    const uint32_t r = ra + (buf ^ 1) * F_TSZ + q * 512;
    const uint4 v = make_uint4(lds32(r), lds32(r + F_TP), lds32(r + 2 * F_TP), lds32(r + 3 * F_TP));
    if (it >= 0) dst[it * 2 + q * 32768] = v;
  };
  int it = cta;
#pragma unroll 1
  for (; it < 128; it += ncta, buf ^= 1) {
    cpa_wait<0>(); __syncthreads();
    uint32_t a[4][2][4], y[4][2][4];
#pragma unroll
    for (int q = 0; q < 8; q++) ldsm4t(a[q & 3][q >> 2], (la + buf * 4096) ^ (q << 4));
    if (it + ncta < 128) fetch(it + ncta, buf ^ 1);
    float o[2][8];
#pragma unroll
    for (int i = 0; i < 4; i++) {
      dft_b(D, a[i], o);
      drain(it - ncta, i);
#pragma unroll
      for (int q = 0; q < 8; q++) y[q >> 1][q & 1][i] = twid(o[0][q], o[1][q], tw[i][q].x, tw[i][q].y);
    }
    const uint32_t w0 = wa + buf * F_TSZ + ((g & 1) << 6);
#pragma unroll
    for (int z = 0; z < 2; z++) {
      float o2[2][8];
      dft_b(D, y[2 * z], o); drain(it - ncta, 4 + 2 * z); dft_b(D, y[2 * z + 1], o2); drain(it - ncta, 5 + 2 * z);
#pragma unroll
      for (int i = 0; i < 4; i++) {
        const float sg = i < 2 ? 1.f : -1.f;
        sts128(w0 + z * wz + fidx<true>(i, 0) * 128, pack2(o[0][2 * i], sg * o[1][2 * i]), pack2(o[0][2 * i + 1], sg * o[1][2 * i + 1]),
               pack2(o2[0][2 * i], sg * o2[1][2 * i]), pack2(o2[0][2 * i + 1], sg * o2[1][2 * i + 1]));
      }
    }
  }
  __syncthreads();
#pragma unroll
  for (int q = 0; q < 8; q++) drain(it - ncta, q);
}

__device__ __forceinline__ void fft_cols(uint32_t sb, int cta, int ncta) {
  const int warp = threadIdx.x >> 5, lane = threadIdx.x & 31, g = lane >> 2, t = lane & 3;
  const uint32_t in = sb + warp * 16384 + lane * 16, tab = sb + 131072 + lane * 16;
  auto fetch_y = [&](int l) {
#pragma unroll
    for (int q = 0; q < 16; q++) cpa16(in + q * 512, g_y + (q < 8 ? l : (1024 - l) & 1023) * 256 + (q & 7) * 32 + lane);
  };
  auto fetch_w = [&](int l) {
#pragma unroll
    for (int q = 0; q < 16; q++) cpa16(in + 8192 + q * 512, g_wt + l * 512 + q * 32 + lane);
  };
  const int l0 = cta * 8 + warp, dl = ncta * 8;
  if (l0 <= 512) fetch_y(l0);
  cpa_commit();
  if (l0 <= 512) fetch_w(l0);
  cpa_commit();
  Dft D; make_dft<false>(D, g, t);
#pragma unroll
  for (int q = 2 * warp; q < 2 * warp + 2; q++) {
    const int r = fidx<false>(q & 3, g), c = fidx<false>(q >> 2, 2 * t);
    const float2 w0 = cis(r * c, 1024), w1 = cis(r * c + r, 1024), p0 = cis(r + 32 * c, 2048), p1 = cis(r + 32 * c + 32, 2048);
    sts128(tab + q * 512, __float_as_uint(w0.x), __float_as_uint(w0.y), __float_as_uint(w1.x), __float_as_uint(w1.y));
    sts128(tab + 8192 + q * 512, __float_as_uint(p0.x), __float_as_uint(p0.y), __float_as_uint(p1.x), __float_as_uint(p1.y));
  }
  if (warp == 0) {
#pragma unroll
    for (int q = 0; q < 8; q++) {
      const int v = q >> 2, b = (q >> 1) & 1, ri = q & 1;
      sts128(tab + 16384 + q * 512, D.m[b][0][ri][v], D.m[b][0][ri][v + 2], D.m[b][1][ri][v], D.m[b][1][ri][v + 2]);
    }
  }
  __syncthreads();
#pragma unroll 1
  for (int l = l0; l <= 512; l += dl) {
    uint32_t a[2][4][2][4], y[2][4][2][4];
    float o[2][2][8];
    cpa_wait<1>();
#pragma unroll
    for (int q = 0; q < 16; q++) lds128(a[q >> 3][(q >> 1) & 3][q & 1], in + q * 512);
    if (!(l & 511)) {
      const uint32_t m0 = l ? 0x80000000u : 0u;
#pragma unroll
      for (int q = 0; q < 32; q++) { a[0][q >> 3][(q >> 2) & 1][q & 3] ^= m0; a[1][q >> 3][(q >> 2) & 1][q & 3] ^= m0 ^ 0x80000000u; }
    }
    auto first = [&]() {
#pragma unroll
      for (int i = 0; i < 4; i++) {
        dft_b(D, a[0][i], o[0]); dft_b(D, a[1][i], o[1]);
#pragma unroll
        for (int r = 0; r < 4; r++) {
          const float4 w = lds128f(tab + (4 * i + r) * 512);
#pragma unroll
          for (int s = 0; s < 2; s++) {
            y[s][r][0][i] = twid(o[s][0][2 * r], o[s][1][2 * r], w.x, w.y);
            y[s][r][1][i] = twid(o[s][0][2 * r + 1], o[s][1][2 * r + 1], w.z, w.w);
          }
        }
      }
    };
    first();
    if (l + dl <= 512) fetch_y(l + dl);
    cpa_commit();
    cpa_wait<1>();
#pragma unroll
    for (int zv = 0; zv < 4; zv++) {
      const int z = zv >> 1, v = zv & 1;
      uint32_t m[2][2][4];
#pragma unroll
      for (int q = 0; q < 4; q++) lds128(m[q >> 1][q & 1], tab + 16384 + (4 * v + q) * 512);
      dft_a(m, y[0][2 * z], y[0][2 * z + 1], o[0]); dft_a(m, y[1][2 * z], y[1][2 * z + 1], o[1]);
#pragma unroll
      for (int q = 0; q < 4; q++) {
        const int i = 2 * z + (q & 1), c = v + (q & 2);
        uint32_t w[4]; lds128(w, in + 8192 + (4 * i + c) * 512);
        const float4 ph = lds128f(tab + 8192 + (4 * c + i) * 512);
#pragma unroll
        for (int b = 0; b < 2; b++) {
          const float cs = b ? ph.z : ph.x, sn = b ? ph.w : ph.y;
          const float r1 = __uint_as_float(w[2 * b] << 16), i1 = __uint_as_float(w[2 * b] & 0xFFFF0000u);
          const float r2 = __uint_as_float(w[2 * b + 1] << 16), i2 = __uint_as_float(w[2 * b + 1] & 0xFFFF0000u);
          const float Sr = r1 + r2, Si = i1 + i2, Dr = r1 - r2, Di = i1 - i2;
          const float ar = fmaf(-Dr, sn, Sr), ai = fmaf(-Di, sn, Si), dr = fmaf(Dr, sn, Sr), di = fmaf(Di, sn, Si), br = -Di * cs, bi = Dr * cs;
          const float Ar = o[0][0][2 * q + b], Ai = o[0][1][2 * q + b], Br = o[1][0][2 * q + b], Bi = o[1][1][2 * q + b];
          a[0][i][b][c] = pack2(fmaf(ar, Ai, fmaf(ai, Ar, fmaf(br, Bi, bi * Br))), fmaf(ar, Ar, fmaf(-ai, Ai, fmaf(br, Br, -bi * Bi))));
          a[1][i][b][c] = pack2(fmaf(dr, Bi, fmaf(di, Br, fmaf(-br, Ai, -bi * Ar))), fmaf(dr, Br, fmaf(-di, Bi, fmaf(-br, Ar, bi * Ai))));
        }
      }
    }
    if (l + dl <= 512) fetch_w(l + dl);
    cpa_commit();
    first();
#pragma unroll
    for (int s = 0; s < 2; s++) {
      uint4* dst = g_y + (s ? (1024 - l) & 1023 : l) * 256 + lane;
      const float sg = s ? -1.f : 1.f;
#pragma unroll
      for (int i = 0; i < 4; i++) {
        dft_b(D, y[s][i], o[0]);
#pragma unroll
        for (int b = 0; b < 2; b++)
          dst[(2 * i + b) * 32] = make_uint4(pack2(sg * o[0][0][b], o[0][1][b]), pack2(sg * o[0][0][2 + b], o[0][1][2 + b]),
                                             pack2(sg * o[0][0][4 + b], o[0][1][4 + b]), pack2(sg * o[0][0][6 + b], o[0][1][6 + b]));
      }
    }
  }
}

__device__ __forceinline__ void fft_rows_inv(const CUtensorMap* om, uint32_t sb, int cta, int ncta) {
  const int warp = threadIdx.x >> 5, lane = threadIdx.x & 31, g = lane >> 2, t = lane & 3, wg = warp >> 2, w4 = warp & 3;
  const uint32_t tb = sb + 32768 + wg * 2 * F_TSZ;
  const uint4* src = g_y + pin((256 * ((lane >> 1) & 3) + 64 * (lane >> 3) + 8 * w4) * 256 + (lane & 1));
  const uint32_t wa = pin(tb + (lane & 1) * 4 * F_TP + w4 * 1024 + (lane >> 1) * 4);
  uint4 pf[8];
  auto fetch = [&](int it, int hf) {
#pragma unroll
    for (int q = 0; q < 8; q++) pf[q] = __ldcg(src + (it * 2 + hf * 8192) + q * 256);
  };
  auto put = [&](uint32_t off) {
#pragma unroll
    for (int q = 0; q < 8; q++) {
      sts32(wa + off + q * 64, pf[q].x); sts32(wa + off + q * 64 + F_TP, pf[q].y);
      sts32(wa + off + q * 64 + 2 * F_TP, pf[q].z); sts32(wa + off + q * 64 + 3 * F_TP, pf[q].w);
    }
  };
  const int it0 = 2 * cta + wg;
  if (it0 >= 128) return;
  fetch(it0, 0); put(0); fetch(it0, 1); put(512);
  Dft D; make_dft<false>(D, g, t);
  float2 tw[4][8];
#pragma unroll
  for (int q = 0; q < 32; q++) {
    tw[q >> 3][q & 7] = cis(fidx<false>((q >> 1) & 3, g) * fidx<false>(q >> 3, 2 * t + (q & 1)), 1024);
    tw[q >> 3][q & 7].x *= 1.f / 2097152.f; tw[q >> 3][q & 7].y *= 1.f / 2097152.f;
  }
  const uint32_t la = pin(tb + w4 * F_TP + lane * 16), ob = uni(sb + warp * 4096);
  const uint32_t oa = pin(ob + (lane >> 1) * 128 + (((4 * (lane & 1)) ^ ((lane >> 1) & 7)) << 4));
#pragma unroll 1
  for (int n = 0;; n++) {
    const int it = it0 + (n >> 1) * 2 * ncta, hf = n & 1, buf = (n >> 1) & 1;
    if (it >= 128) break;
    if (!hf) bar_sync(1 + wg, 128);
    uint32_t a[4][2][4], y[4][2][4];
#pragma unroll
    for (int q = 0; q < 8; q++) lds128(a[q >> 1][q & 1], la + buf * F_TSZ + hf * 4 * F_TP + q * 512);
    fetch(min(it + 2 * ncta, 127), hf);
    float o[2][8];
#pragma unroll
    for (int i = 0; i < 4; i++) {
      dft_b(D, a[i], o);
#pragma unroll
      for (int q = 0; q < 8; q++) y[q >> 1][q & 1][i] = twid(o[0][q], o[1][q], tw[i][q].x, tw[i][q].y);
    }
    if (lane == 0) asm volatile("cp.async.bulk.wait_group.read 0;" ::: "memory");
    __syncwarp();
#pragma unroll
    for (int c = 0; c < 4; c++) {
      dft_b(D, y[c], o);
#pragma unroll
      for (int ri = 0; ri < 2; ri++)
        stsm4((oa ^ (c << 4)) + (1 - ri) * 2048, pack2(o[ri][0], o[ri][1]), pack2(o[ri][2], o[ri][3]), pack2(o[ri][4], o[ri][5]), pack2(o[ri][6], o[ri][7]));
    }
    fence_async();
    __syncwarp();
    if (lane == 0) {
      const int m = 256 * w4 + 32 * ((it >> 1) & 7) + 8 * (it >> 5) + 4 * (it & 1) + 2 * hf + ((it >> 4) & 1);
      asm volatile("cp.async.bulk.tensor.3d.global.shared::cta.bulk_group [%0, {0, 0, %2}], [%1];" :: "l"(om), "r"(ob), "r"(2 * m) : "memory");
      asm volatile("cp.async.bulk.commit_group;" ::: "memory");
    }
    put((buf ^ 1) * F_TSZ + hf * 512);
  }
  if (lane == 0) asm volatile("cp.async.bulk.wait_group 0;" ::: "memory");
}
constexpr int F_SMEM = 65536 + 2 * F_TSZ + 1024;
__global__ void __launch_bounds__(256, 1) fft_pre_kernel(const bf16* __restrict__ x, const bf16* __restrict__ wr, const bf16* __restrict__ wi) {
  extern __shared__ __align__(1024) uint8_t smem_raw[];
  const uint32_t sb = (smem_u32(smem_raw) + 1023) & ~1023u;
  fft_wprep(wr, wi, blockIdx.x, gridDim.x);
  fft_rows_fwd(x, sb, blockIdx.x, gridDim.x);
}
__device__ __forceinline__ void grid_arrive(unsigned* ctr) {
  __syncthreads();
  if (threadIdx.x == 0) { __threadfence(); atomicAdd(ctr, 1u); }
}
__device__ __forceinline__ void grid_wait(unsigned* ctr, unsigned n) {
  if (threadIdx.x == 0) {
    int it = 0;
    while (*reinterpret_cast<volatile unsigned*>(ctr) < n) { __nanosleep(200); if (++it > SPIN_LIMIT) { g_err = 3; break; } }
    __threadfence();
  }
  __syncthreads();
}

struct RecMaps { CUtensorMap wq, wk, wv, wo, x, k, q, v, fo; };
#define NSW 16
#define EXP 0
#define PD1 4
#define NE4 6
#define NE6 0
#define NA4 14
#define NA6 18
#define NB1 24
#define OXPOS 28
#define KVPOS 2
#define NK0 0
#define FLPOS 1
#define XWPOS 10
#define FSPOS 28
#define RL0 4
#define RLS 6
#define RLB 4
#define VL0 3
#define RI 10
#define RJ 8
#define NPRE 0
#define UNP 16
#define XC 2
#define XD 2
#define SPOS 2
#ifndef NV0
#define NV0 1
#endif
#define TGP 3
#define FENP 0
#define LW0 8
#define XB 2
#define XA 4
constexpr int R_WO = 0, R_X = 65536, R_MEM = 131072, R_WC = 147456, R_RED = R_WC + NSW * 2048, R_O = R_RED + 2048, R_S = R_O + 2048, R_P = R_S + 3072, R_STAGE = R_P + 2048,
              R_K = R_STAGE + 8192, R_Q = R_K + 8192, R_V = R_Q + 2048, R_ID = R_V + 16384, R_T = R_ID + 512, R_BAR = R_T + 512, R_TS = R_BAR + 128,
              R_TOTAL = R_TS;
#define TS(i)
#define LOG(i, v)
constexpr int B_KV = R_BAR, B_W = R_BAR + 8, B_X = R_BAR + 80, B_PK = R_BAR + 24, B_C = R_BAR + 32, B_B = R_BAR + 40, B_DUE = R_BAR + 48, B_ONE = R_BAR + 64;
#define DLY_A 150
#define DLY_V 150
#define DLY_C 100
#define DLY_L 90
#define NS_B 1280
#define NS_C 1920
#define NS_P 3008
#define NS_V 128
#define NS_F (NS_B - 192)
#define NS_K 128
#define NS_M 64
#define NS_X 128
#define NS_PEN 576
__device__ __forceinline__ float rcp(float x) { float r; asm("rcp.approx.ftz.f32 %0, %1;" : "=f"(r) : "f"(x)); return r; }
__device__ __forceinline__ uint32_t movm(uint32_t a) { uint32_t d; asm volatile("movmatrix.sync.aligned.m8n8.trans.b16 %0, %1;" : "=r"(d) : "r"(a)); return d; }
__device__ __forceinline__ uint32_t hadd2(uint32_t a, uint32_t b) { uint32_t d; asm("add.rn.bf16x2 %0, %1, %2;" : "=r"(d) : "r"(a), "r"(b)); return d; }
__device__ __forceinline__ void mma_a(float (&d)[4], const uint32_t (&a)[4], uint32_t b0, uint32_t b1) { mma16816(d, a[0], a[1], a[2], a[3], b0, b1); }
__device__ __forceinline__ bool elect() {
  uint32_t p; asm volatile("{.reg .pred p; elect.sync _|p, 0xffffffff; selp.u32 %0, 1, 0, p;}" : "=r"(p)); return p; }
__device__ __forceinline__ void tma3d(uint32_t dst, const CUtensorMap* m, int c1, int c2, uint32_t bar) {
  asm volatile("cp.async.bulk.tensor.3d.shared::cluster.global.mbarrier::complete_tx::bytes [%0], [%1, {0, %3, %4}], [%2];"
    :: "r"(dst), "l"(m), "r"(bar), "r"(c1), "r"(c2) : "memory"); }
__device__ __forceinline__ void tma4d(uint32_t dst, const CUtensorMap* m, int c1, int c2, uint32_t bar) {
  asm volatile("cp.async.bulk.tensor.4d.shared::cluster.global.mbarrier::complete_tx::bytes [%0], [%1, {0, %3, %4, 0}], [%2];"
    :: "r"(dst), "l"(m), "r"(bar), "r"(c1), "r"(c2) : "memory"); }
template <int OFF, int ACC>
__device__ __forceinline__ void wg_rs32(float (&d)[16], const uint32_t (&a)[4], uint32_t db) {
  if (ACC)
    asm volatile("{.reg .b64 db; .reg .b32 lo; add.u32 lo, %20, %21; mov.b64 db, {lo, 0x40000040};\n"
      "wgmma.mma_async.sync.aligned.m64n32k16.f32.bf16.bf16 {%0,%1,%2,%3,%4,%5,%6,%7,%8,%9,%10,%11,%12,%13,%14,%15}, {%16,%17,%18,%19}, db, 1, 1, 1, 0;}"
      : "+f"(d[0]), "+f"(d[1]), "+f"(d[2]), "+f"(d[3]), "+f"(d[4]), "+f"(d[5]), "+f"(d[6]), "+f"(d[7]), "+f"(d[8]), "+f"(d[9]), "+f"(d[10]), "+f"(d[11]), "+f"(d[12]), "+f"(d[13]), "+f"(d[14]), "+f"(d[15])
      : "r"(a[0]), "r"(a[1]), "r"(a[2]), "r"(a[3]), "r"(db), "n"(OFF));
  else
    asm volatile("{.reg .b64 db; .reg .b32 lo; add.u32 lo, %20, %21; mov.b64 db, {lo, 0x40000040};\n"
      "wgmma.mma_async.sync.aligned.m64n32k16.f32.bf16.bf16 {%0,%1,%2,%3,%4,%5,%6,%7,%8,%9,%10,%11,%12,%13,%14,%15}, {%16,%17,%18,%19}, db, 0, 1, 1, 0;}"
      : "=f"(d[0]), "=f"(d[1]), "=f"(d[2]), "=f"(d[3]), "=f"(d[4]), "=f"(d[5]), "=f"(d[6]), "=f"(d[7]), "=f"(d[8]), "=f"(d[9]), "=f"(d[10]), "=f"(d[11]), "=f"(d[12]), "=f"(d[13]), "=f"(d[14]), "=f"(d[15])
      : "r"(a[0]), "r"(a[1]), "r"(a[2]), "r"(a[3]), "r"(db), "n"(OFF));
}
template <int I> using IC = std::integral_constant<int, I>;
template <int I, int N, class F> __device__ __forceinline__ void sfor(F&& f) {
  if constexpr (I < N) { f(std::integral_constant<int, I>{}); sfor<I + 1, N>(f); }
}
__device__ __forceinline__ void keep(float (&d)[16]) {
  asm volatile("" : "+f"(d[0]), "+f"(d[1]), "+f"(d[2]), "+f"(d[3]), "+f"(d[4]), "+f"(d[5]), "+f"(d[6]), "+f"(d[7]),
      "+f"(d[8]), "+f"(d[9]), "+f"(d[10]), "+f"(d[11]), "+f"(d[12]), "+f"(d[13]), "+f"(d[14]), "+f"(d[15]) :: "memory");
}

template <int N, int S2 = 1024> __device__ __forceinline__ void ldx(uint32_t (&v)[N][4], const uint8_t* p) {
#pragma unroll
  for (int i = 0; i < 2 * N; i++)
    asm volatile("ld.relaxed.gpu.global.v2.b32 {%0,%1}, [%2];" : "=r"(v[i >> 1][2 * (i & 1)]), "=r"(v[i >> 1][2 * (i & 1) + 1]) : "l"(p + (i & 3) * 256 + (i >> 2) * S2) : "memory");
}
__device__ __forceinline__ uint32_t dif2(uint32_t a, uint32_t b, uint32_t tag) { uint32_t r; asm("lop3.b32 %0, %1, %2, %3, 0x7e;" : "=r"(r) : "r"(a), "r"(b), "r"(tag)); return r; }
__device__ __forceinline__ uint32_t dif2v(uint32_t a, uint32_t b, uint32_t tag) { uint32_t r; asm volatile("lop3.b32 %0, %1, %2, %3, 0x7e;" : "=r"(r) : "r"(a), "r"(b), "r"(tag)); return r; }
__device__ __forceinline__ uint32_t or3(uint32_t a, uint32_t b, uint32_t c) { uint32_t r; asm("lop3.b32 %0, %1, %2, %3, 0xfe;" : "=r"(r) : "r"(a), "r"(b), "r"(c)); return r; }
__device__ __forceinline__ uint32_t after(uint32_t x, float f, uint32_t z) { uint32_t r; asm("lop3.b32 %0, %1, %2, %3, 0xea;" : "=r"(r) : "r"(__float_as_uint(f)), "r"(z), "r"(x)); return r; }
__device__ __forceinline__ bool any_bit(uint32_t a, uint32_t b, uint32_t m) {
  uint32_t r; asm("lop3.b32 %0, %1, %2, %3, 0xa8;" : "=r"(r) : "r"(a), "r"(b), "r"(m)); return __any_sync(0xffffffffu, r); }
template <int W, int N> __device__ __forceinline__ bool stale(const uint32_t (&v)[N][4], uint32_t tag) {
  uint32_t x = dif2(v[0][0], v[0][2], tag);
  if (N == 4) x = or3(x, dif2(v[1][0], v[1][2], tag), dif2(v[2 % N][0], v[2 % N][2], tag));
  return any_bit(x, dif2(v[N - 1][0], v[N - 1][2], tag), 1);
}
template <int W, int N, int S2 = 1024> __device__ __forceinline__ void retry(uint32_t (&v)[N][4], const uint8_t* p, uint32_t tag, int& it) {
#pragma unroll 1
  do { ldx<N, S2>(v, p); it += INC_A; } while (stale<W>(v, tag) && it < SPIN_LIMIT);
}
__device__ __forceinline__ void mma_h(float (&d)[4], const uint32_t (&a)[4], const uint32_t (&b)[4], int hf) { mma16816(d, a[0], a[1], a[2], a[3], b[2 * hf], b[2 * hf + 1]); }
__device__ __forceinline__ void sts128(uint32_t a, const uint32_t (&r)[4]) { sts128(a, r[0], r[1], r[2], r[3]); }
__device__ __forceinline__ void sts128f(uint32_t a, const float* r) { sts128(a, __float_as_uint(r[0]), __float_as_uint(r[1]), __float_as_uint(r[2]), __float_as_uint(r[3])); }
__device__ __forceinline__ void mbar_spin(uint32_t bar, uint32_t par, int& it) {
  asm volatile("{.reg .pred p; .reg .b32 par; mov.b32 par, %2;\nLOOP: mbarrier.try_wait.parity.shared::cta.b64 p, [%1], par; @p bra.uni DONE;\n"
               "add.s32 %0, %0, 1; setp.le.s32 p, %0, %3; @p bra.uni LOOP;\nDONE: }" : "+r"(it) : "r"(bar), "r"(par), "n"(SPIN_LIMIT) : "memory"); }
__device__ __forceinline__ void warp_arrive(uint32_t bar) {
  __syncwarp(); asm volatile("{.reg .pred p; elect.sync _|p, 0xffffffff; @p mbarrier.arrive.shared::cta.b64 _, [%0];}" :: "r"(bar) : "memory"); }
__device__ __forceinline__ void delay_until(unsigned t) {
  asm volatile("{.reg .pred p; .reg .b64 c; .reg .b32 lo, hi;\nLOOP: mov.u64 c, %%clock64; mov.b64 {lo, hi}, c; sub.s32 lo, lo, %0; setp.lt.s32 p, lo, 0; @p bra.uni LOOP;}" :: "r"(t) : "memory"); }
__device__ __forceinline__ void cut(int it) { asm volatile("{.reg .pred p; setp.lt.s32 p, %0, 0;\nL: @p st.volatile.shared.u32 [%0], %0; @p bra.uni L;}" :: "r"(it) : "memory"); }
__device__ __forceinline__ void zero(float (&c)[4][4]) {
#pragma unroll
  for (int i = 0; i < 4; i++) c[i][0] = c[i][1] = c[i][2] = c[i][3] = 0.f;
}

__device__ __forceinline__ void sched() { asm volatile("griddepcontrol.launch_dependents;" ::: "memory"); }
__device__ __forceinline__ const uint8_t* pinp(const uint8_t* p) { return reinterpret_cast<const uint8_t*>(__shfl_xor_sync(0xffffffffu, reinterpret_cast<unsigned long long>(p), 0)); }
__device__ __forceinline__ uint32_t bar_or(int id, uint32_t x) {
  uint32_t r; asm volatile("{.reg .pred p, q; setp.ne.u32 p, %2, 0; bar.red.or.pred q, %1, 256, p; selp.u32 %0, 1, 0, q;}" : "=r"(r) : "r"(id), "r"(x) : "memory"); return r; }
__device__ __forceinline__ void bar_sync_unless(int id, uint32_t x) { asm volatile("{.reg .pred p; setp.eq.u32 p, %1, 0; @p bar.sync %0, 256;}" :: "r"(id), "r"((uint32_t)x) : "memory"); }
__device__ __forceinline__ void bar_arrive_unless(int id, uint32_t x) { asm volatile("{.reg .pred p; setp.eq.u32 p, %1, 0; @p bar.arrive %0, 256;}" :: "r"(id), "r"((uint32_t)x) : "memory"); }
__device__ __forceinline__ void stsm2t(uint32_t a, uint32_t r0, uint32_t r1, uint32_t x) {
  asm volatile("{.reg .pred p; setp.eq.u32 p, %3, 0; @p stmatrix.sync.aligned.m8n8.x2.trans.shared.b16 [%0], {%1,%2};}" :: "r"(a), "r"(r0), "r"(r1), "r"((uint32_t)x) : "memory"); }
__device__ __forceinline__ uint32_t or_and(uint32_t a, uint32_t b, uint32_t m) { uint32_t r; asm("lop3.b32 %0, %1, %2, %3, 0xa8;" : "=r"(r) : "r"(a), "r"(b), "r"(m)); return r; }
#define rare(x) __builtin_expect(!!(x), 0)
__device__ __forceinline__ uint32_t gtime() { unsigned long long g; asm volatile("mov.u64 %0, %%globaltimer;" : "=l"(g) :: "memory"); return (uint32_t)g; }
__device__ __forceinline__ void wait_time(uint32_t t) {
  asm volatile("{.reg .pred p; .reg .b32 g; .reg .b64 c;\nLOOP: mov.u64 c, %%globaltimer; cvt.u32.u64 g, c; sub.s32 g, %0, g; setp.lt.u32 p, g, 16384; @p bra.uni LOOP;}" :: "r"(t - 1) : "memory"); }
__device__ __forceinline__ uint32_t ldx32(const void* p) { uint32_t v; asm volatile("ld.relaxed.gpu.global.b32 %0, [%1];" : "=r"(v) : "l"(p) : "memory"); return v; }
__device__ __forceinline__ void stx32(const void* p, uint32_t v) { asm volatile("st.relaxed.gpu.global.b32 [%0], %1;" :: "l"(p), "r"(v) : "memory"); }

__global__ void __launch_bounds__(256, 1)
rec_kernel(const __grid_constant__ RecMaps maps, const bf16* __restrict__ xin, const bf16* __restrict__ mem0) {
  extern __shared__ __align__(1024) uint8_t smem_raw[];
  const uint32_t sb = smem_u32(smem_raw);
  int role = blockIdx.x;
  {
    uint32_t smid, nsm; asm volatile("mov.u32 %0, %%smid;" : "=r"(smid)); asm volatile("mov.u32 %0, %%nsmid;" : "=r"(nsm));
    const int p = smid >> 1, u = p - 32;
    if (nsm == gridDim.x)
      role = (smid & 1) + (p < 32 ? 4 * ((p & 7) + 8 * (p >> 4)) + 2 * ((p >> 3) & 1) : p < 60 ? 4 * (16 + u % 7 + 7 * (u / 14)) + 2 * ((u / 7) & 1)
                         : p < 62 ? 2 * p + 8 : 2 * p - 4);
    role = uni(role);
  }
  if (role >= 128) {
    fft_cols(sb, role - 128, 4);
    grid_arrive(&g_x.ctr[32]); grid_wait(&g_x.ctr[32], 4);
    fft_rows_inv(&maps.fo, sb, role - 128, 4);
    return;
  }
  const int tid = threadIdx.x, warp = uni(tid >> 5), lane = tid & 31, wg = warp >> 2, w4 = warp & 3, g = lane >> 2, t = lane & 3;
  const int h = role >> 2, j = role & 3, jh = j & 1;
  uint32_t w[48][4];
  float aq[16], av[16];
  int it = 0;

  if (tid == 224) {
    mbar_init(sb + B_KV, 1); mbar_init(sb + B_W, 1); mbar_init(sb + B_X, 1); mbar_init(sb + B_X + 8, 1); mbar_init(sb + B_X + 16, 1); mbar_init(sb + B_X + 24, 1); mbar_init(sb + B_C, 4); mbar_init(sb + B_PK, 4); mbar_init(sb + B_B, 1);
    asm volatile("fence.mbarrier_init.release.cluster;" ::: "memory");
    mbar_expect_tx(sb + B_W, 3 * 65536);
    for (int i = 0; i < 4; i++) {
      tma2d(sb + R_X + i * 16384, &maps.wq, h * DH + 32 * j, i * 256, sb + B_W);
      tma2d(sb + R_MEM + i * 16384, &maps.wk, h * DH + 32 * j, i * 256, sb + B_W);
    }
    for (int i = 0; i < 2; i++) tma2d(sb + R_WO + i * 32768, &maps.wv, h * DH + 64 * (j >> 1), jh * 512 + i * 256, sb + B_W);
    for (int i = 0; i < 4; i++) asm volatile("cp.async.bulk.prefetch.L2.global [%0], 8192;" :: "l"(xin + role * 16384 + i * 4096) : "memory");
    for (int i = 0; i < 4; i++)
      asm volatile("cp.async.bulk.prefetch.tensor.2d.L2.global [%0, {%1, %2}];" :: "l"(&maps.wo), "r"(256 * j + 64 * i), "r"(h * DH) : "memory");
  }
  if (tid < 128) asm volatile("prefetch.global.L2 [%0];" :: "l"(mem0 + tid * 64));
  __syncthreads();
  mbar_spin(sb + B_W, 0, it);
  const int lrow = (lane & 7) + ((lane >> 4) << 3), lhi = (lane >> 3) & 1;
  const int kq = wg ? 1 - jh : 3 * jh;
  const uint32_t LW = lrow * 128 + ((lhi ^ (lane & 7)) << 4);
  {
    const int chunk = w4 < 2 ? w4 + 2 * lhi : 2 * (w4 & 1) + lhi;
    uint32_t a = sb + (w4 < 2 ? R_X : R_MEM) + kq * 16384 + lrow * 64 + ((chunk ^ ((lrow >> 1) & 3)) << 4);
#pragma unroll
    for (int i = 0; i < 16; i++) ldsm4t(w[i], a + i * 1024);
    const uint32_t st = wg ? 1024 : 2048, av0 = sb + R_WO + (LW ^ (w4 << 5));
    const uint32_t a1 = wg ? a + 16384 : av0 + jh * 32768, a2 = wg ? a + 32768 : av0 + (1 - jh) * 32768;
#pragma unroll
    for (int i = 0; i < 16; i++) { ldsm4t(w[16 + i], a1 + i * st); ldsm4t(w[32 + i], a2 + i * st); }
  }
  uint32_t L16 = pin(lane * 16);
  uint8_t* const xb = reinterpret_cast<uint8_t*>(&g_x);
  const uint32_t uW = uni(sb + w4 * 512), uWo = uni(sb + R_WO + w4 * 16384), uMem = uni(sb + R_MEM + kq * 4096);
  const uint32_t dX = uni(((sb + R_X + kq * 16384) >> 4) | 0x10000u);
  auto load_wo = [&](uint32_t (&d)[32][4], int i0, int i1) {
#pragma unroll
    for (int i = i0; i < i1; i++) lds128(d[i], uWo + L16 + (i & 1) * 512 + (i >> 4) * 1024 + (i & 14) * 1024);
  };
  auto issue_x = [&](int n, int k) {
    const uint32_t bar = sb + B_X + 8 * k, q = (k - jh) & 3;
    mbar_expect_tx(bar, 16384); tma3d(sb + R_X + q * 16384, &maps.x, n * SEG, 4 * q, bar);
  };
  auto store_stage = [&](int n) {
    asm volatile("cp.async.bulk.global.shared::cta.bulk_group [%0], [%1], 8192; cp.async.bulk.commit_group;"
                 :: "l"(g_kqv[n & 3][role]), "r"(sb + R_STAGE) : "memory");
  };
  auto issue_kqv = [&](int n) {
    const int p = (n & 3) * 128 + 4 * h;
    mbar_expect_tx(sb + B_KV, 26624);
    tma3d(sb + R_K, &maps.k, 0, p, sb + B_KV); tma3d(sb + R_Q, &maps.q, 8 + 2 * j, p, sb + B_KV); tma3d(sb + R_V, &maps.v, 16, p, sb + B_KV);
  };
  auto fetch4k = [&](uint32_t dst, uint32_t off, uint32_t bar, uint32_t t) {
    asm volatile("{.reg .pred p, q; .reg .b32 g; .reg .b64 c; elect.sync _|q, 0xffffffff; @q mbarrier.arrive.expect_tx.shared::cta.b64 _, [%2], 4096;\n"
                 "LOOP: mov.u64 c, %%globaltimer; cvt.u32.u64 g, c; sub.s32 g, %3, g; setp.lt.u32 p, g, 16384; @p bra.uni LOOP;\n"
                 "@q cp.async.bulk.shared::cluster.global.mbarrier::complete_tx::bytes [%0], [%1], 4096, [%2];}" :: "r"(dst), "l"(xb + off), "r"(bar), "r"(t - 1) : "memory");
  };
  auto issue_c = [&](uint32_t t) { fetch4k(sb + R_MEM + w4 * 4096, offsetof(Xchg, C) + (j >> 1) * 16384 + w4 * 4096, sb + B_C, t); };
  auto wait_x = [&](int n, int i) { if (!(EXP & 1) || n < 2) mbar_spin(sb + B_X + 8 * i, n & 1, it); };
  auto project_v = [&](auto I0, auto I1, auto&& mid) {
    wg_fence();
    sfor<decltype(I0)::value, decltype(I1)::value>([&](auto I) {
      constexpr int i = decltype(I)::value;
      mid(i);
      wg_rs32<((i >> 2) & 3) * 256 + (i & 3) * 2, (i > 0)>(av, w[16 + i], i < 16 ? dX : dX ^ 1024);
    });
    wg_commit();
  };
  auto project_qk = [&](auto I0, auto I1, auto&& mid) {
    const uint32_t dQ = dX + ((uint32_t)it >> 31);
    wg_fence();
    sfor<decltype(I0)::value, decltype(I1)::value>([&](auto I) {
      constexpr int i = decltype(I)::value;
      mid(i);
      wg_rs32<(i >> 2) * 256 + (i & 3) * 2, i != 16>(aq, w[i], dQ);
    });
    wg_commit();
  };
  const uint32_t uP = uni(sb + R_X + (2 - 2 * jh) * 16384 + w4 * 512);
  auto park = [&]() {
    bar_sync(1, 128);
#pragma unroll
    for (int i = 0; i < 4; i++) sts128f(uP + L16 + i * 2048, aq + 4 * i);
    warp_arrive(sb + B_PK);
  };
  auto unpark = [&]() {
#pragma unroll
    for (int i = 0; i < 4; i++) {
      const float4 p = lds128f(uP + L16 + i * 2048);
      aq[4 * i] = p.x; aq[4 * i + 1] = p.y; aq[4 * i + 2] = p.z; aq[4 * i + 3] = p.w;
    }
  };
  auto fin_qk = [&]() {
    const uint32_t a = sb + R_STAGE + (w4 < 2 ? 2048 + w4 * 128 : (w4 & 1) * 256) + (L16 & 112) + (L16 >> 7) * 512;
    stsm4t(a, pack2(aq[0], aq[1]), pack2(aq[4], aq[5]), pack2(aq[8], aq[9]), pack2(aq[12], aq[13]));
    stsm4t(a + (w4 < 2 ? 256 : 128), pack2(aq[2], aq[3]), pack2(aq[6], aq[7]), pack2(aq[10], aq[11]), pack2(aq[14], aq[15]));
  };
  auto fin_v = [&]() {
#pragma unroll
    for (int a = 0; a < 2; a++)
      sts128(sb + R_STAGE + 4096 + w4 * 1024 + a * 512 + L16, pack2(av[8 * a], av[8 * a + 1]), pack2(av[8 * a + 2], av[8 * a + 3]),
             pack2(av[8 * a + 4], av[8 * a + 5]), pack2(av[8 * a + 6], av[8 * a + 7]));
  };
  __syncthreads();
  if (tid == 224) {
#pragma unroll 1
    for (int i = 0; i < 4; i++) issue_x(0, i);
    mbar_expect_tx(sb + B_W, 65536);
    for (int i = 0; i < 4; i++) tma2d(sb + R_WO + i * 16384, &maps.wo, 256 * j + 64 * i, h * DH, sb + B_W);
  }
  __syncwarp();
  if (wg) {
#pragma unroll
    for (int i = 0; i < NSW; i++) sts128(uW + R_WC + L16 + i * 2048, w[i]);
  }
#pragma unroll
  for (int i = 0; i < 4; i++) {
    const uint32_t* p = reinterpret_cast<const uint32_t*>(mem0 + g * DM + 128 * warp + 32 * i + 2 * t);
    sts128(sb + R_MEM + warp * 2048 + i * 512 + (g >> 1) * 128 + t * 32 + (g & 1) * 16, __ldg(p), __ldg(p + 4), __ldg(p + 8), __ldg(p + 12));
  }
#pragma unroll 1
  for (int n = 0; n < 2; n++) {
    wait_x(n, 1); wait_x(n, 2); wait_x(n, 3);
    if (wg == 0) {
      wait_x(n, 0);
      project_v(IC<0>{}, IC<32>{}, [](int) {});
      if (tid == 96 && n == 1) {
        asm volatile("cp.async.bulk.wait_group 0;" ::: "memory");
        __threadfence(); atomicAdd(&g_x.ctr[h], 1u);
      }
      __syncwarp();
      mbar_spin(sb + B_PK, n, it);
      unpark();
      project_qk(IC<0>{}, IC<16>{}, [](int) {});
      wg_wait<0>(); keep(aq); keep(av);
      fin_v(); fin_qk();
      fence_async();
    } else {
      project_qk(IC<16>{}, IC<48>{}, [](int) {});
      project_qk(IC<0>{}, IC<16>{}, [](int) {});
      wg_wait<0>(); keep(aq);
      park();
      if (tid == 128 && n == 1) {
        for (int k = 0; *reinterpret_cast<volatile unsigned*>(&g_x.ctr[h]) < 4 && k < SPIN_LIMIT; k++) {}
        __threadfence(); asm volatile("fence.proxy.async;" ::: "memory");
        issue_kqv(0);
      }
    }
    __syncthreads();
    if (tid == 96 && n == 0) store_stage(0);
    if (tid == 128 && n == 0) {
#pragma unroll 1
      for (int i = 0; i < 4; i++) issue_x(1, i);
    }
    __syncwarp();
  }
  mbar_spin(sb + B_W, 1, it);
#pragma unroll
  for (int i = 0; i < 4; i++) {
    uint32_t f[4][4];
    const uint32_t a = sb + R_WO + warp * 8192 + i * 2048;
#pragma unroll
    for (int q = 0; q < 4; q++) ldsm4t(f[q], a + (LW ^ (q << 5)));
    __syncwarp();
#pragma unroll
    for (int q = 0; q < 4; q++) sts128(a + q * 512 + L16, f[q]);
  }
  mbar_spin(sb + B_KV, 0, it);
  if (tid == 0) sts32(sb + B_DUE + 4, gtime() & ~31u);
  if (tid < 4) sts32(sb + B_ONE + tid * 4, 0x3F803F80u);
  if (warp == 1) { const uint32_t e = g >> 1 == t ? 0x3F80u << (16 * (g & 1)) : 0u; sts128(sb + R_ID + L16, e, 0, 0, e); }
  __syncthreads();

  const float sc = 0.08838834764831845f * 1.4426950408889634f;
  uint8_t* const xa = xb + uni(h * 16384);
  const uint32_t uA = uni(wg ? (w4 >> 1) * 2048 + j * 512 + (w4 & 1) * 256 : 8192 + (4 * (j >> 1) + w4) * 512 + jh * 256);
  const uint32_t uB = uni(offsetof(Xchg, B) + (32 * w4 + j) * 8192 + h * 128);
  const uint32_t uP2 = uni(sb + R_P + w4 * 256);
  uint32_t nc = 1;
  uint32_t ma;
  auto pin_mem = [&]() { ma = pin(uMem + (L16 & 384) + (L16 & 48) * 2 + (L16 & 64) / 4); };
  pin_mem();

#pragma unroll 1
  for (int s = 0;; nc++) {
    const uint32_t tag = (s + 1) & 1;
    auto fresh = [&]() { L16 += (uint32_t)it >> 31; };
    float c[4][4], r4[4];
    auto fold = [&]() {
#pragma unroll
      for (int i = 0; i < 4; i++) r4[i] = ((c[0][i] + c[1][i]) + c[2][i]) + c[3][i];
    };
    auto mma4 = [&](int n, const uint32_t (&b0)[4], const uint32_t (&b1)[4]) {
      mma_h(c[0], w[n + 2], b1, 0); mma_h(c[1], w[n + 3], b1, 1); mma_h(c[2], w[n], b0, 0); mma_h(c[3], w[n + 1], b0, 1);
    };
    auto xpos = [&](int pos, int wp) {
      if (!(EXP & 1) && (pos == XC || pos == XD || pos == XB || pos == XA) && warp == wp && s + 1 < NSEG && elect()) {
        const int z = (uint32_t)it >> 31;
        if (pos == XC) issue_x(s + 2, 2 + z);
        if (pos == XD) issue_x(s + 2, 3 + z);
        if (pos == XB) issue_x(s + 2, 1 + z);
        if (pos == XA) issue_x(s + 2, z);
      }
      __syncwarp();
    };
    if (wg == 0) {
      mbar_spin(sb + B_C, nc & 1, it);
      TS(13);
      uint32_t b[16][4], tg[4];
#pragma unroll
      for (int i = 0; i < 8; i++) { lds128(b[i], ma + i * 512); __syncwarp(); }
      sched();
      zero(c);
#pragma unroll
      for (int i = 0; i < 8; i++) {
        const int k = i ^ 1;
        mma_h(c[0], w[2 * k], b[k], 0); mma_h(c[1], w[2 * k + 1], b[k], 1);
        if (i < 2 * NV0) { mma_h(c[2], w[16 + 2 * k], b[k], 0); mma_h(c[3], w[17 + 2 * k], b[k], 1); }
        sched();
        if (i == TGP) {
          fresh();
#pragma unroll
          for (int k = 0; k < 4; k++) tg[k] = lds32((uW * 4 + L16) * 2 + (L16 >> 6) * 4 + (R_MEM + k * 1024 - 7 * sb));
          sched();
        }
      }
#pragma unroll
      for (int i = 0; i < 4; i++) { r4[i] = c[0][i] + c[1][i]; c[0][i] = c[1][i] = 0.f; }
      sts128f(uW + R_RED + L16, r4);
      TS(1);
      const uint32_t old = bar_or(4, (dif2(tg[0], tg[1], s) | dif2(tg[2], tg[3], s)) & (s > 0));
      TS(0);
      uint8_t* adst;
#pragma unroll
      for (int i = 0; i < 2 * NV0; i++) { lds128(b[8 + i], (ma ^ 4096) + i * 512); __syncwarp(); }
      sched();
#pragma unroll
      for (int i = NV0; i < 8; i++) {
        mma4(16 + 4 * i, b[2 * i], b[2 * i + 1]);
        if (i < 7) sched();
        if (i < 4) { lds128(b[8 + 2 * i], (ma ^ 4096) + i * 1024); __syncwarp(); lds128(b[9 + 2 * i], (ma ^ 4096) + i * 1024 + 512); sched(); }
        if (i == 4) { adst = const_cast<uint8_t*>(pinp(xa + uA + L16 / 2)); sched(); }
      }
      fold();
      asm volatile("{.reg .pred p; setp.eq.u32 p, %3, 0; @p st.relaxed.gpu.global.v2.b32 [%0], {%1,%2};}" :: "l"(adst), "r"((pack2(r4[0], r4[1]) & ~1u) | tag), "r"(pack2(r4[2], r4[3])), "r"(old) : "memory");
      sched();
      const unsigned tpub = clk();
      if (__any_sync(0xffffffffu, old) && nc < NC_MAX) {
        bar_sync(3, 256);
        issue_c(gtime());
        continue;
      }
      TS(3);
      xpos(0, 0);
      const uint32_t due = lds32(sb + B_DUE + 4);
      uint32_t vf[4][4], vm[2][4], p[4], pm, o[4];
      const uint32_t va = sb + R_V + (w4 >> 1) * 8192 + (w4 & 1) * 2048 + L16;
#pragma unroll
      for (int i = 0; i < 4; i++) {
        uint32_t q[4]; lds128(vf[i], va + i * 512); lds128(q, va + 4096 + i * 512);
#pragma unroll
        for (int e = 0; e < 4; e++) vf[i][e] = hadd2(vf[i][e], q[e]);
      }
      const uint32_t pa = pin(sb + R_P + (L16 >> 1));
      const uint8_t* vsrc = pinp(xa + 8192 + w4 * 1024 + L16 / 2);
      const uint8_t* tsrc = pinp(xb + offsetof(Xchg, T) + L16 * 8);
      uint32_t one[4];
      lds128(one, sb + B_ONE);
      auto pv_x = [&]() {
        zero(c);
        mma_a(c[2], one, p[0], p[1]);
        mma_a(c[0], vf[0], p[0], p[1]); mma_a(c[1], vf[2], p[0], p[1]);
        sched();
        mma_a(c[2], one, p[2], p[3]);
        mma_a(c[0], vf[1], p[2], p[3]); mma_a(c[1], vf[3], p[2], p[3]);
        sched();
      };
      auto pv_m = [&]() {
        mma1688(c[2], one[0], one[1], pm);
        mma_a(c[0], vm[0], pm, pm);
        sched();
        mma_a(c[1], vm[1], pm, pm);
      };
      auto norm = [&]() {
        const float n0 = rcp(c[2][0]), n1 = rcp(c[2][1]);
#pragma unroll
        for (int i = 0; i < 4; i++) o[i] = pack2(c[i >> 1][2 * (i & 1)] * n0, c[i >> 1][2 * (i & 1) + 1] * n1);
        return ((__float_as_uint(c[2][0]) - 0x1F800000u) | (__float_as_uint(c[2][1]) - 0x1F800000u)) >> 30;
      };
      auto load_m = [&](int x) { const float2 e0 = lds64f(pa + 512 + x * 1024), e1 = lds64f(pa + 768 + x * 1024); pm = pack2(e0.x * e1.x, e0.y * e1.y); };
      auto attend_max = [&](int x) {
        float2 sv[6];
#pragma unroll
        for (int i = 0; i < 6; i++) sv[i] = lds64f(pa - 3072 + x * 1536 + i * 256);
        sv[4].x += sv[5].x; sv[4].y += sv[5].y;
        const int dq = (int)(L16 >> 6) - (int)((L16 >> 3) & 6) + 8 * j;
        float m = fmaxf(sv[4].x, sv[4].y);
#pragma unroll
        for (int i = 0; i < 4; i++) {
          if (x && 8 * i > dq) sv[i].x = -INFINITY;
          if (x && 8 * i + 1 > dq) sv[i].y = -INFINITY;
          m = fmaxf(m, fmaxf(sv[i].x, sv[i].y));
        }
        m = fmaxf(m, __shfl_xor_sync(0xffffffffu, m, 1));
        m = fmaxf(m, __shfl_xor_sync(0xffffffffu, m, 2));
#pragma unroll
        for (int i = 0; i < 5; i++) (i < 4 ? p[i] : pm) = pack2(ex2(sv[i].x - m), ex2(sv[i].y - m));
        pv_x(); pv_m(); norm();
      };
      delay_until(tpub + DLY_V);
      wait_time(due + NS_V);
      TS(4);
      ldx(vm, vsrc);
      sched();
      asm volatile("{.reg .pred p; setp.eq.u32 p, %2, 0; @p cp.async.cg.shared.global [%0], [%1], 16;}" :: "r"(sb + R_T + L16), "l"(tsrc), "r"(warp) : "memory");
      cpa_commit();
      xpos(2, 2);
      auto store_kqv = [&]() {
        fence_async();
        if (!(EXP & 4))
          asm volatile("{.reg .pred p; elect.sync _|p, 0xffffffff; @p cp.async.bulk.global.shared::cta.bulk_group [%0], [%1], 2048; cp.async.bulk.commit_group;}"
                       :: "l"(g_kqv[(s + 1) & 3][role] + w4 * 128), "r"(sb + R_STAGE + w4 * 2048) : "memory");
      };
      if (SPOS == 2) store_kqv();
      sched();
      bar_sync(5, 256);
      ldsm4(p, sb + R_P + L16);
      load_m(0);
      pv_x();
      ldsm4(p, sb + R_P + 1024 + L16);
      pv_m();
      const uint32_t r = norm(), tl = after(tag, c[2][0], (uint32_t)it >> 31);
      const bool redo = __any_sync(0xffffffffu, r | ((dif2(vm[0][0], vm[0][2], tl) | dif2(vm[1][0], vm[1][2], tl)) & 1));
      TS(6);
      stsm4t(uW + R_O + L16, o[0], o[1], o[2], o[3]);
      bar_arrive_unless(6, redo);
      sched();
      TS(7);
      pv_x();
      if (rare(redo)) { fresh(); retry<2>(vm, xa + 8192 + w4 * 1024 + L16 / 2, tag, it); }
      bar_sync(8, 256);
      load_m(1);
      pv_m();
      if (rare(__any_sync(0xffffffffu, norm()) || redo)) {
        fresh();
#pragma unroll 1
        for (int x = !redo; x < 2; x++) {
          attend_max(x);
          if (x == 0) { stsm4t(uW + R_O + L16, o[0], o[1], o[2], o[3]); bar_arrive(6, 256); }
        }
      }
      TS(8);
      if (SPOS == 4) store_kqv();
      xpos(4, 2);
      asm volatile("cp.async.bulk.wait_group 0;" ::: "memory");
      if (elect()) stx32(xa + 4096 + j * 16 + w4 * 4, s + 1);
      __syncwarp();
      if (warp == 0 && s + 1 < NSEG) {
        uint32_t tq[4];
        cpa_wait<0>();
        lds128(tq, sb + R_T + L16);
        const uint32_t ref = gtime();
#pragma unroll 1
        while (any_bit(or3(tq[0] - s - 1, tq[1] - s - 1, tq[2] - s - 1), tq[3] - s - 1, 30) && ++it < SPIN_LIMIT) ldx128(tq, xb + offsetof(Xchg, T) + L16 * 8);
        const int d = max(max((int)(tq[0] - ref), (int)(tq[1] - ref)), max((int)(tq[2] - ref), (int)(tq[3] - ref)));
        const uint32_t last = (ref + __reduce_max_sync(0xffffffffu, d)) & ~31u;
        TS(2);
        fetch4k(sb + R_MEM, offsetof(Xchg, B) + role * 8192, sb + B_B, last + NS_B);
        TS(5);
        asm volatile("st.shared.v2.u32 [%0], {%1,%2};" :: "r"(sb + B_DUE), "r"(last), "r"(last + (last == due ? NS_P : NS_P + NS_X)) : "memory");
        xpos(5, 0);
        LOG(9, last);
        LOG(13, tl - last);
      }
      fresh();
      const uint32_t ob = uni(sb + R_MEM + 4096 + w4 * 1024);
      stsm4t(ob + (L16 & 112) * 4 + (((L16 >> 3) ^ (L16 >> 1)) & 48), o[0], o[1], o[2], o[3]);
      __syncwarp();
      lds128(o, ob + (L16 ^ ((L16 >> 3) & 48)));
      auto put_o = [&]() {
        *reinterpret_cast<uint4*>(reinterpret_cast<uint8_t*>(g_ox) + (((s * SEG + 8 * j) * HD + h * DH + 32 * w4) * 2 + (L16 >> 6) * (HD * 2) + (L16 & 48))) = make_uint4(o[0], o[1], o[2], o[3]);
      };
      if (s + 1 == NSEG) { put_o(); break; }
      if (OXPOS < 0) put_o();
      fresh();
      const uint32_t ba = pin(sb + R_MEM + (L16 & 112) * 8 + (L16 >> 8) * 1024 + ((w4 * 32 + ((L16 >> 3) & 16)) ^ (L16 & 112)));
      const uint8_t* cdst = pinp(xb + (offsetof(Xchg, C) + j * 4096 + h * 128 + w4 * 32 + (L16 & 16) * 1024 + (L16 & 64) / 4 + (L16 >> 7) * 4));
      const uint32_t msk = pin((L16 >> 6) == (h & 3) * 2 + ((h >> 2) & 1) ? 0xFFFE0000u : 0xFFFFFFFFu);
      if (warp == 1) {
        wait_time(due + NS_F);
#pragma unroll 1
        while (__any_sync(0xffffffffu, ldx32(xa + 4096 + ((L16 >> 2) & 60)) != s + 1) && !(EXP & 4) && ++it < SPIN_LIMIT) {}
        wait_time(due + (NS_B + NS_K));
        if (!(EXP & 2) && elect()) issue_kqv(s + 1);
        __syncwarp();
      }
      TS(9);
      mbar_spin(sb + B_B, s & 1, it);
      TS(10);
      uint32_t bq[2][4];
      auto sum_b = [&]() {
        ldsm4t(bq[0], ba); ldsm4t(bq[1], ba + 2048);
        sched();
#pragma unroll
        for (int i = 0; i < 8; i++) c[i >> 2][i & 3] = 0.f;
        mma_a(c[0], bq[0], 0x3F803F80u, 0x3F803F80u); mma_a(c[1], bq[1], 0x3F803F80u, 0x3F803F80u);
        const uint32_t t2 = tag * 0x10001u;
        const bool old = any_bit(or3(dif2(bq[0][0], bq[0][1], t2), dif2(bq[0][2], bq[0][3], t2), dif2(bq[1][0], bq[1][1], t2)), dif2(bq[1][2], bq[1][3], t2), L16 < 64 ? 0x10001u : 0u);
        const uint32_t T = (tag << 16) & ~msk, u = ((__float_as_uint(c[0][0] + c[1][0]) + ((0x10000u & ~msk) - T)) & msk) | T;
        asm volatile("{.reg .pred p; setp.eq.u32 p, %2, 0; @p st.relaxed.gpu.global.b32 [%0], %1;}"
                     :: "l"(cdst), "r"(pack2(__uint_as_float(u), c[0][2] + c[1][2])), "r"((uint32_t)(old || (L16 & 32))) : "memory");
        return old;
      };
      if (rare(sum_b())) {
#pragma unroll 1
        do {
          const uint8_t* p = xb + (offsetof(Xchg, B) + role * 8192 + (ba - sb - R_MEM));
          ldx128(bq[0], p); ldx128(bq[1], p + 2048);
          sts128(ba, bq[0]); sts128(ba + 2048, bq[1]);
          __syncwarp();
          it += INC_B;
        } while (sum_b() && it < SPIN_LIMIT);
      }
      sched();
      TS(11);
      bar_arrive(0, 256);
      wait_x(s + 2, 0); wait_x(s + 2, 1 + 2 * jh);
      fresh();
      auto mid = [&](int n) { if (n == OXPOS) { __syncwarp(); put_o(); __syncwarp(); } };
      project_v(IC<0>{}, IC<UNP>{}, mid);
      mbar_spin(sb + B_PK, s & 1, it);
      unpark();
      project_v(IC<UNP>{}, IC<32>{}, mid);
      project_qk(IC<0>{}, IC<16>{}, [](int) {});
      TS(12);
      LOG(warp, it);
      pin_mem();
      wg_wait<1>(); keep(av);
      fin_v();
      wg_wait<0>(); keep(aq);
      fin_qk();
      TS(15);
    } else {
      uint32_t kf[8][4];
      auto load_k = [&]() {
        const uint32_t ka = sb + R_K + w4 * 1024 + (L16 & 112) + (L16 & 128) * 4 + (L16 & 256);
#pragma unroll
        for (int i = 0; i < 8; i++) ldsm4(kf[i], ka + (i >> 1) * 2048 + (i & 1) * 128);
      };
      auto put_p = [&](int x, uint32_t old, uint32_t again) {
        float e[4];
        const int dq = (int)((L16 >> 3) & 6) + 8 * j - (int)(L16 >> 6) - 16 * w4;
#pragma unroll
        for (int i = 0; i < 4; i++) { r4[i] = fmaf(c[3][i], sc, fmaf(c[2][i], sc, fmaf(c[0][i] + c[1][i], sc, __uint_as_float(i == 3 ? 0u - old : 0u)))); e[i] = x && dq + (i & 1) < 8 * (i >> 1) ? 0.f : ex2(r4[i]); }
        stsm2t(uP2 + x * 1024 + L16, pack2(e[0], e[1]), pack2(e[2], e[3]), again);
      };
      auto put_s = [&](int x) {
#pragma unroll
        for (int i = 0; i < 4; i++) sts32f(uW + R_S + x * 1536 + (L16 & 48) * 4 + (L16 >> 6) * 4 + (i & 1) * 32 + (i >> 1) * 256, r4[i]);
      };
      auto load_q = [&](uint32_t (&q)[4], uint32_t off) { ldsm4(q, sb + R_Q + (L16 & 112) + (L16 & 128) * 2 + (L16 >> 8) * 128 + off); };
      const uint8_t* adst = pinp(xa + uA + L16 / 2);
      uint32_t due;
      mbar_spin(sb + B_C, nc & 1, it);
      TS(13);
      float4 o4;
      uint32_t id[4], old;
      {
        uint32_t b[24][4];
#pragma unroll
        for (int i = 0; i < 2 * PD1; i++) { lds128(b[i], ma + i * 512); __syncwarp(); }
        sched();
        zero(c);
#pragma unroll
        for (int i = 0; i < 12; i++) {
          mma4(4 * i, b[2 * i], b[2 * i + 1]);
          if (i < 11) sched();
          if (i + PD1 < 12) { lds128(b[2 * (i + PD1)], ma + (i + PD1) * 1024); __syncwarp(); lds128(b[2 * (i + PD1) + 1], ma + (i + PD1) * 1024 + 512); sched(); }
          if (i == RJ) { lds128(id, sb + R_ID + L16); due = lds32(sb + B_DUE + 4); sched(); }
          if (i == RI) { old = bar_or(4, 0); o4 = lds128f(uW + R_RED + L16); sched(); }
        }
      }
      TS(0);
      {
        float e[4] = {o4.x, o4.y, o4.z, o4.w};
#pragma unroll
        for (int i = 0; i < 4; i++) { r4[i] = (((e[i] + c[0][i]) + c[1][i]) + c[2][i]) + c[3][i]; e[i] = 0.f; }
        mma_a(e, id, pack2(r4[0], r4[1]), pack2(r4[2], r4[3]));
        asm volatile("{.reg .pred p; setp.eq.u32 p, %3, 0; @p st.relaxed.gpu.global.v2.b32 [%0], {%1,%2};}" :: "l"(adst),
                     "r"((__byte_perm(__float_as_uint(e[0]), __float_as_uint(e[1]), 0x7632) & ~1u) | tag), "r"(__byte_perm(__float_as_uint(e[2]), __float_as_uint(e[3]), 0x7632)), "r"(old) : "memory");
        sched();
      }
      const unsigned tpub = clk(), now = gtime();
      if (__any_sync(0xffffffffu, old) && nc < NC_MAX) { bar_sync(3, 256); continue; }
      TS(2);
      const uint8_t* asrc = pinp(adst + ((warp == 7) * 1024 - (int)uA));
      fresh();
      uint32_t wo[32][4];
      uint8_t* dst;
      bool xok;
      auto pin_dst = [&]() { dst = const_cast<uint8_t*>(pinp(xb + uB + ((((L16 >> 2) * 0x2001u) & 0x18070u) ^ ((h & 7) << 4)))); sched(); };
      auto out_proj = [&]() {
        uint32_t b[4][4];
        float d[4][4];
        pin_dst();
        TS(7);
        bar_sync(6, 256);
#pragma unroll
        for (int i = 0; i < 4; i++) { ldsm4(b[i], sb + R_O + i * 512 + L16); __syncwarp(); }
        sched();
        auto put_b = [&](uint8_t* a, const float (&e)[4][4]) {
          stx128(a, (pack2(e[0][0] + e[2][0], e[0][1] + e[2][1]) & ~1u) | tag, pack2(e[0][2] + e[2][2], e[0][3] + e[2][3]),
                 pack2(e[1][0] + e[3][0], e[1][1] + e[3][1]), pack2(e[1][2] + e[3][2], e[1][3] + e[3][3]));
        };
        zero(c); zero(d);
#pragma unroll
        for (int i = 0; i < 32; i++) {
          mma_h(i < 16 ? c[i & 3] : d[i & 3], wo[i], b[(i >> 2) & 3], (i >> 1) & 1);
          if (i >= LW0 && NB1 + i - LW0 < 32) { load_wo(wo, (NB1 + i - LW0) ^ 1, ((NB1 + i - LW0) ^ 1) + 1); __syncwarp(); }
          if (i == 22) put_b(dst, c);
          if ((i & 1) && (i < 20 || i > 22)) sched();
        }
        put_b(dst + 131072, d);
        sched();
      };
      if (warp < 6) {
        delay_until(tpub + DLY_A);
        const int it0 = it;
        bool redo;
#pragma unroll 1
        do {
          uint32_t q[4][4], y[4];
          float d[4][4];
          wait_time(due);
          TS(4);
          ldx(q, asrc);
          sched();
          load_k();
          uint32_t qx[4][4];
#pragma unroll
          for (int i = 0; i < 4; i++) load_q(qx[i], i * 512);
          sched();
          load_wo(wo, 0, NE4);
          sched();
          zero(c);
#pragma unroll
          for (int i = 0; i < 8; i++) mma_h(c[i & 3], kf[i], qx[i >> 1], i & 1);
          put_p(1, 0, 0); put_s(1);
          sched();
          load_wo(wo, NE4, NA4);
          sched();
          zero(c); zero(d);
#pragma unroll
          for (int i = 0; i < 8; i++) {
            if (i == 0) { y[0] = dif2v(q[0][0], q[0][2], q[1][0]); sched(); }
            if (i == 3) { y[1] = dif2v(q[1][2], q[2][0], q[2][2]); sched(); }
            if (i == 6) { y[2] = dif2v(q[3][0], q[3][2], tag); sched(); }
            mma_h(i % 6 < 2 ? c[2 + i % 6] : d[i - 2], kf[i], q[i >> 1], i & 1);
            if (i == 2 || i == 5 || i == 7) sched();
          }
          y[0] = or_and(or3(y[0], y[1], dif2v(q[0][0], q[2][0], tag)), y[2], it < SPIN_LIMIT);
#pragma unroll
          for (int i = 0; i < 4; i++) { c[0][i] = d[0][i] + d[1][i]; c[1][i] = d[2][i] + d[3][i]; }
          put_p(0, y[0], it - it0);
          TS(5);
          bar_sync_unless(5, it - it0);
          redo = __any_sync(0xffffffffu, y[0]);
          it += INC_A;
        } while (redo);
        it -= INC_A;
        put_s(0);
        bar_arrive(8, 256);
        load_wo(wo, NA4, NB1);
        out_proj();
      } else {
        uint32_t qx[2][4], q[4][4];
        if (warp == 6) {
          const uint32_t t1 = (now & ~31u) + NS_M;
          LOG(10, now - due);
          if (elect()) stx32(&g_x.T[h][j], ((int)(t1 - due) > 0 ? t1 + NS_PEN : due) | ((s + 1) & 31));
          __syncwarp();
        }
        auto score = [&](const uint32_t (&a0)[4], const uint32_t (&a1)[4]) {
          zero(c);
#pragma unroll
          for (int i = 0; i < 4; i++) mma_h(c[i], i < 2 ? a0 : a1, q[2 + (i >> 1)], i & 1);
        };
        auto put_m = [&](uint32_t a, uint32_t old, uint32_t again) {
#pragma unroll
          for (int i = 0; i < 2; i++) { r4[i] = fmaf(c[3][2 + i], sc, fmaf((c[0][i] + c[1][2 + i]) + c[2][i], sc, __uint_as_float(i ? 0u - old : 0u))); r4[2 + i] = fmaf(r4[i] * 0x1p122f, 0.f, ex2(r4[i])); }
          asm volatile("{.reg .pred p; setp.eq.u32 p, %3, 0; @p st.shared.v2.f32 [%0], {%1,%2};}" :: "r"(a), "f"(r4[2]), "f"(r4[3]), "r"(again) : "memory");
        };
        delay_until(tpub + DLY_A);
        const uint32_t sa = sb + R_S + 512 + w4 * 256 + (L16 >> 1);
        const int it0 = it;
        bool redo;
#pragma unroll 1
        do {
          wait_time(due);
          TS(4);
          ldx<4, 2048>(q, asrc);
          sched();
          load_q(qx[0], (w4 & 1) * 1024); load_q(qx[1], (w4 & 1) * 1024 + 512);
          load_wo(wo, 0, NA6);
          sched();
          score(q[0], q[1]);
          sched();
          const uint32_t y = or_and(or3(dif2v(q[0][0], q[0][2], tag), dif2v(q[1][0], q[1][2], tag), dif2v(q[2][0], q[2][2], tag)), dif2v(q[3][0], q[3][2], tag), it < SPIN_LIMIT);
          put_m(sa + 2560, y, it - it0);
          TS(5);
          bar_arrive_unless(5, it - it0);
          redo = __any_sync(0xffffffffu, y);
          it += INC_A;
        } while (redo);
        it -= INC_A;
        sts64f(sa, r4[0], r4[1]);
        score(qx[0], qx[1]);
        put_m(sa + 3584, 0, 0);
        sts64f(sa + 1536, r4[0], r4[1]);
        bar_arrive(8, 256);
        load_wo(wo, NA6, NB1);
        out_proj();
      }
      TS(8);
      if (s + 1 == NSEG) break;
      if (warp == 4) LOG(12, tb);
      wait_x(s + 2, 2);
      TS(9);
      fresh();
      auto mid = [&](int n) {
        if (n >= 16 + RL0 && (n - 16 - RL0) % RLS == 0) {
#pragma unroll
          for (int i = (n - 16 - RL0) / RLS * RLB; i < (n - 16 - RL0) / RLS * RLB + RLB && i < NSW; i++) lds128(w[i], uW + R_WC + L16 + i * 2048);
          __syncwarp();
        }
        if (n >= 16 && (n & 15) == XWPOS) { __syncwarp(); xok = mbar_test(sb + B_X + (n < 32 ? 24 : 8), s & 1); __syncwarp(); }
      };
      project_qk(IC<16>{}, IC<32>{}, mid);
      if (rare(!xok)) wait_x(s + 2, 3);
      project_qk(IC<32>{}, IC<48>{}, mid);
      if (rare(!xok)) wait_x(s + 2, 1);
      project_qk(IC<0>{}, IC<16>{}, mid);
      TS(10);
      wg_wait<0>(); keep(aq);
      TS(1);
      park();
      TS(11);
      LOG(warp, it);
      if (warp == 4) LOG(8, nc);
      bar_sync(0, 256);
      const uint32_t cdue = lds32(sb + B_DUE) + NS_C;
      sched();
      delay_until(clk() + DLY_C);
      TS(12);
      if (warp == 7) LOG(11, gtime() - cdue);
      issue_c(cdue);
      TS(14);
      fresh();
      pin_mem();
      if (!(EXP & 2)) mbar_spin(sb + B_KV, tag, it);
      TS(15);
    }
    s++;
  }
  if (it >= SPIN_LIMIT || nc >= NC_MAX) g_err = 2;
}

typedef CUresult (*EncodeFn)(CUtensorMap*, CUtensorMapDataType, cuuint32_t, void*, const cuuint64_t*, const cuuint64_t*, const cuuint32_t*,
                             const cuuint32_t*, CUtensorMapInterleave, CUtensorMapSwizzle, CUtensorMapL2promotion, CUtensorMapFloatOOBfill);
static void make_map(EncodeFn fn, CUtensorMap* m, const void* p, uint64_t cols, uint64_t rows, uint64_t pitch, uint32_t bc, uint32_t br, CUtensorMapSwizzle sw) {
  cuuint64_t dims[2] = {cols, rows}, strides[1] = {pitch * 2};
  cuuint32_t box[2] = {bc, br}, es[2] = {1, 1};
  fn(m, CU_TENSOR_MAP_DATA_TYPE_BFLOAT16, 2, const_cast<void*>(p), dims, strides, box, es, CU_TENSOR_MAP_INTERLEAVE_NONE, sw,
     CU_TENSOR_MAP_L2_PROMOTION_L2_256B, CU_TENSOR_MAP_FLOAT_OOB_FILL_NONE);
}

extern "C" void kernel_launch(void* const* d_in, const int* in_sizes, int n_in, void* d_out, int out_size) {
  const bf16* Ax = (const bf16*)d_in[0]; const bf16* mem0 = (const bf16*)d_in[1];
  const bf16* Wq = (const bf16*)d_in[2]; const bf16* Wk = (const bf16*)d_in[3]; const bf16* Wv = (const bf16*)d_in[4];
  const bf16* Wo = (const bf16*)d_in[5];
  const bf16* Bx = (const bf16*)d_in[7]; const bf16* wr = (const bf16*)d_in[8]; const bf16* wi = (const bf16*)d_in[9];
  bf16* out = (bf16*)d_out;

  void* fp = nullptr; cudaDriverEntryPointQueryResult qr;
  cudaGetDriverEntryPoint("cuTensorMapEncodeTiled", &fp, cudaEnableDefault, &qr);
  EncodeFn fn = (EncodeFn)fp;
  void *kqv, *ox;
  cudaGetSymbolAddress(&kqv, g_kqv); cudaGetSymbolAddress(&ox, g_ox);
  const CUtensorMapSwizzle S128 = CU_TENSOR_MAP_SWIZZLE_128B, S64 = CU_TENSOR_MAP_SWIZZLE_64B;

  GemmMaps m3; RecMaps mr;
  make_map(fn, &m3.a, ox, HD, S_LEN, HD, 64, 128, S128);
  make_map(fn, &m3.b[0], Wo, DM, HD, DM, 64, 64, S128);
  m3.b[1] = m3.b[0]; m3.b[2] = m3.b[0];
  make_map(fn, &m3.c, out, DM, S_LEN, 2 * DM, 64, 64, S128);
  make_map(fn, &mr.wq, Wq, HD, DM, HD, 32, 256, S64);
  make_map(fn, &mr.wk, Wk, HD, DM, HD, 32, 256, S64);
  make_map(fn, &mr.wv, Wv, HD, DM, HD, 64, 256, S128);
  make_map(fn, &mr.wo, Wo, DM, HD, DM, 64, 128, S128);
  {
    cuuint64_t dims[3] = {64, S_LEN, 16}, strides[2] = {DM * 2, 128};
    cuuint32_t box[3] = {64, 32, 4}, es[3] = {1, 1, 1};
    fn(&mr.x, CU_TENSOR_MAP_DATA_TYPE_BFLOAT16, 3, const_cast<bf16*>(Ax), dims, strides, box, es, CU_TENSOR_MAP_INTERLEAVE_NONE, S128,
       CU_TENSOR_MAP_L2_PROMOTION_L2_256B, CU_TENSOR_MAP_FLOAT_OOB_FILL_NONE);
  }
  for (int i = 0; i < 3; i++) {
    cuuint64_t dims[3] = {128, 32, 512}, strides[2] = {256, 8192};
    cuuint32_t box[3] = {128, i == 0 ? 8u : i == 1 ? 2u : 16u, 4}, es[3] = {1, 1, 1};
    fn(i == 0 ? &mr.k : i == 1 ? &mr.q : &mr.v, CU_TENSOR_MAP_DATA_TYPE_BFLOAT16, 3, kqv, dims, strides, box, es, CU_TENSOR_MAP_INTERLEAVE_NONE,
       CU_TENSOR_MAP_SWIZZLE_NONE, CU_TENSOR_MAP_L2_PROMOTION_L2_256B, CU_TENSOR_MAP_FLOAT_OOB_FILL_NONE);
  }
  {
    cuuint64_t dims[3] = {64, 16, S_LEN}, strides[2] = {128, 2 * DM * 2};
    cuuint32_t box[3] = {64, 16, 2}, es[3] = {1, 1, 1};
    fn(&mr.fo, CU_TENSOR_MAP_DATA_TYPE_BFLOAT16, 3, out + DM, dims, strides, box, es, CU_TENSOR_MAP_INTERLEAVE_NONE, S128,
       CU_TENSOR_MAP_L2_PROMOTION_NONE, CU_TENSOR_MAP_FLOAT_OOB_FILL_NONE);
  }
  constexpr int SM3 = 6 * 32768 + 32768 + 256 + 1024;
  cudaFuncSetAttribute(gemm_kernel<128, 6>, cudaFuncAttributeMaxDynamicSharedMemorySize, SM3);
  cudaFuncSetAttribute(rec_kernel, cudaFuncAttributeMaxDynamicSharedMemorySize, R_TOTAL);

  cudaStream_t st = cudaStreamPerThread;
  cudaFuncSetAttribute(fft_pre_kernel, cudaFuncAttributeMaxDynamicSharedMemorySize, F_SMEM);
  fft_pre_kernel<<<128, 256, F_SMEM, st>>>(Bx, wr, wi);
  rec_kernel<<<132, 256, R_TOTAL, st>>>(mr, Ax, mem0);
  gemm_kernel<128, 6><<<128, 384, SM3, st>>>(m3, 16, 8, 64, 8, 1);
}
```

```cpp
#include <cuda_runtime.h>
#include <cuda_bf16.h>
#include <cuda.h>
#include <stdint.h>
#include <stddef.h>
#include <type_traits>

typedef __nv_bfloat16 bf16;

constexpr int S_LEN = 2048, DM = 1024, NH = 32, DH = 128, MEM = 8, SEG = 32, NSEG = 64;
constexpr int HD = NH * DH;
#define SPIN 20
constexpr int SPIN_LIMIT = 1 << SPIN, INC_A = 1, INC_B = 1;

constexpr unsigned NC_MAX = 4096;
__device__ __align__(1024) uint4 g_kqv[4][128][512];
__device__ __align__(1024) bf16 g_ox[(size_t)S_LEN * HD];
struct Xchg {
  uint4 A[32][2][2][256];
  uint4 C[2][4][256];
  uint4 B[128][2][256];
  uint32_t T[32][32];
  unsigned ctr[64];
};
__device__ __align__(8192) Xchg g_x;
__device__ __align__(1024) uint4 g_y[1024 * 256];
__device__ __align__(1024) uint4 g_wt[513 * 512];
__device__ int g_err;

__device__ __forceinline__ unsigned clk() { unsigned long long c; asm volatile("mov.u64 %0, %%clock64;" : "=l"(c)); return (unsigned)c; }
__device__ __forceinline__ uint32_t smem_u32(const void* p) { return (uint32_t)__cvta_generic_to_shared(p); }
__device__ __forceinline__ void mbar_init(uint32_t bar, int cnt) { asm volatile("mbarrier.init.shared::cta.b64 [%0], %1;" :: "r"(bar), "r"(cnt) : "memory"); }
__device__ __forceinline__ void mbar_expect_tx(uint32_t bar, int bytes) { asm volatile("mbarrier.arrive.expect_tx.shared::cta.b64 _, [%0], %1;" :: "r"(bar), "r"(bytes) : "memory"); }
__device__ __forceinline__ void mbar_arrive(uint32_t bar) { asm volatile("mbarrier.arrive.shared::cta.b64 _, [%0];" :: "r"(bar) : "memory"); }
__device__ __forceinline__ void mbar_arrive_cluster(uint32_t bar, int cta) {
  asm volatile("{.reg .b32 r; mapa.shared::cluster.u32 r, %0, %1; mbarrier.arrive.shared::cluster.b64 _, [r];}" :: "r"(bar), "r"(cta) : "memory"); }
__device__ __forceinline__ bool mbar_try(uint32_t bar, int par) {
  uint32_t ok; asm volatile("{.reg .pred p; mbarrier.try_wait.parity.shared::cta.b64 p, [%1], %2; selp.u32 %0, 1, 0, p;}" : "=r"(ok) : "r"(bar), "r"(par) : "memory"); return ok; }
__device__ __forceinline__ bool mbar_test(uint32_t bar, int par) {
  uint32_t ok; asm volatile("{.reg .pred p; mbarrier.test_wait.parity.shared::cta.b64 p, [%1], %2; selp.u32 %0, 1, 0, p;}" : "=r"(ok) : "r"(bar), "r"(par) : "memory"); return ok; }
__device__ __forceinline__ void mbar_wait(uint32_t bar, int par) {
  int it = 0;
  while (!mbar_try(bar, par)) { if (++it > SPIN_LIMIT) { g_err = 1; break; } }
}
__device__ __forceinline__ void tma2d(uint32_t dst, const CUtensorMap* m, int c0, int c1, uint32_t bar) {
  asm volatile("cp.async.bulk.tensor.2d.shared::cluster.global.mbarrier::complete_tx::bytes [%0], [%1, {%3, %4}], [%2];"
    :: "r"(dst), "l"(m), "r"(bar), "r"(c0), "r"(c1) : "memory"); }
__device__ __forceinline__ void tma2d_mc(uint32_t dst, const CUtensorMap* m, int c0, int c1, uint32_t bar, uint16_t mask) {
  asm volatile("cp.async.bulk.tensor.2d.shared::cluster.global.mbarrier::complete_tx::bytes.multicast::cluster [%0], [%1, {%3, %4}], [%2], %5;"
    :: "r"(dst), "l"(m), "r"(bar), "r"(c0), "r"(c1), "h"(mask) : "memory"); }
__device__ __forceinline__ void tma2d_store(const CUtensorMap* m, uint32_t src, int c0, int c1) {
  asm volatile("cp.async.bulk.tensor.2d.global.shared::cta.bulk_group [%0, {%2, %3}], [%1];" :: "l"(m), "r"(src), "r"(c0), "r"(c1) : "memory"); }
__device__ __forceinline__ void fence_async() { asm volatile("fence.proxy.async.shared::cta;" ::: "memory"); }
__device__ __forceinline__ void bar_sync(int id, int n) { asm volatile("bar.sync %0, %1;" :: "r"(id), "r"(n) : "memory"); }
__device__ __forceinline__ void bar_arrive(int id, int n) { asm volatile("bar.arrive %0, %1;" :: "r"(id), "r"(n) : "memory"); }
__device__ __forceinline__ uint32_t pack2(float lo, float hi) { uint32_t r; asm("cvt.rn.bf16x2.f32 %0, %1, %2;" : "=r"(r) : "f"(hi), "f"(lo)); return r; }
__device__ __forceinline__ uint32_t pack2_tag(float lo, float hi, uint32_t T) {
  uint32_t u = ((__float_as_uint(lo) - T + 0x10000u) & 0xFFFE0000u) + T;
  return __byte_perm(u, pack2(0.f, hi), 0x7632); }
__device__ __forceinline__ void ldsm4(uint32_t (&r)[4], uint32_t a) {
  asm volatile("ldmatrix.sync.aligned.m8n8.x4.shared.b16 {%0,%1,%2,%3}, [%4];" : "=r"(r[0]), "=r"(r[1]), "=r"(r[2]), "=r"(r[3]) : "r"(a) : "memory"); }
__device__ __forceinline__ void ldsm4t(uint32_t (&r)[4], uint32_t a) {
  asm volatile("ldmatrix.sync.aligned.m8n8.x4.trans.shared.b16 {%0,%1,%2,%3}, [%4];" : "=r"(r[0]), "=r"(r[1]), "=r"(r[2]), "=r"(r[3]) : "r"(a) : "memory"); }
__device__ __forceinline__ void stsm4(uint32_t a, uint32_t r0, uint32_t r1, uint32_t r2, uint32_t r3) {
  asm volatile("stmatrix.sync.aligned.m8n8.x4.shared.b16 [%0], {%1,%2,%3,%4};" :: "r"(a), "r"(r0), "r"(r1), "r"(r2), "r"(r3) : "memory"); }
__device__ __forceinline__ void stsm4t(uint32_t a, uint32_t r0, uint32_t r1, uint32_t r2, uint32_t r3) {
  asm volatile("stmatrix.sync.aligned.m8n8.x4.trans.shared.b16 [%0], {%1,%2,%3,%4};" :: "r"(a), "r"(r0), "r"(r1), "r"(r2), "r"(r3) : "memory"); }
__device__ __forceinline__ void lds128(uint32_t (&r)[4], uint32_t a) {
  asm volatile("ld.shared.v4.u32 {%0,%1,%2,%3}, [%4];" : "=r"(r[0]), "=r"(r[1]), "=r"(r[2]), "=r"(r[3]) : "r"(a) : "memory"); }
__device__ __forceinline__ float4 lds128f(uint32_t a) { float4 r;
  asm volatile("ld.shared.v4.f32 {%0,%1,%2,%3}, [%4];" : "=f"(r.x), "=f"(r.y), "=f"(r.z), "=f"(r.w) : "r"(a) : "memory"); return r; }
__device__ __forceinline__ float2 lds64f(uint32_t a) { float2 r;
  asm volatile("ld.shared.v2.f32 {%0,%1}, [%2];" : "=f"(r.x), "=f"(r.y) : "r"(a) : "memory"); return r; }
__device__ __forceinline__ void sts128(uint32_t a, uint32_t r0, uint32_t r1, uint32_t r2, uint32_t r3) {
  asm volatile("st.shared.v4.u32 [%0], {%1,%2,%3,%4};" :: "r"(a), "r"(r0), "r"(r1), "r"(r2), "r"(r3) : "memory"); }
__device__ __forceinline__ void sts64f(uint32_t a, float x, float y) { asm volatile("st.shared.v2.f32 [%0], {%1,%2};" :: "r"(a), "f"(x), "f"(y) : "memory"); }
__device__ __forceinline__ void sts32f(uint32_t a, float x) { asm volatile("st.shared.f32 [%0], %1;" :: "r"(a), "f"(x) : "memory"); }
__device__ __forceinline__ void mma16816(float (&d)[4], uint32_t a0, uint32_t a1, uint32_t a2, uint32_t a3, uint32_t b0, uint32_t b1) {
  asm volatile("mma.sync.aligned.m16n8k16.row.col.f32.bf16.bf16.f32 {%0,%1,%2,%3}, {%4,%5,%6,%7}, {%8,%9}, {%0,%1,%2,%3};"
    : "+f"(d[0]), "+f"(d[1]), "+f"(d[2]), "+f"(d[3]) : "r"(a0), "r"(a1), "r"(a2), "r"(a3), "r"(b0), "r"(b1)); }
__device__ __forceinline__ void mma1688(float (&d)[4], uint32_t a0, uint32_t a1, uint32_t b0) {
  asm volatile("mma.sync.aligned.m16n8k8.row.col.f32.bf16.bf16.f32 {%0,%1,%2,%3}, {%4,%5}, {%6}, {%0,%1,%2,%3};"
    : "+f"(d[0]), "+f"(d[1]), "+f"(d[2]), "+f"(d[3]) : "r"(a0), "r"(a1), "r"(b0)); }
__device__ __forceinline__ void ldx128(uint32_t (&r)[4], const void* p) {
  asm volatile("{.reg .b128 t; .reg .b64 a, b; ld.relaxed.gpu.global.b128 t, [%4]; mov.b128 {a, b}, t; mov.b64 {%0,%1}, a; mov.b64 {%2,%3}, b;}"
    : "=r"(r[0]), "=r"(r[1]), "=r"(r[2]), "=r"(r[3]) : "l"(p) : "memory"); }
__device__ __forceinline__ void ldx2x64(uint32_t (&r)[4], const void* p) {
  asm volatile("{.reg .b64 a, b; ld.relaxed.gpu.global.v2.b64 {a, b}, [%4]; mov.b64 {%0,%1}, a; mov.b64 {%2,%3}, b;}"
    : "=r"(r[0]), "=r"(r[1]), "=r"(r[2]), "=r"(r[3]) : "l"(p) : "memory"); }
__device__ __forceinline__ void stx128(void* p, uint32_t r0, uint32_t r1, uint32_t r2, uint32_t r3) {
  asm volatile("{.reg .b128 t; .reg .b64 a, b; mov.b64 a, {%1,%2}; mov.b64 b, {%3,%4}; mov.b128 t, {a, b}; st.relaxed.gpu.global.b128 [%0], t;}"
    :: "l"(p), "r"(r0), "r"(r1), "r"(r2), "r"(r3) : "memory"); }
__device__ __forceinline__ void stx64(void* p, uint32_t r0, uint32_t r1) {
  asm volatile("{.reg .b64 a; mov.b64 a, {%1,%2}; st.relaxed.gpu.global.b64 [%0], a;}" :: "l"(p), "r"(r0), "r"(r1) : "memory"); }
__device__ __forceinline__ uint32_t uni(uint32_t x) { return __shfl_sync(0xffffffffu, x, 0); }
__device__ __forceinline__ uint32_t pin(uint32_t x) { return __shfl_xor_sync(0xffffffffu, x, 0); }
__device__ __forceinline__ float ex2(float x) { float r; asm("ex2.approx.ftz.f32 %0, %1;" : "=f"(r) : "f"(x)); return r; }
__device__ __forceinline__ void wg_fence() { asm volatile("wgmma.fence.sync.aligned;" ::: "memory"); }
__device__ __forceinline__ void wg_commit() { asm volatile("wgmma.commit_group.sync.aligned;" ::: "memory"); }
template <int N> __device__ __forceinline__ void wg_wait() { asm volatile("wgmma.wait_group.sync.aligned %0;" :: "n"(N) : "memory"); }

__device__ __forceinline__ void wgmma_ss_n256_tb1(float (&d)[128], uint64_t da, uint64_t db, int sc) {
  asm volatile("{.reg .pred p; setp.ne.b32 p, %130, 0;\n"
    "wgmma.mma_async.sync.aligned.m64n256k16.f32.bf16.bf16 {%0,%1,%2,%3,%4,%5,%6,%7,%8,%9,%10,%11,%12,%13,%14,%15,%16,%17,%18,%19,%20,%21,%22,%23,%24,%25,%26,%27,%28,%29,%30,%31,%32,%33,%34,%35,%36,%37,%38,%39,%40,%41,%42,%43,%44,%45,%46,%47,%48,%49,%50,%51,%52,%53,%54,%55,%56,%57,%58,%59,%60,%61,%62,%63,%64,%65,%66,%67,%68,%69,%70,%71,%72,%73,%74,%75,%76,%77,%78,%79,%80,%81,%82,%83,%84,%85,%86,%87,%88,%89,%90,%91,%92,%93,%94,%95,%96,%97,%98,%99,%100,%101,%102,%103,%104,%105,%106,%107,%108,%109,%110,%111,%112,%113,%114,%115,%116,%117,%118,%119,%120,%121,%122,%123,%124,%125,%126,%127}, %128, %129, p, 1, 1, 0, 1;}\n"
    : "+f"(d[0]),"+f"(d[1]),"+f"(d[2]),"+f"(d[3]),"+f"(d[4]),"+f"(d[5]),"+f"(d[6]),"+f"(d[7]),"+f"(d[8]),"+f"(d[9]),"+f"(d[10]),"+f"(d[11]),"+f"(d[12]),"+f"(d[13]),"+f"(d[14]),"+f"(d[15]),"+f"(d[16]),"+f"(d[17]),"+f"(d[18]),"+f"(d[19]),"+f"(d[20]),"+f"(d[21]),"+f"(d[22]),"+f"(d[23]),"+f"(d[24]),"+f"(d[25]),"+f"(d[26]),"+f"(d[27]),"+f"(d[28]),"+f"(d[29]),"+f"(d[30]),"+f"(d[31]),"+f"(d[32]),"+f"(d[33]),"+f"(d[34]),"+f"(d[35]),"+f"(d[36]),"+f"(d[37]),"+f"(d[38]),"+f"(d[39]),"+f"(d[40]),"+f"(d[41]),"+f"(d[42]),"+f"(d[43]),"+f"(d[44]),"+f"(d[45]),"+f"(d[46]),"+f"(d[47]),"+f"(d[48]),"+f"(d[49]),"+f"(d[50]),"+f"(d[51]),"+f"(d[52]),"+f"(d[53]),"+f"(d[54]),"+f"(d[55]),"+f"(d[56]),"+f"(d[57]),"+f"(d[58]),"+f"(d[59]),"+f"(d[60]),"+f"(d[61]),"+f"(d[62]),"+f"(d[63]),"+f"(d[64]),"+f"(d[65]),"+f"(d[66]),"+f"(d[67]),"+f"(d[68]),"+f"(d[69]),"+f"(d[70]),"+f"(d[71]),"+f"(d[72]),"+f"(d[73]),"+f"(d[74]),"+f"(d[75]),"+f"(d[76]),"+f"(d[77]),"+f"(d[78]),"+f"(d[79]),"+f"(d[80]),"+f"(d[81]),"+f"(d[82]),"+f"(d[83]),"+f"(d[84]),"+f"(d[85]),"+f"(d[86]),"+f"(d[87]),"+f"(d[88]),"+f"(d[89]),"+f"(d[90]),"+f"(d[91]),"+f"(d[92]),"+f"(d[93]),"+f"(d[94]),"+f"(d[95]),"+f"(d[96]),"+f"(d[97]),"+f"(d[98]),"+f"(d[99]),"+f"(d[100]),"+f"(d[101]),"+f"(d[102]),"+f"(d[103]),"+f"(d[104]),"+f"(d[105]),"+f"(d[106]),"+f"(d[107]),"+f"(d[108]),"+f"(d[109]),"+f"(d[110]),"+f"(d[111]),"+f"(d[112]),"+f"(d[113]),"+f"(d[114]),"+f"(d[115]),"+f"(d[116]),"+f"(d[117]),"+f"(d[118]),"+f"(d[119]),"+f"(d[120]),"+f"(d[121]),"+f"(d[122]),"+f"(d[123]),"+f"(d[124]),"+f"(d[125]),"+f"(d[126]),"+f"(d[127])
    : "l"(da), "l"(db), "r"(sc));
}

__device__ __forceinline__ void wgmma_ss_n128_tb1(float (&d)[64], uint64_t da, uint64_t db, int sc) {
  asm volatile("{.reg .pred p; setp.ne.b32 p, %66, 0;\n"
    "wgmma.mma_async.sync.aligned.m64n128k16.f32.bf16.bf16 {%0,%1,%2,%3,%4,%5,%6,%7,%8,%9,%10,%11,%12,%13,%14,%15,%16,%17,%18,%19,%20,%21,%22,%23,%24,%25,%26,%27,%28,%29,%30,%31,%32,%33,%34,%35,%36,%37,%38,%39,%40,%41,%42,%43,%44,%45,%46,%47,%48,%49,%50,%51,%52,%53,%54,%55,%56,%57,%58,%59,%60,%61,%62,%63}, %64, %65, p, 1, 1, 0, 1;}\n"
    : "+f"(d[0]),"+f"(d[1]),"+f"(d[2]),"+f"(d[3]),"+f"(d[4]),"+f"(d[5]),"+f"(d[6]),"+f"(d[7]),"+f"(d[8]),"+f"(d[9]),"+f"(d[10]),"+f"(d[11]),"+f"(d[12]),"+f"(d[13]),"+f"(d[14]),"+f"(d[15]),"+f"(d[16]),"+f"(d[17]),"+f"(d[18]),"+f"(d[19]),"+f"(d[20]),"+f"(d[21]),"+f"(d[22]),"+f"(d[23]),"+f"(d[24]),"+f"(d[25]),"+f"(d[26]),"+f"(d[27]),"+f"(d[28]),"+f"(d[29]),"+f"(d[30]),"+f"(d[31]),"+f"(d[32]),"+f"(d[33]),"+f"(d[34]),"+f"(d[35]),"+f"(d[36]),"+f"(d[37]),"+f"(d[38]),"+f"(d[39]),"+f"(d[40]),"+f"(d[41]),"+f"(d[42]),"+f"(d[43]),"+f"(d[44]),"+f"(d[45]),"+f"(d[46]),"+f"(d[47]),"+f"(d[48]),"+f"(d[49]),"+f"(d[50]),"+f"(d[51]),"+f"(d[52]),"+f"(d[53]),"+f"(d[54]),"+f"(d[55]),"+f"(d[56]),"+f"(d[57]),"+f"(d[58]),"+f"(d[59]),"+f"(d[60]),"+f"(d[61]),"+f"(d[62]),"+f"(d[63])
    : "l"(da), "l"(db), "r"(sc));
}

template <int BN> struct WG;
template <> struct WG<256> { static __device__ __forceinline__ void mma(float (&d)[128], uint64_t a, uint64_t b, int sc) { wgmma_ss_n256_tb1(d, a, b, sc); } };
template <> struct WG<128> { static __device__ __forceinline__ void mma(float (&d)[64], uint64_t a, uint64_t b, int sc) { wgmma_ss_n128_tb1(d, a, b, sc); } };

struct GemmMaps { CUtensorMap a, b[3], c; };
template <int BN, int STAGES>
__global__ void __cluster_dims__(2, 1, 1) __launch_bounds__(384, 1)
gemm_kernel(const __grid_constant__ GemmMaps maps, int tilesM, int tilesN, int kblocks, int nPerB, int clearX) {
  extern __shared__ __align__(1024) uint8_t smem_raw[];
  constexpr int STAGE_BYTES = 16384 + BN * 128;
  constexpr int NBOX = BN / 64;
  const uint32_t sbase = (smem_u32(smem_raw) + 1023) & ~1023u;
  const uint32_t sEpi = sbase + STAGES * STAGE_BYTES;
  const uint32_t sBar = sEpi + 32768;
  const int warp = threadIdx.x >> 5, lane = threadIdx.x & 31, wg = warp >> 2;
  uint32_t crank; asm("mov.u32 %0, %%cluster_ctarank;" : "=r"(crank));
  if (threadIdx.x == 0) {
    for (int i = 0; i < STAGES; i++) { mbar_init(sBar + 8 * i, 1); mbar_init(sBar + 8 * (STAGES + i), 4); }
    asm volatile("fence.mbarrier_init.release.cluster;" ::: "memory");
  }
  if (clearX) {
    uint4* p = reinterpret_cast<uint4*>(&g_x);
    for (int i = blockIdx.x * 384 + threadIdx.x; i < (int)(sizeof(Xchg) / 16); i += gridDim.x * 384) p[i] = make_uint4(0, 0, 0, 0);
  }
  asm volatile("barrier.cluster.arrive.release.aligned; barrier.cluster.wait.acquire.aligned;" ::: "memory");
  const int npairs = (tilesM >> 1) * tilesN, pair0 = blockIdx.x >> 1, pstep = gridDim.x >> 1;
  if (wg == 2) {
    asm volatile("setmaxnreg.dec.sync.aligned.u32 40;");
    if (warp == 8 && lane == 0) {
      int st = 0, ph = 1;
      for (int p = pair0; p < npairs; p += pstep) {
        const int tm = (p % (tilesM >> 1)) * 2 + crank, tn = p / (tilesM >> 1);
        const CUtensorMap* mb = &maps.b[tn / nPerB];
        const int n0 = (tn % nPerB) * BN;
        for (int kb = 0; kb < kblocks; kb++) {
          mbar_wait(sBar + 8 * (STAGES + st), ph);
          const uint32_t a = sbase + st * STAGE_BYTES, full = sBar + 8 * st;
          mbar_expect_tx(full, STAGE_BYTES);
          tma2d(a, &maps.a, kb * 64, tm * 128, full);
#pragma unroll
          for (int i = 0; i < NBOX / 2; i++) {
            const int bx = crank * (NBOX / 2) + i;
            tma2d_mc(a + 16384 + bx * 8192, mb, n0 + bx * 64, kb * 64, full, (uint16_t)3);
          }
          if (++st == STAGES) { st = 0; ph ^= 1; }
        }
      }
      for (int i = 0; i < STAGES; i++) { mbar_wait(sBar + 8 * (STAGES + st), ph); if (++st == STAGES) { st = 0; ph ^= 1; } }
    }
  } else {
    asm volatile("setmaxnreg.inc.sync.aligned.u32 232;");
    int st = 0, ph = 0;
    float acc[BN / 2];
    const uint64_t descA0 = (uint64_t)(((sbase + wg * 8192) & 0x3FFFF) >> 4) | (1ull << 16) | (64ull << 32) | (1ull << 62);
    const uint64_t descB0 = (uint64_t)(((sbase + 16384) & 0x3FFFF) >> 4) | (512ull << 16) | (64ull << 32) | (1ull << 62);
    const uint32_t epi = sEpi + wg * 16384;
    for (int p = pair0; p < npairs; p += pstep) {
      const int tm = (p % (tilesM >> 1)) * 2 + crank, tn = p / (tilesM >> 1);
      int prev = -1;
      for (int kb = 0; kb < kblocks; kb++) {
        mbar_wait(sBar + 8 * st, ph);
        wg_fence();
        const uint64_t so = (uint64_t)(st * (STAGE_BYTES >> 4));
#pragma unroll
        for (int k = 0; k < 4; k++) WG<BN>::mma(acc, descA0 + so + k * 2, descB0 + so + k * 128, kb | k);
        wg_commit();
        if (prev >= 0) {
          wg_wait<1>();
          if ((threadIdx.x & 127) < 2) mbar_arrive_cluster(sBar + 8 * (STAGES + prev), threadIdx.x & 1);
        }
        prev = st;
        if (++st == STAGES) { st = 0; ph ^= 1; }
      }
      wg_wait<0>();
      if ((threadIdx.x & 127) < 2) mbar_arrive_cluster(sBar + 8 * (STAGES + prev), threadIdx.x & 1);
#pragma unroll
      for (int r = 0; r < BN / 128; r++) {
        if ((threadIdx.x & 127) == 0) asm volatile("cp.async.bulk.wait_group.read 0;" ::: "memory");
        bar_sync(1 + wg, 128);
        const int row = (warp & 3) * 16 + (lane & 15);
#pragma unroll
        for (int i = 0; i < 8; i++) {
          const int c = 2 * (i & 3) + (lane >> 4);
          const float* q = &acc[r * 64 + i * 8];
          stsm4(epi + (i >> 2) * 8192 + row * 128 + ((c ^ (row & 7)) << 4), pack2(q[0], q[1]), pack2(q[2], q[3]), pack2(q[4], q[5]), pack2(q[6], q[7]));
        }
        fence_async();
        bar_sync(1 + wg, 128);
        if ((threadIdx.x & 127) == 0) {
          tma2d_store(&maps.c, epi, tn * BN + r * 128, tm * 128 + wg * 64);
          tma2d_store(&maps.c, epi + 8192, tn * BN + r * 128 + 64, tm * 128 + wg * 64);
          asm volatile("cp.async.bulk.commit_group;" ::: "memory");
        }
      }
    }
    if ((threadIdx.x & 127) == 0) asm volatile("cp.async.bulk.wait_group 0;" ::: "memory");
  }
}

struct Dft { uint32_t m[2][2][2][4]; };
template <bool P4> __device__ __forceinline__ int fidx(int tile, int x) { return P4 ? 4 * (x >> 1) + 2 * (tile & 1) + (x & 1) + 16 * (tile >> 1) : x + 8 * tile; }
__device__ __forceinline__ float2 cis(int k, int n) {
  k &= n - 1; if (2 * k > n) k -= n;
  const float a = (float)k * (6.283185307179586f / (float)n);
  return make_float2(__cosf(a), __sinf(a));
}
template <bool OUT4> __device__ __forceinline__ void make_dft(Dft& D, int g, int t) {
#pragma unroll
  for (int q = 0; q < 16; q++) {
    const int b = q >> 3, u = (q >> 2) & 1, r = (q >> 1) & 1, v = q & 1;
    const float2 w = cis(fidx<OUT4>(v, g) * fidx<false>(2 * u + r, 2 * t + b), 32);
    D.m[b][u][0][q & 3] = pack2(w.x, w.y); D.m[b][u][1][q & 3] = pack2(-w.y, w.x);
  }
}
__device__ __forceinline__ void mma_dc(float (&d)[4], uint32_t a0, uint32_t a1, uint32_t a2, uint32_t a3, uint32_t b0, uint32_t b1, const float (&c)[4]) {
  asm("mma.sync.aligned.m16n8k16.row.col.f32.bf16.bf16.f32 {%0,%1,%2,%3}, {%4,%5,%6,%7}, {%8,%9}, {%10,%11,%12,%13};"
    : "=f"(d[0]), "=f"(d[1]), "=f"(d[2]), "=f"(d[3]) : "r"(a0), "r"(a1), "r"(a2), "r"(a3), "r"(b0), "r"(b1), "f"(c[0]), "f"(c[1]), "f"(c[2]), "f"(c[3])); }
__device__ __forceinline__ void dft_b(const Dft& D, const uint32_t (&x)[2][4], float (&o)[2][8]) {
#pragma unroll
  for (int ri = 0; ri < 2; ri++) {
    float z[4] = {0.f, 0.f, 0.f, 0.f}, e[4], p[4];
    mma_dc(e, D.m[0][0][ri][0], D.m[0][0][ri][1], D.m[0][0][ri][2], D.m[0][0][ri][3], x[0][0], x[0][1], z);
    mma_dc(e, D.m[0][1][ri][0], D.m[0][1][ri][1], D.m[0][1][ri][2], D.m[0][1][ri][3], x[0][2], x[0][3], e);
    mma_dc(p, D.m[1][0][ri][0], D.m[1][0][ri][1], D.m[1][0][ri][2], D.m[1][0][ri][3], x[1][0], x[1][1], e);
    mma_dc(p, D.m[1][1][ri][0], D.m[1][1][ri][1], D.m[1][1][ri][2], D.m[1][1][ri][3], x[1][2], x[1][3], p);
#pragma unroll
    for (int q = 0; q < 4; q++) { o[ri][q] = p[q]; o[ri][4 + q] = fmaf(2.f, e[q], -p[q]); }
  }
}
__device__ __forceinline__ void dft_a(const uint32_t (&m)[2][2][4], const uint32_t (&x0)[2][4], const uint32_t (&x1)[2][4], float (&o)[2][8]) {
#pragma unroll
  for (int ri = 0; ri < 2; ri++) {
    float z[4] = {0.f, 0.f, 0.f, 0.f}, e[4], p[4];
    mma_dc(e, x0[0][0], x1[0][0], x0[0][1], x1[0][1], m[0][ri][0], m[0][ri][1], z);
    mma_dc(e, x0[0][2], x1[0][2], x0[0][3], x1[0][3], m[0][ri][2], m[0][ri][3], e);
    mma_dc(p, x0[1][0], x1[1][0], x0[1][1], x1[1][1], m[1][ri][0], m[1][ri][1], e);
    mma_dc(p, x0[1][2], x1[1][2], x0[1][3], x1[1][3], m[1][ri][2], m[1][ri][3], p);
#pragma unroll
    for (int q = 0; q < 4; q++) { o[ri][q] = p[q]; o[ri][4 + q] = fmaf(2.f, e[q], -p[q]); }
  }
}
__device__ __forceinline__ uint32_t twid(float re, float im, float c, float s) { return pack2(fmaf(re, c, im * s), fmaf(im, c, -re * s)); }
__device__ __forceinline__ void cpa16(uint32_t d, const void* s) { asm volatile("cp.async.cg.shared.global [%0], [%1], 16;" :: "r"(d), "l"(s) : "memory"); }
__device__ __forceinline__ void sts32(uint32_t a, uint32_t x) { asm volatile("st.shared.u32 [%0], %1;" :: "r"(a), "r"(x) : "memory"); }
__device__ __forceinline__ void cpa_commit() { asm volatile("cp.async.commit_group;" ::: "memory"); }
template <int N> __device__ __forceinline__ void cpa_wait() { asm volatile("cp.async.wait_group %0;" :: "n"(N) : "memory"); }
__device__ __forceinline__ uint32_t lds32(uint32_t a) { uint32_t r; asm volatile("ld.shared.u32 %0, [%1];" : "=r"(r) : "r"(a) : "memory"); return r; }
constexpr int F_TP = 4112, F_TSZ = 8 * F_TP;

__device__ __forceinline__ void fft_wprep(const bf16* __restrict__ wr, const bf16* __restrict__ wi, int cta, int ncta) {
  const int tid = threadIdx.x;
#pragma unroll 2
  for (int it = cta; it < 256; it += ncta) {
    const int g = (it >> 1) & 7, c = (it >> 4) & 3, i = it >> 6, t = 2 * (it & 1) + (tid & 1);
    const int k0 = g + 8 * i + 32 * (8 * c + 2 * t), l0 = (tid & ~1) + (g & 1);
    uint32_t a[2][4], b[2][4];
#pragma unroll
    for (int q = 0; q < 8; q++) {
      const int o = (k0 + 32 * ((q >> 1) & 1) + 1024 * (q & 1)) * 513 + l0 + 256 * (q >> 2);
      a[q >> 2][q & 3] = __ldg(reinterpret_cast<const uint32_t*>(wr + o));
      b[q >> 2][q & 3] = __ldg(reinterpret_cast<const uint32_t*>(wi + o));
    }
    uint4* dst = g_wt + l0 * 512 + it * 2 + (tid & 1);
#pragma unroll
    for (int q = 0; q < 4; q++) {
      const int hf = q >> 1, l = l0 + 256 * hf + (q & 1);
      const uint32_t sel = (q & 1) ? 0x7632 : 0x5410;
      if (l & 511) dst[(256 * hf + (q & 1)) * 512] = make_uint4(__byte_perm(a[hf][0], b[hf][0], sel), __byte_perm(a[hf][1], b[hf][1], sel),
                                                              __byte_perm(a[hf][2], b[hf][2], sel), __byte_perm(a[hf][3], b[hf][3], sel));
    }
  }
  for (int e = cta * 256 + tid; e < 4096; e += ncta * 256) {
    const int l = (e >> 11) * 512, k = e & 2047, kn = (2048 - k) & 2047, k2 = (k >> 5) & 31;
    const float re = 0.5f * (__bfloat162float(wr[k * 513 + l]) + __bfloat162float(wr[kn * 513 + l]));
    const float im = 0.5f * (__bfloat162float(wi[k * 513 + l]) - __bfloat162float(wi[kn * 513 + l]));
    reinterpret_cast<uint32_t*>(g_wt)[(64 * ((k >> 3) & 3) + 16 * (k2 >> 3) + 2 * (k & 7) + ((k2 >> 2) & 1)) * 8 + l * 2048 + 2 * (k2 & 3) + (k >> 10)] = pack2(re, im);
  }
}

__device__ __forceinline__ void fft_rows_fwd(const bf16* __restrict__ x, uint32_t sb, int cta, int ncta) {
  const int warp = threadIdx.x >> 5, lane = threadIdx.x & 31, g = lane >> 2, t = lane & 3;
  const uint32_t in = sb + warp * 8192, tb = sb + 65536;
  const uint32_t f0 = pin(in + (lane >> 3) * 256 + (((lane & 7) ^ (2 * (lane >> 3))) << 4));
  const uint32_t xo = pin((256 * (warp & 3) + 64 * (warp >> 2)) * 2048 + lane * 8);
  auto fetch = [&](int it, int buf) {
    const bf16* src = x + (xo + (128 * (it & 1) + 32 * ((it >> 4) & 1) + 8 * (it >> 5) + ((it >> 1) & 7)) * 2048);
#pragma unroll
    for (int q = 0; q < 8; q++) cpa16(((f0 + buf * 4096) ^ ((q >> 2) * 144)) + (q & 3) * 1024, src + q * 256);
    cpa_commit();
  };
  fetch(cta, 0);
  Dft D; make_dft<true>(D, g, t);
  float2 tw[4][8];
#pragma unroll
  for (int q = 0; q < 32; q++) tw[q >> 3][q & 7] = cis(fidx<true>((q >> 1) & 3, g) * fidx<false>(q >> 3, 2 * t + (q & 1)), 1024);
  const uint32_t la = pin(in + lane * 128 + ((lane & 7) << 4));
  const uint32_t wa = pin(tb + warp * F_TP + fidx<true>(0, g) * 128 + t * 16), wz = pin((g & 1) ? -64 : 64);
  const uint32_t ra = pin(tb + (lane & 1) * 4 * F_TP + ((lane >> 1) + 16 * (warp ^ ((warp >> 1) & 1))) * 4);
  uint4* dst = g_y + (threadIdx.x >> 1) * 256 + (lane & 1);
  int buf = 0;
  auto drain = [&](int it, int q) {
    const uint32_t r = ra + (buf ^ 1) * F_TSZ + q * 512;
    const uint4 v = make_uint4(lds32(r), lds32(r + F_TP), lds32(r + 2 * F_TP), lds32(r + 3 * F_TP));
    if (it >= 0) dst[it * 2 + q * 32768] = v;
  };
  int it = cta;
#pragma unroll 1
  for (; it < 128; it += ncta, buf ^= 1) {
    cpa_wait<0>(); __syncthreads();
    uint32_t a[4][2][4], y[4][2][4];
#pragma unroll
    for (int q = 0; q < 8; q++) ldsm4t(a[q & 3][q >> 2], (la + buf * 4096) ^ (q << 4));
    if (it + ncta < 128) fetch(it + ncta, buf ^ 1);
    float o[2][8];
#pragma unroll
    for (int i = 0; i < 4; i++) {
      dft_b(D, a[i], o);
      drain(it - ncta, i);
#pragma unroll
      for (int q = 0; q < 8; q++) y[q >> 1][q & 1][i] = twid(o[0][q], o[1][q], tw[i][q].x, tw[i][q].y);
    }
    const uint32_t w0 = wa + buf * F_TSZ + ((g & 1) << 6);
#pragma unroll
    for (int z = 0; z < 2; z++) {
      float o2[2][8];
      dft_b(D, y[2 * z], o); drain(it - ncta, 4 + 2 * z); dft_b(D, y[2 * z + 1], o2); drain(it - ncta, 5 + 2 * z);
#pragma unroll
      for (int i = 0; i < 4; i++) {
        const float sg = i < 2 ? 1.f : -1.f;
        sts128(w0 + z * wz + fidx<true>(i, 0) * 128, pack2(o[0][2 * i], sg * o[1][2 * i]), pack2(o[0][2 * i + 1], sg * o[1][2 * i + 1]),
               pack2(o2[0][2 * i], sg * o2[1][2 * i]), pack2(o2[0][2 * i + 1], sg * o2[1][2 * i + 1]));
      }
    }
  }
  __syncthreads();
#pragma unroll
  for (int q = 0; q < 8; q++) drain(it - ncta, q);
}

__device__ __forceinline__ void fft_cols(uint32_t sb, int cta, int ncta) {
  const int warp = threadIdx.x >> 5, lane = threadIdx.x & 31, g = lane >> 2, t = lane & 3;
  const uint32_t in = sb + warp * 16384 + lane * 16, tab = sb + 131072 + lane * 16;
  auto fetch_y = [&](int l) {
#pragma unroll
    for (int q = 0; q < 16; q++) cpa16(in + q * 512, g_y + (q < 8 ? l : (1024 - l) & 1023) * 256 + (q & 7) * 32 + lane);
  };
  auto fetch_w = [&](int l) {
#pragma unroll
    for (int q = 0; q < 16; q++) cpa16(in + 8192 + q * 512, g_wt + l * 512 + q * 32 + lane);
  };
  const int l0 = cta * 8 + warp, dl = ncta * 8;
  if (l0 <= 512) fetch_y(l0);
  cpa_commit();
  if (l0 <= 512) fetch_w(l0);
  cpa_commit();
  Dft D; make_dft<false>(D, g, t);
#pragma unroll
  for (int q = 2 * warp; q < 2 * warp + 2; q++) {
    const int r = fidx<false>(q & 3, g), c = fidx<false>(q >> 2, 2 * t);
    const float2 w0 = cis(r * c, 1024), w1 = cis(r * c + r, 1024), p0 = cis(r + 32 * c, 2048), p1 = cis(r + 32 * c + 32, 2048);
    sts128(tab + q * 512, __float_as_uint(w0.x), __float_as_uint(w0.y), __float_as_uint(w1.x), __float_as_uint(w1.y));
    sts128(tab + 8192 + q * 512, __float_as_uint(p0.x), __float_as_uint(p0.y), __float_as_uint(p1.x), __float_as_uint(p1.y));
  }
  if (warp == 0) {
#pragma unroll
    for (int q = 0; q < 8; q++) {
      const int v = q >> 2, b = (q >> 1) & 1, ri = q & 1;
      sts128(tab + 16384 + q * 512, D.m[b][0][ri][v], D.m[b][0][ri][v + 2], D.m[b][1][ri][v], D.m[b][1][ri][v + 2]);
    }
  }
  __syncthreads();
#pragma unroll 1
  for (int l = l0; l <= 512; l += dl) {
    uint32_t a[2][4][2][4], y[2][4][2][4];
    float o[2][2][8];
    cpa_wait<1>();
#pragma unroll
    for (int q = 0; q < 16; q++) lds128(a[q >> 3][(q >> 1) & 3][q & 1], in + q * 512);
    if (!(l & 511)) {
      const uint32_t m0 = l ? 0x80000000u : 0u;
#pragma unroll
      for (int q = 0; q < 32; q++) { a[0][q >> 3][(q >> 2) & 1][q & 3] ^= m0; a[1][q >> 3][(q >> 2) & 1][q & 3] ^= m0 ^ 0x80000000u; }
    }
    auto first = [&]() {
#pragma unroll
      for (int i = 0; i < 4; i++) {
        dft_b(D, a[0][i], o[0]); dft_b(D, a[1][i], o[1]);
#pragma unroll
        for (int r = 0; r < 4; r++) {
          const float4 w = lds128f(tab + (4 * i + r) * 512);
#pragma unroll
          for (int s = 0; s < 2; s++) {
            y[s][r][0][i] = twid(o[s][0][2 * r], o[s][1][2 * r], w.x, w.y);
            y[s][r][1][i] = twid(o[s][0][2 * r + 1], o[s][1][2 * r + 1], w.z, w.w);
          }
        }
      }
    };
    first();
    if (l + dl <= 512) fetch_y(l + dl);
    cpa_commit();
    cpa_wait<1>();
#pragma unroll
    for (int zv = 0; zv < 4; zv++) {
      const int z = zv >> 1, v = zv & 1;
      uint32_t m[2][2][4];
#pragma unroll
      for (int q = 0; q < 4; q++) lds128(m[q >> 1][q & 1], tab + 16384 + (4 * v + q) * 512);
      dft_a(m, y[0][2 * z], y[0][2 * z + 1], o[0]); dft_a(m, y[1][2 * z], y[1][2 * z + 1], o[1]);
#pragma unroll
      for (int q = 0; q < 4; q++) {
        const int i = 2 * z + (q & 1), c = v + (q & 2);
        uint32_t w[4]; lds128(w, in + 8192 + (4 * i + c) * 512);
        const float4 ph = lds128f(tab + 8192 + (4 * c + i) * 512);
#pragma unroll
        for (int b = 0; b < 2; b++) {
          const float cs = b ? ph.z : ph.x, sn = b ? ph.w : ph.y;
          const float r1 = __uint_as_float(w[2 * b] << 16), i1 = __uint_as_float(w[2 * b] & 0xFFFF0000u);
          const float r2 = __uint_as_float(w[2 * b + 1] << 16), i2 = __uint_as_float(w[2 * b + 1] & 0xFFFF0000u);
          const float Sr = r1 + r2, Si = i1 + i2, Dr = r1 - r2, Di = i1 - i2;
          const float ar = fmaf(-Dr, sn, Sr), ai = fmaf(-Di, sn, Si), dr = fmaf(Dr, sn, Sr), di = fmaf(Di, sn, Si), br = -Di * cs, bi = Dr * cs;
          const float Ar = o[0][0][2 * q + b], Ai = o[0][1][2 * q + b], Br = o[1][0][2 * q + b], Bi = o[1][1][2 * q + b];
          a[0][i][b][c] = pack2(fmaf(ar, Ai, fmaf(ai, Ar, fmaf(br, Bi, bi * Br))), fmaf(ar, Ar, fmaf(-ai, Ai, fmaf(br, Br, -bi * Bi))));
          a[1][i][b][c] = pack2(fmaf(dr, Bi, fmaf(di, Br, fmaf(-br, Ai, -bi * Ar))), fmaf(dr, Br, fmaf(-di, Bi, fmaf(-br, Ar, bi * Ai))));
        }
      }
    }
    if (l + dl <= 512) fetch_w(l + dl);
    cpa_commit();
    first();
#pragma unroll
    for (int s = 0; s < 2; s++) {
      uint4* dst = g_y + (s ? (1024 - l) & 1023 : l) * 256 + lane;
      const float sg = s ? -1.f : 1.f;
#pragma unroll
      for (int i = 0; i < 4; i++) {
        dft_b(D, y[s][i], o[0]);
#pragma unroll
        for (int b = 0; b < 2; b++)
          dst[(2 * i + b) * 32] = make_uint4(pack2(sg * o[0][0][b], o[0][1][b]), pack2(sg * o[0][0][2 + b], o[0][1][2 + b]),
                                             pack2(sg * o[0][0][4 + b], o[0][1][4 + b]), pack2(sg * o[0][0][6 + b], o[0][1][6 + b]));
      }
    }
  }
}

__device__ __forceinline__ void fft_rows_inv(const CUtensorMap* om, uint32_t sb, int cta, int ncta) {
  const int warp = threadIdx.x >> 5, lane = threadIdx.x & 31, g = lane >> 2, t = lane & 3, wg = warp >> 2, w4 = warp & 3;
  const uint32_t tb = sb + 32768 + wg * 2 * F_TSZ;
  const uint4* src = g_y + pin((256 * ((lane >> 1) & 3) + 64 * (lane >> 3) + 8 * w4) * 256 + (lane & 1));
  const uint32_t wa = pin(tb + (lane & 1) * 4 * F_TP + w4 * 1024 + (lane >> 1) * 4);
  uint4 pf[8];
  auto fetch = [&](int it, int hf) {
#pragma unroll
    for (int q = 0; q < 8; q++) pf[q] = __ldcg(src + (it * 2 + hf * 8192) + q * 256);
  };
  auto put = [&](uint32_t off) {
#pragma unroll
    for (int q = 0; q < 8; q++) {
      sts32(wa + off + q * 64, pf[q].x); sts32(wa + off + q * 64 + F_TP, pf[q].y);
      sts32(wa + off + q * 64 + 2 * F_TP, pf[q].z); sts32(wa + off + q * 64 + 3 * F_TP, pf[q].w);
    }
  };
  const int it0 = 2 * cta + wg;
  if (it0 >= 128) return;
  fetch(it0, 0); put(0); fetch(it0, 1); put(512);
  Dft D; make_dft<false>(D, g, t);
  float2 tw[4][8];
#pragma unroll
  for (int q = 0; q < 32; q++) {
    tw[q >> 3][q & 7] = cis(fidx<false>((q >> 1) & 3, g) * fidx<false>(q >> 3, 2 * t + (q & 1)), 1024);
    tw[q >> 3][q & 7].x *= 1.f / 2097152.f; tw[q >> 3][q & 7].y *= 1.f / 2097152.f;
  }
  const uint32_t la = pin(tb + w4 * F_TP + lane * 16), ob = uni(sb + warp * 4096);
  const uint32_t oa = pin(ob + (lane >> 1) * 128 + (((4 * (lane & 1)) ^ ((lane >> 1) & 7)) << 4));
#pragma unroll 1
  for (int n = 0;; n++) {
    const int it = it0 + (n >> 1) * 2 * ncta, hf = n & 1, buf = (n >> 1) & 1;
    if (it >= 128) break;
    if (!hf) bar_sync(1 + wg, 128);
    uint32_t a[4][2][4], y[4][2][4];
#pragma unroll
    for (int q = 0; q < 8; q++) lds128(a[q >> 1][q & 1], la + buf * F_TSZ + hf * 4 * F_TP + q * 512);
    fetch(min(it + 2 * ncta, 127), hf);
    float o[2][8];
#pragma unroll
    for (int i = 0; i < 4; i++) {
      dft_b(D, a[i], o);
#pragma unroll
      for (int q = 0; q < 8; q++) y[q >> 1][q & 1][i] = twid(o[0][q], o[1][q], tw[i][q].x, tw[i][q].y);
    }
    if (lane == 0) asm volatile("cp.async.bulk.wait_group.read 0;" ::: "memory");
    __syncwarp();
#pragma unroll
    for (int c = 0; c < 4; c++) {
      dft_b(D, y[c], o);
#pragma unroll
      for (int ri = 0; ri < 2; ri++)
        stsm4((oa ^ (c << 4)) + (1 - ri) * 2048, pack2(o[ri][0], o[ri][1]), pack2(o[ri][2], o[ri][3]), pack2(o[ri][4], o[ri][5]), pack2(o[ri][6], o[ri][7]));
    }
    fence_async();
    __syncwarp();
    if (lane == 0) {
      const int m = 256 * w4 + 32 * ((it >> 1) & 7) + 8 * (it >> 5) + 4 * (it & 1) + 2 * hf + ((it >> 4) & 1);
      asm volatile("cp.async.bulk.tensor.3d.global.shared::cta.bulk_group [%0, {0, 0, %2}], [%1];" :: "l"(om), "r"(ob), "r"(2 * m) : "memory");
      asm volatile("cp.async.bulk.commit_group;" ::: "memory");
    }
    put((buf ^ 1) * F_TSZ + hf * 512);
  }
  if (lane == 0) asm volatile("cp.async.bulk.wait_group 0;" ::: "memory");
}
constexpr int F_SMEM = 65536 + 2 * F_TSZ + 1024;
__global__ void __launch_bounds__(256, 1) fft_pre_kernel(const bf16* __restrict__ x, const bf16* __restrict__ wr, const bf16* __restrict__ wi) {
  extern __shared__ __align__(1024) uint8_t smem_raw[];
  const uint32_t sb = (smem_u32(smem_raw) + 1023) & ~1023u;
  fft_wprep(wr, wi, blockIdx.x, gridDim.x);
  fft_rows_fwd(x, sb, blockIdx.x, gridDim.x);
}
__device__ __forceinline__ void grid_arrive(unsigned* ctr) {
  __syncthreads();
  if (threadIdx.x == 0) { __threadfence(); atomicAdd(ctr, 1u); }
}
__device__ __forceinline__ void grid_wait(unsigned* ctr, unsigned n) {
  if (threadIdx.x == 0) {
    int it = 0;
    while (*reinterpret_cast<volatile unsigned*>(ctr) < n) { __nanosleep(200); if (++it > SPIN_LIMIT) { g_err = 3; break; } }
    __threadfence();
  }
  __syncthreads();
}

struct RecMaps { CUtensorMap wq, wk, wv, wo, x, k, q, v, fo; };
#define NSW 16
#define EXP 0
#define PD1 4
#define NE4 6
#define NE6 0
#define NA4 14
#define NA6 18
#define NB1 24
#define OXPOS 28
#define KVPOS 2
#define NK0 0
#define FLPOS 1
#define XWPOS 10
#define FSPOS 28
#define RL0 4
#define RLS 6
#define RLB 4
#define VL0 3
#define RI 9
#define RJ 8
#define NPRE 0
#define UNP 16
#define XC 2
#define XD 2
#define SPOS 2
#ifndef NV0
#define NV0 2
#endif
#define TGP 3
#define FENP 0
#define LW0 8
#define XB 2
#define XA 4
constexpr int R_WO = 0, R_X = 65536, R_MEM = 131072, R_WC = 147456, R_RED = R_WC + NSW * 2048, R_O = R_RED + 2048, R_S = R_O + 2048, R_P = R_S + 3072, R_STAGE = R_P + 2048,
              R_K = R_STAGE + 8192, R_Q = R_K + 8192, R_V = R_Q + 2048, R_ID = R_V + 16384, R_T = R_ID + 512, R_BAR = R_T + 512, R_TS = R_BAR + 128,
              R_TOTAL = R_TS;
#define TS(i)
#define LOG(i, v)
constexpr int B_KV = R_BAR, B_W = R_BAR + 8, B_X = R_BAR + 80, B_PK = R_BAR + 24, B_C = R_BAR + 32, B_B = R_BAR + 40, B_DUE = R_BAR + 48, B_ONE = R_BAR + 64;
#define DLY_A 150
#define DLY_V 150
#define DLY_C 100
#define DLY_L 90
#define NS_B 1280
#define NS_C 1920
#define NS_P 3008
#define NS_V 128
#define NS_F (NS_B - 192)
#define NS_K 128
#define NS_M 64
#define NS_X 128
#define NS_PEN 576
__device__ __forceinline__ float rcp(float x) { float r; asm("rcp.approx.ftz.f32 %0, %1;" : "=f"(r) : "f"(x)); return r; }
__device__ __forceinline__ uint32_t movm(uint32_t a) { uint32_t d; asm volatile("movmatrix.sync.aligned.m8n8.trans.b16 %0, %1;" : "=r"(d) : "r"(a)); return d; }
__device__ __forceinline__ uint32_t hadd2(uint32_t a, uint32_t b) { uint32_t d; asm("add.rn.bf16x2 %0, %1, %2;" : "=r"(d) : "r"(a), "r"(b)); return d; }
__device__ __forceinline__ void mma_a(float (&d)[4], const uint32_t (&a)[4], uint32_t b0, uint32_t b1) { mma16816(d, a[0], a[1], a[2], a[3], b0, b1); }
__device__ __forceinline__ bool elect() {
  uint32_t p; asm volatile("{.reg .pred p; elect.sync _|p, 0xffffffff; selp.u32 %0, 1, 0, p;}" : "=r"(p)); return p; }
__device__ __forceinline__ void tma3d(uint32_t dst, const CUtensorMap* m, int c1, int c2, uint32_t bar) {
  asm volatile("cp.async.bulk.tensor.3d.shared::cluster.global.mbarrier::complete_tx::bytes [%0], [%1, {0, %3, %4}], [%2];"
    :: "r"(dst), "l"(m), "r"(bar), "r"(c1), "r"(c2) : "memory"); }
__device__ __forceinline__ void tma4d(uint32_t dst, const CUtensorMap* m, int c1, int c2, uint32_t bar) {
  asm volatile("cp.async.bulk.tensor.4d.shared::cluster.global.mbarrier::complete_tx::bytes [%0], [%1, {0, %3, %4, 0}], [%2];"
    :: "r"(dst), "l"(m), "r"(bar), "r"(c1), "r"(c2) : "memory"); }
template <int OFF, int ACC>
__device__ __forceinline__ void wg_rs32(float (&d)[16], const uint32_t (&a)[4], uint32_t db) {
  if (ACC)
    asm volatile("{.reg .b64 db; .reg .b32 lo; add.u32 lo, %20, %21; mov.b64 db, {lo, 0x40000040};\n"
      "wgmma.mma_async.sync.aligned.m64n32k16.f32.bf16.bf16 {%0,%1,%2,%3,%4,%5,%6,%7,%8,%9,%10,%11,%12,%13,%14,%15}, {%16,%17,%18,%19}, db, 1, 1, 1, 0;}"
      : "+f"(d[0]), "+f"(d[1]), "+f"(d[2]), "+f"(d[3]), "+f"(d[4]), "+f"(d[5]), "+f"(d[6]), "+f"(d[7]), "+f"(d[8]), "+f"(d[9]), "+f"(d[10]), "+f"(d[11]), "+f"(d[12]), "+f"(d[13]), "+f"(d[14]), "+f"(d[15])
      : "r"(a[0]), "r"(a[1]), "r"(a[2]), "r"(a[3]), "r"(db), "n"(OFF));
  else
    asm volatile("{.reg .b64 db; .reg .b32 lo; add.u32 lo, %20, %21; mov.b64 db, {lo, 0x40000040};\n"
      "wgmma.mma_async.sync.aligned.m64n32k16.f32.bf16.bf16 {%0,%1,%2,%3,%4,%5,%6,%7,%8,%9,%10,%11,%12,%13,%14,%15}, {%16,%17,%18,%19}, db, 0, 1, 1, 0;}"
      : "=f"(d[0]), "=f"(d[1]), "=f"(d[2]), "=f"(d[3]), "=f"(d[4]), "=f"(d[5]), "=f"(d[6]), "=f"(d[7]), "=f"(d[8]), "=f"(d[9]), "=f"(d[10]), "=f"(d[11]), "=f"(d[12]), "=f"(d[13]), "=f"(d[14]), "=f"(d[15])
      : "r"(a[0]), "r"(a[1]), "r"(a[2]), "r"(a[3]), "r"(db), "n"(OFF));
}
template <int I> using IC = std::integral_constant<int, I>;
template <int I, int N, class F> __device__ __forceinline__ void sfor(F&& f) {
  if constexpr (I < N) { f(std::integral_constant<int, I>{}); sfor<I + 1, N>(f); }
}
__device__ __forceinline__ void keep(float (&d)[16]) {
  asm volatile("" : "+f"(d[0]), "+f"(d[1]), "+f"(d[2]), "+f"(d[3]), "+f"(d[4]), "+f"(d[5]), "+f"(d[6]), "+f"(d[7]),
      "+f"(d[8]), "+f"(d[9]), "+f"(d[10]), "+f"(d[11]), "+f"(d[12]), "+f"(d[13]), "+f"(d[14]), "+f"(d[15]) :: "memory");
}

template <int N, int S2 = 1024> __device__ __forceinline__ void ldx(uint32_t (&v)[N][4], const uint8_t* p) {
#pragma unroll
  for (int k = 0; k < 2 * N; k++) {
    const int i = k;
    asm volatile("ld.relaxed.gpu.global.v2.b32 {%0,%1}, [%2];" : "=r"(v[i >> 1][2 * (i & 1)]), "=r"(v[i >> 1][2 * (i & 1) + 1]) : "l"(p + (i & 3) * 256 + (i >> 2) * S2) : "memory");
  }
}
__device__ __forceinline__ uint32_t dif2(uint32_t a, uint32_t b, uint32_t tag) { uint32_t r; asm("lop3.b32 %0, %1, %2, %3, 0x7e;" : "=r"(r) : "r"(a), "r"(b), "r"(tag)); return r; }
__device__ __forceinline__ uint32_t dif2v(uint32_t a, uint32_t b, uint32_t tag) { uint32_t r; asm volatile("lop3.b32 %0, %1, %2, %3, 0x7e;" : "=r"(r) : "r"(a), "r"(b), "r"(tag)); return r; }
__device__ __forceinline__ uint32_t or3(uint32_t a, uint32_t b, uint32_t c) { uint32_t r; asm("lop3.b32 %0, %1, %2, %3, 0xfe;" : "=r"(r) : "r"(a), "r"(b), "r"(c)); return r; }
__device__ __forceinline__ uint32_t after(uint32_t x, float f, uint32_t z) { uint32_t r; asm("lop3.b32 %0, %1, %2, %3, 0xea;" : "=r"(r) : "r"(__float_as_uint(f)), "r"(z), "r"(x)); return r; }
__device__ __forceinline__ bool any_bit(uint32_t a, uint32_t b, uint32_t m) {
  uint32_t r; asm("lop3.b32 %0, %1, %2, %3, 0xa8;" : "=r"(r) : "r"(a), "r"(b), "r"(m)); return __any_sync(0xffffffffu, r); }
template <int W, int N> __device__ __forceinline__ bool stale(const uint32_t (&v)[N][4], uint32_t tag) {
  uint32_t x = dif2(v[0][0], v[0][2], tag);
  if (N == 4) x = or3(x, dif2(v[1][0], v[1][2], tag), dif2(v[2 % N][0], v[2 % N][2], tag));
  return any_bit(x, dif2(v[N - 1][0], v[N - 1][2], tag), 1);
}
template <int W, int N, int S2 = 1024> __device__ __forceinline__ void retry(uint32_t (&v)[N][4], const uint8_t* p, uint32_t tag, int& it) {
#pragma unroll 1
  do { ldx<N, S2>(v, p); it += INC_A; } while (stale<W>(v, tag) && it < SPIN_LIMIT);
}
__device__ __forceinline__ void mma_h(float (&d)[4], const uint32_t (&a)[4], const uint32_t (&b)[4], int hf) { mma16816(d, a[0], a[1], a[2], a[3], b[2 * hf], b[2 * hf + 1]); }
__device__ __forceinline__ void sts128(uint32_t a, const uint32_t (&r)[4]) { sts128(a, r[0], r[1], r[2], r[3]); }
__device__ __forceinline__ void sts128f(uint32_t a, const float* r) { sts128(a, __float_as_uint(r[0]), __float_as_uint(r[1]), __float_as_uint(r[2]), __float_as_uint(r[3])); }
__device__ __forceinline__ void mbar_spin(uint32_t bar, uint32_t par, int& it) {
  asm volatile("{.reg .pred p; .reg .b32 par; mov.b32 par, %2;\nLOOP: mbarrier.try_wait.parity.shared::cta.b64 p, [%1], par; @p bra.uni DONE;\n"
               "add.s32 %0, %0, 1; setp.le.s32 p, %0, %3; @p bra.uni LOOP;\nDONE: }" : "+r"(it) : "r"(bar), "r"(par), "n"(SPIN_LIMIT) : "memory"); }
__device__ __forceinline__ void warp_arrive(uint32_t bar) {
  __syncwarp(); asm volatile("{.reg .pred p; elect.sync _|p, 0xffffffff; @p mbarrier.arrive.shared::cta.b64 _, [%0];}" :: "r"(bar) : "memory"); }
__device__ __forceinline__ void delay_until(unsigned t) {
  asm volatile("{.reg .pred p; .reg .b64 c; .reg .b32 lo, hi;\nLOOP: mov.u64 c, %%clock64; mov.b64 {lo, hi}, c; sub.s32 lo, lo, %0; setp.lt.s32 p, lo, 0; @p bra.uni LOOP;}" :: "r"(t) : "memory"); }
__device__ __forceinline__ void cut(int it) { asm volatile("{.reg .pred p; setp.lt.s32 p, %0, 0;\nL: @p st.volatile.shared.u32 [%0], %0; @p bra.uni L;}" :: "r"(it) : "memory"); }
__device__ __forceinline__ void zero(float (&c)[4][4]) {
#pragma unroll
  for (int i = 0; i < 4; i++) c[i][0] = c[i][1] = c[i][2] = c[i][3] = 0.f;
}

__device__ __forceinline__ void sched() { asm volatile("griddepcontrol.launch_dependents;" ::: "memory"); }
__device__ __forceinline__ const uint8_t* pinp(const uint8_t* p) { return reinterpret_cast<const uint8_t*>(__shfl_xor_sync(0xffffffffu, reinterpret_cast<unsigned long long>(p), 0)); }
__device__ __forceinline__ uint32_t bar_or(int id, uint32_t x) {
  uint32_t r; asm volatile("{.reg .pred p, q; setp.ne.u32 p, %2, 0; bar.red.or.pred q, %1, 256, p; selp.u32 %0, 1, 0, q;}" : "=r"(r) : "r"(id), "r"(x) : "memory"); return r; }
__device__ __forceinline__ void bar_sync_unless(int id, uint32_t x) { asm volatile("{.reg .pred p; setp.eq.u32 p, %1, 0; @p bar.sync %0, 256;}" :: "r"(id), "r"((uint32_t)x) : "memory"); }
__device__ __forceinline__ void bar_arrive_unless(int id, uint32_t x) { asm volatile("{.reg .pred p; setp.eq.u32 p, %1, 0; @p bar.arrive %0, 256;}" :: "r"(id), "r"((uint32_t)x) : "memory"); }
__device__ __forceinline__ void stsm2t(uint32_t a, uint32_t r0, uint32_t r1, uint32_t x) {
  asm volatile("{.reg .pred p; setp.eq.u32 p, %3, 0; @p stmatrix.sync.aligned.m8n8.x2.trans.shared.b16 [%0], {%1,%2};}" :: "r"(a), "r"(r0), "r"(r1), "r"((uint32_t)x) : "memory"); }
__device__ __forceinline__ uint32_t or_and(uint32_t a, uint32_t b, uint32_t m) { uint32_t r; asm("lop3.b32 %0, %1, %2, %3, 0xa8;" : "=r"(r) : "r"(a), "r"(b), "r"(m)); return r; }
#define rare(x) __builtin_expect(!!(x), 0)
__device__ __forceinline__ uint32_t gtime() { unsigned long long g; asm volatile("mov.u64 %0, %%globaltimer;" : "=l"(g) :: "memory"); return (uint32_t)g; }
__device__ __forceinline__ void wait_time(uint32_t t) {
  asm volatile("{.reg .pred p; .reg .b32 g; .reg .b64 c;\nLOOP: mov.u64 c, %%globaltimer; cvt.u32.u64 g, c; sub.s32 g, %0, g; setp.lt.u32 p, g, 16384; @p bra.uni LOOP;}" :: "r"(t - 1) : "memory"); }
__device__ __forceinline__ uint32_t ldx32(const void* p) { uint32_t v; asm volatile("ld.relaxed.gpu.global.b32 %0, [%1];" : "=r"(v) : "l"(p) : "memory"); return v; }
__device__ __forceinline__ void stx32(const void* p, uint32_t v) { asm volatile("st.relaxed.gpu.global.b32 [%0], %1;" :: "l"(p), "r"(v) : "memory"); }

__global__ void __launch_bounds__(256, 1)
rec_kernel(const __grid_constant__ RecMaps maps, const bf16* __restrict__ xin, const bf16* __restrict__ mem0) {
  extern __shared__ __align__(1024) uint8_t smem_raw[];
  const uint32_t sb = smem_u32(smem_raw);
  int role = blockIdx.x;
  {
    uint32_t smid, nsm; asm volatile("mov.u32 %0, %%smid;" : "=r"(smid)); asm volatile("mov.u32 %0, %%nsmid;" : "=r"(nsm));
    const int p = smid >> 1, u = p - 32;
    if (nsm == gridDim.x)
      role = (smid & 1) + (p < 32 ? 4 * ((p & 7) + 8 * (p >> 4)) + 2 * ((p >> 3) & 1) : p < 60 ? 4 * (16 + u % 7 + 7 * (u / 14)) + 2 * ((u / 7) & 1)
                         : p < 62 ? 2 * p + 8 : 2 * p - 4);
    role = uni(role);
  }
  if (role >= 128) {
    fft_cols(sb, role - 128, 4);
    grid_arrive(&g_x.ctr[32]); grid_wait(&g_x.ctr[32], 4);
    fft_rows_inv(&maps.fo, sb, role - 128, 4);
    return;
  }
  const int tid = threadIdx.x, warp = uni(tid >> 5), lane = tid & 31, wg = warp >> 2, w4 = warp & 3, g = lane >> 2, t = lane & 3;
  const int h = role >> 2, j = role & 3, jh = j & 1;
  uint32_t w[48][4];
  float aq[16], av[16];
  int it = 0;

  if (tid == 224) {
    mbar_init(sb + B_KV, 1); mbar_init(sb + B_W, 1); mbar_init(sb + B_X, 1); mbar_init(sb + B_X + 8, 1); mbar_init(sb + B_X + 16, 1); mbar_init(sb + B_X + 24, 1); mbar_init(sb + B_C, 4); mbar_init(sb + B_PK, 4); mbar_init(sb + B_B, 1);
    asm volatile("fence.mbarrier_init.release.cluster;" ::: "memory");
    mbar_expect_tx(sb + B_W, 3 * 65536);
    for (int i = 0; i < 4; i++) {
      tma2d(sb + R_X + i * 16384, &maps.wq, h * DH + 32 * j, i * 256, sb + B_W);
      tma2d(sb + R_MEM + i * 16384, &maps.wk, h * DH + 32 * j, i * 256, sb + B_W);
    }
    for (int i = 0; i < 2; i++) tma2d(sb + R_WO + i * 32768, &maps.wv, h * DH + 64 * (j >> 1), jh * 512 + i * 256, sb + B_W);
    for (int i = 0; i < 4; i++) asm volatile("cp.async.bulk.prefetch.L2.global [%0], 8192;" :: "l"(xin + role * 16384 + i * 4096) : "memory");
    for (int i = 0; i < 4; i++)
      asm volatile("cp.async.bulk.prefetch.tensor.2d.L2.global [%0, {%1, %2}];" :: "l"(&maps.wo), "r"(256 * j + 64 * i), "r"(h * DH) : "memory");
  }
  if (tid < 128) asm volatile("prefetch.global.L2 [%0];" :: "l"(mem0 + tid * 64));
  __syncthreads();
  mbar_spin(sb + B_W, 0, it);
  const int lrow = (lane & 7) + ((lane >> 4) << 3), lhi = (lane >> 3) & 1;
  const int kq = wg ? 1 - jh : 3 * jh;
  const uint32_t LW = lrow * 128 + ((lhi ^ (lane & 7)) << 4);
  {
    const int chunk = w4 < 2 ? w4 + 2 * lhi : 2 * (w4 & 1) + lhi;
    uint32_t a = sb + (w4 < 2 ? R_X : R_MEM) + kq * 16384 + lrow * 64 + ((chunk ^ ((lrow >> 1) & 3)) << 4);
#pragma unroll
    for (int i = 0; i < 16; i++) ldsm4t(w[i], a + i * 1024);
    const uint32_t st = wg ? 1024 : 2048, av0 = sb + R_WO + (LW ^ (w4 << 5));
    const uint32_t a1 = wg ? a + 16384 : av0 + jh * 32768, a2 = wg ? a + 32768 : av0 + (1 - jh) * 32768;
#pragma unroll
    for (int i = 0; i < 16; i++) { ldsm4t(w[16 + i], a1 + i * st); ldsm4t(w[32 + i], a2 + i * st); }
  }
  uint32_t L16 = pin(lane * 16);
  uint8_t* const xb = reinterpret_cast<uint8_t*>(&g_x);
  const uint32_t uW = uni(sb + w4 * 512), uWo = uni(sb + R_WO + w4 * 16384), uMem = uni(sb + R_MEM + kq * 4096);
  const uint32_t dX = uni(((sb + R_X + kq * 16384) >> 4) | 0x10000u);
  auto load_wo = [&](uint32_t (&d)[32][4], int i0, int i1) {
#pragma unroll
    for (int i = i0; i < i1; i++) lds128(d[i], uWo + L16 + (i & 1) * 512 + (i >> 4) * 1024 + (i & 14) * 1024);
  };
  auto issue_x = [&](int n, int k) {
    const uint32_t bar = sb + B_X + 8 * k, q = (k - jh) & 3;
    mbar_expect_tx(bar, 16384); tma3d(sb + R_X + q * 16384, &maps.x, n * SEG, 4 * q, bar);
  };
  auto store_stage = [&](int n) {
    asm volatile("cp.async.bulk.global.shared::cta.bulk_group [%0], [%1], 8192; cp.async.bulk.commit_group;"
                 :: "l"(g_kqv[n & 3][role]), "r"(sb + R_STAGE) : "memory");
  };
  auto issue_kqv = [&](int n) {
    const int p = (n & 3) * 128 + 4 * h;
    mbar_expect_tx(sb + B_KV, 26624);
    tma3d(sb + R_K, &maps.k, 0, p, sb + B_KV); tma3d(sb + R_Q, &maps.q, 8 + 2 * j, p, sb + B_KV); tma3d(sb + R_V, &maps.v, 16, p, sb + B_KV);
  };
  auto fetch4k = [&](uint32_t dst, uint32_t off, uint32_t bar, uint32_t t) {
    asm volatile("{.reg .pred p, q; .reg .b32 g; .reg .b64 c; elect.sync _|q, 0xffffffff; @q mbarrier.arrive.expect_tx.shared::cta.b64 _, [%2], 4096;\n"
                 "LOOP: mov.u64 c, %%globaltimer; cvt.u32.u64 g, c; sub.s32 g, %3, g; setp.lt.u32 p, g, 16384; @p bra.uni LOOP;\n"
                 "@q cp.async.bulk.shared::cluster.global.mbarrier::complete_tx::bytes [%0], [%1], 4096, [%2];}" :: "r"(dst), "l"(xb + off), "r"(bar), "r"(t - 1) : "memory");
  };
  auto issue_c = [&](uint32_t t) { fetch4k(sb + R_MEM + w4 * 4096, offsetof(Xchg, C) + (j >> 1) * 16384 + w4 * 4096, sb + B_C, t); };
  auto wait_x = [&](int n, int i) { if (!(EXP & 1) || n < 2) mbar_spin(sb + B_X + 8 * i, n & 1, it); };
  auto project_v = [&](auto I0, auto I1, auto&& mid) {
    wg_fence();
    sfor<decltype(I0)::value, decltype(I1)::value>([&](auto I) {
      constexpr int i = decltype(I)::value;
      mid(i);
      wg_rs32<((i >> 2) & 3) * 256 + (i & 3) * 2, (i > 0)>(av, w[16 + i], i < 16 ? dX : dX ^ 1024);
    });
    wg_commit();
  };
  auto project_qk = [&](auto I0, auto I1, auto&& mid) {
    const uint32_t dQ = dX + ((uint32_t)it >> 31);
    wg_fence();
    sfor<decltype(I0)::value, decltype(I1)::value>([&](auto I) {
      constexpr int i = decltype(I)::value;
      mid(i);
      wg_rs32<(i >> 2) * 256 + (i & 3) * 2, i != 16>(aq, w[i], dQ);
    });
    wg_commit();
  };
  const uint32_t uP = uni(sb + R_X + (2 - 2 * jh) * 16384 + w4 * 512);
  auto park = [&]() {
    bar_sync(1, 128);
#pragma unroll
    for (int i = 0; i < 4; i++) sts128f(uP + L16 + i * 2048, aq + 4 * i);
    warp_arrive(sb + B_PK);
  };
  auto unpark = [&]() {
#pragma unroll
    for (int i = 0; i < 4; i++) {
      const float4 p = lds128f(uP + L16 + i * 2048);
      aq[4 * i] = p.x; aq[4 * i + 1] = p.y; aq[4 * i + 2] = p.z; aq[4 * i + 3] = p.w;
    }
  };
  auto fin_qk = [&]() {
    const uint32_t a = sb + R_STAGE + (w4 < 2 ? 2048 + w4 * 128 : (w4 & 1) * 256) + (L16 & 112) + (L16 >> 7) * 512;
    stsm4t(a, pack2(aq[0], aq[1]), pack2(aq[4], aq[5]), pack2(aq[8], aq[9]), pack2(aq[12], aq[13]));
    stsm4t(a + (w4 < 2 ? 256 : 128), pack2(aq[2], aq[3]), pack2(aq[6], aq[7]), pack2(aq[10], aq[11]), pack2(aq[14], aq[15]));
  };
  auto fin_v = [&]() {
#pragma unroll
    for (int a = 0; a < 2; a++)
      sts128(sb + R_STAGE + 4096 + w4 * 1024 + a * 512 + L16, pack2(av[8 * a], av[8 * a + 1]), pack2(av[8 * a + 2], av[8 * a + 3]),
             pack2(av[8 * a + 4], av[8 * a + 5]), pack2(av[8 * a + 6], av[8 * a + 7]));
  };
  __syncthreads();
  if (tid == 224) {
#pragma unroll 1
    for (int i = 0; i < 4; i++) issue_x(0, i);
    mbar_expect_tx(sb + B_W, 65536);
    for (int i = 0; i < 4; i++) tma2d(sb + R_WO + i * 16384, &maps.wo, 256 * j + 64 * i, h * DH, sb + B_W);
  }
  __syncwarp();
  if (wg) {
#pragma unroll
    for (int i = 0; i < NSW; i++) sts128(uW + R_WC + L16 + i * 2048, w[i]);
  }
#pragma unroll
  for (int i = 0; i < 4; i++) {
    const uint32_t* p = reinterpret_cast<const uint32_t*>(mem0 + g * DM + 128 * warp + 32 * i + 2 * t);
    sts128(sb + R_MEM + warp * 2048 + i * 512 + (g >> 1) * 128 + t * 32 + (g & 1) * 16, __ldg(p), __ldg(p + 4), __ldg(p + 8), __ldg(p + 12));
  }
#pragma unroll 1
  for (int n = 0; n < 2; n++) {
    wait_x(n, 1); wait_x(n, 2); wait_x(n, 3);
    if (wg == 0) {
      wait_x(n, 0);
      project_v(IC<0>{}, IC<32>{}, [](int) {});
      if (tid == 96 && n == 1) {
        asm volatile("cp.async.bulk.wait_group 0;" ::: "memory");
        __threadfence(); atomicAdd(&g_x.ctr[h], 1u);
      }
      __syncwarp();
      mbar_spin(sb + B_PK, n, it);
      unpark();
      project_qk(IC<0>{}, IC<16>{}, [](int) {});
      wg_wait<0>(); keep(aq); keep(av);
      fin_v(); fin_qk();
      fence_async();
    } else {
      project_qk(IC<16>{}, IC<48>{}, [](int) {});
      project_qk(IC<0>{}, IC<16>{}, [](int) {});
      wg_wait<0>(); keep(aq);
      park();
      if (tid == 128 && n == 1) {
        for (int k = 0; *reinterpret_cast<volatile unsigned*>(&g_x.ctr[h]) < 4 && k < SPIN_LIMIT; k++) {}
        __threadfence(); asm volatile("fence.proxy.async;" ::: "memory");
        issue_kqv(0);
      }
    }
    __syncthreads();
    if (tid == 96 && n == 0) store_stage(0);
    if (tid == 128 && n == 0) {
#pragma unroll 1
      for (int i = 0; i < 4; i++) issue_x(1, i);
    }
    __syncwarp();
  }
  mbar_spin(sb + B_W, 1, it);
#pragma unroll
  for (int i = 0; i < 4; i++) {
    uint32_t f[4][4];
    const uint32_t a = sb + R_WO + warp * 8192 + i * 2048;
#pragma unroll
    for (int q = 0; q < 4; q++) ldsm4t(f[q], a + (LW ^ (q << 5)));
    __syncwarp();
#pragma unroll
    for (int q = 0; q < 4; q++) sts128(a + q * 512 + L16, f[q]);
  }
  mbar_spin(sb + B_KV, 0, it);
  if (tid == 0) sts32(sb + B_DUE + 4, gtime() & ~31u);
  if (tid < 4) sts32(sb + B_ONE + tid * 4, 0x3F803F80u);
  if (warp == 1) { const uint32_t e = g >> 1 == t ? 0x3F80u << (16 * (g & 1)) : 0u; sts128(sb + R_ID + L16, e, 0, 0, e); }
  __syncthreads();

  const float sc = 0.08838834764831845f * 1.4426950408889634f;
  uint8_t* const xa = xb + uni(h * 16384);
  const uint32_t uA = uni(wg ? (w4 >> 1) * 2048 + j * 512 + (w4 & 1) * 256 : 8192 + (4 * (j >> 1) + w4) * 512 + jh * 256);
  const uint32_t uB = uni(offsetof(Xchg, B) + (32 * w4 + j) * 8192 + h * 128);
  const uint32_t uP2 = uni(sb + R_P + w4 * 256);
  uint32_t nc = 1;
  uint32_t ma;
  auto pin_mem = [&]() { ma = pin(uMem + (L16 & 384) + (L16 & 48) * 2 + (L16 & 64) / 4); };
  pin_mem();

#pragma unroll 1
  for (int s = 0;; nc++) {
    const uint32_t tag = (s + 1) & 1;
    auto fresh = [&]() { L16 += (uint32_t)it >> 31; };
    float c[4][4], r4[4];
    auto fold = [&]() {
#pragma unroll
      for (int i = 0; i < 4; i++) r4[i] = ((c[0][i] + c[1][i]) + c[2][i]) + c[3][i];
    };
    auto mma4 = [&](int n, const uint32_t (&b0)[4], const uint32_t (&b1)[4]) {
      mma_h(c[0], w[n + 2], b1, 0); mma_h(c[1], w[n + 3], b1, 1); mma_h(c[2], w[n], b0, 0); mma_h(c[3], w[n + 1], b0, 1);
    };
    auto xpos = [&](int pos, int wp) {
      if (!(EXP & 1) && (pos == XC || pos == XD || pos == XB || pos == XA) && warp == wp && s + 1 < NSEG && elect()) {
        const int z = (uint32_t)it >> 31;
        if (pos == XC) issue_x(s + 2, 2 + z);
        if (pos == XD) issue_x(s + 2, 3 + z);
        if (pos == XB) issue_x(s + 2, 1 + z);
        if (pos == XA) issue_x(s + 2, z);
      }
      __syncwarp();
    };
    if (wg == 0) {
      mbar_spin(sb + B_C, nc & 1, it);
      TS(13);
      uint32_t b[16][4], tg[4];
#pragma unroll
      for (int i = 0; i < 8; i++) { lds128(b[i], ma + i * 512); __syncwarp(); }
      sched();
      zero(c);
#pragma unroll
      for (int i = 0; i < 8; i++) {
        const int k = i ^ 1;
        mma_h(c[0], w[2 * k], b[k], 0); mma_h(c[1], w[2 * k + 1], b[k], 1);
        if (i < 2 * NV0) { mma_h(c[2], w[16 + 2 * k], b[k], 0); mma_h(c[3], w[17 + 2 * k], b[k], 1); }
        sched();
        if (i == TGP) {
          fresh();
#pragma unroll
          for (int k = 0; k < 4; k++) tg[k] = lds32((uW * 4 + L16) * 2 + (L16 >> 6) * 4 + (R_MEM + k * 1024 - 7 * sb));
          sched();
        }
      }
#pragma unroll
      for (int i = 0; i < 4; i++) { r4[i] = c[0][i] + c[1][i]; c[0][i] = c[1][i] = 0.f; }
      sts128f(uW + R_RED + L16, r4);
      TS(1);
      const uint32_t old = bar_or(4, (dif2(tg[0], tg[1], s) | dif2(tg[2], tg[3], s)) & (s > 0));
      TS(0);
      uint8_t* adst;
#pragma unroll
      for (int i = 0; i < 2 * NV0; i++) { lds128(b[8 + i], (ma ^ 4096) + i * 512); __syncwarp(); }
      sched();
#pragma unroll
      for (int i = NV0; i < 8; i++) {
        mma4(16 + 4 * i, b[2 * i], b[2 * i + 1]);
        if (i < 7) sched();
        if (i < 4) { lds128(b[8 + 2 * i], (ma ^ 4096) + i * 1024); __syncwarp(); lds128(b[9 + 2 * i], (ma ^ 4096) + i * 1024 + 512); sched(); }
        if (i == 4) { adst = const_cast<uint8_t*>(pinp(xa + uA + L16 / 2)); sched(); }
      }
      fold();
      asm volatile("{.reg .pred p; setp.eq.u32 p, %3, 0; @p st.relaxed.gpu.global.v2.b32 [%0], {%1,%2};}" :: "l"(adst), "r"((pack2(r4[0], r4[1]) & ~1u) | tag), "r"(pack2(r4[2], r4[3])), "r"(old) : "memory");
      sched();
      const unsigned tpub = clk();
      if (__any_sync(0xffffffffu, old) && nc < NC_MAX) {
        bar_sync(3, 256);
        issue_c(gtime());
        continue;
      }
      TS(3);
      xpos(0, 0);
      const uint32_t due = lds32(sb + B_DUE + 4);
      uint32_t vf[4][4], vm[2][4], p[4], pm, o[4];
      const uint32_t va = sb + R_V + (w4 >> 1) * 8192 + (w4 & 1) * 2048 + L16;
#pragma unroll
      for (int i = 0; i < 4; i++) {
        uint32_t q[4]; lds128(vf[i], va + i * 512); lds128(q, va + 4096 + i * 512);
#pragma unroll
        for (int e = 0; e < 4; e++) vf[i][e] = hadd2(vf[i][e], q[e]);
      }
      const uint32_t pa = pin(sb + R_P + (L16 >> 1));
      const uint8_t* vsrc = pinp(xa + 8192 + w4 * 1024 + L16 / 2);
      const uint8_t* tsrc = pinp(xb + offsetof(Xchg, T) + L16 * 8);
      uint32_t one[4];
      lds128(one, sb + B_ONE);
      auto pv_x = [&]() {
        zero(c);
        mma_a(c[2], one, p[0], p[1]);
        mma_a(c[0], vf[0], p[0], p[1]); mma_a(c[1], vf[2], p[0], p[1]);
        sched();
        mma_a(c[2], one, p[2], p[3]);
        mma_a(c[0], vf[1], p[2], p[3]); mma_a(c[1], vf[3], p[2], p[3]);
        sched();
      };
      auto pv_m = [&]() {
        mma1688(c[2], one[0], one[1], pm);
        mma_a(c[0], vm[0], pm, pm);
        sched();
        mma_a(c[1], vm[1], pm, pm);
      };
      auto norm = [&]() {
        const float n0 = rcp(c[2][0]), n1 = rcp(c[2][1]);
#pragma unroll
        for (int i = 0; i < 4; i++) o[i] = pack2(c[i >> 1][2 * (i & 1)] * n0, c[i >> 1][2 * (i & 1) + 1] * n1);
        return ((__float_as_uint(c[2][0]) - 0x1F800000u) | (__float_as_uint(c[2][1]) - 0x1F800000u)) >> 30;
      };
      auto load_m = [&](int x) { const float2 e0 = lds64f(pa + 512 + x * 1024), e1 = lds64f(pa + 768 + x * 1024); pm = pack2(e0.x * e1.x, e0.y * e1.y); };
      auto attend_max = [&](int x) {
        float2 sv[6];
#pragma unroll
        for (int i = 0; i < 6; i++) sv[i] = lds64f(pa - 3072 + x * 1536 + i * 256);
        sv[4].x += sv[5].x; sv[4].y += sv[5].y;
        const int dq = (int)(L16 >> 6) - (int)((L16 >> 3) & 6) + 8 * j;
        float m = fmaxf(sv[4].x, sv[4].y);
#pragma unroll
        for (int i = 0; i < 4; i++) {
          if (x && 8 * i > dq) sv[i].x = -INFINITY;
          if (x && 8 * i + 1 > dq) sv[i].y = -INFINITY;
          m = fmaxf(m, fmaxf(sv[i].x, sv[i].y));
        }
        m = fmaxf(m, __shfl_xor_sync(0xffffffffu, m, 1));
        m = fmaxf(m, __shfl_xor_sync(0xffffffffu, m, 2));
#pragma unroll
        for (int i = 0; i < 5; i++) (i < 4 ? p[i] : pm) = pack2(ex2(sv[i].x - m), ex2(sv[i].y - m));
        pv_x(); pv_m(); norm();
      };
      delay_until(tpub + DLY_V);
      wait_time(due + NS_V);
      TS(4);
      ldx(vm, vsrc);
      sched();
      auto get_t = [&](const uint8_t* p) {
        asm volatile("{.reg .pred p; setp.eq.u32 p, %2, 0; @p cp.async.cg.shared.global [%0], [%1], 16;}" :: "r"(sb + R_T + L16), "l"(p), "r"(warp) : "memory");
        cpa_commit();
      };
      get_t(tsrc);
      xpos(2, 2);
      auto store_kqv = [&]() {
        fence_async();
        if (!(EXP & 4))
          asm volatile("{.reg .pred p; elect.sync _|p, 0xffffffff; @p cp.async.bulk.global.shared::cta.bulk_group [%0], [%1], 2048; cp.async.bulk.commit_group;}"
                       :: "l"(g_kqv[(s + 1) & 3][role] + w4 * 128), "r"(sb + R_STAGE + w4 * 2048) : "memory");
      };
      if (SPOS == 2) store_kqv();
      sched();
      bar_sync(5, 256);
      ldsm4(p, sb + R_P + L16);
      load_m(0);
      pv_x();
      ldsm4(p, sb + R_P + 1024 + L16);
      pv_m();
      const uint32_t r = norm(), tl = after(tag, c[2][0], (uint32_t)it >> 31);
      const bool redo = __any_sync(0xffffffffu, r | ((dif2(vm[0][0], vm[0][2], tl) | dif2(vm[1][0], vm[1][2], tl)) & 1));
      TS(6);
      stsm4t(uW + R_O + L16, o[0], o[1], o[2], o[3]);
      bar_arrive_unless(6, redo);
      sched();
      TS(7);
      pv_x();
      if (rare(redo)) retry<2>(vm, vsrc, tag, it);
      bar_sync(8, 256);
      load_m(1);
      pv_m();
      if (rare(__any_sync(0xffffffffu, norm()) || redo)) {
        fresh();
        cpa_wait<0>();
        get_t(xb + offsetof(Xchg, T) + L16 * 8);
#pragma unroll 1
        for (int x = !redo; x < 2; x++) {
          attend_max(x);
          if (x == 0) { stsm4t(uW + R_O + L16, o[0], o[1], o[2], o[3]); bar_arrive(6, 256); }
        }
      }
      TS(8);
      if (SPOS == 4) store_kqv();
      xpos(4, 2);
      asm volatile("cp.async.bulk.wait_group 0;" ::: "memory");
      if (elect()) stx32(xa + 4096 + j * 16 + w4 * 4, s + 1);
      __syncwarp();
      if (warp == 0 && s + 1 < NSEG) {
        uint32_t tq[4];
        cpa_wait<0>();
        lds128(tq, sb + R_T + L16);
        const uint32_t ref = gtime();
#pragma unroll 1
        while (any_bit(or3(tq[0] - s - 1, tq[1] - s - 1, tq[2] - s - 1), tq[3] - s - 1, 30) && ++it < SPIN_LIMIT) ldx128(tq, xb + offsetof(Xchg, T) + L16 * 8);
        const int d = max(max((int)(tq[0] - ref), (int)(tq[1] - ref)), max((int)(tq[2] - ref), (int)(tq[3] - ref)));
        const uint32_t last = (ref + __reduce_max_sync(0xffffffffu, d)) & ~31u;
        TS(2);
        fetch4k(sb + R_MEM, offsetof(Xchg, B) + role * 8192, sb + B_B, last + NS_B);
        TS(5);
        asm volatile("st.shared.v2.u32 [%0], {%1,%2};" :: "r"(sb + B_DUE), "r"(last), "r"(last + (last == due ? NS_P : NS_P + NS_X)) : "memory");
        xpos(5, 0);
        LOG(9, last);
        LOG(13, tl - last);
      }
      fresh();
      const uint32_t ob = uni(sb + R_MEM + 4096 + w4 * 1024);
      stsm4t(ob + (L16 & 112) * 4 + (((L16 >> 3) ^ (L16 >> 1)) & 48), o[0], o[1], o[2], o[3]);
      __syncwarp();
      lds128(o, ob + (L16 ^ ((L16 >> 3) & 48)));
      auto put_o = [&]() {
        *reinterpret_cast<uint4*>(reinterpret_cast<uint8_t*>(g_ox) + (((s * SEG + 8 * j) * HD + h * DH + 32 * w4) * 2 + (L16 >> 6) * (HD * 2) + (L16 & 48))) = make_uint4(o[0], o[1], o[2], o[3]);
      };
      if (s + 1 == NSEG) { put_o(); break; }
      if (OXPOS < 0) put_o();
      fresh();
      const uint32_t ba = pin(sb + R_MEM + (L16 & 112) * 8 + (L16 >> 8) * 1024 + ((w4 * 32 + ((L16 >> 3) & 16)) ^ (L16 & 112)));
      const uint8_t* cdst = pinp(xb + (offsetof(Xchg, C) + j * 4096 + h * 128 + w4 * 32 + (L16 & 16) * 1024 + (L16 & 64) / 4 + (L16 >> 7) * 4));
      const uint32_t msk = pin((L16 >> 6) == (h & 3) * 2 + ((h >> 2) & 1) ? 0xFFFE0000u : 0xFFFFFFFFu);
      if (warp == 1) {
        wait_time(due + NS_F);
#pragma unroll 1
        while (__any_sync(0xffffffffu, ldx32(xa + 4096 + ((L16 >> 2) & 60)) != s + 1) && !(EXP & 4) && ++it < SPIN_LIMIT) {}
        wait_time(due + (NS_B + NS_K));
        if (!(EXP & 2) && elect()) issue_kqv(s + 1);
        __syncwarp();
      }
      TS(9);
      mbar_spin(sb + B_B, s & 1, it);
      TS(10);
      uint32_t bq[2][4];
      auto sum_b = [&]() {
        ldsm4t(bq[0], ba); ldsm4t(bq[1], ba + 2048);
        sched();
#pragma unroll
        for (int i = 0; i < 8; i++) c[i >> 2][i & 3] = 0.f;
        mma_a(c[0], bq[0], 0x3F803F80u, 0x3F803F80u); mma_a(c[1], bq[1], 0x3F803F80u, 0x3F803F80u);
        const uint32_t t2 = tag * 0x10001u;
        const bool old = any_bit(or3(dif2(bq[0][0], bq[0][1], t2), dif2(bq[0][2], bq[0][3], t2), dif2(bq[1][0], bq[1][1], t2)), dif2(bq[1][2], bq[1][3], t2), L16 < 64 ? 0x10001u : 0u);
        const uint32_t T = (tag << 16) & ~msk, u = ((__float_as_uint(c[0][0] + c[1][0]) + ((0x10000u & ~msk) - T)) & msk) | T;
        asm volatile("{.reg .pred p; setp.eq.u32 p, %2, 0; @p st.relaxed.gpu.global.b32 [%0], %1;}"
                     :: "l"(cdst), "r"(pack2(__uint_as_float(u), c[0][2] + c[1][2])), "r"((uint32_t)(old || (L16 & 32))) : "memory");
        return old;
      };
      if (rare(sum_b())) {
#pragma unroll 1
        do {
          const uint8_t* p = xb + (offsetof(Xchg, B) + role * 8192 + (ba - sb - R_MEM));
          ldx128(bq[0], p); ldx128(bq[1], p + 2048);
          sts128(ba, bq[0]); sts128(ba + 2048, bq[1]);
          __syncwarp();
          it += INC_B;
        } while (sum_b() && it < SPIN_LIMIT);
      }
      sched();
      TS(11);
      bar_arrive(0, 256);
      wait_x(s + 2, 0); wait_x(s + 2, 1 + 2 * jh);
      fresh();
      auto mid = [&](int n) { if (n == OXPOS) { __syncwarp(); put_o(); __syncwarp(); } };
      project_v(IC<0>{}, IC<UNP>{}, mid);
      mbar_spin(sb + B_PK, s & 1, it);
      unpark();
      project_v(IC<UNP>{}, IC<32>{}, mid);
      project_qk(IC<0>{}, IC<16>{}, [](int) {});
      TS(12);
      LOG(warp, it);
      pin_mem();
      wg_wait<1>(); keep(av);
      fin_v();
      wg_wait<0>(); keep(aq);
      fin_qk();
      TS(15);
    } else {
      uint32_t kf[8][4];
      auto load_k = [&]() {
        const uint32_t ka = sb + R_K + w4 * 1024 + (L16 & 112) + (L16 & 128) * 4 + (L16 & 256);
#pragma unroll
        for (int i = 0; i < 8; i++) ldsm4(kf[i], ka + (i >> 1) * 2048 + (i & 1) * 128);
      };
      auto put_p = [&](int x, uint32_t old, uint32_t again) {
        float e[4];
        const int dq = (int)((L16 >> 3) & 6) + 8 * j - (int)(L16 >> 6) - 16 * w4;
#pragma unroll
        for (int i = 0; i < 4; i++) { r4[i] = fmaf(c[3][i], sc, fmaf(c[2][i], sc, fmaf(c[0][i] + c[1][i], sc, __uint_as_float(i == 3 ? 0u - old : 0u)))); e[i] = x && dq + (i & 1) < 8 * (i >> 1) ? 0.f : ex2(r4[i]); }
        stsm2t(uP2 + x * 1024 + L16, pack2(e[0], e[1]), pack2(e[2], e[3]), again);
      };
      auto put_s = [&](int x) {
#pragma unroll
        for (int i = 0; i < 4; i++) sts32f(uW + R_S + x * 1536 + (L16 & 48) * 4 + (L16 >> 6) * 4 + (i & 1) * 32 + (i >> 1) * 256, r4[i]);
      };
      auto load_q = [&](uint32_t (&q)[4], uint32_t off) { ldsm4(q, sb + R_Q + (L16 & 112) + (L16 & 128) * 2 + (L16 >> 8) * 128 + off); };
      const uint8_t* adst = pinp(xa + uA + L16 / 2);
      uint32_t due;
      mbar_spin(sb + B_C, nc & 1, it);
      TS(13);
      float4 o4;
      uint32_t id[4], old;
      {
        uint32_t b[24][4];
#pragma unroll
        for (int i = 0; i < 2 * PD1; i++) { lds128(b[i], ma + i * 512); __syncwarp(); }
        sched();
        zero(c);
#pragma unroll
        for (int i = 0; i < 12; i++) {
          mma4(4 * i, b[2 * i], b[2 * i + 1]);
          if (i < 11) sched();
          if (i + PD1 < 12) { lds128(b[2 * (i + PD1)], ma + (i + PD1) * 1024); __syncwarp(); lds128(b[2 * (i + PD1) + 1], ma + (i + PD1) * 1024 + 512); sched(); }
          if (i == RJ) { lds128(id, sb + R_ID + L16); due = lds32(sb + B_DUE + 4); sched(); }
          if (i == RI) { old = bar_or(4, 0); o4 = lds128f(uW + R_RED + L16); sched(); }
        }
      }
      TS(0);
      {
        float e[4] = {o4.x, o4.y, o4.z, o4.w};
#pragma unroll
        for (int i = 0; i < 4; i++) { r4[i] = (((e[i] + c[0][i]) + c[1][i]) + c[2][i]) + c[3][i]; e[i] = 0.f; }
        mma_a(e, id, pack2(r4[0], r4[1]), pack2(r4[2], r4[3]));
        asm volatile("{.reg .pred p; setp.eq.u32 p, %3, 0; @p st.relaxed.gpu.global.v2.b32 [%0], {%1,%2};}" :: "l"(adst),
                     "r"((__byte_perm(__float_as_uint(e[0]), __float_as_uint(e[1]), 0x7632) & ~1u) | tag), "r"(__byte_perm(__float_as_uint(e[2]), __float_as_uint(e[3]), 0x7632)), "r"(old) : "memory");
        sched();
      }
      const unsigned tpub = clk(), now = gtime();
      if (__any_sync(0xffffffffu, old) && nc < NC_MAX) { bar_sync(3, 256); continue; }
      TS(2);
      const uint8_t* asrc = pinp(adst + ((warp == 7) * 1024 - (int)uA));
      fresh();
      uint32_t wo[32][4];
      uint8_t* dst;
      bool xok;
      auto pin_dst = [&]() { dst = const_cast<uint8_t*>(pinp(xb + uB + ((((L16 >> 2) * 0x2001u) & 0x18070u) ^ ((h & 7) << 4)))); sched(); };
      auto out_proj = [&]() {
        uint32_t b[4][4];
        float d[4][4];
        pin_dst();
        TS(7);
        bar_sync(6, 256);
#pragma unroll
        for (int i = 0; i < 4; i++) { ldsm4(b[i], sb + R_O + i * 512 + L16); __syncwarp(); }
        sched();
        auto put_b = [&](uint8_t* a, const float (&e)[4][4]) {
          stx128(a, (pack2(e[0][0] + e[2][0], e[0][1] + e[2][1]) & ~1u) | tag, pack2(e[0][2] + e[2][2], e[0][3] + e[2][3]),
                 pack2(e[1][0] + e[3][0], e[1][1] + e[3][1]), pack2(e[1][2] + e[3][2], e[1][3] + e[3][3]));
        };
        zero(c); zero(d);
#pragma unroll
        for (int i = 0; i < 32; i++) {
          mma_h(i < 16 ? c[i & 3] : d[i & 3], wo[i], b[(i >> 2) & 3], (i >> 1) & 1);
          if (i >= LW0 && NB1 + i - LW0 < 32) { load_wo(wo, (NB1 + i - LW0) ^ 1, ((NB1 + i - LW0) ^ 1) + 1); __syncwarp(); }
          if (i == 22) put_b(dst, c);
          if ((i & 1) && (i < 20 || i > 22)) sched();
        }
        put_b(dst + 131072, d);
        sched();
      };
      if (warp < 6) {
        delay_until(tpub + DLY_A);
        const int it0 = it;
        bool redo;
#pragma unroll 1
        do {
          uint32_t q[4][4], y[4];
          float d[4][4];
          wait_time(due);
          TS(4);
          ldx(q, asrc);
          sched();
          load_k();
          uint32_t qx[4][4];
#pragma unroll
          for (int i = 0; i < 4; i++) load_q(qx[i], i * 512);
          sched();
          load_wo(wo, 0, NE4);
          sched();
          zero(c);
#pragma unroll
          for (int i = 0; i < 8; i++) mma_h(c[i & 3], kf[i], qx[i >> 1], i & 1);
          put_p(1, 0, 0); put_s(1);
          sched();
          load_wo(wo, NE4, NA4);
          sched();
          zero(c); zero(d);
#pragma unroll
          for (int i = 0; i < 8; i++) {
            if (i == 0) { y[0] = dif2v(q[0][0], q[0][2], q[1][0]); sched(); }
            if (i == 3) { y[1] = dif2v(q[1][2], q[2][0], q[2][2]); sched(); }
            if (i == 6) { y[2] = dif2v(q[3][0], q[3][2], tag); sched(); }
            mma_h(i % 6 < 2 ? c[2 + i % 6] : d[i - 2], kf[i], q[i >> 1], i & 1);
            if (i == 2 || i == 5 || i == 7) sched();
          }
          y[0] = or_and(or3(y[0], y[1], dif2v(q[0][0], q[2][0], tag)), y[2], it < SPIN_LIMIT);
#pragma unroll
          for (int i = 0; i < 4; i++) { c[0][i] = d[0][i] + d[1][i]; c[1][i] = d[2][i] + d[3][i]; }
          put_p(0, y[0], it - it0);
          TS(5);
          bar_sync_unless(5, it - it0);
          redo = __any_sync(0xffffffffu, y[0]);
          it += INC_A;
        } while (redo);
        it -= INC_A;
        put_s(0);
        bar_arrive(8, 256);
        load_wo(wo, NA4, NB1);
        out_proj();
      } else {
        uint32_t qx[2][4], q[4][4];
        if (warp == 6) {
          const uint32_t t1 = (now & ~31u) + NS_M;
          LOG(10, now - due);
          if (elect()) stx32(&g_x.T[h][j], ((int)(t1 - due) > 0 ? t1 + NS_PEN : due) | ((s + 1) & 31));
          __syncwarp();
        }
        auto score = [&](const uint32_t (&a0)[4], const uint32_t (&a1)[4]) {
          zero(c);
#pragma unroll
          for (int i = 0; i < 4; i++) mma_h(c[i], i < 2 ? a0 : a1, q[2 + (i >> 1)], i & 1);
        };
        auto put_m = [&](uint32_t a, uint32_t old, uint32_t again) {
#pragma unroll
          for (int i = 0; i < 2; i++) { r4[i] = fmaf(c[3][2 + i], sc, fmaf((c[0][i] + c[1][2 + i]) + c[2][i], sc, __uint_as_float(i ? 0u - old : 0u))); r4[2 + i] = fmaf(r4[i] * 0x1p122f, 0.f, ex2(r4[i])); }
          asm volatile("{.reg .pred p; setp.eq.u32 p, %3, 0; @p st.shared.v2.f32 [%0], {%1,%2};}" :: "r"(a), "f"(r4[2]), "f"(r4[3]), "r"(again) : "memory");
        };
        delay_until(tpub + DLY_A);
        const uint32_t sa = sb + R_S + 512 + w4 * 256 + (L16 >> 1);
        const int it0 = it;
        bool redo;
#pragma unroll 1
        do {
          wait_time(due);
          TS(4);
          ldx<4, 2048>(q, asrc);
          sched();
          load_q(qx[0], (w4 & 1) * 1024); load_q(qx[1], (w4 & 1) * 1024 + 512);
          load_wo(wo, 0, NA6);
          sched();
          score(q[0], q[1]);
          sched();
          const uint32_t y = or_and(or3(dif2v(q[0][0], q[0][2], tag), dif2v(q[1][0], q[1][2], tag), dif2v(q[2][0], q[2][2], tag)), dif2v(q[3][0], q[3][2], tag), it < SPIN_LIMIT);
          put_m(sa + 2560, y, it - it0);
          TS(5);
          bar_arrive_unless(5, it - it0);
          redo = __any_sync(0xffffffffu, y);
          it += INC_A;
        } while (redo);
        it -= INC_A;
        sts64f(sa, r4[0], r4[1]);
        score(qx[0], qx[1]);
        put_m(sa + 3584, 0, 0);
        sts64f(sa + 1536, r4[0], r4[1]);
        bar_arrive(8, 256);
        load_wo(wo, NA6, NB1);
        out_proj();
      }
      TS(8);
      if (s + 1 == NSEG) break;
      if (warp == 4) LOG(12, tb);
      wait_x(s + 2, 2);
      TS(9);
      fresh();
      auto mid = [&](int n) {
        if (n >= 16 + RL0 && (n - 16 - RL0) % RLS == 0) {
#pragma unroll
          for (int i = (n - 16 - RL0) / RLS * RLB; i < (n - 16 - RL0) / RLS * RLB + RLB && i < NSW; i++) lds128(w[i], uW + R_WC + L16 + i * 2048);
          __syncwarp();
        }
        if (n >= 16 && (n & 15) == XWPOS) { __syncwarp(); xok = mbar_test(sb + B_X + (n < 32 ? 24 : 8), s & 1); __syncwarp(); }
      };
      project_qk(IC<16>{}, IC<32>{}, mid);
      if (rare(!xok)) wait_x(s + 2, 3);
      project_qk(IC<32>{}, IC<48>{}, mid);
      if (rare(!xok)) wait_x(s + 2, 1);
      project_qk(IC<0>{}, IC<16>{}, mid);
      TS(10);
      wg_wait<0>(); keep(aq);
      TS(1);
      park();
      TS(11);
      LOG(warp, it);
      if (warp == 4) LOG(8, nc);
      bar_sync(0, 256);
      const uint32_t cdue = lds32(sb + B_DUE) + NS_C;
      sched();
      delay_until(clk() + DLY_C);
      TS(12);
      if (warp == 7) LOG(11, gtime() - cdue);
      issue_c(cdue);
      TS(14);
      fresh();
      pin_mem();
      if (!(EXP & 2)) mbar_spin(sb + B_KV, tag, it);
      TS(15);
    }
    s++;
  }
  if (it >= SPIN_LIMIT || nc >= NC_MAX) g_err = 2;
}

typedef CUresult (*EncodeFn)(CUtensorMap*, CUtensorMapDataType, cuuint32_t, void*, const cuuint64_t*, const cuuint64_t*, const cuuint32_t*,
                             const cuuint32_t*, CUtensorMapInterleave, CUtensorMapSwizzle, CUtensorMapL2promotion, CUtensorMapFloatOOBfill);
static void make_map(EncodeFn fn, CUtensorMap* m, const void* p, uint64_t cols, uint64_t rows, uint64_t pitch, uint32_t bc, uint32_t br, CUtensorMapSwizzle sw) {
  cuuint64_t dims[2] = {cols, rows}, strides[1] = {pitch * 2};
  cuuint32_t box[2] = {bc, br}, es[2] = {1, 1};
  fn(m, CU_TENSOR_MAP_DATA_TYPE_BFLOAT16, 2, const_cast<void*>(p), dims, strides, box, es, CU_TENSOR_MAP_INTERLEAVE_NONE, sw,
     CU_TENSOR_MAP_L2_PROMOTION_L2_256B, CU_TENSOR_MAP_FLOAT_OOB_FILL_NONE);
}

extern "C" void kernel_launch(void* const* d_in, const int* in_sizes, int n_in, void* d_out, int out_size) {
  const bf16* Ax = (const bf16*)d_in[0]; const bf16* mem0 = (const bf16*)d_in[1];
  const bf16* Wq = (const bf16*)d_in[2]; const bf16* Wk = (const bf16*)d_in[3]; const bf16* Wv = (const bf16*)d_in[4];
  const bf16* Wo = (const bf16*)d_in[5];
  const bf16* Bx = (const bf16*)d_in[7]; const bf16* wr = (const bf16*)d_in[8]; const bf16* wi = (const bf16*)d_in[9];
  bf16* out = (bf16*)d_out;

  void* fp = nullptr; cudaDriverEntryPointQueryResult qr;
  cudaGetDriverEntryPoint("cuTensorMapEncodeTiled", &fp, cudaEnableDefault, &qr);
  EncodeFn fn = (EncodeFn)fp;
  void *kqv, *ox;
  cudaGetSymbolAddress(&kqv, g_kqv); cudaGetSymbolAddress(&ox, g_ox);
  const CUtensorMapSwizzle S128 = CU_TENSOR_MAP_SWIZZLE_128B, S64 = CU_TENSOR_MAP_SWIZZLE_64B;

  GemmMaps m3; RecMaps mr;
  make_map(fn, &m3.a, ox, HD, S_LEN, HD, 64, 128, S128);
  make_map(fn, &m3.b[0], Wo, DM, HD, DM, 64, 64, S128);
  m3.b[1] = m3.b[0]; m3.b[2] = m3.b[0];
  make_map(fn, &m3.c, out, DM, S_LEN, 2 * DM, 64, 64, S128);
  make_map(fn, &mr.wq, Wq, HD, DM, HD, 32, 256, S64);
  make_map(fn, &mr.wk, Wk, HD, DM, HD, 32, 256, S64);
  make_map(fn, &mr.wv, Wv, HD, DM, HD, 64, 256, S128);
  make_map(fn, &mr.wo, Wo, DM, HD, DM, 64, 128, S128);
  {
    cuuint64_t dims[3] = {64, S_LEN, 16}, strides[2] = {DM * 2, 128};
    cuuint32_t box[3] = {64, 32, 4}, es[3] = {1, 1, 1};
    fn(&mr.x, CU_TENSOR_MAP_DATA_TYPE_BFLOAT16, 3, const_cast<bf16*>(Ax), dims, strides, box, es, CU_TENSOR_MAP_INTERLEAVE_NONE, S128,
       CU_TENSOR_MAP_L2_PROMOTION_L2_256B, CU_TENSOR_MAP_FLOAT_OOB_FILL_NONE);
  }
  for (int i = 0; i < 3; i++) {
    cuuint64_t dims[3] = {128, 32, 512}, strides[2] = {256, 8192};
    cuuint32_t box[3] = {128, i == 0 ? 8u : i == 1 ? 2u : 16u, 4}, es[3] = {1, 1, 1};
    fn(i == 0 ? &mr.k : i == 1 ? &mr.q : &mr.v, CU_TENSOR_MAP_DATA_TYPE_BFLOAT16, 3, kqv, dims, strides, box, es, CU_TENSOR_MAP_INTERLEAVE_NONE,
       CU_TENSOR_MAP_SWIZZLE_NONE, CU_TENSOR_MAP_L2_PROMOTION_L2_256B, CU_TENSOR_MAP_FLOAT_OOB_FILL_NONE);
  }
  {
    cuuint64_t dims[3] = {64, 16, S_LEN}, strides[2] = {128, 2 * DM * 2};
    cuuint32_t box[3] = {64, 16, 2}, es[3] = {1, 1, 1};
    fn(&mr.fo, CU_TENSOR_MAP_DATA_TYPE_BFLOAT16, 3, out + DM, dims, strides, box, es, CU_TENSOR_MAP_INTERLEAVE_NONE, S128,
       CU_TENSOR_MAP_L2_PROMOTION_NONE, CU_TENSOR_MAP_FLOAT_OOB_FILL_NONE);
  }
  constexpr int SM3 = 6 * 32768 + 32768 + 256 + 1024;
  cudaFuncSetAttribute(gemm_kernel<128, 6>, cudaFuncAttributeMaxDynamicSharedMemorySize, SM3);
  cudaFuncSetAttribute(rec_kernel, cudaFuncAttributeMaxDynamicSharedMemorySize, R_TOTAL);

  cudaStream_t st = cudaStreamPerThread;
  cudaFuncSetAttribute(fft_pre_kernel, cudaFuncAttributeMaxDynamicSharedMemorySize, F_SMEM);
  fft_pre_kernel<<<128, 256, F_SMEM, st>>>(Bx, wr, wi);
  rec_kernel<<<132, 256, R_TOTAL, st>>>(mr, Ax, mem0);
  gemm_kernel<128, 6><<<128, 384, SM3, st>>>(m3, 16, 8, 64, 8, 1);
}
```

```cpp
#include <cuda_runtime.h>
#include <cuda_bf16.h>
#include <cuda.h>
#include <stdint.h>
#include <stddef.h>
#include <type_traits>

typedef __nv_bfloat16 bf16;

constexpr int S_LEN = 2048, DM = 1024, NH = 32, DH = 128, MEM = 8, SEG = 32, NSEG = 64;
constexpr int HD = NH * DH;
#define SPIN 20
constexpr int SPIN_LIMIT = 1 << SPIN, INC_A = 1, INC_B = 1;

constexpr unsigned NC_MAX = 4096;
__device__ __align__(1024) uint4 g_kqv[4][128][512];
__device__ __align__(1024) bf16 g_ox[(size_t)S_LEN * HD];
struct Xchg {
  uint4 A[32][4][256];
  uint4 C[4][2][256];
  uint4 B[128][2][256];
  uint32_t T[32][32];
  uint32_t S[128];
  unsigned ctr[64];
};
__device__ __align__(1024) uint4 g_xraw[(sizeof(Xchg) + 8192) / 16];
__device__ __align__(1024) uint4 g_y[1024 * 256];
__device__ __align__(1024) uint4 g_wt[513 * 512];
__device__ int g_err;

__device__ __forceinline__ unsigned clk() { unsigned long long c; asm volatile("mov.u64 %0, %%clock64;" : "=l"(c)); return (unsigned)c; }
__device__ __forceinline__ uint32_t smem_u32(const void* p) { return (uint32_t)__cvta_generic_to_shared(p); }
__device__ __forceinline__ void mbar_init(uint32_t bar, int cnt) { asm volatile("mbarrier.init.shared::cta.b64 [%0], %1;" :: "r"(bar), "r"(cnt) : "memory"); }
__device__ __forceinline__ void mbar_expect_tx(uint32_t bar, int bytes) { asm volatile("mbarrier.arrive.expect_tx.shared::cta.b64 _, [%0], %1;" :: "r"(bar), "r"(bytes) : "memory"); }
__device__ __forceinline__ void mbar_arrive(uint32_t bar) { asm volatile("mbarrier.arrive.shared::cta.b64 _, [%0];" :: "r"(bar) : "memory"); }
__device__ __forceinline__ void mbar_arrive_cluster(uint32_t bar, int cta) {
  asm volatile("{.reg .b32 r; mapa.shared::cluster.u32 r, %0, %1; mbarrier.arrive.shared::cluster.b64 _, [r];}" :: "r"(bar), "r"(cta) : "memory"); }
__device__ __forceinline__ bool mbar_try(uint32_t bar, int par) {
  uint32_t ok; asm volatile("{.reg .pred p; mbarrier.try_wait.parity.shared::cta.b64 p, [%1], %2; selp.u32 %0, 1, 0, p;}" : "=r"(ok) : "r"(bar), "r"(par) : "memory"); return ok; }
__device__ __forceinline__ bool mbar_test(uint32_t bar, int par) {
  uint32_t ok; asm volatile("{.reg .pred p; mbarrier.test_wait.parity.shared::cta.b64 p, [%1], %2; selp.u32 %0, 1, 0, p;}" : "=r"(ok) : "r"(bar), "r"(par) : "memory"); return ok; }
__device__ __forceinline__ void mbar_wait(uint32_t bar, int par) {
  int it = 0;
  while (!mbar_try(bar, par)) { if (++it > SPIN_LIMIT) { g_err = 1; break; } }
}
__device__ __forceinline__ void tma2d(uint32_t dst, const CUtensorMap* m, int c0, int c1, uint32_t bar) {
  asm volatile("cp.async.bulk.tensor.2d.shared::cluster.global.mbarrier::complete_tx::bytes [%0], [%1, {%3, %4}], [%2];"
    :: "r"(dst), "l"(m), "r"(bar), "r"(c0), "r"(c1) : "memory"); }
__device__ __forceinline__ void tma2d_mc(uint32_t dst, const CUtensorMap* m, int c0, int c1, uint32_t bar, uint16_t mask) {
  asm volatile("cp.async.bulk.tensor.2d.shared::cluster.global.mbarrier::complete_tx::bytes.multicast::cluster [%0], [%1, {%3, %4}], [%2], %5;"
    :: "r"(dst), "l"(m), "r"(bar), "r"(c0), "r"(c1), "h"(mask) : "memory"); }
__device__ __forceinline__ void tma2d_store(const CUtensorMap* m, uint32_t src, int c0, int c1) {
  asm volatile("cp.async.bulk.tensor.2d.global.shared::cta.bulk_group [%0, {%2, %3}], [%1];" :: "l"(m), "r"(src), "r"(c0), "r"(c1) : "memory"); }
__device__ __forceinline__ void fence_async() { asm volatile("fence.proxy.async.shared::cta;" ::: "memory"); }
__device__ __forceinline__ void bar_sync(int id, int n) { asm volatile("bar.sync %0, %1;" :: "r"(id), "r"(n) : "memory"); }
__device__ __forceinline__ void bar_arrive(int id, int n) { asm volatile("bar.arrive %0, %1;" :: "r"(id), "r"(n) : "memory"); }
__device__ __forceinline__ uint32_t pack2(float lo, float hi) { uint32_t r; asm("cvt.rn.bf16x2.f32 %0, %1, %2;" : "=r"(r) : "f"(hi), "f"(lo)); return r; }
__device__ __forceinline__ uint32_t pack2_tag(float lo, float hi, uint32_t T) {
  uint32_t u = ((__float_as_uint(lo) - T + 0x10000u) & 0xFFFE0000u) + T;
  return __byte_perm(u, pack2(0.f, hi), 0x7632); }
__device__ __forceinline__ void ldsm4(uint32_t (&r)[4], uint32_t a) {
  asm volatile("ldmatrix.sync.aligned.m8n8.x4.shared.b16 {%0,%1,%2,%3}, [%4];" : "=r"(r[0]), "=r"(r[1]), "=r"(r[2]), "=r"(r[3]) : "r"(a) : "memory"); }
__device__ __forceinline__ void ldsm4t(uint32_t (&r)[4], uint32_t a) {
  asm volatile("ldmatrix.sync.aligned.m8n8.x4.trans.shared.b16 {%0,%1,%2,%3}, [%4];" : "=r"(r[0]), "=r"(r[1]), "=r"(r[2]), "=r"(r[3]) : "r"(a) : "memory"); }
__device__ __forceinline__ void stsm4(uint32_t a, uint32_t r0, uint32_t r1, uint32_t r2, uint32_t r3) {
  asm volatile("stmatrix.sync.aligned.m8n8.x4.shared.b16 [%0], {%1,%2,%3,%4};" :: "r"(a), "r"(r0), "r"(r1), "r"(r2), "r"(r3) : "memory"); }
__device__ __forceinline__ void stsm4t(uint32_t a, uint32_t r0, uint32_t r1, uint32_t r2, uint32_t r3) {
  asm volatile("stmatrix.sync.aligned.m8n8.x4.trans.shared.b16 [%0], {%1,%2,%3,%4};" :: "r"(a), "r"(r0), "r"(r1), "r"(r2), "r"(r3) : "memory"); }
__device__ __forceinline__ void lds128(uint32_t (&r)[4], uint32_t a) {
  asm volatile("ld.shared.v4.u32 {%0,%1,%2,%3}, [%4];" : "=r"(r[0]), "=r"(r[1]), "=r"(r[2]), "=r"(r[3]) : "r"(a) : "memory"); }
__device__ __forceinline__ float4 lds128f(uint32_t a) { float4 r;
  asm volatile("ld.shared.v4.f32 {%0,%1,%2,%3}, [%4];" : "=f"(r.x), "=f"(r.y), "=f"(r.z), "=f"(r.w) : "r"(a) : "memory"); return r; }
__device__ __forceinline__ float2 lds64f(uint32_t a) { float2 r;
  asm volatile("ld.shared.v2.f32 {%0,%1}, [%2];" : "=f"(r.x), "=f"(r.y) : "r"(a) : "memory"); return r; }
__device__ __forceinline__ void sts128(uint32_t a, uint32_t r0, uint32_t r1, uint32_t r2, uint32_t r3) {
  asm volatile("st.shared.v4.u32 [%0], {%1,%2,%3,%4};" :: "r"(a), "r"(r0), "r"(r1), "r"(r2), "r"(r3) : "memory"); }
__device__ __forceinline__ void sts64f(uint32_t a, float x, float y) { asm volatile("st.shared.v2.f32 [%0], {%1,%2};" :: "r"(a), "f"(x), "f"(y) : "memory"); }
__device__ __forceinline__ void sts32f(uint32_t a, float x) { asm volatile("st.shared.f32 [%0], %1;" :: "r"(a), "f"(x) : "memory"); }
__device__ __forceinline__ void mma16816(float (&d)[4], uint32_t a0, uint32_t a1, uint32_t a2, uint32_t a3, uint32_t b0, uint32_t b1) {
  asm volatile("mma.sync.aligned.m16n8k16.row.col.f32.bf16.bf16.f32 {%0,%1,%2,%3}, {%4,%5,%6,%7}, {%8,%9}, {%0,%1,%2,%3};"
    : "+f"(d[0]), "+f"(d[1]), "+f"(d[2]), "+f"(d[3]) : "r"(a0), "r"(a1), "r"(a2), "r"(a3), "r"(b0), "r"(b1)); }
__device__ __forceinline__ void mma1688(float (&d)[4], uint32_t a0, uint32_t a1, uint32_t b0) {
  asm volatile("mma.sync.aligned.m16n8k8.row.col.f32.bf16.bf16.f32 {%0,%1,%2,%3}, {%4,%5}, {%6}, {%0,%1,%2,%3};"
    : "+f"(d[0]), "+f"(d[1]), "+f"(d[2]), "+f"(d[3]) : "r"(a0), "r"(a1), "r"(b0)); }
__device__ __forceinline__ void ldx128(uint32_t (&r)[4], const void* p) {
  asm volatile("{.reg .b128 t; .reg .b64 a, b; ld.relaxed.gpu.global.b128 t, [%4]; mov.b128 {a, b}, t; mov.b64 {%0,%1}, a; mov.b64 {%2,%3}, b;}"
    : "=r"(r[0]), "=r"(r[1]), "=r"(r[2]), "=r"(r[3]) : "l"(p) : "memory"); }
__device__ __forceinline__ void ldx2x64(uint32_t (&r)[4], const void* p) {
  asm volatile("{.reg .b64 a, b; ld.relaxed.gpu.global.v2.b64 {a, b}, [%4]; mov.b64 {%0,%1}, a; mov.b64 {%2,%3}, b;}"
    : "=r"(r[0]), "=r"(r[1]), "=r"(r[2]), "=r"(r[3]) : "l"(p) : "memory"); }
__device__ __forceinline__ void stx128(void* p, uint32_t r0, uint32_t r1, uint32_t r2, uint32_t r3) {
  asm volatile("{.reg .b128 t; .reg .b64 a, b; mov.b64 a, {%1,%2}; mov.b64 b, {%3,%4}; mov.b128 t, {a, b}; st.relaxed.gpu.global.b128 [%0], t;}"
    :: "l"(p), "r"(r0), "r"(r1), "r"(r2), "r"(r3) : "memory"); }
__device__ __forceinline__ void stx64(void* p, uint32_t r0, uint32_t r1) {
  asm volatile("{.reg .b64 a; mov.b64 a, {%1,%2}; st.relaxed.gpu.global.b64 [%0], a;}" :: "l"(p), "r"(r0), "r"(r1) : "memory"); }
__device__ __forceinline__ uint32_t uni(uint32_t x) { return __shfl_sync(0xffffffffu, x, 0); }
__device__ __forceinline__ uint32_t pin(uint32_t x) { return __shfl_xor_sync(0xffffffffu, x, 0); }
__device__ __forceinline__ float ex2(float x) { float r; asm("ex2.approx.ftz.f32 %0, %1;" : "=f"(r) : "f"(x)); return r; }
__device__ __forceinline__ void wg_fence() { asm volatile("wgmma.fence.sync.aligned;" ::: "memory"); }
__device__ __forceinline__ void wg_commit() { asm volatile("wgmma.commit_group.sync.aligned;" ::: "memory"); }
template <int N> __device__ __forceinline__ void wg_wait() { asm volatile("wgmma.wait_group.sync.aligned %0;" :: "n"(N) : "memory"); }

__device__ __forceinline__ void wgmma_ss_n256_tb1(float (&d)[128], uint64_t da, uint64_t db, int sc) {
  asm volatile("{.reg .pred p; setp.ne.b32 p, %130, 0;\n"
    "wgmma.mma_async.sync.aligned.m64n256k16.f32.bf16.bf16 {%0,%1,%2,%3,%4,%5,%6,%7,%8,%9,%10,%11,%12,%13,%14,%15,%16,%17,%18,%19,%20,%21,%22,%23,%24,%25,%26,%27,%28,%29,%30,%31,%32,%33,%34,%35,%36,%37,%38,%39,%40,%41,%42,%43,%44,%45,%46,%47,%48,%49,%50,%51,%52,%53,%54,%55,%56,%57,%58,%59,%60,%61,%62,%63,%64,%65,%66,%67,%68,%69,%70,%71,%72,%73,%74,%75,%76,%77,%78,%79,%80,%81,%82,%83,%84,%85,%86,%87,%88,%89,%90,%91,%92,%93,%94,%95,%96,%97,%98,%99,%100,%101,%102,%103,%104,%105,%106,%107,%108,%109,%110,%111,%112,%113,%114,%115,%116,%117,%118,%119,%120,%121,%122,%123,%124,%125,%126,%127}, %128, %129, p, 1, 1, 0, 1;}\n"
    : "+f"(d[0]),"+f"(d[1]),"+f"(d[2]),"+f"(d[3]),"+f"(d[4]),"+f"(d[5]),"+f"(d[6]),"+f"(d[7]),"+f"(d[8]),"+f"(d[9]),"+f"(d[10]),"+f"(d[11]),"+f"(d[12]),"+f"(d[13]),"+f"(d[14]),"+f"(d[15]),"+f"(d[16]),"+f"(d[17]),"+f"(d[18]),"+f"(d[19]),"+f"(d[20]),"+f"(d[21]),"+f"(d[22]),"+f"(d[23]),"+f"(d[24]),"+f"(d[25]),"+f"(d[26]),"+f"(d[27]),"+f"(d[28]),"+f"(d[29]),"+f"(d[30]),"+f"(d[31]),"+f"(d[32]),"+f"(d[33]),"+f"(d[34]),"+f"(d[35]),"+f"(d[36]),"+f"(d[37]),"+f"(d[38]),"+f"(d[39]),"+f"(d[40]),"+f"(d[41]),"+f"(d[42]),"+f"(d[43]),"+f"(d[44]),"+f"(d[45]),"+f"(d[46]),"+f"(d[47]),"+f"(d[48]),"+f"(d[49]),"+f"(d[50]),"+f"(d[51]),"+f"(d[52]),"+f"(d[53]),"+f"(d[54]),"+f"(d[55]),"+f"(d[56]),"+f"(d[57]),"+f"(d[58]),"+f"(d[59]),"+f"(d[60]),"+f"(d[61]),"+f"(d[62]),"+f"(d[63]),"+f"(d[64]),"+f"(d[65]),"+f"(d[66]),"+f"(d[67]),"+f"(d[68]),"+f"(d[69]),"+f"(d[70]),"+f"(d[71]),"+f"(d[72]),"+f"(d[73]),"+f"(d[74]),"+f"(d[75]),"+f"(d[76]),"+f"(d[77]),"+f"(d[78]),"+f"(d[79]),"+f"(d[80]),"+f"(d[81]),"+f"(d[82]),"+f"(d[83]),"+f"(d[84]),"+f"(d[85]),"+f"(d[86]),"+f"(d[87]),"+f"(d[88]),"+f"(d[89]),"+f"(d[90]),"+f"(d[91]),"+f"(d[92]),"+f"(d[93]),"+f"(d[94]),"+f"(d[95]),"+f"(d[96]),"+f"(d[97]),"+f"(d[98]),"+f"(d[99]),"+f"(d[100]),"+f"(d[101]),"+f"(d[102]),"+f"(d[103]),"+f"(d[104]),"+f"(d[105]),"+f"(d[106]),"+f"(d[107]),"+f"(d[108]),"+f"(d[109]),"+f"(d[110]),"+f"(d[111]),"+f"(d[112]),"+f"(d[113]),"+f"(d[114]),"+f"(d[115]),"+f"(d[116]),"+f"(d[117]),"+f"(d[118]),"+f"(d[119]),"+f"(d[120]),"+f"(d[121]),"+f"(d[122]),"+f"(d[123]),"+f"(d[124]),"+f"(d[125]),"+f"(d[126]),"+f"(d[127])
    : "l"(da), "l"(db), "r"(sc));
}

__device__ __forceinline__ void wgmma_ss_n128_tb1(float (&d)[64], uint64_t da, uint64_t db, int sc) {
  asm volatile("{.reg .pred p; setp.ne.b32 p, %66, 0;\n"
    "wgmma.mma_async.sync.aligned.m64n128k16.f32.bf16.bf16 {%0,%1,%2,%3,%4,%5,%6,%7,%8,%9,%10,%11,%12,%13,%14,%15,%16,%17,%18,%19,%20,%21,%22,%23,%24,%25,%26,%27,%28,%29,%30,%31,%32,%33,%34,%35,%36,%37,%38,%39,%40,%41,%42,%43,%44,%45,%46,%47,%48,%49,%50,%51,%52,%53,%54,%55,%56,%57,%58,%59,%60,%61,%62,%63}, %64, %65, p, 1, 1, 0, 1;}\n"
    : "+f"(d[0]),"+f"(d[1]),"+f"(d[2]),"+f"(d[3]),"+f"(d[4]),"+f"(d[5]),"+f"(d[6]),"+f"(d[7]),"+f"(d[8]),"+f"(d[9]),"+f"(d[10]),"+f"(d[11]),"+f"(d[12]),"+f"(d[13]),"+f"(d[14]),"+f"(d[15]),"+f"(d[16]),"+f"(d[17]),"+f"(d[18]),"+f"(d[19]),"+f"(d[20]),"+f"(d[21]),"+f"(d[22]),"+f"(d[23]),"+f"(d[24]),"+f"(d[25]),"+f"(d[26]),"+f"(d[27]),"+f"(d[28]),"+f"(d[29]),"+f"(d[30]),"+f"(d[31]),"+f"(d[32]),"+f"(d[33]),"+f"(d[34]),"+f"(d[35]),"+f"(d[36]),"+f"(d[37]),"+f"(d[38]),"+f"(d[39]),"+f"(d[40]),"+f"(d[41]),"+f"(d[42]),"+f"(d[43]),"+f"(d[44]),"+f"(d[45]),"+f"(d[46]),"+f"(d[47]),"+f"(d[48]),"+f"(d[49]),"+f"(d[50]),"+f"(d[51]),"+f"(d[52]),"+f"(d[53]),"+f"(d[54]),"+f"(d[55]),"+f"(d[56]),"+f"(d[57]),"+f"(d[58]),"+f"(d[59]),"+f"(d[60]),"+f"(d[61]),"+f"(d[62]),"+f"(d[63])
    : "l"(da), "l"(db), "r"(sc));
}

template <int BN> struct WG;
template <> struct WG<256> { static __device__ __forceinline__ void mma(float (&d)[128], uint64_t a, uint64_t b, int sc) { wgmma_ss_n256_tb1(d, a, b, sc); } };
template <> struct WG<128> { static __device__ __forceinline__ void mma(float (&d)[64], uint64_t a, uint64_t b, int sc) { wgmma_ss_n128_tb1(d, a, b, sc); } };

struct GemmMaps { CUtensorMap a, b[3], c; };
template <int BN, int STAGES>
__global__ void __cluster_dims__(2, 1, 1) __launch_bounds__(384, 1)
gemm_kernel(const __grid_constant__ GemmMaps maps, int tilesM, int tilesN, int kblocks, int nPerB, int clearX) {
  extern __shared__ __align__(1024) uint8_t smem_raw[];
  constexpr int STAGE_BYTES = 16384 + BN * 128;
  constexpr int NBOX = BN / 64;
  const uint32_t sbase = (smem_u32(smem_raw) + 1023) & ~1023u;
  const uint32_t sEpi = sbase + STAGES * STAGE_BYTES;
  const uint32_t sBar = sEpi + 32768;
  const int warp = threadIdx.x >> 5, lane = threadIdx.x & 31, wg = warp >> 2;
  uint32_t crank; asm("mov.u32 %0, %%cluster_ctarank;" : "=r"(crank));
  if (threadIdx.x == 0) {
    for (int i = 0; i < STAGES; i++) { mbar_init(sBar + 8 * i, 1); mbar_init(sBar + 8 * (STAGES + i), 4); }
    asm volatile("fence.mbarrier_init.release.cluster;" ::: "memory");
  }
  if (clearX) {
    uint4* p = g_xraw;
    for (int i = blockIdx.x * 384 + threadIdx.x; i < (int)(sizeof(g_xraw) / 16); i += gridDim.x * 384) p[i] = make_uint4(0, 0, 0, 0);
  }
  asm volatile("barrier.cluster.arrive.release.aligned; barrier.cluster.wait.acquire.aligned;" ::: "memory");
  const int npairs = (tilesM >> 1) * tilesN, pair0 = blockIdx.x >> 1, pstep = gridDim.x >> 1;
  if (wg == 2) {
    asm volatile("setmaxnreg.dec.sync.aligned.u32 40;");
    if (warp == 8 && lane == 0) {
      int st = 0, ph = 1;
      for (int p = pair0; p < npairs; p += pstep) {
        const int tm = (p % (tilesM >> 1)) * 2 + crank, tn = p / (tilesM >> 1);
        const CUtensorMap* mb = &maps.b[tn / nPerB];
        const int n0 = (tn % nPerB) * BN;
        for (int kb = 0; kb < kblocks; kb++) {
          mbar_wait(sBar + 8 * (STAGES + st), ph);
          const uint32_t a = sbase + st * STAGE_BYTES, full = sBar + 8 * st;
          mbar_expect_tx(full, STAGE_BYTES);
          tma2d(a, &maps.a, kb * 64, tm * 128, full);
#pragma unroll
          for (int i = 0; i < NBOX / 2; i++) {
            const int bx = crank * (NBOX / 2) + i;
            tma2d_mc(a + 16384 + bx * 8192, mb, n0 + bx * 64, kb * 64, full, (uint16_t)3);
          }
          if (++st == STAGES) { st = 0; ph ^= 1; }
        }
      }
      for (int i = 0; i < STAGES; i++) { mbar_wait(sBar + 8 * (STAGES + st), ph); if (++st == STAGES) { st = 0; ph ^= 1; } }
    }
  } else {
    asm volatile("setmaxnreg.inc.sync.aligned.u32 232;");
    int st = 0, ph = 0;
    float acc[BN / 2];
    const uint64_t descA0 = (uint64_t)(((sbase + wg * 8192) & 0x3FFFF) >> 4) | (1ull << 16) | (64ull << 32) | (1ull << 62);
    const uint64_t descB0 = (uint64_t)(((sbase + 16384) & 0x3FFFF) >> 4) | (512ull << 16) | (64ull << 32) | (1ull << 62);
    const uint32_t epi = sEpi + wg * 16384;
    for (int p = pair0; p < npairs; p += pstep) {
      const int tm = (p % (tilesM >> 1)) * 2 + crank, tn = p / (tilesM >> 1);
      int prev = -1;
      for (int kb = 0; kb < kblocks; kb++) {
        mbar_wait(sBar + 8 * st, ph);
        wg_fence();
        const uint64_t so = (uint64_t)(st * (STAGE_BYTES >> 4));
#pragma unroll
        for (int k = 0; k < 4; k++) WG<BN>::mma(acc, descA0 + so + k * 2, descB0 + so + k * 128, kb | k);
        wg_commit();
        if (prev >= 0) {
          wg_wait<1>();
          if ((threadIdx.x & 127) < 2) mbar_arrive_cluster(sBar + 8 * (STAGES + prev), threadIdx.x & 1);
        }
        prev = st;
        if (++st == STAGES) { st = 0; ph ^= 1; }
      }
      wg_wait<0>();
      if ((threadIdx.x & 127) < 2) mbar_arrive_cluster(sBar + 8 * (STAGES + prev), threadIdx.x & 1);
#pragma unroll
      for (int r = 0; r < BN / 128; r++) {
        if ((threadIdx.x & 127) == 0) asm volatile("cp.async.bulk.wait_group.read 0;" ::: "memory");
        bar_sync(1 + wg, 128);
        const int row = (warp & 3) * 16 + (lane & 15);
#pragma unroll
        for (int i = 0; i < 8; i++) {
          const int c = 2 * (i & 3) + (lane >> 4);
          const float* q = &acc[r * 64 + i * 8];
          stsm4(epi + (i >> 2) * 8192 + row * 128 + ((c ^ (row & 7)) << 4), pack2(q[0], q[1]), pack2(q[2], q[3]), pack2(q[4], q[5]), pack2(q[6], q[7]));
        }
        fence_async();
        bar_sync(1 + wg, 128);
        if ((threadIdx.x & 127) == 0) {
          tma2d_store(&maps.c, epi, tn * BN + r * 128, tm * 128 + wg * 64);
          tma2d_store(&maps.c, epi + 8192, tn * BN + r * 128 + 64, tm * 128 + wg * 64);
          asm volatile("cp.async.bulk.commit_group;" ::: "memory");
        }
      }
    }
    if ((threadIdx.x & 127) == 0) asm volatile("cp.async.bulk.wait_group 0;" ::: "memory");
  }
}

struct Dft { uint32_t m[2][2][2][4]; };
template <bool P4> __device__ __forceinline__ int fidx(int tile, int x) { return P4 ? 4 * (x >> 1) + 2 * (tile & 1) + (x & 1) + 16 * (tile >> 1) : x + 8 * tile; }
__device__ __forceinline__ float2 cis(int k, int n) {
  k &= n - 1; if (2 * k > n) k -= n;
  const float a = (float)k * (6.283185307179586f / (float)n);
  return make_float2(__cosf(a), __sinf(a));
}
template <bool OUT4> __device__ __forceinline__ void make_dft(Dft& D, int g, int t) {
#pragma unroll
  for (int q = 0; q < 16; q++) {
    const int b = q >> 3, u = (q >> 2) & 1, r = (q >> 1) & 1, v = q & 1;
    const float2 w = cis(fidx<OUT4>(v, g) * fidx<false>(2 * u + r, 2 * t + b), 32);
    D.m[b][u][0][q & 3] = pack2(w.x, w.y); D.m[b][u][1][q & 3] = pack2(-w.y, w.x);
  }
}
__device__ __forceinline__ void mma_dc(float (&d)[4], uint32_t a0, uint32_t a1, uint32_t a2, uint32_t a3, uint32_t b0, uint32_t b1, const float (&c)[4]) {
  asm("mma.sync.aligned.m16n8k16.row.col.f32.bf16.bf16.f32 {%0,%1,%2,%3}, {%4,%5,%6,%7}, {%8,%9}, {%10,%11,%12,%13};"
    : "=f"(d[0]), "=f"(d[1]), "=f"(d[2]), "=f"(d[3]) : "r"(a0), "r"(a1), "r"(a2), "r"(a3), "r"(b0), "r"(b1), "f"(c[0]), "f"(c[1]), "f"(c[2]), "f"(c[3])); }
__device__ __forceinline__ void dft_b(const Dft& D, const uint32_t (&x)[2][4], float (&o)[2][8]) {
#pragma unroll
  for (int ri = 0; ri < 2; ri++) {
    float z[4] = {0.f, 0.f, 0.f, 0.f}, e[4], p[4];
    mma_dc(e, D.m[0][0][ri][0], D.m[0][0][ri][1], D.m[0][0][ri][2], D.m[0][0][ri][3], x[0][0], x[0][1], z);
    mma_dc(e, D.m[0][1][ri][0], D.m[0][1][ri][1], D.m[0][1][ri][2], D.m[0][1][ri][3], x[0][2], x[0][3], e);
    mma_dc(p, D.m[1][0][ri][0], D.m[1][0][ri][1], D.m[1][0][ri][2], D.m[1][0][ri][3], x[1][0], x[1][1], e);
    mma_dc(p, D.m[1][1][ri][0], D.m[1][1][ri][1], D.m[1][1][ri][2], D.m[1][1][ri][3], x[1][2], x[1][3], p);
#pragma unroll
    for (int q = 0; q < 4; q++) { o[ri][q] = p[q]; o[ri][4 + q] = fmaf(2.f, e[q], -p[q]); }
  }
}
__device__ __forceinline__ void dft_a(const uint32_t (&m)[2][2][4], const uint32_t (&x0)[2][4], const uint32_t (&x1)[2][4], float (&o)[2][8]) {
#pragma unroll
  for (int ri = 0; ri < 2; ri++) {
    float z[4] = {0.f, 0.f, 0.f, 0.f}, e[4], p[4];
    mma_dc(e, x0[0][0], x1[0][0], x0[0][1], x1[0][1], m[0][ri][0], m[0][ri][1], z);
    mma_dc(e, x0[0][2], x1[0][2], x0[0][3], x1[0][3], m[0][ri][2], m[0][ri][3], e);
    mma_dc(p, x0[1][0], x1[1][0], x0[1][1], x1[1][1], m[1][ri][0], m[1][ri][1], e);
    mma_dc(p, x0[1][2], x1[1][2], x0[1][3], x1[1][3], m[1][ri][2], m[1][ri][3], p);
#pragma unroll
    for (int q = 0; q < 4; q++) { o[ri][q] = p[q]; o[ri][4 + q] = fmaf(2.f, e[q], -p[q]); }
  }
}
__device__ __forceinline__ uint32_t twid(float re, float im, float c, float s) { return pack2(fmaf(re, c, im * s), fmaf(im, c, -re * s)); }
__device__ __forceinline__ void cpa16(uint32_t d, const void* s) { asm volatile("cp.async.cg.shared.global [%0], [%1], 16;" :: "r"(d), "l"(s) : "memory"); }
__device__ __forceinline__ void sts32(uint32_t a, uint32_t x) { asm volatile("st.shared.u32 [%0], %1;" :: "r"(a), "r"(x) : "memory"); }
__device__ __forceinline__ void cpa_commit() { asm volatile("cp.async.commit_group;" ::: "memory"); }
template <int N> __device__ __forceinline__ void cpa_wait() { asm volatile("cp.async.wait_group %0;" :: "n"(N) : "memory"); }
__device__ __forceinline__ uint32_t lds32(uint32_t a) { uint32_t r; asm volatile("ld.shared.u32 %0, [%1];" : "=r"(r) : "r"(a) : "memory"); return r; }
constexpr int F_TP = 4112, F_TSZ = 8 * F_TP;

__device__ __forceinline__ void fft_wprep(const bf16* __restrict__ wr, const bf16* __restrict__ wi, int cta, int ncta) {
  const int tid = threadIdx.x;
#pragma unroll 2
  for (int it = cta; it < 256; it += ncta) {
    const int g = (it >> 1) & 7, c = (it >> 4) & 3, i = it >> 6, t = 2 * (it & 1) + (tid & 1);
    const int k0 = g + 8 * i + 32 * (8 * c + 2 * t), l0 = (tid & ~1) + (g & 1);
    uint32_t a[2][4], b[2][4];
#pragma unroll
    for (int q = 0; q < 8; q++) {
      const int o = (k0 + 32 * ((q >> 1) & 1) + 1024 * (q & 1)) * 513 + l0 + 256 * (q >> 2);
      a[q >> 2][q & 3] = __ldg(reinterpret_cast<const uint32_t*>(wr + o));
      b[q >> 2][q & 3] = __ldg(reinterpret_cast<const uint32_t*>(wi + o));
    }
    uint4* dst = g_wt + l0 * 512 + it * 2 + (tid & 1);
#pragma unroll
    for (int q = 0; q < 4; q++) {
      const int hf = q >> 1, l = l0 + 256 * hf + (q & 1);
      const uint32_t sel = (q & 1) ? 0x7632 : 0x5410;
      if (l & 511) dst[(256 * hf + (q & 1)) * 512] = make_uint4(__byte_perm(a[hf][0], b[hf][0], sel), __byte_perm(a[hf][1], b[hf][1], sel),
                                                              __byte_perm(a[hf][2], b[hf][2], sel), __byte_perm(a[hf][3], b[hf][3], sel));
    }
  }
  for (int e = cta * 256 + tid; e < 4096; e += ncta * 256) {
    const int l = (e >> 11) * 512, k = e & 2047, kn = (2048 - k) & 2047, k2 = (k >> 5) & 31;
    const float re = 0.5f * (__bfloat162float(wr[k * 513 + l]) + __bfloat162float(wr[kn * 513 + l]));
    const float im = 0.5f * (__bfloat162float(wi[k * 513 + l]) - __bfloat162float(wi[kn * 513 + l]));
    reinterpret_cast<uint32_t*>(g_wt)[(64 * ((k >> 3) & 3) + 16 * (k2 >> 3) + 2 * (k & 7) + ((k2 >> 2) & 1)) * 8 + l * 2048 + 2 * (k2 & 3) + (k >> 10)] = pack2(re, im);
  }
}

__device__ __forceinline__ void fft_rows_fwd(const bf16* __restrict__ x, uint32_t sb, int cta, int ncta) {
  const int warp = threadIdx.x >> 5, lane = threadIdx.x & 31, g = lane >> 2, t = lane & 3;
  const uint32_t in = sb + warp * 8192, tb = sb + 65536;
  const uint32_t f0 = pin(in + (lane >> 3) * 256 + (((lane & 7) ^ (2 * (lane >> 3))) << 4));
  const uint32_t xo = pin((256 * (warp & 3) + 64 * (warp >> 2)) * 2048 + lane * 8);
  auto fetch = [&](int it, int buf) {
    const bf16* src = x + (xo + (128 * (it & 1) + 32 * ((it >> 4) & 1) + 8 * (it >> 5) + ((it >> 1) & 7)) * 2048);
#pragma unroll
    for (int q = 0; q < 8; q++) cpa16(((f0 + buf * 4096) ^ ((q >> 2) * 144)) + (q & 3) * 1024, src + q * 256);
    cpa_commit();
  };
  fetch(cta, 0);
  Dft D; make_dft<true>(D, g, t);
  float2 tw[4][8];
#pragma unroll
  for (int q = 0; q < 32; q++) tw[q >> 3][q & 7] = cis(fidx<true>((q >> 1) & 3, g) * fidx<false>(q >> 3, 2 * t + (q & 1)), 1024);
  const uint32_t la = pin(in + lane * 128 + ((lane & 7) << 4));
  const uint32_t wa = pin(tb + warp * F_TP + fidx<true>(0, g) * 128 + t * 16), wz = pin((g & 1) ? -64 : 64);
  const uint32_t ra = pin(tb + (lane & 1) * 4 * F_TP + ((lane >> 1) + 16 * (warp ^ ((warp >> 1) & 1))) * 4);
  uint4* dst = g_y + (threadIdx.x >> 1) * 256 + (lane & 1);
  int buf = 0;
  auto drain = [&](int it, int q) {
    const uint32_t r = ra + (buf ^ 1) * F_TSZ + q * 512;
    const uint4 v = make_uint4(lds32(r), lds32(r + F_TP), lds32(r + 2 * F_TP), lds32(r + 3 * F_TP));
    if (it >= 0) dst[it * 2 + q * 32768] = v;
  };
  int it = cta;
#pragma unroll 1
  for (; it < 128; it += ncta, buf ^= 1) {
    cpa_wait<0>(); __syncthreads();
    uint32_t a[4][2][4], y[4][2][4];
#pragma unroll
    for (int q = 0; q < 8; q++) ldsm4t(a[q & 3][q >> 2], (la + buf * 4096) ^ (q << 4));
    if (it + ncta < 128) fetch(it + ncta, buf ^ 1);
    float o[2][8];
#pragma unroll
    for (int i = 0; i < 4; i++) {
      dft_b(D, a[i], o);
      drain(it - ncta, i);
#pragma unroll
      for (int q = 0; q < 8; q++) y[q >> 1][q & 1][i] = twid(o[0][q], o[1][q], tw[i][q].x, tw[i][q].y);
    }
    const uint32_t w0 = wa + buf * F_TSZ + ((g & 1) << 6);
#pragma unroll
    for (int z = 0; z < 2; z++) {
      float o2[2][8];
      dft_b(D, y[2 * z], o); drain(it - ncta, 4 + 2 * z); dft_b(D, y[2 * z + 1], o2); drain(it - ncta, 5 + 2 * z);
#pragma unroll
      for (int i = 0; i < 4; i++) {
        const float sg = i < 2 ? 1.f : -1.f;
        sts128(w0 + z * wz + fidx<true>(i, 0) * 128, pack2(o[0][2 * i], sg * o[1][2 * i]), pack2(o[0][2 * i + 1], sg * o[1][2 * i + 1]),
               pack2(o2[0][2 * i], sg * o2[1][2 * i]), pack2(o2[0][2 * i + 1], sg * o2[1][2 * i + 1]));
      }
    }
  }
  __syncthreads();
#pragma unroll
  for (int q = 0; q < 8; q++) drain(it - ncta, q);
}

__device__ __forceinline__ void fft_cols(uint32_t sb, int cta, int ncta) {
  const int warp = threadIdx.x >> 5, lane = threadIdx.x & 31, g = lane >> 2, t = lane & 3;
  const uint32_t in = sb + warp * 16384 + lane * 16, tab = sb + 131072 + lane * 16;
  auto fetch_y = [&](int l) {
#pragma unroll
    for (int q = 0; q < 16; q++) cpa16(in + q * 512, g_y + (q < 8 ? l : (1024 - l) & 1023) * 256 + (q & 7) * 32 + lane);
  };
  auto fetch_w = [&](int l) {
#pragma unroll
    for (int q = 0; q < 16; q++) cpa16(in + 8192 + q * 512, g_wt + l * 512 + q * 32 + lane);
  };
  const int l0 = cta * 8 + warp, dl = ncta * 8;
  if (l0 <= 512) fetch_y(l0);
  cpa_commit();
  if (l0 <= 512) fetch_w(l0);
  cpa_commit();
  Dft D; make_dft<false>(D, g, t);
#pragma unroll
  for (int q = 2 * warp; q < 2 * warp + 2; q++) {
    const int r = fidx<false>(q & 3, g), c = fidx<false>(q >> 2, 2 * t);
    const float2 w0 = cis(r * c, 1024), w1 = cis(r * c + r, 1024), p0 = cis(r + 32 * c, 2048), p1 = cis(r + 32 * c + 32, 2048);
    sts128(tab + q * 512, __float_as_uint(w0.x), __float_as_uint(w0.y), __float_as_uint(w1.x), __float_as_uint(w1.y));
    sts128(tab + 8192 + q * 512, __float_as_uint(p0.x), __float_as_uint(p0.y), __float_as_uint(p1.x), __float_as_uint(p1.y));
  }
  if (warp == 0) {
#pragma unroll
    for (int q = 0; q < 8; q++) {
      const int v = q >> 2, b = (q >> 1) & 1, ri = q & 1;
      sts128(tab + 16384 + q * 512, D.m[b][0][ri][v], D.m[b][0][ri][v + 2], D.m[b][1][ri][v], D.m[b][1][ri][v + 2]);
    }
  }
  __syncthreads();
#pragma unroll 1
  for (int l = l0; l <= 512; l += dl) {
    uint32_t a[2][4][2][4], y[2][4][2][4];
    float o[2][2][8];
    cpa_wait<1>();
#pragma unroll
    for (int q = 0; q < 16; q++) lds128(a[q >> 3][(q >> 1) & 3][q & 1], in + q * 512);
    if (!(l & 511)) {
      const uint32_t m0 = l ? 0x80000000u : 0u;
#pragma unroll
      for (int q = 0; q < 32; q++) { a[0][q >> 3][(q >> 2) & 1][q & 3] ^= m0; a[1][q >> 3][(q >> 2) & 1][q & 3] ^= m0 ^ 0x80000000u; }
    }
    auto first = [&]() {
#pragma unroll
      for (int i = 0; i < 4; i++) {
        dft_b(D, a[0][i], o[0]); dft_b(D, a[1][i], o[1]);
#pragma unroll
        for (int r = 0; r < 4; r++) {
          const float4 w = lds128f(tab + (4 * i + r) * 512);
#pragma unroll
          for (int s = 0; s < 2; s++) {
            y[s][r][0][i] = twid(o[s][0][2 * r], o[s][1][2 * r], w.x, w.y);
            y[s][r][1][i] = twid(o[s][0][2 * r + 1], o[s][1][2 * r + 1], w.z, w.w);
          }
        }
      }
    };
    first();
    if (l + dl <= 512) fetch_y(l + dl);
    cpa_commit();
    cpa_wait<1>();
#pragma unroll
    for (int zv = 0; zv < 4; zv++) {
      const int z = zv >> 1, v = zv & 1;
      uint32_t m[2][2][4];
#pragma unroll
      for (int q = 0; q < 4; q++) lds128(m[q >> 1][q & 1], tab + 16384 + (4 * v + q) * 512);
      dft_a(m, y[0][2 * z], y[0][2 * z + 1], o[0]); dft_a(m, y[1][2 * z], y[1][2 * z + 1], o[1]);
#pragma unroll
      for (int q = 0; q < 4; q++) {
        const int i = 2 * z + (q & 1), c = v + (q & 2);
        uint32_t w[4]; lds128(w, in + 8192 + (4 * i + c) * 512);
        const float4 ph = lds128f(tab + 8192 + (4 * c + i) * 512);
#pragma unroll
        for (int b = 0; b < 2; b++) {
          const float cs = b ? ph.z : ph.x, sn = b ? ph.w : ph.y;
          const float r1 = __uint_as_float(w[2 * b] << 16), i1 = __uint_as_float(w[2 * b] & 0xFFFF0000u);
          const float r2 = __uint_as_float(w[2 * b + 1] << 16), i2 = __uint_as_float(w[2 * b + 1] & 0xFFFF0000u);
          const float Sr = r1 + r2, Si = i1 + i2, Dr = r1 - r2, Di = i1 - i2;
          const float ar = fmaf(-Dr, sn, Sr), ai = fmaf(-Di, sn, Si), dr = fmaf(Dr, sn, Sr), di = fmaf(Di, sn, Si), br = -Di * cs, bi = Dr * cs;
          const float Ar = o[0][0][2 * q + b], Ai = o[0][1][2 * q + b], Br = o[1][0][2 * q + b], Bi = o[1][1][2 * q + b];
          a[0][i][b][c] = pack2(fmaf(ar, Ai, fmaf(ai, Ar, fmaf(br, Bi, bi * Br))), fmaf(ar, Ar, fmaf(-ai, Ai, fmaf(br, Br, -bi * Bi))));
          a[1][i][b][c] = pack2(fmaf(dr, Bi, fmaf(di, Br, fmaf(-br, Ai, -bi * Ar))), fmaf(dr, Br, fmaf(-di, Bi, fmaf(-br, Ar, bi * Ai))));
        }
      }
    }
    if (l + dl <= 512) fetch_w(l + dl);
    cpa_commit();
    first();
#pragma unroll
    for (int s = 0; s < 2; s++) {
      uint4* dst = g_y + (s ? (1024 - l) & 1023 : l) * 256 + lane;
      const float sg = s ? -1.f : 1.f;
#pragma unroll
      for (int i = 0; i < 4; i++) {
        dft_b(D, y[s][i], o[0]);
#pragma unroll
        for (int b = 0; b < 2; b++)
          dst[(2 * i + b) * 32] = make_uint4(pack2(sg * o[0][0][b], o[0][1][b]), pack2(sg * o[0][0][2 + b], o[0][1][2 + b]),
                                             pack2(sg * o[0][0][4 + b], o[0][1][4 + b]), pack2(sg * o[0][0][6 + b], o[0][1][6 + b]));
      }
    }
  }
}

__device__ __forceinline__ void fft_rows_inv(const CUtensorMap* om, uint32_t sb, int cta, int ncta) {
  const int warp = threadIdx.x >> 5, lane = threadIdx.x & 31, g = lane >> 2, t = lane & 3, wg = warp >> 2, w4 = warp & 3;
  const uint32_t tb = sb + 32768 + wg * 2 * F_TSZ;
  const uint4* src = g_y + pin((256 * ((lane >> 1) & 3) + 64 * (lane >> 3) + 8 * w4) * 256 + (lane & 1));
  const uint32_t wa = pin(tb + (lane & 1) * 4 * F_TP + w4 * 1024 + (lane >> 1) * 4);
  uint4 pf[8];
  auto fetch = [&](int it, int hf) {
#pragma unroll
    for (int q = 0; q < 8; q++) pf[q] = __ldcg(src + (it * 2 + hf * 8192) + q * 256);
  };
  auto put = [&](uint32_t off) {
#pragma unroll
    for (int q = 0; q < 8; q++) {
      sts32(wa + off + q * 64, pf[q].x); sts32(wa + off + q * 64 + F_TP, pf[q].y);
      sts32(wa + off + q * 64 + 2 * F_TP, pf[q].z); sts32(wa + off + q * 64 + 3 * F_TP, pf[q].w);
    }
  };
  const int it0 = 2 * cta + wg;
  if (it0 >= 128) return;
  fetch(it0, 0); put(0); fetch(it0, 1); put(512);
  Dft D; make_dft<false>(D, g, t);
  float2 tw[4][8];
#pragma unroll
  for (int q = 0; q < 32; q++) {
    tw[q >> 3][q & 7] = cis(fidx<false>((q >> 1) & 3, g) * fidx<false>(q >> 3, 2 * t + (q & 1)), 1024);
    tw[q >> 3][q & 7].x *= 1.f / 2097152.f; tw[q >> 3][q & 7].y *= 1.f / 2097152.f;
  }
  const uint32_t la = pin(tb + w4 * F_TP + lane * 16), ob = uni(sb + warp * 4096);
  const uint32_t oa = pin(ob + (lane >> 1) * 128 + (((4 * (lane & 1)) ^ ((lane >> 1) & 7)) << 4));
#pragma unroll 1
  for (int n = 0;; n++) {
    const int it = it0 + (n >> 1) * 2 * ncta, hf = n & 1, buf = (n >> 1) & 1;
    if (it >= 128) break;
    if (!hf) bar_sync(1 + wg, 128);
    uint32_t a[4][2][4], y[4][2][4];
#pragma unroll
    for (int q = 0; q < 8; q++) lds128(a[q >> 1][q & 1], la + buf * F_TSZ + hf * 4 * F_TP + q * 512);
    fetch(min(it + 2 * ncta, 127), hf);
    float o[2][8];
#pragma unroll
    for (int i = 0; i < 4; i++) {
      dft_b(D, a[i], o);
#pragma unroll
      for (int q = 0; q < 8; q++) y[q >> 1][q & 1][i] = twid(o[0][q], o[1][q], tw[i][q].x, tw[i][q].y);
    }
    if (lane == 0) asm volatile("cp.async.bulk.wait_group.read 0;" ::: "memory");
    __syncwarp();
#pragma unroll
    for (int c = 0; c < 4; c++) {
      dft_b(D, y[c], o);
#pragma unroll
      for (int ri = 0; ri < 2; ri++)
        stsm4((oa ^ (c << 4)) + (1 - ri) * 2048, pack2(o[ri][0], o[ri][1]), pack2(o[ri][2], o[ri][3]), pack2(o[ri][4], o[ri][5]), pack2(o[ri][6], o[ri][7]));
    }
    fence_async();
    __syncwarp();
    if (lane == 0) {
      const int m = 256 * w4 + 32 * ((it >> 1) & 7) + 8 * (it >> 5) + 4 * (it & 1) + 2 * hf + ((it >> 4) & 1);
      asm volatile("cp.async.bulk.tensor.3d.global.shared::cta.bulk_group [%0, {0, 0, %2}], [%1];" :: "l"(om), "r"(ob), "r"(2 * m) : "memory");
      asm volatile("cp.async.bulk.commit_group;" ::: "memory");
    }
    put((buf ^ 1) * F_TSZ + hf * 512);
  }
  if (lane == 0) asm volatile("cp.async.bulk.wait_group 0;" ::: "memory");
}
constexpr int F_SMEM = 65536 + 2 * F_TSZ + 1024;
__global__ void __launch_bounds__(256, 1) fft_pre_kernel(const bf16* __restrict__ x, const bf16* __restrict__ wr, const bf16* __restrict__ wi) {
  extern __shared__ __align__(1024) uint8_t smem_raw[];
  const uint32_t sb = (smem_u32(smem_raw) + 1023) & ~1023u;
  fft_wprep(wr, wi, blockIdx.x, gridDim.x);
  fft_rows_fwd(x, sb, blockIdx.x, gridDim.x);
}
__device__ __forceinline__ void grid_arrive(unsigned* ctr) {
  __syncthreads();
  if (threadIdx.x == 0) { __threadfence(); atomicAdd(ctr, 1u); }
}
__device__ __forceinline__ void grid_wait(unsigned* ctr, unsigned n) {
  if (threadIdx.x == 0) {
    int it = 0;
    while (*reinterpret_cast<volatile unsigned*>(ctr) < n) { __nanosleep(200); if (++it > SPIN_LIMIT) { g_err = 3; break; } }
    __threadfence();
  }
  __syncthreads();
}

struct RecMaps { CUtensorMap wq, wk, wv, wo, x, k, q, v, fo; };
#define NSW 16
#define EXP 0
#define NPROBE 2
#define HOME 3
#define DL0 14
#define PD1 4
#define NE4 6
#define NE6 0
#define NA4 14
#define NA6 18
#define NB1 24
#define TQL 7
#define NQ 8
#define TQP (NQ - 1)
#define OXPOS 4
#define KVPOS 2
#define NK0 0
#define FLPOS 1
#define XWPOS 10
#define FSPOS 28
#define RL0 4
#define RLS 6
#define RLB 4
#define VL0 3
#define RI 9
#define RJ 8
#define NPRE 20
#define PFD 4
#define PD0 4
#define VB NV0
#define NPA 0
#define N1 16
#define DL1 16
#define PACE 0
#define RE0 0
#define RE1 0
#define RP1 23
#define UNP 1
#define X2 2
#define X3 2
#define SPOS 2
#ifndef NV0
#define NV0 4
#endif
#define TGP 3
#define FENP 0
#define LW0 8
#define X1 4
#define X0 4
constexpr int R_WO = 0, R_X = 65536, R_MEM = 131072, R_WC = 147456, R_RED = R_WC + NSW * 2048, R_O = R_RED, R_S = R_O + 2048, R_P = R_S + 3072, R_STAGE = R_P + 2048,
              R_K = R_STAGE + 8192, R_Q = R_K + 8192, R_V = R_Q + 2048, R_ID = R_V + 16384, R_T = R_ID + 512, R_DST = R_T + 512, R_RD = R_DST + 2048, R_BAR = R_RD + 2048, R_TS = R_BAR + 128,
              R_TOTAL = R_TS;
#define TS(i)
#define LOG(i, v)
constexpr int B_KV = R_BAR, B_W = R_BAR + 8, B_X = R_BAR + 80, B_PK = R_BAR + 24, B_C = R_BAR + 32, B_B = R_BAR + 40, B_DUE = R_BAR + 48, B_ONE = R_BAR + 64;
#define DLY_A 150
#define DLY_V 150
#define DLY_C 200
#define DLY_L 90
#define NS_B 1088
#define NS_C 1696
#define NS_P 2752
#define NS_V 128
#define NS_F 896
#define NS_K 128
#define NS_M 32
#define NS_X 128
#define NS_PEN 1024
__device__ __forceinline__ float rcp(float x) { float r; asm("rcp.approx.ftz.f32 %0, %1;" : "=f"(r) : "f"(x)); return r; }
__device__ __forceinline__ uint32_t movm(uint32_t a) { uint32_t d; asm volatile("movmatrix.sync.aligned.m8n8.trans.b16 %0, %1;" : "=r"(d) : "r"(a)); return d; }
__device__ __forceinline__ uint32_t hadd2(uint32_t a, uint32_t b) { uint32_t d; asm("add.rn.bf16x2 %0, %1, %2;" : "=r"(d) : "r"(a), "r"(b)); return d; }
__device__ __forceinline__ void mma_a(float (&d)[4], const uint32_t (&a)[4], uint32_t b0, uint32_t b1) { mma16816(d, a[0], a[1], a[2], a[3], b0, b1); }
__device__ __forceinline__ bool elect() {
  uint32_t p; asm volatile("{.reg .pred p; elect.sync _|p, 0xffffffff; selp.u32 %0, 1, 0, p;}" : "=r"(p)); return p; }
__device__ __forceinline__ void tma3d(uint32_t dst, const CUtensorMap* m, int c1, int c2, uint32_t bar) {
  asm volatile("cp.async.bulk.tensor.3d.shared::cluster.global.mbarrier::complete_tx::bytes [%0], [%1, {0, %3, %4}], [%2];"
    :: "r"(dst), "l"(m), "r"(bar), "r"(c1), "r"(c2) : "memory"); }
__device__ __forceinline__ void tma4d(uint32_t dst, const CUtensorMap* m, int c1, int c2, uint32_t bar) {
  asm volatile("cp.async.bulk.tensor.4d.shared::cluster.global.mbarrier::complete_tx::bytes [%0], [%1, {0, %3, %4, 0}], [%2];"
    :: "r"(dst), "l"(m), "r"(bar), "r"(c1), "r"(c2) : "memory"); }
template <int OFF, int ACC>
__device__ __forceinline__ void wg_rs32(float (&d)[16], const uint32_t (&a)[4], uint32_t db) {
  if (ACC)
    asm volatile("{.reg .b64 db; .reg .b32 lo; add.u32 lo, %20, %21; mov.b64 db, {lo, 0x40000040};\n"
      "wgmma.mma_async.sync.aligned.m64n32k16.f32.bf16.bf16 {%0,%1,%2,%3,%4,%5,%6,%7,%8,%9,%10,%11,%12,%13,%14,%15}, {%16,%17,%18,%19}, db, 1, 1, 1, 0;}"
      : "+f"(d[0]), "+f"(d[1]), "+f"(d[2]), "+f"(d[3]), "+f"(d[4]), "+f"(d[5]), "+f"(d[6]), "+f"(d[7]), "+f"(d[8]), "+f"(d[9]), "+f"(d[10]), "+f"(d[11]), "+f"(d[12]), "+f"(d[13]), "+f"(d[14]), "+f"(d[15])
      : "r"(a[0]), "r"(a[1]), "r"(a[2]), "r"(a[3]), "r"(db), "n"(OFF));
  else
    asm volatile("{.reg .b64 db; .reg .b32 lo; add.u32 lo, %20, %21; mov.b64 db, {lo, 0x40000040};\n"
      "wgmma.mma_async.sync.aligned.m64n32k16.f32.bf16.bf16 {%0,%1,%2,%3,%4,%5,%6,%7,%8,%9,%10,%11,%12,%13,%14,%15}, {%16,%17,%18,%19}, db, 0, 1, 1, 0;}"
      : "=f"(d[0]), "=f"(d[1]), "=f"(d[2]), "=f"(d[3]), "=f"(d[4]), "=f"(d[5]), "=f"(d[6]), "=f"(d[7]), "=f"(d[8]), "=f"(d[9]), "=f"(d[10]), "=f"(d[11]), "=f"(d[12]), "=f"(d[13]), "=f"(d[14]), "=f"(d[15])
      : "r"(a[0]), "r"(a[1]), "r"(a[2]), "r"(a[3]), "r"(db), "n"(OFF));
}
template <int I> using IC = std::integral_constant<int, I>;
template <int I, int N, class F> __device__ __forceinline__ void sfor(F&& f) {
  if constexpr (I < N) { f(std::integral_constant<int, I>{}); sfor<I + 1, N>(f); }
}
__device__ __forceinline__ void keep(float (&d)[16]) {
  asm volatile("" : "+f"(d[0]), "+f"(d[1]), "+f"(d[2]), "+f"(d[3]), "+f"(d[4]), "+f"(d[5]), "+f"(d[6]), "+f"(d[7]),
      "+f"(d[8]), "+f"(d[9]), "+f"(d[10]), "+f"(d[11]), "+f"(d[12]), "+f"(d[13]), "+f"(d[14]), "+f"(d[15]) :: "memory");
}

template <int N, int S2 = 1024> __device__ __forceinline__ void ldx(uint32_t (&v)[N][4], const uint8_t* p) {
#pragma unroll
  for (int k = 0; k < 2 * N; k++) {
    const int i = k;
    asm volatile("ld.relaxed.gpu.global.v2.b32 {%0,%1}, [%2];" : "=r"(v[i >> 1][2 * (i & 1)]), "=r"(v[i >> 1][2 * (i & 1) + 1]) : "l"(p + (i & 3) * 256 + (i >> 2) * S2) : "memory");
  }
}
__device__ __forceinline__ uint32_t dif2(uint32_t a, uint32_t b, uint32_t tag) { uint32_t r; asm("lop3.b32 %0, %1, %2, %3, 0x7e;" : "=r"(r) : "r"(a), "r"(b), "r"(tag)); return r; }
__device__ __forceinline__ uint32_t dif2v(uint32_t a, uint32_t b, uint32_t tag) { uint32_t r; asm volatile("lop3.b32 %0, %1, %2, %3, 0x7e;" : "=r"(r) : "r"(a), "r"(b), "r"(tag)); return r; }
__device__ __forceinline__ uint32_t or3(uint32_t a, uint32_t b, uint32_t c) { uint32_t r; asm("lop3.b32 %0, %1, %2, %3, 0xfe;" : "=r"(r) : "r"(a), "r"(b), "r"(c)); return r; }
__device__ __forceinline__ uint32_t after(uint32_t x, float f, uint32_t z) { uint32_t r; asm("lop3.b32 %0, %1, %2, %3, 0xea;" : "=r"(r) : "r"(__float_as_uint(f)), "r"(z), "r"(x)); return r; }
__device__ __forceinline__ bool any_bit(uint32_t a, uint32_t b, uint32_t m) {
  uint32_t r; asm("lop3.b32 %0, %1, %2, %3, 0xa8;" : "=r"(r) : "r"(a), "r"(b), "r"(m)); return __any_sync(0xffffffffu, r); }
template <int W, int N> __device__ __forceinline__ bool stale(const uint32_t (&v)[N][4], uint32_t tag) {
  uint32_t x = dif2(v[0][0], v[0][2], tag);
  if (N == 4) x = or3(x, dif2(v[1][0], v[1][2], tag), dif2(v[2 % N][0], v[2 % N][2], tag));
  return any_bit(x, dif2(v[N - 1][0], v[N - 1][2], tag), 1);
}
template <int W, int N, int S2 = 1024> __device__ __forceinline__ void retry(uint32_t (&v)[N][4], const uint8_t* p, uint32_t tag, int& it) {
#pragma unroll 1
  do { ldx<N, S2>(v, p); it += INC_A; } while (stale<W>(v, tag) && it < SPIN_LIMIT);
}
__device__ __forceinline__ void mma_h(float (&d)[4], const uint32_t (&a)[4], const uint32_t (&b)[4], int hf) { mma16816(d, a[0], a[1], a[2], a[3], b[2 * hf], b[2 * hf + 1]); }
__device__ __forceinline__ void sts128(uint32_t a, const uint32_t (&r)[4]) { sts128(a, r[0], r[1], r[2], r[3]); }
__device__ __forceinline__ void sts128f(uint32_t a, const float* r) { sts128(a, __float_as_uint(r[0]), __float_as_uint(r[1]), __float_as_uint(r[2]), __float_as_uint(r[3])); }
__device__ __forceinline__ void mbar_spin(uint32_t bar, uint32_t par, int& it) {
  asm volatile("{.reg .pred p; .reg .b32 par; mov.b32 par, %2;\nLOOP: mbarrier.try_wait.parity.shared::cta.b64 p, [%1], par; @p bra.uni DONE;\n"
               "add.s32 %0, %0, 1; setp.le.s32 p, %0, %3; @p bra.uni LOOP;\nDONE: }" : "+r"(it) : "r"(bar), "r"(par), "n"(SPIN_LIMIT) : "memory"); }
__device__ __forceinline__ void warp_arrive(uint32_t bar) {
  __syncwarp(); asm volatile("{.reg .pred p; elect.sync _|p, 0xffffffff; @p mbarrier.arrive.shared::cta.b64 _, [%0];}" :: "r"(bar) : "memory"); }
__device__ __forceinline__ void delay_until(unsigned t) {
  asm volatile("{.reg .pred p; .reg .b64 c; .reg .b32 lo, hi;\nLOOP: mov.u64 c, %%clock64; mov.b64 {lo, hi}, c; sub.s32 lo, lo, %0; setp.lt.s32 p, lo, 0; @p bra.uni LOOP;}" :: "r"(t) : "memory"); }
__device__ __forceinline__ void cut(int it) { asm volatile("{.reg .pred p; setp.lt.s32 p, %0, 0;\nL: @p st.volatile.shared.u32 [%0], %0; @p bra.uni L;}" :: "r"(it) : "memory"); }
__device__ __forceinline__ void zero(float (&c)[4][4]) {
#pragma unroll
  for (int i = 0; i < 4; i++) c[i][0] = c[i][1] = c[i][2] = c[i][3] = 0.f;
}

__device__ __forceinline__ void sched() { asm volatile("griddepcontrol.launch_dependents;" ::: "memory"); }
__device__ __forceinline__ const uint8_t* pinp(const uint8_t* p) { return reinterpret_cast<const uint8_t*>(__shfl_xor_sync(0xffffffffu, reinterpret_cast<unsigned long long>(p), 0)); }
__device__ __forceinline__ uint32_t bar_or(int id, uint32_t x) {
  uint32_t r; asm volatile("{.reg .pred p, q; setp.ne.u32 p, %2, 0; bar.red.or.pred q, %1, 256, p; selp.u32 %0, 1, 0, q;}" : "=r"(r) : "r"(id), "r"(x) : "memory"); return r; }
__device__ __forceinline__ void bar_sync_unless(int id, uint32_t x) { asm volatile("{.reg .pred p; setp.eq.u32 p, %1, 0; @p bar.sync %0, 256;}" :: "r"(id), "r"((uint32_t)x) : "memory"); }
__device__ __forceinline__ void bar_arrive_unless(int id, uint32_t x) { asm volatile("{.reg .pred p; setp.eq.u32 p, %1, 0; @p bar.arrive %0, 256;}" :: "r"(id), "r"((uint32_t)x) : "memory"); }
__device__ __forceinline__ void stsm2t(uint32_t a, uint32_t r0, uint32_t r1, uint32_t x) {
  asm volatile("{.reg .pred p; setp.eq.u32 p, %3, 0; @p stmatrix.sync.aligned.m8n8.x2.trans.shared.b16 [%0], {%1,%2};}" :: "r"(a), "r"(r0), "r"(r1), "r"((uint32_t)x) : "memory"); }
__device__ __forceinline__ uint32_t or_and(uint32_t a, uint32_t b, uint32_t m) { uint32_t r; asm("lop3.b32 %0, %1, %2, %3, 0xa8;" : "=r"(r) : "r"(a), "r"(b), "r"(m)); return r; }
#define rare(x) __builtin_expect(!!(x), 0)
__device__ __forceinline__ uint32_t gtime() { unsigned long long g; asm volatile("mov.u64 %0, %%globaltimer;" : "=l"(g) :: "memory"); return (uint32_t)g; }
__device__ __forceinline__ void wait_time(uint32_t t) {
  asm volatile("{.reg .pred p; .reg .b32 g; .reg .b64 c;\nLOOP: mov.u64 c, %%globaltimer; cvt.u32.u64 g, c; sub.s32 g, %0, g; setp.lt.u32 p, g, 16384; @p bra.uni LOOP;}" :: "r"(t - 1) : "memory"); }
__device__ __forceinline__ uint32_t ldx32(const void* p) { uint32_t v; asm volatile("ld.relaxed.gpu.global.b32 %0, [%1];" : "=r"(v) : "l"(p) : "memory"); return v; }
__device__ __forceinline__ void stx32(const void* p, uint32_t v) { asm volatile("st.relaxed.gpu.global.b32 [%0], %1;" :: "l"(p), "r"(v) : "memory"); }

__global__ void __launch_bounds__(256, 1)
rec_kernel(const __grid_constant__ RecMaps maps, const bf16* __restrict__ xin, const bf16* __restrict__ mem0, Xchg* const gx) {
  extern __shared__ __align__(1024) uint8_t smem_raw[];
  const uint32_t sb = smem_u32(smem_raw);
  int role = blockIdx.x;
  {
    uint32_t smid, nsm; asm volatile("mov.u32 %0, %%smid;" : "=r"(smid)); asm volatile("mov.u32 %0, %%nsmid;" : "=r"(nsm));
    const int p = smid >> 1, u = p - 32;
    if (nsm == gridDim.x)
      role = (smid & 1) + (p < 32 ? 4 * ((p & 7) + 8 * (p >> 4)) + 2 * ((p >> 3) & 1) : p < 60 ? 4 * (16 + u % 7 + 7 * (u / 14)) + 2 * ((u / 7) & 1)
                         : p < 62 ? 2 * p + 8 : 2 * p - 4);
    role = uni(role);
  }
  if (role >= 128) {
    fft_cols(sb, role - 128, 4);
    grid_arrive(&gx->ctr[32]); grid_wait(&gx->ctr[32], 4);
    fft_rows_inv(&maps.fo, sb, role - 128, 4);
    return;
  }
  const int tid = threadIdx.x, warp = uni(tid >> 5), lane = tid & 31, wg = warp >> 2, w4 = warp & 3, g = lane >> 2, t = lane & 3;
  const int h = role >> 2, j = role & 3, jh = j & 1;
  uint32_t w[48][4];
  float aq[16], av[16];
  int it = 0;

  if (tid == 224) {
    mbar_init(sb + B_KV, 1); mbar_init(sb + B_W, 1); mbar_init(sb + B_X, 1); mbar_init(sb + B_X + 8, 1); mbar_init(sb + B_X + 16, 1); mbar_init(sb + B_X + 24, 1); mbar_init(sb + B_C, 4); mbar_init(sb + B_PK, 4); mbar_init(sb + B_B, 1);
    asm volatile("fence.mbarrier_init.release.cluster;" ::: "memory");
    mbar_expect_tx(sb + B_W, 3 * 65536);
    for (int i = 0; i < 4; i++) {
      tma2d(sb + R_X + i * 16384, &maps.wq, h * DH + 32 * j, i * 256, sb + B_W);
      tma2d(sb + R_MEM + i * 16384, &maps.wk, h * DH + 32 * j, i * 256, sb + B_W);
    }
    for (int i = 0; i < 2; i++) tma2d(sb + R_WO + i * 32768, &maps.wv, h * DH + 64 * (j >> 1), jh * 512 + i * 256, sb + B_W);
    if (PFD) asm volatile("cp.async.bulk.prefetch.L2.global [%0], 2048;" :: "l"(xin + role * DM) : "memory");
    else for (int i = 0; i < 4; i++) asm volatile("cp.async.bulk.prefetch.L2.global [%0], 8192;" :: "l"(xin + role * 16384 + i * 4096) : "memory");
    for (int i = 0; i < 4; i++)
      asm volatile("cp.async.bulk.prefetch.tensor.2d.L2.global [%0, {%1, %2}];" :: "l"(&maps.wo), "r"(256 * j + 64 * i), "r"(h * DH) : "memory");
  }
  if (tid < 128) asm volatile("prefetch.global.L2 [%0];" :: "l"(mem0 + tid * 64));
  if (tid < 16) sts32(sb + R_T + tid * 4, ~0u);
  __syncthreads();
  uint8_t* const xb = reinterpret_cast<uint8_t*>(gx);
  auto probe_at = [&](int n) { return xb + (n ? offsetof(Xchg, C) + w4 * 8192 + role * 32 : offsetof(Xchg, B) + role * 8192 + warp * 128); };
  if (lane < 8) stx128(probe_at(lane >> 2) + (lane & 2) * 2048 + (lane & 1) * 16, 0, 0, 0, 0);
  mbar_spin(sb + B_W, 0, it);
  const int lrow = (lane & 7) + ((lane >> 4) << 3), lhi = (lane >> 3) & 1;
  const int kq = wg ? 3 - 3 * jh : 3 * jh;
  const uint32_t LW = lrow * 128 + ((lhi ^ (lane & 7)) << 4);
  {
    const int chunk = w4 < 2 ? w4 + 2 * lhi : 2 * (w4 & 1) + lhi;
    uint32_t a = sb + (w4 < 2 ? R_X : R_MEM) + kq * 16384 + lrow * 64 + ((chunk ^ ((lrow >> 1) & 3)) << 4);
#pragma unroll
    for (int i = 0; i < 16; i++) ldsm4t(w[i], a + i * 1024);
    const uint32_t st = wg ? 1024 : 2048, av0 = sb + R_WO + (LW ^ (w4 << 5));
    const uint32_t a1 = wg ? a + (2 * jh - 1) * 16384 : av0 + jh * 32768, a2 = wg ? a + (2 * jh - 1) * 32768 : av0 + (1 - jh) * 32768;
#pragma unroll
    for (int i = 0; i < 16; i++) { ldsm4t(w[16 + i], a1 + i * st); ldsm4t(w[32 + i], a2 + i * st); }
  }
  uint32_t L16 = pin(lane * 16);
  const uint32_t uW = uni(sb + w4 * 512), uWo = uni(sb + R_WO + w4 * 16384), uMem = uni(sb + R_MEM + kq * 4096);
  const uint32_t dX = uni(((sb + R_X + kq * 16384) >> 4) | 0x10000u);
  auto load_wo = [&](uint32_t (&d)[32][4], int i0, int i1) {
#pragma unroll
    for (int i = i0; i < i1; i++) lds128(d[i], uWo + L16 + (i & 1) * 512 + (i >> 4) * 1024 + (i & 14) * 1024);
  };
  auto issue_x = [&](int n, int k) {
    const uint32_t bar = sb + B_X + 8 * k, q = k ^ (3 - 3 * jh);
    mbar_expect_tx(bar, 16384); tma3d(sb + R_X + q * 16384, &maps.x, n * SEG, 4 * q, bar);
  };
  auto store_stage = [&](int n) {
    asm volatile("cp.async.bulk.global.shared::cta.bulk_group [%0], [%1], 8192; cp.async.bulk.commit_group;"
                 :: "l"(g_kqv[n & 3][role]), "r"(sb + R_STAGE) : "memory");
  };
  auto issue_kqv = [&](int n) {
    const int p = (n & 3) * 128 + 4 * h;
    mbar_expect_tx(sb + B_KV, 26624);
    tma3d(sb + R_K, &maps.k, 0, p, sb + B_KV); tma3d(sb + R_Q, &maps.q, 8 + 2 * j, p, sb + B_KV); tma3d(sb + R_V, &maps.v, 16, p, sb + B_KV);
  };
  auto fetch4k = [&](uint32_t dst, uint32_t off, uint32_t bar, uint32_t t) {
    asm volatile("{.reg .pred p, q; .reg .b32 g; .reg .b64 c; elect.sync _|q, 0xffffffff; @q mbarrier.arrive.expect_tx.shared::cta.b64 _, [%2], 4096;\n"
                 "LOOP: mov.u64 c, %%globaltimer; cvt.u32.u64 g, c; sub.s32 g, %3, g; setp.lt.u32 p, g, 16384; @p bra.uni LOOP;\n"
                 "@q cp.async.bulk.shared::cluster.global.mbarrier::complete_tx::bytes [%0], [%1], 4096, [%2];}" :: "r"(dst), "l"(xb + off), "r"(bar), "r"(t - 1) : "memory");
  };
  uint32_t uS;
  auto my_b = [&]() { return offsetof(Xchg, B) + role * 8192 + ((uS + ((uint32_t)it >> 31)) & 1) * 4096; };
  auto issue_c = [&](uint32_t t) { fetch4k(sb + R_MEM + w4 * 4096, offsetof(Xchg, C) + w4 * 8192 + ((uS + ((uint32_t)it >> 31)) & 4096), sb + B_C, t); };
  auto wait_x = [&](int n, int i) { if (!(EXP & 1) || n < 2) mbar_spin(sb + B_X + 8 * i, n & 1, it); };
#define PACED(d0) uint32_t dz = d0; const uint32_t z = (uint32_t)it >> 31; auto pace = [&]() { for (int k = 0; k < PACE; k++) { if (k & 1) asm("add.u32 %0, %0, %1;" : "+r"(dz) : "r"(z)); else asm("xor.b32 %0, %0, %1;" : "+r"(dz) : "r"(z)); } };
  auto project_v = [&](auto I0, auto I1, auto&& mid) {
    PACED(decltype(I0)::value < 16 ? dX : dX ^ 1024);
    wg_fence();
    sfor<decltype(I0)::value, decltype(I1)::value>([&](auto I) {
      constexpr int i = decltype(I)::value;
      mid(i);
      if (i == 16 && decltype(I0)::value < 16) dz ^= 1024;
      wg_rs32<((i >> 2) & 3) * 256 + (i & 3) * 2, (i > 0)>(av, w[16 + i], dz);
      pace();
    });
    wg_commit();
  };
  auto project_qk = [&](auto I0, auto I1, auto first, auto&& mid) {
    PACED((dX ^ (decltype(I0)::value >> 4 << 10)) + ((uint32_t)it >> 31));
    wg_fence();
    sfor<decltype(I0)::value, decltype(I1)::value>([&](auto I) {
      constexpr int i = decltype(I)::value;
      mid(i);
      wg_rs32<((i >> 2) & 3) * 256 + (i & 3) * 2, !decltype(first)::value || i != decltype(I0)::value>(aq, w[i], dz);
      pace();
    });
    wg_commit();
  };
  const uint32_t uP = uni(sb + R_X + 3 * jh * 16384 + w4 * 512);
  auto park = [&]() {
    bar_sync(1, 128);
#pragma unroll
    for (int i = 0; i < 4; i++) sts128f(uP + L16 + i * 2048, aq + 4 * i);
    warp_arrive(sb + B_PK);
  };
  auto unpark = [&]() {
#pragma unroll
    for (int i = 0; i < 4; i++) {
      const float4 p = lds128f(uP + L16 + i * 2048);
      av[4 * i] = p.x; av[4 * i + 1] = p.y; av[4 * i + 2] = p.z; av[4 * i + 3] = p.w;
    }
  };
  auto fin_qk = [&]() {
#pragma unroll
    for (int i = 0; i < 16; i++) aq[i] += av[i];
    const uint32_t a = sb + R_STAGE + (w4 < 2 ? 2048 + w4 * 128 : (w4 & 1) * 256) + (L16 & 112) + (L16 >> 7) * 512;
    stsm4t(a, pack2(aq[0], aq[1]), pack2(aq[4], aq[5]), pack2(aq[8], aq[9]), pack2(aq[12], aq[13]));
    stsm4t(a + (w4 < 2 ? 256 : 128), pack2(aq[2], aq[3]), pack2(aq[6], aq[7]), pack2(aq[10], aq[11]), pack2(aq[14], aq[15]));
  };
  auto fin_v = [&]() {
#pragma unroll
    for (int a = 0; a < 2; a++)
      sts128(sb + R_STAGE + 4096 + w4 * 1024 + a * 512 + L16, pack2(av[8 * a], av[8 * a + 1]), pack2(av[8 * a + 2], av[8 * a + 3]),
             pack2(av[8 * a + 4], av[8 * a + 5]), pack2(av[8 * a + 6], av[8 * a + 7]));
  };
  __syncthreads();
  if (tid == 224) {
#pragma unroll 1
    for (int i = 0; i < 4; i++) issue_x(0, i);
    mbar_expect_tx(sb + B_W, 65536);
    for (int i = 0; i < 4; i++) tma2d(sb + R_WO + i * 16384, &maps.wo, 256 * j + 64 * i, h * DH, sb + B_W);
  }
  __syncwarp();
  if (wg) {
#pragma unroll
    for (int i = 0; i < NSW; i++) sts128(uW + R_WC + L16 + i * 2048, w[i]);
  }
#pragma unroll
  for (int i = 0; i < 4; i++) {
    const uint32_t* p = reinterpret_cast<const uint32_t*>(mem0 + g * DM + 128 * warp + 32 * i + 2 * t);
    sts128(sb + R_MEM + warp * 2048 + i * 512 + (g >> 1) * 128 + t * 32 + (g & 1) * 16, __ldg(p), __ldg(p + 4), __ldg(p + 8), __ldg(p + 12));
  }
#pragma unroll 1
  for (int n = 0; n < 2; n++) {
    if (lane == 0) {
#pragma unroll 1
      for (int i = role >> 7; i < 2 * NPROBE; i++) {
        const int k = (i ^ wg) & 1;
        const unsigned t0 = clk();
        uint32_t v; asm volatile("atom.relaxed.gpu.global.exch.b32 %0, [%1], 0;" : "=r"(v) : "l"(probe_at(n) + k * 4096) : "memory");
        if (v == 0) asm volatile("red.shared.min.u32 [%0], %1;" :: "r"(sb + R_T + (n ? w4 * 8 : 32) + k * 4), "r"(clk() - t0) : "memory");
      }
    }
    __syncwarp();
    wait_x(n, 2);
    if (wg == 0) {
      wait_x(n, 3);
      project_qk(IC<0>{}, IC<16>{}, IC<1>{}, [](int) {});
      project_v(IC<0>{}, IC<32>{}, [](int) {});
      if (tid == 96 && n == 1) {
        asm volatile("cp.async.bulk.wait_group 0;" ::: "memory");
        __threadfence(); atomicAdd(&gx->ctr[h], 1u);
      }
      __syncwarp();
      wg_wait<0>(); keep(aq); keep(av);
      park();
      fin_v();
      fence_async();
    } else {
      wait_x(n, 0); wait_x(n, 1);
      project_qk(IC<32>{}, IC<48>{}, IC<1>{}, [](int) {});
      project_qk(IC<16>{}, IC<32>{}, IC<0>{}, [](int) {});
      project_qk(IC<0>{}, IC<16>{}, IC<0>{}, [](int) {});
      mbar_spin(sb + B_PK, n, it);
      unpark();
      wg_wait<0>(); keep(aq);
      fin_qk();
      fence_async();
      if (tid == 128 && n == 1) {
        for (int k = 0; *reinterpret_cast<volatile unsigned*>(&gx->ctr[h]) < 4 && k < SPIN_LIMIT; k++) {}
        __threadfence(); asm volatile("fence.proxy.async;" ::: "memory");
        issue_kqv(0);
      }
    }
    __syncthreads();
    uS = uni((HOME & 1 ? lds32(sb + R_T + w4 * 8 + 4) < lds32(sb + R_T + w4 * 8) : j >> 1) * 4096 + (HOME & 2 && lds32(sb + R_T + 36) < lds32(sb + R_T + 32)));
    if (tid == 0) stx32(&gx->S[role], 1 + (uS & 1));
    if (tid == 96 && n == 0) store_stage(0);
    if (tid == 128 && n == 0) {
#pragma unroll 1
      for (int i = 0; i < 4; i++) issue_x(1, i);
    }
    __syncwarp();
  }
  mbar_spin(sb + B_W, 1, it);
#pragma unroll
  for (int i = 0; i < 4; i++) {
    uint32_t f[4][4];
    const uint32_t a = sb + R_WO + warp * 8192 + i * 2048;
#pragma unroll
    for (int q = 0; q < 4; q++) ldsm4t(f[q], a + (LW ^ (q << 5)));
    __syncwarp();
#pragma unroll
    for (int q = 0; q < 4; q++) sts128(a + q * 512 + L16, f[q]);
  }
  {
    const int o = 32 * w4 + 16 * wg + 4 * t + j;
    uint32_t v;
#pragma unroll 1
    while (__any_sync(0xffffffffu, (v = ldx32(&gx->S[o])) == 0) && ++it < SPIN_LIMIT) {}
    asm volatile("st.shared.u64 [%0], %1;" :: "r"(sb + R_DST + wg * 1024 + w4 * 256 + lane * 8), "l"(xb + offsetof(Xchg, B) + o * 8192 + (v >> 1) * 4096 + h * 128 + ((g ^ h) & 7) * 16) : "memory");
  }
  if (wg == 0) {
    const uint64_t cd = reinterpret_cast<uint64_t>(xb + (offsetof(Xchg, C) + j * 8192 + h * 128 + w4 * 32 + (L16 & 16) * 256 + (L16 & 64) / 4 + (L16 >> 7) * 4));
    sts128(uW + R_RD + L16, (uint32_t)cd, (uint32_t)(cd >> 32), sb + R_MEM + (L16 & 112) * 8 + (L16 >> 8) * 1024 + ((w4 * 32 + ((L16 >> 3) & 16)) ^ (L16 & 112)),
           (L16 >> 6) == (h & 3) * 2 + ((h >> 2) & 1) ? 0xFFFE0000u : 0xFFFFFFFFu);
  }
  mbar_spin(sb + B_KV, 0, it);
  if (tid == 0) sts32(sb + B_DUE + 8, gtime() & ~31u);
  if (tid < 4) sts32(sb + B_ONE + tid * 4, 0x3F803F80u);
  if (warp == 1) { const uint32_t e = g >> 1 == t ? 0x3F80u << (16 * (g & 1)) : 0u; sts128(sb + R_ID + L16, e, 0, 0, e); }
  __syncthreads();

  const float sc = 0.08838834764831845f * 1.4426950408889634f;
  uint8_t* const xa = xb + uni(h * 16384);
  const uint32_t uA = uni(wg ? (w4 >> 1) * 2048 + j * 512 + (w4 & 1) * 256 : 8192 + (4 * (j >> 1) + w4) * 512 + jh * 256);
  const uint32_t uP2 = uni(sb + R_P + w4 * 256);
  uint32_t nc = 1;
  uint32_t ma;
  const uint8_t* adst;
  auto pin_mem = [&]() { adst = pinp(xa + uA + L16 / 2); ma = pin(uMem + (L16 & 384) + (L16 & 48) * 2 + (L16 & 64) / 4); };
  pin_mem();

#pragma unroll 1
  for (int s = 0;; nc++) {
    const uint32_t tag = (s + 1) & 1;
    auto fresh = [&]() { L16 += (uint32_t)it >> 31; };
    auto get_due = [&]() { return lds32(sb + B_DUE + 4 + tag * 4); };
    float c[4][4], r4[4];
    auto fold = [&]() {
#pragma unroll
      for (int i = 0; i < 4; i++) r4[i] = ((c[0][i] + c[1][i]) + c[2][i]) + c[3][i];
    };
    auto mma4 = [&](int n, const uint32_t (&b0)[4], const uint32_t (&b1)[4]) {
      mma_h(c[0], w[n + 2], b1, 0); mma_h(c[1], w[n + 3], b1, 1); mma_h(c[2], w[n], b0, 0); mma_h(c[3], w[n + 1], b0, 1);
    };
    auto xpos = [&](int pos, int wp) {
      if ((pos == X0 || pos == X1 || pos == X2 || pos == X3) && warp == wp && s + 1 < NSEG && elect()) {
        const int z = (uint32_t)it >> 31;
        if (pos == X2) issue_x(s + 2, 2 + z);
        if (pos == X3) issue_x(s + 2, 3 + z);
        if (pos == X1) issue_x(s + 2, 1 + z);
        if (pos == X0) issue_x(s + 2, z);
      }
      __syncwarp();
    };
    if (wg == 0) {
      mbar_spin(sb + B_C, nc & 1, it);
      TS(13);
      uint32_t b[16][4], tg[4];
#pragma unroll
      for (int i = 0; i < PD0; i++) { lds128(b[i], ma + i * 512); __syncwarp(); }
      sched();
      zero(c);
#pragma unroll
      for (int i = 0; i < 8; i++) {
        const int k = i ^ 1;
        mma_h(c[0], w[2 * k], b[k], 0); mma_h(c[1], w[2 * k + 1], b[k], 1);
        if (i < 2 * NV0) { mma_h(c[2], w[16 + 2 * k], b[k], 0); mma_h(c[3], w[17 + 2 * k], b[k], 1); }
        sched();
        if ((i & 1) && i + PD0 < 9) { lds128(b[i + PD0 - 1], ma + (i + PD0 - 1) * 512); __syncwarp(); lds128(b[i + PD0], ma + (i + PD0) * 512); sched(); }
        if (i == TGP) {
          fresh();
#pragma unroll
          for (int k = 0; k < 4; k++) tg[k] = lds32((uW * 4 + L16) * 2 + (L16 >> 6) * 4 + (R_MEM + k * 1024 - 7 * sb));
          sched();
        }
      }
#pragma unroll
      for (int i = 0; i < 4; i++) { r4[i] = c[0][i] + c[1][i]; c[0][i] = c[1][i] = 0.f; }
      sts128f(uW + R_RED + L16, r4);
      TS(1);
      const uint32_t old = bar_or(4, (dif2(tg[0], tg[1], s) | dif2(tg[2], tg[3], s)) & (s > 0));
      TS(0);
#pragma unroll
      for (int i = 0; i < 2 * NV0; i++) { lds128(b[8 + i], (ma ^ 4096) + i * 512); __syncwarp(); }
      sched();
#pragma unroll
      for (int i = NV0; i < 8; i++) {
        if (VB && i == VB) bar_sync(7, 256);
        mma4(16 + 4 * i, b[2 * i], b[2 * i + 1]);
        if (i < 7) sched();
        if (i < 4) { lds128(b[8 + 2 * i], (ma ^ 4096) + i * 1024); __syncwarp(); lds128(b[9 + 2 * i], (ma ^ 4096) + i * 1024 + 512); sched(); }
      }
      fold();
      asm volatile("{.reg .pred p; setp.eq.u32 p, %3, 0; @p st.relaxed.gpu.global.v2.b32 [%0], {%1,%2};}" :: "l"(adst), "r"((pack2(r4[0], r4[1]) & ~1u) | tag), "r"(pack2(r4[2], r4[3])), "r"(old) : "memory");
      sched();
      const unsigned tpub = clk();
      if (__any_sync(0xffffffffu, old) && nc < NC_MAX) {
        bar_sync(3, 256);
        issue_c(gtime());
        continue;
      }
      TS(3);
      xpos(0, 0);
      const uint32_t due = get_due();
      uint32_t vf[4][4], vm[2][4], p[4], pm, o[4];
      const uint32_t va = sb + R_V + (w4 >> 1) * 8192 + (w4 & 1) * 2048 + L16;
#pragma unroll
      for (int i = 0; i < 4; i++) {
        uint32_t q[4]; lds128(vf[i], va + i * 512); lds128(q, va + 4096 + i * 512);
#pragma unroll
        for (int e = 0; e < 4; e++) vf[i][e] = hadd2(vf[i][e], q[e]);
      }
      const uint32_t pa = pin(sb + R_P + (L16 >> 1));
      const uint8_t* vsrc = pinp(xa + 8192 + w4 * 1024 + L16 / 2);
      uint32_t one[4];
      lds128(one, sb + B_ONE);
      auto pv_x = [&]() {
        zero(c);
        mma_a(c[2], one, p[0], p[1]);
        mma_a(c[0], vf[0], p[0], p[1]); mma_a(c[1], vf[2], p[0], p[1]);
        sched();
        mma_a(c[2], one, p[2], p[3]);
        mma_a(c[0], vf[1], p[2], p[3]); mma_a(c[1], vf[3], p[2], p[3]);
        sched();
      };
      auto pv_m = [&]() {
        mma1688(c[2], one[0], one[1], pm);
        mma_a(c[0], vm[0], pm, pm);
        sched();
        mma_a(c[1], vm[1], pm, pm);
      };
      auto norm = [&]() {
        const float n0 = rcp(c[2][0]), n1 = rcp(c[2][1]);
#pragma unroll
        for (int i = 0; i < 4; i++) o[i] = pack2(c[i >> 1][2 * (i & 1)] * n0, c[i >> 1][2 * (i & 1) + 1] * n1);
        return ((__float_as_uint(c[2][0]) - 0x1F800000u) | (__float_as_uint(c[2][1]) - 0x1F800000u)) >> 30;
      };
      auto load_m = [&](int x) { const float2 e0 = lds64f(pa + 512 + x * 1024), e1 = lds64f(pa + 768 + x * 1024); pm = pack2(e0.x * e1.x, e0.y * e1.y); };
      auto attend_max = [&](int x) {
        float2 sv[6];
#pragma unroll
        for (int i = 0; i < 6; i++) sv[i] = lds64f(pa - 3072 + x * 1536 + i * 256);
        sv[4].x += sv[5].x; sv[4].y += sv[5].y;
        const int dq = (int)(L16 >> 6) - (int)((L16 >> 3) & 6) + 8 * j;
        float m = fmaxf(sv[4].x, sv[4].y);
#pragma unroll
        for (int i = 0; i < 4; i++) {
          if (x && 8 * i > dq) sv[i].x = -INFINITY;
          if (x && 8 * i + 1 > dq) sv[i].y = -INFINITY;
          m = fmaxf(m, fmaxf(sv[i].x, sv[i].y));
        }
        m = fmaxf(m, __shfl_xor_sync(0xffffffffu, m, 1));
        m = fmaxf(m, __shfl_xor_sync(0xffffffffu, m, 2));
#pragma unroll
        for (int i = 0; i < 5; i++) (i < 4 ? p[i] : pm) = pack2(ex2(sv[i].x - m), ex2(sv[i].y - m));
        pv_x(); pv_m(); norm();
      };
      uint32_t tq[4];
      auto get_t = [&]() {
        tq[0] = tq[1] = tq[2] = tq[3] = 0;
        asm volatile("{.reg .pred p; setp.eq.u32 p, %5, 0; @p ld.relaxed.gpu.global.v4.b32 {%0,%1,%2,%3}, [%4];}"
                     : "+r"(tq[0]), "+r"(tq[1]), "+r"(tq[2]), "+r"(tq[3]) : "l"(xb + offsetof(Xchg, T) + L16 * 8), "r"(warp) : "memory");
      };
      delay_until(tpub + DLY_V);
      wait_time(due + NS_V);
      TS(4);
      ldx(vm, vsrc);
      sched();
      xpos(2, 2);
      auto store_kqv = [&]() {
        fence_async();
        if (!(EXP & 4))
          asm volatile("{.reg .pred p; elect.sync _|p, 0xffffffff; @p cp.async.bulk.global.shared::cta.bulk_group [%0], [%1], 2048; cp.async.bulk.commit_group;}"
                       :: "l"(g_kqv[(s + 1) & 3][role] + w4 * 128), "r"(sb + R_STAGE + w4 * 2048) : "memory");
      };
      if (SPOS == 2) store_kqv();
      sched();
      bar_sync(5, 256);
      ldsm4(p, sb + R_P + L16);
      load_m(0);
      pv_x();
      ldsm4(p, sb + R_P + 1024 + L16);
      pv_m();
      const uint32_t r = norm(), tl = after(tag, c[2][0], (uint32_t)it >> 31);
      const bool redo = __any_sync(0xffffffffu, r | ((dif2(vm[0][0], vm[0][2], tl) | dif2(vm[1][0], vm[1][2], tl)) & 1));
      TS(6);
      stsm4t(uW + R_O + L16, o[0], o[1], o[2], o[3]);
      bar_arrive_unless(6, redo);
      sched();
      if (TQL == 7) get_t();
      TS(7);
      pv_x();
      if (rare(redo)) retry<2>(vm, vsrc, tag, it);
      bar_sync(8, 256);
      load_m(1);
      pv_m();
      if (rare(__any_sync(0xffffffffu, norm()) || redo)) {
        fresh();
#pragma unroll 1
        for (int x = !redo; x < 2; x++) {
          attend_max(x);
          if (x == 0) { stsm4t(uW + R_O + L16, o[0], o[1], o[2], o[3]); bar_arrive(6, 256); }
        }
      }
      TS(8);
      if (TQL == 8) get_t();
      const bool xok = mbar_test(sb + B_X + 16, s & 1) & mbar_test(sb + B_X + 24, s & 1);
      xpos(4, 2);
      fresh();
      const uint32_t ob = uni(sb + R_MEM + 4096 + w4 * 1024);
      stsm4t(ob + (L16 & 112) * 4 + (((L16 >> 3) ^ (L16 >> 1)) & 48), o[0], o[1], o[2], o[3]);
      __syncwarp();
      uint32_t rd[4];
      lds128(rd, uW + R_RD + L16);
      lds128(o, ob + (L16 ^ ((L16 >> 3) & 48)));
      auto put_o = [&]() {
        *reinterpret_cast<uint4*>(reinterpret_cast<uint8_t*>(g_ox) + (((s * SEG + 8 * j) * HD + h * DH + 32 * w4) * 2 + (L16 >> 6) * (HD * 2) + (L16 & 48))) = make_uint4(o[0], o[1], o[2], o[3]);
      };
      if (s + 1 == NSEG) { put_o(); asm volatile("cp.async.bulk.wait_group 0;" ::: "memory"); break; }
      asm volatile("cp.async.bulk.wait_group 0;" ::: "memory");
      if (elect()) stx32(xa + 4096 + j * 16 + w4 * 4, s + 1);
      __syncwarp();
      if (rare(!xok)) { wait_x(s + 2, 3); wait_x(s + 2, 2); }
      TS(9);
      fresh();
      const uint32_t e = due | ((s + 1) & 31);
      project_qk(IC<0>{}, IC<NQ>{}, IC<1>{}, [&](int n) {
        if (n == OXPOS) { __syncwarp(); put_o(); __syncwarp(); }
        if (n == TQP) { __syncwarp(); tq[0] = dif2v(tq[0], tq[1], e) | dif2v(tq[2], tq[3], e); __syncwarp(); }
      });
      if (NPA) project_v(IC<0>{}, IC<NPA>{}, [](int) {});
      TS(2);
      if (warp == 0) {
        uint32_t last = due, nx = NS_P;
        if (rare(__any_sync(0xffffffffu, tq[0]))) {
          const uint32_t ref = gtime();
#pragma unroll 1
          do ldx128(o, xb + offsetof(Xchg, T) + L16 * 8); while (any_bit(or3(o[0] - s - 1, o[1] - s - 1, o[2] - s - 1), o[3] - s - 1, 30) && ++it < SPIN_LIMIT);
          const int d = max(max((int)(o[0] - ref), (int)(o[1] - ref)), max((int)(o[2] - ref), (int)(o[3] - ref)));
          last = (ref + __reduce_max_sync(0xffffffffu, d)) & ~31u;
          if (last != due) nx += NS_X;
        }
        sts32(sb + B_DUE, last);
        sts32(sb + B_DUE + 8 - tag * 4, last + nx);
        fetch4k(sb + R_MEM, my_b(), sb + B_B, last + NS_B);
        LOG(13, tl - last);
        LOG(9, last);
      }
      if (NQ < 16) project_qk(IC<NQ>{}, IC<16>{}, IC<0>{}, [](int) {});
      project_v(IC<NPA>{}, IC<NPRE>{}, [](int) {});
      const uint32_t ba = rd[2], msk = rd[3];
      const uint8_t* cdst = reinterpret_cast<const uint8_t*>(rd[0] | (uint64_t)rd[1] << 32);
      TS(14);
      mbar_spin(sb + B_B, s & 1, it);
      TS(10);
      uint32_t bq[2][4];
      auto sum_b = [&]() {
        ldsm4t(bq[0], ba); ldsm4t(bq[1], ba + 2048);
        sched();
#pragma unroll
        for (int i = 0; i < 8; i++) c[i >> 2][i & 3] = 0.f;
        mma_a(c[0], bq[0], 0x3F803F80u, 0x3F803F80u); mma_a(c[1], bq[1], 0x3F803F80u, 0x3F803F80u);
        const uint32_t t2 = tag * 0x10001u;
        const bool old = any_bit(or3(dif2(bq[0][0], bq[0][1], t2), dif2(bq[0][2], bq[0][3], t2), dif2(bq[1][0], bq[1][1], t2)), dif2(bq[1][2], bq[1][3], t2), L16 < 64 ? 0x10001u : 0u);
        const uint32_t T = (tag << 16) & ~msk, u = ((__float_as_uint(c[0][0] + c[1][0]) + ((0x10000u & ~msk) - T)) & msk) | T;
        asm volatile("{.reg .pred p; setp.eq.u32 p, %2, 0; @p st.relaxed.gpu.global.b32 [%0], %1;}"
                     :: "l"(cdst), "r"(pack2(__uint_as_float(u), c[0][2] + c[1][2])), "r"((uint32_t)(old || (L16 & 32))) : "memory");
        return old;
      };
      if (rare(sum_b())) {
#pragma unroll 1
        do {
          const uint8_t* p = xb + (my_b() + (ba - sb - R_MEM));
          ldx128(bq[0], p); ldx128(bq[1], p + 2048);
          sts128(ba, bq[0]); sts128(ba + 2048, bq[1]);
          __syncwarp();
          it += INC_B;
        } while (sum_b() && it < SPIN_LIMIT);
      }
      sched();
      TS(11);
      bar_arrive(0, 256);
      const unsigned tc = clk();
      const uint32_t cdue = lds32(sb + B_DUE) + NS_C;
      if (warp == 3) LOG(11, gtime() - cdue);
      fresh();
      wg_wait<0>(); keep(aq); keep(av);
      park();
      if (NPRE < 32) project_v(IC<NPRE>{}, IC<32>{}, [](int) {}); else fin_v();
      TS(12);
      delay_until(tc + DLY_C);
      issue_c(cdue);
      TS(5);
      LOG(warp, it);
      pin_mem();
      if (NPRE < 32) { wg_wait<0>(); keep(av); fin_v(); }
      if (!(EXP & 2)) mbar_spin(sb + B_KV, tag, it);
      TS(15);
    } else {
      uint32_t kf[8][4];
      auto load_k = [&]() {
        const uint32_t ka = sb + R_K + w4 * 1024 + (L16 & 112) + (L16 & 128) * 4 + (L16 & 256);
#pragma unroll
        for (int i = 0; i < 8; i++) ldsm4(kf[i], ka + (i >> 1) * 2048 + (i & 1) * 128);
      };
      auto put_p = [&](int x, uint32_t old, uint32_t again) {
        float e[4];
        const int dq = (int)((L16 >> 3) & 6) + 8 * j - (int)(L16 >> 6) - 16 * w4;
#pragma unroll
        for (int i = 0; i < 4; i++) { r4[i] = fmaf(c[3][i], sc, fmaf(c[2][i], sc, fmaf(c[0][i] + c[1][i], sc, __uint_as_float(i == 3 ? 0u - old : 0u)))); e[i] = x && dq + (i & 1) < 8 * (i >> 1) ? 0.f : ex2(r4[i]); }
        stsm2t(uP2 + x * 1024 + L16, pack2(e[0], e[1]), pack2(e[2], e[3]), again);
      };
      auto put_s = [&](int x) {
#pragma unroll
        for (int i = 0; i < 4; i++) sts32f(uW + R_S + x * 1536 + (L16 & 48) * 4 + (L16 >> 6) * 4 + (i & 1) * 32 + (i >> 1) * 256, r4[i]);
      };
      auto load_q = [&](uint32_t (&q)[4], uint32_t off) { ldsm4(q, sb + R_Q + (L16 & 112) + (L16 & 128) * 2 + (L16 >> 8) * 128 + off); };
      mbar_spin(sb + B_C, nc & 1, it);
      TS(13);
      float4 o4;
      uint32_t id[4], old;
      {
        uint32_t b[24][4];
#pragma unroll
        for (int i = 0; i < 2 * PD1; i++) { lds128(b[i], ma + i * 512); __syncwarp(); }
        sched();
        zero(c);
#pragma unroll
        for (int i = 0; i < 12; i++) {
          mma4(4 * i, b[2 * i], b[2 * i + 1]);
          if (i < 11) sched();
          if (i + PD1 < 12) { const int k = i + PD1; const uint32_t a = (ma ^ (k >> 2 << 12)) + (k & 3) * 1024; lds128(b[2 * k], a); __syncwarp(); lds128(b[2 * k + 1], a + 512); sched(); }
          if (i == RJ) { lds128(id, sb + R_ID + L16); sched(); }
          if (i == RI) { old = bar_or(4, 0); o4 = lds128f(uW + R_RED + L16); sched(); }
        }
      }
      TS(0);
      {
        float e[4] = {o4.x, o4.y, o4.z, o4.w};
#pragma unroll
        for (int i = 0; i < 4; i++) { r4[i] = (((e[i] + c[0][i]) + c[1][i]) + c[2][i]) + c[3][i]; e[i] = 0.f; }
        mma_a(e, id, pack2(r4[0], r4[1]), pack2(r4[2], r4[3]));
        sched();
        if (VB) bar_arrive(7, 256);
        sched();
        asm volatile("{.reg .pred p; setp.eq.u32 p, %3, 0; @p st.relaxed.gpu.global.v2.b32 [%0], {%1,%2};}" :: "l"(adst),
                     "r"((__byte_perm(__float_as_uint(e[0]), __float_as_uint(e[1]), 0x7632) & ~1u) | tag), "r"(__byte_perm(__float_as_uint(e[2]), __float_as_uint(e[3]), 0x7632)), "r"(old) : "memory");
        sched();
      }
      const unsigned tpub = clk(), now = gtime(), due = get_due();
      if (__any_sync(0xffffffffu, old) && nc < NC_MAX) { bar_sync(3, 256); continue; }
      TS(2);
      const uint8_t* asrc = pinp(adst + ((warp == 7) * 1024 - (int)uA));
      fresh();
      uint32_t wo[32][4];
      bool xok;
      auto reload = [&]() {
        sched();
#pragma unroll
        for (int i = RE0 + RE1; i < NSW; i++) lds128(w[i], uW + R_WC + L16 + i * 2048);
        sched();
      };
      auto out_proj = [&]() {
        uint32_t b[4][4];
        float d[4][4];
        uint8_t* dst[2];
        const uint32_t da = pin(uP2 + (R_DST - R_P) + L16 / 2);
        sched();
        TS(7);
        bar_sync(6, 256);
#pragma unroll
        for (int i = 0; i < 4; i++) { ldsm4(b[i], sb + R_O + i * 512 + L16); __syncwarp(); }
        sched();
        auto put_b = [&](uint8_t* a, const float (&e)[4][4]) {
          stx128(a, (pack2(e[0][0] + e[2][0], e[0][1] + e[2][1]) & ~1u) | tag, pack2(e[0][2] + e[2][2], e[0][3] + e[2][3]),
                 pack2(e[1][0] + e[3][0], e[1][1] + e[3][1]), pack2(e[1][2] + e[3][2], e[1][3] + e[3][3]));
        };
        zero(c); zero(d);
#pragma unroll
        for (int i = 0; i < 32; i++) {
          mma_h(i < 16 ? c[i & 3] : d[i & 3], wo[i], b[(i >> 2) & 3], (i >> 1) & 1);
          if (i >= LW0 && NB1 + i - LW0 < 32) { load_wo(wo, (NB1 + i - LW0) ^ 1, ((NB1 + i - LW0) ^ 1) + 1); __syncwarp(); }
          if (i == DL0 || i == DL1) asm volatile("ld.shared.u64 %0, [%1];" : "=l"(dst[i > DL0]) : "r"(da + (i > DL0) * 1024) : "memory");
          if (i >= 16 && i < 16 + RE0) { lds128(w[i - 16], uW + R_WC + L16 + (i - 16) * 2048); __syncwarp(); }
          if (i >= RP1 && i < RP1 + RE1) { lds128(w[i - RP1 + RE0], uW + R_WC + L16 + (i - RP1 + RE0) * 2048); __syncwarp(); }
          if (i == 22) put_b(dst[0], c);
          if ((i & 1) && (i < 20 || i > 22)) sched();
        }
        put_b(dst[1], d);
        sched();
        TS(6);
      };
      if (warp < 6) {
        delay_until(tpub + DLY_A);
        const int it0 = it;
        bool redo;
#pragma unroll 1
        do {
          uint32_t q[4][4], y[4];
          float d[4][4];
          wait_time(due);
          TS(4);
          ldx(q, asrc);
          sched();
          load_k();
          uint32_t qx[4][4];
#pragma unroll
          for (int i = 0; i < 4; i++) load_q(qx[i], i * 512);
          sched();
          load_wo(wo, 0, NE4);
          sched();
          zero(c);
#pragma unroll
          for (int i = 0; i < 8; i++) mma_h(c[i & 3], kf[i], qx[i >> 1], i & 1);
          put_p(1, 0, 0); put_s(1);
          sched();
          load_wo(wo, NE4, NA4);
          sched();
          zero(c); zero(d);
#pragma unroll
          for (int i = 0; i < 8; i++) {
            if (i == 0) { y[0] = dif2v(q[0][0], q[0][2], q[1][0]); sched(); }
            if (i == 3) { y[1] = dif2v(q[1][2], q[2][0], q[2][2]); sched(); }
            if (i == 6) { y[2] = dif2v(q[3][0], q[3][2], tag); sched(); }
            mma_h(i % 6 < 2 ? c[2 + i % 6] : d[i - 2], kf[i], q[i >> 1], i & 1);
            if (i == 2 || i == 5 || i == 7) sched();
          }
          y[0] = or_and(or3(y[0], y[1], dif2v(q[0][0], q[2][0], tag)), y[2], it < SPIN_LIMIT);
#pragma unroll
          for (int i = 0; i < 4; i++) { c[0][i] = d[0][i] + d[1][i]; c[1][i] = d[2][i] + d[3][i]; }
          put_p(0, y[0], it - it0);
          TS(5);
          bar_sync_unless(5, it - it0);
          redo = __any_sync(0xffffffffu, y[0]);
          it += INC_A;
        } while (redo);
        it -= INC_A;
        put_s(0);
        bar_arrive(8, 256);
        load_wo(wo, NA4, NB1);
        out_proj();
        if (warp == 4) LOG(12, tb);
      } else {
        uint32_t qx[2][4], q[4][4];
        if (warp == 6) {
          const uint32_t t1 = (now & ~31u) + NS_M;
          LOG(10, now - due);
          if (elect()) stx32(&gx->T[h][j], ((int)(t1 - due) > 0 ? t1 + NS_PEN : due) | ((s + 1) & 31));
          __syncwarp();
        }
        auto score = [&](const uint32_t (&a0)[4], const uint32_t (&a1)[4]) {
          zero(c);
#pragma unroll
          for (int i = 0; i < 4; i++) mma_h(c[i], i < 2 ? a0 : a1, q[2 + (i >> 1)], i & 1);
        };
        auto put_m = [&](uint32_t a, uint32_t old, uint32_t again) {
#pragma unroll
          for (int i = 0; i < 2; i++) { r4[i] = fmaf(c[3][2 + i], sc, fmaf((c[0][i] + c[1][2 + i]) + c[2][i], sc, __uint_as_float(i ? 0u - old : 0u))); r4[2 + i] = fmaf(r4[i] * 0x1p122f, 0.f, ex2(r4[i])); }
          asm volatile("{.reg .pred p; setp.eq.u32 p, %3, 0; @p st.shared.v2.f32 [%0], {%1,%2};}" :: "r"(a), "f"(r4[2]), "f"(r4[3]), "r"(again) : "memory");
        };
        delay_until(tpub + DLY_A);
        const uint32_t sa = sb + R_S + 512 + w4 * 256 + (L16 >> 1);
        const int it0 = it;
        bool redo;
#pragma unroll 1
        do {
          wait_time(due);
          TS(4);
          ldx<4, 2048>(q, asrc);
          sched();
          load_q(qx[0], (w4 & 1) * 1024); load_q(qx[1], (w4 & 1) * 1024 + 512);
          load_wo(wo, 0, NA6);
          sched();
          score(q[0], q[1]);
          sched();
          const uint32_t y = or_and(or3(dif2v(q[0][0], q[0][2], tag), dif2v(q[1][0], q[1][2], tag), dif2v(q[2][0], q[2][2], tag)), dif2v(q[3][0], q[3][2], tag), it < SPIN_LIMIT);
          put_m(sa + 2560, y, it - it0);
          TS(5);
          bar_arrive_unless(5, it - it0);
          redo = __any_sync(0xffffffffu, y);
          it += INC_A;
        } while (redo);
        it -= INC_A;
        sts64f(sa, r4[0], r4[1]);
        score(qx[0], qx[1]);
        put_m(sa + 3584, 0, 0);
        sts64f(sa + 1536, r4[0], r4[1]);
        bar_arrive(8, 256);
        load_wo(wo, NA6, NB1);
        out_proj();
      }
      TS(8);
      if (s + 1 == NSEG) break;
      wait_x(s + 2, 2);
      TS(9);
      fresh();
      if (N1) project_qk(IC<32>{}, IC<32 + N1>{}, IC<1>{}, [](int) {});
      TS(10);
      xpos(6, 6);
      uint32_t fl = s + 1;
      if (warp == 5) { wait_time(due + NS_F); fl = ldx32(xa + 4096 + ((L16 >> 2) & 60)); }
      reload();
      TS(14);
      pin_mem();
      wait_x(s + 2, 1); wait_x(s + 2, 0);
      if (warp == 5) {
#pragma unroll 1
        while (__any_sync(0xffffffffu, fl != s + 1) && !(EXP & 4) && ++it < SPIN_LIMIT) fl = ldx32(xa + 4096 + ((L16 >> 2) & 60));
        wait_time(due + (NS_B + NS_K));
        if (!(EXP & 2) && elect()) issue_kqv(s + 1);
        __syncwarp();
      }
      if (PFD && warp == 6 && s + PFD < NSEG && elect())
        asm volatile("cp.async.bulk.prefetch.L2.global [%0], 2048;" :: "l"(xin + ((s + PFD) * SEG + ((role + 4 * (role >> 5)) & 31)) * DM) : "memory");
      __syncwarp();
      TS(11);
      LOG(warp, it);
      if (warp == 4) LOG(8, nc);
      bar_sync(0, 256);
      if (N1 < 16) project_qk(IC<32 + N1>{}, IC<48>{}, IC<!N1>{}, [](int) {});
      project_qk(IC<16>{}, IC<32>{}, IC<0>{}, [&](int n) { if ((n & 15) == XWPOS) { __syncwarp(); xok = mbar_test(sb + B_PK, s & 1); __syncwarp(); } });
      if (rare(!xok)) mbar_spin(sb + B_PK, s & 1, it);
      unpark();
      project_qk(IC<0>{}, IC<16>{}, IC<0>{}, [](int) {});
      TS(12);
      wg_wait<0>(); keep(aq);
      TS(1);
      fin_qk();
      TS(15);
    }
    s++;
  }
  if (it >= SPIN_LIMIT || nc >= NC_MAX) g_err = 2;
}

typedef CUresult (*EncodeFn)(CUtensorMap*, CUtensorMapDataType, cuuint32_t, void*, const cuuint64_t*, const cuuint64_t*, const cuuint32_t*,
                             const cuuint32_t*, CUtensorMapInterleave, CUtensorMapSwizzle, CUtensorMapL2promotion, CUtensorMapFloatOOBfill);
static void make_map(EncodeFn fn, CUtensorMap* m, const void* p, uint64_t cols, uint64_t rows, uint64_t pitch, uint32_t bc, uint32_t br, CUtensorMapSwizzle sw) {
  cuuint64_t dims[2] = {cols, rows}, strides[1] = {pitch * 2};
  cuuint32_t box[2] = {bc, br}, es[2] = {1, 1};
  fn(m, CU_TENSOR_MAP_DATA_TYPE_BFLOAT16, 2, const_cast<void*>(p), dims, strides, box, es, CU_TENSOR_MAP_INTERLEAVE_NONE, sw,
     CU_TENSOR_MAP_L2_PROMOTION_L2_256B, CU_TENSOR_MAP_FLOAT_OOB_FILL_NONE);
}

extern "C" void kernel_launch(void* const* d_in, const int* in_sizes, int n_in, void* d_out, int out_size) {
  const bf16* Ax = (const bf16*)d_in[0]; const bf16* mem0 = (const bf16*)d_in[1];
  const bf16* Wq = (const bf16*)d_in[2]; const bf16* Wk = (const bf16*)d_in[3]; const bf16* Wv = (const bf16*)d_in[4];
  const bf16* Wo = (const bf16*)d_in[5];
  const bf16* Bx = (const bf16*)d_in[7]; const bf16* wr = (const bf16*)d_in[8]; const bf16* wi = (const bf16*)d_in[9];
  bf16* out = (bf16*)d_out;

  void* fp = nullptr; cudaDriverEntryPointQueryResult qr;
  cudaGetDriverEntryPoint("cuTensorMapEncodeTiled", &fp, cudaEnableDefault, &qr);
  EncodeFn fn = (EncodeFn)fp;
  void *kqv, *ox, *xr;
  cudaGetSymbolAddress(&xr, g_xraw);
  cudaGetSymbolAddress(&kqv, g_kqv); cudaGetSymbolAddress(&ox, g_ox);
  const CUtensorMapSwizzle S128 = CU_TENSOR_MAP_SWIZZLE_128B, S64 = CU_TENSOR_MAP_SWIZZLE_64B;

  GemmMaps m3; RecMaps mr;
  make_map(fn, &m3.a, ox, HD, S_LEN, HD, 64, 128, S128);
  make_map(fn, &m3.b[0], Wo, DM, HD, DM, 64, 64, S128);
  m3.b[1] = m3.b[0]; m3.b[2] = m3.b[0];
  make_map(fn, &m3.c, out, DM, S_LEN, 2 * DM, 64, 64, S128);
  make_map(fn, &mr.wq, Wq, HD, DM, HD, 32, 256, S64);
  make_map(fn, &mr.wk, Wk, HD, DM, HD, 32, 256, S64);
  make_map(fn, &mr.wv, Wv, HD, DM, HD, 64, 256, S128);
  make_map(fn, &mr.wo, Wo, DM, HD, DM, 64, 128, S128);
  {
    cuuint64_t dims[3] = {64, S_LEN, 16}, strides[2] = {DM * 2, 128};
    cuuint32_t box[3] = {64, 32, 4}, es[3] = {1, 1, 1};
    fn(&mr.x, CU_TENSOR_MAP_DATA_TYPE_BFLOAT16, 3, const_cast<bf16*>(Ax), dims, strides, box, es, CU_TENSOR_MAP_INTERLEAVE_NONE, S128,
       CU_TENSOR_MAP_L2_PROMOTION_L2_256B, CU_TENSOR_MAP_FLOAT_OOB_FILL_NONE);
  }
  for (int i = 0; i < 3; i++) {
    cuuint64_t dims[3] = {128, 32, 512}, strides[2] = {256, 8192};
    cuuint32_t box[3] = {128, i == 0 ? 8u : i == 1 ? 2u : 16u, 4}, es[3] = {1, 1, 1};
    fn(i == 0 ? &mr.k : i == 1 ? &mr.q : &mr.v, CU_TENSOR_MAP_DATA_TYPE_BFLOAT16, 3, kqv, dims, strides, box, es, CU_TENSOR_MAP_INTERLEAVE_NONE,
       CU_TENSOR_MAP_SWIZZLE_NONE, CU_TENSOR_MAP_L2_PROMOTION_L2_256B, CU_TENSOR_MAP_FLOAT_OOB_FILL_NONE);
  }
  {
    cuuint64_t dims[3] = {64, 16, S_LEN}, strides[2] = {128, 2 * DM * 2};
    cuuint32_t box[3] = {64, 16, 2}, es[3] = {1, 1, 1};
    fn(&mr.fo, CU_TENSOR_MAP_DATA_TYPE_BFLOAT16, 3, out + DM, dims, strides, box, es, CU_TENSOR_MAP_INTERLEAVE_NONE, S128,
       CU_TENSOR_MAP_L2_PROMOTION_NONE, CU_TENSOR_MAP_FLOAT_OOB_FILL_NONE);
  }
  constexpr int SM3 = 6 * 32768 + 32768 + 256 + 1024;
  cudaFuncSetAttribute(gemm_kernel<128, 6>, cudaFuncAttributeMaxDynamicSharedMemorySize, SM3);
  cudaFuncSetAttribute(rec_kernel, cudaFuncAttributeMaxDynamicSharedMemorySize, R_TOTAL);

  cudaStream_t st = cudaStreamPerThread;
  cudaFuncSetAttribute(fft_pre_kernel, cudaFuncAttributeMaxDynamicSharedMemorySize, F_SMEM);
  fft_pre_kernel<<<128, 256, F_SMEM, st>>>(Bx, wr, wi);
  rec_kernel<<<132, 256, R_TOTAL, st>>>(mr, Ax, mem0, reinterpret_cast<Xchg*>((reinterpret_cast<uintptr_t>(xr) + 8191) & ~(uintptr_t)8191));
  gemm_kernel<128, 6><<<128, 384, SM3, st>>>(m3, 16, 8, 64, 8, 1);
}
```

```cpp
#include <cuda_runtime.h>
#include <cuda_bf16.h>
#include <cuda.h>
#include <stdint.h>
#include <stddef.h>
#include <type_traits>

typedef __nv_bfloat16 bf16;

constexpr int S_LEN = 2048, DM = 1024, NH = 32, DH = 128, MEM = 8, SEG = 32, NSEG = 64;
constexpr int HD = NH * DH;
#define SPIN 20
constexpr int SPIN_LIMIT = 1 << SPIN, INC_A = 1, INC_B = 1;

constexpr unsigned NC_MAX = 4096;
__device__ __align__(1024) uint4 g_kqv[4][128][512];
__device__ __align__(1024) bf16 g_ox[(size_t)S_LEN * HD];
struct Xchg {
  uint4 A[32][4][256];
  uint4 C[4][2][256];
  uint4 B[128][2][256];
  uint32_t T[32][32];
  uint32_t S[128];
  unsigned ctr[64];
};
__device__ __align__(1024) uint4 g_xraw[(sizeof(Xchg) + 8192) / 16];
__device__ __align__(1024) uint4 g_y[1024 * 256];
__device__ __align__(1024) uint4 g_wt[513 * 512];
__device__ int g_err;

__device__ __forceinline__ unsigned clk() { unsigned long long c; asm volatile("mov.u64 %0, %%clock64;" : "=l"(c)); return (unsigned)c; }
__device__ __forceinline__ uint32_t smem_u32(const void* p) { return (uint32_t)__cvta_generic_to_shared(p); }
__device__ __forceinline__ void mbar_init(uint32_t bar, int cnt) { asm volatile("mbarrier.init.shared::cta.b64 [%0], %1;" :: "r"(bar), "r"(cnt) : "memory"); }
__device__ __forceinline__ void mbar_expect_tx(uint32_t bar, int bytes) { asm volatile("mbarrier.arrive.expect_tx.shared::cta.b64 _, [%0], %1;" :: "r"(bar), "r"(bytes) : "memory"); }
__device__ __forceinline__ void mbar_arrive(uint32_t bar) { asm volatile("mbarrier.arrive.shared::cta.b64 _, [%0];" :: "r"(bar) : "memory"); }
__device__ __forceinline__ void mbar_arrive_cluster(uint32_t bar, int cta) {
  asm volatile("{.reg .b32 r; mapa.shared::cluster.u32 r, %0, %1; mbarrier.arrive.shared::cluster.b64 _, [r];}" :: "r"(bar), "r"(cta) : "memory"); }
__device__ __forceinline__ bool mbar_try(uint32_t bar, int par) {
  uint32_t ok; asm volatile("{.reg .pred p; mbarrier.try_wait.parity.shared::cta.b64 p, [%1], %2; selp.u32 %0, 1, 0, p;}" : "=r"(ok) : "r"(bar), "r"(par) : "memory"); return ok; }
__device__ __forceinline__ bool mbar_test(uint32_t bar, int par) {
  uint32_t ok; asm volatile("{.reg .pred p; mbarrier.test_wait.parity.shared::cta.b64 p, [%1], %2; selp.u32 %0, 1, 0, p;}" : "=r"(ok) : "r"(bar), "r"(par) : "memory"); return ok; }
__device__ __forceinline__ void mbar_wait(uint32_t bar, int par) {
  int it = 0;
  while (!mbar_try(bar, par)) { if (++it > SPIN_LIMIT) { g_err = 1; break; } }
}
__device__ __forceinline__ void tma2d(uint32_t dst, const CUtensorMap* m, int c0, int c1, uint32_t bar) {
  asm volatile("cp.async.bulk.tensor.2d.shared::cluster.global.mbarrier::complete_tx::bytes [%0], [%1, {%3, %4}], [%2];"
    :: "r"(dst), "l"(m), "r"(bar), "r"(c0), "r"(c1) : "memory"); }
__device__ __forceinline__ void tma2d_mc(uint32_t dst, const CUtensorMap* m, int c0, int c1, uint32_t bar, uint16_t mask) {
  asm volatile("cp.async.bulk.tensor.2d.shared::cluster.global.mbarrier::complete_tx::bytes.multicast::cluster [%0], [%1, {%3, %4}], [%2], %5;"
    :: "r"(dst), "l"(m), "r"(bar), "r"(c0), "r"(c1), "h"(mask) : "memory"); }
__device__ __forceinline__ void tma2d_store(const CUtensorMap* m, uint32_t src, int c0, int c1) {
  asm volatile("cp.async.bulk.tensor.2d.global.shared::cta.bulk_group [%0, {%2, %3}], [%1];" :: "l"(m), "r"(src), "r"(c0), "r"(c1) : "memory"); }
__device__ __forceinline__ void fence_async() { asm volatile("fence.proxy.async.shared::cta;" ::: "memory"); }
__device__ __forceinline__ void bar_sync(int id, int n) { asm volatile("bar.sync %0, %1;" :: "r"(id), "r"(n) : "memory"); }
__device__ __forceinline__ void bar_arrive(int id, int n) { asm volatile("bar.arrive %0, %1;" :: "r"(id), "r"(n) : "memory"); }
__device__ __forceinline__ uint32_t pack2(float lo, float hi) { uint32_t r; asm("cvt.rn.bf16x2.f32 %0, %1, %2;" : "=r"(r) : "f"(hi), "f"(lo)); return r; }
__device__ __forceinline__ uint32_t pack2_tag(float lo, float hi, uint32_t T) {
  uint32_t u = ((__float_as_uint(lo) - T + 0x10000u) & 0xFFFE0000u) + T;
  return __byte_perm(u, pack2(0.f, hi), 0x7632); }
__device__ __forceinline__ void ldsm4(uint32_t (&r)[4], uint32_t a) {
  asm volatile("ldmatrix.sync.aligned.m8n8.x4.shared.b16 {%0,%1,%2,%3}, [%4];" : "=r"(r[0]), "=r"(r[1]), "=r"(r[2]), "=r"(r[3]) : "r"(a) : "memory"); }
__device__ __forceinline__ void ldsm4t(uint32_t (&r)[4], uint32_t a) {
  asm volatile("ldmatrix.sync.aligned.m8n8.x4.trans.shared.b16 {%0,%1,%2,%3}, [%4];" : "=r"(r[0]), "=r"(r[1]), "=r"(r[2]), "=r"(r[3]) : "r"(a) : "memory"); }
__device__ __forceinline__ void stsm4(uint32_t a, uint32_t r0, uint32_t r1, uint32_t r2, uint32_t r3) {
  asm volatile("stmatrix.sync.aligned.m8n8.x4.shared.b16 [%0], {%1,%2,%3,%4};" :: "r"(a), "r"(r0), "r"(r1), "r"(r2), "r"(r3) : "memory"); }
__device__ __forceinline__ void stsm4t(uint32_t a, uint32_t r0, uint32_t r1, uint32_t r2, uint32_t r3) {
  asm volatile("stmatrix.sync.aligned.m8n8.x4.trans.shared.b16 [%0], {%1,%2,%3,%4};" :: "r"(a), "r"(r0), "r"(r1), "r"(r2), "r"(r3) : "memory"); }
__device__ __forceinline__ void lds128(uint32_t (&r)[4], uint32_t a) {
  asm volatile("ld.shared.v4.u32 {%0,%1,%2,%3}, [%4];" : "=r"(r[0]), "=r"(r[1]), "=r"(r[2]), "=r"(r[3]) : "r"(a) : "memory"); }
__device__ __forceinline__ float4 lds128f(uint32_t a) { float4 r;
  asm volatile("ld.shared.v4.f32 {%0,%1,%2,%3}, [%4];" : "=f"(r.x), "=f"(r.y), "=f"(r.z), "=f"(r.w) : "r"(a) : "memory"); return r; }
__device__ __forceinline__ float2 lds64f(uint32_t a) { float2 r;
  asm volatile("ld.shared.v2.f32 {%0,%1}, [%2];" : "=f"(r.x), "=f"(r.y) : "r"(a) : "memory"); return r; }
__device__ __forceinline__ void sts128(uint32_t a, uint32_t r0, uint32_t r1, uint32_t r2, uint32_t r3) {
  asm volatile("st.shared.v4.u32 [%0], {%1,%2,%3,%4};" :: "r"(a), "r"(r0), "r"(r1), "r"(r2), "r"(r3) : "memory"); }
__device__ __forceinline__ void sts64f(uint32_t a, float x, float y) { asm volatile("st.shared.v2.f32 [%0], {%1,%2};" :: "r"(a), "f"(x), "f"(y) : "memory"); }
__device__ __forceinline__ void sts32f(uint32_t a, float x) { asm volatile("st.shared.f32 [%0], %1;" :: "r"(a), "f"(x) : "memory"); }
__device__ __forceinline__ void mma16816(float (&d)[4], uint32_t a0, uint32_t a1, uint32_t a2, uint32_t a3, uint32_t b0, uint32_t b1) {
  asm volatile("mma.sync.aligned.m16n8k16.row.col.f32.bf16.bf16.f32 {%0,%1,%2,%3}, {%4,%5,%6,%7}, {%8,%9}, {%0,%1,%2,%3};"
    : "+f"(d[0]), "+f"(d[1]), "+f"(d[2]), "+f"(d[3]) : "r"(a0), "r"(a1), "r"(a2), "r"(a3), "r"(b0), "r"(b1)); }
__device__ __forceinline__ void mma1688(float (&d)[4], uint32_t a0, uint32_t a1, uint32_t b0) {
  asm volatile("mma.sync.aligned.m16n8k8.row.col.f32.bf16.bf16.f32 {%0,%1,%2,%3}, {%4,%5}, {%6}, {%0,%1,%2,%3};"
    : "+f"(d[0]), "+f"(d[1]), "+f"(d[2]), "+f"(d[3]) : "r"(a0), "r"(a1), "r"(b0)); }
__device__ __forceinline__ void ldx128(uint32_t (&r)[4], const void* p) {
  asm volatile("{.reg .b128 t; .reg .b64 a, b; ld.relaxed.gpu.global.b128 t, [%4]; mov.b128 {a, b}, t; mov.b64 {%0,%1}, a; mov.b64 {%2,%3}, b;}"
    : "=r"(r[0]), "=r"(r[1]), "=r"(r[2]), "=r"(r[3]) : "l"(p) : "memory"); }
__device__ __forceinline__ void ldx2x64(uint32_t (&r)[4], const void* p) {
  asm volatile("{.reg .b64 a, b; ld.relaxed.gpu.global.v2.b64 {a, b}, [%4]; mov.b64 {%0,%1}, a; mov.b64 {%2,%3}, b;}"
    : "=r"(r[0]), "=r"(r[1]), "=r"(r[2]), "=r"(r[3]) : "l"(p) : "memory"); }
__device__ __forceinline__ void stx128(void* p, uint32_t r0, uint32_t r1, uint32_t r2, uint32_t r3) {
  asm volatile("{.reg .b128 t; .reg .b64 a, b; mov.b64 a, {%1,%2}; mov.b64 b, {%3,%4}; mov.b128 t, {a, b}; st.relaxed.gpu.global.b128 [%0], t;}"
    :: "l"(p), "r"(r0), "r"(r1), "r"(r2), "r"(r3) : "memory"); }
__device__ __forceinline__ void stx64(void* p, uint32_t r0, uint32_t r1) {
  asm volatile("{.reg .b64 a; mov.b64 a, {%1,%2}; st.relaxed.gpu.global.b64 [%0], a;}" :: "l"(p), "r"(r0), "r"(r1) : "memory"); }
__device__ __forceinline__ uint32_t uni(uint32_t x) { return __shfl_sync(0xffffffffu, x, 0); }
__device__ __forceinline__ uint32_t pin(uint32_t x) { return __shfl_xor_sync(0xffffffffu, x, 0); }
__device__ __forceinline__ float ex2(float x) { float r; asm("ex2.approx.ftz.f32 %0, %1;" : "=f"(r) : "f"(x)); return r; }
__device__ __forceinline__ void wg_fence() { asm volatile("wgmma.fence.sync.aligned;" ::: "memory"); }
__device__ __forceinline__ void wg_commit() { asm volatile("wgmma.commit_group.sync.aligned;" ::: "memory"); }
template <int N> __device__ __forceinline__ void wg_wait() { asm volatile("wgmma.wait_group.sync.aligned %0;" :: "n"(N) : "memory"); }

__device__ __forceinline__ void wgmma_ss_n256_tb1(float (&d)[128], uint64_t da, uint64_t db, int sc) {
  asm volatile("{.reg .pred p; setp.ne.b32 p, %130, 0;\n"
    "wgmma.mma_async.sync.aligned.m64n256k16.f32.bf16.bf16 {%0,%1,%2,%3,%4,%5,%6,%7,%8,%9,%10,%11,%12,%13,%14,%15,%16,%17,%18,%19,%20,%21,%22,%23,%24,%25,%26,%27,%28,%29,%30,%31,%32,%33,%34,%35,%36,%37,%38,%39,%40,%41,%42,%43,%44,%45,%46,%47,%48,%49,%50,%51,%52,%53,%54,%55,%56,%57,%58,%59,%60,%61,%62,%63,%64,%65,%66,%67,%68,%69,%70,%71,%72,%73,%74,%75,%76,%77,%78,%79,%80,%81,%82,%83,%84,%85,%86,%87,%88,%89,%90,%91,%92,%93,%94,%95,%96,%97,%98,%99,%100,%101,%102,%103,%104,%105,%106,%107,%108,%109,%110,%111,%112,%113,%114,%115,%116,%117,%118,%119,%120,%121,%122,%123,%124,%125,%126,%127}, %128, %129, p, 1, 1, 0, 1;}\n"
    : "+f"(d[0]),"+f"(d[1]),"+f"(d[2]),"+f"(d[3]),"+f"(d[4]),"+f"(d[5]),"+f"(d[6]),"+f"(d[7]),"+f"(d[8]),"+f"(d[9]),"+f"(d[10]),"+f"(d[11]),"+f"(d[12]),"+f"(d[13]),"+f"(d[14]),"+f"(d[15]),"+f"(d[16]),"+f"(d[17]),"+f"(d[18]),"+f"(d[19]),"+f"(d[20]),"+f"(d[21]),"+f"(d[22]),"+f"(d[23]),"+f"(d[24]),"+f"(d[25]),"+f"(d[26]),"+f"(d[27]),"+f"(d[28]),"+f"(d[29]),"+f"(d[30]),"+f"(d[31]),"+f"(d[32]),"+f"(d[33]),"+f"(d[34]),"+f"(d[35]),"+f"(d[36]),"+f"(d[37]),"+f"(d[38]),"+f"(d[39]),"+f"(d[40]),"+f"(d[41]),"+f"(d[42]),"+f"(d[43]),"+f"(d[44]),"+f"(d[45]),"+f"(d[46]),"+f"(d[47]),"+f"(d[48]),"+f"(d[49]),"+f"(d[50]),"+f"(d[51]),"+f"(d[52]),"+f"(d[53]),"+f"(d[54]),"+f"(d[55]),"+f"(d[56]),"+f"(d[57]),"+f"(d[58]),"+f"(d[59]),"+f"(d[60]),"+f"(d[61]),"+f"(d[62]),"+f"(d[63]),"+f"(d[64]),"+f"(d[65]),"+f"(d[66]),"+f"(d[67]),"+f"(d[68]),"+f"(d[69]),"+f"(d[70]),"+f"(d[71]),"+f"(d[72]),"+f"(d[73]),"+f"(d[74]),"+f"(d[75]),"+f"(d[76]),"+f"(d[77]),"+f"(d[78]),"+f"(d[79]),"+f"(d[80]),"+f"(d[81]),"+f"(d[82]),"+f"(d[83]),"+f"(d[84]),"+f"(d[85]),"+f"(d[86]),"+f"(d[87]),"+f"(d[88]),"+f"(d[89]),"+f"(d[90]),"+f"(d[91]),"+f"(d[92]),"+f"(d[93]),"+f"(d[94]),"+f"(d[95]),"+f"(d[96]),"+f"(d[97]),"+f"(d[98]),"+f"(d[99]),"+f"(d[100]),"+f"(d[101]),"+f"(d[102]),"+f"(d[103]),"+f"(d[104]),"+f"(d[105]),"+f"(d[106]),"+f"(d[107]),"+f"(d[108]),"+f"(d[109]),"+f"(d[110]),"+f"(d[111]),"+f"(d[112]),"+f"(d[113]),"+f"(d[114]),"+f"(d[115]),"+f"(d[116]),"+f"(d[117]),"+f"(d[118]),"+f"(d[119]),"+f"(d[120]),"+f"(d[121]),"+f"(d[122]),"+f"(d[123]),"+f"(d[124]),"+f"(d[125]),"+f"(d[126]),"+f"(d[127])
    : "l"(da), "l"(db), "r"(sc));
}

__device__ __forceinline__ void wgmma_ss_n128_tb1(float (&d)[64], uint64_t da, uint64_t db, int sc) {
  asm volatile("{.reg .pred p; setp.ne.b32 p, %66, 0;\n"
    "wgmma.mma_async.sync.aligned.m64n128k16.f32.bf16.bf16 {%0,%1,%2,%3,%4,%5,%6,%7,%8,%9,%10,%11,%12,%13,%14,%15,%16,%17,%18,%19,%20,%21,%22,%23,%24,%25,%26,%27,%28,%29,%30,%31,%32,%33,%34,%35,%36,%37,%38,%39,%40,%41,%42,%43,%44,%45,%46,%47,%48,%49,%50,%51,%52,%53,%54,%55,%56,%57,%58,%59,%60,%61,%62,%63}, %64, %65, p, 1, 1, 0, 1;}\n"
    : "+f"(d[0]),"+f"(d[1]),"+f"(d[2]),"+f"(d[3]),"+f"(d[4]),"+f"(d[5]),"+f"(d[6]),"+f"(d[7]),"+f"(d[8]),"+f"(d[9]),"+f"(d[10]),"+f"(d[11]),"+f"(d[12]),"+f"(d[13]),"+f"(d[14]),"+f"(d[15]),"+f"(d[16]),"+f"(d[17]),"+f"(d[18]),"+f"(d[19]),"+f"(d[20]),"+f"(d[21]),"+f"(d[22]),"+f"(d[23]),"+f"(d[24]),"+f"(d[25]),"+f"(d[26]),"+f"(d[27]),"+f"(d[28]),"+f"(d[29]),"+f"(d[30]),"+f"(d[31]),"+f"(d[32]),"+f"(d[33]),"+f"(d[34]),"+f"(d[35]),"+f"(d[36]),"+f"(d[37]),"+f"(d[38]),"+f"(d[39]),"+f"(d[40]),"+f"(d[41]),"+f"(d[42]),"+f"(d[43]),"+f"(d[44]),"+f"(d[45]),"+f"(d[46]),"+f"(d[47]),"+f"(d[48]),"+f"(d[49]),"+f"(d[50]),"+f"(d[51]),"+f"(d[52]),"+f"(d[53]),"+f"(d[54]),"+f"(d[55]),"+f"(d[56]),"+f"(d[57]),"+f"(d[58]),"+f"(d[59]),"+f"(d[60]),"+f"(d[61]),"+f"(d[62]),"+f"(d[63])
    : "l"(da), "l"(db), "r"(sc));
}

template <int BN> struct WG;
template <> struct WG<256> { static __device__ __forceinline__ void mma(float (&d)[128], uint64_t a, uint64_t b, int sc) { wgmma_ss_n256_tb1(d, a, b, sc); } };
template <> struct WG<128> { static __device__ __forceinline__ void mma(float (&d)[64], uint64_t a, uint64_t b, int sc) { wgmma_ss_n128_tb1(d, a, b, sc); } };

struct GemmMaps { CUtensorMap a, b[3], c; };
template <int BN, int STAGES>
__global__ void __cluster_dims__(2, 1, 1) __launch_bounds__(384, 1)
gemm_kernel(const __grid_constant__ GemmMaps maps, int tilesM, int tilesN, int kblocks, int nPerB, int clearX) {
  extern __shared__ __align__(1024) uint8_t smem_raw[];
  constexpr int STAGE_BYTES = 16384 + BN * 128;
  constexpr int NBOX = BN / 64;
  const uint32_t sbase = (smem_u32(smem_raw) + 1023) & ~1023u;
  const uint32_t sEpi = sbase + STAGES * STAGE_BYTES;
  const uint32_t sBar = sEpi + 32768;
  const int warp = threadIdx.x >> 5, lane = threadIdx.x & 31, wg = warp >> 2;
  uint32_t crank; asm("mov.u32 %0, %%cluster_ctarank;" : "=r"(crank));
  if (threadIdx.x == 0) {
    for (int i = 0; i < STAGES; i++) { mbar_init(sBar + 8 * i, 1); mbar_init(sBar + 8 * (STAGES + i), 4); }
    asm volatile("fence.mbarrier_init.release.cluster;" ::: "memory");
  }
  if (clearX) {
    uint4* p = g_xraw;
    for (int i = blockIdx.x * 384 + threadIdx.x; i < (int)(sizeof(g_xraw) / 16); i += gridDim.x * 384) p[i] = make_uint4(0, 0, 0, 0);
  }
  asm volatile("barrier.cluster.arrive.release.aligned; barrier.cluster.wait.acquire.aligned;" ::: "memory");
  const int npairs = (tilesM >> 1) * tilesN, pair0 = blockIdx.x >> 1, pstep = gridDim.x >> 1;
  if (wg == 2) {
    asm volatile("setmaxnreg.dec.sync.aligned.u32 40;");
    if (warp == 8 && lane == 0) {
      int st = 0, ph = 1;
      for (int p = pair0; p < npairs; p += pstep) {
        const int tm = (p % (tilesM >> 1)) * 2 + crank, tn = p / (tilesM >> 1);
        const CUtensorMap* mb = &maps.b[tn / nPerB];
        const int n0 = (tn % nPerB) * BN;
        for (int kb = 0; kb < kblocks; kb++) {
          mbar_wait(sBar + 8 * (STAGES + st), ph);
          const uint32_t a = sbase + st * STAGE_BYTES, full = sBar + 8 * st;
          mbar_expect_tx(full, STAGE_BYTES);
          tma2d(a, &maps.a, kb * 64, tm * 128, full);
#pragma unroll
          for (int i = 0; i < NBOX / 2; i++) {
            const int bx = crank * (NBOX / 2) + i;
            tma2d_mc(a + 16384 + bx * 8192, mb, n0 + bx * 64, kb * 64, full, (uint16_t)3);
          }
          if (++st == STAGES) { st = 0; ph ^= 1; }
        }
      }
      for (int i = 0; i < STAGES; i++) { mbar_wait(sBar + 8 * (STAGES + st), ph); if (++st == STAGES) { st = 0; ph ^= 1; } }
    }
  } else {
    asm volatile("setmaxnreg.inc.sync.aligned.u32 232;");
    int st = 0, ph = 0;
    float acc[BN / 2];
    const uint64_t descA0 = (uint64_t)(((sbase + wg * 8192) & 0x3FFFF) >> 4) | (1ull << 16) | (64ull << 32) | (1ull << 62);
    const uint64_t descB0 = (uint64_t)(((sbase + 16384) & 0x3FFFF) >> 4) | (512ull << 16) | (64ull << 32) | (1ull << 62);
    const uint32_t epi = sEpi + wg * 16384;
    for (int p = pair0; p < npairs; p += pstep) {
      const int tm = (p % (tilesM >> 1)) * 2 + crank, tn = p / (tilesM >> 1);
      int prev = -1;
      for (int kb = 0; kb < kblocks; kb++) {
        mbar_wait(sBar + 8 * st, ph);
        wg_fence();
        const uint64_t so = (uint64_t)(st * (STAGE_BYTES >> 4));
#pragma unroll
        for (int k = 0; k < 4; k++) WG<BN>::mma(acc, descA0 + so + k * 2, descB0 + so + k * 128, kb | k);
        wg_commit();
        if (prev >= 0) {
          wg_wait<1>();
          if ((threadIdx.x & 127) < 2) mbar_arrive_cluster(sBar + 8 * (STAGES + prev), threadIdx.x & 1);
        }
        prev = st;
        if (++st == STAGES) { st = 0; ph ^= 1; }
      }
      wg_wait<0>();
      if ((threadIdx.x & 127) < 2) mbar_arrive_cluster(sBar + 8 * (STAGES + prev), threadIdx.x & 1);
#pragma unroll
      for (int r = 0; r < BN / 128; r++) {
        if ((threadIdx.x & 127) == 0) asm volatile("cp.async.bulk.wait_group.read 0;" ::: "memory");
        bar_sync(1 + wg, 128);
        const int row = (warp & 3) * 16 + (lane & 15);
#pragma unroll
        for (int i = 0; i < 8; i++) {
          const int c = 2 * (i & 3) + (lane >> 4);
          const float* q = &acc[r * 64 + i * 8];
          stsm4(epi + (i >> 2) * 8192 + row * 128 + ((c ^ (row & 7)) << 4), pack2(q[0], q[1]), pack2(q[2], q[3]), pack2(q[4], q[5]), pack2(q[6], q[7]));
        }
        fence_async();
        bar_sync(1 + wg, 128);
        if ((threadIdx.x & 127) == 0) {
          tma2d_store(&maps.c, epi, tn * BN + r * 128, tm * 128 + wg * 64);
          tma2d_store(&maps.c, epi + 8192, tn * BN + r * 128 + 64, tm * 128 + wg * 64);
          asm volatile("cp.async.bulk.commit_group;" ::: "memory");
        }
      }
    }
    if ((threadIdx.x & 127) == 0) asm volatile("cp.async.bulk.wait_group 0;" ::: "memory");
  }
}

struct Dft { uint32_t m[2][2][2][4]; };
template <bool P4> __device__ __forceinline__ int fidx(int tile, int x) { return P4 ? 4 * (x >> 1) + 2 * (tile & 1) + (x & 1) + 16 * (tile >> 1) : x + 8 * tile; }
__device__ __forceinline__ float2 cis(int k, int n) {
  k &= n - 1; if (2 * k > n) k -= n;
  const float a = (float)k * (6.283185307179586f / (float)n);
  return make_float2(__cosf(a), __sinf(a));
}
template <bool OUT4> __device__ __forceinline__ void make_dft(Dft& D, int g, int t) {
#pragma unroll
  for (int q = 0; q < 16; q++) {
    const int b = q >> 3, u = (q >> 2) & 1, r = (q >> 1) & 1, v = q & 1;
    const float2 w = cis(fidx<OUT4>(v, g) * fidx<false>(2 * u + r, 2 * t + b), 32);
    D.m[b][u][0][q & 3] = pack2(w.x, w.y); D.m[b][u][1][q & 3] = pack2(-w.y, w.x);
  }
}
__device__ __forceinline__ void mma_dc(float (&d)[4], uint32_t a0, uint32_t a1, uint32_t a2, uint32_t a3, uint32_t b0, uint32_t b1, const float (&c)[4]) {
  asm("mma.sync.aligned.m16n8k16.row.col.f32.bf16.bf16.f32 {%0,%1,%2,%3}, {%4,%5,%6,%7}, {%8,%9}, {%10,%11,%12,%13};"
    : "=f"(d[0]), "=f"(d[1]), "=f"(d[2]), "=f"(d[3]) : "r"(a0), "r"(a1), "r"(a2), "r"(a3), "r"(b0), "r"(b1), "f"(c[0]), "f"(c[1]), "f"(c[2]), "f"(c[3])); }
__device__ __forceinline__ void dft_b(const Dft& D, const uint32_t (&x)[2][4], float (&o)[2][8]) {
#pragma unroll
  for (int ri = 0; ri < 2; ri++) {
    float z[4] = {0.f, 0.f, 0.f, 0.f}, e[4], p[4];
    mma_dc(e, D.m[0][0][ri][0], D.m[0][0][ri][1], D.m[0][0][ri][2], D.m[0][0][ri][3], x[0][0], x[0][1], z);
    mma_dc(e, D.m[0][1][ri][0], D.m[0][1][ri][1], D.m[0][1][ri][2], D.m[0][1][ri][3], x[0][2], x[0][3], e);
    mma_dc(p, D.m[1][0][ri][0], D.m[1][0][ri][1], D.m[1][0][ri][2], D.m[1][0][ri][3], x[1][0], x[1][1], e);
    mma_dc(p, D.m[1][1][ri][0], D.m[1][1][ri][1], D.m[1][1][ri][2], D.m[1][1][ri][3], x[1][2], x[1][3], p);
#pragma unroll
    for (int q = 0; q < 4; q++) { o[ri][q] = p[q]; o[ri][4 + q] = fmaf(2.f, e[q], -p[q]); }
  }
}
__device__ __forceinline__ void dft_a(const uint32_t (&m)[2][2][4], const uint32_t (&x0)[2][4], const uint32_t (&x1)[2][4], float (&o)[2][8]) {
#pragma unroll
  for (int ri = 0; ri < 2; ri++) {
    float z[4] = {0.f, 0.f, 0.f, 0.f}, e[4], p[4];
    mma_dc(e, x0[0][0], x1[0][0], x0[0][1], x1[0][1], m[0][ri][0], m[0][ri][1], z);
    mma_dc(e, x0[0][2], x1[0][2], x0[0][3], x1[0][3], m[0][ri][2], m[0][ri][3], e);
    mma_dc(p, x0[1][0], x1[1][0], x0[1][1], x1[1][1], m[1][ri][0], m[1][ri][1], e);
    mma_dc(p, x0[1][2], x1[1][2], x0[1][3], x1[1][3], m[1][ri][2], m[1][ri][3], p);
#pragma unroll
    for (int q = 0; q < 4; q++) { o[ri][q] = p[q]; o[ri][4 + q] = fmaf(2.f, e[q], -p[q]); }
  }
}
__device__ __forceinline__ uint32_t twid(float re, float im, float c, float s) { return pack2(fmaf(re, c, im * s), fmaf(im, c, -re * s)); }
__device__ __forceinline__ void cpa16(uint32_t d, const void* s) { asm volatile("cp.async.cg.shared.global [%0], [%1], 16;" :: "r"(d), "l"(s) : "memory"); }
__device__ __forceinline__ void sts32(uint32_t a, uint32_t x) { asm volatile("st.shared.u32 [%0], %1;" :: "r"(a), "r"(x) : "memory"); }
__device__ __forceinline__ void cpa_commit() { asm volatile("cp.async.commit_group;" ::: "memory"); }
template <int N> __device__ __forceinline__ void cpa_wait() { asm volatile("cp.async.wait_group %0;" :: "n"(N) : "memory"); }
__device__ __forceinline__ uint32_t lds32(uint32_t a) { uint32_t r; asm volatile("ld.shared.u32 %0, [%1];" : "=r"(r) : "r"(a) : "memory"); return r; }
constexpr int F_TP = 4112, F_TSZ = 8 * F_TP;

__device__ __forceinline__ uint32_t ldnc32(const void* p) { uint32_t v; asm volatile("ld.global.nc.b32 %0, [%1];" : "=r"(v) : "l"(p) : "memory"); return v; }
template <class F>
__device__ __forceinline__ void fft_wprep(const bf16* __restrict__ wr, const bf16* __restrict__ wi, int cta, F&& mid) {
  const int tid = threadIdx.x, g = (cta >> 1) & 7, c = (cta >> 4) & 3, t = 2 * (cta & 1) + (tid & 1);
  const int k0 = g + 8 * (cta >> 6) + 32 * (8 * c + 2 * t), l0 = (tid & ~1) + (g & 1);
  uint32_t a[4][4], b[4][4];
#pragma unroll
  for (int q = 0; q < 16; q++) {
    const int o = (k0 + 16 * (q >> 3) + 32 * ((q >> 1) & 1) + 1024 * (q & 1)) * 513 + l0 + 256 * ((q >> 2) & 1);
    a[q >> 2][q & 3] = ldnc32(wr + o);
    b[q >> 2][q & 3] = ldnc32(wi + o);
  }
  mid();
  uint4* dst = g_wt + l0 * 512 + cta * 2 + (tid & 1);
#pragma unroll
  for (int q = 0; q < 8; q++) {
    const int hf = q >> 1, l = l0 + 256 * (hf & 1) + (q & 1);
    const uint32_t sel = (q & 1) ? 0x7632 : 0x5410;
    if (l & 511) dst[(256 * (hf & 1) + (q & 1)) * 512 + 256 * (q >> 2)] = make_uint4(__byte_perm(a[hf][0], b[hf][0], sel), __byte_perm(a[hf][1], b[hf][1], sel),
                                                                                   __byte_perm(a[hf][2], b[hf][2], sel), __byte_perm(a[hf][3], b[hf][3], sel));
  }
  if (tid < 32) {
    const int e = cta * 32 + tid, l = (e >> 11) * 512, k = e & 2047, kn = (2048 - k) & 2047, k2 = (k >> 5) & 31;
    const float re = 0.5f * (__bfloat162float(wr[k * 513 + l]) + __bfloat162float(wr[kn * 513 + l]));
    const float im = 0.5f * (__bfloat162float(wi[k * 513 + l]) - __bfloat162float(wi[kn * 513 + l]));
    reinterpret_cast<uint32_t*>(g_wt)[(64 * ((k >> 3) & 3) + 16 * (k2 >> 3) + 2 * (k & 7) + ((k2 >> 2) & 1)) * 8 + l * 2048 + 2 * (k2 & 3) + (k >> 10)] = pack2(re, im);
  }
}

template <class F>
__device__ __forceinline__ void fft_rows_fwd(const bf16* __restrict__ x, const bf16* __restrict__ wr, const bf16* __restrict__ wi, uint32_t tb, int it, F&& mid) {
  const int warp = threadIdx.x >> 5, lane = threadIdx.x & 31, g = lane >> 2, t = lane & 3;
  const uint32_t in = tb + warp * 4096;
  const uint32_t f0 = in + (lane >> 3) * 256 + (((lane & 7) ^ (2 * (lane >> 3))) << 4);
  const bf16* src = x + ((256 * (warp & 3) + 64 * (warp >> 2) + 128 * (it & 1) + 32 * ((it >> 4) & 1) + 8 * (it >> 5) + ((it >> 1) & 7)) * 2048 + lane * 8);
#pragma unroll
  for (int q = 0; q < 8; q++) cpa16((f0 ^ ((q >> 2) * 144)) + (q & 3) * 1024, src + q * 256);
  cpa_commit();
  fft_wprep(wr, wi, it, mid);
  Dft D; make_dft<true>(D, g, t);
  float2 tw[4][8];
#pragma unroll
  for (int q = 0; q < 32; q++) tw[q >> 3][q & 7] = cis(fidx<true>((q >> 1) & 3, g) * fidx<false>(q >> 3, 2 * t + (q & 1)), 1024);
  cpa_wait<0>(); __syncwarp();
  uint32_t a[4][2][4], y[4][2][4];
#pragma unroll
  for (int q = 0; q < 8; q++) ldsm4t(a[q & 3][q >> 2], (in + lane * 128 + ((lane & 7) << 4)) ^ (q << 4));
  float o[2][8];
#pragma unroll
  for (int i = 0; i < 4; i++) {
    dft_b(D, a[i], o);
#pragma unroll
    for (int q = 0; q < 8; q++) y[q >> 1][q & 1][i] = twid(o[0][q], o[1][q], tw[i][q].x, tw[i][q].y);
  }
  __syncthreads();
  const uint32_t w0 = tb + warp * F_TP + fidx<true>(0, g) * 128 + t * 16 + ((g & 1) << 6), wz = (g & 1) ? -64 : 64;
#pragma unroll
  for (int z = 0; z < 2; z++) {
    float o2[2][8];
    dft_b(D, y[2 * z], o); dft_b(D, y[2 * z + 1], o2);
#pragma unroll
    for (int i = 0; i < 4; i++) {
      const float sg = i < 2 ? 1.f : -1.f;
      sts128(w0 + z * wz + fidx<true>(i, 0) * 128, pack2(o[0][2 * i], sg * o[1][2 * i]), pack2(o[0][2 * i + 1], sg * o[1][2 * i + 1]),
             pack2(o2[0][2 * i], sg * o2[1][2 * i]), pack2(o2[0][2 * i + 1], sg * o2[1][2 * i + 1]));
    }
  }
  __syncthreads();
  const uint32_t ra = tb + (lane & 1) * 4 * F_TP + ((lane >> 1) + 16 * (warp ^ ((warp >> 1) & 1))) * 4;
  uint4* dst = g_y + (threadIdx.x >> 1) * 256 + (lane & 1) + it * 2;
#pragma unroll
  for (int q = 0; q < 8; q++) { const uint32_t r = ra + q * 512; dst[q * 32768] = make_uint4(lds32(r), lds32(r + F_TP), lds32(r + 2 * F_TP), lds32(r + 3 * F_TP)); }
}

__device__ __forceinline__ void fft_cols(uint32_t sb, int cta, int ncta) {
  const int warp = threadIdx.x >> 5, lane = threadIdx.x & 31, g = lane >> 2, t = lane & 3;
  const uint32_t in = sb + warp * 16384 + lane * 16, tab = sb + 131072 + lane * 16;
  auto fetch_y = [&](int l) {
#pragma unroll
    for (int q = 0; q < 16; q++) cpa16(in + q * 512, g_y + (q < 8 ? l : (1024 - l) & 1023) * 256 + (q & 7) * 32 + lane);
  };
  auto fetch_w = [&](int l) {
#pragma unroll
    for (int q = 0; q < 16; q++) cpa16(in + 8192 + q * 512, g_wt + l * 512 + q * 32 + lane);
  };
  const int l0 = cta * 8 + warp, dl = ncta * 8;
  if (l0 <= 512) fetch_y(l0);
  cpa_commit();
  if (l0 <= 512) fetch_w(l0);
  cpa_commit();
  Dft D; make_dft<false>(D, g, t);
#pragma unroll
  for (int q = 2 * warp; q < 2 * warp + 2; q++) {
    const int r = fidx<false>(q & 3, g), c = fidx<false>(q >> 2, 2 * t);
    const float2 w0 = cis(r * c, 1024), w1 = cis(r * c + r, 1024), p0 = cis(r + 32 * c, 2048), p1 = cis(r + 32 * c + 32, 2048);
    sts128(tab + q * 512, __float_as_uint(w0.x), __float_as_uint(w0.y), __float_as_uint(w1.x), __float_as_uint(w1.y));
    sts128(tab + 8192 + q * 512, __float_as_uint(p0.x), __float_as_uint(p0.y), __float_as_uint(p1.x), __float_as_uint(p1.y));
  }
  if (warp == 0) {
#pragma unroll
    for (int q = 0; q < 8; q++) {
      const int v = q >> 2, b = (q >> 1) & 1, ri = q & 1;
      sts128(tab + 16384 + q * 512, D.m[b][0][ri][v], D.m[b][0][ri][v + 2], D.m[b][1][ri][v], D.m[b][1][ri][v + 2]);
    }
  }
  __syncthreads();
#pragma unroll 1
  for (int l = l0; l <= 512; l += dl) {
    uint32_t a[2][4][2][4], y[2][4][2][4];
    float o[2][2][8];
    cpa_wait<1>();
#pragma unroll
    for (int q = 0; q < 16; q++) lds128(a[q >> 3][(q >> 1) & 3][q & 1], in + q * 512);
    if (!(l & 511)) {
      const uint32_t m0 = l ? 0x80000000u : 0u;
#pragma unroll
      for (int q = 0; q < 32; q++) { a[0][q >> 3][(q >> 2) & 1][q & 3] ^= m0; a[1][q >> 3][(q >> 2) & 1][q & 3] ^= m0 ^ 0x80000000u; }
    }
    auto first = [&]() {
#pragma unroll
      for (int i = 0; i < 4; i++) {
        dft_b(D, a[0][i], o[0]); dft_b(D, a[1][i], o[1]);
#pragma unroll
        for (int r = 0; r < 4; r++) {
          const float4 w = lds128f(tab + (4 * i + r) * 512);
#pragma unroll
          for (int s = 0; s < 2; s++) {
            y[s][r][0][i] = twid(o[s][0][2 * r], o[s][1][2 * r], w.x, w.y);
            y[s][r][1][i] = twid(o[s][0][2 * r + 1], o[s][1][2 * r + 1], w.z, w.w);
          }
        }
      }
    };
    first();
    if (l + dl <= 512) fetch_y(l + dl);
    cpa_commit();
    cpa_wait<1>();
#pragma unroll
    for (int zv = 0; zv < 4; zv++) {
      const int z = zv >> 1, v = zv & 1;
      uint32_t m[2][2][4];
#pragma unroll
      for (int q = 0; q < 4; q++) lds128(m[q >> 1][q & 1], tab + 16384 + (4 * v + q) * 512);
      dft_a(m, y[0][2 * z], y[0][2 * z + 1], o[0]); dft_a(m, y[1][2 * z], y[1][2 * z + 1], o[1]);
#pragma unroll
      for (int q = 0; q < 4; q++) {
        const int i = 2 * z + (q & 1), c = v + (q & 2);
        uint32_t w[4]; lds128(w, in + 8192 + (4 * i + c) * 512);
        const float4 ph = lds128f(tab + 8192 + (4 * c + i) * 512);
#pragma unroll
        for (int b = 0; b < 2; b++) {
          const float cs = b ? ph.z : ph.x, sn = b ? ph.w : ph.y;
          const float r1 = __uint_as_float(w[2 * b] << 16), i1 = __uint_as_float(w[2 * b] & 0xFFFF0000u);
          const float r2 = __uint_as_float(w[2 * b + 1] << 16), i2 = __uint_as_float(w[2 * b + 1] & 0xFFFF0000u);
          const float Sr = r1 + r2, Si = i1 + i2, Dr = r1 - r2, Di = i1 - i2;
          const float ar = fmaf(-Dr, sn, Sr), ai = fmaf(-Di, sn, Si), dr = fmaf(Dr, sn, Sr), di = fmaf(Di, sn, Si), br = -Di * cs, bi = Dr * cs;
          const float Ar = o[0][0][2 * q + b], Ai = o[0][1][2 * q + b], Br = o[1][0][2 * q + b], Bi = o[1][1][2 * q + b];
          a[0][i][b][c] = pack2(fmaf(ar, Ai, fmaf(ai, Ar, fmaf(br, Bi, bi * Br))), fmaf(ar, Ar, fmaf(-ai, Ai, fmaf(br, Br, -bi * Bi))));
          a[1][i][b][c] = pack2(fmaf(dr, Bi, fmaf(di, Br, fmaf(-br, Ai, -bi * Ar))), fmaf(dr, Br, fmaf(-di, Bi, fmaf(-br, Ar, bi * Ai))));
        }
      }
    }
    if (l + dl <= 512) fetch_w(l + dl);
    cpa_commit();
    first();
#pragma unroll
    for (int s = 0; s < 2; s++) {
      uint4* dst = g_y + (s ? (1024 - l) & 1023 : l) * 256 + lane;
      const float sg = s ? -1.f : 1.f;
#pragma unroll
      for (int i = 0; i < 4; i++) {
        dft_b(D, y[s][i], o[0]);
#pragma unroll
        for (int b = 0; b < 2; b++)
          dst[(2 * i + b) * 32] = make_uint4(pack2(sg * o[0][0][b], o[0][1][b]), pack2(sg * o[0][0][2 + b], o[0][1][2 + b]),
                                             pack2(sg * o[0][0][4 + b], o[0][1][4 + b]), pack2(sg * o[0][0][6 + b], o[0][1][6 + b]));
      }
    }
  }
}

__device__ __forceinline__ void fft_rows_inv(const CUtensorMap* om, uint32_t sb, int cta, int ncta) {
  const int warp = threadIdx.x >> 5, lane = threadIdx.x & 31, g = lane >> 2, t = lane & 3, wg = warp >> 2, w4 = warp & 3;
  const uint32_t tb = sb + 32768 + wg * 2 * F_TSZ;
  const uint4* src = g_y + pin((256 * ((lane >> 1) & 3) + 64 * (lane >> 3) + 8 * w4) * 256 + (lane & 1));
  const uint32_t wa = pin(tb + (lane & 1) * 4 * F_TP + w4 * 1024 + (lane >> 1) * 4);
  uint4 pf[8];
  auto fetch = [&](int it, int hf) {
#pragma unroll
    for (int q = 0; q < 8; q++) pf[q] = __ldcg(src + (it * 2 + hf * 8192) + q * 256);
  };
  auto put = [&](uint32_t off) {
#pragma unroll
    for (int q = 0; q < 8; q++) {
      sts32(wa + off + q * 64, pf[q].x); sts32(wa + off + q * 64 + F_TP, pf[q].y);
      sts32(wa + off + q * 64 + 2 * F_TP, pf[q].z); sts32(wa + off + q * 64 + 3 * F_TP, pf[q].w);
    }
  };
  const int it0 = 2 * cta + wg;
  if (it0 >= 128) return;
  fetch(it0, 0); put(0); fetch(it0, 1); put(512);
  Dft D; make_dft<false>(D, g, t);
  float2 tw[4][8];
#pragma unroll
  for (int q = 0; q < 32; q++) {
    tw[q >> 3][q & 7] = cis(fidx<false>((q >> 1) & 3, g) * fidx<false>(q >> 3, 2 * t + (q & 1)), 1024);
    tw[q >> 3][q & 7].x *= 1.f / 2097152.f; tw[q >> 3][q & 7].y *= 1.f / 2097152.f;
  }
  const uint32_t la = pin(tb + w4 * F_TP + lane * 16), ob = uni(sb + warp * 4096);
  const uint32_t oa = pin(ob + (lane >> 1) * 128 + (((4 * (lane & 1)) ^ ((lane >> 1) & 7)) << 4));
#pragma unroll 1
  for (int n = 0;; n++) {
    const int it = it0 + (n >> 1) * 2 * ncta, hf = n & 1, buf = (n >> 1) & 1;
    if (it >= 128) break;
    if (!hf) bar_sync(1 + wg, 128);
    uint32_t a[4][2][4], y[4][2][4];
#pragma unroll
    for (int q = 0; q < 8; q++) lds128(a[q >> 1][q & 1], la + buf * F_TSZ + hf * 4 * F_TP + q * 512);
    fetch(min(it + 2 * ncta, 127), hf);
    float o[2][8];
#pragma unroll
    for (int i = 0; i < 4; i++) {
      dft_b(D, a[i], o);
#pragma unroll
      for (int q = 0; q < 8; q++) y[q >> 1][q & 1][i] = twid(o[0][q], o[1][q], tw[i][q].x, tw[i][q].y);
    }
    if (lane == 0) asm volatile("cp.async.bulk.wait_group.read 0;" ::: "memory");
    __syncwarp();
#pragma unroll
    for (int c = 0; c < 4; c++) {
      dft_b(D, y[c], o);
#pragma unroll
      for (int ri = 0; ri < 2; ri++)
        stsm4((oa ^ (c << 4)) + (1 - ri) * 2048, pack2(o[ri][0], o[ri][1]), pack2(o[ri][2], o[ri][3]), pack2(o[ri][4], o[ri][5]), pack2(o[ri][6], o[ri][7]));
    }
    fence_async();
    __syncwarp();
    if (lane == 0) {
      const int m = 256 * w4 + 32 * ((it >> 1) & 7) + 8 * (it >> 5) + 4 * (it & 1) + 2 * hf + ((it >> 4) & 1);
      asm volatile("cp.async.bulk.tensor.3d.global.shared::cta.bulk_group [%0, {0, 0, %2}], [%1];" :: "l"(om), "r"(ob), "r"(2 * m) : "memory");
      asm volatile("cp.async.bulk.commit_group;" ::: "memory");
    }
    put((buf ^ 1) * F_TSZ + hf * 512);
  }
  if (lane == 0) asm volatile("cp.async.bulk.wait_group 0;" ::: "memory");
}
__device__ __forceinline__ void grid_arrive(unsigned* ctr) {
  __syncthreads();
  if (threadIdx.x == 0) { __threadfence(); atomicAdd(ctr, 1u); }
}
__device__ __forceinline__ void grid_wait(unsigned* ctr, unsigned n) {
  if (threadIdx.x == 0) {
    int it = 0;
    while (*reinterpret_cast<volatile unsigned*>(ctr) < n) { __nanosleep(200); if (++it > SPIN_LIMIT) { g_err = 3; break; } }
    __threadfence();
  }
  __syncthreads();
}

struct RecMaps { CUtensorMap wq, wk, wv, wo, x, k, q, v, fo; };
#define NSW 16
#define EXP 0
#define NPROBE 2
#define HOME 3
#define DL0 14
#define PD1 4
#define NE4 6
#define NE6 0
#define NA4 14
#define NA6 18
#define NB1 24
#define TQL 7
#define NQ 8
#define TQP (NQ - 1)
#define OXPOS 4
#define KVPOS 2
#define NK0 0
#define FLPOS 1
#define XWPOS 10
#define FSPOS 28
#define RL0 4
#define RLS 6
#define RLB 4
#define VL0 3
#define RI 9
#define RJ 8
#define NPRE 20
#define PFD 4
#define PD0 4
#define VB NV0
#define NPA 0
#define N1 16
#define DL1 16
#define PACE 0
#define RE0 0
#define RE1 0
#define RP1 23
#define UNP 1
#define X2 2
#define X3 2
#define SPOS 2
#ifndef NV0
#define NV0 4
#endif
#define TGP 3
#define FENP 0
#define LW0 8
#define X1 4
#define X0 4
constexpr int R_WO = 0, R_X = 65536, R_MEM = 131072, R_WC = 147456, R_RED = R_WC + NSW * 2048, R_O = R_RED, R_S = R_O + 2048, R_P = R_S + 3072, R_STAGE = R_P + 2048,
              R_K = R_STAGE + 8192, R_Q = R_K + 8192, R_V = R_Q + 2048, R_ID = R_V + 16384, R_T = R_ID + 512, R_DST = R_T + 512, R_RD = R_DST + 2048, R_BAR = R_RD + 2048, R_TS = R_BAR + 128,
              R_TOTAL = R_TS;
#define TS(i)
#define LOG(i, v)
constexpr int B_KV = R_BAR, B_W = R_BAR + 8, B_X = R_BAR + 80, B_PK = R_BAR + 24, B_C = R_BAR + 32, B_B = R_BAR + 40, B_DUE = R_BAR + 48, B_ONE = R_BAR + 64;
#define DLY_A 150
#define DLY_V 150
#define DLY_C 200
#define DLY_L 90
#define NS_B 1088
#define NS_C 1696
#define NS_P 2752
#define NS_V 128
#define NS_F 896
#define NS_K 128
#define NS_M 32
#define NS_X 128
#define NS_PEN 1024
__device__ __forceinline__ float rcp(float x) { float r; asm("rcp.approx.ftz.f32 %0, %1;" : "=f"(r) : "f"(x)); return r; }
__device__ __forceinline__ uint32_t movm(uint32_t a) { uint32_t d; asm volatile("movmatrix.sync.aligned.m8n8.trans.b16 %0, %1;" : "=r"(d) : "r"(a)); return d; }
__device__ __forceinline__ uint32_t hadd2(uint32_t a, uint32_t b) { uint32_t d; asm("add.rn.bf16x2 %0, %1, %2;" : "=r"(d) : "r"(a), "r"(b)); return d; }
__device__ __forceinline__ void mma_a(float (&d)[4], const uint32_t (&a)[4], uint32_t b0, uint32_t b1) { mma16816(d, a[0], a[1], a[2], a[3], b0, b1); }
__device__ __forceinline__ bool elect() {
  uint32_t p; asm volatile("{.reg .pred p; elect.sync _|p, 0xffffffff; selp.u32 %0, 1, 0, p;}" : "=r"(p)); return p; }
__device__ __forceinline__ void tma3d(uint32_t dst, const CUtensorMap* m, int c1, int c2, uint32_t bar) {
  asm volatile("cp.async.bulk.tensor.3d.shared::cluster.global.mbarrier::complete_tx::bytes [%0], [%1, {0, %3, %4}], [%2];"
    :: "r"(dst), "l"(m), "r"(bar), "r"(c1), "r"(c2) : "memory"); }
__device__ __forceinline__ void tma4d(uint32_t dst, const CUtensorMap* m, int c1, int c2, uint32_t bar) {
  asm volatile("cp.async.bulk.tensor.4d.shared::cluster.global.mbarrier::complete_tx::bytes [%0], [%1, {0, %3, %4, 0}], [%2];"
    :: "r"(dst), "l"(m), "r"(bar), "r"(c1), "r"(c2) : "memory"); }
template <int OFF, int ACC>
__device__ __forceinline__ void wg_rs32(float (&d)[16], const uint32_t (&a)[4], uint32_t db) {
  if (ACC)
    asm volatile("{.reg .b64 db; .reg .b32 lo; add.u32 lo, %20, %21; mov.b64 db, {lo, 0x40000040};\n"
      "wgmma.mma_async.sync.aligned.m64n32k16.f32.bf16.bf16 {%0,%1,%2,%3,%4,%5,%6,%7,%8,%9,%10,%11,%12,%13,%14,%15}, {%16,%17,%18,%19}, db, 1, 1, 1, 0;}"
      : "+f"(d[0]), "+f"(d[1]), "+f"(d[2]), "+f"(d[3]), "+f"(d[4]), "+f"(d[5]), "+f"(d[6]), "+f"(d[7]), "+f"(d[8]), "+f"(d[9]), "+f"(d[10]), "+f"(d[11]), "+f"(d[12]), "+f"(d[13]), "+f"(d[14]), "+f"(d[15])
      : "r"(a[0]), "r"(a[1]), "r"(a[2]), "r"(a[3]), "r"(db), "n"(OFF));
  else
    asm volatile("{.reg .b64 db; .reg .b32 lo; add.u32 lo, %20, %21; mov.b64 db, {lo, 0x40000040};\n"
      "wgmma.mma_async.sync.aligned.m64n32k16.f32.bf16.bf16 {%0,%1,%2,%3,%4,%5,%6,%7,%8,%9,%10,%11,%12,%13,%14,%15}, {%16,%17,%18,%19}, db, 0, 1, 1, 0;}"
      : "=f"(d[0]), "=f"(d[1]), "=f"(d[2]), "=f"(d[3]), "=f"(d[4]), "=f"(d[5]), "=f"(d[6]), "=f"(d[7]), "=f"(d[8]), "=f"(d[9]), "=f"(d[10]), "=f"(d[11]), "=f"(d[12]), "=f"(d[13]), "=f"(d[14]), "=f"(d[15])
      : "r"(a[0]), "r"(a[1]), "r"(a[2]), "r"(a[3]), "r"(db), "n"(OFF));
}
template <int I> using IC = std::integral_constant<int, I>;
template <int I, int N, class F> __device__ __forceinline__ void sfor(F&& f) {
  if constexpr (I < N) { f(std::integral_constant<int, I>{}); sfor<I + 1, N>(f); }
}
__device__ __forceinline__ void keep(float (&d)[16]) {
  asm volatile("" : "+f"(d[0]), "+f"(d[1]), "+f"(d[2]), "+f"(d[3]), "+f"(d[4]), "+f"(d[5]), "+f"(d[6]), "+f"(d[7]),
      "+f"(d[8]), "+f"(d[9]), "+f"(d[10]), "+f"(d[11]), "+f"(d[12]), "+f"(d[13]), "+f"(d[14]), "+f"(d[15]) :: "memory");
}

template <int N, int S2 = 1024> __device__ __forceinline__ void ldx(uint32_t (&v)[N][4], const uint8_t* p) {
#pragma unroll
  for (int k = 0; k < 2 * N; k++) {
    const int i = k;
    asm volatile("ld.relaxed.gpu.global.v2.b32 {%0,%1}, [%2];" : "=r"(v[i >> 1][2 * (i & 1)]), "=r"(v[i >> 1][2 * (i & 1) + 1]) : "l"(p + (i & 3) * 256 + (i >> 2) * S2) : "memory");
  }
}
__device__ __forceinline__ uint32_t dif2(uint32_t a, uint32_t b, uint32_t tag) { uint32_t r; asm("lop3.b32 %0, %1, %2, %3, 0x7e;" : "=r"(r) : "r"(a), "r"(b), "r"(tag)); return r; }
__device__ __forceinline__ uint32_t dif2v(uint32_t a, uint32_t b, uint32_t tag) { uint32_t r; asm volatile("lop3.b32 %0, %1, %2, %3, 0x7e;" : "=r"(r) : "r"(a), "r"(b), "r"(tag)); return r; }
__device__ __forceinline__ uint32_t or3(uint32_t a, uint32_t b, uint32_t c) { uint32_t r; asm("lop3.b32 %0, %1, %2, %3, 0xfe;" : "=r"(r) : "r"(a), "r"(b), "r"(c)); return r; }
__device__ __forceinline__ uint32_t after(uint32_t x, float f, uint32_t z) { uint32_t r; asm("lop3.b32 %0, %1, %2, %3, 0xea;" : "=r"(r) : "r"(__float_as_uint(f)), "r"(z), "r"(x)); return r; }
__device__ __forceinline__ bool any_bit(uint32_t a, uint32_t b, uint32_t m) {
  uint32_t r; asm("lop3.b32 %0, %1, %2, %3, 0xa8;" : "=r"(r) : "r"(a), "r"(b), "r"(m)); return __any_sync(0xffffffffu, r); }
template <int W, int N> __device__ __forceinline__ bool stale(const uint32_t (&v)[N][4], uint32_t tag) {
  uint32_t x = dif2(v[0][0], v[0][2], tag);
  if (N == 4) x = or3(x, dif2(v[1][0], v[1][2], tag), dif2(v[2 % N][0], v[2 % N][2], tag));
  return any_bit(x, dif2(v[N - 1][0], v[N - 1][2], tag), 1);
}
template <int W, int N, int S2 = 1024> __device__ __forceinline__ void retry(uint32_t (&v)[N][4], const uint8_t* p, uint32_t tag, int& it) {
#pragma unroll 1
  do { ldx<N, S2>(v, p); it += INC_A; } while (stale<W>(v, tag) && it < SPIN_LIMIT);
}
__device__ __forceinline__ void mma_h(float (&d)[4], const uint32_t (&a)[4], const uint32_t (&b)[4], int hf) { mma16816(d, a[0], a[1], a[2], a[3], b[2 * hf], b[2 * hf + 1]); }
__device__ __forceinline__ void sts128(uint32_t a, const uint32_t (&r)[4]) { sts128(a, r[0], r[1], r[2], r[3]); }
__device__ __forceinline__ void sts128f(uint32_t a, const float* r) { sts128(a, __float_as_uint(r[0]), __float_as_uint(r[1]), __float_as_uint(r[2]), __float_as_uint(r[3])); }
__device__ __forceinline__ void mbar_spin(uint32_t bar, uint32_t par, int& it) {
  asm volatile("{.reg .pred p; .reg .b32 par; mov.b32 par, %2;\nLOOP: mbarrier.try_wait.parity.shared::cta.b64 p, [%1], par; @p bra.uni DONE;\n"
               "add.s32 %0, %0, 1; setp.le.s32 p, %0, %3; @p bra.uni LOOP;\nDONE: }" : "+r"(it) : "r"(bar), "r"(par), "n"(SPIN_LIMIT) : "memory"); }
__device__ __forceinline__ void warp_arrive(uint32_t bar) {
  __syncwarp(); asm volatile("{.reg .pred p; elect.sync _|p, 0xffffffff; @p mbarrier.arrive.shared::cta.b64 _, [%0];}" :: "r"(bar) : "memory"); }
__device__ __forceinline__ void delay_until(unsigned t) {
  asm volatile("{.reg .pred p; .reg .b64 c; .reg .b32 lo, hi;\nLOOP: mov.u64 c, %%clock64; mov.b64 {lo, hi}, c; sub.s32 lo, lo, %0; setp.lt.s32 p, lo, 0; @p bra.uni LOOP;}" :: "r"(t) : "memory"); }
__device__ __forceinline__ void cut(int it) { asm volatile("{.reg .pred p; setp.lt.s32 p, %0, 0;\nL: @p st.volatile.shared.u32 [%0], %0; @p bra.uni L;}" :: "r"(it) : "memory"); }
__device__ __forceinline__ void zero(float (&c)[4][4]) {
#pragma unroll
  for (int i = 0; i < 4; i++) c[i][0] = c[i][1] = c[i][2] = c[i][3] = 0.f;
}

__device__ __forceinline__ void sched() { asm volatile("griddepcontrol.launch_dependents;" ::: "memory"); }
__device__ __forceinline__ const uint8_t* pinp(const uint8_t* p) { return reinterpret_cast<const uint8_t*>(__shfl_xor_sync(0xffffffffu, reinterpret_cast<unsigned long long>(p), 0)); }
__device__ __forceinline__ uint32_t bar_or(int id, uint32_t x) {
  uint32_t r; asm volatile("{.reg .pred p, q; setp.ne.u32 p, %2, 0; bar.red.or.pred q, %1, 256, p; selp.u32 %0, 1, 0, q;}" : "=r"(r) : "r"(id), "r"(x) : "memory"); return r; }
__device__ __forceinline__ void bar_sync_unless(int id, uint32_t x) { asm volatile("{.reg .pred p; setp.eq.u32 p, %1, 0; @p bar.sync %0, 256;}" :: "r"(id), "r"((uint32_t)x) : "memory"); }
__device__ __forceinline__ void bar_arrive_unless(int id, uint32_t x) { asm volatile("{.reg .pred p; setp.eq.u32 p, %1, 0; @p bar.arrive %0, 256;}" :: "r"(id), "r"((uint32_t)x) : "memory"); }
__device__ __forceinline__ void stsm2t(uint32_t a, uint32_t r0, uint32_t r1, uint32_t x) {
  asm volatile("{.reg .pred p; setp.eq.u32 p, %3, 0; @p stmatrix.sync.aligned.m8n8.x2.trans.shared.b16 [%0], {%1,%2};}" :: "r"(a), "r"(r0), "r"(r1), "r"((uint32_t)x) : "memory"); }
__device__ __forceinline__ uint32_t or_and(uint32_t a, uint32_t b, uint32_t m) { uint32_t r; asm("lop3.b32 %0, %1, %2, %3, 0xa8;" : "=r"(r) : "r"(a), "r"(b), "r"(m)); return r; }
#define rare(x) __builtin_expect(!!(x), 0)
__device__ __forceinline__ uint32_t gtime() { unsigned long long g; asm volatile("mov.u64 %0, %%globaltimer;" : "=l"(g) :: "memory"); return (uint32_t)g; }
__device__ __forceinline__ void wait_time(uint32_t t) {
  asm volatile("{.reg .pred p; .reg .b32 g; .reg .b64 c;\nLOOP: mov.u64 c, %%globaltimer; cvt.u32.u64 g, c; sub.s32 g, %0, g; setp.lt.u32 p, g, 16384; @p bra.uni LOOP;}" :: "r"(t - 1) : "memory"); }
__device__ __forceinline__ uint32_t ldx32(const void* p) { uint32_t v; asm volatile("ld.relaxed.gpu.global.b32 %0, [%1];" : "=r"(v) : "l"(p) : "memory"); return v; }
__device__ __forceinline__ void stx32(const void* p, uint32_t v) { asm volatile("st.relaxed.gpu.global.b32 [%0], %1;" :: "l"(p), "r"(v) : "memory"); }

__global__ void __launch_bounds__(256, 1)
rec_kernel(const __grid_constant__ RecMaps maps, const bf16* __restrict__ xin, const bf16* __restrict__ mem0, Xchg* const gx,
           const bf16* __restrict__ fx, const bf16* __restrict__ wr, const bf16* __restrict__ wi) {
  extern __shared__ __align__(1024) uint8_t smem_raw[];
  const uint32_t sb = smem_u32(smem_raw);
  int role = blockIdx.x;
  {
    uint32_t smid, nsm; asm volatile("mov.u32 %0, %%smid;" : "=r"(smid)); asm volatile("mov.u32 %0, %%nsmid;" : "=r"(nsm));
    const int p = smid >> 1, u = p - 32;
    if (nsm == gridDim.x)
      role = (smid & 1) + (p < 32 ? 4 * ((p & 7) + 8 * (p >> 4)) + 2 * ((p >> 3) & 1) : p < 60 ? 4 * (16 + u % 7 + 7 * (u / 14)) + 2 * ((u / 7) & 1)
                         : p < 62 ? 2 * p + 8 : 2 * p - 4);
    role = uni(role);
  }
  if (role >= 128) {
    grid_wait(&gx->ctr[33], 128);
    fft_cols(sb, role - 128, 4);
    grid_arrive(&gx->ctr[32]); grid_wait(&gx->ctr[32], 4);
    fft_rows_inv(&maps.fo, sb, role - 128, 4);
    return;
  }
  const int tid = threadIdx.x, warp = uni(tid >> 5), lane = tid & 31, wg = warp >> 2, w4 = warp & 3, g = lane >> 2, t = lane & 3;
  const int h = role >> 2, j = role & 3, jh = j & 1;
  uint32_t w[48][4];
  float aq[16], av[16];
  int it = 0;

  fft_rows_fwd(fx, wr, wi, sb + R_MEM + 49152, role, [&]() {
    if (tid == 224) {
      mbar_init(sb + B_KV, 1); mbar_init(sb + B_W, 1); mbar_init(sb + B_X, 1); mbar_init(sb + B_X + 8, 1); mbar_init(sb + B_X + 16, 1); mbar_init(sb + B_X + 24, 1); mbar_init(sb + B_C, 4); mbar_init(sb + B_PK, 4); mbar_init(sb + B_B, 1);
      asm volatile("fence.mbarrier_init.release.cluster;" ::: "memory");
      mbar_expect_tx(sb + B_W, 3 * 65536);
      for (int i = 0; i < 4; i++) {
        tma2d(sb + R_X + i * 16384, &maps.wq, h * DH + 32 * j, i * 256, sb + B_W);
        if (i < 3) tma2d(sb + R_MEM + i * 16384, &maps.wk, h * DH + 32 * j, i * 256, sb + B_W);
        else asm volatile("cp.async.bulk.prefetch.tensor.2d.L2.global [%0, {%1, %2}];" :: "l"(&maps.wk), "r"(h * DH + 32 * j), "r"(768) : "memory");
      }
      for (int i = 0; i < 2; i++) tma2d(sb + R_WO + i * 32768, &maps.wv, h * DH + 64 * (j >> 1), jh * 512 + i * 256, sb + B_W);
      if (PFD) asm volatile("cp.async.bulk.prefetch.L2.global [%0], 2048;" :: "l"(xin + role * DM) : "memory");
      else for (int i = 0; i < 4; i++) asm volatile("cp.async.bulk.prefetch.L2.global [%0], 8192;" :: "l"(xin + role * 16384 + i * 4096) : "memory");
      for (int i = 0; i < 4; i++)
        asm volatile("cp.async.bulk.prefetch.tensor.2d.L2.global [%0, {%1, %2}];" :: "l"(&maps.wo), "r"(256 * j + 64 * i), "r"(h * DH) : "memory");
    }
    __syncwarp();
  });
  if (tid < 128) asm volatile("prefetch.global.L2 [%0];" :: "l"(mem0 + tid * 64));
  if (tid < 16) sts32(sb + R_T + tid * 4, ~0u);
  fence_async();
  grid_arrive(&gx->ctr[33]);
  if (tid == 224) tma2d(sb + R_MEM + 49152, &maps.wk, h * DH + 32 * j, 768, sb + B_W);
  __syncwarp();
  uint8_t* const xb = reinterpret_cast<uint8_t*>(gx);
  auto probe_at = [&](int n) { return xb + (n ? offsetof(Xchg, C) + w4 * 8192 + role * 32 : offsetof(Xchg, B) + role * 8192 + warp * 128); };
  if (lane < 8) stx128(probe_at(lane >> 2) + (lane & 2) * 2048 + (lane & 1) * 16, 0, 0, 0, 0);
  mbar_spin(sb + B_W, 0, it);
  const int lrow = (lane & 7) + ((lane >> 4) << 3), lhi = (lane >> 3) & 1;
  const int kq = wg ? 3 - 3 * jh : 3 * jh;
  const uint32_t LW = lrow * 128 + ((lhi ^ (lane & 7)) << 4);
  {
    const int chunk = w4 < 2 ? w4 + 2 * lhi : 2 * (w4 & 1) + lhi;
    uint32_t a = sb + (w4 < 2 ? R_X : R_MEM) + kq * 16384 + lrow * 64 + ((chunk ^ ((lrow >> 1) & 3)) << 4);
#pragma unroll
    for (int i = 0; i < 16; i++) ldsm4t(w[i], a + i * 1024);
    const uint32_t st = wg ? 1024 : 2048, av0 = sb + R_WO + (LW ^ (w4 << 5));
    const uint32_t a1 = wg ? a + (2 * jh - 1) * 16384 : av0 + jh * 32768, a2 = wg ? a + (2 * jh - 1) * 32768 : av0 + (1 - jh) * 32768;
#pragma unroll
    for (int i = 0; i < 16; i++) { ldsm4t(w[16 + i], a1 + i * st); ldsm4t(w[32 + i], a2 + i * st); }
  }
  uint32_t L16 = pin(lane * 16);
  const uint32_t uW = uni(sb + w4 * 512), uWo = uni(sb + R_WO + w4 * 16384), uMem = uni(sb + R_MEM + kq * 4096);
  const uint32_t dX = uni(((sb + R_X + kq * 16384) >> 4) | 0x10000u);
  auto load_wo = [&](uint32_t (&d)[32][4], int i0, int i1) {
#pragma unroll
    for (int i = i0; i < i1; i++) lds128(d[i], uWo + L16 + (i & 1) * 512 + (i >> 4) * 1024 + (i & 14) * 1024);
  };
  auto issue_x = [&](int n, int k) {
    const uint32_t bar = sb + B_X + 8 * k, q = k ^ (3 - 3 * jh);
    mbar_expect_tx(bar, 16384); tma3d(sb + R_X + q * 16384, &maps.x, n * SEG, 4 * q, bar);
  };
  auto store_stage = [&](int n) {
    asm volatile("cp.async.bulk.global.shared::cta.bulk_group [%0], [%1], 8192; cp.async.bulk.commit_group;"
                 :: "l"(g_kqv[n & 3][role]), "r"(sb + R_STAGE) : "memory");
  };
  auto issue_kqv = [&](int n) {
    const int p = (n & 3) * 128 + 4 * h;
    mbar_expect_tx(sb + B_KV, 26624);
    tma3d(sb + R_K, &maps.k, 0, p, sb + B_KV); tma3d(sb + R_Q, &maps.q, 8 + 2 * j, p, sb + B_KV); tma3d(sb + R_V, &maps.v, 16, p, sb + B_KV);
  };
  auto fetch4k = [&](uint32_t dst, uint32_t off, uint32_t bar, uint32_t t) {
    asm volatile("{.reg .pred p, q; .reg .b32 g; .reg .b64 c; elect.sync _|q, 0xffffffff; @q mbarrier.arrive.expect_tx.shared::cta.b64 _, [%2], 4096;\n"
                 "LOOP: mov.u64 c, %%globaltimer; cvt.u32.u64 g, c; sub.s32 g, %3, g; setp.lt.u32 p, g, 16384; @p bra.uni LOOP;\n"
                 "@q cp.async.bulk.shared::cluster.global.mbarrier::complete_tx::bytes [%0], [%1], 4096, [%2];}" :: "r"(dst), "l"(xb + off), "r"(bar), "r"(t - 1) : "memory");
  };
  uint32_t uS;
  auto my_b = [&]() { return offsetof(Xchg, B) + role * 8192 + ((uS + ((uint32_t)it >> 31)) & 1) * 4096; };
  auto issue_c = [&](uint32_t t) { fetch4k(sb + R_MEM + w4 * 4096, offsetof(Xchg, C) + w4 * 8192 + ((uS + ((uint32_t)it >> 31)) & 4096), sb + B_C, t); };
  auto wait_x = [&](int n, int i) { if (!(EXP & 1) || n < 2) mbar_spin(sb + B_X + 8 * i, n & 1, it); };
#define PACED(d0) uint32_t dz = d0; const uint32_t z = (uint32_t)it >> 31; auto pace = [&]() { for (int k = 0; k < PACE; k++) { if (k & 1) asm("add.u32 %0, %0, %1;" : "+r"(dz) : "r"(z)); else asm("xor.b32 %0, %0, %1;" : "+r"(dz) : "r"(z)); } };
  auto project_v = [&](auto I0, auto I1, auto&& mid) {
    PACED(decltype(I0)::value < 16 ? dX : dX ^ 1024);
    wg_fence();
    sfor<decltype(I0)::value, decltype(I1)::value>([&](auto I) {
      constexpr int i = decltype(I)::value;
      mid(i);
      if (i == 16 && decltype(I0)::value < 16) dz ^= 1024;
      wg_rs32<((i >> 2) & 3) * 256 + (i & 3) * 2, (i > 0)>(av, w[16 + i], dz);
      pace();
    });
    wg_commit();
  };
  auto project_qk = [&](auto I0, auto I1, auto first, auto&& mid) {
    PACED((dX ^ (decltype(I0)::value >> 4 << 10)) + ((uint32_t)it >> 31));
    wg_fence();
    sfor<decltype(I0)::value, decltype(I1)::value>([&](auto I) {
      constexpr int i = decltype(I)::value;
      mid(i);
      wg_rs32<((i >> 2) & 3) * 256 + (i & 3) * 2, !decltype(first)::value || i != decltype(I0)::value>(aq, w[i], dz);
      pace();
    });
    wg_commit();
  };
  const uint32_t uP = uni(sb + R_X + 3 * jh * 16384 + w4 * 512);
  auto park = [&]() {
    bar_sync(1, 128);
#pragma unroll
    for (int i = 0; i < 4; i++) sts128f(uP + L16 + i * 2048, aq + 4 * i);
    warp_arrive(sb + B_PK);
  };
  auto unpark = [&]() {
#pragma unroll
    for (int i = 0; i < 4; i++) {
      const float4 p = lds128f(uP + L16 + i * 2048);
      av[4 * i] = p.x; av[4 * i + 1] = p.y; av[4 * i + 2] = p.z; av[4 * i + 3] = p.w;
    }
  };
  auto fin_qk = [&]() {
#pragma unroll
    for (int i = 0; i < 16; i++) aq[i] += av[i];
    const uint32_t a = sb + R_STAGE + (w4 < 2 ? 2048 + w4 * 128 : (w4 & 1) * 256) + (L16 & 112) + (L16 >> 7) * 512;
    stsm4t(a, pack2(aq[0], aq[1]), pack2(aq[4], aq[5]), pack2(aq[8], aq[9]), pack2(aq[12], aq[13]));
    stsm4t(a + (w4 < 2 ? 256 : 128), pack2(aq[2], aq[3]), pack2(aq[6], aq[7]), pack2(aq[10], aq[11]), pack2(aq[14], aq[15]));
  };
  auto fin_v = [&]() {
#pragma unroll
    for (int a = 0; a < 2; a++)
      sts128(sb + R_STAGE + 4096 + w4 * 1024 + a * 512 + L16, pack2(av[8 * a], av[8 * a + 1]), pack2(av[8 * a + 2], av[8 * a + 3]),
             pack2(av[8 * a + 4], av[8 * a + 5]), pack2(av[8 * a + 6], av[8 * a + 7]));
  };
  __syncthreads();
  if (tid == 224) {
#pragma unroll 1
    for (int i = 0; i < 4; i++) issue_x(0, i);
    mbar_expect_tx(sb + B_W, 65536);
    for (int i = 0; i < 4; i++) tma2d(sb + R_WO + i * 16384, &maps.wo, 256 * j + 64 * i, h * DH, sb + B_W);
  }
  __syncwarp();
  if (wg) {
#pragma unroll
    for (int i = 0; i < NSW; i++) sts128(uW + R_WC + L16 + i * 2048, w[i]);
  }
#pragma unroll
  for (int i = 0; i < 4; i++) {
    const uint32_t* p = reinterpret_cast<const uint32_t*>(mem0 + g * DM + 128 * warp + 32 * i + 2 * t);
    sts128(sb + R_MEM + warp * 2048 + i * 512 + (g >> 1) * 128 + t * 32 + (g & 1) * 16, __ldg(p), __ldg(p + 4), __ldg(p + 8), __ldg(p + 12));
  }
#pragma unroll 1
  for (int n = 0; n < 2; n++) {
    if (lane == 0) {
#pragma unroll 1
      for (int i = role >> 7; i < 2 * NPROBE; i++) {
        const int k = (i ^ wg) & 1;
        const unsigned t0 = clk();
        uint32_t v; asm volatile("atom.relaxed.gpu.global.exch.b32 %0, [%1], 0;" : "=r"(v) : "l"(probe_at(n) + k * 4096) : "memory");
        if (v == 0) asm volatile("red.shared.min.u32 [%0], %1;" :: "r"(sb + R_T + (n ? w4 * 8 : 32) + k * 4), "r"(clk() - t0) : "memory");
      }
    }
    __syncwarp();
    wait_x(n, 2);
    if (wg == 0) {
      wait_x(n, 3);
      project_qk(IC<0>{}, IC<16>{}, IC<1>{}, [](int) {});
      project_v(IC<0>{}, IC<32>{}, [](int) {});
      if (tid == 96 && n == 1) {
        asm volatile("cp.async.bulk.wait_group 0;" ::: "memory");
        __threadfence(); atomicAdd(&gx->ctr[h], 1u);
      }
      __syncwarp();
      wg_wait<0>(); keep(aq); keep(av);
      park();
      fin_v();
      fence_async();
    } else {
      wait_x(n, 0); wait_x(n, 1);
      project_qk(IC<32>{}, IC<48>{}, IC<1>{}, [](int) {});
      project_qk(IC<16>{}, IC<32>{}, IC<0>{}, [](int) {});
      project_qk(IC<0>{}, IC<16>{}, IC<0>{}, [](int) {});
      mbar_spin(sb + B_PK, n, it);
      unpark();
      wg_wait<0>(); keep(aq);
      fin_qk();
      fence_async();
      if (tid == 128 && n == 1) {
        for (int k = 0; *reinterpret_cast<volatile unsigned*>(&gx->ctr[h]) < 4 && k < SPIN_LIMIT; k++) {}
        __threadfence(); asm volatile("fence.proxy.async;" ::: "memory");
        issue_kqv(0);
      }
    }
    __syncthreads();
    uS = uni((HOME & 1 ? lds32(sb + R_T + w4 * 8 + 4) < lds32(sb + R_T + w4 * 8) : j >> 1) * 4096 + (HOME & 2 && lds32(sb + R_T + 36) < lds32(sb + R_T + 32)));
    if (tid == 0) stx32(&gx->S[role], 1 + (uS & 1));
    if (tid == 96 && n == 0) store_stage(0);
    if (tid == 128 && n == 0) {
#pragma unroll 1
      for (int i = 0; i < 4; i++) issue_x(1, i);
    }
    __syncwarp();
  }
  mbar_spin(sb + B_W, 1, it);
#pragma unroll
  for (int i = 0; i < 4; i++) {
    uint32_t f[4][4];
    const uint32_t a = sb + R_WO + warp * 8192 + i * 2048;
#pragma unroll
    for (int q = 0; q < 4; q++) ldsm4t(f[q], a + (LW ^ (q << 5)));
    __syncwarp();
#pragma unroll
    for (int q = 0; q < 4; q++) sts128(a + q * 512 + L16, f[q]);
  }
  {
    const int o = 32 * w4 + 16 * wg + 4 * t + j;
    uint32_t v;
#pragma unroll 1
    while (__any_sync(0xffffffffu, (v = ldx32(&gx->S[o])) == 0) && ++it < SPIN_LIMIT) {}
    asm volatile("st.shared.u64 [%0], %1;" :: "r"(sb + R_DST + wg * 1024 + w4 * 256 + lane * 8), "l"(xb + offsetof(Xchg, B) + o * 8192 + (v >> 1) * 4096 + h * 128 + ((g ^ h) & 7) * 16) : "memory");
  }
  if (wg == 0) {
    const uint64_t cd = reinterpret_cast<uint64_t>(xb + (offsetof(Xchg, C) + j * 8192 + h * 128 + w4 * 32 + (L16 & 16) * 256 + (L16 & 64) / 4 + (L16 >> 7) * 4));
    sts128(uW + R_RD + L16, (uint32_t)cd, (uint32_t)(cd >> 32), sb + R_MEM + (L16 & 112) * 8 + (L16 >> 8) * 1024 + ((w4 * 32 + ((L16 >> 3) & 16)) ^ (L16 & 112)),
           (L16 >> 6) == (h & 3) * 2 + ((h >> 2) & 1) ? 0xFFFE0000u : 0xFFFFFFFFu);
  }
  mbar_spin(sb + B_KV, 0, it);
  if (tid == 0) sts32(sb + B_DUE + 8, gtime() & ~31u);
  if (tid < 4) sts32(sb + B_ONE + tid * 4, 0x3F803F80u);
  if (warp == 1) { const uint32_t e = g >> 1 == t ? 0x3F80u << (16 * (g & 1)) : 0u; sts128(sb + R_ID + L16, e, 0, 0, e); }
  __syncthreads();

  const float sc = 0.08838834764831845f * 1.4426950408889634f;
  uint8_t* const xa = xb + uni(h * 16384);
  const uint32_t uA = uni(wg ? (w4 >> 1) * 2048 + j * 512 + (w4 & 1) * 256 : 8192 + (4 * (j >> 1) + w4) * 512 + jh * 256);
  const uint32_t uP2 = uni(sb + R_P + w4 * 256);
  uint32_t nc = 1;
  uint32_t ma;
  const uint8_t* adst;
  auto pin_mem = [&]() { adst = pinp(xa + uA + L16 / 2); ma = pin(uMem + (L16 & 384) + (L16 & 48) * 2 + (L16 & 64) / 4); };
  pin_mem();

#pragma unroll 1
  for (int s = 0;; nc++) {
    const uint32_t tag = (s + 1) & 1;
    auto fresh = [&]() { L16 += (uint32_t)it >> 31; };
    auto get_due = [&]() { return lds32(sb + B_DUE + 4 + tag * 4); };
    float c[4][4], r4[4];
    auto fold = [&]() {
#pragma unroll
      for (int i = 0; i < 4; i++) r4[i] = ((c[0][i] + c[1][i]) + c[2][i]) + c[3][i];
    };
    auto mma4 = [&](int n, const uint32_t (&b0)[4], const uint32_t (&b1)[4]) {
      mma_h(c[0], w[n + 2], b1, 0); mma_h(c[1], w[n + 3], b1, 1); mma_h(c[2], w[n], b0, 0); mma_h(c[3], w[n + 1], b0, 1);
    };
    auto xpos = [&](int pos, int wp) {
      if ((pos == X0 || pos == X1 || pos == X2 || pos == X3) && warp == wp && s + 1 < NSEG && elect()) {
        const int z = (uint32_t)it >> 31;
        if (pos == X2) issue_x(s + 2, 2 + z);
        if (pos == X3) issue_x(s + 2, 3 + z);
        if (pos == X1) issue_x(s + 2, 1 + z);
        if (pos == X0) issue_x(s + 2, z);
      }
      __syncwarp();
    };
    if (wg == 0) {
      mbar_spin(sb + B_C, nc & 1, it);
      TS(13);
      uint32_t b[16][4], tg[4];
#pragma unroll
      for (int i = 0; i < PD0; i++) { lds128(b[i], ma + i * 512); __syncwarp(); }
      sched();
      zero(c);
#pragma unroll
      for (int i = 0; i < 8; i++) {
        const int k = i ^ 1;
        mma_h(c[0], w[2 * k], b[k], 0); mma_h(c[1], w[2 * k + 1], b[k], 1);
        if (i < 2 * NV0) { mma_h(c[2], w[16 + 2 * k], b[k], 0); mma_h(c[3], w[17 + 2 * k], b[k], 1); }
        sched();
        if ((i & 1) && i + PD0 < 9) { lds128(b[i + PD0 - 1], ma + (i + PD0 - 1) * 512); __syncwarp(); lds128(b[i + PD0], ma + (i + PD0) * 512); sched(); }
        if (i == TGP) {
          fresh();
#pragma unroll
          for (int k = 0; k < 4; k++) tg[k] = lds32((uW * 4 + L16) * 2 + (L16 >> 6) * 4 + (R_MEM + k * 1024 - 7 * sb));
          sched();
        }
      }
#pragma unroll
      for (int i = 0; i < 4; i++) { r4[i] = c[0][i] + c[1][i]; c[0][i] = c[1][i] = 0.f; }
      sts128f(uW + R_RED + L16, r4);
      TS(1);
      const uint32_t old = bar_or(4, (dif2(tg[0], tg[1], s) | dif2(tg[2], tg[3], s)) & (s > 0));
      TS(0);
#pragma unroll
      for (int i = 0; i < 2 * NV0; i++) { lds128(b[8 + i], (ma ^ 4096) + i * 512); __syncwarp(); }
      sched();
#pragma unroll
      for (int i = NV0; i < 8; i++) {
        if (VB && i == VB) bar_sync(7, 256);
        mma4(16 + 4 * i, b[2 * i], b[2 * i + 1]);
        if (i < 7) sched();
        if (i < 4) { lds128(b[8 + 2 * i], (ma ^ 4096) + i * 1024); __syncwarp(); lds128(b[9 + 2 * i], (ma ^ 4096) + i * 1024 + 512); sched(); }
      }
      fold();
      asm volatile("{.reg .pred p; setp.eq.u32 p, %3, 0; @p st.relaxed.gpu.global.v2.b32 [%0], {%1,%2};}" :: "l"(adst), "r"((pack2(r4[0], r4[1]) & ~1u) | tag), "r"(pack2(r4[2], r4[3])), "r"(old) : "memory");
      sched();
      const unsigned tpub = clk();
      if (__any_sync(0xffffffffu, old) && nc < NC_MAX) {
        bar_sync(3, 256);
        issue_c(gtime());
        continue;
      }
      TS(3);
      xpos(0, 0);
      const uint32_t due = get_due();
      uint32_t vf[4][4], vm[2][4], p[4], pm, o[4];
      const uint32_t va = sb + R_V + (w4 >> 1) * 8192 + (w4 & 1) * 2048 + L16;
#pragma unroll
      for (int i = 0; i < 4; i++) {
        uint32_t q[4]; lds128(vf[i], va + i * 512); lds128(q, va + 4096 + i * 512);
#pragma unroll
        for (int e = 0; e < 4; e++) vf[i][e] = hadd2(vf[i][e], q[e]);
      }
      const uint32_t pa = pin(sb + R_P + (L16 >> 1));
      const uint8_t* vsrc = pinp(xa + 8192 + w4 * 1024 + L16 / 2);
      uint32_t one[4];
      lds128(one, sb + B_ONE);
      auto pv_x = [&]() {
        zero(c);
        mma_a(c[2], one, p[0], p[1]);
        mma_a(c[0], vf[0], p[0], p[1]); mma_a(c[1], vf[2], p[0], p[1]);
        sched();
        mma_a(c[2], one, p[2], p[3]);
        mma_a(c[0], vf[1], p[2], p[3]); mma_a(c[1], vf[3], p[2], p[3]);
        sched();
      };
      auto pv_m = [&]() {
        mma1688(c[2], one[0], one[1], pm);
        mma_a(c[0], vm[0], pm, pm);
        sched();
        mma_a(c[1], vm[1], pm, pm);
      };
      auto norm = [&]() {
        const float n0 = rcp(c[2][0]), n1 = rcp(c[2][1]);
#pragma unroll
        for (int i = 0; i < 4; i++) o[i] = pack2(c[i >> 1][2 * (i & 1)] * n0, c[i >> 1][2 * (i & 1) + 1] * n1);
        return ((__float_as_uint(c[2][0]) - 0x1F800000u) | (__float_as_uint(c[2][1]) - 0x1F800000u)) >> 30;
      };
      auto load_m = [&](int x) { const float2 e0 = lds64f(pa + 512 + x * 1024), e1 = lds64f(pa + 768 + x * 1024); pm = pack2(e0.x * e1.x, e0.y * e1.y); };
      auto attend_max = [&](int x) {
        float2 sv[6];
#pragma unroll
        for (int i = 0; i < 6; i++) sv[i] = lds64f(pa - 3072 + x * 1536 + i * 256);
        sv[4].x += sv[5].x; sv[4].y += sv[5].y;
        const int dq = (int)(L16 >> 6) - (int)((L16 >> 3) & 6) + 8 * j;
        float m = fmaxf(sv[4].x, sv[4].y);
#pragma unroll
        for (int i = 0; i < 4; i++) {
          if (x && 8 * i > dq) sv[i].x = -INFINITY;
          if (x && 8 * i + 1 > dq) sv[i].y = -INFINITY;
          m = fmaxf(m, fmaxf(sv[i].x, sv[i].y));
        }
        m = fmaxf(m, __shfl_xor_sync(0xffffffffu, m, 1));
        m = fmaxf(m, __shfl_xor_sync(0xffffffffu, m, 2));
#pragma unroll
        for (int i = 0; i < 5; i++) (i < 4 ? p[i] : pm) = pack2(ex2(sv[i].x - m), ex2(sv[i].y - m));
        pv_x(); pv_m(); norm();
      };
      uint32_t tq[4];
      auto get_t = [&]() {
        tq[0] = tq[1] = tq[2] = tq[3] = 0;
        asm volatile("{.reg .pred p; setp.eq.u32 p, %5, 0; @p ld.relaxed.gpu.global.v4.b32 {%0,%1,%2,%3}, [%4];}"
                     : "+r"(tq[0]), "+r"(tq[1]), "+r"(tq[2]), "+r"(tq[3]) : "l"(xb + offsetof(Xchg, T) + L16 * 8), "r"(warp) : "memory");
      };
      delay_until(tpub + DLY_V);
      wait_time(due + NS_V);
      TS(4);
      ldx(vm, vsrc);
      sched();
      xpos(2, 2);
      auto store_kqv = [&]() {
        fence_async();
        if (!(EXP & 4))
          asm volatile("{.reg .pred p; elect.sync _|p, 0xffffffff; @p cp.async.bulk.global.shared::cta.bulk_group [%0], [%1], 2048; cp.async.bulk.commit_group;}"
                       :: "l"(g_kqv[(s + 1) & 3][role] + w4 * 128), "r"(sb + R_STAGE + w4 * 2048) : "memory");
      };
      if (SPOS == 2) store_kqv();
      sched();
      bar_sync(5, 256);
      ldsm4(p, sb + R_P + L16);
      load_m(0);
      pv_x();
      ldsm4(p, sb + R_P + 1024 + L16);
      pv_m();
      const uint32_t r = norm(), tl = after(tag, c[2][0], (uint32_t)it >> 31);
      const bool redo = __any_sync(0xffffffffu, r | ((dif2(vm[0][0], vm[0][2], tl) | dif2(vm[1][0], vm[1][2], tl)) & 1));
      TS(6);
      stsm4t(uW + R_O + L16, o[0], o[1], o[2], o[3]);
      bar_arrive_unless(6, redo);
      sched();
      if (TQL == 7) get_t();
      TS(7);
      pv_x();
      if (rare(redo)) retry<2>(vm, vsrc, tag, it);
      bar_sync(8, 256);
      load_m(1);
      pv_m();
      if (rare(__any_sync(0xffffffffu, norm()) || redo)) {
        fresh();
#pragma unroll 1
        for (int x = !redo; x < 2; x++) {
          attend_max(x);
          if (x == 0) { stsm4t(uW + R_O + L16, o[0], o[1], o[2], o[3]); bar_arrive(6, 256); }
        }
      }
      TS(8);
      if (TQL == 8) get_t();
      const bool xok = mbar_test(sb + B_X + 16, s & 1) & mbar_test(sb + B_X + 24, s & 1);
      xpos(4, 2);
      fresh();
      const uint32_t ob = uni(sb + R_MEM + 4096 + w4 * 1024);
      stsm4t(ob + (L16 & 112) * 4 + (((L16 >> 3) ^ (L16 >> 1)) & 48), o[0], o[1], o[2], o[3]);
      __syncwarp();
      uint32_t rd[4];
      lds128(rd, uW + R_RD + L16);
      lds128(o, ob + (L16 ^ ((L16 >> 3) & 48)));
      auto put_o = [&]() {
        *reinterpret_cast<uint4*>(reinterpret_cast<uint8_t*>(g_ox) + (((s * SEG + 8 * j) * HD + h * DH + 32 * w4) * 2 + (L16 >> 6) * (HD * 2) + (L16 & 48))) = make_uint4(o[0], o[1], o[2], o[3]);
      };
      if (s + 1 == NSEG) { put_o(); asm volatile("cp.async.bulk.wait_group 0;" ::: "memory"); break; }
      asm volatile("cp.async.bulk.wait_group 0;" ::: "memory");
      if (elect()) stx32(xa + 4096 + j * 16 + w4 * 4, s + 1);
      __syncwarp();
      if (rare(!xok)) { wait_x(s + 2, 3); wait_x(s + 2, 2); }
      TS(9);
      fresh();
      const uint32_t e = due | ((s + 1) & 31);
      project_qk(IC<0>{}, IC<NQ>{}, IC<1>{}, [&](int n) {
        if (n == OXPOS) { __syncwarp(); put_o(); __syncwarp(); }
        if (n == TQP) { __syncwarp(); tq[0] = dif2v(tq[0], tq[1], e) | dif2v(tq[2], tq[3], e); __syncwarp(); }
      });
      if (NPA) project_v(IC<0>{}, IC<NPA>{}, [](int) {});
      TS(2);
      if (warp == 0) {
        uint32_t last = due, nx = NS_P;
        if (rare(__any_sync(0xffffffffu, tq[0]))) {
          const uint32_t ref = gtime();
#pragma unroll 1
          do ldx128(o, xb + offsetof(Xchg, T) + L16 * 8); while (any_bit(or3(o[0] - s - 1, o[1] - s - 1, o[2] - s - 1), o[3] - s - 1, 30) && ++it < SPIN_LIMIT);
          const int d = max(max((int)(o[0] - ref), (int)(o[1] - ref)), max((int)(o[2] - ref), (int)(o[3] - ref)));
          last = (ref + __reduce_max_sync(0xffffffffu, d)) & ~31u;
          if (last != due) nx += NS_X;
        }
        sts32(sb + B_DUE, last);
        sts32(sb + B_DUE + 8 - tag * 4, last + nx);
        fetch4k(sb + R_MEM, my_b(), sb + B_B, last + NS_B);
        LOG(13, tl - last);
        LOG(9, last);
      }
      if (NQ < 16) project_qk(IC<NQ>{}, IC<16>{}, IC<0>{}, [](int) {});
      project_v(IC<NPA>{}, IC<NPRE>{}, [](int) {});
      const uint32_t ba = rd[2], msk = rd[3];
      const uint8_t* cdst = reinterpret_cast<const uint8_t*>(rd[0] | (uint64_t)rd[1] << 32);
      TS(14);
      mbar_spin(sb + B_B, s & 1, it);
      TS(10);
      uint32_t bq[2][4];
      auto sum_b = [&]() {
        ldsm4t(bq[0], ba); ldsm4t(bq[1], ba + 2048);
        sched();
#pragma unroll
        for (int i = 0; i < 8; i++) c[i >> 2][i & 3] = 0.f;
        mma_a(c[0], bq[0], 0x3F803F80u, 0x3F803F80u); mma_a(c[1], bq[1], 0x3F803F80u, 0x3F803F80u);
        const uint32_t t2 = tag * 0x10001u;
        const bool old = any_bit(or3(dif2(bq[0][0], bq[0][1], t2), dif2(bq[0][2], bq[0][3], t2), dif2(bq[1][0], bq[1][1], t2)), dif2(bq[1][2], bq[1][3], t2), L16 < 64 ? 0x10001u : 0u);
        const uint32_t T = (tag << 16) & ~msk, u = ((__float_as_uint(c[0][0] + c[1][0]) + ((0x10000u & ~msk) - T)) & msk) | T;
        asm volatile("{.reg .pred p; setp.eq.u32 p, %2, 0; @p st.relaxed.gpu.global.b32 [%0], %1;}"
                     :: "l"(cdst), "r"(pack2(__uint_as_float(u), c[0][2] + c[1][2])), "r"((uint32_t)(old || (L16 & 32))) : "memory");
        return old;
      };
      if (rare(sum_b())) {
#pragma unroll 1
        do {
          const uint8_t* p = xb + (my_b() + (ba - sb - R_MEM));
          ldx128(bq[0], p); ldx128(bq[1], p + 2048);
          sts128(ba, bq[0]); sts128(ba + 2048, bq[1]);
          __syncwarp();
          it += INC_B;
        } while (sum_b() && it < SPIN_LIMIT);
      }
      sched();
      TS(11);
      bar_arrive(0, 256);
      const unsigned tc = clk();
      const uint32_t cdue = lds32(sb + B_DUE) + NS_C;
      if (warp == 3) LOG(11, gtime() - cdue);
      fresh();
      wg_wait<0>(); keep(aq); keep(av);
      park();
      if (NPRE < 32) project_v(IC<NPRE>{}, IC<32>{}, [](int) {}); else fin_v();
      TS(12);
      delay_until(tc + DLY_C);
      issue_c(cdue);
      TS(5);
      LOG(warp, it);
      pin_mem();
      if (NPRE < 32) { wg_wait<0>(); keep(av); fin_v(); }
      if (!(EXP & 2)) mbar_spin(sb + B_KV, tag, it);
      TS(15);
    } else {
      uint32_t kf[8][4];
      auto load_k = [&]() {
        const uint32_t ka = sb + R_K + w4 * 1024 + (L16 & 112) + (L16 & 128) * 4 + (L16 & 256);
#pragma unroll
        for (int i = 0; i < 8; i++) ldsm4(kf[i], ka + (i >> 1) * 2048 + (i & 1) * 128);
      };
      auto put_p = [&](int x, uint32_t old, uint32_t again) {
        float e[4];
        const int dq = (int)((L16 >> 3) & 6) + 8 * j - (int)(L16 >> 6) - 16 * w4;
#pragma unroll
        for (int i = 0; i < 4; i++) { r4[i] = fmaf(c[3][i], sc, fmaf(c[2][i], sc, fmaf(c[0][i] + c[1][i], sc, __uint_as_float(i == 3 ? 0u - old : 0u)))); e[i] = x && dq + (i & 1) < 8 * (i >> 1) ? 0.f : ex2(r4[i]); }
        stsm2t(uP2 + x * 1024 + L16, pack2(e[0], e[1]), pack2(e[2], e[3]), again);
      };
      auto put_s = [&](int x) {
#pragma unroll
        for (int i = 0; i < 4; i++) sts32f(uW + R_S + x * 1536 + (L16 & 48) * 4 + (L16 >> 6) * 4 + (i & 1) * 32 + (i >> 1) * 256, r4[i]);
      };
      auto load_q = [&](uint32_t (&q)[4], uint32_t off) { ldsm4(q, sb + R_Q + (L16 & 112) + (L16 & 128) * 2 + (L16 >> 8) * 128 + off); };
      mbar_spin(sb + B_C, nc & 1, it);
      TS(13);
      float4 o4;
      uint32_t id[4], old;
      {
        uint32_t b[24][4];
#pragma unroll
        for (int i = 0; i < 2 * PD1; i++) { lds128(b[i], ma + i * 512); __syncwarp(); }
        sched();
        zero(c);
#pragma unroll
        for (int i = 0; i < 12; i++) {
          mma4(4 * i, b[2 * i], b[2 * i + 1]);
          if (i < 11) sched();
          if (i + PD1 < 12) { const int k = i + PD1; const uint32_t a = (ma ^ (k >> 2 << 12)) + (k & 3) * 1024; lds128(b[2 * k], a); __syncwarp(); lds128(b[2 * k + 1], a + 512); sched(); }
          if (i == RJ) { lds128(id, sb + R_ID + L16); sched(); }
          if (i == RI) { old = bar_or(4, 0); o4 = lds128f(uW + R_RED + L16); sched(); }
        }
      }
      TS(0);
      {
        float e[4] = {o4.x, o4.y, o4.z, o4.w};
#pragma unroll
        for (int i = 0; i < 4; i++) { r4[i] = (((e[i] + c[0][i]) + c[1][i]) + c[2][i]) + c[3][i]; e[i] = 0.f; }
        mma_a(e, id, pack2(r4[0], r4[1]), pack2(r4[2], r4[3]));
        sched();
        if (VB) bar_arrive(7, 256);
        sched();
        asm volatile("{.reg .pred p; setp.eq.u32 p, %3, 0; @p st.relaxed.gpu.global.v2.b32 [%0], {%1,%2};}" :: "l"(adst),
                     "r"((__byte_perm(__float_as_uint(e[0]), __float_as_uint(e[1]), 0x7632) & ~1u) | tag), "r"(__byte_perm(__float_as_uint(e[2]), __float_as_uint(e[3]), 0x7632)), "r"(old) : "memory");
        sched();
      }
      const unsigned tpub = clk(), now = gtime(), due = get_due();
      if (__any_sync(0xffffffffu, old) && nc < NC_MAX) { bar_sync(3, 256); continue; }
      TS(2);
      const uint8_t* asrc = pinp(adst + ((warp == 7) * 1024 - (int)uA));
      fresh();
      uint32_t wo[32][4];
      bool xok;
      auto reload = [&]() {
        sched();
#pragma unroll
        for (int i = RE0 + RE1; i < NSW; i++) lds128(w[i], uW + R_WC + L16 + i * 2048);
        sched();
      };
      auto out_proj = [&]() {
        uint32_t b[4][4];
        float d[4][4];
        uint8_t* dst[2];
        const uint32_t da = pin(uP2 + (R_DST - R_P) + L16 / 2);
        sched();
        TS(7);
        bar_sync(6, 256);
#pragma unroll
        for (int i = 0; i < 4; i++) { ldsm4(b[i], sb + R_O + i * 512 + L16); __syncwarp(); }
        sched();
        auto put_b = [&](uint8_t* a, const float (&e)[4][4]) {
          stx128(a, (pack2(e[0][0] + e[2][0], e[0][1] + e[2][1]) & ~1u) | tag, pack2(e[0][2] + e[2][2], e[0][3] + e[2][3]),
                 pack2(e[1][0] + e[3][0], e[1][1] + e[3][1]), pack2(e[1][2] + e[3][2], e[1][3] + e[3][3]));
        };
        zero(c); zero(d);
#pragma unroll
        for (int i = 0; i < 32; i++) {
          mma_h(i < 16 ? c[i & 3] : d[i & 3], wo[i], b[(i >> 2) & 3], (i >> 1) & 1);
          if (i >= LW0 && NB1 + i - LW0 < 32) { load_wo(wo, (NB1 + i - LW0) ^ 1, ((NB1 + i - LW0) ^ 1) + 1); __syncwarp(); }
          if (i == DL0 || i == DL1) asm volatile("ld.shared.u64 %0, [%1];" : "=l"(dst[i > DL0]) : "r"(da + (i > DL0) * 1024) : "memory");
          if (i >= 16 && i < 16 + RE0) { lds128(w[i - 16], uW + R_WC + L16 + (i - 16) * 2048); __syncwarp(); }
          if (i >= RP1 && i < RP1 + RE1) { lds128(w[i - RP1 + RE0], uW + R_WC + L16 + (i - RP1 + RE0) * 2048); __syncwarp(); }
          if (i == 22) put_b(dst[0], c);
          if ((i & 1) && (i < 20 || i > 22)) sched();
        }
        put_b(dst[1], d);
        sched();
        TS(6);
      };
      if (warp < 6) {
        delay_until(tpub + DLY_A);
        const int it0 = it;
        bool redo;
#pragma unroll 1
        do {
          uint32_t q[4][4], y[4];
          float d[4][4];
          wait_time(due);
          TS(4);
          ldx(q, asrc);
          sched();
          load_k();
          uint32_t qx[4][4];
#pragma unroll
          for (int i = 0; i < 4; i++) load_q(qx[i], i * 512);
          sched();
          load_wo(wo, 0, NE4);
          sched();
          zero(c);
#pragma unroll
          for (int i = 0; i < 8; i++) mma_h(c[i & 3], kf[i], qx[i >> 1], i & 1);
          put_p(1, 0, 0); put_s(1);
          sched();
          load_wo(wo, NE4, NA4);
          sched();
          zero(c); zero(d);
#pragma unroll
          for (int i = 0; i < 8; i++) {
            if (i == 0) { y[0] = dif2v(q[0][0], q[0][2], q[1][0]); sched(); }
            if (i == 3) { y[1] = dif2v(q[1][2], q[2][0], q[2][2]); sched(); }
            if (i == 6) { y[2] = dif2v(q[3][0], q[3][2], tag); sched(); }
            mma_h(i % 6 < 2 ? c[2 + i % 6] : d[i - 2], kf[i], q[i >> 1], i & 1);
            if (i == 2 || i == 5 || i == 7) sched();
          }
          y[0] = or_and(or3(y[0], y[1], dif2v(q[0][0], q[2][0], tag)), y[2], it < SPIN_LIMIT);
#pragma unroll
          for (int i = 0; i < 4; i++) { c[0][i] = d[0][i] + d[1][i]; c[1][i] = d[2][i] + d[3][i]; }
          put_p(0, y[0], it - it0);
          TS(5);
          bar_sync_unless(5, it - it0);
          redo = __any_sync(0xffffffffu, y[0]);
          it += INC_A;
        } while (redo);
        it -= INC_A;
        put_s(0);
        bar_arrive(8, 256);
        load_wo(wo, NA4, NB1);
        out_proj();
        if (warp == 4) LOG(12, tb);
      } else {
        uint32_t qx[2][4], q[4][4];
        if (warp == 6) {
          const uint32_t t1 = (now & ~31u) + NS_M;
          LOG(10, now - due);
          if (elect()) stx32(&gx->T[h][j], ((int)(t1 - due) > 0 ? t1 + NS_PEN : due) | ((s + 1) & 31));
          __syncwarp();
        }
        auto score = [&](const uint32_t (&a0)[4], const uint32_t (&a1)[4]) {
          zero(c);
#pragma unroll
          for (int i = 0; i < 4; i++) mma_h(c[i], i < 2 ? a0 : a1, q[2 + (i >> 1)], i & 1);
        };
        auto put_m = [&](uint32_t a, uint32_t old, uint32_t again) {
#pragma unroll
          for (int i = 0; i < 2; i++) { r4[i] = fmaf(c[3][2 + i], sc, fmaf((c[0][i] + c[1][2 + i]) + c[2][i], sc, __uint_as_float(i ? 0u - old : 0u))); r4[2 + i] = fmaf(r4[i] * 0x1p122f, 0.f, ex2(r4[i])); }
          asm volatile("{.reg .pred p; setp.eq.u32 p, %3, 0; @p st.shared.v2.f32 [%0], {%1,%2};}" :: "r"(a), "f"(r4[2]), "f"(r4[3]), "r"(again) : "memory");
        };
        delay_until(tpub + DLY_A);
        const uint32_t sa = sb + R_S + 512 + w4 * 256 + (L16 >> 1);
        const int it0 = it;
        bool redo;
#pragma unroll 1
        do {
          wait_time(due);
          TS(4);
          ldx<4, 2048>(q, asrc);
          sched();
          load_q(qx[0], (w4 & 1) * 1024); load_q(qx[1], (w4 & 1) * 1024 + 512);
          load_wo(wo, 0, NA6);
          sched();
          score(q[0], q[1]);
          sched();
          const uint32_t y = or_and(or3(dif2v(q[0][0], q[0][2], tag), dif2v(q[1][0], q[1][2], tag), dif2v(q[2][0], q[2][2], tag)), dif2v(q[3][0], q[3][2], tag), it < SPIN_LIMIT);
          put_m(sa + 2560, y, it - it0);
          TS(5);
          bar_arrive_unless(5, it - it0);
          redo = __any_sync(0xffffffffu, y);
          it += INC_A;
        } while (redo);
        it -= INC_A;
        sts64f(sa, r4[0], r4[1]);
        score(qx[0], qx[1]);
        put_m(sa + 3584, 0, 0);
        sts64f(sa + 1536, r4[0], r4[1]);
        bar_arrive(8, 256);
        load_wo(wo, NA6, NB1);
        out_proj();
      }
      TS(8);
      if (s + 1 == NSEG) break;
      wait_x(s + 2, 2);
      TS(9);
      fresh();
      if (N1) project_qk(IC<32>{}, IC<32 + N1>{}, IC<1>{}, [](int) {});
      TS(10);
      xpos(6, 6);
      uint32_t fl = s + 1;
      if (warp == 5) { wait_time(due + NS_F); fl = ldx32(xa + 4096 + ((L16 >> 2) & 60)); }
      reload();
      TS(14);
      pin_mem();
      wait_x(s + 2, 1); wait_x(s + 2, 0);
      if (warp == 5) {
#pragma unroll 1
        while (__any_sync(0xffffffffu, fl != s + 1) && !(EXP & 4) && ++it < SPIN_LIMIT) fl = ldx32(xa + 4096 + ((L16 >> 2) & 60));
        wait_time(due + (NS_B + NS_K));
        if (!(EXP & 2) && elect()) issue_kqv(s + 1);
        __syncwarp();
      }
      if (PFD && warp == 6 && s + PFD < NSEG && elect())
        asm volatile("cp.async.bulk.prefetch.L2.global [%0], 2048;" :: "l"(xin + ((s + PFD) * SEG + ((role + 4 * (role >> 5)) & 31)) * DM) : "memory");
      __syncwarp();
      TS(11);
      LOG(warp, it);
      if (warp == 4) LOG(8, nc);
      bar_sync(0, 256);
      if (N1 < 16) project_qk(IC<32 + N1>{}, IC<48>{}, IC<!N1>{}, [](int) {});
      project_qk(IC<16>{}, IC<32>{}, IC<0>{}, [&](int n) { if ((n & 15) == XWPOS) { __syncwarp(); xok = mbar_test(sb + B_PK, s & 1); __syncwarp(); } });
      if (rare(!xok)) mbar_spin(sb + B_PK, s & 1, it);
      unpark();
      project_qk(IC<0>{}, IC<16>{}, IC<0>{}, [](int) {});
      TS(12);
      wg_wait<0>(); keep(aq);
      TS(1);
      fin_qk();
      TS(15);
    }
    s++;
  }
  if (it >= SPIN_LIMIT || nc >= NC_MAX) g_err = 2;
}

typedef CUresult (*EncodeFn)(CUtensorMap*, CUtensorMapDataType, cuuint32_t, void*, const cuuint64_t*, const cuuint64_t*, const cuuint32_t*,
                             const cuuint32_t*, CUtensorMapInterleave, CUtensorMapSwizzle, CUtensorMapL2promotion, CUtensorMapFloatOOBfill);
static void make_map(EncodeFn fn, CUtensorMap* m, const void* p, uint64_t cols, uint64_t rows, uint64_t pitch, uint32_t bc, uint32_t br, CUtensorMapSwizzle sw) {
  cuuint64_t dims[2] = {cols, rows}, strides[1] = {pitch * 2};
  cuuint32_t box[2] = {bc, br}, es[2] = {1, 1};
  fn(m, CU_TENSOR_MAP_DATA_TYPE_BFLOAT16, 2, const_cast<void*>(p), dims, strides, box, es, CU_TENSOR_MAP_INTERLEAVE_NONE, sw,
     CU_TENSOR_MAP_L2_PROMOTION_L2_256B, CU_TENSOR_MAP_FLOAT_OOB_FILL_NONE);
}

extern "C" void kernel_launch(void* const* d_in, const int* in_sizes, int n_in, void* d_out, int out_size) {
  const bf16* Ax = (const bf16*)d_in[0]; const bf16* mem0 = (const bf16*)d_in[1];
  const bf16* Wq = (const bf16*)d_in[2]; const bf16* Wk = (const bf16*)d_in[3]; const bf16* Wv = (const bf16*)d_in[4];
  const bf16* Wo = (const bf16*)d_in[5];
  const bf16* Bx = (const bf16*)d_in[7]; const bf16* wr = (const bf16*)d_in[8]; const bf16* wi = (const bf16*)d_in[9];
  bf16* out = (bf16*)d_out;

  void* fp = nullptr; cudaDriverEntryPointQueryResult qr;
  cudaGetDriverEntryPoint("cuTensorMapEncodeTiled", &fp, cudaEnableDefault, &qr);
  EncodeFn fn = (EncodeFn)fp;
  void *kqv, *ox, *xr;
  cudaGetSymbolAddress(&xr, g_xraw);
  cudaGetSymbolAddress(&kqv, g_kqv); cudaGetSymbolAddress(&ox, g_ox);
  const CUtensorMapSwizzle S128 = CU_TENSOR_MAP_SWIZZLE_128B, S64 = CU_TENSOR_MAP_SWIZZLE_64B;

  GemmMaps m3; RecMaps mr;
  make_map(fn, &m3.a, ox, HD, S_LEN, HD, 64, 128, S128);
  make_map(fn, &m3.b[0], Wo, DM, HD, DM, 64, 64, S128);
  m3.b[1] = m3.b[0]; m3.b[2] = m3.b[0];
  make_map(fn, &m3.c, out, DM, S_LEN, 2 * DM, 64, 64, S128);
  make_map(fn, &mr.wq, Wq, HD, DM, HD, 32, 256, S64);
  make_map(fn, &mr.wk, Wk, HD, DM, HD, 32, 256, S64);
  make_map(fn, &mr.wv, Wv, HD, DM, HD, 64, 256, S128);
  make_map(fn, &mr.wo, Wo, DM, HD, DM, 64, 128, S128);
  {
    cuuint64_t dims[3] = {64, S_LEN, 16}, strides[2] = {DM * 2, 128};
    cuuint32_t box[3] = {64, 32, 4}, es[3] = {1, 1, 1};
    fn(&mr.x, CU_TENSOR_MAP_DATA_TYPE_BFLOAT16, 3, const_cast<bf16*>(Ax), dims, strides, box, es, CU_TENSOR_MAP_INTERLEAVE_NONE, S128,
       CU_TENSOR_MAP_L2_PROMOTION_L2_256B, CU_TENSOR_MAP_FLOAT_OOB_FILL_NONE);
  }
  for (int i = 0; i < 3; i++) {
    cuuint64_t dims[3] = {128, 32, 512}, strides[2] = {256, 8192};
    cuuint32_t box[3] = {128, i == 0 ? 8u : i == 1 ? 2u : 16u, 4}, es[3] = {1, 1, 1};
    fn(i == 0 ? &mr.k : i == 1 ? &mr.q : &mr.v, CU_TENSOR_MAP_DATA_TYPE_BFLOAT16, 3, kqv, dims, strides, box, es, CU_TENSOR_MAP_INTERLEAVE_NONE,
       CU_TENSOR_MAP_SWIZZLE_NONE, CU_TENSOR_MAP_L2_PROMOTION_L2_256B, CU_TENSOR_MAP_FLOAT_OOB_FILL_NONE);
  }
  {
    cuuint64_t dims[3] = {64, 16, S_LEN}, strides[2] = {128, 2 * DM * 2};
    cuuint32_t box[3] = {64, 16, 2}, es[3] = {1, 1, 1};
    fn(&mr.fo, CU_TENSOR_MAP_DATA_TYPE_BFLOAT16, 3, out + DM, dims, strides, box, es, CU_TENSOR_MAP_INTERLEAVE_NONE, S128,
       CU_TENSOR_MAP_L2_PROMOTION_NONE, CU_TENSOR_MAP_FLOAT_OOB_FILL_NONE);
  }
  constexpr int SM3 = 6 * 32768 + 32768 + 256 + 1024;
  cudaFuncSetAttribute(gemm_kernel<128, 6>, cudaFuncAttributeMaxDynamicSharedMemorySize, SM3);
  cudaFuncSetAttribute(rec_kernel, cudaFuncAttributeMaxDynamicSharedMemorySize, R_TOTAL);

  cudaStream_t st = cudaStreamPerThread;
  rec_kernel<<<132, 256, R_TOTAL, st>>>(mr, Ax, mem0, reinterpret_cast<Xchg*>((reinterpret_cast<uintptr_t>(xr) + 8191) & ~(uintptr_t)8191), Bx, wr, wi);
  gemm_kernel<128, 6><<<128, 384, SM3, st>>>(m3, 16, 8, 64, 8, 1);
}
```

```cpp
#include <cuda_runtime.h>
#include <cuda_bf16.h>
#include <cuda.h>
#include <stdint.h>
#include <stddef.h>
#include <type_traits>

typedef __nv_bfloat16 bf16;

constexpr int S_LEN = 2048, DM = 1024, NH = 32, DH = 128, MEM = 8, SEG = 32, NSEG = 64;
constexpr int HD = NH * DH;
#define SPIN 20
constexpr int SPIN_LIMIT = 1 << SPIN, INC_A = 1, INC_B = 1;

constexpr unsigned NC_MAX = 4096;
__device__ __align__(1024) uint4 g_kqv[4][128][512];
__device__ __align__(1024) bf16 g_ox[(size_t)S_LEN * HD];
struct Xchg {
  uint4 A[32][4][256];
  uint4 C[4][2][256];
  uint4 B[128][2][256];
  uint32_t T[32][32];
  uint32_t S[128];
  unsigned ctr[64];
};
__device__ __align__(1024) uint4 g_xraw[(sizeof(Xchg) + 8192) / 16];
__device__ __align__(1024) uint4 g_y[1024 * 256];
__device__ __align__(1024) uint4 g_wt[513 * 512];
__device__ int g_err;

__device__ __forceinline__ unsigned clk() { unsigned long long c; asm volatile("mov.u64 %0, %%clock64;" : "=l"(c)); return (unsigned)c; }
__device__ __forceinline__ uint32_t smem_u32(const void* p) { return (uint32_t)__cvta_generic_to_shared(p); }
__device__ __forceinline__ void mbar_init(uint32_t bar, int cnt) { asm volatile("mbarrier.init.shared::cta.b64 [%0], %1;" :: "r"(bar), "r"(cnt) : "memory"); }
__device__ __forceinline__ void mbar_expect_tx(uint32_t bar, int bytes) { asm volatile("mbarrier.arrive.expect_tx.shared::cta.b64 _, [%0], %1;" :: "r"(bar), "r"(bytes) : "memory"); }
__device__ __forceinline__ void mbar_arrive(uint32_t bar) { asm volatile("mbarrier.arrive.shared::cta.b64 _, [%0];" :: "r"(bar) : "memory"); }
__device__ __forceinline__ void mbar_arrive_cluster(uint32_t bar, int cta) {
  asm volatile("{.reg .b32 r; mapa.shared::cluster.u32 r, %0, %1; mbarrier.arrive.shared::cluster.b64 _, [r];}" :: "r"(bar), "r"(cta) : "memory"); }
__device__ __forceinline__ bool mbar_try(uint32_t bar, int par) {
  uint32_t ok; asm volatile("{.reg .pred p; mbarrier.try_wait.parity.shared::cta.b64 p, [%1], %2; selp.u32 %0, 1, 0, p;}" : "=r"(ok) : "r"(bar), "r"(par) : "memory"); return ok; }
__device__ __forceinline__ bool mbar_test(uint32_t bar, int par) {
  uint32_t ok; asm volatile("{.reg .pred p; mbarrier.test_wait.parity.shared::cta.b64 p, [%1], %2; selp.u32 %0, 1, 0, p;}" : "=r"(ok) : "r"(bar), "r"(par) : "memory"); return ok; }
__device__ __forceinline__ void mbar_wait(uint32_t bar, int par) {
  int it = 0;
  while (!mbar_try(bar, par)) { if (++it > SPIN_LIMIT) { g_err = 1; break; } }
}
__device__ __forceinline__ void tma2d(uint32_t dst, const CUtensorMap* m, int c0, int c1, uint32_t bar) {
  asm volatile("cp.async.bulk.tensor.2d.shared::cluster.global.mbarrier::complete_tx::bytes [%0], [%1, {%3, %4}], [%2];"
    :: "r"(dst), "l"(m), "r"(bar), "r"(c0), "r"(c1) : "memory"); }
__device__ __forceinline__ void tma2d_mc(uint32_t dst, const CUtensorMap* m, int c0, int c1, uint32_t bar, uint16_t mask) {
  asm volatile("cp.async.bulk.tensor.2d.shared::cluster.global.mbarrier::complete_tx::bytes.multicast::cluster [%0], [%1, {%3, %4}], [%2], %5;"
    :: "r"(dst), "l"(m), "r"(bar), "r"(c0), "r"(c1), "h"(mask) : "memory"); }
__device__ __forceinline__ void tma2d_store(const CUtensorMap* m, uint32_t src, int c0, int c1) {
  asm volatile("cp.async.bulk.tensor.2d.global.shared::cta.bulk_group [%0, {%2, %3}], [%1];" :: "l"(m), "r"(src), "r"(c0), "r"(c1) : "memory"); }
__device__ __forceinline__ void fence_async() { asm volatile("fence.proxy.async.shared::cta;" ::: "memory"); }
__device__ __forceinline__ void bar_sync(int id, int n) { asm volatile("bar.sync %0, %1;" :: "r"(id), "r"(n) : "memory"); }
__device__ __forceinline__ void bar_arrive(int id, int n) { asm volatile("bar.arrive %0, %1;" :: "r"(id), "r"(n) : "memory"); }
__device__ __forceinline__ uint32_t pack2(float lo, float hi) { uint32_t r; asm("cvt.rn.bf16x2.f32 %0, %1, %2;" : "=r"(r) : "f"(hi), "f"(lo)); return r; }
__device__ __forceinline__ uint32_t pack2_tag(float lo, float hi, uint32_t T) {
  uint32_t u = ((__float_as_uint(lo) - T + 0x10000u) & 0xFFFE0000u) + T;
  return __byte_perm(u, pack2(0.f, hi), 0x7632); }
__device__ __forceinline__ void ldsm4(uint32_t (&r)[4], uint32_t a) {
  asm volatile("ldmatrix.sync.aligned.m8n8.x4.shared.b16 {%0,%1,%2,%3}, [%4];" : "=r"(r[0]), "=r"(r[1]), "=r"(r[2]), "=r"(r[3]) : "r"(a) : "memory"); }
__device__ __forceinline__ void ldsm4t(uint32_t (&r)[4], uint32_t a) {
  asm volatile("ldmatrix.sync.aligned.m8n8.x4.trans.shared.b16 {%0,%1,%2,%3}, [%4];" : "=r"(r[0]), "=r"(r[1]), "=r"(r[2]), "=r"(r[3]) : "r"(a) : "memory"); }
__device__ __forceinline__ void stsm4(uint32_t a, uint32_t r0, uint32_t r1, uint32_t r2, uint32_t r3) {
  asm volatile("stmatrix.sync.aligned.m8n8.x4.shared.b16 [%0], {%1,%2,%3,%4};" :: "r"(a), "r"(r0), "r"(r1), "r"(r2), "r"(r3) : "memory"); }
__device__ __forceinline__ void stsm4t(uint32_t a, uint32_t r0, uint32_t r1, uint32_t r2, uint32_t r3) {
  asm volatile("stmatrix.sync.aligned.m8n8.x4.trans.shared.b16 [%0], {%1,%2,%3,%4};" :: "r"(a), "r"(r0), "r"(r1), "r"(r2), "r"(r3) : "memory"); }
__device__ __forceinline__ void lds128(uint32_t (&r)[4], uint32_t a) {
  asm volatile("ld.shared.v4.u32 {%0,%1,%2,%3}, [%4];" : "=r"(r[0]), "=r"(r[1]), "=r"(r[2]), "=r"(r[3]) : "r"(a) : "memory"); }
__device__ __forceinline__ float4 lds128f(uint32_t a) { float4 r;
  asm volatile("ld.shared.v4.f32 {%0,%1,%2,%3}, [%4];" : "=f"(r.x), "=f"(r.y), "=f"(r.z), "=f"(r.w) : "r"(a) : "memory"); return r; }
__device__ __forceinline__ float2 lds64f(uint32_t a) { float2 r;
  asm volatile("ld.shared.v2.f32 {%0,%1}, [%2];" : "=f"(r.x), "=f"(r.y) : "r"(a) : "memory"); return r; }
__device__ __forceinline__ void sts128(uint32_t a, uint32_t r0, uint32_t r1, uint32_t r2, uint32_t r3) {
  asm volatile("st.shared.v4.u32 [%0], {%1,%2,%3,%4};" :: "r"(a), "r"(r0), "r"(r1), "r"(r2), "r"(r3) : "memory"); }
__device__ __forceinline__ void sts64f(uint32_t a, float x, float y) { asm volatile("st.shared.v2.f32 [%0], {%1,%2};" :: "r"(a), "f"(x), "f"(y) : "memory"); }
__device__ __forceinline__ void sts32f(uint32_t a, float x) { asm volatile("st.shared.f32 [%0], %1;" :: "r"(a), "f"(x) : "memory"); }
__device__ __forceinline__ void mma16816(float (&d)[4], uint32_t a0, uint32_t a1, uint32_t a2, uint32_t a3, uint32_t b0, uint32_t b1) {
  asm volatile("mma.sync.aligned.m16n8k16.row.col.f32.bf16.bf16.f32 {%0,%1,%2,%3}, {%4,%5,%6,%7}, {%8,%9}, {%0,%1,%2,%3};"
    : "+f"(d[0]), "+f"(d[1]), "+f"(d[2]), "+f"(d[3]) : "r"(a0), "r"(a1), "r"(a2), "r"(a3), "r"(b0), "r"(b1)); }
__device__ __forceinline__ void mma1688(float (&d)[4], uint32_t a0, uint32_t a1, uint32_t b0) {
  asm volatile("mma.sync.aligned.m16n8k8.row.col.f32.bf16.bf16.f32 {%0,%1,%2,%3}, {%4,%5}, {%6}, {%0,%1,%2,%3};"
    : "+f"(d[0]), "+f"(d[1]), "+f"(d[2]), "+f"(d[3]) : "r"(a0), "r"(a1), "r"(b0)); }
__device__ __forceinline__ void ldx128(uint32_t (&r)[4], const void* p) {
  asm volatile("{.reg .b128 t; .reg .b64 a, b; ld.relaxed.gpu.global.b128 t, [%4]; mov.b128 {a, b}, t; mov.b64 {%0,%1}, a; mov.b64 {%2,%3}, b;}"
    : "=r"(r[0]), "=r"(r[1]), "=r"(r[2]), "=r"(r[3]) : "l"(p) : "memory"); }
__device__ __forceinline__ void ldx2x64(uint32_t (&r)[4], const void* p) {
  asm volatile("{.reg .b64 a, b; ld.relaxed.gpu.global.v2.b64 {a, b}, [%4]; mov.b64 {%0,%1}, a; mov.b64 {%2,%3}, b;}"
    : "=r"(r[0]), "=r"(r[1]), "=r"(r[2]), "=r"(r[3]) : "l"(p) : "memory"); }
__device__ __forceinline__ void stx128(void* p, uint32_t r0, uint32_t r1, uint32_t r2, uint32_t r3) {
  asm volatile("{.reg .b128 t; .reg .b64 a, b; mov.b64 a, {%1,%2}; mov.b64 b, {%3,%4}; mov.b128 t, {a, b}; st.relaxed.gpu.global.b128 [%0], t;}"
    :: "l"(p), "r"(r0), "r"(r1), "r"(r2), "r"(r3) : "memory"); }
__device__ __forceinline__ void stx64(void* p, uint32_t r0, uint32_t r1) {
  asm volatile("{.reg .b64 a; mov.b64 a, {%1,%2}; st.relaxed.gpu.global.b64 [%0], a;}" :: "l"(p), "r"(r0), "r"(r1) : "memory"); }
__device__ __forceinline__ uint32_t uni(uint32_t x) { return __shfl_sync(0xffffffffu, x, 0); }
__device__ __forceinline__ uint32_t pin(uint32_t x) { return __shfl_xor_sync(0xffffffffu, x, 0); }
__device__ __forceinline__ float ex2(float x) { float r; asm("ex2.approx.ftz.f32 %0, %1;" : "=f"(r) : "f"(x)); return r; }
__device__ __forceinline__ void wg_fence() { asm volatile("wgmma.fence.sync.aligned;" ::: "memory"); }
__device__ __forceinline__ void wg_commit() { asm volatile("wgmma.commit_group.sync.aligned;" ::: "memory"); }
template <int N> __device__ __forceinline__ void wg_wait() { asm volatile("wgmma.wait_group.sync.aligned %0;" :: "n"(N) : "memory"); }

__device__ __forceinline__ void wgmma_ss_n256_tb1(float (&d)[128], uint64_t da, uint64_t db, int sc) {
  asm volatile("{.reg .pred p; setp.ne.b32 p, %130, 0;\n"
    "wgmma.mma_async.sync.aligned.m64n256k16.f32.bf16.bf16 {%0,%1,%2,%3,%4,%5,%6,%7,%8,%9,%10,%11,%12,%13,%14,%15,%16,%17,%18,%19,%20,%21,%22,%23,%24,%25,%26,%27,%28,%29,%30,%31,%32,%33,%34,%35,%36,%37,%38,%39,%40,%41,%42,%43,%44,%45,%46,%47,%48,%49,%50,%51,%52,%53,%54,%55,%56,%57,%58,%59,%60,%61,%62,%63,%64,%65,%66,%67,%68,%69,%70,%71,%72,%73,%74,%75,%76,%77,%78,%79,%80,%81,%82,%83,%84,%85,%86,%87,%88,%89,%90,%91,%92,%93,%94,%95,%96,%97,%98,%99,%100,%101,%102,%103,%104,%105,%106,%107,%108,%109,%110,%111,%112,%113,%114,%115,%116,%117,%118,%119,%120,%121,%122,%123,%124,%125,%126,%127}, %128, %129, p, 1, 1, 0, 1;}\n"
    : "+f"(d[0]),"+f"(d[1]),"+f"(d[2]),"+f"(d[3]),"+f"(d[4]),"+f"(d[5]),"+f"(d[6]),"+f"(d[7]),"+f"(d[8]),"+f"(d[9]),"+f"(d[10]),"+f"(d[11]),"+f"(d[12]),"+f"(d[13]),"+f"(d[14]),"+f"(d[15]),"+f"(d[16]),"+f"(d[17]),"+f"(d[18]),"+f"(d[19]),"+f"(d[20]),"+f"(d[21]),"+f"(d[22]),"+f"(d[23]),"+f"(d[24]),"+f"(d[25]),"+f"(d[26]),"+f"(d[27]),"+f"(d[28]),"+f"(d[29]),"+f"(d[30]),"+f"(d[31]),"+f"(d[32]),"+f"(d[33]),"+f"(d[34]),"+f"(d[35]),"+f"(d[36]),"+f"(d[37]),"+f"(d[38]),"+f"(d[39]),"+f"(d[40]),"+f"(d[41]),"+f"(d[42]),"+f"(d[43]),"+f"(d[44]),"+f"(d[45]),"+f"(d[46]),"+f"(d[47]),"+f"(d[48]),"+f"(d[49]),"+f"(d[50]),"+f"(d[51]),"+f"(d[52]),"+f"(d[53]),"+f"(d[54]),"+f"(d[55]),"+f"(d[56]),"+f"(d[57]),"+f"(d[58]),"+f"(d[59]),"+f"(d[60]),"+f"(d[61]),"+f"(d[62]),"+f"(d[63]),"+f"(d[64]),"+f"(d[65]),"+f"(d[66]),"+f"(d[67]),"+f"(d[68]),"+f"(d[69]),"+f"(d[70]),"+f"(d[71]),"+f"(d[72]),"+f"(d[73]),"+f"(d[74]),"+f"(d[75]),"+f"(d[76]),"+f"(d[77]),"+f"(d[78]),"+f"(d[79]),"+f"(d[80]),"+f"(d[81]),"+f"(d[82]),"+f"(d[83]),"+f"(d[84]),"+f"(d[85]),"+f"(d[86]),"+f"(d[87]),"+f"(d[88]),"+f"(d[89]),"+f"(d[90]),"+f"(d[91]),"+f"(d[92]),"+f"(d[93]),"+f"(d[94]),"+f"(d[95]),"+f"(d[96]),"+f"(d[97]),"+f"(d[98]),"+f"(d[99]),"+f"(d[100]),"+f"(d[101]),"+f"(d[102]),"+f"(d[103]),"+f"(d[104]),"+f"(d[105]),"+f"(d[106]),"+f"(d[107]),"+f"(d[108]),"+f"(d[109]),"+f"(d[110]),"+f"(d[111]),"+f"(d[112]),"+f"(d[113]),"+f"(d[114]),"+f"(d[115]),"+f"(d[116]),"+f"(d[117]),"+f"(d[118]),"+f"(d[119]),"+f"(d[120]),"+f"(d[121]),"+f"(d[122]),"+f"(d[123]),"+f"(d[124]),"+f"(d[125]),"+f"(d[126]),"+f"(d[127])
    : "l"(da), "l"(db), "r"(sc));
}

__device__ __forceinline__ void wgmma_ss_n128_tb1(float (&d)[64], uint64_t da, uint64_t db, int sc) {
  asm volatile("{.reg .pred p; setp.ne.b32 p, %66, 0;\n"
    "wgmma.mma_async.sync.aligned.m64n128k16.f32.bf16.bf16 {%0,%1,%2,%3,%4,%5,%6,%7,%8,%9,%10,%11,%12,%13,%14,%15,%16,%17,%18,%19,%20,%21,%22,%23,%24,%25,%26,%27,%28,%29,%30,%31,%32,%33,%34,%35,%36,%37,%38,%39,%40,%41,%42,%43,%44,%45,%46,%47,%48,%49,%50,%51,%52,%53,%54,%55,%56,%57,%58,%59,%60,%61,%62,%63}, %64, %65, p, 1, 1, 0, 1;}\n"
    : "+f"(d[0]),"+f"(d[1]),"+f"(d[2]),"+f"(d[3]),"+f"(d[4]),"+f"(d[5]),"+f"(d[6]),"+f"(d[7]),"+f"(d[8]),"+f"(d[9]),"+f"(d[10]),"+f"(d[11]),"+f"(d[12]),"+f"(d[13]),"+f"(d[14]),"+f"(d[15]),"+f"(d[16]),"+f"(d[17]),"+f"(d[18]),"+f"(d[19]),"+f"(d[20]),"+f"(d[21]),"+f"(d[22]),"+f"(d[23]),"+f"(d[24]),"+f"(d[25]),"+f"(d[26]),"+f"(d[27]),"+f"(d[28]),"+f"(d[29]),"+f"(d[30]),"+f"(d[31]),"+f"(d[32]),"+f"(d[33]),"+f"(d[34]),"+f"(d[35]),"+f"(d[36]),"+f"(d[37]),"+f"(d[38]),"+f"(d[39]),"+f"(d[40]),"+f"(d[41]),"+f"(d[42]),"+f"(d[43]),"+f"(d[44]),"+f"(d[45]),"+f"(d[46]),"+f"(d[47]),"+f"(d[48]),"+f"(d[49]),"+f"(d[50]),"+f"(d[51]),"+f"(d[52]),"+f"(d[53]),"+f"(d[54]),"+f"(d[55]),"+f"(d[56]),"+f"(d[57]),"+f"(d[58]),"+f"(d[59]),"+f"(d[60]),"+f"(d[61]),"+f"(d[62]),"+f"(d[63])
    : "l"(da), "l"(db), "r"(sc));
}

template <int BN> struct WG;
template <> struct WG<256> { static __device__ __forceinline__ void mma(float (&d)[128], uint64_t a, uint64_t b, int sc) { wgmma_ss_n256_tb1(d, a, b, sc); } };
template <> struct WG<128> { static __device__ __forceinline__ void mma(float (&d)[64], uint64_t a, uint64_t b, int sc) { wgmma_ss_n128_tb1(d, a, b, sc); } };

struct GemmMaps { CUtensorMap a, b[3], c; };
template <int BN, int STAGES>
__global__ void __cluster_dims__(2, 1, 1) __launch_bounds__(384, 1)
gemm_kernel(const __grid_constant__ GemmMaps maps, int tilesM, int tilesN, int kblocks, int nPerB, int clearX) {
  extern __shared__ __align__(1024) uint8_t smem_raw[];
  constexpr int STAGE_BYTES = 16384 + BN * 128;
  constexpr int NBOX = BN / 64;
  const uint32_t sbase = (smem_u32(smem_raw) + 1023) & ~1023u;
  const uint32_t sEpi = sbase + STAGES * STAGE_BYTES;
  const uint32_t sBar = sEpi + 32768;
  const int warp = threadIdx.x >> 5, lane = threadIdx.x & 31, wg = warp >> 2;
  uint32_t crank; asm("mov.u32 %0, %%cluster_ctarank;" : "=r"(crank));
  if (threadIdx.x == 0) {
    for (int i = 0; i < STAGES; i++) { mbar_init(sBar + 8 * i, 1); mbar_init(sBar + 8 * (STAGES + i), 4); }
    asm volatile("fence.mbarrier_init.release.cluster;" ::: "memory");
  }
  if (clearX) {
    uint4* p = g_xraw;
    for (int i = blockIdx.x * 384 + threadIdx.x; i < (int)(sizeof(g_xraw) / 16); i += gridDim.x * 384) p[i] = make_uint4(0, 0, 0, 0);
  }
  asm volatile("barrier.cluster.arrive.release.aligned; barrier.cluster.wait.acquire.aligned;" ::: "memory");
  const int npairs = (tilesM >> 1) * tilesN, pair0 = blockIdx.x >> 1, pstep = gridDim.x >> 1;
  if (wg == 2) {
    asm volatile("setmaxnreg.dec.sync.aligned.u32 40;");
    if (warp == 8 && lane == 0) {
      int st = 0, ph = 1;
      for (int p = pair0; p < npairs; p += pstep) {
        const int tm = (p % (tilesM >> 1)) * 2 + crank, tn = p / (tilesM >> 1);
        const CUtensorMap* mb = &maps.b[tn / nPerB];
        const int n0 = (tn % nPerB) * BN;
        for (int kb = 0; kb < kblocks; kb++) {
          mbar_wait(sBar + 8 * (STAGES + st), ph);
          const uint32_t a = sbase + st * STAGE_BYTES, full = sBar + 8 * st;
          mbar_expect_tx(full, STAGE_BYTES);
          tma2d(a, &maps.a, kb * 64, tm * 128, full);
#pragma unroll
          for (int i = 0; i < NBOX / 2; i++) {
            const int bx = crank * (NBOX / 2) + i;
            tma2d_mc(a + 16384 + bx * 8192, mb, n0 + bx * 64, kb * 64, full, (uint16_t)3);
          }
          if (++st == STAGES) { st = 0; ph ^= 1; }
        }
      }
      for (int i = 0; i < STAGES; i++) { mbar_wait(sBar + 8 * (STAGES + st), ph); if (++st == STAGES) { st = 0; ph ^= 1; } }
    }
  } else {
    asm volatile("setmaxnreg.inc.sync.aligned.u32 232;");
    int st = 0, ph = 0;
    float acc[BN / 2];
    const uint64_t descA0 = (uint64_t)(((sbase + wg * 8192) & 0x3FFFF) >> 4) | (1ull << 16) | (64ull << 32) | (1ull << 62);
    const uint64_t descB0 = (uint64_t)(((sbase + 16384) & 0x3FFFF) >> 4) | (512ull << 16) | (64ull << 32) | (1ull << 62);
    const uint32_t epi = sEpi + wg * 16384;
    for (int p = pair0; p < npairs; p += pstep) {
      const int tm = (p % (tilesM >> 1)) * 2 + crank, tn = p / (tilesM >> 1);
      int prev = -1;
      for (int kb = 0; kb < kblocks; kb++) {
        mbar_wait(sBar + 8 * st, ph);
        wg_fence();
        const uint64_t so = (uint64_t)(st * (STAGE_BYTES >> 4));
#pragma unroll
        for (int k = 0; k < 4; k++) WG<BN>::mma(acc, descA0 + so + k * 2, descB0 + so + k * 128, kb | k);
        wg_commit();
        if (prev >= 0) {
          wg_wait<1>();
          if ((threadIdx.x & 127) < 2) mbar_arrive_cluster(sBar + 8 * (STAGES + prev), threadIdx.x & 1);
        }
        prev = st;
        if (++st == STAGES) { st = 0; ph ^= 1; }
      }
      wg_wait<0>();
      if ((threadIdx.x & 127) < 2) mbar_arrive_cluster(sBar + 8 * (STAGES + prev), threadIdx.x & 1);
#pragma unroll
      for (int r = 0; r < BN / 128; r++) {
        if ((threadIdx.x & 127) == 0) asm volatile("cp.async.bulk.wait_group.read 0;" ::: "memory");
        bar_sync(1 + wg, 128);
        const int row = (warp & 3) * 16 + (lane & 15);
#pragma unroll
        for (int i = 0; i < 8; i++) {
          const int c = 2 * (i & 3) + (lane >> 4);
          const float* q = &acc[r * 64 + i * 8];
          stsm4(epi + (i >> 2) * 8192 + row * 128 + ((c ^ (row & 7)) << 4), pack2(q[0], q[1]), pack2(q[2], q[3]), pack2(q[4], q[5]), pack2(q[6], q[7]));
        }
        fence_async();
        bar_sync(1 + wg, 128);
        if ((threadIdx.x & 127) == 0) {
          tma2d_store(&maps.c, epi, tn * BN + r * 128, tm * 128 + wg * 64);
          tma2d_store(&maps.c, epi + 8192, tn * BN + r * 128 + 64, tm * 128 + wg * 64);
          asm volatile("cp.async.bulk.commit_group;" ::: "memory");
        }
      }
    }
    if ((threadIdx.x & 127) == 0) asm volatile("cp.async.bulk.wait_group 0;" ::: "memory");
  }
}

struct Dft { uint32_t m[2][2][2][4]; };
template <bool P4> __device__ __forceinline__ int fidx(int tile, int x) { return P4 ? 4 * (x >> 1) + 2 * (tile & 1) + (x & 1) + 16 * (tile >> 1) : x + 8 * tile; }
__device__ __forceinline__ float2 cis(int k, int n) {
  k &= n - 1; if (2 * k > n) k -= n;
  const float a = (float)k * (6.283185307179586f / (float)n);
  return make_float2(__cosf(a), __sinf(a));
}
template <bool OUT4> __device__ __forceinline__ void make_dft(Dft& D, int g, int t) {
#pragma unroll
  for (int q = 0; q < 16; q++) {
    const int b = q >> 3, u = (q >> 2) & 1, r = (q >> 1) & 1, v = q & 1;
    const float2 w = cis(fidx<OUT4>(v, g) * fidx<false>(2 * u + r, 2 * t + b), 32);
    D.m[b][u][0][q & 3] = pack2(w.x, w.y); D.m[b][u][1][q & 3] = pack2(-w.y, w.x);
  }
}
__device__ __forceinline__ void mma_dc(float (&d)[4], uint32_t a0, uint32_t a1, uint32_t a2, uint32_t a3, uint32_t b0, uint32_t b1, const float (&c)[4]) {
  asm("mma.sync.aligned.m16n8k16.row.col.f32.bf16.bf16.f32 {%0,%1,%2,%3}, {%4,%5,%6,%7}, {%8,%9}, {%10,%11,%12,%13};"
    : "=f"(d[0]), "=f"(d[1]), "=f"(d[2]), "=f"(d[3]) : "r"(a0), "r"(a1), "r"(a2), "r"(a3), "r"(b0), "r"(b1), "f"(c[0]), "f"(c[1]), "f"(c[2]), "f"(c[3])); }
__device__ __forceinline__ void dft_b(const Dft& D, const uint32_t (&x)[2][4], float (&o)[2][8]) {
#pragma unroll
  for (int ri = 0; ri < 2; ri++) {
    float z[4] = {0.f, 0.f, 0.f, 0.f}, e[4], p[4];
    mma_dc(e, D.m[0][0][ri][0], D.m[0][0][ri][1], D.m[0][0][ri][2], D.m[0][0][ri][3], x[0][0], x[0][1], z);
    mma_dc(e, D.m[0][1][ri][0], D.m[0][1][ri][1], D.m[0][1][ri][2], D.m[0][1][ri][3], x[0][2], x[0][3], e);
    mma_dc(p, D.m[1][0][ri][0], D.m[1][0][ri][1], D.m[1][0][ri][2], D.m[1][0][ri][3], x[1][0], x[1][1], e);
    mma_dc(p, D.m[1][1][ri][0], D.m[1][1][ri][1], D.m[1][1][ri][2], D.m[1][1][ri][3], x[1][2], x[1][3], p);
#pragma unroll
    for (int q = 0; q < 4; q++) { o[ri][q] = p[q]; o[ri][4 + q] = fmaf(2.f, e[q], -p[q]); }
  }
}
__device__ __forceinline__ void dft_a(const uint32_t (&m)[2][2][4], const uint32_t (&x0)[2][4], const uint32_t (&x1)[2][4], float (&o)[2][8]) {
#pragma unroll
  for (int ri = 0; ri < 2; ri++) {
    float z[4] = {0.f, 0.f, 0.f, 0.f}, e[4], p[4];
    mma_dc(e, x0[0][0], x1[0][0], x0[0][1], x1[0][1], m[0][ri][0], m[0][ri][1], z);
    mma_dc(e, x0[0][2], x1[0][2], x0[0][3], x1[0][3], m[0][ri][2], m[0][ri][3], e);
    mma_dc(p, x0[1][0], x1[1][0], x0[1][1], x1[1][1], m[1][ri][0], m[1][ri][1], e);
    mma_dc(p, x0[1][2], x1[1][2], x0[1][3], x1[1][3], m[1][ri][2], m[1][ri][3], p);
#pragma unroll
    for (int q = 0; q < 4; q++) { o[ri][q] = p[q]; o[ri][4 + q] = fmaf(2.f, e[q], -p[q]); }
  }
}
__device__ __forceinline__ uint32_t twid(float re, float im, float c, float s) { return pack2(fmaf(re, c, im * s), fmaf(im, c, -re * s)); }
__device__ __forceinline__ void cpa16(uint32_t d, const void* s) { asm volatile("cp.async.cg.shared.global [%0], [%1], 16;" :: "r"(d), "l"(s) : "memory"); }
__device__ __forceinline__ void sts32(uint32_t a, uint32_t x) { asm volatile("st.shared.u32 [%0], %1;" :: "r"(a), "r"(x) : "memory"); }
__device__ __forceinline__ void cpa_commit() { asm volatile("cp.async.commit_group;" ::: "memory"); }
template <int N> __device__ __forceinline__ void cpa_wait() { asm volatile("cp.async.wait_group %0;" :: "n"(N) : "memory"); }
__device__ __forceinline__ uint32_t lds32(uint32_t a) { uint32_t r; asm volatile("ld.shared.u32 %0, [%1];" : "=r"(r) : "r"(a) : "memory"); return r; }
#define FMID 0
constexpr int F_TP = 4112, F_TSZ = 8 * F_TP;

__device__ __forceinline__ uint32_t ldnc32(const void* p) { uint32_t v; asm volatile("ld.global.nc.b32 %0, [%1];" : "=r"(v) : "l"(p) : "memory"); return v; }
template <class F>
__device__ __forceinline__ void fft_wprep(const bf16* __restrict__ wr, const bf16* __restrict__ wi, int cta, F&& mid) {
  const int tid = threadIdx.x, g = (cta >> 1) & 7, c = (cta >> 4) & 3, t = 2 * (cta & 1) + (tid & 1);
  const int k0 = g + 8 * (cta >> 6) + 32 * (8 * c + 2 * t), l0 = (tid & ~1) + (g & 1);
  uint32_t a[4][4], b[4][4];
#pragma unroll
  for (int q = 0; q < 16; q++) {
    const int o = (k0 + 16 * (q >> 3) + 32 * ((q >> 1) & 1) + 1024 * (q & 1)) * 513 + l0 + 256 * ((q >> 2) & 1);
    a[q >> 2][q & 3] = ldnc32(wr + o);
    b[q >> 2][q & 3] = ldnc32(wi + o);
  }
  const int e = cta * 32 + (tid & 31), lh = (e >> 11) * 512, k = e & 2047, k2 = (k >> 5) & 31;
  uint32_t hz[4];
#pragma unroll
  for (int q = 0; q < 4; q++) asm volatile("ld.global.nc.u16 %0, [%1];" : "=r"(hz[q]) : "l"((q < 2 ? wr : wi) + (q & 1 ? (2048 - k) & 2047 : k) * 513 + lh) : "memory");
  mid();
  uint4* dst = g_wt + l0 * 512 + cta * 2 + (tid & 1);
#pragma unroll
  for (int q = 0; q < 8; q++) {
    const int hf = q >> 1, l = l0 + 256 * (hf & 1) + (q & 1);
    const uint32_t sel = (q & 1) ? 0x7632 : 0x5410;
    if (l & 511) dst[(256 * (hf & 1) + (q & 1)) * 512 + 256 * (q >> 2)] = make_uint4(__byte_perm(a[hf][0], b[hf][0], sel), __byte_perm(a[hf][1], b[hf][1], sel),
                                                                                   __byte_perm(a[hf][2], b[hf][2], sel), __byte_perm(a[hf][3], b[hf][3], sel));
  }
  if (tid < 32) reinterpret_cast<uint32_t*>(g_wt)[(64 * ((k >> 3) & 3) + 16 * (k2 >> 3) + 2 * (k & 7) + ((k2 >> 2) & 1)) * 8 + lh * 2048 + 2 * (k2 & 3) + (k >> 10)] =
      pack2(0.5f * (__uint_as_float(hz[0] << 16) + __uint_as_float(hz[1] << 16)), 0.5f * (__uint_as_float(hz[2] << 16) - __uint_as_float(hz[3] << 16)));
}

template <class F>
__device__ __forceinline__ void fft_rows_fwd(const bf16* __restrict__ x, const bf16* __restrict__ wr, const bf16* __restrict__ wi, uint32_t tb, int it, F&& mid) {
  const int warp = threadIdx.x >> 5, lane = threadIdx.x & 31, g = lane >> 2, t = lane & 3;
  const uint32_t in = tb + warp * 4096;
  const uint32_t f0 = in + (lane >> 3) * 256 + (((lane & 7) ^ (2 * (lane >> 3))) << 4);
  const bf16* src = x + ((256 * (warp & 3) + 64 * (warp >> 2) + 128 * (it & 1) + 32 * ((it >> 4) & 1) + 8 * (it >> 5) + ((it >> 1) & 7)) * 2048 + lane * 8);
#pragma unroll
  for (int q = 0; q < 8; q++) cpa16((f0 ^ ((q >> 2) * 144)) + (q & 3) * 1024, src + q * 256);
  cpa_commit();
  Dft D;
  float2 tw[4][8];
  fft_wprep(wr, wi, it, [&]() {
    if (FMID == 0) mid();
    make_dft<true>(D, g, t);
#pragma unroll
    for (int q = 0; q < 32; q++) {
      tw[q >> 3][q & 7] = cis(fidx<true>((q >> 1) & 3, g) * fidx<false>(q >> 3, 2 * t + (q & 1)), 1024);
      if (FMID) asm volatile("" : "+f"(tw[q >> 3][q & 7].x), "+f"(tw[q >> 3][q & 7].y) :: "memory");
    }
    if (FMID == 1) mid();
  });
  if (FMID == 2) mid();
  cpa_wait<0>(); __syncwarp();
  uint32_t a[4][2][4], y[4][2][4];
#pragma unroll
  for (int q = 0; q < 8; q++) ldsm4t(a[q & 3][q >> 2], (in + lane * 128 + ((lane & 7) << 4)) ^ (q << 4));
  float o[2][8];
#pragma unroll
  for (int i = 0; i < 4; i++) {
    dft_b(D, a[i], o);
#pragma unroll
    for (int q = 0; q < 8; q++) y[q >> 1][q & 1][i] = twid(o[0][q], o[1][q], tw[i][q].x, tw[i][q].y);
  }
  __syncthreads();
  const uint32_t w0 = tb + warp * F_TP + fidx<true>(0, g) * 128 + t * 16 + ((g & 1) << 6), wz = (g & 1) ? -64 : 64;
#pragma unroll
  for (int z = 0; z < 2; z++) {
    float o2[2][8];
    dft_b(D, y[2 * z], o); dft_b(D, y[2 * z + 1], o2);
#pragma unroll
    for (int i = 0; i < 4; i++) {
      const float sg = i < 2 ? 1.f : -1.f;
      sts128(w0 + z * wz + fidx<true>(i, 0) * 128, pack2(o[0][2 * i], sg * o[1][2 * i]), pack2(o[0][2 * i + 1], sg * o[1][2 * i + 1]),
             pack2(o2[0][2 * i], sg * o2[1][2 * i]), pack2(o2[0][2 * i + 1], sg * o2[1][2 * i + 1]));
    }
  }
  __syncthreads();
  const uint32_t ra = tb + (lane & 1) * 4 * F_TP + ((lane >> 1) + 16 * (warp ^ ((warp >> 1) & 1))) * 4;
  uint4* dst = g_y + (threadIdx.x >> 1) * 256 + (lane & 1) + it * 2;
#pragma unroll
  for (int q = 0; q < 8; q++) { const uint32_t r = ra + q * 512; dst[q * 32768] = make_uint4(lds32(r), lds32(r + F_TP), lds32(r + 2 * F_TP), lds32(r + 3 * F_TP)); }
}

__device__ __forceinline__ void fft_cols(uint32_t sb, int cta, int ncta) {
  const int warp = threadIdx.x >> 5, lane = threadIdx.x & 31, g = lane >> 2, t = lane & 3;
  const uint32_t in = sb + warp * 16384 + lane * 16, tab = sb + 131072 + lane * 16;
  auto fetch_y = [&](int l) {
#pragma unroll
    for (int q = 0; q < 16; q++) cpa16(in + q * 512, g_y + (q < 8 ? l : (1024 - l) & 1023) * 256 + (q & 7) * 32 + lane);
  };
  auto fetch_w = [&](int l) {
#pragma unroll
    for (int q = 0; q < 16; q++) cpa16(in + 8192 + q * 512, g_wt + l * 512 + q * 32 + lane);
  };
  const int l0 = cta * 8 + warp, dl = ncta * 8;
  if (l0 <= 512) fetch_y(l0);
  cpa_commit();
  if (l0 <= 512) fetch_w(l0);
  cpa_commit();
  Dft D; make_dft<false>(D, g, t);
#pragma unroll
  for (int q = 2 * warp; q < 2 * warp + 2; q++) {
    const int r = fidx<false>(q & 3, g), c = fidx<false>(q >> 2, 2 * t);
    const float2 w0 = cis(r * c, 1024), w1 = cis(r * c + r, 1024), p0 = cis(r + 32 * c, 2048), p1 = cis(r + 32 * c + 32, 2048);
    sts128(tab + q * 512, __float_as_uint(w0.x), __float_as_uint(w0.y), __float_as_uint(w1.x), __float_as_uint(w1.y));
    sts128(tab + 8192 + q * 512, __float_as_uint(p0.x), __float_as_uint(p0.y), __float_as_uint(p1.x), __float_as_uint(p1.y));
  }
  if (warp == 0) {
#pragma unroll
    for (int q = 0; q < 8; q++) {
      const int v = q >> 2, b = (q >> 1) & 1, ri = q & 1;
      sts128(tab + 16384 + q * 512, D.m[b][0][ri][v], D.m[b][0][ri][v + 2], D.m[b][1][ri][v], D.m[b][1][ri][v + 2]);
    }
  }
  __syncthreads();
#pragma unroll 1
  for (int l = l0; l <= 512; l += dl) {
    uint32_t a[2][4][2][4], y[2][4][2][4];
    float o[2][2][8];
    cpa_wait<1>();
#pragma unroll
    for (int q = 0; q < 16; q++) lds128(a[q >> 3][(q >> 1) & 3][q & 1], in + q * 512);
    if (!(l & 511)) {
      const uint32_t m0 = l ? 0x80000000u : 0u;
#pragma unroll
      for (int q = 0; q < 32; q++) { a[0][q >> 3][(q >> 2) & 1][q & 3] ^= m0; a[1][q >> 3][(q >> 2) & 1][q & 3] ^= m0 ^ 0x80000000u; }
    }
    auto first = [&]() {
#pragma unroll
      for (int i = 0; i < 4; i++) {
        dft_b(D, a[0][i], o[0]); dft_b(D, a[1][i], o[1]);
#pragma unroll
        for (int r = 0; r < 4; r++) {
          const float4 w = lds128f(tab + (4 * i + r) * 512);
#pragma unroll
          for (int s = 0; s < 2; s++) {
            y[s][r][0][i] = twid(o[s][0][2 * r], o[s][1][2 * r], w.x, w.y);
            y[s][r][1][i] = twid(o[s][0][2 * r + 1], o[s][1][2 * r + 1], w.z, w.w);
          }
        }
      }
    };
    first();
    if (l + dl <= 512) fetch_y(l + dl);
    cpa_commit();
    cpa_wait<1>();
#pragma unroll
    for (int zv = 0; zv < 4; zv++) {
      const int z = zv >> 1, v = zv & 1;
      uint32_t m[2][2][4];
#pragma unroll
      for (int q = 0; q < 4; q++) lds128(m[q >> 1][q & 1], tab + 16384 + (4 * v + q) * 512);
      dft_a(m, y[0][2 * z], y[0][2 * z + 1], o[0]); dft_a(m, y[1][2 * z], y[1][2 * z + 1], o[1]);
#pragma unroll
      for (int q = 0; q < 4; q++) {
        const int i = 2 * z + (q & 1), c = v + (q & 2);
        uint32_t w[4]; lds128(w, in + 8192 + (4 * i + c) * 512);
        const float4 ph = lds128f(tab + 8192 + (4 * c + i) * 512);
#pragma unroll
        for (int b = 0; b < 2; b++) {
          const float cs = b ? ph.z : ph.x, sn = b ? ph.w : ph.y;
          const float r1 = __uint_as_float(w[2 * b] << 16), i1 = __uint_as_float(w[2 * b] & 0xFFFF0000u);
          const float r2 = __uint_as_float(w[2 * b + 1] << 16), i2 = __uint_as_float(w[2 * b + 1] & 0xFFFF0000u);
          const float Sr = r1 + r2, Si = i1 + i2, Dr = r1 - r2, Di = i1 - i2;
          const float ar = fmaf(-Dr, sn, Sr), ai = fmaf(-Di, sn, Si), dr = fmaf(Dr, sn, Sr), di = fmaf(Di, sn, Si), br = -Di * cs, bi = Dr * cs;
          const float Ar = o[0][0][2 * q + b], Ai = o[0][1][2 * q + b], Br = o[1][0][2 * q + b], Bi = o[1][1][2 * q + b];
          a[0][i][b][c] = pack2(fmaf(ar, Ai, fmaf(ai, Ar, fmaf(br, Bi, bi * Br))), fmaf(ar, Ar, fmaf(-ai, Ai, fmaf(br, Br, -bi * Bi))));
          a[1][i][b][c] = pack2(fmaf(dr, Bi, fmaf(di, Br, fmaf(-br, Ai, -bi * Ar))), fmaf(dr, Br, fmaf(-di, Bi, fmaf(-br, Ar, bi * Ai))));
        }
      }
    }
    if (l + dl <= 512) fetch_w(l + dl);
    cpa_commit();
    first();
#pragma unroll
    for (int s = 0; s < 2; s++) {
      uint4* dst = g_y + (s ? (1024 - l) & 1023 : l) * 256 + lane;
      const float sg = s ? -1.f : 1.f;
#pragma unroll
      for (int i = 0; i < 4; i++) {
        dft_b(D, y[s][i], o[0]);
#pragma unroll
        for (int b = 0; b < 2; b++)
          dst[(2 * i + b) * 32] = make_uint4(pack2(sg * o[0][0][b], o[0][1][b]), pack2(sg * o[0][0][2 + b], o[0][1][2 + b]),
                                             pack2(sg * o[0][0][4 + b], o[0][1][4 + b]), pack2(sg * o[0][0][6 + b], o[0][1][6 + b]));
      }
    }
  }
}

__device__ __forceinline__ void fft_rows_inv(const CUtensorMap* om, uint32_t sb, int cta, int ncta) {
  const int warp = threadIdx.x >> 5, lane = threadIdx.x & 31, g = lane >> 2, t = lane & 3, wg = warp >> 2, w4 = warp & 3;
  const uint32_t tb = sb + 32768 + wg * 2 * F_TSZ;
  const uint4* src = g_y + pin((256 * ((lane >> 1) & 3) + 64 * (lane >> 3) + 8 * w4) * 256 + (lane & 1));
  const uint32_t wa = pin(tb + (lane & 1) * 4 * F_TP + w4 * 1024 + (lane >> 1) * 4);
  uint4 pf[8];
  auto fetch = [&](int it, int hf) {
#pragma unroll
    for (int q = 0; q < 8; q++) pf[q] = __ldcg(src + (it * 2 + hf * 8192) + q * 256);
  };
  auto put = [&](uint32_t off) {
#pragma unroll
    for (int q = 0; q < 8; q++) {
      sts32(wa + off + q * 64, pf[q].x); sts32(wa + off + q * 64 + F_TP, pf[q].y);
      sts32(wa + off + q * 64 + 2 * F_TP, pf[q].z); sts32(wa + off + q * 64 + 3 * F_TP, pf[q].w);
    }
  };
  const int it0 = 2 * cta + wg;
  if (it0 >= 128) return;
  fetch(it0, 0); put(0); fetch(it0, 1); put(512);
  Dft D; make_dft<false>(D, g, t);
  float2 tw[4][8];
#pragma unroll
  for (int q = 0; q < 32; q++) {
    tw[q >> 3][q & 7] = cis(fidx<false>((q >> 1) & 3, g) * fidx<false>(q >> 3, 2 * t + (q & 1)), 1024);
    tw[q >> 3][q & 7].x *= 1.f / 2097152.f; tw[q >> 3][q & 7].y *= 1.f / 2097152.f;
  }
  const uint32_t la = pin(tb + w4 * F_TP + lane * 16), ob = uni(sb + warp * 4096);
  const uint32_t oa = pin(ob + (lane >> 1) * 128 + (((4 * (lane & 1)) ^ ((lane >> 1) & 7)) << 4));
#pragma unroll 1
  for (int n = 0;; n++) {
    const int it = it0 + (n >> 1) * 2 * ncta, hf = n & 1, buf = (n >> 1) & 1;
    if (it >= 128) break;
    if (!hf) bar_sync(1 + wg, 128);
    uint32_t a[4][2][4], y[4][2][4];
#pragma unroll
    for (int q = 0; q < 8; q++) lds128(a[q >> 1][q & 1], la + buf * F_TSZ + hf * 4 * F_TP + q * 512);
    fetch(min(it + 2 * ncta, 127), hf);
    float o[2][8];
#pragma unroll
    for (int i = 0; i < 4; i++) {
      dft_b(D, a[i], o);
#pragma unroll
      for (int q = 0; q < 8; q++) y[q >> 1][q & 1][i] = twid(o[0][q], o[1][q], tw[i][q].x, tw[i][q].y);
    }
    if (lane == 0) asm volatile("cp.async.bulk.wait_group.read 0;" ::: "memory");
    __syncwarp();
#pragma unroll
    for (int c = 0; c < 4; c++) {
      dft_b(D, y[c], o);
#pragma unroll
      for (int ri = 0; ri < 2; ri++)
        stsm4((oa ^ (c << 4)) + (1 - ri) * 2048, pack2(o[ri][0], o[ri][1]), pack2(o[ri][2], o[ri][3]), pack2(o[ri][4], o[ri][5]), pack2(o[ri][6], o[ri][7]));
    }
    fence_async();
    __syncwarp();
    if (lane == 0) {
      const int m = 256 * w4 + 32 * ((it >> 1) & 7) + 8 * (it >> 5) + 4 * (it & 1) + 2 * hf + ((it >> 4) & 1);
      asm volatile("cp.async.bulk.tensor.3d.global.shared::cta.bulk_group [%0, {0, 0, %2}], [%1];" :: "l"(om), "r"(ob), "r"(2 * m) : "memory");
      asm volatile("cp.async.bulk.commit_group;" ::: "memory");
    }
    put((buf ^ 1) * F_TSZ + hf * 512);
  }
  if (lane == 0) asm volatile("cp.async.bulk.wait_group 0;" ::: "memory");
}
__device__ __forceinline__ void grid_arrive(unsigned* ctr) {
  __syncthreads();
  if (threadIdx.x == 0) { __threadfence(); atomicAdd(ctr, 1u); }
}
__device__ __forceinline__ void grid_wait(unsigned* ctr, unsigned n) {
  if (threadIdx.x == 0) {
    int it = 0;
    while (*reinterpret_cast<volatile unsigned*>(ctr) < n) { __nanosleep(200); if (++it > SPIN_LIMIT) { g_err = 3; break; } }
    __threadfence();
  }
  __syncthreads();
}

struct RecMaps { CUtensorMap wq, wk, wv, wo, x, k, q, v, fo; };
#define NSW 16
#define EXP 0
#define NPB 2
#define NPC 4
#define WOP 2
#define HOME 3
#define DL0 14
#define PD1 4
#define NE4 6
#define NE6 0
#define NA4 14
#define NA6 18
#define NB1 24
#define TQL 7
#define NQ 8
#define TQP (NQ - 1)
#define OXPOS 4
#define KVPOS 2
#define NK0 0
#define FLPOS 1
#define XWPOS 10
#define FSPOS 28
#define RL0 4
#define RLS 6
#define RLB 4
#define VL0 3
#define RI 9
#define RJ 8
#define NPRE 20
#define PFD 4
#define PD0 4
#define VB NV0
#define NPA 0
#define N1 16
#define DL1 16
#define PACE 0
#define RE0 0
#define RE1 0
#define RP1 23
#define UNP 1
#define X2 2
#define X3 2
#define SPOS 2
#ifndef NV0
#define NV0 4
#endif
#define TGP 3
#define FENP 0
#define LW0 8
#define X1 4
#define X0 4
constexpr int R_WO = 0, R_X = 65536, R_MEM = 131072, R_WC = 147456, R_RED = R_WC + NSW * 2048, R_O = R_RED, R_S = R_O + 2048, R_P = R_S + 3072, R_STAGE = R_P + 2048,
              R_K = R_STAGE + 8192, R_Q = R_K + 8192, R_V = R_Q + 2048, R_ID = R_V + 16384, R_T = R_ID + 512, R_DST = R_T + 512, R_RD = R_DST + 2048, R_BAR = R_RD + 2048, R_TS = R_BAR + 128,
              R_TOTAL = R_TS;
#define TS(i)
#define LOG(i, v)
constexpr int B_KV = R_BAR, B_W = R_BAR + 8, B_X = R_BAR + 80, B_PK = R_BAR + 24, B_C = R_BAR + 32, B_B = R_BAR + 40, B_DUE = R_BAR + 48, B_ONE = R_BAR + 64;
#define DLY_A 150
#define DLY_V 150
#define DLY_C 200
#define DLY_L 90
#define NS_B 1088
#define NS_C 1728
#define NS_P 2688
#define NS_V 128
#define NS_F 896
#define NS_K 128
#define NS_M 32
#define NS_X 128
#define NS_PEN 1024
__device__ __forceinline__ float rcp(float x) { float r; asm("rcp.approx.ftz.f32 %0, %1;" : "=f"(r) : "f"(x)); return r; }
__device__ __forceinline__ uint32_t movm(uint32_t a) { uint32_t d; asm volatile("movmatrix.sync.aligned.m8n8.trans.b16 %0, %1;" : "=r"(d) : "r"(a)); return d; }
__device__ __forceinline__ uint32_t hadd2(uint32_t a, uint32_t b) { uint32_t d; asm("add.rn.bf16x2 %0, %1, %2;" : "=r"(d) : "r"(a), "r"(b)); return d; }
__device__ __forceinline__ void mma_a(float (&d)[4], const uint32_t (&a)[4], uint32_t b0, uint32_t b1) { mma16816(d, a[0], a[1], a[2], a[3], b0, b1); }
__device__ __forceinline__ bool elect() {
  uint32_t p; asm volatile("{.reg .pred p; elect.sync _|p, 0xffffffff; selp.u32 %0, 1, 0, p;}" : "=r"(p)); return p; }
__device__ __forceinline__ void tma3d(uint32_t dst, const CUtensorMap* m, int c1, int c2, uint32_t bar) {
  asm volatile("cp.async.bulk.tensor.3d.shared::cluster.global.mbarrier::complete_tx::bytes [%0], [%1, {0, %3, %4}], [%2];"
    :: "r"(dst), "l"(m), "r"(bar), "r"(c1), "r"(c2) : "memory"); }
__device__ __forceinline__ void tma4d(uint32_t dst, const CUtensorMap* m, int c1, int c2, uint32_t bar) {
  asm volatile("cp.async.bulk.tensor.4d.shared::cluster.global.mbarrier::complete_tx::bytes [%0], [%1, {0, %3, %4, 0}], [%2];"
    :: "r"(dst), "l"(m), "r"(bar), "r"(c1), "r"(c2) : "memory"); }
template <int OFF, int ACC>
__device__ __forceinline__ void wg_rs32(float (&d)[16], const uint32_t (&a)[4], uint32_t db) {
  if (ACC)
    asm volatile("{.reg .b64 db; .reg .b32 lo; add.u32 lo, %20, %21; mov.b64 db, {lo, 0x40000040};\n"
      "wgmma.mma_async.sync.aligned.m64n32k16.f32.bf16.bf16 {%0,%1,%2,%3,%4,%5,%6,%7,%8,%9,%10,%11,%12,%13,%14,%15}, {%16,%17,%18,%19}, db, 1, 1, 1, 0;}"
      : "+f"(d[0]), "+f"(d[1]), "+f"(d[2]), "+f"(d[3]), "+f"(d[4]), "+f"(d[5]), "+f"(d[6]), "+f"(d[7]), "+f"(d[8]), "+f"(d[9]), "+f"(d[10]), "+f"(d[11]), "+f"(d[12]), "+f"(d[13]), "+f"(d[14]), "+f"(d[15])
      : "r"(a[0]), "r"(a[1]), "r"(a[2]), "r"(a[3]), "r"(db), "n"(OFF));
  else
    asm volatile("{.reg .b64 db; .reg .b32 lo; add.u32 lo, %20, %21; mov.b64 db, {lo, 0x40000040};\n"
      "wgmma.mma_async.sync.aligned.m64n32k16.f32.bf16.bf16 {%0,%1,%2,%3,%4,%5,%6,%7,%8,%9,%10,%11,%12,%13,%14,%15}, {%16,%17,%18,%19}, db, 0, 1, 1, 0;}"
      : "=f"(d[0]), "=f"(d[1]), "=f"(d[2]), "=f"(d[3]), "=f"(d[4]), "=f"(d[5]), "=f"(d[6]), "=f"(d[7]), "=f"(d[8]), "=f"(d[9]), "=f"(d[10]), "=f"(d[11]), "=f"(d[12]), "=f"(d[13]), "=f"(d[14]), "=f"(d[15])
      : "r"(a[0]), "r"(a[1]), "r"(a[2]), "r"(a[3]), "r"(db), "n"(OFF));
}
template <int I> using IC = std::integral_constant<int, I>;
template <int I, int N, class F> __device__ __forceinline__ void sfor(F&& f) {
  if constexpr (I < N) { f(std::integral_constant<int, I>{}); sfor<I + 1, N>(f); }
}
__device__ __forceinline__ void keep(float (&d)[16]) {
  asm volatile("" : "+f"(d[0]), "+f"(d[1]), "+f"(d[2]), "+f"(d[3]), "+f"(d[4]), "+f"(d[5]), "+f"(d[6]), "+f"(d[7]),
      "+f"(d[8]), "+f"(d[9]), "+f"(d[10]), "+f"(d[11]), "+f"(d[12]), "+f"(d[13]), "+f"(d[14]), "+f"(d[15]) :: "memory");
}

template <int N, int S2 = 1024> __device__ __forceinline__ void ldx(uint32_t (&v)[N][4], const uint8_t* p) {
#pragma unroll
  for (int k = 0; k < 2 * N; k++) {
    const int i = k;
    asm volatile("ld.relaxed.gpu.global.v2.b32 {%0,%1}, [%2];" : "=r"(v[i >> 1][2 * (i & 1)]), "=r"(v[i >> 1][2 * (i & 1) + 1]) : "l"(p + (i & 3) * 256 + (i >> 2) * S2) : "memory");
  }
}
__device__ __forceinline__ uint32_t dif2(uint32_t a, uint32_t b, uint32_t tag) { uint32_t r; asm("lop3.b32 %0, %1, %2, %3, 0x7e;" : "=r"(r) : "r"(a), "r"(b), "r"(tag)); return r; }
__device__ __forceinline__ uint32_t dif2v(uint32_t a, uint32_t b, uint32_t tag) { uint32_t r; asm volatile("lop3.b32 %0, %1, %2, %3, 0x7e;" : "=r"(r) : "r"(a), "r"(b), "r"(tag)); return r; }
__device__ __forceinline__ uint32_t or3(uint32_t a, uint32_t b, uint32_t c) { uint32_t r; asm("lop3.b32 %0, %1, %2, %3, 0xfe;" : "=r"(r) : "r"(a), "r"(b), "r"(c)); return r; }
__device__ __forceinline__ uint32_t after(uint32_t x, float f, uint32_t z) { uint32_t r; asm("lop3.b32 %0, %1, %2, %3, 0xea;" : "=r"(r) : "r"(__float_as_uint(f)), "r"(z), "r"(x)); return r; }
__device__ __forceinline__ bool any_bit(uint32_t a, uint32_t b, uint32_t m) {
  uint32_t r; asm("lop3.b32 %0, %1, %2, %3, 0xa8;" : "=r"(r) : "r"(a), "r"(b), "r"(m)); return __any_sync(0xffffffffu, r); }
template <int W, int N> __device__ __forceinline__ bool stale(const uint32_t (&v)[N][4], uint32_t tag) {
  uint32_t x = dif2(v[0][0], v[0][2], tag);
  if (N == 4) x = or3(x, dif2(v[1][0], v[1][2], tag), dif2(v[2 % N][0], v[2 % N][2], tag));
  return any_bit(x, dif2(v[N - 1][0], v[N - 1][2], tag), 1);
}
template <int W, int N, int S2 = 1024> __device__ __forceinline__ void retry(uint32_t (&v)[N][4], const uint8_t* p, uint32_t tag, int& it) {
#pragma unroll 1
  do { ldx<N, S2>(v, p); it += INC_A; } while (stale<W>(v, tag) && it < SPIN_LIMIT);
}
__device__ __forceinline__ void mma_h(float (&d)[4], const uint32_t (&a)[4], const uint32_t (&b)[4], int hf) { mma16816(d, a[0], a[1], a[2], a[3], b[2 * hf], b[2 * hf + 1]); }
__device__ __forceinline__ void sts128(uint32_t a, const uint32_t (&r)[4]) { sts128(a, r[0], r[1], r[2], r[3]); }
__device__ __forceinline__ void sts128f(uint32_t a, const float* r) { sts128(a, __float_as_uint(r[0]), __float_as_uint(r[1]), __float_as_uint(r[2]), __float_as_uint(r[3])); }
__device__ __forceinline__ void mbar_spin(uint32_t bar, uint32_t par, int& it) {
  asm volatile("{.reg .pred p; .reg .b32 par; mov.b32 par, %2;\nLOOP: mbarrier.try_wait.parity.shared::cta.b64 p, [%1], par; @p bra.uni DONE;\n"
               "add.s32 %0, %0, 1; setp.le.s32 p, %0, %3; @p bra.uni LOOP;\nDONE: }" : "+r"(it) : "r"(bar), "r"(par), "n"(SPIN_LIMIT) : "memory"); }
__device__ __forceinline__ void warp_arrive(uint32_t bar) {
  __syncwarp(); asm volatile("{.reg .pred p; elect.sync _|p, 0xffffffff; @p mbarrier.arrive.shared::cta.b64 _, [%0];}" :: "r"(bar) : "memory"); }
__device__ __forceinline__ void delay_until(unsigned t) {
  asm volatile("{.reg .pred p; .reg .b64 c; .reg .b32 lo, hi;\nLOOP: mov.u64 c, %%clock64; mov.b64 {lo, hi}, c; sub.s32 lo, lo, %0; setp.lt.s32 p, lo, 0; @p bra.uni LOOP;}" :: "r"(t) : "memory"); }
__device__ __forceinline__ void cut(int it) { asm volatile("{.reg .pred p; setp.lt.s32 p, %0, 0;\nL: @p st.volatile.shared.u32 [%0], %0; @p bra.uni L;}" :: "r"(it) : "memory"); }
__device__ __forceinline__ void zero(float (&c)[4][4]) {
#pragma unroll
  for (int i = 0; i < 4; i++) c[i][0] = c[i][1] = c[i][2] = c[i][3] = 0.f;
}

__device__ __forceinline__ void sched() { asm volatile("griddepcontrol.launch_dependents;" ::: "memory"); }
__device__ __forceinline__ const uint8_t* pinp(const uint8_t* p) { return reinterpret_cast<const uint8_t*>(__shfl_xor_sync(0xffffffffu, reinterpret_cast<unsigned long long>(p), 0)); }
__device__ __forceinline__ uint32_t bar_or(int id, uint32_t x) {
  uint32_t r; asm volatile("{.reg .pred p, q; setp.ne.u32 p, %2, 0; bar.red.or.pred q, %1, 256, p; selp.u32 %0, 1, 0, q;}" : "=r"(r) : "r"(id), "r"(x) : "memory"); return r; }
__device__ __forceinline__ void bar_sync_unless(int id, uint32_t x) { asm volatile("{.reg .pred p; setp.eq.u32 p, %1, 0; @p bar.sync %0, 256;}" :: "r"(id), "r"((uint32_t)x) : "memory"); }
__device__ __forceinline__ void bar_arrive_unless(int id, uint32_t x) { asm volatile("{.reg .pred p; setp.eq.u32 p, %1, 0; @p bar.arrive %0, 256;}" :: "r"(id), "r"((uint32_t)x) : "memory"); }
__device__ __forceinline__ void stsm2t(uint32_t a, uint32_t r0, uint32_t r1, uint32_t x) {
  asm volatile("{.reg .pred p; setp.eq.u32 p, %3, 0; @p stmatrix.sync.aligned.m8n8.x2.trans.shared.b16 [%0], {%1,%2};}" :: "r"(a), "r"(r0), "r"(r1), "r"((uint32_t)x) : "memory"); }
__device__ __forceinline__ uint32_t or_and(uint32_t a, uint32_t b, uint32_t m) { uint32_t r; asm("lop3.b32 %0, %1, %2, %3, 0xa8;" : "=r"(r) : "r"(a), "r"(b), "r"(m)); return r; }
#define rare(x) __builtin_expect(!!(x), 0)
__device__ __forceinline__ uint32_t gtime() { unsigned long long g; asm volatile("mov.u64 %0, %%globaltimer;" : "=l"(g) :: "memory"); return (uint32_t)g; }
__device__ __forceinline__ void wait_time(uint32_t t) {
  asm volatile("{.reg .pred p; .reg .b32 g; .reg .b64 c;\nLOOP: mov.u64 c, %%globaltimer; cvt.u32.u64 g, c; sub.s32 g, %0, g; setp.lt.u32 p, g, 16384; @p bra.uni LOOP;}" :: "r"(t - 1) : "memory"); }
__device__ __forceinline__ uint32_t ldx32(const void* p) { uint32_t v; asm volatile("ld.relaxed.gpu.global.b32 %0, [%1];" : "=r"(v) : "l"(p) : "memory"); return v; }
__device__ __forceinline__ void stx32(const void* p, uint32_t v) { asm volatile("st.relaxed.gpu.global.b32 [%0], %1;" :: "l"(p), "r"(v) : "memory"); }

__global__ void __launch_bounds__(256, 1)
rec_kernel(const __grid_constant__ RecMaps maps, const bf16* __restrict__ xin, const bf16* __restrict__ mem0, Xchg* const gx,
           const bf16* __restrict__ fx, const bf16* __restrict__ wr, const bf16* __restrict__ wi) {
  extern __shared__ __align__(1024) uint8_t smem_raw[];
  const uint32_t sb = smem_u32(smem_raw);
  int role = blockIdx.x;
  {
    uint32_t smid, nsm; asm volatile("mov.u32 %0, %%smid;" : "=r"(smid)); asm volatile("mov.u32 %0, %%nsmid;" : "=r"(nsm));
    const int p = smid >> 1, u = p - 32;
    if (nsm == gridDim.x)
      role = (smid & 1) + (p < 32 ? 4 * ((p & 7) + 8 * (p >> 4)) + 2 * ((p >> 3) & 1) : p < 60 ? 4 * (16 + u % 7 + 7 * (u / 14)) + 2 * ((u / 7) & 1)
                         : p < 62 ? 2 * p + 8 : 2 * p - 4);
    role = uni(role);
  }
  if (role >= 128) {
    grid_wait(&gx->ctr[33], 128);
    fft_cols(sb, role - 128, 4);
    grid_arrive(&gx->ctr[32]); grid_wait(&gx->ctr[32], 4);
    fft_rows_inv(&maps.fo, sb, role - 128, 4);
    return;
  }
  const int tid = threadIdx.x, warp = uni(tid >> 5), lane = tid & 31, wg = warp >> 2, w4 = warp & 3, g = lane >> 2, t = lane & 3;
  const int h = role >> 2, j = role & 3, jh = j & 1;
  uint32_t w[48][4];
  float aq[16], av[16];
  int it = 0;

#define PT(k)
  auto pf_wo = [&]() {
    for (int i = 0; i < 4; i++)
      asm volatile("cp.async.bulk.prefetch.tensor.2d.L2.global [%0, {%1, %2}];" :: "l"(&maps.wo), "r"(256 * j + 64 * i), "r"(h * DH) : "memory");
  };
  fft_rows_fwd(fx, wr, wi, sb + R_MEM + 49152, role, [&]() {
    if (tid == 224) {
      mbar_init(sb + B_KV, 1); mbar_init(sb + B_W, 1); mbar_init(sb + B_X, 1); mbar_init(sb + B_X + 8, 1); mbar_init(sb + B_X + 16, 1); mbar_init(sb + B_X + 24, 1); mbar_init(sb + B_C, 4); mbar_init(sb + B_PK, 4); mbar_init(sb + B_B, 1);
      asm volatile("fence.mbarrier_init.release.cluster;" ::: "memory");
      mbar_expect_tx(sb + B_W, 3 * 65536);
      for (int i = 0; i < 4; i++) {
        tma2d(sb + R_X + i * 16384, &maps.wq, h * DH + 32 * j, i * 256, sb + B_W);
        if (i < 3) tma2d(sb + R_MEM + i * 16384, &maps.wk, h * DH + 32 * j, i * 256, sb + B_W);
        else asm volatile("cp.async.bulk.prefetch.tensor.2d.L2.global [%0, {%1, %2}];" :: "l"(&maps.wk), "r"(h * DH + 32 * j), "r"(768) : "memory");
      }
      for (int i = 0; i < 2; i++) tma2d(sb + R_WO + i * 32768, &maps.wv, h * DH + 64 * (j >> 1), jh * 512 + i * 256, sb + B_W);
      if (PFD) asm volatile("cp.async.bulk.prefetch.L2.global [%0], 2048;" :: "l"(xin + role * DM) : "memory");
      else for (int i = 0; i < 4; i++) asm volatile("cp.async.bulk.prefetch.L2.global [%0], 8192;" :: "l"(xin + role * 16384 + i * 4096) : "memory");
      if (WOP == 0) pf_wo();
    }
    __syncwarp();
  });
  if (tid < 16) sts32(sb + R_T + tid * 4, ~0u);
  fence_async();
  PT(0);
  grid_arrive(&gx->ctr[33]);
  PT(1);
  if (tid == 224) { tma2d(sb + R_MEM + 49152, &maps.wk, h * DH + 32 * j, 768, sb + B_W); if (WOP == 1) pf_wo(); }
  __syncwarp();
  uint8_t* const xb = reinterpret_cast<uint8_t*>(gx);
  auto probe_at = [&](int n) { return xb + (n ? offsetof(Xchg, C) + w4 * 8192 + role * 32 : offsetof(Xchg, B) + role * 8192 + warp * 128); };
  if (lane < 8) stx128(probe_at(lane >> 2) + (lane & 2) * 2048 + (lane & 1) * 16, 0, 0, 0, 0);
  uint32_t m0[4][4];
#pragma unroll
  for (int i = 0; i < 16; i++) m0[i >> 2][i & 3] = ldnc32(mem0 + g * DM + 128 * warp + 8 * i + 2 * t);
  mbar_spin(sb + B_W, 0, it);
  PT(2);
  const int lrow = (lane & 7) + ((lane >> 4) << 3), lhi = (lane >> 3) & 1;
  const int kq = wg ? 3 - 3 * jh : 3 * jh;
  const uint32_t LW = lrow * 128 + ((lhi ^ (lane & 7)) << 4);
  {
    const int chunk = w4 < 2 ? w4 + 2 * lhi : 2 * (w4 & 1) + lhi;
    uint32_t a = sb + (w4 < 2 ? R_X : R_MEM) + kq * 16384 + lrow * 64 + ((chunk ^ ((lrow >> 1) & 3)) << 4);
#pragma unroll
    for (int i = 0; i < 16; i++) ldsm4t(w[i], a + i * 1024);
    const uint32_t st = wg ? 1024 : 2048, av0 = sb + R_WO + (LW ^ (w4 << 5));
    const uint32_t a1 = wg ? a + (2 * jh - 1) * 16384 : av0 + jh * 32768, a2 = wg ? a + (2 * jh - 1) * 32768 : av0 + (1 - jh) * 32768;
#pragma unroll
    for (int i = 0; i < 16; i++) { ldsm4t(w[16 + i], a1 + i * st); ldsm4t(w[32 + i], a2 + i * st); }
  }
  uint32_t L16 = pin(lane * 16);
  const uint32_t uW = uni(sb + w4 * 512), uWo = uni(sb + R_WO + w4 * 16384), uMem = uni(sb + R_MEM + kq * 4096);
  const uint32_t dX = uni(((sb + R_X + kq * 16384) >> 4) | 0x10000u);
  auto load_wo = [&](uint32_t (&d)[32][4], int i0, int i1) {
#pragma unroll
    for (int i = i0; i < i1; i++) lds128(d[i], uWo + L16 + (i & 1) * 512 + (i >> 4) * 1024 + (i & 14) * 1024);
  };
  auto issue_x = [&](int n, int k) {
    const uint32_t bar = sb + B_X + 8 * k, q = k ^ (3 - 3 * jh);
    mbar_expect_tx(bar, 16384); tma3d(sb + R_X + q * 16384, &maps.x, n * SEG, 4 * q, bar);
  };
  auto store_stage = [&](int n) {
    asm volatile("cp.async.bulk.global.shared::cta.bulk_group [%0], [%1], 8192; cp.async.bulk.commit_group;"
                 :: "l"(g_kqv[n & 3][role]), "r"(sb + R_STAGE) : "memory");
  };
  auto issue_kqv = [&](int n) {
    const int p = (n & 3) * 128 + 4 * h;
    mbar_expect_tx(sb + B_KV, 26624);
    tma3d(sb + R_K, &maps.k, 0, p, sb + B_KV); tma3d(sb + R_Q, &maps.q, 8 + 2 * j, p, sb + B_KV); tma3d(sb + R_V, &maps.v, 16, p, sb + B_KV);
  };
  auto fetch4k = [&](uint32_t dst, uint32_t off, uint32_t bar, uint32_t t) {
    asm volatile("{.reg .pred p, q; .reg .b32 g; .reg .b64 c; elect.sync _|q, 0xffffffff; @q mbarrier.arrive.expect_tx.shared::cta.b64 _, [%2], 4096;\n"
                 "LOOP: mov.u64 c, %%globaltimer; cvt.u32.u64 g, c; sub.s32 g, %3, g; setp.lt.u32 p, g, 16384; @p bra.uni LOOP;\n"
                 "@q cp.async.bulk.shared::cluster.global.mbarrier::complete_tx::bytes [%0], [%1], 4096, [%2];}" :: "r"(dst), "l"(xb + off), "r"(bar), "r"(t - 1) : "memory");
  };
  uint32_t uS;
  auto my_b = [&]() { return offsetof(Xchg, B) + role * 8192 + ((uS + ((uint32_t)it >> 31)) & 1) * 4096; };
  auto issue_c = [&](uint32_t t) { fetch4k(sb + R_MEM + w4 * 4096, offsetof(Xchg, C) + w4 * 8192 + ((uS + ((uint32_t)it >> 31)) & 4096), sb + B_C, t); };
  auto wait_x = [&](int n, int i) { if (!(EXP & 1) || n < 2) mbar_spin(sb + B_X + 8 * i, n & 1, it); };
#define PACED(d0) uint32_t dz = d0; const uint32_t z = (uint32_t)it >> 31; auto pace = [&]() { for (int k = 0; k < PACE; k++) { if (k & 1) asm("add.u32 %0, %0, %1;" : "+r"(dz) : "r"(z)); else asm("xor.b32 %0, %0, %1;" : "+r"(dz) : "r"(z)); } };
  auto project_v = [&](auto I0, auto I1, auto&& mid) {
    PACED(decltype(I0)::value < 16 ? dX : dX ^ 1024);
    wg_fence();
    sfor<decltype(I0)::value, decltype(I1)::value>([&](auto I) {
      constexpr int i = decltype(I)::value;
      mid(i);
      if (i == 16 && decltype(I0)::value < 16) dz ^= 1024;
      wg_rs32<((i >> 2) & 3) * 256 + (i & 3) * 2, (i > 0)>(av, w[16 + i], dz);
      pace();
    });
    wg_commit();
  };
  auto project_qk = [&](auto I0, auto I1, auto first, auto&& mid) {
    PACED((dX ^ (decltype(I0)::value >> 4 << 10)) + ((uint32_t)it >> 31));
    wg_fence();
    sfor<decltype(I0)::value, decltype(I1)::value>([&](auto I) {
      constexpr int i = decltype(I)::value;
      mid(i);
      wg_rs32<((i >> 2) & 3) * 256 + (i & 3) * 2, !decltype(first)::value || i != decltype(I0)::value>(aq, w[i], dz);
      pace();
    });
    wg_commit();
  };
  const uint32_t uP = uni(sb + R_X + 3 * jh * 16384 + w4 * 512);
  auto park = [&]() {
    bar_sync(1, 128);
#pragma unroll
    for (int i = 0; i < 4; i++) sts128f(uP + L16 + i * 2048, aq + 4 * i);
    warp_arrive(sb + B_PK);
  };
  auto unpark = [&]() {
#pragma unroll
    for (int i = 0; i < 4; i++) {
      const float4 p = lds128f(uP + L16 + i * 2048);
      av[4 * i] = p.x; av[4 * i + 1] = p.y; av[4 * i + 2] = p.z; av[4 * i + 3] = p.w;
    }
  };
  auto fin_qk = [&]() {
#pragma unroll
    for (int i = 0; i < 16; i++) aq[i] += av[i];
    const uint32_t a = sb + R_STAGE + (w4 < 2 ? 2048 + w4 * 128 : (w4 & 1) * 256) + (L16 & 112) + (L16 >> 7) * 512;
    stsm4t(a, pack2(aq[0], aq[1]), pack2(aq[4], aq[5]), pack2(aq[8], aq[9]), pack2(aq[12], aq[13]));
    stsm4t(a + (w4 < 2 ? 256 : 128), pack2(aq[2], aq[3]), pack2(aq[6], aq[7]), pack2(aq[10], aq[11]), pack2(aq[14], aq[15]));
  };
  auto fin_v = [&]() {
#pragma unroll
    for (int a = 0; a < 2; a++)
      sts128(sb + R_STAGE + 4096 + w4 * 1024 + a * 512 + L16, pack2(av[8 * a], av[8 * a + 1]), pack2(av[8 * a + 2], av[8 * a + 3]),
             pack2(av[8 * a + 4], av[8 * a + 5]), pack2(av[8 * a + 6], av[8 * a + 7]));
  };
  __syncthreads();
  if (tid == 224) {
#pragma unroll 1
    for (int i = 0; i < 4; i++) issue_x(0, i);
    mbar_expect_tx(sb + B_W, 65536);
    for (int i = 0; i < 4; i++) tma2d(sb + R_WO + i * 16384, &maps.wo, 256 * j + 64 * i, h * DH, sb + B_W);
  }
  __syncwarp();
  if (wg) {
#pragma unroll
    for (int i = 0; i < NSW; i++) sts128(uW + R_WC + L16 + i * 2048, w[i]);
  }
#pragma unroll
  for (int i = 0; i < 4; i++) sts128(sb + R_MEM + warp * 2048 + i * 512 + (g >> 1) * 128 + t * 32 + (g & 1) * 16, m0[i]);
  auto probe = [&](int n, int cnt) {
    if (lane == 0) {
#pragma unroll 1
      for (int i = role >> 7; i < cnt; i++) {
        const int k = (i ^ wg) & 1;
        const unsigned t0 = clk();
        uint32_t v; asm volatile("atom.relaxed.gpu.global.exch.b32 %0, [%1], 0;" : "=r"(v) : "l"(probe_at(n) + k * 4096) : "memory");
        if (v == 0) asm volatile("red.shared.min.u32 [%0], %1;" :: "r"(sb + R_T + (n ? w4 * 8 : 32) + k * 4), "r"(clk() - t0) : "memory");
      }
    }
    __syncwarp();
  };
#pragma unroll 1
  for (int n = 0; n < 2; n++) {
    probe(0, NPB);
    PT(3 + 3 * n);
    wait_x(n, 2);
    PT(4 + 3 * n);
    if (wg == 0) {
      wait_x(n, 3);
      project_qk(IC<0>{}, IC<16>{}, IC<1>{}, [](int) {});
      project_v(IC<0>{}, IC<32>{}, [](int) {});
      if (tid == 96 && n == 1) {
        asm volatile("cp.async.bulk.wait_group 0;" ::: "memory");
        __threadfence(); atomicAdd(&gx->ctr[h], 1u);
      }
      __syncwarp();
      wg_wait<0>(); keep(aq); keep(av);
      park();
      fin_v();
      fence_async();
    } else {
      wait_x(n, 0); wait_x(n, 1);
      project_qk(IC<32>{}, IC<48>{}, IC<1>{}, [](int) {});
      project_qk(IC<16>{}, IC<32>{}, IC<0>{}, [](int) {});
      project_qk(IC<0>{}, IC<16>{}, IC<0>{}, [](int) {});
      mbar_spin(sb + B_PK, n, it);
      unpark();
      wg_wait<0>(); keep(aq);
      fin_qk();
      fence_async();
    }
    __syncthreads();
    if (tid == 0 && n) stx32(&gx->S[role], 1 + (HOME & 2 && lds32(sb + R_T + 36) < lds32(sb + R_T + 32)));
    PT(5 + 3 * n);
    if (tid == 96 && n == 0) store_stage(0);
    if (tid == 128 && n == 0) {
#pragma unroll 1
      for (int i = 0; i < 4; i++) issue_x(1, i);
    }
    if (warp == 5 && n == 1) {
#pragma unroll 1
      while (__any_sync(0xffffffffu, ldx32(&gx->ctr[h]) < 4) && ++it < SPIN_LIMIT) {}
      __threadfence(); asm volatile("fence.proxy.async;" ::: "memory");
      if (elect()) issue_kqv(0);
    }
    __syncwarp();
  }
  mbar_spin(sb + B_W, 1, it);
  PT(9);
#pragma unroll
  for (int i = 0; i < 4; i++) {
    uint32_t f[4][4];
    const uint32_t a = sb + R_WO + warp * 8192 + i * 2048;
#pragma unroll
    for (int q = 0; q < 4; q++) ldsm4t(f[q], a + (LW ^ (q << 5)));
    __syncwarp();
#pragma unroll
    for (int q = 0; q < 4; q++) sts128(a + q * 512 + L16, f[q]);
  }
  probe(1, NPC);
  {
    const int o = 32 * w4 + 16 * wg + 4 * t + j;
    uint32_t v;
#pragma unroll 1
    while (__any_sync(0xffffffffu, (v = ldx32(&gx->S[o])) == 0) && ++it < SPIN_LIMIT) {}
    asm volatile("st.shared.u64 [%0], %1;" :: "r"(sb + R_DST + wg * 1024 + w4 * 256 + lane * 8), "l"(xb + offsetof(Xchg, B) + o * 8192 + (v >> 1) * 4096 + h * 128 + ((g ^ h) & 7) * 16) : "memory");
  }
  if (wg == 0) {
    const uint64_t cd = reinterpret_cast<uint64_t>(xb + (offsetof(Xchg, C) + j * 8192 + h * 128 + w4 * 32 + (L16 & 16) * 256 + (L16 & 64) / 4 + (L16 >> 7) * 4));
    sts128(uW + R_RD + L16, (uint32_t)cd, (uint32_t)(cd >> 32), sb + R_MEM + (L16 & 112) * 8 + (L16 >> 8) * 1024 + ((w4 * 32 + ((L16 >> 3) & 16)) ^ (L16 & 112)),
           (L16 >> 6) == (h & 3) * 2 + ((h >> 2) & 1) ? 0xFFFE0000u : 0xFFFFFFFFu);
  }
  PT(10);
  mbar_spin(sb + B_KV, 0, it);
  PT(11);
  if (tid == 0) sts32(sb + B_DUE + 8, gtime() & ~31u);
  if (tid < 4) sts32(sb + B_ONE + tid * 4, 0x3F803F80u);
  if (warp == 1) { const uint32_t e = g >> 1 == t ? 0x3F80u << (16 * (g & 1)) : 0u; sts128(sb + R_ID + L16, e, 0, 0, e); }
  __syncthreads();
  uS = uni((HOME & 1 ? lds32(sb + R_T + w4 * 8 + 4) < lds32(sb + R_T + w4 * 8) : j >> 1) * 4096 + (HOME & 2 && lds32(sb + R_T + 36) < lds32(sb + R_T + 32)));

  const float sc = 0.08838834764831845f * 1.4426950408889634f;
  uint8_t* const xa = xb + uni(h * 16384);
  const uint32_t uA = uni(wg ? (w4 >> 1) * 2048 + j * 512 + (w4 & 1) * 256 : 8192 + (4 * (j >> 1) + w4) * 512 + jh * 256);
  const uint32_t uP2 = uni(sb + R_P + w4 * 256);
  uint32_t nc = 1;
  uint32_t ma;
  const uint8_t* adst;
  auto pin_mem = [&]() { adst = pinp(xa + uA + L16 / 2); ma = pin(uMem + (L16 & 384) + (L16 & 48) * 2 + (L16 & 64) / 4); };
  pin_mem();

#pragma unroll 1
  for (int s = 0;; nc++) {
    const uint32_t tag = (s + 1) & 1;
    auto fresh = [&]() { L16 += (uint32_t)it >> 31; };
    auto get_due = [&]() { return lds32(sb + B_DUE + 4 + tag * 4); };
    float c[4][4], r4[4];
    auto fold = [&]() {
#pragma unroll
      for (int i = 0; i < 4; i++) r4[i] = ((c[0][i] + c[1][i]) + c[2][i]) + c[3][i];
    };
    auto mma4 = [&](int n, const uint32_t (&b0)[4], const uint32_t (&b1)[4]) {
      mma_h(c[0], w[n + 2], b1, 0); mma_h(c[1], w[n + 3], b1, 1); mma_h(c[2], w[n], b0, 0); mma_h(c[3], w[n + 1], b0, 1);
    };
    auto xpos = [&](int pos, int wp) {
      if ((pos == X0 || pos == X1 || pos == X2 || pos == X3) && warp == wp && s + 1 < NSEG && elect()) {
        const int z = (uint32_t)it >> 31;
        if (pos == X2) issue_x(s + 2, 2 + z);
        if (pos == X3) issue_x(s + 2, 3 + z);
        if (pos == X1) issue_x(s + 2, 1 + z);
        if (pos == X0) issue_x(s + 2, z);
      }
      __syncwarp();
    };
    if (wg == 0) {
      mbar_spin(sb + B_C, nc & 1, it);
      TS(13);
      uint32_t b[16][4], tg[4];
#pragma unroll
      for (int i = 0; i < PD0; i++) { lds128(b[i], ma + i * 512); __syncwarp(); }
      sched();
      zero(c);
#pragma unroll
      for (int i = 0; i < 8; i++) {
        const int k = i ^ 1;
        mma_h(c[0], w[2 * k], b[k], 0); mma_h(c[1], w[2 * k + 1], b[k], 1);
        if (i < 2 * NV0) { mma_h(c[2], w[16 + 2 * k], b[k], 0); mma_h(c[3], w[17 + 2 * k], b[k], 1); }
        sched();
        if ((i & 1) && i + PD0 < 9) { lds128(b[i + PD0 - 1], ma + (i + PD0 - 1) * 512); __syncwarp(); lds128(b[i + PD0], ma + (i + PD0) * 512); sched(); }
        if (i == TGP) {
          fresh();
#pragma unroll
          for (int k = 0; k < 4; k++) tg[k] = lds32((uW * 4 + L16) * 2 + (L16 >> 6) * 4 + (R_MEM + k * 1024 - 7 * sb));
          sched();
        }
      }
#pragma unroll
      for (int i = 0; i < 4; i++) { r4[i] = c[0][i] + c[1][i]; c[0][i] = c[1][i] = 0.f; }
      sts128f(uW + R_RED + L16, r4);
      TS(1);
      const uint32_t old = bar_or(4, (dif2(tg[0], tg[1], s) | dif2(tg[2], tg[3], s)) & (s > 0));
      TS(0);
#pragma unroll
      for (int i = 0; i < 2 * NV0; i++) { lds128(b[8 + i], (ma ^ 4096) + i * 512); __syncwarp(); }
      sched();
#pragma unroll
      for (int i = NV0; i < 8; i++) {
        if (VB && i == VB) bar_sync(7, 256);
        mma4(16 + 4 * i, b[2 * i], b[2 * i + 1]);
        if (i < 7) sched();
        if (i < 4) { lds128(b[8 + 2 * i], (ma ^ 4096) + i * 1024); __syncwarp(); lds128(b[9 + 2 * i], (ma ^ 4096) + i * 1024 + 512); sched(); }
      }
      fold();
      asm volatile("{.reg .pred p; setp.eq.u32 p, %3, 0; @p st.relaxed.gpu.global.v2.b32 [%0], {%1,%2};}" :: "l"(adst), "r"((pack2(r4[0], r4[1]) & ~1u) | tag), "r"(pack2(r4[2], r4[3])), "r"(old) : "memory");
      sched();
      const unsigned tpub = clk();
      if (__any_sync(0xffffffffu, old) && nc < NC_MAX) {
        bar_sync(3, 256);
        issue_c(gtime());
        continue;
      }
      TS(3);
      xpos(0, 0);
      const uint32_t due = get_due();
      uint32_t vf[4][4], vm[2][4], p[4], pm, o[4];
      const uint32_t va = sb + R_V + (w4 >> 1) * 8192 + (w4 & 1) * 2048 + L16;
#pragma unroll
      for (int i = 0; i < 4; i++) {
        uint32_t q[4]; lds128(vf[i], va + i * 512); lds128(q, va + 4096 + i * 512);
#pragma unroll
        for (int e = 0; e < 4; e++) vf[i][e] = hadd2(vf[i][e], q[e]);
      }
      const uint32_t pa = pin(sb + R_P + (L16 >> 1));
      const uint8_t* vsrc = pinp(xa + 8192 + w4 * 1024 + L16 / 2);
      uint32_t one[4];
      lds128(one, sb + B_ONE);
      auto pv_x = [&]() {
        zero(c);
        mma_a(c[2], one, p[0], p[1]);
        mma_a(c[0], vf[0], p[0], p[1]); mma_a(c[1], vf[2], p[0], p[1]);
        sched();
        mma_a(c[2], one, p[2], p[3]);
        mma_a(c[0], vf[1], p[2], p[3]); mma_a(c[1], vf[3], p[2], p[3]);
        sched();
      };
      auto pv_m = [&]() {
        mma1688(c[2], one[0], one[1], pm);
        mma_a(c[0], vm[0], pm, pm);
        sched();
        mma_a(c[1], vm[1], pm, pm);
      };
      auto norm = [&]() {
        const float n0 = rcp(c[2][0]), n1 = rcp(c[2][1]);
#pragma unroll
        for (int i = 0; i < 4; i++) o[i] = pack2(c[i >> 1][2 * (i & 1)] * n0, c[i >> 1][2 * (i & 1) + 1] * n1);
        return ((__float_as_uint(c[2][0]) - 0x1F800000u) | (__float_as_uint(c[2][1]) - 0x1F800000u)) >> 30;
      };
      auto load_m = [&](int x) { const float2 e0 = lds64f(pa + 512 + x * 1024), e1 = lds64f(pa + 768 + x * 1024); pm = pack2(e0.x * e1.x, e0.y * e1.y); };
      auto attend_max = [&](int x) {
        float2 sv[6];
#pragma unroll
        for (int i = 0; i < 6; i++) sv[i] = lds64f(pa - 3072 + x * 1536 + i * 256);
        sv[4].x += sv[5].x; sv[4].y += sv[5].y;
        const int dq = (int)(L16 >> 6) - (int)((L16 >> 3) & 6) + 8 * j;
        float m = fmaxf(sv[4].x, sv[4].y);
#pragma unroll
        for (int i = 0; i < 4; i++) {
          if (x && 8 * i > dq) sv[i].x = -INFINITY;
          if (x && 8 * i + 1 > dq) sv[i].y = -INFINITY;
          m = fmaxf(m, fmaxf(sv[i].x, sv[i].y));
        }
        m = fmaxf(m, __shfl_xor_sync(0xffffffffu, m, 1));
        m = fmaxf(m, __shfl_xor_sync(0xffffffffu, m, 2));
#pragma unroll
        for (int i = 0; i < 5; i++) (i < 4 ? p[i] : pm) = pack2(ex2(sv[i].x - m), ex2(sv[i].y - m));
        pv_x(); pv_m(); norm();
      };
      uint32_t tq[4];
      auto get_t = [&]() {
        tq[0] = tq[1] = tq[2] = tq[3] = 0;
        asm volatile("{.reg .pred p; setp.eq.u32 p, %5, 0; @p ld.relaxed.gpu.global.v4.b32 {%0,%1,%2,%3}, [%4];}"
                     : "+r"(tq[0]), "+r"(tq[1]), "+r"(tq[2]), "+r"(tq[3]) : "l"(xb + offsetof(Xchg, T) + L16 * 8), "r"(warp) : "memory");
      };
      delay_until(tpub + DLY_V);
      wait_time(due + NS_V);
      TS(4);
      ldx(vm, vsrc);
      sched();
      xpos(2, 2);
      auto store_kqv = [&]() {
        fence_async();
        if (!(EXP & 4))
          asm volatile("{.reg .pred p; elect.sync _|p, 0xffffffff; @p cp.async.bulk.global.shared::cta.bulk_group [%0], [%1], 2048; cp.async.bulk.commit_group;}"
                       :: "l"(g_kqv[(s + 1) & 3][role] + w4 * 128), "r"(sb + R_STAGE + w4 * 2048) : "memory");
      };
      if (SPOS == 2) store_kqv();
      sched();
      bar_sync(5, 256);
      ldsm4(p, sb + R_P + L16);
      load_m(0);
      pv_x();
      ldsm4(p, sb + R_P + 1024 + L16);
      pv_m();
      const uint32_t r = norm(), tl = after(tag, c[2][0], (uint32_t)it >> 31);
      const bool redo = __any_sync(0xffffffffu, r | ((dif2(vm[0][0], vm[0][2], tl) | dif2(vm[1][0], vm[1][2], tl)) & 1));
      TS(6);
      stsm4t(uW + R_O + L16, o[0], o[1], o[2], o[3]);
      bar_arrive_unless(6, redo);
      sched();
      if (TQL == 7) get_t();
      TS(7);
      pv_x();
      if (rare(redo)) retry<2>(vm, vsrc, tag, it);
      bar_sync(8, 256);
      load_m(1);
      pv_m();
      if (rare(__any_sync(0xffffffffu, norm()) || redo)) {
        fresh();
#pragma unroll 1
        for (int x = !redo; x < 2; x++) {
          attend_max(x);
          if (x == 0) { stsm4t(uW + R_O + L16, o[0], o[1], o[2], o[3]); bar_arrive(6, 256); }
        }
      }
      TS(8);
      if (TQL == 8) get_t();
      const bool xok = mbar_test(sb + B_X + 16, s & 1) & mbar_test(sb + B_X + 24, s & 1);
      xpos(4, 2);
      fresh();
      const uint32_t ob = uni(sb + R_MEM + 4096 + w4 * 1024);
      stsm4t(ob + (L16 & 112) * 4 + (((L16 >> 3) ^ (L16 >> 1)) & 48), o[0], o[1], o[2], o[3]);
      __syncwarp();
      uint32_t rd[4];
      lds128(rd, uW + R_RD + L16);
      lds128(o, ob + (L16 ^ ((L16 >> 3) & 48)));
      auto put_o = [&]() {
        *reinterpret_cast<uint4*>(reinterpret_cast<uint8_t*>(g_ox) + (((s * SEG + 8 * j) * HD + h * DH + 32 * w4) * 2 + (L16 >> 6) * (HD * 2) + (L16 & 48))) = make_uint4(o[0], o[1], o[2], o[3]);
      };
      if (s + 1 == NSEG) { put_o(); asm volatile("cp.async.bulk.wait_group 0;" ::: "memory"); break; }
      asm volatile("cp.async.bulk.wait_group 0;" ::: "memory");
      if (elect()) stx32(xa + 4096 + j * 16 + w4 * 4, s + 1);
      __syncwarp();
      if (rare(!xok)) { wait_x(s + 2, 3); wait_x(s + 2, 2); }
      TS(9);
      fresh();
      const uint32_t e = due | ((s + 1) & 31);
      project_qk(IC<0>{}, IC<NQ>{}, IC<1>{}, [&](int n) {
        if (n == OXPOS) { __syncwarp(); put_o(); __syncwarp(); }
        if (n == TQP) { __syncwarp(); tq[0] = dif2v(tq[0], tq[1], e) | dif2v(tq[2], tq[3], e); __syncwarp(); }
      });
      if (NPA) project_v(IC<0>{}, IC<NPA>{}, [](int) {});
      TS(2);
      if (warp == 0) {
        uint32_t last = due, nx = NS_P;
        if (rare(__any_sync(0xffffffffu, tq[0]))) {
          const uint32_t ref = gtime();
#pragma unroll 1
          do ldx128(o, xb + offsetof(Xchg, T) + L16 * 8); while (any_bit(or3(o[0] - s - 1, o[1] - s - 1, o[2] - s - 1), o[3] - s - 1, 30) && ++it < SPIN_LIMIT);
          const int d = max(max((int)(o[0] - ref), (int)(o[1] - ref)), max((int)(o[2] - ref), (int)(o[3] - ref)));
          last = (ref + __reduce_max_sync(0xffffffffu, d)) & ~31u;
          if (last != due) nx += NS_X;
        }
        sts32(sb + B_DUE, last);
        sts32(sb + B_DUE + 8 - tag * 4, last + nx);
        fetch4k(sb + R_MEM, my_b(), sb + B_B, last + NS_B);
        LOG(13, tl - last);
        LOG(9, last);
      }
      if (NQ < 16) project_qk(IC<NQ>{}, IC<16>{}, IC<0>{}, [](int) {});
      project_v(IC<NPA>{}, IC<NPRE>{}, [](int) {});
      const uint32_t ba = rd[2], msk = rd[3];
      const uint8_t* cdst = reinterpret_cast<const uint8_t*>(rd[0] | (uint64_t)rd[1] << 32);
      TS(14);
      mbar_spin(sb + B_B, s & 1, it);
      TS(10);
      uint32_t bq[2][4];
      auto sum_b = [&]() {
        ldsm4t(bq[0], ba); ldsm4t(bq[1], ba + 2048);
        sched();
#pragma unroll
        for (int i = 0; i < 8; i++) c[i >> 2][i & 3] = 0.f;
        mma_a(c[0], bq[0], 0x3F803F80u, 0x3F803F80u); mma_a(c[1], bq[1], 0x3F803F80u, 0x3F803F80u);
        const uint32_t t2 = tag * 0x10001u;
        const bool old = any_bit(or3(dif2(bq[0][0], bq[0][1], t2), dif2(bq[0][2], bq[0][3], t2), dif2(bq[1][0], bq[1][1], t2)), dif2(bq[1][2], bq[1][3], t2), L16 < 64 ? 0x10001u : 0u);
        const uint32_t T = (tag << 16) & ~msk, u = ((__float_as_uint(c[0][0] + c[1][0]) + ((0x10000u & ~msk) - T)) & msk) | T;
        asm volatile("{.reg .pred p; setp.eq.u32 p, %2, 0; @p st.relaxed.gpu.global.b32 [%0], %1;}"
                     :: "l"(cdst), "r"(pack2(__uint_as_float(u), c[0][2] + c[1][2])), "r"((uint32_t)(old || (L16 & 32))) : "memory");
        return old;
      };
      if (rare(sum_b())) {
#pragma unroll 1
        do {
          const uint8_t* p = xb + (my_b() + (ba - sb - R_MEM));
          ldx128(bq[0], p); ldx128(bq[1], p + 2048);
          sts128(ba, bq[0]); sts128(ba + 2048, bq[1]);
          __syncwarp();
          it += INC_B;
        } while (sum_b() && it < SPIN_LIMIT);
      }
      sched();
      TS(11);
      bar_arrive(0, 256);
      const unsigned tc = clk();
      const uint32_t cdue = lds32(sb + B_DUE) + NS_C;
      if (warp == 3) LOG(11, gtime() - cdue);
      fresh();
      wg_wait<0>(); keep(aq); keep(av);
      park();
      if (NPRE < 32) project_v(IC<NPRE>{}, IC<32>{}, [](int) {}); else fin_v();
      TS(12);
      delay_until(tc + DLY_C);
      issue_c(cdue);
      TS(5);
      LOG(warp, it);
      pin_mem();
      if (NPRE < 32) { wg_wait<0>(); keep(av); fin_v(); }
      if (!(EXP & 2)) mbar_spin(sb + B_KV, tag, it);
      TS(15);
    } else {
      uint32_t kf[8][4];
      auto load_k = [&]() {
        const uint32_t ka = sb + R_K + w4 * 1024 + (L16 & 112) + (L16 & 128) * 4 + (L16 & 256);
#pragma unroll
        for (int i = 0; i < 8; i++) ldsm4(kf[i], ka + (i >> 1) * 2048 + (i & 1) * 128);
      };
      auto put_p = [&](int x, uint32_t old, uint32_t again) {
        float e[4];
        const int dq = (int)((L16 >> 3) & 6) + 8 * j - (int)(L16 >> 6) - 16 * w4;
#pragma unroll
        for (int i = 0; i < 4; i++) { r4[i] = fmaf(c[3][i], sc, fmaf(c[2][i], sc, fmaf(c[0][i] + c[1][i], sc, __uint_as_float(i == 3 ? 0u - old : 0u)))); e[i] = x && dq + (i & 1) < 8 * (i >> 1) ? 0.f : ex2(r4[i]); }
        stsm2t(uP2 + x * 1024 + L16, pack2(e[0], e[1]), pack2(e[2], e[3]), again);
      };
      auto put_s = [&](int x) {
#pragma unroll
        for (int i = 0; i < 4; i++) sts32f(uW + R_S + x * 1536 + (L16 & 48) * 4 + (L16 >> 6) * 4 + (i & 1) * 32 + (i >> 1) * 256, r4[i]);
      };
      auto load_q = [&](uint32_t (&q)[4], uint32_t off) { ldsm4(q, sb + R_Q + (L16 & 112) + (L16 & 128) * 2 + (L16 >> 8) * 128 + off); };
      mbar_spin(sb + B_C, nc & 1, it);
      TS(13);
      float4 o4;
      uint32_t id[4], old;
      {
        uint32_t b[24][4];
#pragma unroll
        for (int i = 0; i < 2 * PD1; i++) { lds128(b[i], ma + i * 512); __syncwarp(); }
        sched();
        zero(c);
#pragma unroll
        for (int i = 0; i < 12; i++) {
          mma4(4 * i, b[2 * i], b[2 * i + 1]);
          if (i < 11) sched();
          if (i + PD1 < 12) { const int k = i + PD1; const uint32_t a = (ma ^ (k >> 2 << 12)) + (k & 3) * 1024; lds128(b[2 * k], a); __syncwarp(); lds128(b[2 * k + 1], a + 512); sched(); }
          if (i == RJ) { lds128(id, sb + R_ID + L16); sched(); }
          if (i == RI) { old = bar_or(4, 0); o4 = lds128f(uW + R_RED + L16); sched(); }
        }
      }
      TS(0);
      {
        float e[4] = {o4.x, o4.y, o4.z, o4.w};
#pragma unroll
        for (int i = 0; i < 4; i++) { r4[i] = (((e[i] + c[0][i]) + c[1][i]) + c[2][i]) + c[3][i]; e[i] = 0.f; }
        mma_a(e, id, pack2(r4[0], r4[1]), pack2(r4[2], r4[3]));
        sched();
        if (VB) bar_arrive(7, 256);
        sched();
        asm volatile("{.reg .pred p; setp.eq.u32 p, %3, 0; @p st.relaxed.gpu.global.v2.b32 [%0], {%1,%2};}" :: "l"(adst),
                     "r"((__byte_perm(__float_as_uint(e[0]), __float_as_uint(e[1]), 0x7632) & ~1u) | tag), "r"(__byte_perm(__float_as_uint(e[2]), __float_as_uint(e[3]), 0x7632)), "r"(old) : "memory");
        sched();
      }
      const unsigned tpub = clk(), now = gtime(), due = get_due();
      if (__any_sync(0xffffffffu, old) && nc < NC_MAX) { bar_sync(3, 256); continue; }
      TS(2);
      const uint8_t* asrc = pinp(adst + ((warp == 7) * 1024 - (int)uA));
      fresh();
      uint32_t wo[32][4];
      bool xok;
      auto reload = [&]() {
        sched();
#pragma unroll
        for (int i = RE0 + RE1; i < NSW; i++) lds128(w[i], uW + R_WC + L16 + i * 2048);
        sched();
      };
      auto out_proj = [&]() {
        uint32_t b[4][4];
        float d[4][4];
        uint8_t* dst[2];
        const uint32_t da = pin(uP2 + (R_DST - R_P) + L16 / 2);
        sched();
        TS(7);
        bar_sync(6, 256);
#pragma unroll
        for (int i = 0; i < 4; i++) { ldsm4(b[i], sb + R_O + i * 512 + L16); __syncwarp(); }
        sched();
        auto put_b = [&](uint8_t* a, const float (&e)[4][4]) {
          stx128(a, (pack2(e[0][0] + e[2][0], e[0][1] + e[2][1]) & ~1u) | tag, pack2(e[0][2] + e[2][2], e[0][3] + e[2][3]),
                 pack2(e[1][0] + e[3][0], e[1][1] + e[3][1]), pack2(e[1][2] + e[3][2], e[1][3] + e[3][3]));
        };
        zero(c); zero(d);
#pragma unroll
        for (int i = 0; i < 32; i++) {
          mma_h(i < 16 ? c[i & 3] : d[i & 3], wo[i], b[(i >> 2) & 3], (i >> 1) & 1);
          if (i >= LW0 && NB1 + i - LW0 < 32) { load_wo(wo, (NB1 + i - LW0) ^ 1, ((NB1 + i - LW0) ^ 1) + 1); __syncwarp(); }
          if (i == DL0 || i == DL1) asm volatile("ld.shared.u64 %0, [%1];" : "=l"(dst[i > DL0]) : "r"(da + (i > DL0) * 1024) : "memory");
          if (i >= 16 && i < 16 + RE0) { lds128(w[i - 16], uW + R_WC + L16 + (i - 16) * 2048); __syncwarp(); }
          if (i >= RP1 && i < RP1 + RE1) { lds128(w[i - RP1 + RE0], uW + R_WC + L16 + (i - RP1 + RE0) * 2048); __syncwarp(); }
          if (i == 22) put_b(dst[0], c);
          if ((i & 1) && (i < 20 || i > 22)) sched();
        }
        put_b(dst[1], d);
        sched();
        TS(6);
      };
      if (warp < 6) {
        delay_until(tpub + DLY_A);
        const int it0 = it;
        bool redo;
#pragma unroll 1
        do {
          uint32_t q[4][4], y[4];
          float d[4][4];
          wait_time(due);
          TS(4);
          ldx(q, asrc);
          sched();
          load_k();
          uint32_t qx[4][4];
#pragma unroll
          for (int i = 0; i < 4; i++) load_q(qx[i], i * 512);
          sched();
          load_wo(wo, 0, NE4);
          sched();
          zero(c);
#pragma unroll
          for (int i = 0; i < 8; i++) mma_h(c[i & 3], kf[i], qx[i >> 1], i & 1);
          put_p(1, 0, 0); put_s(1);
          sched();
          load_wo(wo, NE4, NA4);
          sched();
          zero(c); zero(d);
#pragma unroll
          for (int i = 0; i < 8; i++) {
            if (i == 0) { y[0] = dif2v(q[0][0], q[0][2], q[1][0]); sched(); }
            if (i == 3) { y[1] = dif2v(q[1][2], q[2][0], q[2][2]); sched(); }
            if (i == 6) { y[2] = dif2v(q[3][0], q[3][2], tag); sched(); }
            mma_h(i % 6 < 2 ? c[2 + i % 6] : d[i - 2], kf[i], q[i >> 1], i & 1);
            if (i == 2 || i == 5 || i == 7) sched();
          }
          y[0] = or_and(or3(y[0], y[1], dif2v(q[0][0], q[2][0], tag)), y[2], it < SPIN_LIMIT);
#pragma unroll
          for (int i = 0; i < 4; i++) { c[0][i] = d[0][i] + d[1][i]; c[1][i] = d[2][i] + d[3][i]; }
          put_p(0, y[0], it - it0);
          TS(5);
          bar_sync_unless(5, it - it0);
          redo = __any_sync(0xffffffffu, y[0]);
          it += INC_A;
        } while (redo);
        it -= INC_A;
        put_s(0);
        bar_arrive(8, 256);
        load_wo(wo, NA4, NB1);
        out_proj();
        if (warp == 4) LOG(12, tb);
      } else {
        uint32_t qx[2][4], q[4][4];
        if (warp == 6) {
          const uint32_t t1 = (now & ~31u) + NS_M;
          LOG(10, now - due);
          if (elect()) stx32(&gx->T[h][j], ((int)(t1 - due) > 0 ? t1 + NS_PEN : due) | ((s + 1) & 31));
          __syncwarp();
        }
        auto score = [&](const uint32_t (&a0)[4], const uint32_t (&a1)[4]) {
          zero(c);
#pragma unroll
          for (int i = 0; i < 4; i++) mma_h(c[i], i < 2 ? a0 : a1, q[2 + (i >> 1)], i & 1);
        };
        auto put_m = [&](uint32_t a, uint32_t old, uint32_t again) {
#pragma unroll
          for (int i = 0; i < 2; i++) { r4[i] = fmaf(c[3][2 + i], sc, fmaf((c[0][i] + c[1][2 + i]) + c[2][i], sc, __uint_as_float(i ? 0u - old : 0u))); r4[2 + i] = fmaf(r4[i] * 0x1p122f, 0.f, ex2(r4[i])); }
          asm volatile("{.reg .pred p; setp.eq.u32 p, %3, 0; @p st.shared.v2.f32 [%0], {%1,%2};}" :: "r"(a), "f"(r4[2]), "f"(r4[3]), "r"(again) : "memory");
        };
        delay_until(tpub + DLY_A);
        const uint32_t sa = sb + R_S + 512 + w4 * 256 + (L16 >> 1);
        const int it0 = it;
        bool redo;
#pragma unroll 1
        do {
          wait_time(due);
          TS(4);
          ldx<4, 2048>(q, asrc);
          sched();
          load_q(qx[0], (w4 & 1) * 1024); load_q(qx[1], (w4 & 1) * 1024 + 512);
          load_wo(wo, 0, NA6);
          sched();
          score(q[0], q[1]);
          sched();
          const uint32_t y = or_and(or3(dif2v(q[0][0], q[0][2], tag), dif2v(q[1][0], q[1][2], tag), dif2v(q[2][0], q[2][2], tag)), dif2v(q[3][0], q[3][2], tag), it < SPIN_LIMIT);
          put_m(sa + 2560, y, it - it0);
          TS(5);
          bar_arrive_unless(5, it - it0);
          redo = __any_sync(0xffffffffu, y);
          it += INC_A;
        } while (redo);
        it -= INC_A;
        sts64f(sa, r4[0], r4[1]);
        score(qx[0], qx[1]);
        put_m(sa + 3584, 0, 0);
        sts64f(sa + 1536, r4[0], r4[1]);
        bar_arrive(8, 256);
        load_wo(wo, NA6, NB1);
        out_proj();
      }
      TS(8);
      if (s + 1 == NSEG) break;
      wait_x(s + 2, 2);
      TS(9);
      fresh();
      if (N1) project_qk(IC<32>{}, IC<32 + N1>{}, IC<1>{}, [](int) {});
      TS(10);
      xpos(6, 6);
      uint32_t fl = s + 1;
      if (warp == 5) { wait_time(due + NS_F); fl = ldx32(xa + 4096 + ((L16 >> 2) & 60)); }
      reload();
      TS(14);
      pin_mem();
      wait_x(s + 2, 1); wait_x(s + 2, 0);
      if (warp == 5) {
#pragma unroll 1
        while (__any_sync(0xffffffffu, fl != s + 1) && !(EXP & 4) && ++it < SPIN_LIMIT) fl = ldx32(xa + 4096 + ((L16 >> 2) & 60));
        wait_time(due + (NS_B + NS_K));
        if (!(EXP & 2) && elect()) issue_kqv(s + 1);
        __syncwarp();
      }
      if (PFD && warp == 6 && s + PFD < NSEG && elect())
        asm volatile("cp.async.bulk.prefetch.L2.global [%0], 2048;" :: "l"(xin + ((s + PFD) * SEG + ((role + 4 * (role >> 5)) & 31)) * DM) : "memory");
      __syncwarp();
      TS(11);
      LOG(warp, it);
      if (warp == 4) LOG(8, nc);
      bar_sync(0, 256);
      if (N1 < 16) project_qk(IC<32 + N1>{}, IC<48>{}, IC<!N1>{}, [](int) {});
      project_qk(IC<16>{}, IC<32>{}, IC<0>{}, [&](int n) { if ((n & 15) == XWPOS) { __syncwarp(); xok = mbar_test(sb + B_PK, s & 1); __syncwarp(); } });
      if (rare(!xok)) mbar_spin(sb + B_PK, s & 1, it);
      unpark();
      project_qk(IC<0>{}, IC<16>{}, IC<0>{}, [](int) {});
      TS(12);
      wg_wait<0>(); keep(aq);
      TS(1);
      fin_qk();
      TS(15);
    }
    s++;
  }
  if (it >= SPIN_LIMIT || nc >= NC_MAX) g_err = 2;
}

typedef CUresult (*EncodeFn)(CUtensorMap*, CUtensorMapDataType, cuuint32_t, void*, const cuuint64_t*, const cuuint64_t*, const cuuint32_t*,
                             const cuuint32_t*, CUtensorMapInterleave, CUtensorMapSwizzle, CUtensorMapL2promotion, CUtensorMapFloatOOBfill);
static void make_map(EncodeFn fn, CUtensorMap* m, const void* p, uint64_t cols, uint64_t rows, uint64_t pitch, uint32_t bc, uint32_t br, CUtensorMapSwizzle sw) {
  cuuint64_t dims[2] = {cols, rows}, strides[1] = {pitch * 2};
  cuuint32_t box[2] = {bc, br}, es[2] = {1, 1};
  fn(m, CU_TENSOR_MAP_DATA_TYPE_BFLOAT16, 2, const_cast<void*>(p), dims, strides, box, es, CU_TENSOR_MAP_INTERLEAVE_NONE, sw,
     CU_TENSOR_MAP_L2_PROMOTION_L2_256B, CU_TENSOR_MAP_FLOAT_OOB_FILL_NONE);
}

extern "C" void kernel_launch(void* const* d_in, const int* in_sizes, int n_in, void* d_out, int out_size) {
  const bf16* Ax = (const bf16*)d_in[0]; const bf16* mem0 = (const bf16*)d_in[1];
  const bf16* Wq = (const bf16*)d_in[2]; const bf16* Wk = (const bf16*)d_in[3]; const bf16* Wv = (const bf16*)d_in[4];
  const bf16* Wo = (const bf16*)d_in[5];
  const bf16* Bx = (const bf16*)d_in[7]; const bf16* wr = (const bf16*)d_in[8]; const bf16* wi = (const bf16*)d_in[9];
  bf16* out = (bf16*)d_out;

  void* fp = nullptr; cudaDriverEntryPointQueryResult qr;
  cudaGetDriverEntryPoint("cuTensorMapEncodeTiled", &fp, cudaEnableDefault, &qr);
  EncodeFn fn = (EncodeFn)fp;
  void *kqv, *ox, *xr;
  cudaGetSymbolAddress(&xr, g_xraw);
  cudaGetSymbolAddress(&kqv, g_kqv); cudaGetSymbolAddress(&ox, g_ox);
  const CUtensorMapSwizzle S128 = CU_TENSOR_MAP_SWIZZLE_128B, S64 = CU_TENSOR_MAP_SWIZZLE_64B;

  GemmMaps m3; RecMaps mr;
  make_map(fn, &m3.a, ox, HD, S_LEN, HD, 64, 128, S128);
  make_map(fn, &m3.b[0], Wo, DM, HD, DM, 64, 64, S128);
  m3.b[1] = m3.b[0]; m3.b[2] = m3.b[0];
  make_map(fn, &m3.c, out, DM, S_LEN, 2 * DM, 64, 64, S128);
  make_map(fn, &mr.wq, Wq, HD, DM, HD, 32, 256, S64);
  make_map(fn, &mr.wk, Wk, HD, DM, HD, 32, 256, S64);
  make_map(fn, &mr.wv, Wv, HD, DM, HD, 64, 256, S128);
  make_map(fn, &mr.wo, Wo, DM, HD, DM, 64, 128, S128);
  {
    cuuint64_t dims[3] = {64, S_LEN, 16}, strides[2] = {DM * 2, 128};
    cuuint32_t box[3] = {64, 32, 4}, es[3] = {1, 1, 1};
    fn(&mr.x, CU_TENSOR_MAP_DATA_TYPE_BFLOAT16, 3, const_cast<bf16*>(Ax), dims, strides, box, es, CU_TENSOR_MAP_INTERLEAVE_NONE, S128,
       CU_TENSOR_MAP_L2_PROMOTION_L2_256B, CU_TENSOR_MAP_FLOAT_OOB_FILL_NONE);
  }
  for (int i = 0; i < 3; i++) {
    cuuint64_t dims[3] = {128, 32, 512}, strides[2] = {256, 8192};
    cuuint32_t box[3] = {128, i == 0 ? 8u : i == 1 ? 2u : 16u, 4}, es[3] = {1, 1, 1};
    fn(i == 0 ? &mr.k : i == 1 ? &mr.q : &mr.v, CU_TENSOR_MAP_DATA_TYPE_BFLOAT16, 3, kqv, dims, strides, box, es, CU_TENSOR_MAP_INTERLEAVE_NONE,
       CU_TENSOR_MAP_SWIZZLE_NONE, CU_TENSOR_MAP_L2_PROMOTION_L2_256B, CU_TENSOR_MAP_FLOAT_OOB_FILL_NONE);
  }
  {
    cuuint64_t dims[3] = {64, 16, S_LEN}, strides[2] = {128, 2 * DM * 2};
    cuuint32_t box[3] = {64, 16, 2}, es[3] = {1, 1, 1};
    fn(&mr.fo, CU_TENSOR_MAP_DATA_TYPE_BFLOAT16, 3, out + DM, dims, strides, box, es, CU_TENSOR_MAP_INTERLEAVE_NONE, S128,
       CU_TENSOR_MAP_L2_PROMOTION_NONE, CU_TENSOR_MAP_FLOAT_OOB_FILL_NONE);
  }
  constexpr int SM3 = 6 * 32768 + 32768 + 256 + 1024;
  cudaFuncSetAttribute(gemm_kernel<128, 6>, cudaFuncAttributeMaxDynamicSharedMemorySize, SM3);
  cudaFuncSetAttribute(rec_kernel, cudaFuncAttributeMaxDynamicSharedMemorySize, R_TOTAL);

  cudaStream_t st = cudaStreamPerThread;
  rec_kernel<<<132, 256, R_TOTAL, st>>>(mr, Ax, mem0, reinterpret_cast<Xchg*>((reinterpret_cast<uintptr_t>(xr) + 8191) & ~(uintptr_t)8191), Bx, wr, wi);
  gemm_kernel<128, 6><<<128, 384, SM3, st>>>(m3, 16, 8, 64, 8, 1);
}
```

```cpp
#include <cuda_runtime.h>
#include <cuda_bf16.h>
#include <cuda.h>
#include <stdint.h>
#include <stddef.h>
#include <type_traits>

typedef __nv_bfloat16 bf16;

constexpr int S_LEN = 2048, DM = 1024, NH = 32, DH = 128, MEM = 8, SEG = 32, NSEG = 64;
constexpr int HD = NH * DH;
#define SPIN 20
constexpr int SPIN_LIMIT = 1 << SPIN, INC_A = 1, INC_B = 1;

constexpr unsigned NC_MAX = 4096;
__device__ __align__(1024) uint4 g_kqv[4][128][512];
__device__ __align__(1024) bf16 g_ox[(size_t)S_LEN * HD];
struct Xchg {
  uint4 A[32][4][256];
  uint4 C[4][2][256];
  uint4 B[128][2][256];
  uint32_t T[32][32];
  uint32_t S[128];
  unsigned ctr[64];
};
__device__ __align__(1024) uint4 g_xraw[(sizeof(Xchg) + 8192) / 16];
__device__ __align__(1024) uint4 g_y[1024 * 256];
__device__ __align__(1024) uint4 g_wt[513 * 512];
__device__ int g_err;

__device__ __forceinline__ unsigned clk() { unsigned long long c; asm volatile("mov.u64 %0, %%clock64;" : "=l"(c)); return (unsigned)c; }
__device__ __forceinline__ uint32_t smem_u32(const void* p) { return (uint32_t)__cvta_generic_to_shared(p); }
__device__ __forceinline__ void mbar_init(uint32_t bar, int cnt) { asm volatile("mbarrier.init.shared::cta.b64 [%0], %1;" :: "r"(bar), "r"(cnt) : "memory"); }
__device__ __forceinline__ void mbar_expect_tx(uint32_t bar, int bytes) { asm volatile("mbarrier.arrive.expect_tx.shared::cta.b64 _, [%0], %1;" :: "r"(bar), "r"(bytes) : "memory"); }
__device__ __forceinline__ void mbar_arrive(uint32_t bar) { asm volatile("mbarrier.arrive.shared::cta.b64 _, [%0];" :: "r"(bar) : "memory"); }
__device__ __forceinline__ void mbar_arrive_cluster(uint32_t bar, int cta) {
  asm volatile("{.reg .b32 r; mapa.shared::cluster.u32 r, %0, %1; mbarrier.arrive.shared::cluster.b64 _, [r];}" :: "r"(bar), "r"(cta) : "memory"); }
__device__ __forceinline__ bool mbar_try(uint32_t bar, int par) {
  uint32_t ok; asm volatile("{.reg .pred p; mbarrier.try_wait.parity.shared::cta.b64 p, [%1], %2; selp.u32 %0, 1, 0, p;}" : "=r"(ok) : "r"(bar), "r"(par) : "memory"); return ok; }
__device__ __forceinline__ bool mbar_test(uint32_t bar, int par) {
  uint32_t ok; asm volatile("{.reg .pred p; mbarrier.test_wait.parity.shared::cta.b64 p, [%1], %2; selp.u32 %0, 1, 0, p;}" : "=r"(ok) : "r"(bar), "r"(par) : "memory"); return ok; }
__device__ __forceinline__ void mbar_wait(uint32_t bar, int par) {
  int it = 0;
  while (!mbar_try(bar, par)) { if (++it > SPIN_LIMIT) { g_err = 1; break; } }
}
__device__ __forceinline__ void tma2d(uint32_t dst, const CUtensorMap* m, int c0, int c1, uint32_t bar) {
  asm volatile("cp.async.bulk.tensor.2d.shared::cluster.global.mbarrier::complete_tx::bytes [%0], [%1, {%3, %4}], [%2];"
    :: "r"(dst), "l"(m), "r"(bar), "r"(c0), "r"(c1) : "memory"); }
__device__ __forceinline__ void tma2d_mc(uint32_t dst, const CUtensorMap* m, int c0, int c1, uint32_t bar, uint16_t mask) {
  asm volatile("cp.async.bulk.tensor.2d.shared::cluster.global.mbarrier::complete_tx::bytes.multicast::cluster [%0], [%1, {%3, %4}], [%2], %5;"
    :: "r"(dst), "l"(m), "r"(bar), "r"(c0), "r"(c1), "h"(mask) : "memory"); }
__device__ __forceinline__ void tma2d_store(const CUtensorMap* m, uint32_t src, int c0, int c1) {
  asm volatile("cp.async.bulk.tensor.2d.global.shared::cta.bulk_group [%0, {%2, %3}], [%1];" :: "l"(m), "r"(src), "r"(c0), "r"(c1) : "memory"); }
__device__ __forceinline__ void fence_async() { asm volatile("fence.proxy.async.shared::cta;" ::: "memory"); }
__device__ __forceinline__ void bar_sync(int id, int n) { asm volatile("bar.sync %0, %1;" :: "r"(id), "r"(n) : "memory"); }
__device__ __forceinline__ void bar_arrive(int id, int n) { asm volatile("bar.arrive %0, %1;" :: "r"(id), "r"(n) : "memory"); }
__device__ __forceinline__ uint32_t pack2(float lo, float hi) { uint32_t r; asm("cvt.rn.bf16x2.f32 %0, %1, %2;" : "=r"(r) : "f"(hi), "f"(lo)); return r; }
__device__ __forceinline__ uint32_t pack2_tag(float lo, float hi, uint32_t T) {
  uint32_t u = ((__float_as_uint(lo) - T + 0x10000u) & 0xFFFE0000u) + T;
  return __byte_perm(u, pack2(0.f, hi), 0x7632); }
__device__ __forceinline__ void ldsm4(uint32_t (&r)[4], uint32_t a) {
  asm volatile("ldmatrix.sync.aligned.m8n8.x4.shared.b16 {%0,%1,%2,%3}, [%4];" : "=r"(r[0]), "=r"(r[1]), "=r"(r[2]), "=r"(r[3]) : "r"(a) : "memory"); }
__device__ __forceinline__ void ldsm4t(uint32_t (&r)[4], uint32_t a) {
  asm volatile("ldmatrix.sync.aligned.m8n8.x4.trans.shared.b16 {%0,%1,%2,%3}, [%4];" : "=r"(r[0]), "=r"(r[1]), "=r"(r[2]), "=r"(r[3]) : "r"(a) : "memory"); }
__device__ __forceinline__ void stsm4(uint32_t a, uint32_t r0, uint32_t r1, uint32_t r2, uint32_t r3) {
  asm volatile("stmatrix.sync.aligned.m8n8.x4.shared.b16 [%0], {%1,%2,%3,%4};" :: "r"(a), "r"(r0), "r"(r1), "r"(r2), "r"(r3) : "memory"); }
__device__ __forceinline__ void stsm4t(uint32_t a, uint32_t r0, uint32_t r1, uint32_t r2, uint32_t r3) {
  asm volatile("stmatrix.sync.aligned.m8n8.x4.trans.shared.b16 [%0], {%1,%2,%3,%4};" :: "r"(a), "r"(r0), "r"(r1), "r"(r2), "r"(r3) : "memory"); }
__device__ __forceinline__ void lds128(uint32_t (&r)[4], uint32_t a) {
  asm volatile("ld.shared.v4.u32 {%0,%1,%2,%3}, [%4];" : "=r"(r[0]), "=r"(r[1]), "=r"(r[2]), "=r"(r[3]) : "r"(a) : "memory"); }
__device__ __forceinline__ float4 lds128f(uint32_t a) { float4 r;
  asm volatile("ld.shared.v4.f32 {%0,%1,%2,%3}, [%4];" : "=f"(r.x), "=f"(r.y), "=f"(r.z), "=f"(r.w) : "r"(a) : "memory"); return r; }
__device__ __forceinline__ float2 lds64f(uint32_t a) { float2 r;
  asm volatile("ld.shared.v2.f32 {%0,%1}, [%2];" : "=f"(r.x), "=f"(r.y) : "r"(a) : "memory"); return r; }
__device__ __forceinline__ void sts128(uint32_t a, uint32_t r0, uint32_t r1, uint32_t r2, uint32_t r3) {
  asm volatile("st.shared.v4.u32 [%0], {%1,%2,%3,%4};" :: "r"(a), "r"(r0), "r"(r1), "r"(r2), "r"(r3) : "memory"); }
__device__ __forceinline__ void sts64f(uint32_t a, float x, float y) { asm volatile("st.shared.v2.f32 [%0], {%1,%2};" :: "r"(a), "f"(x), "f"(y) : "memory"); }
__device__ __forceinline__ void sts32f(uint32_t a, float x) { asm volatile("st.shared.f32 [%0], %1;" :: "r"(a), "f"(x) : "memory"); }
__device__ __forceinline__ void mma16816(float (&d)[4], uint32_t a0, uint32_t a1, uint32_t a2, uint32_t a3, uint32_t b0, uint32_t b1) {
  asm volatile("mma.sync.aligned.m16n8k16.row.col.f32.bf16.bf16.f32 {%0,%1,%2,%3}, {%4,%5,%6,%7}, {%8,%9}, {%0,%1,%2,%3};"
    : "+f"(d[0]), "+f"(d[1]), "+f"(d[2]), "+f"(d[3]) : "r"(a0), "r"(a1), "r"(a2), "r"(a3), "r"(b0), "r"(b1)); }
__device__ __forceinline__ void mma1688(float (&d)[4], uint32_t a0, uint32_t a1, uint32_t b0) {
  asm volatile("mma.sync.aligned.m16n8k8.row.col.f32.bf16.bf16.f32 {%0,%1,%2,%3}, {%4,%5}, {%6}, {%0,%1,%2,%3};"
    : "+f"(d[0]), "+f"(d[1]), "+f"(d[2]), "+f"(d[3]) : "r"(a0), "r"(a1), "r"(b0)); }
__device__ __forceinline__ void ldx128(uint32_t (&r)[4], const void* p) {
  asm volatile("{.reg .b128 t; .reg .b64 a, b; ld.relaxed.gpu.global.b128 t, [%4]; mov.b128 {a, b}, t; mov.b64 {%0,%1}, a; mov.b64 {%2,%3}, b;}"
    : "=r"(r[0]), "=r"(r[1]), "=r"(r[2]), "=r"(r[3]) : "l"(p) : "memory"); }
__device__ __forceinline__ void ldx2x64(uint32_t (&r)[4], const void* p) {
  asm volatile("{.reg .b64 a, b; ld.relaxed.gpu.global.v2.b64 {a, b}, [%4]; mov.b64 {%0,%1}, a; mov.b64 {%2,%3}, b;}"
    : "=r"(r[0]), "=r"(r[1]), "=r"(r[2]), "=r"(r[3]) : "l"(p) : "memory"); }
__device__ __forceinline__ void stx128(void* p, uint32_t r0, uint32_t r1, uint32_t r2, uint32_t r3) {
  asm volatile("{.reg .b128 t; .reg .b64 a, b; mov.b64 a, {%1,%2}; mov.b64 b, {%3,%4}; mov.b128 t, {a, b}; st.relaxed.gpu.global.b128 [%0], t;}"
    :: "l"(p), "r"(r0), "r"(r1), "r"(r2), "r"(r3) : "memory"); }
__device__ __forceinline__ void stx64(void* p, uint32_t r0, uint32_t r1) {
  asm volatile("{.reg .b64 a; mov.b64 a, {%1,%2}; st.relaxed.gpu.global.b64 [%0], a;}" :: "l"(p), "r"(r0), "r"(r1) : "memory"); }
__device__ __forceinline__ uint32_t uni(uint32_t x) { return __shfl_sync(0xffffffffu, x, 0); }
__device__ __forceinline__ uint32_t pin(uint32_t x) { return __shfl_xor_sync(0xffffffffu, x, 0); }
__device__ __forceinline__ float ex2(float x) { float r; asm("ex2.approx.ftz.f32 %0, %1;" : "=f"(r) : "f"(x)); return r; }
__device__ __forceinline__ void wg_fence() { asm volatile("wgmma.fence.sync.aligned;" ::: "memory"); }
__device__ __forceinline__ void wg_commit() { asm volatile("wgmma.commit_group.sync.aligned;" ::: "memory"); }
template <int N> __device__ __forceinline__ void wg_wait() { asm volatile("wgmma.wait_group.sync.aligned %0;" :: "n"(N) : "memory"); }

__device__ __forceinline__ void wgmma_ss_n256_tb1(float (&d)[128], uint64_t da, uint64_t db, int sc) {
  asm volatile("{.reg .pred p; setp.ne.b32 p, %130, 0;\n"
    "wgmma.mma_async.sync.aligned.m64n256k16.f32.bf16.bf16 {%0,%1,%2,%3,%4,%5,%6,%7,%8,%9,%10,%11,%12,%13,%14,%15,%16,%17,%18,%19,%20,%21,%22,%23,%24,%25,%26,%27,%28,%29,%30,%31,%32,%33,%34,%35,%36,%37,%38,%39,%40,%41,%42,%43,%44,%45,%46,%47,%48,%49,%50,%51,%52,%53,%54,%55,%56,%57,%58,%59,%60,%61,%62,%63,%64,%65,%66,%67,%68,%69,%70,%71,%72,%73,%74,%75,%76,%77,%78,%79,%80,%81,%82,%83,%84,%85,%86,%87,%88,%89,%90,%91,%92,%93,%94,%95,%96,%97,%98,%99,%100,%101,%102,%103,%104,%105,%106,%107,%108,%109,%110,%111,%112,%113,%114,%115,%116,%117,%118,%119,%120,%121,%122,%123,%124,%125,%126,%127}, %128, %129, p, 1, 1, 0, 1;}\n"
    : "+f"(d[0]),"+f"(d[1]),"+f"(d[2]),"+f"(d[3]),"+f"(d[4]),"+f"(d[5]),"+f"(d[6]),"+f"(d[7]),"+f"(d[8]),"+f"(d[9]),"+f"(d[10]),"+f"(d[11]),"+f"(d[12]),"+f"(d[13]),"+f"(d[14]),"+f"(d[15]),"+f"(d[16]),"+f"(d[17]),"+f"(d[18]),"+f"(d[19]),"+f"(d[20]),"+f"(d[21]),"+f"(d[22]),"+f"(d[23]),"+f"(d[24]),"+f"(d[25]),"+f"(d[26]),"+f"(d[27]),"+f"(d[28]),"+f"(d[29]),"+f"(d[30]),"+f"(d[31]),"+f"(d[32]),"+f"(d[33]),"+f"(d[34]),"+f"(d[35]),"+f"(d[36]),"+f"(d[37]),"+f"(d[38]),"+f"(d[39]),"+f"(d[40]),"+f"(d[41]),"+f"(d[42]),"+f"(d[43]),"+f"(d[44]),"+f"(d[45]),"+f"(d[46]),"+f"(d[47]),"+f"(d[48]),"+f"(d[49]),"+f"(d[50]),"+f"(d[51]),"+f"(d[52]),"+f"(d[53]),"+f"(d[54]),"+f"(d[55]),"+f"(d[56]),"+f"(d[57]),"+f"(d[58]),"+f"(d[59]),"+f"(d[60]),"+f"(d[61]),"+f"(d[62]),"+f"(d[63]),"+f"(d[64]),"+f"(d[65]),"+f"(d[66]),"+f"(d[67]),"+f"(d[68]),"+f"(d[69]),"+f"(d[70]),"+f"(d[71]),"+f"(d[72]),"+f"(d[73]),"+f"(d[74]),"+f"(d[75]),"+f"(d[76]),"+f"(d[77]),"+f"(d[78]),"+f"(d[79]),"+f"(d[80]),"+f"(d[81]),"+f"(d[82]),"+f"(d[83]),"+f"(d[84]),"+f"(d[85]),"+f"(d[86]),"+f"(d[87]),"+f"(d[88]),"+f"(d[89]),"+f"(d[90]),"+f"(d[91]),"+f"(d[92]),"+f"(d[93]),"+f"(d[94]),"+f"(d[95]),"+f"(d[96]),"+f"(d[97]),"+f"(d[98]),"+f"(d[99]),"+f"(d[100]),"+f"(d[101]),"+f"(d[102]),"+f"(d[103]),"+f"(d[104]),"+f"(d[105]),"+f"(d[106]),"+f"(d[107]),"+f"(d[108]),"+f"(d[109]),"+f"(d[110]),"+f"(d[111]),"+f"(d[112]),"+f"(d[113]),"+f"(d[114]),"+f"(d[115]),"+f"(d[116]),"+f"(d[117]),"+f"(d[118]),"+f"(d[119]),"+f"(d[120]),"+f"(d[121]),"+f"(d[122]),"+f"(d[123]),"+f"(d[124]),"+f"(d[125]),"+f"(d[126]),"+f"(d[127])
    : "l"(da), "l"(db), "r"(sc));
}

__device__ __forceinline__ void wgmma_ss_n128_tb1(float (&d)[64], uint64_t da, uint64_t db, int sc) {
  asm volatile("{.reg .pred p; setp.ne.b32 p, %66, 0;\n"
    "wgmma.mma_async.sync.aligned.m64n128k16.f32.bf16.bf16 {%0,%1,%2,%3,%4,%5,%6,%7,%8,%9,%10,%11,%12,%13,%14,%15,%16,%17,%18,%19,%20,%21,%22,%23,%24,%25,%26,%27,%28,%29,%30,%31,%32,%33,%34,%35,%36,%37,%38,%39,%40,%41,%42,%43,%44,%45,%46,%47,%48,%49,%50,%51,%52,%53,%54,%55,%56,%57,%58,%59,%60,%61,%62,%63}, %64, %65, p, 1, 1, 0, 1;}\n"
    : "+f"(d[0]),"+f"(d[1]),"+f"(d[2]),"+f"(d[3]),"+f"(d[4]),"+f"(d[5]),"+f"(d[6]),"+f"(d[7]),"+f"(d[8]),"+f"(d[9]),"+f"(d[10]),"+f"(d[11]),"+f"(d[12]),"+f"(d[13]),"+f"(d[14]),"+f"(d[15]),"+f"(d[16]),"+f"(d[17]),"+f"(d[18]),"+f"(d[19]),"+f"(d[20]),"+f"(d[21]),"+f"(d[22]),"+f"(d[23]),"+f"(d[24]),"+f"(d[25]),"+f"(d[26]),"+f"(d[27]),"+f"(d[28]),"+f"(d[29]),"+f"(d[30]),"+f"(d[31]),"+f"(d[32]),"+f"(d[33]),"+f"(d[34]),"+f"(d[35]),"+f"(d[36]),"+f"(d[37]),"+f"(d[38]),"+f"(d[39]),"+f"(d[40]),"+f"(d[41]),"+f"(d[42]),"+f"(d[43]),"+f"(d[44]),"+f"(d[45]),"+f"(d[46]),"+f"(d[47]),"+f"(d[48]),"+f"(d[49]),"+f"(d[50]),"+f"(d[51]),"+f"(d[52]),"+f"(d[53]),"+f"(d[54]),"+f"(d[55]),"+f"(d[56]),"+f"(d[57]),"+f"(d[58]),"+f"(d[59]),"+f"(d[60]),"+f"(d[61]),"+f"(d[62]),"+f"(d[63])
    : "l"(da), "l"(db), "r"(sc));
}

template <int BN> struct WG;
template <> struct WG<256> { static __device__ __forceinline__ void mma(float (&d)[128], uint64_t a, uint64_t b, int sc) { wgmma_ss_n256_tb1(d, a, b, sc); } };
template <> struct WG<128> { static __device__ __forceinline__ void mma(float (&d)[64], uint64_t a, uint64_t b, int sc) { wgmma_ss_n128_tb1(d, a, b, sc); } };

struct GemmMaps { CUtensorMap a, b[3], c; };
template <int BN, int STAGES>
__global__ void __cluster_dims__(2, 1, 1) __launch_bounds__(384, 1)
gemm_kernel(const __grid_constant__ GemmMaps maps, int tilesM, int tilesN, int kblocks, int nPerB, int clearX) {
  extern __shared__ __align__(1024) uint8_t smem_raw[];
  constexpr int STAGE_BYTES = 16384 + BN * 128;
  constexpr int NBOX = BN / 64;
  const uint32_t sbase = (smem_u32(smem_raw) + 1023) & ~1023u;
  const uint32_t sEpi = sbase + STAGES * STAGE_BYTES;
  const uint32_t sBar = sEpi + 32768;
  const int warp = threadIdx.x >> 5, lane = threadIdx.x & 31, wg = warp >> 2;
  uint32_t crank; asm("mov.u32 %0, %%cluster_ctarank;" : "=r"(crank));
  if (threadIdx.x == 0) {
    for (int i = 0; i < STAGES; i++) { mbar_init(sBar + 8 * i, 1); mbar_init(sBar + 8 * (STAGES + i), 4); }
    asm volatile("fence.mbarrier_init.release.cluster;" ::: "memory");
  }
  asm volatile("barrier.cluster.arrive.release.aligned; barrier.cluster.wait.acquire.aligned;" ::: "memory");
  const int npairs = (tilesM >> 1) * tilesN, pair0 = blockIdx.x >> 1, pstep = gridDim.x >> 1;
  if (wg == 2) {
    asm volatile("setmaxnreg.dec.sync.aligned.u32 40;");
    if (warp > 8 && clearX) {
      asm volatile("griddepcontrol.wait;" ::: "memory");
      for (int i = blockIdx.x * 96 + threadIdx.x - 288; i < (int)(sizeof(g_xraw) / 16); i += gridDim.x * 96) g_xraw[i] = make_uint4(0, 0, 0, 0);
    }
    if (warp == 8 && lane == 0) {
      int st = 0, ph = 1;
      for (int p = pair0; p < npairs; p += pstep) {
        const int tm = (p % (tilesM >> 1)) * 2 + crank, tn = p / (tilesM >> 1);
        const CUtensorMap* mb = &maps.b[tn / nPerB];
        const int n0 = (tn % nPerB) * BN;
        auto load_b = [&](int kb, int st) {
          mbar_expect_tx(sBar + 8 * st, STAGE_BYTES);
#pragma unroll
          for (int i = 0; i < NBOX / 2; i++) {
            const int bx = crank * (NBOX / 2) + i;
            tma2d_mc(sbase + st * STAGE_BYTES + 16384 + bx * 8192, mb, n0 + bx * 64, kb * 64, sBar + 8 * st, (uint16_t)3);
          }
        };
        if (p == pair0) {
          for (int kb = 0; kb < STAGES; kb++) load_b(kb, kb);
          asm volatile("griddepcontrol.wait;" ::: "memory");
        }
        for (int kb = 0; kb < kblocks; kb++) {
          if (p > pair0 || kb >= STAGES) { mbar_wait(sBar + 8 * (STAGES + st), ph); load_b(kb, st); }
          tma2d(sbase + st * STAGE_BYTES, &maps.a, kb * 64, tm * 128, sBar + 8 * st);
          if (++st == STAGES) { st = 0; ph ^= 1; }
        }
      }
      for (int i = 0; i < STAGES; i++) { mbar_wait(sBar + 8 * (STAGES + st), ph); if (++st == STAGES) { st = 0; ph ^= 1; } }
    }
  } else {
    asm volatile("setmaxnreg.inc.sync.aligned.u32 232;");
    int st = 0, ph = 0;
    float acc[BN / 2];
    const uint64_t descA0 = (uint64_t)(((sbase + wg * 8192) & 0x3FFFF) >> 4) | (1ull << 16) | (64ull << 32) | (1ull << 62);
    const uint64_t descB0 = (uint64_t)(((sbase + 16384) & 0x3FFFF) >> 4) | (512ull << 16) | (64ull << 32) | (1ull << 62);
    const uint32_t epi = sEpi + wg * 16384;
    for (int p = pair0; p < npairs; p += pstep) {
      const int tm = (p % (tilesM >> 1)) * 2 + crank, tn = p / (tilesM >> 1);
      int prev = -1;
      for (int kb = 0; kb < kblocks; kb++) {
        mbar_wait(sBar + 8 * st, ph);
        wg_fence();
        const uint64_t so = (uint64_t)(st * (STAGE_BYTES >> 4));
#pragma unroll
        for (int k = 0; k < 4; k++) WG<BN>::mma(acc, descA0 + so + k * 2, descB0 + so + k * 128, kb | k);
        wg_commit();
        if (prev >= 0) {
          wg_wait<1>();
          if ((threadIdx.x & 127) < 2) mbar_arrive_cluster(sBar + 8 * (STAGES + prev), threadIdx.x & 1);
        }
        prev = st;
        if (++st == STAGES) { st = 0; ph ^= 1; }
      }
      wg_wait<0>();
      if ((threadIdx.x & 127) < 2) mbar_arrive_cluster(sBar + 8 * (STAGES + prev), threadIdx.x & 1);
#pragma unroll
      for (int r = 0; r < BN / 128; r++) {
        if ((threadIdx.x & 127) == 0) asm volatile("cp.async.bulk.wait_group.read 0;" ::: "memory");
        bar_sync(1 + wg, 128);
        const int row = (warp & 3) * 16 + (lane & 15);
#pragma unroll
        for (int i = 0; i < 8; i++) {
          const int c = 2 * (i & 3) + (lane >> 4);
          const float* q = &acc[r * 64 + i * 8];
          stsm4(epi + (i >> 2) * 8192 + row * 128 + ((c ^ (row & 7)) << 4), pack2(q[0], q[1]), pack2(q[2], q[3]), pack2(q[4], q[5]), pack2(q[6], q[7]));
        }
        fence_async();
        bar_sync(1 + wg, 128);
        if ((threadIdx.x & 127) == 0) {
          tma2d_store(&maps.c, epi, tn * BN + r * 128, tm * 128 + wg * 64);
          tma2d_store(&maps.c, epi + 8192, tn * BN + r * 128 + 64, tm * 128 + wg * 64);
          asm volatile("cp.async.bulk.commit_group;" ::: "memory");
        }
      }
    }
    if ((threadIdx.x & 127) == 0) asm volatile("cp.async.bulk.wait_group 0;" ::: "memory");
  }
}

struct Dft { uint32_t m[2][2][2][4]; };
template <bool P4> __device__ __forceinline__ int fidx(int tile, int x) { return P4 ? 4 * (x >> 1) + 2 * (tile & 1) + (x & 1) + 16 * (tile >> 1) : x + 8 * tile; }
__device__ __forceinline__ float2 cis(int k, int n) {
  k &= n - 1; if (2 * k > n) k -= n;
  const float a = (float)k * (6.283185307179586f / (float)n);
  return make_float2(__cosf(a), __sinf(a));
}
template <bool OUT4> __device__ __forceinline__ void make_dft(Dft& D, int g, int t) {
#pragma unroll
  for (int q = 0; q < 16; q++) {
    const int b = q >> 3, u = (q >> 2) & 1, r = (q >> 1) & 1, v = q & 1;
    const float2 w = cis(fidx<OUT4>(v, g) * fidx<false>(2 * u + r, 2 * t + b), 32);
    D.m[b][u][0][q & 3] = pack2(w.x, w.y); D.m[b][u][1][q & 3] = pack2(-w.y, w.x);
  }
}
__device__ __forceinline__ void mma_dc(float (&d)[4], uint32_t a0, uint32_t a1, uint32_t a2, uint32_t a3, uint32_t b0, uint32_t b1, const float (&c)[4]) {
  asm("mma.sync.aligned.m16n8k16.row.col.f32.bf16.bf16.f32 {%0,%1,%2,%3}, {%4,%5,%6,%7}, {%8,%9}, {%10,%11,%12,%13};"
    : "=f"(d[0]), "=f"(d[1]), "=f"(d[2]), "=f"(d[3]) : "r"(a0), "r"(a1), "r"(a2), "r"(a3), "r"(b0), "r"(b1), "f"(c[0]), "f"(c[1]), "f"(c[2]), "f"(c[3])); }
__device__ __forceinline__ void dft_b(const Dft& D, const uint32_t (&x)[2][4], float (&o)[2][8]) {
#pragma unroll
  for (int ri = 0; ri < 2; ri++) {
    float z[4] = {0.f, 0.f, 0.f, 0.f}, e[4], p[4];
    mma_dc(e, D.m[0][0][ri][0], D.m[0][0][ri][1], D.m[0][0][ri][2], D.m[0][0][ri][3], x[0][0], x[0][1], z);
    mma_dc(e, D.m[0][1][ri][0], D.m[0][1][ri][1], D.m[0][1][ri][2], D.m[0][1][ri][3], x[0][2], x[0][3], e);
    mma_dc(p, D.m[1][0][ri][0], D.m[1][0][ri][1], D.m[1][0][ri][2], D.m[1][0][ri][3], x[1][0], x[1][1], e);
    mma_dc(p, D.m[1][1][ri][0], D.m[1][1][ri][1], D.m[1][1][ri][2], D.m[1][1][ri][3], x[1][2], x[1][3], p);
#pragma unroll
    for (int q = 0; q < 4; q++) { o[ri][q] = p[q]; o[ri][4 + q] = fmaf(2.f, e[q], -p[q]); }
  }
}
__device__ __forceinline__ void dft_a(const uint32_t (&m)[2][2][4], const uint32_t (&x0)[2][4], const uint32_t (&x1)[2][4], float (&o)[2][8]) {
#pragma unroll
  for (int ri = 0; ri < 2; ri++) {
    float z[4] = {0.f, 0.f, 0.f, 0.f}, e[4], p[4];
    mma_dc(e, x0[0][0], x1[0][0], x0[0][1], x1[0][1], m[0][ri][0], m[0][ri][1], z);
    mma_dc(e, x0[0][2], x1[0][2], x0[0][3], x1[0][3], m[0][ri][2], m[0][ri][3], e);
    mma_dc(p, x0[1][0], x1[1][0], x0[1][1], x1[1][1], m[1][ri][0], m[1][ri][1], e);
    mma_dc(p, x0[1][2], x1[1][2], x0[1][3], x1[1][3], m[1][ri][2], m[1][ri][3], p);
#pragma unroll
    for (int q = 0; q < 4; q++) { o[ri][q] = p[q]; o[ri][4 + q] = fmaf(2.f, e[q], -p[q]); }
  }
}
__device__ __forceinline__ uint32_t twid(float re, float im, float c, float s) { return pack2(fmaf(re, c, im * s), fmaf(im, c, -re * s)); }
__device__ __forceinline__ void cpa16(uint32_t d, const void* s) { asm volatile("cp.async.cg.shared.global [%0], [%1], 16;" :: "r"(d), "l"(s) : "memory"); }
__device__ __forceinline__ void sts32(uint32_t a, uint32_t x) { asm volatile("st.shared.u32 [%0], %1;" :: "r"(a), "r"(x) : "memory"); }
__device__ __forceinline__ void cpa_commit() { asm volatile("cp.async.commit_group;" ::: "memory"); }
template <int N> __device__ __forceinline__ void cpa_wait() { asm volatile("cp.async.wait_group %0;" :: "n"(N) : "memory"); }
__device__ __forceinline__ uint32_t lds32(uint32_t a) { uint32_t r; asm volatile("ld.shared.u32 %0, [%1];" : "=r"(r) : "r"(a) : "memory"); return r; }
#define FMID 0
constexpr int F_TP = 4112, F_TSZ = 8 * F_TP;

__device__ __forceinline__ uint32_t ldnc32(const void* p) { uint32_t v; asm volatile("ld.global.nc.b32 %0, [%1];" : "=r"(v) : "l"(p) : "memory"); return v; }
template <class F>
__device__ __forceinline__ void fft_wprep(const bf16* __restrict__ wr, const bf16* __restrict__ wi, int cta, F&& mid) {
  const int tid = threadIdx.x, g = (cta >> 1) & 7, c = (cta >> 4) & 3, t = 2 * (cta & 1) + (tid & 1);
  const int k0 = g + 8 * (cta >> 6) + 32 * (8 * c + 2 * t), l0 = (tid & ~1) + (g & 1);
  uint32_t a[4][4], b[4][4];
#pragma unroll
  for (int q = 0; q < 16; q++) {
    const int o = (k0 + 16 * (q >> 3) + 32 * ((q >> 1) & 1) + 1024 * (q & 1)) * 513 + l0 + 256 * ((q >> 2) & 1);
    a[q >> 2][q & 3] = ldnc32(wr + o);
    b[q >> 2][q & 3] = ldnc32(wi + o);
  }
  const int e = cta * 32 + (tid & 31), lh = (e >> 11) * 512, k = e & 2047, k2 = (k >> 5) & 31;
  uint32_t hz[4];
#pragma unroll
  for (int q = 0; q < 4; q++) asm volatile("ld.global.nc.u16 %0, [%1];" : "=r"(hz[q]) : "l"((q < 2 ? wr : wi) + (q & 1 ? (2048 - k) & 2047 : k) * 513 + lh) : "memory");
  mid();
  uint4* dst = g_wt + l0 * 512 + cta * 2 + (tid & 1);
#pragma unroll
  for (int q = 0; q < 8; q++) {
    const int hf = q >> 1, l = l0 + 256 * (hf & 1) + (q & 1);
    const uint32_t sel = (q & 1) ? 0x7632 : 0x5410;
    if (l & 511) dst[(256 * (hf & 1) + (q & 1)) * 512 + 256 * (q >> 2)] = make_uint4(__byte_perm(a[hf][0], b[hf][0], sel), __byte_perm(a[hf][1], b[hf][1], sel),
                                                                                   __byte_perm(a[hf][2], b[hf][2], sel), __byte_perm(a[hf][3], b[hf][3], sel));
  }
  if (tid < 32) reinterpret_cast<uint32_t*>(g_wt)[(64 * ((k >> 3) & 3) + 16 * (k2 >> 3) + 2 * (k & 7) + ((k2 >> 2) & 1)) * 8 + lh * 2048 + 2 * (k2 & 3) + (k >> 10)] =
      pack2(0.5f * (__uint_as_float(hz[0] << 16) + __uint_as_float(hz[1] << 16)), 0.5f * (__uint_as_float(hz[2] << 16) - __uint_as_float(hz[3] << 16)));
}

template <class F>
__device__ __forceinline__ void fft_rows_fwd(const bf16* __restrict__ x, const bf16* __restrict__ wr, const bf16* __restrict__ wi, uint32_t tb, int it, F&& mid) {
  const int warp = threadIdx.x >> 5, lane = threadIdx.x & 31, g = lane >> 2, t = lane & 3;
  const uint32_t in = tb + warp * 4096;
  const uint32_t f0 = in + (lane >> 3) * 256 + (((lane & 7) ^ (2 * (lane >> 3))) << 4);
  const bf16* src = x + ((256 * (warp & 3) + 64 * (warp >> 2) + 128 * (it & 1) + 32 * ((it >> 4) & 1) + 8 * (it >> 5) + ((it >> 1) & 7)) * 2048 + lane * 8);
#pragma unroll
  for (int q = 0; q < 8; q++) cpa16((f0 ^ ((q >> 2) * 144)) + (q & 3) * 1024, src + q * 256);
  cpa_commit();
  Dft D;
  float2 tw[4][8];
  fft_wprep(wr, wi, it, [&]() {
    if (FMID == 0) mid();
    make_dft<true>(D, g, t);
#pragma unroll
    for (int q = 0; q < 32; q++) {
      tw[q >> 3][q & 7] = cis(fidx<true>((q >> 1) & 3, g) * fidx<false>(q >> 3, 2 * t + (q & 1)), 1024);
      if (FMID) asm volatile("" : "+f"(tw[q >> 3][q & 7].x), "+f"(tw[q >> 3][q & 7].y) :: "memory");
    }
    if (FMID == 1) mid();
  });
  if (FMID == 2) mid();
  cpa_wait<0>(); __syncwarp();
  uint32_t a[4][2][4], y[4][2][4];
#pragma unroll
  for (int q = 0; q < 8; q++) ldsm4t(a[q & 3][q >> 2], (in + lane * 128 + ((lane & 7) << 4)) ^ (q << 4));
  float o[2][8];
#pragma unroll
  for (int i = 0; i < 4; i++) {
    dft_b(D, a[i], o);
#pragma unroll
    for (int q = 0; q < 8; q++) y[q >> 1][q & 1][i] = twid(o[0][q], o[1][q], tw[i][q].x, tw[i][q].y);
  }
  __syncthreads();
  const uint32_t w0 = tb + warp * F_TP + fidx<true>(0, g) * 128 + t * 16 + ((g & 1) << 6), wz = (g & 1) ? -64 : 64;
#pragma unroll
  for (int z = 0; z < 2; z++) {
    float o2[2][8];
    dft_b(D, y[2 * z], o); dft_b(D, y[2 * z + 1], o2);
#pragma unroll
    for (int i = 0; i < 4; i++) {
      const float sg = i < 2 ? 1.f : -1.f;
      sts128(w0 + z * wz + fidx<true>(i, 0) * 128, pack2(o[0][2 * i], sg * o[1][2 * i]), pack2(o[0][2 * i + 1], sg * o[1][2 * i + 1]),
             pack2(o2[0][2 * i], sg * o2[1][2 * i]), pack2(o2[0][2 * i + 1], sg * o2[1][2 * i + 1]));
    }
  }
  __syncthreads();
  const uint32_t ra = tb + (lane & 1) * 4 * F_TP + ((lane >> 1) + 16 * (warp ^ ((warp >> 1) & 1))) * 4;
  uint4* dst = g_y + (threadIdx.x >> 1) * 256 + (lane & 1) + it * 2;
#pragma unroll
  for (int q = 0; q < 8; q++) { const uint32_t r = ra + q * 512; dst[q * 32768] = make_uint4(lds32(r), lds32(r + F_TP), lds32(r + 2 * F_TP), lds32(r + 3 * F_TP)); }
}

__device__ __forceinline__ void fft_cols(uint32_t sb, int cta, int ncta) {
  const int warp = threadIdx.x >> 5, lane = threadIdx.x & 31, g = lane >> 2, t = lane & 3;
  const uint32_t in = sb + warp * 16384 + lane * 16, tab = sb + 131072 + lane * 16;
  auto fetch_y = [&](int l) {
#pragma unroll
    for (int q = 0; q < 16; q++) cpa16(in + q * 512, g_y + (q < 8 ? l : (1024 - l) & 1023) * 256 + (q & 7) * 32 + lane);
  };
  auto fetch_w = [&](int l) {
#pragma unroll
    for (int q = 0; q < 16; q++) cpa16(in + 8192 + q * 512, g_wt + l * 512 + q * 32 + lane);
  };
  const int l0 = cta * 8 + warp, dl = ncta * 8;
  if (l0 <= 512) fetch_y(l0);
  cpa_commit();
  if (l0 <= 512) fetch_w(l0);
  cpa_commit();
  Dft D; make_dft<false>(D, g, t);
#pragma unroll
  for (int q = 2 * warp; q < 2 * warp + 2; q++) {
    const int r = fidx<false>(q & 3, g), c = fidx<false>(q >> 2, 2 * t);
    const float2 w0 = cis(r * c, 1024), w1 = cis(r * c + r, 1024), p0 = cis(r + 32 * c, 2048), p1 = cis(r + 32 * c + 32, 2048);
    sts128(tab + q * 512, __float_as_uint(w0.x), __float_as_uint(w0.y), __float_as_uint(w1.x), __float_as_uint(w1.y));
    sts128(tab + 8192 + q * 512, __float_as_uint(p0.x), __float_as_uint(p0.y), __float_as_uint(p1.x), __float_as_uint(p1.y));
  }
  if (warp == 0) {
#pragma unroll
    for (int q = 0; q < 8; q++) {
      const int v = q >> 2, b = (q >> 1) & 1, ri = q & 1;
      sts128(tab + 16384 + q * 512, D.m[b][0][ri][v], D.m[b][0][ri][v + 2], D.m[b][1][ri][v], D.m[b][1][ri][v + 2]);
    }
  }
  __syncthreads();
#pragma unroll 1
  for (int l = l0; l <= 512; l += dl) {
    uint32_t a[2][4][2][4], y[2][4][2][4];
    float o[2][2][8];
    cpa_wait<1>();
#pragma unroll
    for (int q = 0; q < 16; q++) lds128(a[q >> 3][(q >> 1) & 3][q & 1], in + q * 512);
    if (!(l & 511)) {
      const uint32_t m0 = l ? 0x80000000u : 0u;
#pragma unroll
      for (int q = 0; q < 32; q++) { a[0][q >> 3][(q >> 2) & 1][q & 3] ^= m0; a[1][q >> 3][(q >> 2) & 1][q & 3] ^= m0 ^ 0x80000000u; }
    }
    auto first = [&]() {
#pragma unroll
      for (int i = 0; i < 4; i++) {
        dft_b(D, a[0][i], o[0]); dft_b(D, a[1][i], o[1]);
#pragma unroll
        for (int r = 0; r < 4; r++) {
          const float4 w = lds128f(tab + (4 * i + r) * 512);
#pragma unroll
          for (int s = 0; s < 2; s++) {
            y[s][r][0][i] = twid(o[s][0][2 * r], o[s][1][2 * r], w.x, w.y);
            y[s][r][1][i] = twid(o[s][0][2 * r + 1], o[s][1][2 * r + 1], w.z, w.w);
          }
        }
      }
    };
    first();
    if (l + dl <= 512) fetch_y(l + dl);
    cpa_commit();
    cpa_wait<1>();
#pragma unroll
    for (int zv = 0; zv < 4; zv++) {
      const int z = zv >> 1, v = zv & 1;
      uint32_t m[2][2][4];
#pragma unroll
      for (int q = 0; q < 4; q++) lds128(m[q >> 1][q & 1], tab + 16384 + (4 * v + q) * 512);
      dft_a(m, y[0][2 * z], y[0][2 * z + 1], o[0]); dft_a(m, y[1][2 * z], y[1][2 * z + 1], o[1]);
#pragma unroll
      for (int q = 0; q < 4; q++) {
        const int i = 2 * z + (q & 1), c = v + (q & 2);
        uint32_t w[4]; lds128(w, in + 8192 + (4 * i + c) * 512);
        const float4 ph = lds128f(tab + 8192 + (4 * c + i) * 512);
#pragma unroll
        for (int b = 0; b < 2; b++) {
          const float cs = b ? ph.z : ph.x, sn = b ? ph.w : ph.y;
          const float r1 = __uint_as_float(w[2 * b] << 16), i1 = __uint_as_float(w[2 * b] & 0xFFFF0000u);
          const float r2 = __uint_as_float(w[2 * b + 1] << 16), i2 = __uint_as_float(w[2 * b + 1] & 0xFFFF0000u);
          const float Sr = r1 + r2, Si = i1 + i2, Dr = r1 - r2, Di = i1 - i2;
          const float ar = fmaf(-Dr, sn, Sr), ai = fmaf(-Di, sn, Si), dr = fmaf(Dr, sn, Sr), di = fmaf(Di, sn, Si), br = -Di * cs, bi = Dr * cs;
          const float Ar = o[0][0][2 * q + b], Ai = o[0][1][2 * q + b], Br = o[1][0][2 * q + b], Bi = o[1][1][2 * q + b];
          a[0][i][b][c] = pack2(fmaf(ar, Ai, fmaf(ai, Ar, fmaf(br, Bi, bi * Br))), fmaf(ar, Ar, fmaf(-ai, Ai, fmaf(br, Br, -bi * Bi))));
          a[1][i][b][c] = pack2(fmaf(dr, Bi, fmaf(di, Br, fmaf(-br, Ai, -bi * Ar))), fmaf(dr, Br, fmaf(-di, Bi, fmaf(-br, Ar, bi * Ai))));
        }
      }
    }
    if (l + dl <= 512) fetch_w(l + dl);
    cpa_commit();
    first();
#pragma unroll
    for (int s = 0; s < 2; s++) {
      uint4* dst = g_y + (s ? (1024 - l) & 1023 : l) * 256 + lane;
      const float sg = s ? -1.f : 1.f;
#pragma unroll
      for (int i = 0; i < 4; i++) {
        dft_b(D, y[s][i], o[0]);
#pragma unroll
        for (int b = 0; b < 2; b++)
          dst[(2 * i + b) * 32] = make_uint4(pack2(sg * o[0][0][b], o[0][1][b]), pack2(sg * o[0][0][2 + b], o[0][1][2 + b]),
                                             pack2(sg * o[0][0][4 + b], o[0][1][4 + b]), pack2(sg * o[0][0][6 + b], o[0][1][6 + b]));
      }
    }
  }
}

__device__ __forceinline__ void fft_rows_inv(const CUtensorMap* om, uint32_t sb, int cta, int ncta) {
  const int warp = threadIdx.x >> 5, lane = threadIdx.x & 31, g = lane >> 2, t = lane & 3, wg = warp >> 2, w4 = warp & 3;
  const uint32_t tb = sb + 32768 + wg * 2 * F_TSZ;
  const uint4* src = g_y + pin((256 * ((lane >> 1) & 3) + 64 * (lane >> 3) + 8 * w4) * 256 + (lane & 1));
  const uint32_t wa = pin(tb + (lane & 1) * 4 * F_TP + w4 * 1024 + (lane >> 1) * 4);
  uint4 pf[8];
  auto fetch = [&](int it, int hf) {
#pragma unroll
    for (int q = 0; q < 8; q++) pf[q] = __ldcg(src + (it * 2 + hf * 8192) + q * 256);
  };
  auto put = [&](uint32_t off) {
#pragma unroll
    for (int q = 0; q < 8; q++) {
      sts32(wa + off + q * 64, pf[q].x); sts32(wa + off + q * 64 + F_TP, pf[q].y);
      sts32(wa + off + q * 64 + 2 * F_TP, pf[q].z); sts32(wa + off + q * 64 + 3 * F_TP, pf[q].w);
    }
  };
  const int it0 = 2 * cta + wg;
  if (it0 >= 128) return;
  fetch(it0, 0); put(0); fetch(it0, 1); put(512);
  Dft D; make_dft<false>(D, g, t);
  float2 tw[4][8];
#pragma unroll
  for (int q = 0; q < 32; q++) {
    tw[q >> 3][q & 7] = cis(fidx<false>((q >> 1) & 3, g) * fidx<false>(q >> 3, 2 * t + (q & 1)), 1024);
    tw[q >> 3][q & 7].x *= 1.f / 2097152.f; tw[q >> 3][q & 7].y *= 1.f / 2097152.f;
  }
  const uint32_t la = pin(tb + w4 * F_TP + lane * 16), ob = uni(sb + warp * 4096);
  const uint32_t oa = pin(ob + (lane >> 1) * 128 + (((4 * (lane & 1)) ^ ((lane >> 1) & 7)) << 4));
#pragma unroll 1
  for (int n = 0;; n++) {
    const int it = it0 + (n >> 1) * 2 * ncta, hf = n & 1, buf = (n >> 1) & 1;
    if (it >= 128) break;
    if (!hf) bar_sync(1 + wg, 128);
    uint32_t a[4][2][4], y[4][2][4];
#pragma unroll
    for (int q = 0; q < 8; q++) lds128(a[q >> 1][q & 1], la + buf * F_TSZ + hf * 4 * F_TP + q * 512);
    fetch(min(it + 2 * ncta, 127), hf);
    float o[2][8];
#pragma unroll
    for (int i = 0; i < 4; i++) {
      dft_b(D, a[i], o);
#pragma unroll
      for (int q = 0; q < 8; q++) y[q >> 1][q & 1][i] = twid(o[0][q], o[1][q], tw[i][q].x, tw[i][q].y);
    }
    if (lane == 0) asm volatile("cp.async.bulk.wait_group.read 0;" ::: "memory");
    __syncwarp();
#pragma unroll
    for (int c = 0; c < 4; c++) {
      dft_b(D, y[c], o);
#pragma unroll
      for (int ri = 0; ri < 2; ri++)
        stsm4((oa ^ (c << 4)) + (1 - ri) * 2048, pack2(o[ri][0], o[ri][1]), pack2(o[ri][2], o[ri][3]), pack2(o[ri][4], o[ri][5]), pack2(o[ri][6], o[ri][7]));
    }
    fence_async();
    __syncwarp();
    if (lane == 0) {
      const int m = 256 * w4 + 32 * ((it >> 1) & 7) + 8 * (it >> 5) + 4 * (it & 1) + 2 * hf + ((it >> 4) & 1);
      asm volatile("cp.async.bulk.tensor.3d.global.shared::cta.bulk_group [%0, {0, 0, %2}], [%1];" :: "l"(om), "r"(ob), "r"(2 * m) : "memory");
      asm volatile("cp.async.bulk.commit_group;" ::: "memory");
    }
    put((buf ^ 1) * F_TSZ + hf * 512);
  }
  if (lane == 0) asm volatile("cp.async.bulk.wait_group 0;" ::: "memory");
}
__device__ __forceinline__ void grid_arrive(unsigned* ctr) {
  __syncthreads();
  if (threadIdx.x == 0) { __threadfence(); atomicAdd(ctr, 1u); }
}
__device__ __forceinline__ void grid_wait(unsigned* ctr, unsigned n) {
  if (threadIdx.x == 0) {
    int it = 0;
    while (*reinterpret_cast<volatile unsigned*>(ctr) < n) { __nanosleep(200); if (++it > SPIN_LIMIT) { g_err = 3; break; } }
    __threadfence();
  }
  __syncthreads();
}

struct RecMaps { CUtensorMap wq, wk, wv, wo, x, k, q, v, fo; };
#define NSW 16
#define EXP 0
#define NPB 2
#define NPC 4
#define PDL 1
#define WPF 0
#define WOP 2
#define HOME 3
#define DL0 14
#define PD1 4
#define NE4 6
#define NE6 0
#define NA4 14
#define NA6 18
#define NB1 24
#define TQL 7
#define NQ 8
#define TQP (NQ - 1)
#define OXPOS 4
#define KVPOS 2
#define NK0 0
#define FLPOS 1
#define XWPOS 10
#define FSPOS 28
#define RL0 4
#define RLS 6
#define RLB 4
#define VL0 3
#define RI 9
#define RJ 8
#define NPRE 20
#define PFD 4
#define PD0 4
#define VB NV0
#define NPA 0
#define N1 16
#define DL1 16
#define PACE 0
#define RE0 0
#define RE1 0
#define RP1 23
#define UNP 1
#define X2 2
#define X3 2
#define SPOS 2
#ifndef NV0
#define NV0 4
#endif
#define TGP 3
#define FENP 0
#define LW0 8
#define X1 4
#define X0 4
constexpr int R_WO = 0, R_X = 65536, R_MEM = 131072, R_WC = 147456, R_RED = R_WC + NSW * 2048, R_O = R_RED, R_S = R_O + 2048, R_P = R_S + 3072, R_STAGE = R_P + 2048,
              R_K = R_STAGE + 8192, R_Q = R_K + 8192, R_V = R_Q + 2048, R_ID = R_V + 16384, R_T = R_ID + 512, R_DST = R_T + 512, R_RD = R_DST + 2048, R_BAR = R_RD + 2048, R_TS = R_BAR + 128,
              R_TOTAL = R_TS;
#define TS(i)
#define LOG(i, v)
constexpr int B_KV = R_BAR, B_W = R_BAR + 8, B_X = R_BAR + 80, B_PK = R_BAR + 24, B_C = R_BAR + 32, B_B = R_BAR + 40, B_DUE = R_BAR + 48, B_ONE = R_BAR + 64;
#define DLY_A 150
#define DLY_V 150
#define DLY_C 200
#define DLY_L 90
#define NS_B 1088
#define NS_C 1728
#define NS_P 2688
#define NS_V 128
#define NS_F 896
#define NS_K 128
#define NS_M 32
#define NS_X 128
#define NS_PEN 1024
__device__ __forceinline__ float rcp(float x) { float r; asm("rcp.approx.ftz.f32 %0, %1;" : "=f"(r) : "f"(x)); return r; }
__device__ __forceinline__ uint32_t movm(uint32_t a) { uint32_t d; asm volatile("movmatrix.sync.aligned.m8n8.trans.b16 %0, %1;" : "=r"(d) : "r"(a)); return d; }
__device__ __forceinline__ uint32_t hadd2(uint32_t a, uint32_t b) { uint32_t d; asm("add.rn.bf16x2 %0, %1, %2;" : "=r"(d) : "r"(a), "r"(b)); return d; }
__device__ __forceinline__ void mma_a(float (&d)[4], const uint32_t (&a)[4], uint32_t b0, uint32_t b1) { mma16816(d, a[0], a[1], a[2], a[3], b0, b1); }
__device__ __forceinline__ bool elect() {
  uint32_t p; asm volatile("{.reg .pred p; elect.sync _|p, 0xffffffff; selp.u32 %0, 1, 0, p;}" : "=r"(p)); return p; }
__device__ __forceinline__ void tma3d(uint32_t dst, const CUtensorMap* m, int c1, int c2, uint32_t bar) {
  asm volatile("cp.async.bulk.tensor.3d.shared::cluster.global.mbarrier::complete_tx::bytes [%0], [%1, {0, %3, %4}], [%2];"
    :: "r"(dst), "l"(m), "r"(bar), "r"(c1), "r"(c2) : "memory"); }
__device__ __forceinline__ void tma4d(uint32_t dst, const CUtensorMap* m, int c1, int c2, uint32_t bar) {
  asm volatile("cp.async.bulk.tensor.4d.shared::cluster.global.mbarrier::complete_tx::bytes [%0], [%1, {0, %3, %4, 0}], [%2];"
    :: "r"(dst), "l"(m), "r"(bar), "r"(c1), "r"(c2) : "memory"); }
template <int OFF, int ACC>
__device__ __forceinline__ void wg_rs32(float (&d)[16], const uint32_t (&a)[4], uint32_t db) {
  if (ACC)
    asm volatile("{.reg .b64 db; .reg .b32 lo; add.u32 lo, %20, %21; mov.b64 db, {lo, 0x40000040};\n"
      "wgmma.mma_async.sync.aligned.m64n32k16.f32.bf16.bf16 {%0,%1,%2,%3,%4,%5,%6,%7,%8,%9,%10,%11,%12,%13,%14,%15}, {%16,%17,%18,%19}, db, 1, 1, 1, 0;}"
      : "+f"(d[0]), "+f"(d[1]), "+f"(d[2]), "+f"(d[3]), "+f"(d[4]), "+f"(d[5]), "+f"(d[6]), "+f"(d[7]), "+f"(d[8]), "+f"(d[9]), "+f"(d[10]), "+f"(d[11]), "+f"(d[12]), "+f"(d[13]), "+f"(d[14]), "+f"(d[15])
      : "r"(a[0]), "r"(a[1]), "r"(a[2]), "r"(a[3]), "r"(db), "n"(OFF));
  else
    asm volatile("{.reg .b64 db; .reg .b32 lo; add.u32 lo, %20, %21; mov.b64 db, {lo, 0x40000040};\n"
      "wgmma.mma_async.sync.aligned.m64n32k16.f32.bf16.bf16 {%0,%1,%2,%3,%4,%5,%6,%7,%8,%9,%10,%11,%12,%13,%14,%15}, {%16,%17,%18,%19}, db, 0, 1, 1, 0;}"
      : "=f"(d[0]), "=f"(d[1]), "=f"(d[2]), "=f"(d[3]), "=f"(d[4]), "=f"(d[5]), "=f"(d[6]), "=f"(d[7]), "=f"(d[8]), "=f"(d[9]), "=f"(d[10]), "=f"(d[11]), "=f"(d[12]), "=f"(d[13]), "=f"(d[14]), "=f"(d[15])
      : "r"(a[0]), "r"(a[1]), "r"(a[2]), "r"(a[3]), "r"(db), "n"(OFF));
}
template <int I> using IC = std::integral_constant<int, I>;
template <int I, int N, class F> __device__ __forceinline__ void sfor(F&& f) {
  if constexpr (I < N) { f(std::integral_constant<int, I>{}); sfor<I + 1, N>(f); }
}
__device__ __forceinline__ void keep(float (&d)[16]) {
  asm volatile("" : "+f"(d[0]), "+f"(d[1]), "+f"(d[2]), "+f"(d[3]), "+f"(d[4]), "+f"(d[5]), "+f"(d[6]), "+f"(d[7]),
      "+f"(d[8]), "+f"(d[9]), "+f"(d[10]), "+f"(d[11]), "+f"(d[12]), "+f"(d[13]), "+f"(d[14]), "+f"(d[15]) :: "memory");
}

template <int N, int S2 = 1024> __device__ __forceinline__ void ldx(uint32_t (&v)[N][4], const uint8_t* p) {
#pragma unroll
  for (int k = 0; k < 2 * N; k++) {
    const int i = k;
    asm volatile("ld.relaxed.gpu.global.v2.b32 {%0,%1}, [%2];" : "=r"(v[i >> 1][2 * (i & 1)]), "=r"(v[i >> 1][2 * (i & 1) + 1]) : "l"(p + (i & 3) * 256 + (i >> 2) * S2) : "memory");
  }
}
__device__ __forceinline__ uint32_t dif2(uint32_t a, uint32_t b, uint32_t tag) { uint32_t r; asm("lop3.b32 %0, %1, %2, %3, 0x7e;" : "=r"(r) : "r"(a), "r"(b), "r"(tag)); return r; }
__device__ __forceinline__ uint32_t dif2v(uint32_t a, uint32_t b, uint32_t tag) { uint32_t r; asm volatile("lop3.b32 %0, %1, %2, %3, 0x7e;" : "=r"(r) : "r"(a), "r"(b), "r"(tag)); return r; }
__device__ __forceinline__ uint32_t or3(uint32_t a, uint32_t b, uint32_t c) { uint32_t r; asm("lop3.b32 %0, %1, %2, %3, 0xfe;" : "=r"(r) : "r"(a), "r"(b), "r"(c)); return r; }
__device__ __forceinline__ uint32_t after(uint32_t x, float f, uint32_t z) { uint32_t r; asm("lop3.b32 %0, %1, %2, %3, 0xea;" : "=r"(r) : "r"(__float_as_uint(f)), "r"(z), "r"(x)); return r; }
__device__ __forceinline__ bool any_bit(uint32_t a, uint32_t b, uint32_t m) {
  uint32_t r; asm("lop3.b32 %0, %1, %2, %3, 0xa8;" : "=r"(r) : "r"(a), "r"(b), "r"(m)); return __any_sync(0xffffffffu, r); }
template <int W, int N> __device__ __forceinline__ bool stale(const uint32_t (&v)[N][4], uint32_t tag) {
  uint32_t x = dif2(v[0][0], v[0][2], tag);
  if (N == 4) x = or3(x, dif2(v[1][0], v[1][2], tag), dif2(v[2 % N][0], v[2 % N][2], tag));
  return any_bit(x, dif2(v[N - 1][0], v[N - 1][2], tag), 1);
}
template <int W, int N, int S2 = 1024> __device__ __forceinline__ void retry(uint32_t (&v)[N][4], const uint8_t* p, uint32_t tag, int& it) {
#pragma unroll 1
  do { ldx<N, S2>(v, p); it += INC_A; } while (stale<W>(v, tag) && it < SPIN_LIMIT);
}
__device__ __forceinline__ void mma_h(float (&d)[4], const uint32_t (&a)[4], const uint32_t (&b)[4], int hf) { mma16816(d, a[0], a[1], a[2], a[3], b[2 * hf], b[2 * hf + 1]); }
__device__ __forceinline__ void sts128(uint32_t a, const uint32_t (&r)[4]) { sts128(a, r[0], r[1], r[2], r[3]); }
__device__ __forceinline__ void sts128f(uint32_t a, const float* r) { sts128(a, __float_as_uint(r[0]), __float_as_uint(r[1]), __float_as_uint(r[2]), __float_as_uint(r[3])); }
__device__ __forceinline__ void mbar_spin(uint32_t bar, uint32_t par, int& it) {
  asm volatile("{.reg .pred p; .reg .b32 par; mov.b32 par, %2;\nLOOP: mbarrier.try_wait.parity.shared::cta.b64 p, [%1], par; @p bra.uni DONE;\n"
               "add.s32 %0, %0, 1; setp.le.s32 p, %0, %3; @p bra.uni LOOP;\nDONE: }" : "+r"(it) : "r"(bar), "r"(par), "n"(SPIN_LIMIT) : "memory"); }
__device__ __forceinline__ void warp_arrive(uint32_t bar) {
  __syncwarp(); asm volatile("{.reg .pred p; elect.sync _|p, 0xffffffff; @p mbarrier.arrive.shared::cta.b64 _, [%0];}" :: "r"(bar) : "memory"); }
__device__ __forceinline__ void delay_until(unsigned t) {
  asm volatile("{.reg .pred p; .reg .b64 c; .reg .b32 lo, hi;\nLOOP: mov.u64 c, %%clock64; mov.b64 {lo, hi}, c; sub.s32 lo, lo, %0; setp.lt.s32 p, lo, 0; @p bra.uni LOOP;}" :: "r"(t) : "memory"); }
__device__ __forceinline__ void cut(int it) { asm volatile("{.reg .pred p; setp.lt.s32 p, %0, 0;\nL: @p st.volatile.shared.u32 [%0], %0; @p bra.uni L;}" :: "r"(it) : "memory"); }
__device__ __forceinline__ void zero(float (&c)[4][4]) {
#pragma unroll
  for (int i = 0; i < 4; i++) c[i][0] = c[i][1] = c[i][2] = c[i][3] = 0.f;
}

__device__ __forceinline__ void sched() { asm volatile("griddepcontrol.launch_dependents;" ::: "memory"); }
__device__ __forceinline__ const uint8_t* pinp(const uint8_t* p) { return reinterpret_cast<const uint8_t*>(__shfl_xor_sync(0xffffffffu, reinterpret_cast<unsigned long long>(p), 0)); }
__device__ __forceinline__ uint32_t bar_or(int id, uint32_t x) {
  uint32_t r; asm volatile("{.reg .pred p, q; setp.ne.u32 p, %2, 0; bar.red.or.pred q, %1, 256, p; selp.u32 %0, 1, 0, q;}" : "=r"(r) : "r"(id), "r"(x) : "memory"); return r; }
__device__ __forceinline__ void bar_sync_unless(int id, uint32_t x) { asm volatile("{.reg .pred p; setp.eq.u32 p, %1, 0; @p bar.sync %0, 256;}" :: "r"(id), "r"((uint32_t)x) : "memory"); }
__device__ __forceinline__ void bar_arrive_unless(int id, uint32_t x) { asm volatile("{.reg .pred p; setp.eq.u32 p, %1, 0; @p bar.arrive %0, 256;}" :: "r"(id), "r"((uint32_t)x) : "memory"); }
__device__ __forceinline__ void stsm2t(uint32_t a, uint32_t r0, uint32_t r1, uint32_t x) {
  asm volatile("{.reg .pred p; setp.eq.u32 p, %3, 0; @p stmatrix.sync.aligned.m8n8.x2.trans.shared.b16 [%0], {%1,%2};}" :: "r"(a), "r"(r0), "r"(r1), "r"((uint32_t)x) : "memory"); }
__device__ __forceinline__ uint32_t or_and(uint32_t a, uint32_t b, uint32_t m) { uint32_t r; asm("lop3.b32 %0, %1, %2, %3, 0xa8;" : "=r"(r) : "r"(a), "r"(b), "r"(m)); return r; }
#define rare(x) __builtin_expect(!!(x), 0)
__device__ __forceinline__ uint32_t gtime() { unsigned long long g; asm volatile("mov.u64 %0, %%globaltimer;" : "=l"(g) :: "memory"); return (uint32_t)g; }
__device__ __forceinline__ void wait_time(uint32_t t) {
  asm volatile("{.reg .pred p; .reg .b32 g; .reg .b64 c;\nLOOP: mov.u64 c, %%globaltimer; cvt.u32.u64 g, c; sub.s32 g, %0, g; setp.lt.u32 p, g, 16384; @p bra.uni LOOP;}" :: "r"(t - 1) : "memory"); }
__device__ __forceinline__ uint32_t ldx32(const void* p) { uint32_t v; asm volatile("ld.relaxed.gpu.global.b32 %0, [%1];" : "=r"(v) : "l"(p) : "memory"); return v; }
__device__ __forceinline__ void stx32(const void* p, uint32_t v) { asm volatile("st.relaxed.gpu.global.b32 [%0], %1;" :: "l"(p), "r"(v) : "memory"); }

__global__ void __launch_bounds__(256, 1)
rec_kernel(const __grid_constant__ RecMaps maps, const bf16* __restrict__ xin, const bf16* __restrict__ mem0, Xchg* const gx,
           const bf16* __restrict__ fx, const bf16* __restrict__ wr, const bf16* __restrict__ wi) {
  extern __shared__ __align__(1024) uint8_t smem_raw[];
  const uint32_t sb = smem_u32(smem_raw);
  int role = blockIdx.x;
  {
    uint32_t smid, nsm; asm volatile("mov.u32 %0, %%smid;" : "=r"(smid)); asm volatile("mov.u32 %0, %%nsmid;" : "=r"(nsm));
    const int p = smid >> 1, u = p - 32;
    if (nsm == gridDim.x)
      role = (smid & 1) + (p < 32 ? 4 * ((p & 7) + 8 * (p >> 4)) + 2 * ((p >> 3) & 1) : p < 60 ? 4 * (16 + u % 7 + 7 * (u / 14)) + 2 * ((u / 7) & 1)
                         : p < 62 ? 2 * p + 8 : 2 * p - 4);
    role = uni(role);
  }
  if (role >= 128) {
    grid_wait(&gx->ctr[33], 128);
    fft_cols(sb, role - 128, 4);
    grid_arrive(&gx->ctr[32]); grid_wait(&gx->ctr[32], 4);
    fft_rows_inv(&maps.fo, sb, role - 128, 4);
    if (WPF && threadIdx.x == 0) {
#pragma unroll 1
      for (int i = role - 128; i < 512; i += 4) {
        asm volatile("cp.async.bulk.prefetch.tensor.2d.L2.global [%0, {%1, %2}];" :: "l"(&maps.wo), "r"(64 * (i & 15)), "r"((i >> 4) * DH) : "memory");
        __nanosleep(WPF);
      }
    }
    return;
  }
  const int tid = threadIdx.x, warp = uni(tid >> 5), lane = tid & 31, wg = warp >> 2, w4 = warp & 3, g = lane >> 2, t = lane & 3;
  const int h = role >> 2, j = role & 3, jh = j & 1;
  uint32_t w[48][4];
  float aq[16], av[16];
  int it = 0;

#define PT(k)
  auto pf_wo = [&]() {
    for (int i = 0; i < 4; i++)
      asm volatile("cp.async.bulk.prefetch.tensor.2d.L2.global [%0, {%1, %2}];" :: "l"(&maps.wo), "r"(256 * j + 64 * i), "r"(h * DH) : "memory");
  };
  fft_rows_fwd(fx, wr, wi, sb + R_MEM + 49152, role, [&]() {
    if (tid == 224) {
      mbar_init(sb + B_KV, 1); mbar_init(sb + B_W, 1); mbar_init(sb + B_X, 1); mbar_init(sb + B_X + 8, 1); mbar_init(sb + B_X + 16, 1); mbar_init(sb + B_X + 24, 1); mbar_init(sb + B_C, 4); mbar_init(sb + B_PK, 4); mbar_init(sb + B_B, 1);
      asm volatile("fence.mbarrier_init.release.cluster;" ::: "memory");
      mbar_expect_tx(sb + B_W, 3 * 65536);
      for (int i = 0; i < 4; i++) {
        tma2d(sb + R_X + i * 16384, &maps.wq, h * DH + 32 * j, i * 256, sb + B_W);
        if (i < 3) tma2d(sb + R_MEM + i * 16384, &maps.wk, h * DH + 32 * j, i * 256, sb + B_W);
        else asm volatile("cp.async.bulk.prefetch.tensor.2d.L2.global [%0, {%1, %2}];" :: "l"(&maps.wk), "r"(h * DH + 32 * j), "r"(768) : "memory");
      }
      for (int i = 0; i < 2; i++) tma2d(sb + R_WO + i * 32768, &maps.wv, h * DH + 64 * (j >> 1), jh * 512 + i * 256, sb + B_W);
      if (PFD) asm volatile("cp.async.bulk.prefetch.L2.global [%0], 2048;" :: "l"(xin + role * DM) : "memory");
      else for (int i = 0; i < 4; i++) asm volatile("cp.async.bulk.prefetch.L2.global [%0], 8192;" :: "l"(xin + role * 16384 + i * 4096) : "memory");
      if (WOP == 0) pf_wo();
    }
    __syncwarp();
  });
  if (tid < 16) sts32(sb + R_T + tid * 4, ~0u);
  fence_async();
  PT(0);
  grid_arrive(&gx->ctr[33]);
  PT(1);
  if (tid == 224) { tma2d(sb + R_MEM + 49152, &maps.wk, h * DH + 32 * j, 768, sb + B_W); if (WOP == 1) pf_wo(); }
  __syncwarp();
  uint8_t* const xb = reinterpret_cast<uint8_t*>(gx);
  auto probe_at = [&](int n) { return xb + (n ? offsetof(Xchg, C) + w4 * 8192 + role * 32 : offsetof(Xchg, B) + role * 8192 + warp * 128); };
  if (lane < 8) stx128(probe_at(lane >> 2) + (lane & 2) * 2048 + (lane & 1) * 16, 0, 0, 0, 0);
  uint32_t m0[4][4];
#pragma unroll
  for (int i = 0; i < 16; i++) m0[i >> 2][i & 3] = ldnc32(mem0 + g * DM + 128 * warp + 8 * i + 2 * t);
  mbar_spin(sb + B_W, 0, it);
  PT(2);
  const int lrow = (lane & 7) + ((lane >> 4) << 3), lhi = (lane >> 3) & 1;
  const int kq = wg ? 3 - 3 * jh : 3 * jh;
  const uint32_t LW = lrow * 128 + ((lhi ^ (lane & 7)) << 4);
  {
    const int chunk = w4 < 2 ? w4 + 2 * lhi : 2 * (w4 & 1) + lhi;
    uint32_t a = sb + (w4 < 2 ? R_X : R_MEM) + kq * 16384 + lrow * 64 + ((chunk ^ ((lrow >> 1) & 3)) << 4);
#pragma unroll
    for (int i = 0; i < 16; i++) ldsm4t(w[i], a + i * 1024);
    const uint32_t st = wg ? 1024 : 2048, av0 = sb + R_WO + (LW ^ (w4 << 5));
    const uint32_t a1 = wg ? a + (2 * jh - 1) * 16384 : av0 + jh * 32768, a2 = wg ? a + (2 * jh - 1) * 32768 : av0 + (1 - jh) * 32768;
#pragma unroll
    for (int i = 0; i < 16; i++) { ldsm4t(w[16 + i], a1 + i * st); ldsm4t(w[32 + i], a2 + i * st); }
  }
  uint32_t L16 = pin(lane * 16);
  const uint32_t uW = uni(sb + w4 * 512), uWo = uni(sb + R_WO + w4 * 16384), uMem = uni(sb + R_MEM + kq * 4096);
  const uint32_t dX = uni(((sb + R_X + kq * 16384) >> 4) | 0x10000u);
  auto load_wo = [&](uint32_t (&d)[32][4], int i0, int i1) {
#pragma unroll
    for (int i = i0; i < i1; i++) lds128(d[i], uWo + L16 + (i & 1) * 512 + (i >> 4) * 1024 + (i & 14) * 1024);
  };
  auto issue_x = [&](int n, int k) {
    const uint32_t bar = sb + B_X + 8 * k, q = k ^ (3 - 3 * jh);
    mbar_expect_tx(bar, 16384); tma3d(sb + R_X + q * 16384, &maps.x, n * SEG, 4 * q, bar);
  };
  auto store_stage = [&](int n) {
    asm volatile("cp.async.bulk.global.shared::cta.bulk_group [%0], [%1], 8192; cp.async.bulk.commit_group;"
                 :: "l"(g_kqv[n & 3][role]), "r"(sb + R_STAGE) : "memory");
  };
  auto issue_kqv = [&](int n) {
    const int p = (n & 3) * 128 + 4 * h;
    mbar_expect_tx(sb + B_KV, 26624);
    tma3d(sb + R_K, &maps.k, 0, p, sb + B_KV); tma3d(sb + R_Q, &maps.q, 8 + 2 * j, p, sb + B_KV); tma3d(sb + R_V, &maps.v, 16, p, sb + B_KV);
  };
  auto fetch4k = [&](uint32_t dst, uint32_t off, uint32_t bar, uint32_t t) {
    asm volatile("{.reg .pred p, q; .reg .b32 g; .reg .b64 c; elect.sync _|q, 0xffffffff; @q mbarrier.arrive.expect_tx.shared::cta.b64 _, [%2], 4096;\n"
                 "LOOP: mov.u64 c, %%globaltimer; cvt.u32.u64 g, c; sub.s32 g, %3, g; setp.lt.u32 p, g, 16384; @p bra.uni LOOP;\n"
                 "@q cp.async.bulk.shared::cluster.global.mbarrier::complete_tx::bytes [%0], [%1], 4096, [%2];}" :: "r"(dst), "l"(xb + off), "r"(bar), "r"(t - 1) : "memory");
  };
  uint32_t uS;
  auto my_b = [&]() { return offsetof(Xchg, B) + role * 8192 + ((uS + ((uint32_t)it >> 31)) & 1) * 4096; };
  auto issue_c = [&](uint32_t t) { fetch4k(sb + R_MEM + w4 * 4096, offsetof(Xchg, C) + w4 * 8192 + ((uS + ((uint32_t)it >> 31)) & 4096), sb + B_C, t); };
  auto wait_x = [&](int n, int i) { if (!(EXP & 1) || n < 2) mbar_spin(sb + B_X + 8 * i, n & 1, it); };
#define PACED(d0) uint32_t dz = d0; const uint32_t z = (uint32_t)it >> 31; auto pace = [&]() { for (int k = 0; k < PACE; k++) { if (k & 1) asm("add.u32 %0, %0, %1;" : "+r"(dz) : "r"(z)); else asm("xor.b32 %0, %0, %1;" : "+r"(dz) : "r"(z)); } };
  auto project_v = [&](auto I0, auto I1, auto&& mid) {
    PACED(decltype(I0)::value < 16 ? dX : dX ^ 1024);
    wg_fence();
    sfor<decltype(I0)::value, decltype(I1)::value>([&](auto I) {
      constexpr int i = decltype(I)::value;
      mid(i);
      if (i == 16 && decltype(I0)::value < 16) dz ^= 1024;
      wg_rs32<((i >> 2) & 3) * 256 + (i & 3) * 2, (i > 0)>(av, w[16 + i], dz);
      pace();
    });
    wg_commit();
  };
  auto project_qk = [&](auto I0, auto I1, auto first, auto&& mid) {
    PACED((dX ^ (decltype(I0)::value >> 4 << 10)) + ((uint32_t)it >> 31));
    wg_fence();
    sfor<decltype(I0)::value, decltype(I1)::value>([&](auto I) {
      constexpr int i = decltype(I)::value;
      mid(i);
      wg_rs32<((i >> 2) & 3) * 256 + (i & 3) * 2, !decltype(first)::value || i != decltype(I0)::value>(aq, w[i], dz);
      pace();
    });
    wg_commit();
  };
  const uint32_t uP = uni(sb + R_X + 3 * jh * 16384 + w4 * 512);
  auto park = [&]() {
    bar_sync(1, 128);
#pragma unroll
    for (int i = 0; i < 4; i++) sts128f(uP + L16 + i * 2048, aq + 4 * i);
    warp_arrive(sb + B_PK);
  };
  auto unpark = [&]() {
#pragma unroll
    for (int i = 0; i < 4; i++) {
      const float4 p = lds128f(uP + L16 + i * 2048);
      av[4 * i] = p.x; av[4 * i + 1] = p.y; av[4 * i + 2] = p.z; av[4 * i + 3] = p.w;
    }
  };
  auto fin_qk = [&]() {
#pragma unroll
    for (int i = 0; i < 16; i++) aq[i] += av[i];
    const uint32_t a = sb + R_STAGE + (w4 < 2 ? 2048 + w4 * 128 : (w4 & 1) * 256) + (L16 & 112) + (L16 >> 7) * 512;
    stsm4t(a, pack2(aq[0], aq[1]), pack2(aq[4], aq[5]), pack2(aq[8], aq[9]), pack2(aq[12], aq[13]));
    stsm4t(a + (w4 < 2 ? 256 : 128), pack2(aq[2], aq[3]), pack2(aq[6], aq[7]), pack2(aq[10], aq[11]), pack2(aq[14], aq[15]));
  };
  auto fin_v = [&]() {
#pragma unroll
    for (int a = 0; a < 2; a++)
      sts128(sb + R_STAGE + 4096 + w4 * 1024 + a * 512 + L16, pack2(av[8 * a], av[8 * a + 1]), pack2(av[8 * a + 2], av[8 * a + 3]),
             pack2(av[8 * a + 4], av[8 * a + 5]), pack2(av[8 * a + 6], av[8 * a + 7]));
  };
  __syncthreads();
  if (tid == 224) {
#pragma unroll 1
    for (int i = 0; i < 4; i++) issue_x(0, i);
    mbar_expect_tx(sb + B_W, 65536);
    for (int i = 0; i < 4; i++) tma2d(sb + R_WO + i * 16384, &maps.wo, 256 * j + 64 * i, h * DH, sb + B_W);
  }
  __syncwarp();
  if (wg) {
#pragma unroll
    for (int i = 0; i < NSW; i++) sts128(uW + R_WC + L16 + i * 2048, w[i]);
  }
#pragma unroll
  for (int i = 0; i < 4; i++) sts128(sb + R_MEM + warp * 2048 + i * 512 + (g >> 1) * 128 + t * 32 + (g & 1) * 16, m0[i]);
  auto probe = [&](int n, int cnt) {
    if (lane == 0) {
#pragma unroll 1
      for (int i = role >> 7; i < cnt; i++) {
        const int k = (i ^ wg) & 1;
        const unsigned t0 = clk();
        uint32_t v; asm volatile("atom.relaxed.gpu.global.exch.b32 %0, [%1], 0;" : "=r"(v) : "l"(probe_at(n) + k * 4096) : "memory");
        if (v == 0) asm volatile("red.shared.min.u32 [%0], %1;" :: "r"(sb + R_T + (n ? w4 * 8 : 32) + k * 4), "r"(clk() - t0) : "memory");
      }
    }
    __syncwarp();
  };
#pragma unroll 1
  for (int n = 0; n < 2; n++) {
    probe(0, NPB);
    PT(3 + 3 * n);
    wait_x(n, 2);
    PT(4 + 3 * n);
    if (wg == 0) {
      wait_x(n, 3);
      project_qk(IC<0>{}, IC<16>{}, IC<1>{}, [](int) {});
      project_v(IC<0>{}, IC<32>{}, [](int) {});
      if (tid == 96 && n == 1) {
        asm volatile("cp.async.bulk.wait_group 0;" ::: "memory");
        __threadfence(); atomicAdd(&gx->ctr[h], 1u);
      }
      __syncwarp();
      wg_wait<0>(); keep(aq); keep(av);
      park();
      fin_v();
      fence_async();
    } else {
      wait_x(n, 0); wait_x(n, 1);
      project_qk(IC<32>{}, IC<48>{}, IC<1>{}, [](int) {});
      project_qk(IC<16>{}, IC<32>{}, IC<0>{}, [](int) {});
      project_qk(IC<0>{}, IC<16>{}, IC<0>{}, [](int) {});
      mbar_spin(sb + B_PK, n, it);
      unpark();
      wg_wait<0>(); keep(aq);
      fin_qk();
      fence_async();
    }
    __syncthreads();
    if (tid == 0 && n) stx32(&gx->S[role], 1 + (HOME & 2 && lds32(sb + R_T + 36) < lds32(sb + R_T + 32)));
    PT(5 + 3 * n);
    if (tid == 96 && n == 0) store_stage(0);
    if (tid == 128 && n == 0) {
#pragma unroll 1
      for (int i = 0; i < 4; i++) issue_x(1, i);
    }
    if (warp == 5 && n == 1) {
#pragma unroll 1
      while (__any_sync(0xffffffffu, ldx32(&gx->ctr[h]) < 4) && ++it < SPIN_LIMIT) {}
      __threadfence(); asm volatile("fence.proxy.async;" ::: "memory");
      if (elect()) issue_kqv(0);
    }
    __syncwarp();
  }
  mbar_spin(sb + B_W, 1, it);
  PT(9);
#pragma unroll
  for (int i = 0; i < 4; i++) {
    uint32_t f[4][4];
    const uint32_t a = sb + R_WO + warp * 8192 + i * 2048;
#pragma unroll
    for (int q = 0; q < 4; q++) ldsm4t(f[q], a + (LW ^ (q << 5)));
    __syncwarp();
#pragma unroll
    for (int q = 0; q < 4; q++) sts128(a + q * 512 + L16, f[q]);
  }
  probe(1, NPC);
  {
    const int o = 32 * w4 + 16 * wg + 4 * t + j;
    uint32_t v;
#pragma unroll 1
    while (__any_sync(0xffffffffu, (v = ldx32(&gx->S[o])) == 0) && ++it < SPIN_LIMIT) {}
    asm volatile("st.shared.u64 [%0], %1;" :: "r"(sb + R_DST + wg * 1024 + w4 * 256 + lane * 8), "l"(xb + offsetof(Xchg, B) + o * 8192 + (v >> 1) * 4096 + h * 128 + ((g ^ h) & 7) * 16) : "memory");
  }
  if (wg == 0) {
    const uint64_t cd = reinterpret_cast<uint64_t>(xb + (offsetof(Xchg, C) + j * 8192 + h * 128 + w4 * 32 + (L16 & 16) * 256 + (L16 & 64) / 4 + (L16 >> 7) * 4));
    sts128(uW + R_RD + L16, (uint32_t)cd, (uint32_t)(cd >> 32), sb + R_MEM + (L16 & 112) * 8 + (L16 >> 8) * 1024 + ((w4 * 32 + ((L16 >> 3) & 16)) ^ (L16 & 112)),
           (L16 >> 6) == (h & 3) * 2 + ((h >> 2) & 1) ? 0xFFFE0000u : 0xFFFFFFFFu);
  }
  PT(10);
  mbar_spin(sb + B_KV, 0, it);
  PT(11);
  if (tid == 0) sts32(sb + B_DUE + 8, gtime() & ~31u);
  if (tid < 4) sts32(sb + B_ONE + tid * 4, 0x3F803F80u);
  if (warp == 1) { const uint32_t e = g >> 1 == t ? 0x3F80u << (16 * (g & 1)) : 0u; sts128(sb + R_ID + L16, e, 0, 0, e); }
  __syncthreads();
  uS = uni((HOME & 1 ? lds32(sb + R_T + w4 * 8 + 4) < lds32(sb + R_T + w4 * 8) : j >> 1) * 4096 + (HOME & 2 && lds32(sb + R_T + 36) < lds32(sb + R_T + 32)));

  const float sc = 0.08838834764831845f * 1.4426950408889634f;
  uint8_t* const xa = xb + uni(h * 16384);
  const uint32_t uA = uni(wg ? (w4 >> 1) * 2048 + j * 512 + (w4 & 1) * 256 : 8192 + (4 * (j >> 1) + w4) * 512 + jh * 256);
  const uint32_t uP2 = uni(sb + R_P + w4 * 256);
  uint32_t nc = 1;
  uint32_t ma;
  const uint8_t* adst;
  auto pin_mem = [&]() { adst = pinp(xa + uA + L16 / 2); ma = pin(uMem + (L16 & 384) + (L16 & 48) * 2 + (L16 & 64) / 4); };
  pin_mem();

#pragma unroll 1
  for (int s = 0;; nc++) {
    const uint32_t tag = (s + 1) & 1;
    auto fresh = [&]() { L16 += (uint32_t)it >> 31; };
    auto get_due = [&]() { return lds32(sb + B_DUE + 4 + tag * 4); };
    float c[4][4], r4[4];
    auto fold = [&]() {
#pragma unroll
      for (int i = 0; i < 4; i++) r4[i] = ((c[0][i] + c[1][i]) + c[2][i]) + c[3][i];
    };
    auto mma4 = [&](int n, const uint32_t (&b0)[4], const uint32_t (&b1)[4]) {
      mma_h(c[0], w[n + 2], b1, 0); mma_h(c[1], w[n + 3], b1, 1); mma_h(c[2], w[n], b0, 0); mma_h(c[3], w[n + 1], b0, 1);
    };
    auto xpos = [&](int pos, int wp) {
      if ((pos == X0 || pos == X1 || pos == X2 || pos == X3) && warp == wp && s + 1 < NSEG && elect()) {
        const int z = (uint32_t)it >> 31;
        if (pos == X2) issue_x(s + 2, 2 + z);
        if (pos == X3) issue_x(s + 2, 3 + z);
        if (pos == X1) issue_x(s + 2, 1 + z);
        if (pos == X0) issue_x(s + 2, z);
      }
      __syncwarp();
    };
    if (wg == 0) {
      mbar_spin(sb + B_C, nc & 1, it);
      TS(13);
      uint32_t b[16][4], tg[4];
#pragma unroll
      for (int i = 0; i < PD0; i++) { lds128(b[i], ma + i * 512); __syncwarp(); }
      sched();
      zero(c);
#pragma unroll
      for (int i = 0; i < 8; i++) {
        const int k = i ^ 1;
        mma_h(c[0], w[2 * k], b[k], 0); mma_h(c[1], w[2 * k + 1], b[k], 1);
        if (i < 2 * NV0) { mma_h(c[2], w[16 + 2 * k], b[k], 0); mma_h(c[3], w[17 + 2 * k], b[k], 1); }
        sched();
        if ((i & 1) && i + PD0 < 9) { lds128(b[i + PD0 - 1], ma + (i + PD0 - 1) * 512); __syncwarp(); lds128(b[i + PD0], ma + (i + PD0) * 512); sched(); }
        if (i == TGP) {
          fresh();
#pragma unroll
          for (int k = 0; k < 4; k++) tg[k] = lds32((uW * 4 + L16) * 2 + (L16 >> 6) * 4 + (R_MEM + k * 1024 - 7 * sb));
          sched();
        }
      }
#pragma unroll
      for (int i = 0; i < 4; i++) { r4[i] = c[0][i] + c[1][i]; c[0][i] = c[1][i] = 0.f; }
      sts128f(uW + R_RED + L16, r4);
      TS(1);
      const uint32_t old = bar_or(4, (dif2(tg[0], tg[1], s) | dif2(tg[2], tg[3], s)) & (s > 0));
      TS(0);
#pragma unroll
      for (int i = 0; i < 2 * NV0; i++) { lds128(b[8 + i], (ma ^ 4096) + i * 512); __syncwarp(); }
      sched();
#pragma unroll
      for (int i = NV0; i < 8; i++) {
        if (VB && i == VB) bar_sync(7, 256);
        mma4(16 + 4 * i, b[2 * i], b[2 * i + 1]);
        if (i < 7) sched();
        if (i < 4) { lds128(b[8 + 2 * i], (ma ^ 4096) + i * 1024); __syncwarp(); lds128(b[9 + 2 * i], (ma ^ 4096) + i * 1024 + 512); sched(); }
      }
      fold();
      asm volatile("{.reg .pred p; setp.eq.u32 p, %3, 0; @p st.relaxed.gpu.global.v2.b32 [%0], {%1,%2};}" :: "l"(adst), "r"((pack2(r4[0], r4[1]) & ~1u) | tag), "r"(pack2(r4[2], r4[3])), "r"(old) : "memory");
      sched();
      const unsigned tpub = clk();
      if (__any_sync(0xffffffffu, old) && nc < NC_MAX) {
        bar_sync(3, 256);
        issue_c(gtime());
        continue;
      }
      TS(3);
      xpos(0, 0);
      const uint32_t due = get_due();
      uint32_t vf[4][4], vm[2][4], p[4], pm, o[4];
      const uint32_t va = sb + R_V + (w4 >> 1) * 8192 + (w4 & 1) * 2048 + L16;
#pragma unroll
      for (int i = 0; i < 4; i++) {
        uint32_t q[4]; lds128(vf[i], va + i * 512); lds128(q, va + 4096 + i * 512);
#pragma unroll
        for (int e = 0; e < 4; e++) vf[i][e] = hadd2(vf[i][e], q[e]);
      }
      const uint32_t pa = pin(sb + R_P + (L16 >> 1));
      const uint8_t* vsrc = pinp(xa + 8192 + w4 * 1024 + L16 / 2);
      uint32_t one[4];
      lds128(one, sb + B_ONE);
      auto pv_x = [&]() {
        zero(c);
        mma_a(c[2], one, p[0], p[1]);
        mma_a(c[0], vf[0], p[0], p[1]); mma_a(c[1], vf[2], p[0], p[1]);
        sched();
        mma_a(c[2], one, p[2], p[3]);
        mma_a(c[0], vf[1], p[2], p[3]); mma_a(c[1], vf[3], p[2], p[3]);
        sched();
      };
      auto pv_m = [&]() {
        mma1688(c[2], one[0], one[1], pm);
        mma_a(c[0], vm[0], pm, pm);
        sched();
        mma_a(c[1], vm[1], pm, pm);
      };
      auto norm = [&]() {
        const float n0 = rcp(c[2][0]), n1 = rcp(c[2][1]);
#pragma unroll
        for (int i = 0; i < 4; i++) o[i] = pack2(c[i >> 1][2 * (i & 1)] * n0, c[i >> 1][2 * (i & 1) + 1] * n1);
        return ((__float_as_uint(c[2][0]) - 0x1F800000u) | (__float_as_uint(c[2][1]) - 0x1F800000u)) >> 30;
      };
      auto load_m = [&](int x) { const float2 e0 = lds64f(pa + 512 + x * 1024), e1 = lds64f(pa + 768 + x * 1024); pm = pack2(e0.x * e1.x, e0.y * e1.y); };
      auto attend_max = [&](int x) {
        float2 sv[6];
#pragma unroll
        for (int i = 0; i < 6; i++) sv[i] = lds64f(pa - 3072 + x * 1536 + i * 256);
        sv[4].x += sv[5].x; sv[4].y += sv[5].y;
        const int dq = (int)(L16 >> 6) - (int)((L16 >> 3) & 6) + 8 * j;
        float m = fmaxf(sv[4].x, sv[4].y);
#pragma unroll
        for (int i = 0; i < 4; i++) {
          if (x && 8 * i > dq) sv[i].x = -INFINITY;
          if (x && 8 * i + 1 > dq) sv[i].y = -INFINITY;
          m = fmaxf(m, fmaxf(sv[i].x, sv[i].y));
        }
        m = fmaxf(m, __shfl_xor_sync(0xffffffffu, m, 1));
        m = fmaxf(m, __shfl_xor_sync(0xffffffffu, m, 2));
#pragma unroll
        for (int i = 0; i < 5; i++) (i < 4 ? p[i] : pm) = pack2(ex2(sv[i].x - m), ex2(sv[i].y - m));
        pv_x(); pv_m(); norm();
      };
      uint32_t tq[4];
      auto get_t = [&]() {
        tq[0] = tq[1] = tq[2] = tq[3] = 0;
        asm volatile("{.reg .pred p; setp.eq.u32 p, %5, 0; @p ld.relaxed.gpu.global.v4.b32 {%0,%1,%2,%3}, [%4];}"
                     : "+r"(tq[0]), "+r"(tq[1]), "+r"(tq[2]), "+r"(tq[3]) : "l"(xb + offsetof(Xchg, T) + L16 * 8), "r"(warp) : "memory");
      };
      delay_until(tpub + DLY_V);
      wait_time(due + NS_V);
      TS(4);
      ldx(vm, vsrc);
      sched();
      xpos(2, 2);
      auto store_kqv = [&]() {
        fence_async();
        if (!(EXP & 4))
          asm volatile("{.reg .pred p; elect.sync _|p, 0xffffffff; @p cp.async.bulk.global.shared::cta.bulk_group [%0], [%1], 2048; cp.async.bulk.commit_group;}"
                       :: "l"(g_kqv[(s + 1) & 3][role] + w4 * 128), "r"(sb + R_STAGE + w4 * 2048) : "memory");
      };
      if (SPOS == 2) store_kqv();
      sched();
      bar_sync(5, 256);
      ldsm4(p, sb + R_P + L16);
      load_m(0);
      pv_x();
      ldsm4(p, sb + R_P + 1024 + L16);
      pv_m();
      const uint32_t r = norm(), tl = after(tag, c[2][0], (uint32_t)it >> 31);
      const bool redo = __any_sync(0xffffffffu, r | ((dif2(vm[0][0], vm[0][2], tl) | dif2(vm[1][0], vm[1][2], tl)) & 1));
      TS(6);
      stsm4t(uW + R_O + L16, o[0], o[1], o[2], o[3]);
      bar_arrive_unless(6, redo);
      sched();
      if (TQL == 7) get_t();
      TS(7);
      pv_x();
      if (rare(redo)) retry<2>(vm, vsrc, tag, it);
      bar_sync(8, 256);
      load_m(1);
      pv_m();
      if (rare(__any_sync(0xffffffffu, norm()) || redo)) {
        fresh();
#pragma unroll 1
        for (int x = !redo; x < 2; x++) {
          attend_max(x);
          if (x == 0) { stsm4t(uW + R_O + L16, o[0], o[1], o[2], o[3]); bar_arrive(6, 256); }
        }
      }
      TS(8);
      if (TQL == 8) get_t();
      const bool xok = mbar_test(sb + B_X + 16, s & 1) & mbar_test(sb + B_X + 24, s & 1);
      xpos(4, 2);
      fresh();
      const uint32_t ob = uni(sb + R_MEM + 4096 + w4 * 1024);
      stsm4t(ob + (L16 & 112) * 4 + (((L16 >> 3) ^ (L16 >> 1)) & 48), o[0], o[1], o[2], o[3]);
      __syncwarp();
      uint32_t rd[4];
      lds128(rd, uW + R_RD + L16);
      lds128(o, ob + (L16 ^ ((L16 >> 3) & 48)));
      auto put_o = [&]() {
        *reinterpret_cast<uint4*>(reinterpret_cast<uint8_t*>(g_ox) + (((s * SEG + 8 * j) * HD + h * DH + 32 * w4) * 2 + (L16 >> 6) * (HD * 2) + (L16 & 48))) = make_uint4(o[0], o[1], o[2], o[3]);
      };
      if (s + 1 == NSEG) { put_o(); asm volatile("cp.async.bulk.wait_group 0;" ::: "memory"); break; }
      asm volatile("cp.async.bulk.wait_group 0;" ::: "memory");
      if (elect()) stx32(xa + 4096 + j * 16 + w4 * 4, s + 1);
      __syncwarp();
      if (rare(!xok)) { wait_x(s + 2, 3); wait_x(s + 2, 2); }
      TS(9);
      fresh();
      const uint32_t e = due | ((s + 1) & 31);
      project_qk(IC<0>{}, IC<NQ>{}, IC<1>{}, [&](int n) {
        if (n == OXPOS) { __syncwarp(); put_o(); __syncwarp(); }
        if (n == TQP) { __syncwarp(); tq[0] = dif2v(tq[0], tq[1], e) | dif2v(tq[2], tq[3], e); __syncwarp(); }
      });
      if (NPA) project_v(IC<0>{}, IC<NPA>{}, [](int) {});
      TS(2);
      if (warp == 0) {
        uint32_t last = due, nx = NS_P;
        if (rare(__any_sync(0xffffffffu, tq[0]))) {
          const uint32_t ref = gtime();
#pragma unroll 1
          do ldx128(o, xb + offsetof(Xchg, T) + L16 * 8); while (any_bit(or3(o[0] - s - 1, o[1] - s - 1, o[2] - s - 1), o[3] - s - 1, 30) && ++it < SPIN_LIMIT);
          const int d = max(max((int)(o[0] - ref), (int)(o[1] - ref)), max((int)(o[2] - ref), (int)(o[3] - ref)));
          last = (ref + __reduce_max_sync(0xffffffffu, d)) & ~31u;
          if (last != due) nx += NS_X;
        }
        sts32(sb + B_DUE, last);
        sts32(sb + B_DUE + 8 - tag * 4, last + nx);
        fetch4k(sb + R_MEM, my_b(), sb + B_B, last + NS_B);
        LOG(13, tl - last);
        LOG(9, last);
      }
      if (NQ < 16) project_qk(IC<NQ>{}, IC<16>{}, IC<0>{}, [](int) {});
      project_v(IC<NPA>{}, IC<NPRE>{}, [](int) {});
      const uint32_t ba = rd[2], msk = rd[3];
      const uint8_t* cdst = reinterpret_cast<const uint8_t*>(rd[0] | (uint64_t)rd[1] << 32);
      TS(14);
      mbar_spin(sb + B_B, s & 1, it);
      TS(10);
      uint32_t bq[2][4];
      auto sum_b = [&]() {
        ldsm4t(bq[0], ba); ldsm4t(bq[1], ba + 2048);
        sched();
#pragma unroll
        for (int i = 0; i < 8; i++) c[i >> 2][i & 3] = 0.f;
        mma_a(c[0], bq[0], 0x3F803F80u, 0x3F803F80u); mma_a(c[1], bq[1], 0x3F803F80u, 0x3F803F80u);
        const uint32_t t2 = tag * 0x10001u;
        const bool old = any_bit(or3(dif2(bq[0][0], bq[0][1], t2), dif2(bq[0][2], bq[0][3], t2), dif2(bq[1][0], bq[1][1], t2)), dif2(bq[1][2], bq[1][3], t2), L16 < 64 ? 0x10001u : 0u);
        const uint32_t T = (tag << 16) & ~msk, u = ((__float_as_uint(c[0][0] + c[1][0]) + ((0x10000u & ~msk) - T)) & msk) | T;
        asm volatile("{.reg .pred p; setp.eq.u32 p, %2, 0; @p st.relaxed.gpu.global.b32 [%0], %1;}"
                     :: "l"(cdst), "r"(pack2(__uint_as_float(u), c[0][2] + c[1][2])), "r"((uint32_t)(old || (L16 & 32))) : "memory");
        return old;
      };
      if (rare(sum_b())) {
#pragma unroll 1
        do {
          const uint8_t* p = xb + (my_b() + (ba - sb - R_MEM));
          ldx128(bq[0], p); ldx128(bq[1], p + 2048);
          sts128(ba, bq[0]); sts128(ba + 2048, bq[1]);
          __syncwarp();
          it += INC_B;
        } while (sum_b() && it < SPIN_LIMIT);
      }
      sched();
      TS(11);
      bar_arrive(0, 256);
      const unsigned tc = clk();
      const uint32_t cdue = lds32(sb + B_DUE) + NS_C;
      if (warp == 3) LOG(11, gtime() - cdue);
      fresh();
      wg_wait<0>(); keep(aq); keep(av);
      park();
      if (NPRE < 32) project_v(IC<NPRE>{}, IC<32>{}, [](int) {}); else fin_v();
      TS(12);
      delay_until(tc + DLY_C);
      issue_c(cdue);
      TS(5);
      LOG(warp, it);
      pin_mem();
      if (NPRE < 32) { wg_wait<0>(); keep(av); fin_v(); }
      if (!(EXP & 2)) mbar_spin(sb + B_KV, tag, it);
      TS(15);
    } else {
      uint32_t kf[8][4];
      auto load_k = [&]() {
        const uint32_t ka = sb + R_K + w4 * 1024 + (L16 & 112) + (L16 & 128) * 4 + (L16 & 256);
#pragma unroll
        for (int i = 0; i < 8; i++) ldsm4(kf[i], ka + (i >> 1) * 2048 + (i & 1) * 128);
      };
      auto put_p = [&](int x, uint32_t old, uint32_t again) {
        float e[4];
        const int dq = (int)((L16 >> 3) & 6) + 8 * j - (int)(L16 >> 6) - 16 * w4;
#pragma unroll
        for (int i = 0; i < 4; i++) { r4[i] = fmaf(c[3][i], sc, fmaf(c[2][i], sc, fmaf(c[0][i] + c[1][i], sc, __uint_as_float(i == 3 ? 0u - old : 0u)))); e[i] = x && dq + (i & 1) < 8 * (i >> 1) ? 0.f : ex2(r4[i]); }
        stsm2t(uP2 + x * 1024 + L16, pack2(e[0], e[1]), pack2(e[2], e[3]), again);
      };
      auto put_s = [&](int x) {
#pragma unroll
        for (int i = 0; i < 4; i++) sts32f(uW + R_S + x * 1536 + (L16 & 48) * 4 + (L16 >> 6) * 4 + (i & 1) * 32 + (i >> 1) * 256, r4[i]);
      };
      auto load_q = [&](uint32_t (&q)[4], uint32_t off) { ldsm4(q, sb + R_Q + (L16 & 112) + (L16 & 128) * 2 + (L16 >> 8) * 128 + off); };
      mbar_spin(sb + B_C, nc & 1, it);
      TS(13);
      float4 o4;
      uint32_t id[4], old;
      {
        uint32_t b[24][4];
#pragma unroll
        for (int i = 0; i < 2 * PD1; i++) { lds128(b[i], ma + i * 512); __syncwarp(); }
        sched();
        zero(c);
#pragma unroll
        for (int i = 0; i < 12; i++) {
          mma4(4 * i, b[2 * i], b[2 * i + 1]);
          if (i < 11) sched();
          if (i + PD1 < 12) { const int k = i + PD1; const uint32_t a = (ma ^ (k >> 2 << 12)) + (k & 3) * 1024; lds128(b[2 * k], a); __syncwarp(); lds128(b[2 * k + 1], a + 512); sched(); }
          if (i == RJ) { lds128(id, sb + R_ID + L16); sched(); }
          if (i == RI) { old = bar_or(4, 0); o4 = lds128f(uW + R_RED + L16); sched(); }
        }
      }
      TS(0);
      {
        float e[4] = {o4.x, o4.y, o4.z, o4.w};
#pragma unroll
        for (int i = 0; i < 4; i++) { r4[i] = (((e[i] + c[0][i]) + c[1][i]) + c[2][i]) + c[3][i]; e[i] = 0.f; }
        mma_a(e, id, pack2(r4[0], r4[1]), pack2(r4[2], r4[3]));
        sched();
        if (VB) bar_arrive(7, 256);
        sched();
        asm volatile("{.reg .pred p; setp.eq.u32 p, %3, 0; @p st.relaxed.gpu.global.v2.b32 [%0], {%1,%2};}" :: "l"(adst),
                     "r"((__byte_perm(__float_as_uint(e[0]), __float_as_uint(e[1]), 0x7632) & ~1u) | tag), "r"(__byte_perm(__float_as_uint(e[2]), __float_as_uint(e[3]), 0x7632)), "r"(old) : "memory");
        sched();
      }
      const unsigned tpub = clk(), now = gtime(), due = get_due();
      if (__any_sync(0xffffffffu, old) && nc < NC_MAX) { bar_sync(3, 256); continue; }
      TS(2);
      const uint8_t* asrc = pinp(adst + ((warp == 7) * 1024 - (int)uA));
      fresh();
      uint32_t wo[32][4];
      bool xok;
      auto reload = [&]() {
        sched();
#pragma unroll
        for (int i = RE0 + RE1; i < NSW; i++) lds128(w[i], uW + R_WC + L16 + i * 2048);
        sched();
      };
      auto out_proj = [&]() {
        uint32_t b[4][4];
        float d[4][4];
        uint8_t* dst[2];
        const uint32_t da = pin(uP2 + (R_DST - R_P) + L16 / 2);
        sched();
        TS(7);
        bar_sync(6, 256);
#pragma unroll
        for (int i = 0; i < 4; i++) { ldsm4(b[i], sb + R_O + i * 512 + L16); __syncwarp(); }
        sched();
        auto put_b = [&](uint8_t* a, const float (&e)[4][4]) {
          stx128(a, (pack2(e[0][0] + e[2][0], e[0][1] + e[2][1]) & ~1u) | tag, pack2(e[0][2] + e[2][2], e[0][3] + e[2][3]),
                 pack2(e[1][0] + e[3][0], e[1][1] + e[3][1]), pack2(e[1][2] + e[3][2], e[1][3] + e[3][3]));
        };
        zero(c); zero(d);
#pragma unroll
        for (int i = 0; i < 32; i++) {
          mma_h(i < 16 ? c[i & 3] : d[i & 3], wo[i], b[(i >> 2) & 3], (i >> 1) & 1);
          if (i >= LW0 && NB1 + i - LW0 < 32) { load_wo(wo, (NB1 + i - LW0) ^ 1, ((NB1 + i - LW0) ^ 1) + 1); __syncwarp(); }
          if (i == DL0 || i == DL1) asm volatile("ld.shared.u64 %0, [%1];" : "=l"(dst[i > DL0]) : "r"(da + (i > DL0) * 1024) : "memory");
          if (i >= 16 && i < 16 + RE0) { lds128(w[i - 16], uW + R_WC + L16 + (i - 16) * 2048); __syncwarp(); }
          if (i >= RP1 && i < RP1 + RE1) { lds128(w[i - RP1 + RE0], uW + R_WC + L16 + (i - RP1 + RE0) * 2048); __syncwarp(); }
          if (i == 22) put_b(dst[0], c);
          if ((i & 1) && (i < 20 || i > 22)) sched();
        }
        put_b(dst[1], d);
        sched();
        TS(6);
      };
      if (warp < 6) {
        delay_until(tpub + DLY_A);
        const int it0 = it;
        bool redo;
#pragma unroll 1
        do {
          uint32_t q[4][4], y[4];
          float d[4][4];
          wait_time(due);
          TS(4);
          ldx(q, asrc);
          sched();
          load_k();
          uint32_t qx[4][4];
#pragma unroll
          for (int i = 0; i < 4; i++) load_q(qx[i], i * 512);
          sched();
          load_wo(wo, 0, NE4);
          sched();
          zero(c);
#pragma unroll
          for (int i = 0; i < 8; i++) mma_h(c[i & 3], kf[i], qx[i >> 1], i & 1);
          put_p(1, 0, 0); put_s(1);
          sched();
          load_wo(wo, NE4, NA4);
          sched();
          zero(c); zero(d);
#pragma unroll
          for (int i = 0; i < 8; i++) {
            if (i == 0) { y[0] = dif2v(q[0][0], q[0][2], q[1][0]); sched(); }
            if (i == 3) { y[1] = dif2v(q[1][2], q[2][0], q[2][2]); sched(); }
            if (i == 6) { y[2] = dif2v(q[3][0], q[3][2], tag); sched(); }
            mma_h(i % 6 < 2 ? c[2 + i % 6] : d[i - 2], kf[i], q[i >> 1], i & 1);
            if (i == 2 || i == 5 || i == 7) sched();
          }
          y[0] = or_and(or3(y[0], y[1], dif2v(q[0][0], q[2][0], tag)), y[2], it < SPIN_LIMIT);
#pragma unroll
          for (int i = 0; i < 4; i++) { c[0][i] = d[0][i] + d[1][i]; c[1][i] = d[2][i] + d[3][i]; }
          put_p(0, y[0], it - it0);
          TS(5);
          bar_sync_unless(5, it - it0);
          redo = __any_sync(0xffffffffu, y[0]);
          it += INC_A;
        } while (redo);
        it -= INC_A;
        put_s(0);
        bar_arrive(8, 256);
        load_wo(wo, NA4, NB1);
        out_proj();
        if (warp == 4) LOG(12, tb);
      } else {
        uint32_t qx[2][4], q[4][4];
        if (warp == 6) {
          const uint32_t t1 = (now & ~31u) + NS_M;
          LOG(10, now - due);
          if (elect()) stx32(&gx->T[h][j], ((int)(t1 - due) > 0 ? t1 + NS_PEN : due) | ((s + 1) & 31));
          __syncwarp();
        }
        auto score = [&](const uint32_t (&a0)[4], const uint32_t (&a1)[4]) {
          zero(c);
#pragma unroll
          for (int i = 0; i < 4; i++) mma_h(c[i], i < 2 ? a0 : a1, q[2 + (i >> 1)], i & 1);
        };
        auto put_m = [&](uint32_t a, uint32_t old, uint32_t again) {
#pragma unroll
          for (int i = 0; i < 2; i++) { r4[i] = fmaf(c[3][2 + i], sc, fmaf((c[0][i] + c[1][2 + i]) + c[2][i], sc, __uint_as_float(i ? 0u - old : 0u))); r4[2 + i] = fmaf(r4[i] * 0x1p122f, 0.f, ex2(r4[i])); }
          asm volatile("{.reg .pred p; setp.eq.u32 p, %3, 0; @p st.shared.v2.f32 [%0], {%1,%2};}" :: "r"(a), "f"(r4[2]), "f"(r4[3]), "r"(again) : "memory");
        };
        delay_until(tpub + DLY_A);
        const uint32_t sa = sb + R_S + 512 + w4 * 256 + (L16 >> 1);
        const int it0 = it;
        bool redo;
#pragma unroll 1
        do {
          wait_time(due);
          TS(4);
          ldx<4, 2048>(q, asrc);
          sched();
          load_q(qx[0], (w4 & 1) * 1024); load_q(qx[1], (w4 & 1) * 1024 + 512);
          load_wo(wo, 0, NA6);
          sched();
          score(q[0], q[1]);
          sched();
          const uint32_t y = or_and(or3(dif2v(q[0][0], q[0][2], tag), dif2v(q[1][0], q[1][2], tag), dif2v(q[2][0], q[2][2], tag)), dif2v(q[3][0], q[3][2], tag), it < SPIN_LIMIT);
          put_m(sa + 2560, y, it - it0);
          TS(5);
          bar_arrive_unless(5, it - it0);
          redo = __any_sync(0xffffffffu, y);
          it += INC_A;
        } while (redo);
        it -= INC_A;
        sts64f(sa, r4[0], r4[1]);
        score(qx[0], qx[1]);
        put_m(sa + 3584, 0, 0);
        sts64f(sa + 1536, r4[0], r4[1]);
        bar_arrive(8, 256);
        load_wo(wo, NA6, NB1);
        out_proj();
      }
      TS(8);
      if (s + 1 == NSEG) break;
      wait_x(s + 2, 2);
      TS(9);
      fresh();
      if (N1) project_qk(IC<32>{}, IC<32 + N1>{}, IC<1>{}, [](int) {});
      TS(10);
      xpos(6, 6);
      uint32_t fl = s + 1;
      if (warp == 5) { wait_time(due + NS_F); fl = ldx32(xa + 4096 + ((L16 >> 2) & 60)); }
      reload();
      TS(14);
      pin_mem();
      wait_x(s + 2, 1); wait_x(s + 2, 0);
      if (warp == 5) {
#pragma unroll 1
        while (__any_sync(0xffffffffu, fl != s + 1) && !(EXP & 4) && ++it < SPIN_LIMIT) fl = ldx32(xa + 4096 + ((L16 >> 2) & 60));
        wait_time(due + (NS_B + NS_K));
        if (!(EXP & 2) && elect()) issue_kqv(s + 1);
        __syncwarp();
      }
      if (PFD && warp == 6 && s + PFD < NSEG && elect())
        asm volatile("cp.async.bulk.prefetch.L2.global [%0], 2048;" :: "l"(xin + ((s + PFD) * SEG + ((role + 4 * (role >> 5)) & 31)) * DM) : "memory");
      __syncwarp();
      TS(11);
      LOG(warp, it);
      if (warp == 4) LOG(8, nc);
      bar_sync(0, 256);
      if (N1 < 16) project_qk(IC<32 + N1>{}, IC<48>{}, IC<!N1>{}, [](int) {});
      project_qk(IC<16>{}, IC<32>{}, IC<0>{}, [&](int n) { if ((n & 15) == XWPOS) { __syncwarp(); xok = mbar_test(sb + B_PK, s & 1); __syncwarp(); } });
      if (rare(!xok)) mbar_spin(sb + B_PK, s & 1, it);
      unpark();
      project_qk(IC<0>{}, IC<16>{}, IC<0>{}, [](int) {});
      TS(12);
      wg_wait<0>(); keep(aq);
      TS(1);
      fin_qk();
      TS(15);
    }
    s++;
  }
  if (it >= SPIN_LIMIT || nc >= NC_MAX) g_err = 2;
}

typedef CUresult (*EncodeFn)(CUtensorMap*, CUtensorMapDataType, cuuint32_t, void*, const cuuint64_t*, const cuuint64_t*, const cuuint32_t*,
                             const cuuint32_t*, CUtensorMapInterleave, CUtensorMapSwizzle, CUtensorMapL2promotion, CUtensorMapFloatOOBfill);
static void make_map(EncodeFn fn, CUtensorMap* m, const void* p, uint64_t cols, uint64_t rows, uint64_t pitch, uint32_t bc, uint32_t br, CUtensorMapSwizzle sw) {
  cuuint64_t dims[2] = {cols, rows}, strides[1] = {pitch * 2};
  cuuint32_t box[2] = {bc, br}, es[2] = {1, 1};
  fn(m, CU_TENSOR_MAP_DATA_TYPE_BFLOAT16, 2, const_cast<void*>(p), dims, strides, box, es, CU_TENSOR_MAP_INTERLEAVE_NONE, sw,
     CU_TENSOR_MAP_L2_PROMOTION_L2_256B, CU_TENSOR_MAP_FLOAT_OOB_FILL_NONE);
}

extern "C" void kernel_launch(void* const* d_in, const int* in_sizes, int n_in, void* d_out, int out_size) {
  const bf16* Ax = (const bf16*)d_in[0]; const bf16* mem0 = (const bf16*)d_in[1];
  const bf16* Wq = (const bf16*)d_in[2]; const bf16* Wk = (const bf16*)d_in[3]; const bf16* Wv = (const bf16*)d_in[4];
  const bf16* Wo = (const bf16*)d_in[5];
  const bf16* Bx = (const bf16*)d_in[7]; const bf16* wr = (const bf16*)d_in[8]; const bf16* wi = (const bf16*)d_in[9];
  bf16* out = (bf16*)d_out;

  void* fp = nullptr; cudaDriverEntryPointQueryResult qr;
  cudaGetDriverEntryPoint("cuTensorMapEncodeTiled", &fp, cudaEnableDefault, &qr);
  EncodeFn fn = (EncodeFn)fp;
  void *kqv, *ox, *xr;
  cudaGetSymbolAddress(&xr, g_xraw);
  cudaGetSymbolAddress(&kqv, g_kqv); cudaGetSymbolAddress(&ox, g_ox);
  const CUtensorMapSwizzle S128 = CU_TENSOR_MAP_SWIZZLE_128B, S64 = CU_TENSOR_MAP_SWIZZLE_64B;

  GemmMaps m3; RecMaps mr;
  make_map(fn, &m3.a, ox, HD, S_LEN, HD, 64, 128, S128);
  make_map(fn, &m3.b[0], Wo, DM, HD, DM, 64, 64, S128);
  m3.b[1] = m3.b[0]; m3.b[2] = m3.b[0];
  make_map(fn, &m3.c, out, DM, S_LEN, 2 * DM, 64, 64, S128);
  make_map(fn, &mr.wq, Wq, HD, DM, HD, 32, 256, S64);
  make_map(fn, &mr.wk, Wk, HD, DM, HD, 32, 256, S64);
  make_map(fn, &mr.wv, Wv, HD, DM, HD, 64, 256, S128);
  make_map(fn, &mr.wo, Wo, DM, HD, DM, 64, 128, S128);
  {
    cuuint64_t dims[3] = {64, S_LEN, 16}, strides[2] = {DM * 2, 128};
    cuuint32_t box[3] = {64, 32, 4}, es[3] = {1, 1, 1};
    fn(&mr.x, CU_TENSOR_MAP_DATA_TYPE_BFLOAT16, 3, const_cast<bf16*>(Ax), dims, strides, box, es, CU_TENSOR_MAP_INTERLEAVE_NONE, S128,
       CU_TENSOR_MAP_L2_PROMOTION_L2_256B, CU_TENSOR_MAP_FLOAT_OOB_FILL_NONE);
  }
  for (int i = 0; i < 3; i++) {
    cuuint64_t dims[3] = {128, 32, 512}, strides[2] = {256, 8192};
    cuuint32_t box[3] = {128, i == 0 ? 8u : i == 1 ? 2u : 16u, 4}, es[3] = {1, 1, 1};
    fn(i == 0 ? &mr.k : i == 1 ? &mr.q : &mr.v, CU_TENSOR_MAP_DATA_TYPE_BFLOAT16, 3, kqv, dims, strides, box, es, CU_TENSOR_MAP_INTERLEAVE_NONE,
       CU_TENSOR_MAP_SWIZZLE_NONE, CU_TENSOR_MAP_L2_PROMOTION_L2_256B, CU_TENSOR_MAP_FLOAT_OOB_FILL_NONE);
  }
  {
    cuuint64_t dims[3] = {64, 16, S_LEN}, strides[2] = {128, 2 * DM * 2};
    cuuint32_t box[3] = {64, 16, 2}, es[3] = {1, 1, 1};
    fn(&mr.fo, CU_TENSOR_MAP_DATA_TYPE_BFLOAT16, 3, out + DM, dims, strides, box, es, CU_TENSOR_MAP_INTERLEAVE_NONE, S128,
       CU_TENSOR_MAP_L2_PROMOTION_NONE, CU_TENSOR_MAP_FLOAT_OOB_FILL_NONE);
  }
  constexpr int SM3 = 6 * 32768 + 32768 + 256 + 1024;
  cudaFuncSetAttribute(gemm_kernel<128, 6>, cudaFuncAttributeMaxDynamicSharedMemorySize, SM3);
  cudaFuncSetAttribute(rec_kernel, cudaFuncAttributeMaxDynamicSharedMemorySize, R_TOTAL);

  cudaStream_t st = cudaStreamPerThread;
  rec_kernel<<<132, 256, R_TOTAL, st>>>(mr, Ax, mem0, reinterpret_cast<Xchg*>((reinterpret_cast<uintptr_t>(xr) + 8191) & ~(uintptr_t)8191), Bx, wr, wi);
  cudaLaunchConfig_t cfg = {};
  cudaLaunchAttribute at[1];
  at[0].id = cudaLaunchAttributeProgrammaticStreamSerialization; at[0].val.programmaticStreamSerializationAllowed = PDL;
  cfg.gridDim = dim3(128); cfg.blockDim = dim3(384); cfg.dynamicSmemBytes = SM3; cfg.stream = st; cfg.attrs = at; cfg.numAttrs = 1;
  cudaLaunchKernelEx(&cfg, gemm_kernel<128, 6>, m3, 16, 8, 64, 8, 1);
}
```

```cpp
#include <cuda_runtime.h>
#include <cuda_bf16.h>
#include <cuda.h>
#include <stdint.h>
#include <stddef.h>
#include <type_traits>

typedef __nv_bfloat16 bf16;

constexpr int S_LEN = 2048, DM = 1024, NH = 32, DH = 128, MEM = 8, SEG = 32, NSEG = 64;
constexpr int HD = NH * DH;
#define SPIN 20
constexpr int SPIN_LIMIT = 1 << SPIN, INC_A = 1, INC_B = 1;

constexpr unsigned NC_MAX = 4096;
__device__ __align__(1024) uint4 g_kqv[4][128][512];
__device__ __align__(1024) bf16 g_ox[(size_t)S_LEN * HD];
struct Xchg {
  uint4 A[32][4][256];
  uint4 C[4][2][256];
  uint4 B[128][2][256];
  uint32_t T[32][32];
  uint32_t S[128];
  unsigned ctr[64];
};
__device__ __align__(1024) uint4 g_xraw[(sizeof(Xchg) + 8192) / 16];
__device__ __align__(1024) uint4 g_y[1024 * 256];
__device__ __align__(1024) uint4 g_wt[513 * 512];
__device__ int g_err;

__device__ __forceinline__ unsigned clk() { unsigned long long c; asm volatile("mov.u64 %0, %%clock64;" : "=l"(c)); return (unsigned)c; }
__device__ __forceinline__ uint32_t smem_u32(const void* p) { return (uint32_t)__cvta_generic_to_shared(p); }
__device__ __forceinline__ void mbar_init(uint32_t bar, int cnt) { asm volatile("mbarrier.init.shared::cta.b64 [%0], %1;" :: "r"(bar), "r"(cnt) : "memory"); }
__device__ __forceinline__ void mbar_expect_tx(uint32_t bar, int bytes) { asm volatile("mbarrier.arrive.expect_tx.shared::cta.b64 _, [%0], %1;" :: "r"(bar), "r"(bytes) : "memory"); }
__device__ __forceinline__ void mbar_arrive(uint32_t bar) { asm volatile("mbarrier.arrive.shared::cta.b64 _, [%0];" :: "r"(bar) : "memory"); }
__device__ __forceinline__ void mbar_arrive_cluster(uint32_t bar, int cta) {
  asm volatile("{.reg .b32 r; mapa.shared::cluster.u32 r, %0, %1; mbarrier.arrive.shared::cluster.b64 _, [r];}" :: "r"(bar), "r"(cta) : "memory"); }
__device__ __forceinline__ bool mbar_try(uint32_t bar, int par) {
  uint32_t ok; asm volatile("{.reg .pred p; mbarrier.try_wait.parity.shared::cta.b64 p, [%1], %2; selp.u32 %0, 1, 0, p;}" : "=r"(ok) : "r"(bar), "r"(par) : "memory"); return ok; }
__device__ __forceinline__ bool mbar_test(uint32_t bar, int par) {
  uint32_t ok; asm volatile("{.reg .pred p; mbarrier.test_wait.parity.shared::cta.b64 p, [%1], %2; selp.u32 %0, 1, 0, p;}" : "=r"(ok) : "r"(bar), "r"(par) : "memory"); return ok; }
__device__ __forceinline__ void mbar_wait(uint32_t bar, int par) {
  int it = 0;
  while (!mbar_try(bar, par)) { if (++it > SPIN_LIMIT) { g_err = 1; break; } }
}
__device__ __forceinline__ void tma2d(uint32_t dst, const CUtensorMap* m, int c0, int c1, uint32_t bar) {
  asm volatile("cp.async.bulk.tensor.2d.shared::cluster.global.mbarrier::complete_tx::bytes [%0], [%1, {%3, %4}], [%2];"
    :: "r"(dst), "l"(m), "r"(bar), "r"(c0), "r"(c1) : "memory"); }
__device__ __forceinline__ void tma2d_mc(uint32_t dst, const CUtensorMap* m, int c0, int c1, uint32_t bar, uint16_t mask) {
  asm volatile("cp.async.bulk.tensor.2d.shared::cluster.global.mbarrier::complete_tx::bytes.multicast::cluster [%0], [%1, {%3, %4}], [%2], %5;"
    :: "r"(dst), "l"(m), "r"(bar), "r"(c0), "r"(c1), "h"(mask) : "memory"); }
__device__ __forceinline__ void tma2d_store(const CUtensorMap* m, uint32_t src, int c0, int c1) {
  asm volatile("cp.async.bulk.tensor.2d.global.shared::cta.bulk_group [%0, {%2, %3}], [%1];" :: "l"(m), "r"(src), "r"(c0), "r"(c1) : "memory"); }
__device__ __forceinline__ void fence_async() { asm volatile("fence.proxy.async.shared::cta;" ::: "memory"); }
__device__ __forceinline__ void bar_sync(int id, int n) { asm volatile("bar.sync %0, %1;" :: "r"(id), "r"(n) : "memory"); }
__device__ __forceinline__ void bar_arrive(int id, int n) { asm volatile("bar.arrive %0, %1;" :: "r"(id), "r"(n) : "memory"); }
__device__ __forceinline__ uint32_t pack2(float lo, float hi) { uint32_t r; asm("cvt.rn.bf16x2.f32 %0, %1, %2;" : "=r"(r) : "f"(hi), "f"(lo)); return r; }
__device__ __forceinline__ uint32_t pack2_tag(float lo, float hi, uint32_t T) {
  uint32_t u = ((__float_as_uint(lo) - T + 0x10000u) & 0xFFFE0000u) + T;
  return __byte_perm(u, pack2(0.f, hi), 0x7632); }
__device__ __forceinline__ void ldsm4(uint32_t (&r)[4], uint32_t a) {
  asm volatile("ldmatrix.sync.aligned.m8n8.x4.shared.b16 {%0,%1,%2,%3}, [%4];" : "=r"(r[0]), "=r"(r[1]), "=r"(r[2]), "=r"(r[3]) : "r"(a) : "memory"); }
__device__ __forceinline__ void ldsm4t(uint32_t (&r)[4], uint32_t a) {
  asm volatile("ldmatrix.sync.aligned.m8n8.x4.trans.shared.b16 {%0,%1,%2,%3}, [%4];" : "=r"(r[0]), "=r"(r[1]), "=r"(r[2]), "=r"(r[3]) : "r"(a) : "memory"); }
__device__ __forceinline__ void stsm4(uint32_t a, uint32_t r0, uint32_t r1, uint32_t r2, uint32_t r3) {
  asm volatile("stmatrix.sync.aligned.m8n8.x4.shared.b16 [%0], {%1,%2,%3,%4};" :: "r"(a), "r"(r0), "r"(r1), "r"(r2), "r"(r3) : "memory"); }
__device__ __forceinline__ void stsm4t(uint32_t a, uint32_t r0, uint32_t r1, uint32_t r2, uint32_t r3) {
  asm volatile("stmatrix.sync.aligned.m8n8.x4.trans.shared.b16 [%0], {%1,%2,%3,%4};" :: "r"(a), "r"(r0), "r"(r1), "r"(r2), "r"(r3) : "memory"); }
__device__ __forceinline__ void lds128(uint32_t (&r)[4], uint32_t a) {
  asm volatile("ld.shared.v4.u32 {%0,%1,%2,%3}, [%4];" : "=r"(r[0]), "=r"(r[1]), "=r"(r[2]), "=r"(r[3]) : "r"(a) : "memory"); }
__device__ __forceinline__ float4 lds128f(uint32_t a) { float4 r;
  asm volatile("ld.shared.v4.f32 {%0,%1,%2,%3}, [%4];" : "=f"(r.x), "=f"(r.y), "=f"(r.z), "=f"(r.w) : "r"(a) : "memory"); return r; }
__device__ __forceinline__ float2 lds64f(uint32_t a) { float2 r;
  asm volatile("ld.shared.v2.f32 {%0,%1}, [%2];" : "=f"(r.x), "=f"(r.y) : "r"(a) : "memory"); return r; }
__device__ __forceinline__ void sts128(uint32_t a, uint32_t r0, uint32_t r1, uint32_t r2, uint32_t r3) {
  asm volatile("st.shared.v4.u32 [%0], {%1,%2,%3,%4};" :: "r"(a), "r"(r0), "r"(r1), "r"(r2), "r"(r3) : "memory"); }
__device__ __forceinline__ void sts64f(uint32_t a, float x, float y) { asm volatile("st.shared.v2.f32 [%0], {%1,%2};" :: "r"(a), "f"(x), "f"(y) : "memory"); }
__device__ __forceinline__ void sts32f(uint32_t a, float x) { asm volatile("st.shared.f32 [%0], %1;" :: "r"(a), "f"(x) : "memory"); }
__device__ __forceinline__ void mma16816(float (&d)[4], uint32_t a0, uint32_t a1, uint32_t a2, uint32_t a3, uint32_t b0, uint32_t b1) {
  asm volatile("mma.sync.aligned.m16n8k16.row.col.f32.bf16.bf16.f32 {%0,%1,%2,%3}, {%4,%5,%6,%7}, {%8,%9}, {%0,%1,%2,%3};"
    : "+f"(d[0]), "+f"(d[1]), "+f"(d[2]), "+f"(d[3]) : "r"(a0), "r"(a1), "r"(a2), "r"(a3), "r"(b0), "r"(b1)); }
__device__ __forceinline__ void mma1688(float (&d)[4], uint32_t a0, uint32_t a1, uint32_t b0) {
  asm volatile("mma.sync.aligned.m16n8k8.row.col.f32.bf16.bf16.f32 {%0,%1,%2,%3}, {%4,%5}, {%6}, {%0,%1,%2,%3};"
    : "+f"(d[0]), "+f"(d[1]), "+f"(d[2]), "+f"(d[3]) : "r"(a0), "r"(a1), "r"(b0)); }
__device__ __forceinline__ void ldx128(uint32_t (&r)[4], const void* p) {
  asm volatile("{.reg .b128 t; .reg .b64 a, b; ld.relaxed.gpu.global.b128 t, [%4]; mov.b128 {a, b}, t; mov.b64 {%0,%1}, a; mov.b64 {%2,%3}, b;}"
    : "=r"(r[0]), "=r"(r[1]), "=r"(r[2]), "=r"(r[3]) : "l"(p) : "memory"); }
__device__ __forceinline__ void ldx2x64(uint32_t (&r)[4], const void* p) {
  asm volatile("{.reg .b64 a, b; ld.relaxed.gpu.global.v2.b64 {a, b}, [%4]; mov.b64 {%0,%1}, a; mov.b64 {%2,%3}, b;}"
    : "=r"(r[0]), "=r"(r[1]), "=r"(r[2]), "=r"(r[3]) : "l"(p) : "memory"); }
__device__ __forceinline__ void stx128(void* p, uint32_t r0, uint32_t r1, uint32_t r2, uint32_t r3) {
  asm volatile("{.reg .b128 t; .reg .b64 a, b; mov.b64 a, {%1,%2}; mov.b64 b, {%3,%4}; mov.b128 t, {a, b}; st.relaxed.gpu.global.b128 [%0], t;}"
    :: "l"(p), "r"(r0), "r"(r1), "r"(r2), "r"(r3) : "memory"); }
__device__ __forceinline__ void stx64(void* p, uint32_t r0, uint32_t r1) {
  asm volatile("{.reg .b64 a; mov.b64 a, {%1,%2}; st.relaxed.gpu.global.b64 [%0], a;}" :: "l"(p), "r"(r0), "r"(r1) : "memory"); }
__device__ __forceinline__ uint32_t uni(uint32_t x) { return __shfl_sync(0xffffffffu, x, 0); }
__device__ __forceinline__ uint32_t pin(uint32_t x) { return __shfl_xor_sync(0xffffffffu, x, 0); }
__device__ __forceinline__ float ex2(float x) { float r; asm("ex2.approx.ftz.f32 %0, %1;" : "=f"(r) : "f"(x)); return r; }
__device__ __forceinline__ void wg_fence() { asm volatile("wgmma.fence.sync.aligned;" ::: "memory"); }
__device__ __forceinline__ void wg_commit() { asm volatile("wgmma.commit_group.sync.aligned;" ::: "memory"); }
template <int N> __device__ __forceinline__ void wg_wait() { asm volatile("wgmma.wait_group.sync.aligned %0;" :: "n"(N) : "memory"); }

__device__ __forceinline__ void wgmma_ss_n256_tb1(float (&d)[128], uint64_t da, uint64_t db, int sc) {
  asm volatile("{.reg .pred p; setp.ne.b32 p, %130, 0;\n"
    "wgmma.mma_async.sync.aligned.m64n256k16.f32.bf16.bf16 {%0,%1,%2,%3,%4,%5,%6,%7,%8,%9,%10,%11,%12,%13,%14,%15,%16,%17,%18,%19,%20,%21,%22,%23,%24,%25,%26,%27,%28,%29,%30,%31,%32,%33,%34,%35,%36,%37,%38,%39,%40,%41,%42,%43,%44,%45,%46,%47,%48,%49,%50,%51,%52,%53,%54,%55,%56,%57,%58,%59,%60,%61,%62,%63,%64,%65,%66,%67,%68,%69,%70,%71,%72,%73,%74,%75,%76,%77,%78,%79,%80,%81,%82,%83,%84,%85,%86,%87,%88,%89,%90,%91,%92,%93,%94,%95,%96,%97,%98,%99,%100,%101,%102,%103,%104,%105,%106,%107,%108,%109,%110,%111,%112,%113,%114,%115,%116,%117,%118,%119,%120,%121,%122,%123,%124,%125,%126,%127}, %128, %129, p, 1, 1, 0, 1;}\n"
    : "+f"(d[0]),"+f"(d[1]),"+f"(d[2]),"+f"(d[3]),"+f"(d[4]),"+f"(d[5]),"+f"(d[6]),"+f"(d[7]),"+f"(d[8]),"+f"(d[9]),"+f"(d[10]),"+f"(d[11]),"+f"(d[12]),"+f"(d[13]),"+f"(d[14]),"+f"(d[15]),"+f"(d[16]),"+f"(d[17]),"+f"(d[18]),"+f"(d[19]),"+f"(d[20]),"+f"(d[21]),"+f"(d[22]),"+f"(d[23]),"+f"(d[24]),"+f"(d[25]),"+f"(d[26]),"+f"(d[27]),"+f"(d[28]),"+f"(d[29]),"+f"(d[30]),"+f"(d[31]),"+f"(d[32]),"+f"(d[33]),"+f"(d[34]),"+f"(d[35]),"+f"(d[36]),"+f"(d[37]),"+f"(d[38]),"+f"(d[39]),"+f"(d[40]),"+f"(d[41]),"+f"(d[42]),"+f"(d[43]),"+f"(d[44]),"+f"(d[45]),"+f"(d[46]),"+f"(d[47]),"+f"(d[48]),"+f"(d[49]),"+f"(d[50]),"+f"(d[51]),"+f"(d[52]),"+f"(d[53]),"+f"(d[54]),"+f"(d[55]),"+f"(d[56]),"+f"(d[57]),"+f"(d[58]),"+f"(d[59]),"+f"(d[60]),"+f"(d[61]),"+f"(d[62]),"+f"(d[63]),"+f"(d[64]),"+f"(d[65]),"+f"(d[66]),"+f"(d[67]),"+f"(d[68]),"+f"(d[69]),"+f"(d[70]),"+f"(d[71]),"+f"(d[72]),"+f"(d[73]),"+f"(d[74]),"+f"(d[75]),"+f"(d[76]),"+f"(d[77]),"+f"(d[78]),"+f"(d[79]),"+f"(d[80]),"+f"(d[81]),"+f"(d[82]),"+f"(d[83]),"+f"(d[84]),"+f"(d[85]),"+f"(d[86]),"+f"(d[87]),"+f"(d[88]),"+f"(d[89]),"+f"(d[90]),"+f"(d[91]),"+f"(d[92]),"+f"(d[93]),"+f"(d[94]),"+f"(d[95]),"+f"(d[96]),"+f"(d[97]),"+f"(d[98]),"+f"(d[99]),"+f"(d[100]),"+f"(d[101]),"+f"(d[102]),"+f"(d[103]),"+f"(d[104]),"+f"(d[105]),"+f"(d[106]),"+f"(d[107]),"+f"(d[108]),"+f"(d[109]),"+f"(d[110]),"+f"(d[111]),"+f"(d[112]),"+f"(d[113]),"+f"(d[114]),"+f"(d[115]),"+f"(d[116]),"+f"(d[117]),"+f"(d[118]),"+f"(d[119]),"+f"(d[120]),"+f"(d[121]),"+f"(d[122]),"+f"(d[123]),"+f"(d[124]),"+f"(d[125]),"+f"(d[126]),"+f"(d[127])
    : "l"(da), "l"(db), "r"(sc));
}

__device__ __forceinline__ void wgmma_ss_n128_tb1(float (&d)[64], uint64_t da, uint64_t db, int sc) {
  asm volatile("{.reg .pred p; setp.ne.b32 p, %66, 0;\n"
    "wgmma.mma_async.sync.aligned.m64n128k16.f32.bf16.bf16 {%0,%1,%2,%3,%4,%5,%6,%7,%8,%9,%10,%11,%12,%13,%14,%15,%16,%17,%18,%19,%20,%21,%22,%23,%24,%25,%26,%27,%28,%29,%30,%31,%32,%33,%34,%35,%36,%37,%38,%39,%40,%41,%42,%43,%44,%45,%46,%47,%48,%49,%50,%51,%52,%53,%54,%55,%56,%57,%58,%59,%60,%61,%62,%63}, %64, %65, p, 1, 1, 0, 1;}\n"
    : "+f"(d[0]),"+f"(d[1]),"+f"(d[2]),"+f"(d[3]),"+f"(d[4]),"+f"(d[5]),"+f"(d[6]),"+f"(d[7]),"+f"(d[8]),"+f"(d[9]),"+f"(d[10]),"+f"(d[11]),"+f"(d[12]),"+f"(d[13]),"+f"(d[14]),"+f"(d[15]),"+f"(d[16]),"+f"(d[17]),"+f"(d[18]),"+f"(d[19]),"+f"(d[20]),"+f"(d[21]),"+f"(d[22]),"+f"(d[23]),"+f"(d[24]),"+f"(d[25]),"+f"(d[26]),"+f"(d[27]),"+f"(d[28]),"+f"(d[29]),"+f"(d[30]),"+f"(d[31]),"+f"(d[32]),"+f"(d[33]),"+f"(d[34]),"+f"(d[35]),"+f"(d[36]),"+f"(d[37]),"+f"(d[38]),"+f"(d[39]),"+f"(d[40]),"+f"(d[41]),"+f"(d[42]),"+f"(d[43]),"+f"(d[44]),"+f"(d[45]),"+f"(d[46]),"+f"(d[47]),"+f"(d[48]),"+f"(d[49]),"+f"(d[50]),"+f"(d[51]),"+f"(d[52]),"+f"(d[53]),"+f"(d[54]),"+f"(d[55]),"+f"(d[56]),"+f"(d[57]),"+f"(d[58]),"+f"(d[59]),"+f"(d[60]),"+f"(d[61]),"+f"(d[62]),"+f"(d[63])
    : "l"(da), "l"(db), "r"(sc));
}

template <int BN> struct WG;
template <> struct WG<256> { static __device__ __forceinline__ void mma(float (&d)[128], uint64_t a, uint64_t b, int sc) { wgmma_ss_n256_tb1(d, a, b, sc); } };
template <> struct WG<128> { static __device__ __forceinline__ void mma(float (&d)[64], uint64_t a, uint64_t b, int sc) { wgmma_ss_n128_tb1(d, a, b, sc); } };

struct GemmMaps { CUtensorMap a, b[3], c; };
template <int BN, int STAGES>
__global__ void __cluster_dims__(2, 1, 1) __launch_bounds__(384, 1)
gemm_kernel(const __grid_constant__ GemmMaps maps, int tilesM, int tilesN, int kblocks, int nPerB, int clearX) {
  extern __shared__ __align__(1024) uint8_t smem_raw[];
  constexpr int STAGE_BYTES = 16384 + BN * 128;
  constexpr int NBOX = BN / 64;
  const uint32_t sbase = (smem_u32(smem_raw) + 1023) & ~1023u;
  const uint32_t sEpi = sbase + STAGES * STAGE_BYTES;
  const uint32_t sBar = sEpi + 32768;
  const int warp = threadIdx.x >> 5, lane = threadIdx.x & 31, wg = warp >> 2;
  uint32_t crank; asm("mov.u32 %0, %%cluster_ctarank;" : "=r"(crank));
  if (threadIdx.x == 0) {
    for (int i = 0; i < STAGES; i++) { mbar_init(sBar + 8 * i, 1); mbar_init(sBar + 8 * (STAGES + i), 4); }
    asm volatile("fence.mbarrier_init.release.cluster;" ::: "memory");
  }
  if (clearX) {
    uint4* p = g_xraw;
    for (int i = blockIdx.x * 384 + threadIdx.x; i < (int)(sizeof(g_xraw) / 16); i += gridDim.x * 384) p[i] = make_uint4(0, 0, 0, 0);
  }
  asm volatile("barrier.cluster.arrive.release.aligned; barrier.cluster.wait.acquire.aligned;" ::: "memory");
  const int npairs = (tilesM >> 1) * tilesN, pair0 = blockIdx.x >> 1, pstep = gridDim.x >> 1;
  if (wg == 2) {
    asm volatile("setmaxnreg.dec.sync.aligned.u32 40;");
    if (warp == 8 && lane == 0) {
      int st = 0, ph = 1;
      for (int p = pair0; p < npairs; p += pstep) {
        const int tm = (p % (tilesM >> 1)) * 2 + crank, tn = p / (tilesM >> 1);
        const CUtensorMap* mb = &maps.b[tn / nPerB];
        const int n0 = (tn % nPerB) * BN;
        for (int kb = 0; kb < kblocks; kb++) {
          mbar_wait(sBar + 8 * (STAGES + st), ph);
          const uint32_t a = sbase + st * STAGE_BYTES, full = sBar + 8 * st;
          mbar_expect_tx(full, STAGE_BYTES);
          tma2d(a, &maps.a, kb * 64, tm * 128, full);
#pragma unroll
          for (int i = 0; i < NBOX / 2; i++) {
            const int bx = crank * (NBOX / 2) + i;
            tma2d_mc(a + 16384 + bx * 8192, mb, n0 + bx * 64, kb * 64, full, (uint16_t)3);
          }
          if (++st == STAGES) { st = 0; ph ^= 1; }
        }
      }
      for (int i = 0; i < STAGES; i++) { mbar_wait(sBar + 8 * (STAGES + st), ph); if (++st == STAGES) { st = 0; ph ^= 1; } }
    }
  } else {
    asm volatile("setmaxnreg.inc.sync.aligned.u32 232;");
    int st = 0, ph = 0;
    float acc[BN / 2];
    const uint64_t descA0 = (uint64_t)(((sbase + wg * 8192) & 0x3FFFF) >> 4) | (1ull << 16) | (64ull << 32) | (1ull << 62);
    const uint64_t descB0 = (uint64_t)(((sbase + 16384) & 0x3FFFF) >> 4) | (512ull << 16) | (64ull << 32) | (1ull << 62);
    const uint32_t epi = sEpi + wg * 16384;
    for (int p = pair0; p < npairs; p += pstep) {
      const int tm = (p % (tilesM >> 1)) * 2 + crank, tn = p / (tilesM >> 1);
      int prev = -1;
      for (int kb = 0; kb < kblocks; kb++) {
        mbar_wait(sBar + 8 * st, ph);
        wg_fence();
        const uint64_t so = (uint64_t)(st * (STAGE_BYTES >> 4));
#pragma unroll
        for (int k = 0; k < 4; k++) WG<BN>::mma(acc, descA0 + so + k * 2, descB0 + so + k * 128, kb | k);
        wg_commit();
        if (prev >= 0) {
          wg_wait<1>();
          if ((threadIdx.x & 127) < 2) mbar_arrive_cluster(sBar + 8 * (STAGES + prev), threadIdx.x & 1);
        }
        prev = st;
        if (++st == STAGES) { st = 0; ph ^= 1; }
      }
      wg_wait<0>();
      if ((threadIdx.x & 127) < 2) mbar_arrive_cluster(sBar + 8 * (STAGES + prev), threadIdx.x & 1);
#pragma unroll
      for (int r = 0; r < BN / 128; r++) {
        if ((threadIdx.x & 127) == 0) asm volatile("cp.async.bulk.wait_group.read 0;" ::: "memory");
        bar_sync(1 + wg, 128);
        const int row = (warp & 3) * 16 + (lane & 15);
#pragma unroll
        for (int i = 0; i < 8; i++) {
          const int c = 2 * (i & 3) + (lane >> 4);
          const float* q = &acc[r * 64 + i * 8];
          stsm4(epi + (i >> 2) * 8192 + row * 128 + ((c ^ (row & 7)) << 4), pack2(q[0], q[1]), pack2(q[2], q[3]), pack2(q[4], q[5]), pack2(q[6], q[7]));
        }
        fence_async();
        bar_sync(1 + wg, 128);
        if ((threadIdx.x & 127) == 0) {
          tma2d_store(&maps.c, epi, tn * BN + r * 128, tm * 128 + wg * 64);
          tma2d_store(&maps.c, epi + 8192, tn * BN + r * 128 + 64, tm * 128 + wg * 64);
          asm volatile("cp.async.bulk.commit_group;" ::: "memory");
        }
      }
    }
    if ((threadIdx.x & 127) == 0) asm volatile("cp.async.bulk.wait_group 0;" ::: "memory");
  }
}

struct Dft { uint32_t m[2][2][2][4]; };
template <bool P4> __device__ __forceinline__ int fidx(int tile, int x) { return P4 ? 4 * (x >> 1) + 2 * (tile & 1) + (x & 1) + 16 * (tile >> 1) : x + 8 * tile; }
__device__ __forceinline__ float2 cis(int k, int n) {
  k &= n - 1; if (2 * k > n) k -= n;
  const float a = (float)k * (6.283185307179586f / (float)n);
  return make_float2(__cosf(a), __sinf(a));
}
template <bool OUT4> __device__ __forceinline__ void make_dft(Dft& D, int g, int t) {
#pragma unroll
  for (int q = 0; q < 16; q++) {
    const int b = q >> 3, u = (q >> 2) & 1, r = (q >> 1) & 1, v = q & 1;
    const float2 w = cis(fidx<OUT4>(v, g) * fidx<false>(2 * u + r, 2 * t + b), 32);
    D.m[b][u][0][q & 3] = pack2(w.x, w.y); D.m[b][u][1][q & 3] = pack2(-w.y, w.x);
  }
}
__device__ __forceinline__ void mma_dc(float (&d)[4], uint32_t a0, uint32_t a1, uint32_t a2, uint32_t a3, uint32_t b0, uint32_t b1, const float (&c)[4]) {
  asm("mma.sync.aligned.m16n8k16.row.col.f32.bf16.bf16.f32 {%0,%1,%2,%3}, {%4,%5,%6,%7}, {%8,%9}, {%10,%11,%12,%13};"
    : "=f"(d[0]), "=f"(d[1]), "=f"(d[2]), "=f"(d[3]) : "r"(a0), "r"(a1), "r"(a2), "r"(a3), "r"(b0), "r"(b1), "f"(c[0]), "f"(c[1]), "f"(c[2]), "f"(c[3])); }
__device__ __forceinline__ void dft_b(const Dft& D, const uint32_t (&x)[2][4], float (&o)[2][8]) {
#pragma unroll
  for (int ri = 0; ri < 2; ri++) {
    float z[4] = {0.f, 0.f, 0.f, 0.f}, e[4], p[4];
    mma_dc(e, D.m[0][0][ri][0], D.m[0][0][ri][1], D.m[0][0][ri][2], D.m[0][0][ri][3], x[0][0], x[0][1], z);
    mma_dc(e, D.m[0][1][ri][0], D.m[0][1][ri][1], D.m[0][1][ri][2], D.m[0][1][ri][3], x[0][2], x[0][3], e);
    mma_dc(p, D.m[1][0][ri][0], D.m[1][0][ri][1], D.m[1][0][ri][2], D.m[1][0][ri][3], x[1][0], x[1][1], e);
    mma_dc(p, D.m[1][1][ri][0], D.m[1][1][ri][1], D.m[1][1][ri][2], D.m[1][1][ri][3], x[1][2], x[1][3], p);
#pragma unroll
    for (int q = 0; q < 4; q++) { o[ri][q] = p[q]; o[ri][4 + q] = fmaf(2.f, e[q], -p[q]); }
  }
}
__device__ __forceinline__ void dft_a(const uint32_t (&m)[2][2][4], const uint32_t (&x0)[2][4], const uint32_t (&x1)[2][4], float (&o)[2][8]) {
#pragma unroll
  for (int ri = 0; ri < 2; ri++) {
    float z[4] = {0.f, 0.f, 0.f, 0.f}, e[4], p[4];
    mma_dc(e, x0[0][0], x1[0][0], x0[0][1], x1[0][1], m[0][ri][0], m[0][ri][1], z);
    mma_dc(e, x0[0][2], x1[0][2], x0[0][3], x1[0][3], m[0][ri][2], m[0][ri][3], e);
    mma_dc(p, x0[1][0], x1[1][0], x0[1][1], x1[1][1], m[1][ri][0], m[1][ri][1], e);
    mma_dc(p, x0[1][2], x1[1][2], x0[1][3], x1[1][3], m[1][ri][2], m[1][ri][3], p);
#pragma unroll
    for (int q = 0; q < 4; q++) { o[ri][q] = p[q]; o[ri][4 + q] = fmaf(2.f, e[q], -p[q]); }
  }
}
__device__ __forceinline__ uint32_t twid(float re, float im, float c, float s) { return pack2(fmaf(re, c, im * s), fmaf(im, c, -re * s)); }
__device__ __forceinline__ void cpa16(uint32_t d, const void* s) { asm volatile("cp.async.cg.shared.global [%0], [%1], 16;" :: "r"(d), "l"(s) : "memory"); }
__device__ __forceinline__ void sts32(uint32_t a, uint32_t x) { asm volatile("st.shared.u32 [%0], %1;" :: "r"(a), "r"(x) : "memory"); }
__device__ __forceinline__ void cpa_commit() { asm volatile("cp.async.commit_group;" ::: "memory"); }
template <int N> __device__ __forceinline__ void cpa_wait() { asm volatile("cp.async.wait_group %0;" :: "n"(N) : "memory"); }
__device__ __forceinline__ uint32_t lds32(uint32_t a) { uint32_t r; asm volatile("ld.shared.u32 %0, [%1];" : "=r"(r) : "r"(a) : "memory"); return r; }
#define FMID 0
constexpr int F_TP = 4112, F_TSZ = 8 * F_TP;

__device__ __forceinline__ uint32_t ldnc32(const void* p) { uint32_t v; asm volatile("ld.global.nc.b32 %0, [%1];" : "=r"(v) : "l"(p) : "memory"); return v; }
template <class F>
__device__ __forceinline__ void fft_wprep(const bf16* __restrict__ wr, const bf16* __restrict__ wi, int cta, F&& mid) {
  const int tid = threadIdx.x, g = (cta >> 1) & 7, c = (cta >> 4) & 3, t = 2 * (cta & 1) + (tid & 1);
  const int k0 = g + 8 * (cta >> 6) + 32 * (8 * c + 2 * t), l0 = (tid & ~1) + (g & 1);
  uint32_t a[4][4], b[4][4];
#pragma unroll
  for (int q = 0; q < 16; q++) {
    const int o = (k0 + 16 * (q >> 3) + 32 * ((q >> 1) & 1) + 1024 * (q & 1)) * 513 + l0 + 256 * ((q >> 2) & 1);
    a[q >> 2][q & 3] = ldnc32(wr + o);
    b[q >> 2][q & 3] = ldnc32(wi + o);
  }
  const int e = cta * 32 + (tid & 31), lh = (e >> 11) * 512, k = e & 2047, k2 = (k >> 5) & 31;
  uint32_t hz[4];
#pragma unroll
  for (int q = 0; q < 4; q++) asm volatile("ld.global.nc.u16 %0, [%1];" : "=r"(hz[q]) : "l"((q < 2 ? wr : wi) + (q & 1 ? (2048 - k) & 2047 : k) * 513 + lh) : "memory");
  mid();
  uint4* dst = g_wt + l0 * 512 + cta * 2 + (tid & 1);
#pragma unroll
  for (int q = 0; q < 8; q++) {
    const int hf = q >> 1, l = l0 + 256 * (hf & 1) + (q & 1);
    const uint32_t sel = (q & 1) ? 0x7632 : 0x5410;
    if (l & 511) dst[(256 * (hf & 1) + (q & 1)) * 512 + 256 * (q >> 2)] = make_uint4(__byte_perm(a[hf][0], b[hf][0], sel), __byte_perm(a[hf][1], b[hf][1], sel),
                                                                                   __byte_perm(a[hf][2], b[hf][2], sel), __byte_perm(a[hf][3], b[hf][3], sel));
  }
  if (tid < 32) reinterpret_cast<uint32_t*>(g_wt)[(64 * ((k >> 3) & 3) + 16 * (k2 >> 3) + 2 * (k & 7) + ((k2 >> 2) & 1)) * 8 + lh * 2048 + 2 * (k2 & 3) + (k >> 10)] =
      pack2(0.5f * (__uint_as_float(hz[0] << 16) + __uint_as_float(hz[1] << 16)), 0.5f * (__uint_as_float(hz[2] << 16) - __uint_as_float(hz[3] << 16)));
}

template <class F>
__device__ __forceinline__ void fft_rows_fwd(const bf16* __restrict__ x, const bf16* __restrict__ wr, const bf16* __restrict__ wi, uint32_t tb, int it, F&& mid) {
  const int warp = threadIdx.x >> 5, lane = threadIdx.x & 31, g = lane >> 2, t = lane & 3;
  const uint32_t in = tb + warp * 4096;
  const uint32_t f0 = in + (lane >> 3) * 256 + (((lane & 7) ^ (2 * (lane >> 3))) << 4);
  const bf16* src = x + ((256 * (warp & 3) + 64 * (warp >> 2) + 128 * (it & 1) + 32 * ((it >> 4) & 1) + 8 * (it >> 5) + ((it >> 1) & 7)) * 2048 + lane * 8);
#pragma unroll
  for (int q = 0; q < 8; q++) cpa16((f0 ^ ((q >> 2) * 144)) + (q & 3) * 1024, src + q * 256);
  cpa_commit();
  Dft D;
  float2 tw[4][8];
  fft_wprep(wr, wi, it, [&]() {
    if (FMID == 0) mid();
    make_dft<true>(D, g, t);
#pragma unroll
    for (int q = 0; q < 32; q++) {
      tw[q >> 3][q & 7] = cis(fidx<true>((q >> 1) & 3, g) * fidx<false>(q >> 3, 2 * t + (q & 1)), 1024);
      if (FMID) asm volatile("" : "+f"(tw[q >> 3][q & 7].x), "+f"(tw[q >> 3][q & 7].y) :: "memory");
    }
    if (FMID == 1) mid();
  });
  if (FMID == 2) mid();
  cpa_wait<0>(); __syncwarp();
  uint32_t a[4][2][4], y[4][2][4];
#pragma unroll
  for (int q = 0; q < 8; q++) ldsm4t(a[q & 3][q >> 2], (in + lane * 128 + ((lane & 7) << 4)) ^ (q << 4));
  float o[2][8];
#pragma unroll
  for (int i = 0; i < 4; i++) {
    dft_b(D, a[i], o);
#pragma unroll
    for (int q = 0; q < 8; q++) y[q >> 1][q & 1][i] = twid(o[0][q], o[1][q], tw[i][q].x, tw[i][q].y);
  }
  __syncthreads();
  const uint32_t w0 = tb + warp * F_TP + fidx<true>(0, g) * 128 + t * 16 + ((g & 1) << 6), wz = (g & 1) ? -64 : 64;
#pragma unroll
  for (int z = 0; z < 2; z++) {
    float o2[2][8];
    dft_b(D, y[2 * z], o); dft_b(D, y[2 * z + 1], o2);
#pragma unroll
    for (int i = 0; i < 4; i++) {
      const float sg = i < 2 ? 1.f : -1.f;
      sts128(w0 + z * wz + fidx<true>(i, 0) * 128, pack2(o[0][2 * i], sg * o[1][2 * i]), pack2(o[0][2 * i + 1], sg * o[1][2 * i + 1]),
             pack2(o2[0][2 * i], sg * o2[1][2 * i]), pack2(o2[0][2 * i + 1], sg * o2[1][2 * i + 1]));
    }
  }
  __syncthreads();
  const uint32_t ra = tb + (lane & 1) * 4 * F_TP + ((lane >> 1) + 16 * (warp ^ ((warp >> 1) & 1))) * 4;
  uint4* dst = g_y + (threadIdx.x >> 1) * 256 + (lane & 1) + it * 2;
#pragma unroll
  for (int q = 0; q < 8; q++) { const uint32_t r = ra + q * 512; dst[q * 32768] = make_uint4(lds32(r), lds32(r + F_TP), lds32(r + 2 * F_TP), lds32(r + 3 * F_TP)); }
}

__device__ __forceinline__ void fft_cols(uint32_t sb, int cta, int ncta) {
  const int warp = threadIdx.x >> 5, lane = threadIdx.x & 31, g = lane >> 2, t = lane & 3;
  const uint32_t in = sb + warp * 16384 + lane * 16, tab = sb + 131072 + lane * 16;
  auto fetch_y = [&](int l) {
#pragma unroll
    for (int q = 0; q < 16; q++) cpa16(in + q * 512, g_y + (q < 8 ? l : (1024 - l) & 1023) * 256 + (q & 7) * 32 + lane);
  };
  auto fetch_w = [&](int l) {
#pragma unroll
    for (int q = 0; q < 16; q++) cpa16(in + 8192 + q * 512, g_wt + l * 512 + q * 32 + lane);
  };
  const int l0 = cta * 8 + warp, dl = ncta * 8;
  if (l0 <= 512) fetch_y(l0);
  cpa_commit();
  if (l0 <= 512) fetch_w(l0);
  cpa_commit();
  Dft D; make_dft<false>(D, g, t);
#pragma unroll
  for (int q = 2 * warp; q < 2 * warp + 2; q++) {
    const int r = fidx<false>(q & 3, g), c = fidx<false>(q >> 2, 2 * t);
    const float2 w0 = cis(r * c, 1024), w1 = cis(r * c + r, 1024), p0 = cis(r + 32 * c, 2048), p1 = cis(r + 32 * c + 32, 2048);
    sts128(tab + q * 512, __float_as_uint(w0.x), __float_as_uint(w0.y), __float_as_uint(w1.x), __float_as_uint(w1.y));
    sts128(tab + 8192 + q * 512, __float_as_uint(p0.x), __float_as_uint(p0.y), __float_as_uint(p1.x), __float_as_uint(p1.y));
  }
  if (warp == 0) {
#pragma unroll
    for (int q = 0; q < 8; q++) {
      const int v = q >> 2, b = (q >> 1) & 1, ri = q & 1;
      sts128(tab + 16384 + q * 512, D.m[b][0][ri][v], D.m[b][0][ri][v + 2], D.m[b][1][ri][v], D.m[b][1][ri][v + 2]);
    }
  }
  __syncthreads();
#pragma unroll 1
  for (int l = l0; l <= 512; l += dl) {
    uint32_t a[2][4][2][4], y[2][4][2][4];
    float o[2][2][8];
    cpa_wait<1>();
#pragma unroll
    for (int q = 0; q < 16; q++) lds128(a[q >> 3][(q >> 1) & 3][q & 1], in + q * 512);
    if (!(l & 511)) {
      const uint32_t m0 = l ? 0x80000000u : 0u;
#pragma unroll
      for (int q = 0; q < 32; q++) { a[0][q >> 3][(q >> 2) & 1][q & 3] ^= m0; a[1][q >> 3][(q >> 2) & 1][q & 3] ^= m0 ^ 0x80000000u; }
    }
    auto first = [&]() {
#pragma unroll
      for (int i = 0; i < 4; i++) {
        dft_b(D, a[0][i], o[0]); dft_b(D, a[1][i], o[1]);
#pragma unroll
        for (int r = 0; r < 4; r++) {
          const float4 w = lds128f(tab + (4 * i + r) * 512);
#pragma unroll
          for (int s = 0; s < 2; s++) {
            y[s][r][0][i] = twid(o[s][0][2 * r], o[s][1][2 * r], w.x, w.y);
            y[s][r][1][i] = twid(o[s][0][2 * r + 1], o[s][1][2 * r + 1], w.z, w.w);
          }
        }
      }
    };
    first();
    if (l + dl <= 512) fetch_y(l + dl);
    cpa_commit();
    cpa_wait<1>();
#pragma unroll
    for (int zv = 0; zv < 4; zv++) {
      const int z = zv >> 1, v = zv & 1;
      uint32_t m[2][2][4];
#pragma unroll
      for (int q = 0; q < 4; q++) lds128(m[q >> 1][q & 1], tab + 16384 + (4 * v + q) * 512);
      dft_a(m, y[0][2 * z], y[0][2 * z + 1], o[0]); dft_a(m, y[1][2 * z], y[1][2 * z + 1], o[1]);
#pragma unroll
      for (int q = 0; q < 4; q++) {
        const int i = 2 * z + (q & 1), c = v + (q & 2);
        uint32_t w[4]; lds128(w, in + 8192 + (4 * i + c) * 512);
        const float4 ph = lds128f(tab + 8192 + (4 * c + i) * 512);
#pragma unroll
        for (int b = 0; b < 2; b++) {
          const float cs = b ? ph.z : ph.x, sn = b ? ph.w : ph.y;
          const float r1 = __uint_as_float(w[2 * b] << 16), i1 = __uint_as_float(w[2 * b] & 0xFFFF0000u);
          const float r2 = __uint_as_float(w[2 * b + 1] << 16), i2 = __uint_as_float(w[2 * b + 1] & 0xFFFF0000u);
          const float Sr = r1 + r2, Si = i1 + i2, Dr = r1 - r2, Di = i1 - i2;
          const float ar = fmaf(-Dr, sn, Sr), ai = fmaf(-Di, sn, Si), dr = fmaf(Dr, sn, Sr), di = fmaf(Di, sn, Si), br = -Di * cs, bi = Dr * cs;
          const float Ar = o[0][0][2 * q + b], Ai = o[0][1][2 * q + b], Br = o[1][0][2 * q + b], Bi = o[1][1][2 * q + b];
          a[0][i][b][c] = pack2(fmaf(ar, Ai, fmaf(ai, Ar, fmaf(br, Bi, bi * Br))), fmaf(ar, Ar, fmaf(-ai, Ai, fmaf(br, Br, -bi * Bi))));
          a[1][i][b][c] = pack2(fmaf(dr, Bi, fmaf(di, Br, fmaf(-br, Ai, -bi * Ar))), fmaf(dr, Br, fmaf(-di, Bi, fmaf(-br, Ar, bi * Ai))));
        }
      }
    }
    if (l + dl <= 512) fetch_w(l + dl);
    cpa_commit();
    first();
#pragma unroll
    for (int s = 0; s < 2; s++) {
      uint4* dst = g_y + (s ? (1024 - l) & 1023 : l) * 256 + lane;
      const float sg = s ? -1.f : 1.f;
#pragma unroll
      for (int i = 0; i < 4; i++) {
        dft_b(D, y[s][i], o[0]);
#pragma unroll
        for (int b = 0; b < 2; b++)
          dst[(2 * i + b) * 32] = make_uint4(pack2(sg * o[0][0][b], o[0][1][b]), pack2(sg * o[0][0][2 + b], o[0][1][2 + b]),
                                             pack2(sg * o[0][0][4 + b], o[0][1][4 + b]), pack2(sg * o[0][0][6 + b], o[0][1][6 + b]));
      }
    }
  }
}

__device__ __forceinline__ void fft_rows_inv(const CUtensorMap* om, uint32_t sb, int cta, int ncta) {
  const int warp = threadIdx.x >> 5, lane = threadIdx.x & 31, g = lane >> 2, t = lane & 3, wg = warp >> 2, w4 = warp & 3;
  const uint32_t tb = sb + 32768 + wg * 2 * F_TSZ;
  const uint4* src = g_y + pin((256 * ((lane >> 1) & 3) + 64 * (lane >> 3) + 8 * w4) * 256 + (lane & 1));
  const uint32_t wa = pin(tb + (lane & 1) * 4 * F_TP + w4 * 1024 + (lane >> 1) * 4);
  uint4 pf[8];
  auto fetch = [&](int it, int hf) {
#pragma unroll
    for (int q = 0; q < 8; q++) pf[q] = __ldcg(src + (it * 2 + hf * 8192) + q * 256);
  };
  auto put = [&](uint32_t off) {
#pragma unroll
    for (int q = 0; q < 8; q++) {
      sts32(wa + off + q * 64, pf[q].x); sts32(wa + off + q * 64 + F_TP, pf[q].y);
      sts32(wa + off + q * 64 + 2 * F_TP, pf[q].z); sts32(wa + off + q * 64 + 3 * F_TP, pf[q].w);
    }
  };
  const int it0 = 2 * cta + wg;
  if (it0 >= 128) return;
  fetch(it0, 0); put(0); fetch(it0, 1); put(512);
  Dft D; make_dft<false>(D, g, t);
  float2 tw[4][8];
#pragma unroll
  for (int q = 0; q < 32; q++) {
    tw[q >> 3][q & 7] = cis(fidx<false>((q >> 1) & 3, g) * fidx<false>(q >> 3, 2 * t + (q & 1)), 1024);
    tw[q >> 3][q & 7].x *= 1.f / 2097152.f; tw[q >> 3][q & 7].y *= 1.f / 2097152.f;
  }
  const uint32_t la = pin(tb + w4 * F_TP + lane * 16), ob = uni(sb + warp * 4096);
  const uint32_t oa = pin(ob + (lane >> 1) * 128 + (((4 * (lane & 1)) ^ ((lane >> 1) & 7)) << 4));
#pragma unroll 1
  for (int n = 0;; n++) {
    const int it = it0 + (n >> 1) * 2 * ncta, hf = n & 1, buf = (n >> 1) & 1;
    if (it >= 128) break;
    if (!hf) bar_sync(1 + wg, 128);
    uint32_t a[4][2][4], y[4][2][4];
#pragma unroll
    for (int q = 0; q < 8; q++) lds128(a[q >> 1][q & 1], la + buf * F_TSZ + hf * 4 * F_TP + q * 512);
    fetch(min(it + 2 * ncta, 127), hf);
    float o[2][8];
#pragma unroll
    for (int i = 0; i < 4; i++) {
      dft_b(D, a[i], o);
#pragma unroll
      for (int q = 0; q < 8; q++) y[q >> 1][q & 1][i] = twid(o[0][q], o[1][q], tw[i][q].x, tw[i][q].y);
    }
    if (lane == 0) asm volatile("cp.async.bulk.wait_group.read 0;" ::: "memory");
    __syncwarp();
#pragma unroll
    for (int c = 0; c < 4; c++) {
      dft_b(D, y[c], o);
#pragma unroll
      for (int ri = 0; ri < 2; ri++)
        stsm4((oa ^ (c << 4)) + (1 - ri) * 2048, pack2(o[ri][0], o[ri][1]), pack2(o[ri][2], o[ri][3]), pack2(o[ri][4], o[ri][5]), pack2(o[ri][6], o[ri][7]));
    }
    fence_async();
    __syncwarp();
    if (lane == 0) {
      const int m = 256 * w4 + 32 * ((it >> 1) & 7) + 8 * (it >> 5) + 4 * (it & 1) + 2 * hf + ((it >> 4) & 1);
      asm volatile("cp.async.bulk.tensor.3d.global.shared::cta.bulk_group [%0, {0, 0, %2}], [%1];" :: "l"(om), "r"(ob), "r"(2 * m) : "memory");
      asm volatile("cp.async.bulk.commit_group;" ::: "memory");
    }
    put((buf ^ 1) * F_TSZ + hf * 512);
  }
  if (lane == 0) asm volatile("cp.async.bulk.wait_group 0;" ::: "memory");
}
__device__ __forceinline__ void grid_arrive(unsigned* ctr) {
  __syncthreads();
  if (threadIdx.x == 0) { __threadfence(); atomicAdd(ctr, 1u); }
}
__device__ __forceinline__ void grid_wait(unsigned* ctr, unsigned n) {
  if (threadIdx.x == 0) {
    int it = 0;
    while (*reinterpret_cast<volatile unsigned*>(ctr) < n) { __nanosleep(200); if (++it > SPIN_LIMIT) { g_err = 3; break; } }
    __threadfence();
  }
  __syncthreads();
}

struct RecMaps { CUtensorMap wq, wk, wv, wo, x, k, q, v, fo; };
#define NSW 16
#define EXP 0
#define NPB 2
#define NPC 4
#define WOP 2
#define HOME 3
#define DL0 14
#define PD1 4
#define NE4 6
#define NE6 0
#define NA4 14
#define NA6 18
#define NB1 24
#define TQL 7
#define NQ 8
#define TQP (NQ - 1)
#define OXPOS 4
#define KVPOS 2
#define NK0 0
#define FLPOS 1
#define XWPOS 10
#define FSPOS 28
#define RL0 4
#define RLS 6
#define RLB 4
#define VL0 3
#define RI 9
#define RJ 8
#define NPRE 20
#define PFD 4
#define PD0 4
#define VB NV0
#define NPA 0
#define N1 16
#define DL1 16
#define PACE 0
#define RE0 0
#define RE1 0
#define RP1 23
#define UNP 1
#define X2 2
#define X3 2
#define SPOS 2
#ifndef NV0
#define NV0 4
#endif
#define TGP 3
#define FENP 0
#define LW0 8
#define X1 4
#define X0 4
constexpr int R_WO = 0, R_X = 65536, R_MEM = 131072, R_WC = 147456, R_RED = R_WC + NSW * 2048, R_O = R_RED, R_S = R_O + 2048, R_P = R_S + 3072, R_STAGE = R_P + 2048,
              R_K = R_STAGE + 8192, R_Q = R_K + 8192, R_V = R_Q + 2048, R_ID = R_V + 16384, R_T = R_ID + 512, R_DST = R_T + 512, R_RD = R_DST + 2048, R_BAR = R_RD + 2048, R_TS = R_BAR + 128,
              R_TOTAL = R_TS;
#define TS(i)
#define LOG(i, v)
constexpr int B_KV = R_BAR, B_W = R_BAR + 8, B_X = R_BAR + 80, B_PK = R_BAR + 24, B_C = R_BAR + 32, B_B = R_BAR + 40, B_DUE = R_BAR + 48, B_ONE = R_BAR + 64;
#define DLY_A 150
#define DLY_V 150
#define DLY_C 200
#define DLY_L 90
#define NS_B 1088
#define NS_C 1728
#define NS_P 2688
#define NS_V 128
#define NS_F 896
#define NS_K 128
#define NS_M 32
#define NS_X 128
#define NS_Z 192
#define NS_Y 704
#define NS_PEN 1024
__device__ __forceinline__ float rcp(float x) { float r; asm("rcp.approx.ftz.f32 %0, %1;" : "=f"(r) : "f"(x)); return r; }
__device__ __forceinline__ uint32_t movm(uint32_t a) { uint32_t d; asm volatile("movmatrix.sync.aligned.m8n8.trans.b16 %0, %1;" : "=r"(d) : "r"(a)); return d; }
__device__ __forceinline__ uint32_t hadd2(uint32_t a, uint32_t b) { uint32_t d; asm("add.rn.bf16x2 %0, %1, %2;" : "=r"(d) : "r"(a), "r"(b)); return d; }
__device__ __forceinline__ void mma_a(float (&d)[4], const uint32_t (&a)[4], uint32_t b0, uint32_t b1) { mma16816(d, a[0], a[1], a[2], a[3], b0, b1); }
__device__ __forceinline__ bool elect() {
  uint32_t p; asm volatile("{.reg .pred p; elect.sync _|p, 0xffffffff; selp.u32 %0, 1, 0, p;}" : "=r"(p)); return p; }
__device__ __forceinline__ void tma3d(uint32_t dst, const CUtensorMap* m, int c1, int c2, uint32_t bar) {
  asm volatile("cp.async.bulk.tensor.3d.shared::cluster.global.mbarrier::complete_tx::bytes [%0], [%1, {0, %3, %4}], [%2];"
    :: "r"(dst), "l"(m), "r"(bar), "r"(c1), "r"(c2) : "memory"); }
__device__ __forceinline__ void tma4d(uint32_t dst, const CUtensorMap* m, int c1, int c2, uint32_t bar) {
  asm volatile("cp.async.bulk.tensor.4d.shared::cluster.global.mbarrier::complete_tx::bytes [%0], [%1, {0, %3, %4, 0}], [%2];"
    :: "r"(dst), "l"(m), "r"(bar), "r"(c1), "r"(c2) : "memory"); }
template <int OFF, int ACC>
__device__ __forceinline__ void wg_rs32(float (&d)[16], const uint32_t (&a)[4], uint32_t db) {
  if (ACC)
    asm volatile("{.reg .b64 db; .reg .b32 lo; add.u32 lo, %20, %21; mov.b64 db, {lo, 0x40000040};\n"
      "wgmma.mma_async.sync.aligned.m64n32k16.f32.bf16.bf16 {%0,%1,%2,%3,%4,%5,%6,%7,%8,%9,%10,%11,%12,%13,%14,%15}, {%16,%17,%18,%19}, db, 1, 1, 1, 0;}"
      : "+f"(d[0]), "+f"(d[1]), "+f"(d[2]), "+f"(d[3]), "+f"(d[4]), "+f"(d[5]), "+f"(d[6]), "+f"(d[7]), "+f"(d[8]), "+f"(d[9]), "+f"(d[10]), "+f"(d[11]), "+f"(d[12]), "+f"(d[13]), "+f"(d[14]), "+f"(d[15])
      : "r"(a[0]), "r"(a[1]), "r"(a[2]), "r"(a[3]), "r"(db), "n"(OFF));
  else
    asm volatile("{.reg .b64 db; .reg .b32 lo; add.u32 lo, %20, %21; mov.b64 db, {lo, 0x40000040};\n"
      "wgmma.mma_async.sync.aligned.m64n32k16.f32.bf16.bf16 {%0,%1,%2,%3,%4,%5,%6,%7,%8,%9,%10,%11,%12,%13,%14,%15}, {%16,%17,%18,%19}, db, 0, 1, 1, 0;}"
      : "=f"(d[0]), "=f"(d[1]), "=f"(d[2]), "=f"(d[3]), "=f"(d[4]), "=f"(d[5]), "=f"(d[6]), "=f"(d[7]), "=f"(d[8]), "=f"(d[9]), "=f"(d[10]), "=f"(d[11]), "=f"(d[12]), "=f"(d[13]), "=f"(d[14]), "=f"(d[15])
      : "r"(a[0]), "r"(a[1]), "r"(a[2]), "r"(a[3]), "r"(db), "n"(OFF));
}
template <int I> using IC = std::integral_constant<int, I>;
template <int I, int N, class F> __device__ __forceinline__ void sfor(F&& f) {
  if constexpr (I < N) { f(std::integral_constant<int, I>{}); sfor<I + 1, N>(f); }
}
__device__ __forceinline__ void keep(float (&d)[16]) {
  asm volatile("" : "+f"(d[0]), "+f"(d[1]), "+f"(d[2]), "+f"(d[3]), "+f"(d[4]), "+f"(d[5]), "+f"(d[6]), "+f"(d[7]),
      "+f"(d[8]), "+f"(d[9]), "+f"(d[10]), "+f"(d[11]), "+f"(d[12]), "+f"(d[13]), "+f"(d[14]), "+f"(d[15]) :: "memory");
}

template <int N, int S2 = 1024> __device__ __forceinline__ void ldx(uint32_t (&v)[N][4], const uint8_t* p) {
#pragma unroll
  for (int k = 0; k < 2 * N; k++) {
    const int i = k;
    asm volatile("ld.relaxed.gpu.global.v2.b32 {%0,%1}, [%2];" : "=r"(v[i >> 1][2 * (i & 1)]), "=r"(v[i >> 1][2 * (i & 1) + 1]) : "l"(p + (i & 3) * 256 + (i >> 2) * S2) : "memory");
  }
}
__device__ __forceinline__ uint32_t dif2(uint32_t a, uint32_t b, uint32_t tag) { uint32_t r; asm("lop3.b32 %0, %1, %2, %3, 0x7e;" : "=r"(r) : "r"(a), "r"(b), "r"(tag)); return r; }
__device__ __forceinline__ uint32_t dif2v(uint32_t a, uint32_t b, uint32_t tag) { uint32_t r; asm volatile("lop3.b32 %0, %1, %2, %3, 0x7e;" : "=r"(r) : "r"(a), "r"(b), "r"(tag)); return r; }
__device__ __forceinline__ uint32_t or3(uint32_t a, uint32_t b, uint32_t c) { uint32_t r; asm("lop3.b32 %0, %1, %2, %3, 0xfe;" : "=r"(r) : "r"(a), "r"(b), "r"(c)); return r; }
__device__ __forceinline__ uint32_t after(uint32_t x, float f, uint32_t z) { uint32_t r; asm("lop3.b32 %0, %1, %2, %3, 0xea;" : "=r"(r) : "r"(__float_as_uint(f)), "r"(z), "r"(x)); return r; }
__device__ __forceinline__ bool any_bit(uint32_t a, uint32_t b, uint32_t m) {
  uint32_t r; asm("lop3.b32 %0, %1, %2, %3, 0xa8;" : "=r"(r) : "r"(a), "r"(b), "r"(m)); return __any_sync(0xffffffffu, r); }
template <int W, int N> __device__ __forceinline__ bool stale(const uint32_t (&v)[N][4], uint32_t tag) {
  uint32_t x = dif2(v[0][0], v[0][2], tag);
  if (N == 4) x = or3(x, dif2(v[1][0], v[1][2], tag), dif2(v[2 % N][0], v[2 % N][2], tag));
  return any_bit(x, dif2(v[N - 1][0], v[N - 1][2], tag), 1);
}
template <int W, int N, int S2 = 1024> __device__ __forceinline__ void retry(uint32_t (&v)[N][4], const uint8_t* p, uint32_t tag, int& it) {
#pragma unroll 1
  do { ldx<N, S2>(v, p); it += INC_A; } while (stale<W>(v, tag) && it < SPIN_LIMIT);
}
__device__ __forceinline__ void mma_h(float (&d)[4], const uint32_t (&a)[4], const uint32_t (&b)[4], int hf) { mma16816(d, a[0], a[1], a[2], a[3], b[2 * hf], b[2 * hf + 1]); }
__device__ __forceinline__ void sts128(uint32_t a, const uint32_t (&r)[4]) { sts128(a, r[0], r[1], r[2], r[3]); }
__device__ __forceinline__ void sts128f(uint32_t a, const float* r) { sts128(a, __float_as_uint(r[0]), __float_as_uint(r[1]), __float_as_uint(r[2]), __float_as_uint(r[3])); }
__device__ __forceinline__ void mbar_spin(uint32_t bar, uint32_t par, int& it) {
  asm volatile("{.reg .pred p; .reg .b32 par; mov.b32 par, %2;\nLOOP: mbarrier.try_wait.parity.shared::cta.b64 p, [%1], par; @p bra.uni DONE;\n"
               "add.s32 %0, %0, 1; setp.le.s32 p, %0, %3; @p bra.uni LOOP;\nDONE: }" : "+r"(it) : "r"(bar), "r"(par), "n"(SPIN_LIMIT) : "memory"); }
__device__ __forceinline__ void warp_arrive(uint32_t bar) {
  __syncwarp(); asm volatile("{.reg .pred p; elect.sync _|p, 0xffffffff; @p mbarrier.arrive.shared::cta.b64 _, [%0];}" :: "r"(bar) : "memory"); }
__device__ __forceinline__ void delay_until(unsigned t) {
  asm volatile("{.reg .pred p; .reg .b64 c; .reg .b32 lo, hi;\nLOOP: mov.u64 c, %%clock64; mov.b64 {lo, hi}, c; sub.s32 lo, lo, %0; setp.lt.s32 p, lo, 0; @p bra.uni LOOP;}" :: "r"(t) : "memory"); }
__device__ __forceinline__ void cut(int it) { asm volatile("{.reg .pred p; setp.lt.s32 p, %0, 0;\nL: @p st.volatile.shared.u32 [%0], %0; @p bra.uni L;}" :: "r"(it) : "memory"); }
__device__ __forceinline__ void zero(float (&c)[4][4]) {
#pragma unroll
  for (int i = 0; i < 4; i++) c[i][0] = c[i][1] = c[i][2] = c[i][3] = 0.f;
}

__device__ __forceinline__ void sched() { asm volatile("griddepcontrol.launch_dependents;" ::: "memory"); }
__device__ __forceinline__ const uint8_t* pinp(const uint8_t* p) { return reinterpret_cast<const uint8_t*>(__shfl_xor_sync(0xffffffffu, reinterpret_cast<unsigned long long>(p), 0)); }
__device__ __forceinline__ uint32_t bar_or(int id, uint32_t x) {
  uint32_t r; asm volatile("{.reg .pred p, q; setp.ne.u32 p, %2, 0; bar.red.or.pred q, %1, 256, p; selp.u32 %0, 1, 0, q;}" : "=r"(r) : "r"(id), "r"(x) : "memory"); return r; }
__device__ __forceinline__ void bar_sync_unless(int id, uint32_t x) { asm volatile("{.reg .pred p; setp.eq.u32 p, %1, 0; @p bar.sync %0, 256;}" :: "r"(id), "r"((uint32_t)x) : "memory"); }
__device__ __forceinline__ void bar_arrive_unless(int id, uint32_t x) { asm volatile("{.reg .pred p; setp.eq.u32 p, %1, 0; @p bar.arrive %0, 256;}" :: "r"(id), "r"((uint32_t)x) : "memory"); }
__device__ __forceinline__ void stsm2t(uint32_t a, uint32_t r0, uint32_t r1, uint32_t x) {
  asm volatile("{.reg .pred p; setp.eq.u32 p, %3, 0; @p stmatrix.sync.aligned.m8n8.x2.trans.shared.b16 [%0], {%1,%2};}" :: "r"(a), "r"(r0), "r"(r1), "r"((uint32_t)x) : "memory"); }
__device__ __forceinline__ uint32_t or_and(uint32_t a, uint32_t b, uint32_t m) { uint32_t r; asm("lop3.b32 %0, %1, %2, %3, 0xa8;" : "=r"(r) : "r"(a), "r"(b), "r"(m)); return r; }
#define rare(x) __builtin_expect(!!(x), 0)
__device__ __forceinline__ uint32_t gtime() { unsigned long long g; asm volatile("mov.u64 %0, %%globaltimer;" : "=l"(g) :: "memory"); return (uint32_t)g; }
__device__ __forceinline__ void wait_time(uint32_t t) {
  asm volatile("{.reg .pred p; .reg .b32 g; .reg .b64 c;\nLOOP: mov.u64 c, %%globaltimer; cvt.u32.u64 g, c; sub.s32 g, %0, g; setp.lt.u32 p, g, 16384; @p bra.uni LOOP;}" :: "r"(t - 1) : "memory"); }
__device__ __forceinline__ uint32_t ldx32(const void* p) { uint32_t v; asm volatile("ld.relaxed.gpu.global.b32 %0, [%1];" : "=r"(v) : "l"(p) : "memory"); return v; }
__device__ __forceinline__ void stx32(const void* p, uint32_t v) { asm volatile("st.relaxed.gpu.global.b32 [%0], %1;" :: "l"(p), "r"(v) : "memory"); }

__global__ void __launch_bounds__(256, 1)
rec_kernel(const __grid_constant__ RecMaps maps, const bf16* __restrict__ xin, const bf16* __restrict__ mem0, Xchg* const gx,
           const bf16* __restrict__ fx, const bf16* __restrict__ wr, const bf16* __restrict__ wi) {
  extern __shared__ __align__(1024) uint8_t smem_raw[];
  const uint32_t sb = smem_u32(smem_raw);
  int role = blockIdx.x;
  {
    uint32_t smid, nsm; asm volatile("mov.u32 %0, %%smid;" : "=r"(smid)); asm volatile("mov.u32 %0, %%nsmid;" : "=r"(nsm));
    const int p = smid >> 1, u = p - 32;
    if (nsm == gridDim.x)
      role = (smid & 1) + (p < 32 ? 4 * ((p & 7) + 8 * (p >> 4)) + 2 * ((p >> 3) & 1) : p < 60 ? 4 * (16 + u % 7 + 7 * (u / 14)) + 2 * ((u / 7) & 1)
                         : p < 62 ? 2 * p + 8 : 2 * p - 4);
    role = uni(role);
  }
  if (role >= 128) {
    grid_wait(&gx->ctr[33], 128);
    fft_cols(sb, role - 128, 4);
    grid_arrive(&gx->ctr[32]); grid_wait(&gx->ctr[32], 4);
    fft_rows_inv(&maps.fo, sb, role - 128, 4);
    return;
  }
  const int tid = threadIdx.x, warp = uni(tid >> 5), lane = tid & 31, wg = warp >> 2, w4 = warp & 3, g = lane >> 2, t = lane & 3;
  const int h = role >> 2, j = role & 3, jh = j & 1;
  uint32_t w[48][4];
  float aq[16], av[16];
  int it = 0;

#define PT(k)
  auto pf_wo = [&]() {
    for (int i = 0; i < 4; i++)
      asm volatile("cp.async.bulk.prefetch.tensor.2d.L2.global [%0, {%1, %2}];" :: "l"(&maps.wo), "r"(256 * j + 64 * i), "r"(h * DH) : "memory");
  };
  fft_rows_fwd(fx, wr, wi, sb + R_MEM + 49152, role, [&]() {
    if (tid == 224) {
      mbar_init(sb + B_KV, 1); mbar_init(sb + B_W, 1); mbar_init(sb + B_X, 1); mbar_init(sb + B_X + 8, 1); mbar_init(sb + B_X + 16, 1); mbar_init(sb + B_X + 24, 1); mbar_init(sb + B_C, 4); mbar_init(sb + B_PK, 4); mbar_init(sb + B_B, 1);
      asm volatile("fence.mbarrier_init.release.cluster;" ::: "memory");
      mbar_expect_tx(sb + B_W, 3 * 65536);
      for (int i = 0; i < 4; i++) {
        tma2d(sb + R_X + i * 16384, &maps.wq, h * DH + 32 * j, i * 256, sb + B_W);
        if (i < 3) tma2d(sb + R_MEM + i * 16384, &maps.wk, h * DH + 32 * j, i * 256, sb + B_W);
        else asm volatile("cp.async.bulk.prefetch.tensor.2d.L2.global [%0, {%1, %2}];" :: "l"(&maps.wk), "r"(h * DH + 32 * j), "r"(768) : "memory");
      }
      for (int i = 0; i < 2; i++) tma2d(sb + R_WO + i * 32768, &maps.wv, h * DH + 64 * (j >> 1), jh * 512 + i * 256, sb + B_W);
      if (PFD) asm volatile("cp.async.bulk.prefetch.L2.global [%0], 2048;" :: "l"(xin + role * DM) : "memory");
      else for (int i = 0; i < 4; i++) asm volatile("cp.async.bulk.prefetch.L2.global [%0], 8192;" :: "l"(xin + role * 16384 + i * 4096) : "memory");
      if (WOP == 0) pf_wo();
    }
    __syncwarp();
  });
  if (tid < 16) sts32(sb + R_T + tid * 4, ~0u);
  fence_async();
  PT(0);
  grid_arrive(&gx->ctr[33]);
  PT(1);
  if (tid == 224) { tma2d(sb + R_MEM + 49152, &maps.wk, h * DH + 32 * j, 768, sb + B_W); if (WOP == 1) pf_wo(); }
  __syncwarp();
  uint8_t* const xb = reinterpret_cast<uint8_t*>(gx);
  auto probe_at = [&](int n) { return xb + (n ? offsetof(Xchg, C) + w4 * 8192 + role * 32 : offsetof(Xchg, B) + role * 8192 + warp * 128); };
  if (lane < 8) stx128(probe_at(lane >> 2) + (lane & 2) * 2048 + (lane & 1) * 16, 0, 0, 0, 0);
  uint32_t m0[4][4];
#pragma unroll
  for (int i = 0; i < 16; i++) m0[i >> 2][i & 3] = ldnc32(mem0 + g * DM + 128 * warp + 8 * i + 2 * t);
  mbar_spin(sb + B_W, 0, it);
  PT(2);
  const int lrow = (lane & 7) + ((lane >> 4) << 3), lhi = (lane >> 3) & 1;
  const int kq = wg ? 3 - 3 * jh : 3 * jh;
  const uint32_t LW = lrow * 128 + ((lhi ^ (lane & 7)) << 4);
  {
    const int chunk = w4 < 2 ? w4 + 2 * lhi : 2 * (w4 & 1) + lhi;
    uint32_t a = sb + (w4 < 2 ? R_X : R_MEM) + kq * 16384 + lrow * 64 + ((chunk ^ ((lrow >> 1) & 3)) << 4);
#pragma unroll
    for (int i = 0; i < 16; i++) ldsm4t(w[i], a + i * 1024);
    const uint32_t st = wg ? 1024 : 2048, av0 = sb + R_WO + (LW ^ (w4 << 5));
    const uint32_t a1 = wg ? a + (2 * jh - 1) * 16384 : av0 + jh * 32768, a2 = wg ? a + (2 * jh - 1) * 32768 : av0 + (1 - jh) * 32768;
#pragma unroll
    for (int i = 0; i < 16; i++) { ldsm4t(w[16 + i], a1 + i * st); ldsm4t(w[32 + i], a2 + i * st); }
  }
  uint32_t L16 = pin(lane * 16);
  const uint32_t uW = uni(sb + w4 * 512), uWo = uni(sb + R_WO + w4 * 16384), uMem = uni(sb + R_MEM + kq * 4096);
  const uint32_t dX = uni(((sb + R_X + kq * 16384) >> 4) | 0x10000u);
  auto load_wo = [&](uint32_t (&d)[32][4], int i0, int i1) {
#pragma unroll
    for (int i = i0; i < i1; i++) lds128(d[i], uWo + L16 + (i & 1) * 512 + (i >> 4) * 1024 + (i & 14) * 1024);
  };
  auto issue_x = [&](int n, int k) {
    const uint32_t bar = sb + B_X + 8 * k, q = k ^ (3 - 3 * jh);
    mbar_expect_tx(bar, 16384); tma3d(sb + R_X + q * 16384, &maps.x, n * SEG, 4 * q, bar);
  };
  auto store_stage = [&](int n) {
    asm volatile("cp.async.bulk.global.shared::cta.bulk_group [%0], [%1], 8192; cp.async.bulk.commit_group;"
                 :: "l"(g_kqv[n & 3][role]), "r"(sb + R_STAGE) : "memory");
  };
  auto issue_kqv = [&](int n) {
    const int p = (n & 3) * 128 + 4 * h;
    mbar_expect_tx(sb + B_KV, 26624);
    tma3d(sb + R_K, &maps.k, 0, p, sb + B_KV); tma3d(sb + R_Q, &maps.q, 8 + 2 * j, p, sb + B_KV); tma3d(sb + R_V, &maps.v, 16, p, sb + B_KV);
  };
  auto fetch4k = [&](uint32_t dst, uint32_t off, uint32_t bar, uint32_t t) {
    asm volatile("{.reg .pred p, q; .reg .b32 g; .reg .b64 c; elect.sync _|q, 0xffffffff; @q mbarrier.arrive.expect_tx.shared::cta.b64 _, [%2], 4096;\n"
                 "LOOP: mov.u64 c, %%globaltimer; cvt.u32.u64 g, c; sub.s32 g, %3, g; setp.lt.u32 p, g, 16384; @p bra.uni LOOP;\n"
                 "@q cp.async.bulk.shared::cluster.global.mbarrier::complete_tx::bytes [%0], [%1], 4096, [%2];}" :: "r"(dst), "l"(xb + off), "r"(bar), "r"(t - 1) : "memory");
  };
  uint32_t uS;
  auto my_b = [&]() { return offsetof(Xchg, B) + role * 8192 + ((uS + ((uint32_t)it >> 31)) & 1) * 4096; };
  auto issue_c = [&](uint32_t t) { fetch4k(sb + R_MEM + w4 * 4096, offsetof(Xchg, C) + w4 * 8192 + ((uS + ((uint32_t)it >> 31)) & 4096), sb + B_C, t); };
  auto wait_x = [&](int n, int i) { if (!(EXP & 1) || n < 2) mbar_spin(sb + B_X + 8 * i, n & 1, it); };
#define PACED(d0) uint32_t dz = d0; const uint32_t z = (uint32_t)it >> 31; auto pace = [&]() { for (int k = 0; k < PACE; k++) { if (k & 1) asm("add.u32 %0, %0, %1;" : "+r"(dz) : "r"(z)); else asm("xor.b32 %0, %0, %1;" : "+r"(dz) : "r"(z)); } };
  auto project_v = [&](auto I0, auto I1, auto&& mid) {
    PACED(decltype(I0)::value < 16 ? dX : dX ^ 1024);
    wg_fence();
    sfor<decltype(I0)::value, decltype(I1)::value>([&](auto I) {
      constexpr int i = decltype(I)::value;
      mid(i);
      if (i == 16 && decltype(I0)::value < 16) dz ^= 1024;
      wg_rs32<((i >> 2) & 3) * 256 + (i & 3) * 2, (i > 0)>(av, w[16 + i], dz);
      pace();
    });
    wg_commit();
  };
  auto project_qk = [&](auto I0, auto I1, auto first, auto&& mid) {
    PACED((dX ^ (decltype(I0)::value >> 4 << 10)) + ((uint32_t)it >> 31));
    wg_fence();
    sfor<decltype(I0)::value, decltype(I1)::value>([&](auto I) {
      constexpr int i = decltype(I)::value;
      mid(i);
      wg_rs32<((i >> 2) & 3) * 256 + (i & 3) * 2, !decltype(first)::value || i != decltype(I0)::value>(aq, w[i], dz);
      pace();
    });
    wg_commit();
  };
  const uint32_t uP = uni(sb + R_X + 3 * jh * 16384 + w4 * 512);
  auto park = [&]() {
    bar_sync(1, 128);
#pragma unroll
    for (int i = 0; i < 4; i++) sts128f(uP + L16 + i * 2048, aq + 4 * i);
    warp_arrive(sb + B_PK);
  };
  auto unpark = [&]() {
#pragma unroll
    for (int i = 0; i < 4; i++) {
      const float4 p = lds128f(uP + L16 + i * 2048);
      av[4 * i] = p.x; av[4 * i + 1] = p.y; av[4 * i + 2] = p.z; av[4 * i + 3] = p.w;
    }
  };
  auto fin_qk = [&]() {
#pragma unroll
    for (int i = 0; i < 16; i++) aq[i] += av[i];
    const uint32_t a = sb + R_STAGE + (w4 < 2 ? 2048 + w4 * 128 : (w4 & 1) * 256) + (L16 & 112) + (L16 >> 7) * 512;
    stsm4t(a, pack2(aq[0], aq[1]), pack2(aq[4], aq[5]), pack2(aq[8], aq[9]), pack2(aq[12], aq[13]));
    stsm4t(a + (w4 < 2 ? 256 : 128), pack2(aq[2], aq[3]), pack2(aq[6], aq[7]), pack2(aq[10], aq[11]), pack2(aq[14], aq[15]));
  };
  auto fin_v = [&]() {
#pragma unroll
    for (int a = 0; a < 2; a++)
      sts128(sb + R_STAGE + 4096 + w4 * 1024 + a * 512 + L16, pack2(av[8 * a], av[8 * a + 1]), pack2(av[8 * a + 2], av[8 * a + 3]),
             pack2(av[8 * a + 4], av[8 * a + 5]), pack2(av[8 * a + 6], av[8 * a + 7]));
  };
  __syncthreads();
  if (tid == 224) {
#pragma unroll 1
    for (int i = 0; i < 4; i++) issue_x(0, i);
    mbar_expect_tx(sb + B_W, 65536);
    for (int i = 0; i < 4; i++) tma2d(sb + R_WO + i * 16384, &maps.wo, 256 * j + 64 * i, h * DH, sb + B_W);
  }
  __syncwarp();
  if (wg) {
#pragma unroll
    for (int i = 0; i < NSW; i++) sts128(uW + R_WC + L16 + i * 2048, w[i]);
  }
#pragma unroll
  for (int i = 0; i < 4; i++) sts128(sb + R_MEM + warp * 2048 + i * 512 + (g >> 1) * 128 + t * 32 + (g & 1) * 16, m0[i]);
  auto probe = [&](int n, int cnt) {
    if (lane == 0) {
#pragma unroll 1
      for (int i = role >> 7; i < cnt; i++) {
        const int k = (i ^ wg) & 1;
        const unsigned t0 = clk();
        uint32_t v; asm volatile("atom.relaxed.gpu.global.exch.b32 %0, [%1], 0;" : "=r"(v) : "l"(probe_at(n) + k * 4096) : "memory");
        if (v == 0) asm volatile("red.shared.min.u32 [%0], %1;" :: "r"(sb + R_T + (n ? w4 * 8 : 32) + k * 4), "r"(clk() - t0) : "memory");
      }
    }
    __syncwarp();
  };
#pragma unroll 1
  for (int n = 0; n < 2; n++) {
    probe(0, NPB);
    PT(3 + 3 * n);
    wait_x(n, 2);
    PT(4 + 3 * n);
    if (wg == 0) {
      wait_x(n, 3);
      project_qk(IC<0>{}, IC<16>{}, IC<1>{}, [](int) {});
      project_v(IC<0>{}, IC<32>{}, [](int) {});
      if (tid == 96 && n == 1) {
        asm volatile("cp.async.bulk.wait_group 0;" ::: "memory");
        __threadfence(); atomicAdd(&gx->ctr[h], 1u);
      }
      __syncwarp();
      wg_wait<0>(); keep(aq); keep(av);
      park();
      fin_v();
      fence_async();
    } else {
      wait_x(n, 0); wait_x(n, 1);
      project_qk(IC<32>{}, IC<48>{}, IC<1>{}, [](int) {});
      project_qk(IC<16>{}, IC<32>{}, IC<0>{}, [](int) {});
      project_qk(IC<0>{}, IC<16>{}, IC<0>{}, [](int) {});
      mbar_spin(sb + B_PK, n, it);
      unpark();
      wg_wait<0>(); keep(aq);
      fin_qk();
      fence_async();
    }
    __syncthreads();
    if (tid == 0 && n) stx32(&gx->S[role], 1 + (HOME & 2 && lds32(sb + R_T + 36) < lds32(sb + R_T + 32)));
    PT(5 + 3 * n);
    if (tid == 96 && n == 0) store_stage(0);
    if (tid == 128 && n == 0) {
#pragma unroll 1
      for (int i = 0; i < 4; i++) issue_x(1, i);
    }
    if (warp == 5 && n == 1) {
#pragma unroll 1
      while (__any_sync(0xffffffffu, ldx32(&gx->ctr[h]) < 4) && ++it < SPIN_LIMIT) {}
      __threadfence(); asm volatile("fence.proxy.async;" ::: "memory");
      if (elect()) issue_kqv(0);
    }
    __syncwarp();
  }
  mbar_spin(sb + B_W, 1, it);
  PT(9);
#pragma unroll
  for (int i = 0; i < 4; i++) {
    uint32_t f[4][4];
    const uint32_t a = sb + R_WO + warp * 8192 + i * 2048;
#pragma unroll
    for (int q = 0; q < 4; q++) ldsm4t(f[q], a + (LW ^ (q << 5)));
    __syncwarp();
#pragma unroll
    for (int q = 0; q < 4; q++) sts128(a + q * 512 + L16, f[q]);
  }
  probe(1, NPC);
  {
    const int o = 32 * w4 + 16 * wg + 4 * t + j;
    uint32_t v;
#pragma unroll 1
    while (__any_sync(0xffffffffu, (v = ldx32(&gx->S[o])) == 0) && ++it < SPIN_LIMIT) {}
    asm volatile("st.shared.u64 [%0], %1;" :: "r"(sb + R_DST + wg * 1024 + w4 * 256 + lane * 8), "l"(xb + offsetof(Xchg, B) + o * 8192 + (v >> 1) * 4096 + h * 128 + ((g ^ h) & 7) * 16) : "memory");
  }
  if (wg == 0) {
    const uint64_t cd = reinterpret_cast<uint64_t>(xb + (offsetof(Xchg, C) + j * 8192 + h * 128 + w4 * 32 + (L16 & 16) * 256 + (L16 & 64) / 4 + (L16 >> 7) * 4));
    sts128(uW + R_RD + L16, (uint32_t)cd, (uint32_t)(cd >> 32), sb + R_MEM + (L16 & 112) * 8 + (L16 >> 8) * 1024 + ((w4 * 32 + ((L16 >> 3) & 16)) ^ (L16 & 112)),
           (L16 >> 6) == (h & 3) * 2 + ((h >> 2) & 1) ? 0xFFFE0000u : 0xFFFFFFFFu);
  }
  if (tid == 0) sts32(sb + B_DUE + 8, gtime() & ~31u);
  PT(10);
  mbar_spin(sb + B_KV, 0, it);
  PT(11);
  if (tid < 4) sts32(sb + B_ONE + tid * 4, 0x3F803F80u);
  if (warp == 1) { const uint32_t e = g >> 1 == t ? 0x3F80u << (16 * (g & 1)) : 0u; sts128(sb + R_ID + L16, e, 0, 0, e); }
  __syncthreads();
  uS = uni((HOME & 1 ? lds32(sb + R_T + w4 * 8 + 4) < lds32(sb + R_T + w4 * 8) : j >> 1) * 4096 + (HOME & 2 && lds32(sb + R_T + 36) < lds32(sb + R_T + 32)));

  const float sc = 0.08838834764831845f * 1.4426950408889634f;
  uint8_t* const xa = xb + uni(h * 16384);
  const uint32_t uA = uni(wg ? (w4 >> 1) * 2048 + j * 512 + (w4 & 1) * 256 : 8192 + (4 * (j >> 1) + w4) * 512 + jh * 256);
  const uint32_t uP2 = uni(sb + R_P + w4 * 256);
  uint32_t nc = 1;
  uint32_t ma;
  const uint8_t* adst;
  auto pin_mem = [&]() { adst = pinp(xa + uA + L16 / 2); ma = pin(uMem + (L16 & 384) + (L16 & 48) * 2 + (L16 & 64) / 4); };
  pin_mem();

#pragma unroll 1
  for (int s = 0;; nc++) {
    const uint32_t tag = (s + 1) & 1;
    auto fresh = [&]() { L16 += (uint32_t)it >> 31; };
    auto get_due = [&]() { return lds32(sb + B_DUE + 4 + tag * 4); };
    float c[4][4], r4[4];
    auto fold = [&]() {
#pragma unroll
      for (int i = 0; i < 4; i++) r4[i] = ((c[0][i] + c[1][i]) + c[2][i]) + c[3][i];
    };
    auto mma4 = [&](int n, const uint32_t (&b0)[4], const uint32_t (&b1)[4]) {
      mma_h(c[0], w[n + 2], b1, 0); mma_h(c[1], w[n + 3], b1, 1); mma_h(c[2], w[n], b0, 0); mma_h(c[3], w[n + 1], b0, 1);
    };
    auto xpos = [&](int pos, int wp) {
      if ((pos == X0 || pos == X1 || pos == X2 || pos == X3) && warp == wp && s + 1 < NSEG && elect()) {
        const int z = (uint32_t)it >> 31;
        if (pos == X2) issue_x(s + 2, 2 + z);
        if (pos == X3) issue_x(s + 2, 3 + z);
        if (pos == X1) issue_x(s + 2, 1 + z);
        if (pos == X0) issue_x(s + 2, z);
      }
      __syncwarp();
    };
    if (wg == 0) {
      mbar_spin(sb + B_C, nc & 1, it);
      TS(13);
      uint32_t b[16][4], tg[4];
#pragma unroll
      for (int i = 0; i < PD0; i++) { lds128(b[i], ma + i * 512); __syncwarp(); }
      sched();
      zero(c);
#pragma unroll
      for (int i = 0; i < 8; i++) {
        const int k = i ^ 1;
        mma_h(c[0], w[2 * k], b[k], 0); mma_h(c[1], w[2 * k + 1], b[k], 1);
        if (i < 2 * NV0) { mma_h(c[2], w[16 + 2 * k], b[k], 0); mma_h(c[3], w[17 + 2 * k], b[k], 1); }
        sched();
        if ((i & 1) && i + PD0 < 9) { lds128(b[i + PD0 - 1], ma + (i + PD0 - 1) * 512); __syncwarp(); lds128(b[i + PD0], ma + (i + PD0) * 512); sched(); }
        if (i == TGP) {
          fresh();
#pragma unroll
          for (int k = 0; k < 4; k++) tg[k] = lds32((uW * 4 + L16) * 2 + (L16 >> 6) * 4 + (R_MEM + k * 1024 - 7 * sb));
          sched();
        }
      }
#pragma unroll
      for (int i = 0; i < 4; i++) { r4[i] = c[0][i] + c[1][i]; c[0][i] = c[1][i] = 0.f; }
      sts128f(uW + R_RED + L16, r4);
      TS(1);
      const uint32_t old = bar_or(4, (dif2(tg[0], tg[1], s) | dif2(tg[2], tg[3], s)) & (s > 0));
      TS(0);
#pragma unroll
      for (int i = 0; i < 2 * NV0; i++) { lds128(b[8 + i], (ma ^ 4096) + i * 512); __syncwarp(); }
      sched();
#pragma unroll
      for (int i = NV0; i < 8; i++) {
        if (VB && i == VB) bar_sync(7, 256);
        mma4(16 + 4 * i, b[2 * i], b[2 * i + 1]);
        if (i < 7) sched();
        if (i < 4) { lds128(b[8 + 2 * i], (ma ^ 4096) + i * 1024); __syncwarp(); lds128(b[9 + 2 * i], (ma ^ 4096) + i * 1024 + 512); sched(); }
      }
      fold();
      asm volatile("{.reg .pred p; setp.eq.u32 p, %3, 0; @p st.relaxed.gpu.global.v2.b32 [%0], {%1,%2};}" :: "l"(adst), "r"((pack2(r4[0], r4[1]) & ~1u) | tag), "r"(pack2(r4[2], r4[3])), "r"(old) : "memory");
      sched();
      const unsigned tpub = clk();
      if (__any_sync(0xffffffffu, old) && nc < NC_MAX) {
        bar_sync(3, 256);
        issue_c(gtime());
        continue;
      }
      TS(3);
      xpos(0, 0);
      const uint32_t due = get_due();
      uint32_t vf[4][4], vm[2][4], p[4], pm, o[4];
      const uint32_t va = sb + R_V + (w4 >> 1) * 8192 + (w4 & 1) * 2048 + L16;
#pragma unroll
      for (int i = 0; i < 4; i++) {
        uint32_t q[4]; lds128(vf[i], va + i * 512); lds128(q, va + 4096 + i * 512);
#pragma unroll
        for (int e = 0; e < 4; e++) vf[i][e] = hadd2(vf[i][e], q[e]);
      }
      const uint32_t pa = pin(sb + R_P + (L16 >> 1));
      const uint8_t* vsrc = pinp(xa + 8192 + w4 * 1024 + L16 / 2);
      uint32_t one[4];
      lds128(one, sb + B_ONE);
      auto pv_x = [&]() {
        zero(c);
        mma_a(c[2], one, p[0], p[1]);
        mma_a(c[0], vf[0], p[0], p[1]); mma_a(c[1], vf[2], p[0], p[1]);
        sched();
        mma_a(c[2], one, p[2], p[3]);
        mma_a(c[0], vf[1], p[2], p[3]); mma_a(c[1], vf[3], p[2], p[3]);
        sched();
      };
      auto pv_m = [&]() {
        mma1688(c[2], one[0], one[1], pm);
        mma_a(c[0], vm[0], pm, pm);
        sched();
        mma_a(c[1], vm[1], pm, pm);
      };
      auto norm = [&]() {
        const float n0 = rcp(c[2][0]), n1 = rcp(c[2][1]);
#pragma unroll
        for (int i = 0; i < 4; i++) o[i] = pack2(c[i >> 1][2 * (i & 1)] * n0, c[i >> 1][2 * (i & 1) + 1] * n1);
        return ((__float_as_uint(c[2][0]) - 0x1F800000u) | (__float_as_uint(c[2][1]) - 0x1F800000u)) >> 30;
      };
      auto load_m = [&](int x) { const float2 e0 = lds64f(pa + 512 + x * 1024), e1 = lds64f(pa + 768 + x * 1024); pm = pack2(e0.x * e1.x, e0.y * e1.y); };
      auto attend_max = [&](int x) {
        float2 sv[6];
#pragma unroll
        for (int i = 0; i < 6; i++) sv[i] = lds64f(pa - 3072 + x * 1536 + i * 256);
        sv[4].x += sv[5].x; sv[4].y += sv[5].y;
        const int dq = (int)(L16 >> 6) - (int)((L16 >> 3) & 6) + 8 * j;
        float m = fmaxf(sv[4].x, sv[4].y);
#pragma unroll
        for (int i = 0; i < 4; i++) {
          if (x && 8 * i > dq) sv[i].x = -INFINITY;
          if (x && 8 * i + 1 > dq) sv[i].y = -INFINITY;
          m = fmaxf(m, fmaxf(sv[i].x, sv[i].y));
        }
        m = fmaxf(m, __shfl_xor_sync(0xffffffffu, m, 1));
        m = fmaxf(m, __shfl_xor_sync(0xffffffffu, m, 2));
#pragma unroll
        for (int i = 0; i < 5; i++) (i < 4 ? p[i] : pm) = pack2(ex2(sv[i].x - m), ex2(sv[i].y - m));
        pv_x(); pv_m(); norm();
      };
      uint32_t tq[4];
      auto get_t = [&]() {
        tq[0] = tq[1] = tq[2] = tq[3] = 0;
        asm volatile("{.reg .pred p; setp.eq.u32 p, %5, 0; @p ld.relaxed.gpu.global.v4.b32 {%0,%1,%2,%3}, [%4];}"
                     : "+r"(tq[0]), "+r"(tq[1]), "+r"(tq[2]), "+r"(tq[3]) : "l"(xb + offsetof(Xchg, T) + L16 * 8), "r"(warp) : "memory");
      };
      delay_until(tpub + DLY_V);
      wait_time(due + NS_V);
      TS(4);
      ldx(vm, vsrc);
      sched();
      xpos(2, 2);
      auto store_kqv = [&]() {
        fence_async();
        if (!(EXP & 4))
          asm volatile("{.reg .pred p; elect.sync _|p, 0xffffffff; @p cp.async.bulk.global.shared::cta.bulk_group [%0], [%1], 2048; cp.async.bulk.commit_group;}"
                       :: "l"(g_kqv[(s + 1) & 3][role] + w4 * 128), "r"(sb + R_STAGE + w4 * 2048) : "memory");
      };
      if (SPOS == 2) store_kqv();
      sched();
      bar_sync(5, 256);
      ldsm4(p, sb + R_P + L16);
      load_m(0);
      pv_x();
      ldsm4(p, sb + R_P + 1024 + L16);
      pv_m();
      const uint32_t r = norm(), tl = after(tag, c[2][0], (uint32_t)it >> 31);
      const bool redo = __any_sync(0xffffffffu, r | ((dif2(vm[0][0], vm[0][2], tl) | dif2(vm[1][0], vm[1][2], tl)) & 1));
      TS(6);
      stsm4t(uW + R_O + L16, o[0], o[1], o[2], o[3]);
      bar_arrive_unless(6, redo);
      sched();
      if (TQL == 7) get_t();
      TS(7);
      pv_x();
      if (rare(redo)) retry<2>(vm, vsrc, tag, it);
      bar_sync(8, 256);
      load_m(1);
      pv_m();
      if (rare(__any_sync(0xffffffffu, norm()) || redo)) {
        fresh();
#pragma unroll 1
        for (int x = !redo; x < 2; x++) {
          attend_max(x);
          if (x == 0) { stsm4t(uW + R_O + L16, o[0], o[1], o[2], o[3]); bar_arrive(6, 256); }
        }
      }
      TS(8);
      if (TQL == 8) get_t();
      const bool xok = mbar_test(sb + B_X + 16, s & 1) & mbar_test(sb + B_X + 24, s & 1);
      xpos(4, 2);
      fresh();
      const uint32_t ob = uni(sb + R_MEM + 4096 + w4 * 1024);
      stsm4t(ob + (L16 & 112) * 4 + (((L16 >> 3) ^ (L16 >> 1)) & 48), o[0], o[1], o[2], o[3]);
      __syncwarp();
      uint32_t rd[4];
      lds128(rd, uW + R_RD + L16);
      lds128(o, ob + (L16 ^ ((L16 >> 3) & 48)));
      auto put_o = [&]() {
        *reinterpret_cast<uint4*>(reinterpret_cast<uint8_t*>(g_ox) + (((s * SEG + 8 * j) * HD + h * DH + 32 * w4) * 2 + (L16 >> 6) * (HD * 2) + (L16 & 48))) = make_uint4(o[0], o[1], o[2], o[3]);
      };
      if (s + 1 == NSEG) { put_o(); asm volatile("cp.async.bulk.wait_group 0;" ::: "memory"); break; }
      asm volatile("cp.async.bulk.wait_group 0;" ::: "memory");
      if (elect()) stx32(xa + 4096 + j * 16 + w4 * 4, s + 1);
      __syncwarp();
      if (rare(!xok)) { wait_x(s + 2, 3); wait_x(s + 2, 2); }
      TS(9);
      fresh();
      const uint32_t e = due | ((s + 1) & 31);
      project_qk(IC<0>{}, IC<NQ>{}, IC<1>{}, [&](int n) {
        if (n == OXPOS) { __syncwarp(); put_o(); __syncwarp(); }
        if (n == TQP) { __syncwarp(); tq[0] = dif2v(tq[0], tq[1], e) | dif2v(tq[2], tq[3], e); __syncwarp(); }
      });
      if (NPA) project_v(IC<0>{}, IC<NPA>{}, [](int) {});
      TS(2);
      if (warp == 0) {
        uint32_t last = due, nx = NS_P;
        if (rare(__any_sync(0xffffffffu, tq[0]))) {
          const uint32_t ref = gtime();
#pragma unroll 1
          do ldx128(o, xb + offsetof(Xchg, T) + L16 * 8); while (any_bit(or3(o[0] - s - 1, o[1] - s - 1, o[2] - s - 1), o[3] - s - 1, 30) && ++it < SPIN_LIMIT);
          const int d = max(max((int)(o[0] - ref), (int)(o[1] - ref)), max((int)(o[2] - ref), (int)(o[3] - ref)));
          last = (ref + __reduce_max_sync(0xffffffffu, d)) & ~31u;
          if (last != due) nx += NS_X;
        }
        const uint32_t bdue = last + NS_B;
        if (s == 0) { last += NS_Y; nx += NS_Z; }
        sts32(sb + B_DUE, last);
        sts32(sb + B_DUE + 8 - tag * 4, last + nx);
        fetch4k(sb + R_MEM, my_b(), sb + B_B, bdue);
        LOG(13, tl - last);
        LOG(9, last);
      }
      if (NQ < 16) project_qk(IC<NQ>{}, IC<16>{}, IC<0>{}, [](int) {});
      project_v(IC<NPA>{}, IC<NPRE>{}, [](int) {});
      const uint32_t ba = rd[2], msk = rd[3];
      const uint8_t* cdst = reinterpret_cast<const uint8_t*>(rd[0] | (uint64_t)rd[1] << 32);
      TS(14);
      mbar_spin(sb + B_B, s & 1, it);
      TS(10);
      uint32_t bq[2][4];
      auto sum_b = [&]() {
        ldsm4t(bq[0], ba); ldsm4t(bq[1], ba + 2048);
        sched();
#pragma unroll
        for (int i = 0; i < 8; i++) c[i >> 2][i & 3] = 0.f;
        mma_a(c[0], bq[0], 0x3F803F80u, 0x3F803F80u); mma_a(c[1], bq[1], 0x3F803F80u, 0x3F803F80u);
        const uint32_t t2 = tag * 0x10001u;
        const bool old = any_bit(or3(dif2(bq[0][0], bq[0][1], t2), dif2(bq[0][2], bq[0][3], t2), dif2(bq[1][0], bq[1][1], t2)), dif2(bq[1][2], bq[1][3], t2), L16 < 64 ? 0x10001u : 0u);
        const uint32_t T = (tag << 16) & ~msk, u = ((__float_as_uint(c[0][0] + c[1][0]) + ((0x10000u & ~msk) - T)) & msk) | T;
        asm volatile("{.reg .pred p; setp.eq.u32 p, %2, 0; @p st.relaxed.gpu.global.b32 [%0], %1;}"
                     :: "l"(cdst), "r"(pack2(__uint_as_float(u), c[0][2] + c[1][2])), "r"((uint32_t)(old || (L16 & 32))) : "memory");
        return old;
      };
      if (rare(sum_b())) {
#pragma unroll 1
        do {
          const uint8_t* p = xb + (my_b() + (ba - sb - R_MEM));
          ldx128(bq[0], p); ldx128(bq[1], p + 2048);
          sts128(ba, bq[0]); sts128(ba + 2048, bq[1]);
          __syncwarp();
          it += INC_B;
        } while (sum_b() && it < SPIN_LIMIT);
      }
      sched();
      TS(11);
      bar_arrive(0, 256);
      const unsigned tc = clk();
      const uint32_t cdue = lds32(sb + B_DUE) + NS_C;
      if (warp == 3) LOG(11, gtime() - cdue);
      fresh();
      wg_wait<0>(); keep(aq); keep(av);
      park();
      if (NPRE < 32) project_v(IC<NPRE>{}, IC<32>{}, [](int) {}); else fin_v();
      TS(12);
      delay_until(tc + DLY_C);
      issue_c(cdue);
      TS(5);
      LOG(warp, it);
      pin_mem();
      if (NPRE < 32) { wg_wait<0>(); keep(av); fin_v(); }
      if (!(EXP & 2)) mbar_spin(sb + B_KV, tag, it);
      TS(15);
    } else {
      uint32_t kf[8][4];
      auto load_k = [&]() {
        const uint32_t ka = sb + R_K + w4 * 1024 + (L16 & 112) + (L16 & 128) * 4 + (L16 & 256);
#pragma unroll
        for (int i = 0; i < 8; i++) ldsm4(kf[i], ka + (i >> 1) * 2048 + (i & 1) * 128);
      };
      auto put_p = [&](int x, uint32_t old, uint32_t again) {
        float e[4];
        const int dq = (int)((L16 >> 3) & 6) + 8 * j - (int)(L16 >> 6) - 16 * w4;
#pragma unroll
        for (int i = 0; i < 4; i++) { r4[i] = fmaf(c[3][i], sc, fmaf(c[2][i], sc, fmaf(c[0][i] + c[1][i], sc, __uint_as_float(i == 3 ? 0u - old : 0u)))); e[i] = x && dq + (i & 1) < 8 * (i >> 1) ? 0.f : ex2(r4[i]); }
        stsm2t(uP2 + x * 1024 + L16, pack2(e[0], e[1]), pack2(e[2], e[3]), again);
      };
      auto put_s = [&](int x) {
#pragma unroll
        for (int i = 0; i < 4; i++) sts32f(uW + R_S + x * 1536 + (L16 & 48) * 4 + (L16 >> 6) * 4 + (i & 1) * 32 + (i >> 1) * 256, r4[i]);
      };
      auto load_q = [&](uint32_t (&q)[4], uint32_t off) { ldsm4(q, sb + R_Q + (L16 & 112) + (L16 & 128) * 2 + (L16 >> 8) * 128 + off); };
      mbar_spin(sb + B_C, nc & 1, it);
      TS(13);
      float4 o4;
      uint32_t id[4], old;
      {
        uint32_t b[24][4];
#pragma unroll
        for (int i = 0; i < 2 * PD1; i++) { lds128(b[i], ma + i * 512); __syncwarp(); }
        sched();
        zero(c);
#pragma unroll
        for (int i = 0; i < 12; i++) {
          mma4(4 * i, b[2 * i], b[2 * i + 1]);
          if (i < 11) sched();
          if (i + PD1 < 12) { const int k = i + PD1; const uint32_t a = (ma ^ (k >> 2 << 12)) + (k & 3) * 1024; lds128(b[2 * k], a); __syncwarp(); lds128(b[2 * k + 1], a + 512); sched(); }
          if (i == RJ) { lds128(id, sb + R_ID + L16); sched(); }
          if (i == RI) { old = bar_or(4, 0); o4 = lds128f(uW + R_RED + L16); sched(); }
        }
      }
      TS(0);
      {
        float e[4] = {o4.x, o4.y, o4.z, o4.w};
#pragma unroll
        for (int i = 0; i < 4; i++) { r4[i] = (((e[i] + c[0][i]) + c[1][i]) + c[2][i]) + c[3][i]; e[i] = 0.f; }
        mma_a(e, id, pack2(r4[0], r4[1]), pack2(r4[2], r4[3]));
        sched();
        if (VB) bar_arrive(7, 256);
        sched();
        asm volatile("{.reg .pred p; setp.eq.u32 p, %3, 0; @p st.relaxed.gpu.global.v2.b32 [%0], {%1,%2};}" :: "l"(adst),
                     "r"((__byte_perm(__float_as_uint(e[0]), __float_as_uint(e[1]), 0x7632) & ~1u) | tag), "r"(__byte_perm(__float_as_uint(e[2]), __float_as_uint(e[3]), 0x7632)), "r"(old) : "memory");
        sched();
      }
      const unsigned tpub = clk(), now = gtime(), due = get_due();
      if (__any_sync(0xffffffffu, old) && nc < NC_MAX) { bar_sync(3, 256); continue; }
      TS(2);
      const uint8_t* asrc = pinp(adst + ((warp == 7) * 1024 - (int)uA));
      fresh();
      uint32_t wo[32][4];
      bool xok;
      auto reload = [&]() {
        sched();
#pragma unroll
        for (int i = RE0 + RE1; i < NSW; i++) lds128(w[i], uW + R_WC + L16 + i * 2048);
        sched();
      };
      auto out_proj = [&]() {
        uint32_t b[4][4];
        float d[4][4];
        uint8_t* dst[2];
        const uint32_t da = pin(uP2 + (R_DST - R_P) + L16 / 2);
        sched();
        TS(7);
        bar_sync(6, 256);
#pragma unroll
        for (int i = 0; i < 4; i++) { ldsm4(b[i], sb + R_O + i * 512 + L16); __syncwarp(); }
        sched();
        auto put_b = [&](uint8_t* a, const float (&e)[4][4]) {
          stx128(a, (pack2(e[0][0] + e[2][0], e[0][1] + e[2][1]) & ~1u) | tag, pack2(e[0][2] + e[2][2], e[0][3] + e[2][3]),
                 pack2(e[1][0] + e[3][0], e[1][1] + e[3][1]), pack2(e[1][2] + e[3][2], e[1][3] + e[3][3]));
        };
        zero(c); zero(d);
#pragma unroll
        for (int i = 0; i < 32; i++) {
          mma_h(i < 16 ? c[i & 3] : d[i & 3], wo[i], b[(i >> 2) & 3], (i >> 1) & 1);
          if (i >= LW0 && NB1 + i - LW0 < 32) { load_wo(wo, (NB1 + i - LW0) ^ 1, ((NB1 + i - LW0) ^ 1) + 1); __syncwarp(); }
          if (i == DL0 || i == DL1) asm volatile("ld.shared.u64 %0, [%1];" : "=l"(dst[i > DL0]) : "r"(da + (i > DL0) * 1024) : "memory");
          if (i >= 16 && i < 16 + RE0) { lds128(w[i - 16], uW + R_WC + L16 + (i - 16) * 2048); __syncwarp(); }
          if (i >= RP1 && i < RP1 + RE1) { lds128(w[i - RP1 + RE0], uW + R_WC + L16 + (i - RP1 + RE0) * 2048); __syncwarp(); }
          if (i == 22) put_b(dst[0], c);
          if ((i & 1) && (i < 20 || i > 22)) sched();
        }
        put_b(dst[1], d);
        sched();
        TS(6);
      };
      if (warp < 6) {
        delay_until(tpub + DLY_A);
        const int it0 = it;
        bool redo;
#pragma unroll 1
        do {
          uint32_t q[4][4], y[4];
          float d[4][4];
          wait_time(due);
          TS(4);
          ldx(q, asrc);
          sched();
          load_k();
          uint32_t qx[4][4];
#pragma unroll
          for (int i = 0; i < 4; i++) load_q(qx[i], i * 512);
          sched();
          load_wo(wo, 0, NE4);
          sched();
          zero(c);
#pragma unroll
          for (int i = 0; i < 8; i++) mma_h(c[i & 3], kf[i], qx[i >> 1], i & 1);
          put_p(1, 0, 0); put_s(1);
          sched();
          load_wo(wo, NE4, NA4);
          sched();
          zero(c); zero(d);
#pragma unroll
          for (int i = 0; i < 8; i++) {
            if (i == 0) { y[0] = dif2v(q[0][0], q[0][2], q[1][0]); sched(); }
            if (i == 3) { y[1] = dif2v(q[1][2], q[2][0], q[2][2]); sched(); }
            if (i == 6) { y[2] = dif2v(q[3][0], q[3][2], tag); sched(); }
            mma_h(i % 6 < 2 ? c[2 + i % 6] : d[i - 2], kf[i], q[i >> 1], i & 1);
            if (i == 2 || i == 5 || i == 7) sched();
          }
          y[0] = or_and(or3(y[0], y[1], dif2v(q[0][0], q[2][0], tag)), y[2], it < SPIN_LIMIT);
#pragma unroll
          for (int i = 0; i < 4; i++) { c[0][i] = d[0][i] + d[1][i]; c[1][i] = d[2][i] + d[3][i]; }
          put_p(0, y[0], it - it0);
          TS(5);
          bar_sync_unless(5, it - it0);
          redo = __any_sync(0xffffffffu, y[0]);
          it += INC_A;
        } while (redo);
        it -= INC_A;
        put_s(0);
        bar_arrive(8, 256);
        load_wo(wo, NA4, NB1);
        out_proj();
        if (warp == 4) LOG(12, tb);
      } else {
        uint32_t qx[2][4], q[4][4];
        if (warp == 6) {
          const uint32_t t1 = (now & ~31u) + NS_M;
          LOG(10, now - due);
          if (elect()) stx32(&gx->T[h][j], ((int)(t1 - due) > 0 ? t1 + NS_PEN : due) | ((s + 1) & 31));
          __syncwarp();
        }
        auto score = [&](const uint32_t (&a0)[4], const uint32_t (&a1)[4]) {
          zero(c);
#pragma unroll
          for (int i = 0; i < 4; i++) mma_h(c[i], i < 2 ? a0 : a1, q[2 + (i >> 1)], i & 1);
        };
        auto put_m = [&](uint32_t a, uint32_t old, uint32_t again) {
#pragma unroll
          for (int i = 0; i < 2; i++) { r4[i] = fmaf(c[3][2 + i], sc, fmaf((c[0][i] + c[1][2 + i]) + c[2][i], sc, __uint_as_float(i ? 0u - old : 0u))); r4[2 + i] = fmaf(r4[i] * 0x1p122f, 0.f, ex2(r4[i])); }
          asm volatile("{.reg .pred p; setp.eq.u32 p, %3, 0; @p st.shared.v2.f32 [%0], {%1,%2};}" :: "r"(a), "f"(r4[2]), "f"(r4[3]), "r"(again) : "memory");
        };
        delay_until(tpub + DLY_A);
        const uint32_t sa = sb + R_S + 512 + w4 * 256 + (L16 >> 1);
        const int it0 = it;
        bool redo;
#pragma unroll 1
        do {
          wait_time(due);
          TS(4);
          ldx<4, 2048>(q, asrc);
          sched();
          load_q(qx[0], (w4 & 1) * 1024); load_q(qx[1], (w4 & 1) * 1024 + 512);
          load_wo(wo, 0, NA6);
          sched();
          score(q[0], q[1]);
          sched();
          const uint32_t y = or_and(or3(dif2v(q[0][0], q[0][2], tag), dif2v(q[1][0], q[1][2], tag), dif2v(q[2][0], q[2][2], tag)), dif2v(q[3][0], q[3][2], tag), it < SPIN_LIMIT);
          put_m(sa + 2560, y, it - it0);
          TS(5);
          bar_arrive_unless(5, it - it0);
          redo = __any_sync(0xffffffffu, y);
          it += INC_A;
        } while (redo);
        it -= INC_A;
        sts64f(sa, r4[0], r4[1]);
        score(qx[0], qx[1]);
        put_m(sa + 3584, 0, 0);
        sts64f(sa + 1536, r4[0], r4[1]);
        bar_arrive(8, 256);
        load_wo(wo, NA6, NB1);
        out_proj();
      }
      TS(8);
      if (s + 1 == NSEG) break;
      wait_x(s + 2, 2);
      TS(9);
      fresh();
      if (N1) project_qk(IC<32>{}, IC<32 + N1>{}, IC<1>{}, [](int) {});
      TS(10);
      xpos(6, 6);
      uint32_t fl = s + 1;
      if (warp == 5) { wait_time(due + NS_F); fl = ldx32(xa + 4096 + ((L16 >> 2) & 60)); }
      reload();
      TS(14);
      pin_mem();
      wait_x(s + 2, 1); wait_x(s + 2, 0);
      if (warp == 5) {
#pragma unroll 1
        while (__any_sync(0xffffffffu, fl != s + 1) && !(EXP & 4) && ++it < SPIN_LIMIT) fl = ldx32(xa + 4096 + ((L16 >> 2) & 60));
        wait_time(due + (NS_B + NS_K));
        if (!(EXP & 2) && elect()) issue_kqv(s + 1);
        __syncwarp();
      }
      if (PFD && warp == 6 && s + PFD < NSEG && elect())
        asm volatile("cp.async.bulk.prefetch.L2.global [%0], 2048;" :: "l"(xin + ((s + PFD) * SEG + ((role + 4 * (role >> 5)) & 31)) * DM) : "memory");
      __syncwarp();
      TS(11);
      LOG(warp, it);
      if (warp == 4) LOG(8, nc);
      bar_sync(0, 256);
      if (N1 < 16) project_qk(IC<32 + N1>{}, IC<48>{}, IC<!N1>{}, [](int) {});
      project_qk(IC<16>{}, IC<32>{}, IC<0>{}, [&](int n) { if ((n & 15) == XWPOS) { __syncwarp(); xok = mbar_test(sb + B_PK, s & 1); __syncwarp(); } });
      if (rare(!xok)) mbar_spin(sb + B_PK, s & 1, it);
      unpark();
      project_qk(IC<0>{}, IC<16>{}, IC<0>{}, [](int) {});
      TS(12);
      wg_wait<0>(); keep(aq);
      TS(1);
      fin_qk();
      TS(15);
    }
    s++;
  }
  if (it >= SPIN_LIMIT || nc >= NC_MAX) g_err = 2;
}

typedef CUresult (*EncodeFn)(CUtensorMap*, CUtensorMapDataType, cuuint32_t, void*, const cuuint64_t*, const cuuint64_t*, const cuuint32_t*,
                             const cuuint32_t*, CUtensorMapInterleave, CUtensorMapSwizzle, CUtensorMapL2promotion, CUtensorMapFloatOOBfill);
static void make_map(EncodeFn fn, CUtensorMap* m, const void* p, uint64_t cols, uint64_t rows, uint64_t pitch, uint32_t bc, uint32_t br, CUtensorMapSwizzle sw) {
  cuuint64_t dims[2] = {cols, rows}, strides[1] = {pitch * 2};
  cuuint32_t box[2] = {bc, br}, es[2] = {1, 1};
  fn(m, CU_TENSOR_MAP_DATA_TYPE_BFLOAT16, 2, const_cast<void*>(p), dims, strides, box, es, CU_TENSOR_MAP_INTERLEAVE_NONE, sw,
     CU_TENSOR_MAP_L2_PROMOTION_L2_256B, CU_TENSOR_MAP_FLOAT_OOB_FILL_NONE);
}

extern "C" void kernel_launch(void* const* d_in, const int* in_sizes, int n_in, void* d_out, int out_size) {
  const bf16* Ax = (const bf16*)d_in[0]; const bf16* mem0 = (const bf16*)d_in[1];
  const bf16* Wq = (const bf16*)d_in[2]; const bf16* Wk = (const bf16*)d_in[3]; const bf16* Wv = (const bf16*)d_in[4];
  const bf16* Wo = (const bf16*)d_in[5];
  const bf16* Bx = (const bf16*)d_in[7]; const bf16* wr = (const bf16*)d_in[8]; const bf16* wi = (const bf16*)d_in[9];
  bf16* out = (bf16*)d_out;

  void* fp = nullptr; cudaDriverEntryPointQueryResult qr;
  cudaGetDriverEntryPoint("cuTensorMapEncodeTiled", &fp, cudaEnableDefault, &qr);
  EncodeFn fn = (EncodeFn)fp;
  void *kqv, *ox, *xr;
  cudaGetSymbolAddress(&xr, g_xraw);
  cudaGetSymbolAddress(&kqv, g_kqv); cudaGetSymbolAddress(&ox, g_ox);
  const CUtensorMapSwizzle S128 = CU_TENSOR_MAP_SWIZZLE_128B, S64 = CU_TENSOR_MAP_SWIZZLE_64B;

  GemmMaps m3; RecMaps mr;
  make_map(fn, &m3.a, ox, HD, S_LEN, HD, 64, 128, S128);
  make_map(fn, &m3.b[0], Wo, DM, HD, DM, 64, 64, S128);
  m3.b[1] = m3.b[0]; m3.b[2] = m3.b[0];
  make_map(fn, &m3.c, out, DM, S_LEN, 2 * DM, 64, 64, S128);
  make_map(fn, &mr.wq, Wq, HD, DM, HD, 32, 256, S64);
  make_map(fn, &mr.wk, Wk, HD, DM, HD, 32, 256, S64);
  make_map(fn, &mr.wv, Wv, HD, DM, HD, 64, 256, S128);
  make_map(fn, &mr.wo, Wo, DM, HD, DM, 64, 128, S128);
  {
    cuuint64_t dims[3] = {64, S_LEN, 16}, strides[2] = {DM * 2, 128};
    cuuint32_t box[3] = {64, 32, 4}, es[3] = {1, 1, 1};
    fn(&mr.x, CU_TENSOR_MAP_DATA_TYPE_BFLOAT16, 3, const_cast<bf16*>(Ax), dims, strides, box, es, CU_TENSOR_MAP_INTERLEAVE_NONE, S128,
       CU_TENSOR_MAP_L2_PROMOTION_L2_256B, CU_TENSOR_MAP_FLOAT_OOB_FILL_NONE);
  }
  for (int i = 0; i < 3; i++) {
    cuuint64_t dims[3] = {128, 32, 512}, strides[2] = {256, 8192};
    cuuint32_t box[3] = {128, i == 0 ? 8u : i == 1 ? 2u : 16u, 4}, es[3] = {1, 1, 1};
    fn(i == 0 ? &mr.k : i == 1 ? &mr.q : &mr.v, CU_TENSOR_MAP_DATA_TYPE_BFLOAT16, 3, kqv, dims, strides, box, es, CU_TENSOR_MAP_INTERLEAVE_NONE,
       CU_TENSOR_MAP_SWIZZLE_NONE, CU_TENSOR_MAP_L2_PROMOTION_L2_256B, CU_TENSOR_MAP_FLOAT_OOB_FILL_NONE);
  }
  {
    cuuint64_t dims[3] = {64, 16, S_LEN}, strides[2] = {128, 2 * DM * 2};
    cuuint32_t box[3] = {64, 16, 2}, es[3] = {1, 1, 1};
    fn(&mr.fo, CU_TENSOR_MAP_DATA_TYPE_BFLOAT16, 3, out + DM, dims, strides, box, es, CU_TENSOR_MAP_INTERLEAVE_NONE, S128,
       CU_TENSOR_MAP_L2_PROMOTION_NONE, CU_TENSOR_MAP_FLOAT_OOB_FILL_NONE);
  }
  constexpr int SM3 = 6 * 32768 + 32768 + 256 + 1024;
  cudaFuncSetAttribute(gemm_kernel<128, 6>, cudaFuncAttributeMaxDynamicSharedMemorySize, SM3);
  cudaFuncSetAttribute(rec_kernel, cudaFuncAttributeMaxDynamicSharedMemorySize, R_TOTAL);

  cudaStream_t st = cudaStreamPerThread;
  rec_kernel<<<132, 256, R_TOTAL, st>>>(mr, Ax, mem0, reinterpret_cast<Xchg*>((reinterpret_cast<uintptr_t>(xr) + 8191) & ~(uintptr_t)8191), Bx, wr, wi);
  gemm_kernel<128, 6><<<128, 384, SM3, st>>>(m3, 16, 8, 64, 8, 1);
}
```

```cpp
#include <cuda_runtime.h>
#include <cuda_bf16.h>
#include <cuda.h>
#include <stdint.h>
#include <stddef.h>
#include <type_traits>

typedef __nv_bfloat16 bf16;

constexpr int S_LEN = 2048, DM = 1024, NH = 32, DH = 128, MEM = 8, SEG = 32, NSEG = 64;
constexpr int HD = NH * DH;
#define SPIN 20
constexpr int SPIN_LIMIT = 1 << SPIN, INC_A = 1, INC_B = 1;

constexpr unsigned NC_MAX = 4096;
__device__ __align__(1024) uint4 g_kqv[4][128][512];
__device__ __align__(1024) bf16 g_ox[(size_t)S_LEN * HD];
struct Xchg {
  uint4 A[32][4][256];
  uint4 C[4][2][256];
  uint4 B[128][2][256];
  uint32_t T[32][32];
  uint32_t S[128];
  unsigned ctr[64];
};
__device__ __align__(1024) uint4 g_xraw[(sizeof(Xchg) + (1 << 21)) / 16];
__device__ __align__(1024) uint4 g_y[1024 * 256];
__device__ __align__(1024) uint4 g_wt[513 * 512];
__device__ int g_err;

__device__ __forceinline__ unsigned clk() { unsigned long long c; asm volatile("mov.u64 %0, %%clock64;" : "=l"(c)); return (unsigned)c; }
__device__ __forceinline__ uint32_t smem_u32(const void* p) { return (uint32_t)__cvta_generic_to_shared(p); }
__device__ __forceinline__ void mbar_init(uint32_t bar, int cnt) { asm volatile("mbarrier.init.shared::cta.b64 [%0], %1;" :: "r"(bar), "r"(cnt) : "memory"); }
__device__ __forceinline__ void mbar_expect_tx(uint32_t bar, int bytes) { asm volatile("mbarrier.arrive.expect_tx.shared::cta.b64 _, [%0], %1;" :: "r"(bar), "r"(bytes) : "memory"); }
__device__ __forceinline__ void mbar_arrive(uint32_t bar) { asm volatile("mbarrier.arrive.shared::cta.b64 _, [%0];" :: "r"(bar) : "memory"); }
__device__ __forceinline__ void mbar_arrive_cluster(uint32_t bar, int cta) {
  asm volatile("{.reg .b32 r; mapa.shared::cluster.u32 r, %0, %1; mbarrier.arrive.shared::cluster.b64 _, [r];}" :: "r"(bar), "r"(cta) : "memory"); }
__device__ __forceinline__ bool mbar_try(uint32_t bar, int par) {
  uint32_t ok; asm volatile("{.reg .pred p; mbarrier.try_wait.parity.shared::cta.b64 p, [%1], %2; selp.u32 %0, 1, 0, p;}" : "=r"(ok) : "r"(bar), "r"(par) : "memory"); return ok; }
__device__ __forceinline__ bool mbar_test(uint32_t bar, int par) {
  uint32_t ok; asm volatile("{.reg .pred p; mbarrier.test_wait.parity.shared::cta.b64 p, [%1], %2; selp.u32 %0, 1, 0, p;}" : "=r"(ok) : "r"(bar), "r"(par) : "memory"); return ok; }
__device__ __forceinline__ void mbar_wait(uint32_t bar, int par) {
  int it = 0;
  while (!mbar_try(bar, par)) { if (++it > SPIN_LIMIT) { g_err = 1; break; } }
}
__device__ __forceinline__ void tma2d(uint32_t dst, const CUtensorMap* m, int c0, int c1, uint32_t bar) {
  asm volatile("cp.async.bulk.tensor.2d.shared::cluster.global.mbarrier::complete_tx::bytes [%0], [%1, {%3, %4}], [%2];"
    :: "r"(dst), "l"(m), "r"(bar), "r"(c0), "r"(c1) : "memory"); }
__device__ __forceinline__ void tma2d_mc(uint32_t dst, const CUtensorMap* m, int c0, int c1, uint32_t bar, uint16_t mask) {
  asm volatile("cp.async.bulk.tensor.2d.shared::cluster.global.mbarrier::complete_tx::bytes.multicast::cluster [%0], [%1, {%3, %4}], [%2], %5;"
    :: "r"(dst), "l"(m), "r"(bar), "r"(c0), "r"(c1), "h"(mask) : "memory"); }
__device__ __forceinline__ void tma2d_store(const CUtensorMap* m, uint32_t src, int c0, int c1) {
  asm volatile("cp.async.bulk.tensor.2d.global.shared::cta.bulk_group [%0, {%2, %3}], [%1];" :: "l"(m), "r"(src), "r"(c0), "r"(c1) : "memory"); }
__device__ __forceinline__ void fence_async() { asm volatile("fence.proxy.async.shared::cta;" ::: "memory"); }
__device__ __forceinline__ void bar_sync(int id, int n) { asm volatile("bar.sync %0, %1;" :: "r"(id), "r"(n) : "memory"); }
__device__ __forceinline__ void bar_arrive(int id, int n) { asm volatile("bar.arrive %0, %1;" :: "r"(id), "r"(n) : "memory"); }
__device__ __forceinline__ uint32_t pack2(float lo, float hi) { uint32_t r; asm("cvt.rn.bf16x2.f32 %0, %1, %2;" : "=r"(r) : "f"(hi), "f"(lo)); return r; }
__device__ __forceinline__ uint32_t pack2_tag(float lo, float hi, uint32_t T) {
  uint32_t u = ((__float_as_uint(lo) - T + 0x10000u) & 0xFFFE0000u) + T;
  return __byte_perm(u, pack2(0.f, hi), 0x7632); }
__device__ __forceinline__ void ldsm4(uint32_t (&r)[4], uint32_t a) {
  asm volatile("ldmatrix.sync.aligned.m8n8.x4.shared.b16 {%0,%1,%2,%3}, [%4];" : "=r"(r[0]), "=r"(r[1]), "=r"(r[2]), "=r"(r[3]) : "r"(a) : "memory"); }
__device__ __forceinline__ void ldsm4t(uint32_t (&r)[4], uint32_t a) {
  asm volatile("ldmatrix.sync.aligned.m8n8.x4.trans.shared.b16 {%0,%1,%2,%3}, [%4];" : "=r"(r[0]), "=r"(r[1]), "=r"(r[2]), "=r"(r[3]) : "r"(a) : "memory"); }
__device__ __forceinline__ void stsm4(uint32_t a, uint32_t r0, uint32_t r1, uint32_t r2, uint32_t r3) {
  asm volatile("stmatrix.sync.aligned.m8n8.x4.shared.b16 [%0], {%1,%2,%3,%4};" :: "r"(a), "r"(r0), "r"(r1), "r"(r2), "r"(r3) : "memory"); }
__device__ __forceinline__ void stsm4t(uint32_t a, uint32_t r0, uint32_t r1, uint32_t r2, uint32_t r3) {
  asm volatile("stmatrix.sync.aligned.m8n8.x4.trans.shared.b16 [%0], {%1,%2,%3,%4};" :: "r"(a), "r"(r0), "r"(r1), "r"(r2), "r"(r3) : "memory"); }
__device__ __forceinline__ void lds128(uint32_t (&r)[4], uint32_t a) {
  asm volatile("ld.shared.v4.u32 {%0,%1,%2,%3}, [%4];" : "=r"(r[0]), "=r"(r[1]), "=r"(r[2]), "=r"(r[3]) : "r"(a) : "memory"); }
__device__ __forceinline__ float4 lds128f(uint32_t a) { float4 r;
  asm volatile("ld.shared.v4.f32 {%0,%1,%2,%3}, [%4];" : "=f"(r.x), "=f"(r.y), "=f"(r.z), "=f"(r.w) : "r"(a) : "memory"); return r; }
__device__ __forceinline__ float2 lds64f(uint32_t a) { float2 r;
  asm volatile("ld.shared.v2.f32 {%0,%1}, [%2];" : "=f"(r.x), "=f"(r.y) : "r"(a) : "memory"); return r; }
__device__ __forceinline__ void sts128(uint32_t a, uint32_t r0, uint32_t r1, uint32_t r2, uint32_t r3) {
  asm volatile("st.shared.v4.u32 [%0], {%1,%2,%3,%4};" :: "r"(a), "r"(r0), "r"(r1), "r"(r2), "r"(r3) : "memory"); }
__device__ __forceinline__ void sts64f(uint32_t a, float x, float y) { asm volatile("st.shared.v2.f32 [%0], {%1,%2};" :: "r"(a), "f"(x), "f"(y) : "memory"); }
__device__ __forceinline__ void sts32f(uint32_t a, float x) { asm volatile("st.shared.f32 [%0], %1;" :: "r"(a), "f"(x) : "memory"); }
__device__ __forceinline__ void mma16816(float (&d)[4], uint32_t a0, uint32_t a1, uint32_t a2, uint32_t a3, uint32_t b0, uint32_t b1) {
  asm volatile("mma.sync.aligned.m16n8k16.row.col.f32.bf16.bf16.f32 {%0,%1,%2,%3}, {%4,%5,%6,%7}, {%8,%9}, {%0,%1,%2,%3};"
    : "+f"(d[0]), "+f"(d[1]), "+f"(d[2]), "+f"(d[3]) : "r"(a0), "r"(a1), "r"(a2), "r"(a3), "r"(b0), "r"(b1)); }
__device__ __forceinline__ void mma1688(float (&d)[4], uint32_t a0, uint32_t a1, uint32_t b0) {
  asm volatile("mma.sync.aligned.m16n8k8.row.col.f32.bf16.bf16.f32 {%0,%1,%2,%3}, {%4,%5}, {%6}, {%0,%1,%2,%3};"
    : "+f"(d[0]), "+f"(d[1]), "+f"(d[2]), "+f"(d[3]) : "r"(a0), "r"(a1), "r"(b0)); }
__device__ __forceinline__ void ldx128(uint32_t (&r)[4], const void* p) {
  asm volatile("{.reg .b128 t; .reg .b64 a, b; ld.relaxed.gpu.global.b128 t, [%4]; mov.b128 {a, b}, t; mov.b64 {%0,%1}, a; mov.b64 {%2,%3}, b;}"
    : "=r"(r[0]), "=r"(r[1]), "=r"(r[2]), "=r"(r[3]) : "l"(p) : "memory"); }
__device__ __forceinline__ void ldx2x64(uint32_t (&r)[4], const void* p) {
  asm volatile("{.reg .b64 a, b; ld.relaxed.gpu.global.v2.b64 {a, b}, [%4]; mov.b64 {%0,%1}, a; mov.b64 {%2,%3}, b;}"
    : "=r"(r[0]), "=r"(r[1]), "=r"(r[2]), "=r"(r[3]) : "l"(p) : "memory"); }
__device__ __forceinline__ void stx128(void* p, uint32_t r0, uint32_t r1, uint32_t r2, uint32_t r3) {
  asm volatile("{.reg .b128 t; .reg .b64 a, b; mov.b64 a, {%1,%2}; mov.b64 b, {%3,%4}; mov.b128 t, {a, b}; st.relaxed.gpu.global.b128 [%0], t;}"
    :: "l"(p), "r"(r0), "r"(r1), "r"(r2), "r"(r3) : "memory"); }
__device__ __forceinline__ void stx64(void* p, uint32_t r0, uint32_t r1) {
  asm volatile("{.reg .b64 a; mov.b64 a, {%1,%2}; st.relaxed.gpu.global.b64 [%0], a;}" :: "l"(p), "r"(r0), "r"(r1) : "memory"); }
__device__ __forceinline__ uint32_t uni(uint32_t x) { return __shfl_sync(0xffffffffu, x, 0); }
__device__ __forceinline__ uint32_t pin(uint32_t x) { return __shfl_xor_sync(0xffffffffu, x, 0); }
__device__ __forceinline__ float ex2(float x) { float r; asm("ex2.approx.ftz.f32 %0, %1;" : "=f"(r) : "f"(x)); return r; }
__device__ __forceinline__ void wg_fence() { asm volatile("wgmma.fence.sync.aligned;" ::: "memory"); }
__device__ __forceinline__ void wg_commit() { asm volatile("wgmma.commit_group.sync.aligned;" ::: "memory"); }
template <int N> __device__ __forceinline__ void wg_wait() { asm volatile("wgmma.wait_group.sync.aligned %0;" :: "n"(N) : "memory"); }

__device__ __forceinline__ void wgmma_ss_n256_tb1(float (&d)[128], uint64_t da, uint64_t db, int sc) {
  asm volatile("{.reg .pred p; setp.ne.b32 p, %130, 0;\n"
    "wgmma.mma_async.sync.aligned.m64n256k16.f32.bf16.bf16 {%0,%1,%2,%3,%4,%5,%6,%7,%8,%9,%10,%11,%12,%13,%14,%15,%16,%17,%18,%19,%20,%21,%22,%23,%24,%25,%26,%27,%28,%29,%30,%31,%32,%33,%34,%35,%36,%37,%38,%39,%40,%41,%42,%43,%44,%45,%46,%47,%48,%49,%50,%51,%52,%53,%54,%55,%56,%57,%58,%59,%60,%61,%62,%63,%64,%65,%66,%67,%68,%69,%70,%71,%72,%73,%74,%75,%76,%77,%78,%79,%80,%81,%82,%83,%84,%85,%86,%87,%88,%89,%90,%91,%92,%93,%94,%95,%96,%97,%98,%99,%100,%101,%102,%103,%104,%105,%106,%107,%108,%109,%110,%111,%112,%113,%114,%115,%116,%117,%118,%119,%120,%121,%122,%123,%124,%125,%126,%127}, %128, %129, p, 1, 1, 0, 1;}\n"
    : "+f"(d[0]),"+f"(d[1]),"+f"(d[2]),"+f"(d[3]),"+f"(d[4]),"+f"(d[5]),"+f"(d[6]),"+f"(d[7]),"+f"(d[8]),"+f"(d[9]),"+f"(d[10]),"+f"(d[11]),"+f"(d[12]),"+f"(d[13]),"+f"(d[14]),"+f"(d[15]),"+f"(d[16]),"+f"(d[17]),"+f"(d[18]),"+f"(d[19]),"+f"(d[20]),"+f"(d[21]),"+f"(d[22]),"+f"(d[23]),"+f"(d[24]),"+f"(d[25]),"+f"(d[26]),"+f"(d[27]),"+f"(d[28]),"+f"(d[29]),"+f"(d[30]),"+f"(d[31]),"+f"(d[32]),"+f"(d[33]),"+f"(d[34]),"+f"(d[35]),"+f"(d[36]),"+f"(d[37]),"+f"(d[38]),"+f"(d[39]),"+f"(d[40]),"+f"(d[41]),"+f"(d[42]),"+f"(d[43]),"+f"(d[44]),"+f"(d[45]),"+f"(d[46]),"+f"(d[47]),"+f"(d[48]),"+f"(d[49]),"+f"(d[50]),"+f"(d[51]),"+f"(d[52]),"+f"(d[53]),"+f"(d[54]),"+f"(d[55]),"+f"(d[56]),"+f"(d[57]),"+f"(d[58]),"+f"(d[59]),"+f"(d[60]),"+f"(d[61]),"+f"(d[62]),"+f"(d[63]),"+f"(d[64]),"+f"(d[65]),"+f"(d[66]),"+f"(d[67]),"+f"(d[68]),"+f"(d[69]),"+f"(d[70]),"+f"(d[71]),"+f"(d[72]),"+f"(d[73]),"+f"(d[74]),"+f"(d[75]),"+f"(d[76]),"+f"(d[77]),"+f"(d[78]),"+f"(d[79]),"+f"(d[80]),"+f"(d[81]),"+f"(d[82]),"+f"(d[83]),"+f"(d[84]),"+f"(d[85]),"+f"(d[86]),"+f"(d[87]),"+f"(d[88]),"+f"(d[89]),"+f"(d[90]),"+f"(d[91]),"+f"(d[92]),"+f"(d[93]),"+f"(d[94]),"+f"(d[95]),"+f"(d[96]),"+f"(d[97]),"+f"(d[98]),"+f"(d[99]),"+f"(d[100]),"+f"(d[101]),"+f"(d[102]),"+f"(d[103]),"+f"(d[104]),"+f"(d[105]),"+f"(d[106]),"+f"(d[107]),"+f"(d[108]),"+f"(d[109]),"+f"(d[110]),"+f"(d[111]),"+f"(d[112]),"+f"(d[113]),"+f"(d[114]),"+f"(d[115]),"+f"(d[116]),"+f"(d[117]),"+f"(d[118]),"+f"(d[119]),"+f"(d[120]),"+f"(d[121]),"+f"(d[122]),"+f"(d[123]),"+f"(d[124]),"+f"(d[125]),"+f"(d[126]),"+f"(d[127])
    : "l"(da), "l"(db), "r"(sc));
}

__device__ __forceinline__ void wgmma_ss_n128_tb1(float (&d)[64], uint64_t da, uint64_t db, int sc) {
  asm volatile("{.reg .pred p; setp.ne.b32 p, %66, 0;\n"
    "wgmma.mma_async.sync.aligned.m64n128k16.f32.bf16.bf16 {%0,%1,%2,%3,%4,%5,%6,%7,%8,%9,%10,%11,%12,%13,%14,%15,%16,%17,%18,%19,%20,%21,%22,%23,%24,%25,%26,%27,%28,%29,%30,%31,%32,%33,%34,%35,%36,%37,%38,%39,%40,%41,%42,%43,%44,%45,%46,%47,%48,%49,%50,%51,%52,%53,%54,%55,%56,%57,%58,%59,%60,%61,%62,%63}, %64, %65, p, 1, 1, 0, 1;}\n"
    : "+f"(d[0]),"+f"(d[1]),"+f"(d[2]),"+f"(d[3]),"+f"(d[4]),"+f"(d[5]),"+f"(d[6]),"+f"(d[7]),"+f"(d[8]),"+f"(d[9]),"+f"(d[10]),"+f"(d[11]),"+f"(d[12]),"+f"(d[13]),"+f"(d[14]),"+f"(d[15]),"+f"(d[16]),"+f"(d[17]),"+f"(d[18]),"+f"(d[19]),"+f"(d[20]),"+f"(d[21]),"+f"(d[22]),"+f"(d[23]),"+f"(d[24]),"+f"(d[25]),"+f"(d[26]),"+f"(d[27]),"+f"(d[28]),"+f"(d[29]),"+f"(d[30]),"+f"(d[31]),"+f"(d[32]),"+f"(d[33]),"+f"(d[34]),"+f"(d[35]),"+f"(d[36]),"+f"(d[37]),"+f"(d[38]),"+f"(d[39]),"+f"(d[40]),"+f"(d[41]),"+f"(d[42]),"+f"(d[43]),"+f"(d[44]),"+f"(d[45]),"+f"(d[46]),"+f"(d[47]),"+f"(d[48]),"+f"(d[49]),"+f"(d[50]),"+f"(d[51]),"+f"(d[52]),"+f"(d[53]),"+f"(d[54]),"+f"(d[55]),"+f"(d[56]),"+f"(d[57]),"+f"(d[58]),"+f"(d[59]),"+f"(d[60]),"+f"(d[61]),"+f"(d[62]),"+f"(d[63])
    : "l"(da), "l"(db), "r"(sc));
}

template <int BN> struct WG;
template <> struct WG<256> { static __device__ __forceinline__ void mma(float (&d)[128], uint64_t a, uint64_t b, int sc) { wgmma_ss_n256_tb1(d, a, b, sc); } };
template <> struct WG<128> { static __device__ __forceinline__ void mma(float (&d)[64], uint64_t a, uint64_t b, int sc) { wgmma_ss_n128_tb1(d, a, b, sc); } };

struct GemmMaps { CUtensorMap a, b[3], c; };
template <int BN, int STAGES>
__global__ void __cluster_dims__(2, 1, 1) __launch_bounds__(384, 1)
gemm_kernel(const __grid_constant__ GemmMaps maps, int tilesM, int tilesN, int kblocks, int nPerB, uint4* __restrict__ clearX) {
  extern __shared__ __align__(1024) uint8_t smem_raw[];
  constexpr int STAGE_BYTES = 16384 + BN * 128;
  constexpr int NBOX = BN / 64;
  const uint32_t sbase = (smem_u32(smem_raw) + 1023) & ~1023u;
  const uint32_t sEpi = sbase + STAGES * STAGE_BYTES;
  const uint32_t sBar = sEpi + 32768;
  const int warp = threadIdx.x >> 5, lane = threadIdx.x & 31, wg = warp >> 2;
  uint32_t crank; asm("mov.u32 %0, %%cluster_ctarank;" : "=r"(crank));
  if (threadIdx.x == 0) {
    for (int i = 0; i < STAGES; i++) { mbar_init(sBar + 8 * i, 1); mbar_init(sBar + 8 * (STAGES + i), 4); }
    asm volatile("fence.mbarrier_init.release.cluster;" ::: "memory");
  }
  for (int i = blockIdx.x * 384 + threadIdx.x; i < (int)(sizeof(Xchg) / 16); i += gridDim.x * 384) clearX[i] = make_uint4(0, 0, 0, 0);
  asm volatile("barrier.cluster.arrive.release.aligned; barrier.cluster.wait.acquire.aligned;" ::: "memory");
  const int npairs = (tilesM >> 1) * tilesN, pair0 = blockIdx.x >> 1, pstep = gridDim.x >> 1;
  if (wg == 2) {
    asm volatile("setmaxnreg.dec.sync.aligned.u32 40;");
    if (warp == 8 && lane == 0) {
      int st = 0, ph = 1;
      for (int p = pair0; p < npairs; p += pstep) {
        const int tm = (p % (tilesM >> 1)) * 2 + crank, tn = p / (tilesM >> 1);
        const CUtensorMap* mb = &maps.b[tn / nPerB];
        const int n0 = (tn % nPerB) * BN;
        for (int kb = 0; kb < kblocks; kb++) {
          mbar_wait(sBar + 8 * (STAGES + st), ph);
          const uint32_t a = sbase + st * STAGE_BYTES, full = sBar + 8 * st;
          mbar_expect_tx(full, STAGE_BYTES);
          tma2d(a, &maps.a, kb * 64, tm * 128, full);
#pragma unroll
          for (int i = 0; i < NBOX / 2; i++) {
            const int bx = crank * (NBOX / 2) + i;
            tma2d_mc(a + 16384 + bx * 8192, mb, n0 + bx * 64, kb * 64, full, (uint16_t)3);
          }
          if (++st == STAGES) { st = 0; ph ^= 1; }
        }
      }
      for (int i = 0; i < STAGES; i++) { mbar_wait(sBar + 8 * (STAGES + st), ph); if (++st == STAGES) { st = 0; ph ^= 1; } }
    }
  } else {
    asm volatile("setmaxnreg.inc.sync.aligned.u32 232;");
    int st = 0, ph = 0;
    float acc[BN / 2];
    const uint64_t descA0 = (uint64_t)(((sbase + wg * 8192) & 0x3FFFF) >> 4) | (1ull << 16) | (64ull << 32) | (1ull << 62);
    const uint64_t descB0 = (uint64_t)(((sbase + 16384) & 0x3FFFF) >> 4) | (512ull << 16) | (64ull << 32) | (1ull << 62);
    const uint32_t epi = sEpi + wg * 16384;
    for (int p = pair0; p < npairs; p += pstep) {
      const int tm = (p % (tilesM >> 1)) * 2 + crank, tn = p / (tilesM >> 1);
      int prev = -1;
      for (int kb = 0; kb < kblocks; kb++) {
        mbar_wait(sBar + 8 * st, ph);
        wg_fence();
        const uint64_t so = (uint64_t)(st * (STAGE_BYTES >> 4));
#pragma unroll
        for (int k = 0; k < 4; k++) WG<BN>::mma(acc, descA0 + so + k * 2, descB0 + so + k * 128, kb | k);
        wg_commit();
        if (prev >= 0) {
          wg_wait<1>();
          if ((threadIdx.x & 127) < 2) mbar_arrive_cluster(sBar + 8 * (STAGES + prev), threadIdx.x & 1);
        }
        prev = st;
        if (++st == STAGES) { st = 0; ph ^= 1; }
      }
      wg_wait<0>();
      if ((threadIdx.x & 127) < 2) mbar_arrive_cluster(sBar + 8 * (STAGES + prev), threadIdx.x & 1);
#pragma unroll
      for (int r = 0; r < BN / 128; r++) {
        if ((threadIdx.x & 127) == 0) asm volatile("cp.async.bulk.wait_group.read 0;" ::: "memory");
        bar_sync(1 + wg, 128);
        const int row = (warp & 3) * 16 + (lane & 15);
#pragma unroll
        for (int i = 0; i < 8; i++) {
          const int c = 2 * (i & 3) + (lane >> 4);
          const float* q = &acc[r * 64 + i * 8];
          stsm4(epi + (i >> 2) * 8192 + row * 128 + ((c ^ (row & 7)) << 4), pack2(q[0], q[1]), pack2(q[2], q[3]), pack2(q[4], q[5]), pack2(q[6], q[7]));
        }
        fence_async();
        bar_sync(1 + wg, 128);
        if ((threadIdx.x & 127) == 0) {
          tma2d_store(&maps.c, epi, tn * BN + r * 128, tm * 128 + wg * 64);
          tma2d_store(&maps.c, epi + 8192, tn * BN + r * 128 + 64, tm * 128 + wg * 64);
          asm volatile("cp.async.bulk.commit_group;" ::: "memory");
        }
      }
    }
    if ((threadIdx.x & 127) == 0) asm volatile("cp.async.bulk.wait_group 0;" ::: "memory");
  }
}

struct Dft { uint32_t m[2][2][2][4]; };
template <bool P4> __device__ __forceinline__ int fidx(int tile, int x) { return P4 ? 4 * (x >> 1) + 2 * (tile & 1) + (x & 1) + 16 * (tile >> 1) : x + 8 * tile; }
__device__ __forceinline__ float2 cis(int k, int n) {
  k &= n - 1; if (2 * k > n) k -= n;
  const float a = (float)k * (6.283185307179586f / (float)n);
  return make_float2(__cosf(a), __sinf(a));
}
template <bool OUT4> __device__ __forceinline__ void make_dft(Dft& D, int g, int t) {
#pragma unroll
  for (int q = 0; q < 16; q++) {
    const int b = q >> 3, u = (q >> 2) & 1, r = (q >> 1) & 1, v = q & 1;
    const float2 w = cis(fidx<OUT4>(v, g) * fidx<false>(2 * u + r, 2 * t + b), 32);
    D.m[b][u][0][q & 3] = pack2(w.x, w.y); D.m[b][u][1][q & 3] = pack2(-w.y, w.x);
  }
}
__device__ __forceinline__ void mma_dc(float (&d)[4], uint32_t a0, uint32_t a1, uint32_t a2, uint32_t a3, uint32_t b0, uint32_t b1, const float (&c)[4]) {
  asm("mma.sync.aligned.m16n8k16.row.col.f32.bf16.bf16.f32 {%0,%1,%2,%3}, {%4,%5,%6,%7}, {%8,%9}, {%10,%11,%12,%13};"
    : "=f"(d[0]), "=f"(d[1]), "=f"(d[2]), "=f"(d[3]) : "r"(a0), "r"(a1), "r"(a2), "r"(a3), "r"(b0), "r"(b1), "f"(c[0]), "f"(c[1]), "f"(c[2]), "f"(c[3])); }
__device__ __forceinline__ void dft_b(const Dft& D, const uint32_t (&x)[2][4], float (&o)[2][8]) {
#pragma unroll
  for (int ri = 0; ri < 2; ri++) {
    float z[4] = {0.f, 0.f, 0.f, 0.f}, e[4], p[4];
    mma_dc(e, D.m[0][0][ri][0], D.m[0][0][ri][1], D.m[0][0][ri][2], D.m[0][0][ri][3], x[0][0], x[0][1], z);
    mma_dc(e, D.m[0][1][ri][0], D.m[0][1][ri][1], D.m[0][1][ri][2], D.m[0][1][ri][3], x[0][2], x[0][3], e);
    mma_dc(p, D.m[1][0][ri][0], D.m[1][0][ri][1], D.m[1][0][ri][2], D.m[1][0][ri][3], x[1][0], x[1][1], e);
    mma_dc(p, D.m[1][1][ri][0], D.m[1][1][ri][1], D.m[1][1][ri][2], D.m[1][1][ri][3], x[1][2], x[1][3], p);
#pragma unroll
    for (int q = 0; q < 4; q++) { o[ri][q] = p[q]; o[ri][4 + q] = fmaf(2.f, e[q], -p[q]); }
  }
}
__device__ __forceinline__ void dft_a(const uint32_t (&m)[2][2][4], const uint32_t (&x0)[2][4], const uint32_t (&x1)[2][4], float (&o)[2][8]) {
#pragma unroll
  for (int ri = 0; ri < 2; ri++) {
    float z[4] = {0.f, 0.f, 0.f, 0.f}, e[4], p[4];
    mma_dc(e, x0[0][0], x1[0][0], x0[0][1], x1[0][1], m[0][ri][0], m[0][ri][1], z);
    mma_dc(e, x0[0][2], x1[0][2], x0[0][3], x1[0][3], m[0][ri][2], m[0][ri][3], e);
    mma_dc(p, x0[1][0], x1[1][0], x0[1][1], x1[1][1], m[1][ri][0], m[1][ri][1], e);
    mma_dc(p, x0[1][2], x1[1][2], x0[1][3], x1[1][3], m[1][ri][2], m[1][ri][3], p);
#pragma unroll
    for (int q = 0; q < 4; q++) { o[ri][q] = p[q]; o[ri][4 + q] = fmaf(2.f, e[q], -p[q]); }
  }
}
__device__ __forceinline__ uint32_t twid(float re, float im, float c, float s) { return pack2(fmaf(re, c, im * s), fmaf(im, c, -re * s)); }
__device__ __forceinline__ void cpa16(uint32_t d, const void* s) { asm volatile("cp.async.cg.shared.global [%0], [%1], 16;" :: "r"(d), "l"(s) : "memory"); }
__device__ __forceinline__ void sts32(uint32_t a, uint32_t x) { asm volatile("st.shared.u32 [%0], %1;" :: "r"(a), "r"(x) : "memory"); }
__device__ __forceinline__ void cpa_commit() { asm volatile("cp.async.commit_group;" ::: "memory"); }
template <int N> __device__ __forceinline__ void cpa_wait() { asm volatile("cp.async.wait_group %0;" :: "n"(N) : "memory"); }
__device__ __forceinline__ uint32_t lds32(uint32_t a) { uint32_t r; asm volatile("ld.shared.u32 %0, [%1];" : "=r"(r) : "r"(a) : "memory"); return r; }
#define FMID 0
constexpr int F_TP = 4112, F_TSZ = 8 * F_TP;

__device__ __forceinline__ uint32_t ldnc32(const void* p) { uint32_t v; asm volatile("ld.global.nc.b32 %0, [%1];" : "=r"(v) : "l"(p) : "memory"); return v; }
template <class F>
__device__ __forceinline__ void fft_wprep(const bf16* __restrict__ wr, const bf16* __restrict__ wi, int cta, F&& mid) {
  const int tid = threadIdx.x, g = (cta >> 1) & 7, c = (cta >> 4) & 3, t = 2 * (cta & 1) + (tid & 1);
  const int k0 = g + 8 * (cta >> 6) + 32 * (8 * c + 2 * t), l0 = (tid & ~1) + (g & 1);
  uint32_t a[4][4], b[4][4];
#pragma unroll
  for (int q = 0; q < 16; q++) {
    const int o = (k0 + 16 * (q >> 3) + 32 * ((q >> 1) & 1) + 1024 * (q & 1)) * 513 + l0 + 256 * ((q >> 2) & 1);
    a[q >> 2][q & 3] = ldnc32(wr + o);
    b[q >> 2][q & 3] = ldnc32(wi + o);
  }
  const int e = cta * 32 + (tid & 31), lh = (e >> 11) * 512, k = e & 2047, k2 = (k >> 5) & 31;
  uint32_t hz[4];
#pragma unroll
  for (int q = 0; q < 4; q++) asm volatile("ld.global.nc.u16 %0, [%1];" : "=r"(hz[q]) : "l"((q < 2 ? wr : wi) + (q & 1 ? (2048 - k) & 2047 : k) * 513 + lh) : "memory");
  mid();
  uint4* dst = g_wt + l0 * 512 + cta * 2 + (tid & 1);
#pragma unroll
  for (int q = 0; q < 8; q++) {
    const int hf = q >> 1, l = l0 + 256 * (hf & 1) + (q & 1);
    const uint32_t sel = (q & 1) ? 0x7632 : 0x5410;
    if (l & 511) dst[(256 * (hf & 1) + (q & 1)) * 512 + 256 * (q >> 2)] = make_uint4(__byte_perm(a[hf][0], b[hf][0], sel), __byte_perm(a[hf][1], b[hf][1], sel),
                                                                                   __byte_perm(a[hf][2], b[hf][2], sel), __byte_perm(a[hf][3], b[hf][3], sel));
  }
  if (tid < 32) reinterpret_cast<uint32_t*>(g_wt)[(64 * ((k >> 3) & 3) + 16 * (k2 >> 3) + 2 * (k & 7) + ((k2 >> 2) & 1)) * 8 + lh * 2048 + 2 * (k2 & 3) + (k >> 10)] =
      pack2(0.5f * (__uint_as_float(hz[0] << 16) + __uint_as_float(hz[1] << 16)), 0.5f * (__uint_as_float(hz[2] << 16) - __uint_as_float(hz[3] << 16)));
}

template <class F>
__device__ __forceinline__ void fft_rows_fwd(const bf16* __restrict__ x, const bf16* __restrict__ wr, const bf16* __restrict__ wi, uint32_t tb, int it, F&& mid) {
  const int warp = threadIdx.x >> 5, lane = threadIdx.x & 31, g = lane >> 2, t = lane & 3;
  const uint32_t in = tb + warp * 4096;
  const uint32_t f0 = in + (lane >> 3) * 256 + (((lane & 7) ^ (2 * (lane >> 3))) << 4);
  const bf16* src = x + ((256 * (warp & 3) + 64 * (warp >> 2) + 128 * (it & 1) + 32 * ((it >> 4) & 1) + 8 * (it >> 5) + ((it >> 1) & 7)) * 2048 + lane * 8);
#pragma unroll
  for (int q = 0; q < 8; q++) cpa16((f0 ^ ((q >> 2) * 144)) + (q & 3) * 1024, src + q * 256);
  cpa_commit();
  Dft D;
  float2 tw[4][8];
  fft_wprep(wr, wi, it, [&]() {
    if (FMID == 0) mid();
    make_dft<true>(D, g, t);
#pragma unroll
    for (int q = 0; q < 32; q++) {
      tw[q >> 3][q & 7] = cis(fidx<true>((q >> 1) & 3, g) * fidx<false>(q >> 3, 2 * t + (q & 1)), 1024);
      if (FMID) asm volatile("" : "+f"(tw[q >> 3][q & 7].x), "+f"(tw[q >> 3][q & 7].y) :: "memory");
    }
    if (FMID == 1) mid();
  });
  if (FMID == 2) mid();
  cpa_wait<0>(); __syncwarp();
  uint32_t a[4][2][4], y[4][2][4];
#pragma unroll
  for (int q = 0; q < 8; q++) ldsm4t(a[q & 3][q >> 2], (in + lane * 128 + ((lane & 7) << 4)) ^ (q << 4));
  float o[2][8];
#pragma unroll
  for (int i = 0; i < 4; i++) {
    dft_b(D, a[i], o);
#pragma unroll
    for (int q = 0; q < 8; q++) y[q >> 1][q & 1][i] = twid(o[0][q], o[1][q], tw[i][q].x, tw[i][q].y);
  }
  __syncthreads();
  const uint32_t w0 = tb + warp * F_TP + fidx<true>(0, g) * 128 + t * 16 + ((g & 1) << 6), wz = (g & 1) ? -64 : 64;
#pragma unroll
  for (int z = 0; z < 2; z++) {
    float o2[2][8];
    dft_b(D, y[2 * z], o); dft_b(D, y[2 * z + 1], o2);
#pragma unroll
    for (int i = 0; i < 4; i++) {
      const float sg = i < 2 ? 1.f : -1.f;
      sts128(w0 + z * wz + fidx<true>(i, 0) * 128, pack2(o[0][2 * i], sg * o[1][2 * i]), pack2(o[0][2 * i + 1], sg * o[1][2 * i + 1]),
             pack2(o2[0][2 * i], sg * o2[1][2 * i]), pack2(o2[0][2 * i + 1], sg * o2[1][2 * i + 1]));
    }
  }
  __syncthreads();
  const uint32_t ra = tb + (lane & 1) * 4 * F_TP + ((lane >> 1) + 16 * (warp ^ ((warp >> 1) & 1))) * 4;
  uint4* dst = g_y + (threadIdx.x >> 1) * 256 + (lane & 1) + it * 2;
#pragma unroll
  for (int q = 0; q < 8; q++) { const uint32_t r = ra + q * 512; dst[q * 32768] = make_uint4(lds32(r), lds32(r + F_TP), lds32(r + 2 * F_TP), lds32(r + 3 * F_TP)); }
}

__device__ __forceinline__ void fft_cols(uint32_t sb, int cta, int ncta) {
  const int warp = threadIdx.x >> 5, lane = threadIdx.x & 31, g = lane >> 2, t = lane & 3;
  const uint32_t in = sb + warp * 16384 + lane * 16, tab = sb + 131072 + lane * 16;
  auto fetch_y = [&](int l) {
#pragma unroll
    for (int q = 0; q < 16; q++) cpa16(in + q * 512, g_y + (q < 8 ? l : (1024 - l) & 1023) * 256 + (q & 7) * 32 + lane);
  };
  auto fetch_w = [&](int l) {
#pragma unroll
    for (int q = 0; q < 16; q++) cpa16(in + 8192 + q * 512, g_wt + l * 512 + q * 32 + lane);
  };
  const int l0 = cta * 8 + warp, dl = ncta * 8;
  if (l0 <= 512) fetch_y(l0);
  cpa_commit();
  if (l0 <= 512) fetch_w(l0);
  cpa_commit();
  Dft D; make_dft<false>(D, g, t);
#pragma unroll
  for (int q = 2 * warp; q < 2 * warp + 2; q++) {
    const int r = fidx<false>(q & 3, g), c = fidx<false>(q >> 2, 2 * t);
    const float2 w0 = cis(r * c, 1024), w1 = cis(r * c + r, 1024), p0 = cis(r + 32 * c, 2048), p1 = cis(r + 32 * c + 32, 2048);
    sts128(tab + q * 512, __float_as_uint(w0.x), __float_as_uint(w0.y), __float_as_uint(w1.x), __float_as_uint(w1.y));
    sts128(tab + 8192 + q * 512, __float_as_uint(p0.x), __float_as_uint(p0.y), __float_as_uint(p1.x), __float_as_uint(p1.y));
  }
  if (warp == 0) {
#pragma unroll
    for (int q = 0; q < 8; q++) {
      const int v = q >> 2, b = (q >> 1) & 1, ri = q & 1;
      sts128(tab + 16384 + q * 512, D.m[b][0][ri][v], D.m[b][0][ri][v + 2], D.m[b][1][ri][v], D.m[b][1][ri][v + 2]);
    }
  }
  __syncthreads();
#pragma unroll 1
  for (int l = l0; l <= 512; l += dl) {
    uint32_t a[2][4][2][4], y[2][4][2][4];
    float o[2][2][8];
    cpa_wait<1>();
#pragma unroll
    for (int q = 0; q < 16; q++) lds128(a[q >> 3][(q >> 1) & 3][q & 1], in + q * 512);
    if (!(l & 511)) {
      const uint32_t m0 = l ? 0x80000000u : 0u;
#pragma unroll
      for (int q = 0; q < 32; q++) { a[0][q >> 3][(q >> 2) & 1][q & 3] ^= m0; a[1][q >> 3][(q >> 2) & 1][q & 3] ^= m0 ^ 0x80000000u; }
    }
    auto first = [&]() {
#pragma unroll
      for (int i = 0; i < 4; i++) {
        dft_b(D, a[0][i], o[0]); dft_b(D, a[1][i], o[1]);
#pragma unroll
        for (int r = 0; r < 4; r++) {
          const float4 w = lds128f(tab + (4 * i + r) * 512);
#pragma unroll
          for (int s = 0; s < 2; s++) {
            y[s][r][0][i] = twid(o[s][0][2 * r], o[s][1][2 * r], w.x, w.y);
            y[s][r][1][i] = twid(o[s][0][2 * r + 1], o[s][1][2 * r + 1], w.z, w.w);
          }
        }
      }
    };
    first();
    if (l + dl <= 512) fetch_y(l + dl);
    cpa_commit();
    cpa_wait<1>();
#pragma unroll
    for (int zv = 0; zv < 4; zv++) {
      const int z = zv >> 1, v = zv & 1;
      uint32_t m[2][2][4];
#pragma unroll
      for (int q = 0; q < 4; q++) lds128(m[q >> 1][q & 1], tab + 16384 + (4 * v + q) * 512);
      dft_a(m, y[0][2 * z], y[0][2 * z + 1], o[0]); dft_a(m, y[1][2 * z], y[1][2 * z + 1], o[1]);
#pragma unroll
      for (int q = 0; q < 4; q++) {
        const int i = 2 * z + (q & 1), c = v + (q & 2);
        uint32_t w[4]; lds128(w, in + 8192 + (4 * i + c) * 512);
        const float4 ph = lds128f(tab + 8192 + (4 * c + i) * 512);
#pragma unroll
        for (int b = 0; b < 2; b++) {
          const float cs = b ? ph.z : ph.x, sn = b ? ph.w : ph.y;
          const float r1 = __uint_as_float(w[2 * b] << 16), i1 = __uint_as_float(w[2 * b] & 0xFFFF0000u);
          const float r2 = __uint_as_float(w[2 * b + 1] << 16), i2 = __uint_as_float(w[2 * b + 1] & 0xFFFF0000u);
          const float Sr = r1 + r2, Si = i1 + i2, Dr = r1 - r2, Di = i1 - i2;
          const float ar = fmaf(-Dr, sn, Sr), ai = fmaf(-Di, sn, Si), dr = fmaf(Dr, sn, Sr), di = fmaf(Di, sn, Si), br = -Di * cs, bi = Dr * cs;
          const float Ar = o[0][0][2 * q + b], Ai = o[0][1][2 * q + b], Br = o[1][0][2 * q + b], Bi = o[1][1][2 * q + b];
          a[0][i][b][c] = pack2(fmaf(ar, Ai, fmaf(ai, Ar, fmaf(br, Bi, bi * Br))), fmaf(ar, Ar, fmaf(-ai, Ai, fmaf(br, Br, -bi * Bi))));
          a[1][i][b][c] = pack2(fmaf(dr, Bi, fmaf(di, Br, fmaf(-br, Ai, -bi * Ar))), fmaf(dr, Br, fmaf(-di, Bi, fmaf(-br, Ar, bi * Ai))));
        }
      }
    }
    if (l + dl <= 512) fetch_w(l + dl);
    cpa_commit();
    first();
#pragma unroll
    for (int s = 0; s < 2; s++) {
      uint4* dst = g_y + (s ? (1024 - l) & 1023 : l) * 256 + lane;
      const float sg = s ? -1.f : 1.f;
#pragma unroll
      for (int i = 0; i < 4; i++) {
        dft_b(D, y[s][i], o[0]);
#pragma unroll
        for (int b = 0; b < 2; b++)
          dst[(2 * i + b) * 32] = make_uint4(pack2(sg * o[0][0][b], o[0][1][b]), pack2(sg * o[0][0][2 + b], o[0][1][2 + b]),
                                             pack2(sg * o[0][0][4 + b], o[0][1][4 + b]), pack2(sg * o[0][0][6 + b], o[0][1][6 + b]));
      }
    }
  }
}

__device__ __forceinline__ void fft_rows_inv(const CUtensorMap* om, uint32_t sb, int cta, int ncta) {
  const int warp = threadIdx.x >> 5, lane = threadIdx.x & 31, g = lane >> 2, t = lane & 3, wg = warp >> 2, w4 = warp & 3;
  const uint32_t tb = sb + 32768 + wg * 2 * F_TSZ;
  const uint4* src = g_y + pin((256 * ((lane >> 1) & 3) + 64 * (lane >> 3) + 8 * w4) * 256 + (lane & 1));
  const uint32_t wa = pin(tb + (lane & 1) * 4 * F_TP + w4 * 1024 + (lane >> 1) * 4);
  uint4 pf[8];
  auto fetch = [&](int it, int hf) {
#pragma unroll
    for (int q = 0; q < 8; q++) pf[q] = __ldcg(src + (it * 2 + hf * 8192) + q * 256);
  };
  auto put = [&](uint32_t off) {
#pragma unroll
    for (int q = 0; q < 8; q++) {
      sts32(wa + off + q * 64, pf[q].x); sts32(wa + off + q * 64 + F_TP, pf[q].y);
      sts32(wa + off + q * 64 + 2 * F_TP, pf[q].z); sts32(wa + off + q * 64 + 3 * F_TP, pf[q].w);
    }
  };
  const int it0 = 2 * cta + wg;
  if (it0 >= 128) return;
  fetch(it0, 0); put(0); fetch(it0, 1); put(512);
  Dft D; make_dft<false>(D, g, t);
  float2 tw[4][8];
#pragma unroll
  for (int q = 0; q < 32; q++) {
    tw[q >> 3][q & 7] = cis(fidx<false>((q >> 1) & 3, g) * fidx<false>(q >> 3, 2 * t + (q & 1)), 1024);
    tw[q >> 3][q & 7].x *= 1.f / 2097152.f; tw[q >> 3][q & 7].y *= 1.f / 2097152.f;
  }
  const uint32_t la = pin(tb + w4 * F_TP + lane * 16), ob = uni(sb + warp * 4096);
  const uint32_t oa = pin(ob + (lane >> 1) * 128 + (((4 * (lane & 1)) ^ ((lane >> 1) & 7)) << 4));
#pragma unroll 1
  for (int n = 0;; n++) {
    const int it = it0 + (n >> 1) * 2 * ncta, hf = n & 1, buf = (n >> 1) & 1;
    if (it >= 128) break;
    if (!hf) bar_sync(1 + wg, 128);
    uint32_t a[4][2][4], y[4][2][4];
#pragma unroll
    for (int q = 0; q < 8; q++) lds128(a[q >> 1][q & 1], la + buf * F_TSZ + hf * 4 * F_TP + q * 512);
    fetch(min(it + 2 * ncta, 127), hf);
    float o[2][8];
#pragma unroll
    for (int i = 0; i < 4; i++) {
      dft_b(D, a[i], o);
#pragma unroll
      for (int q = 0; q < 8; q++) y[q >> 1][q & 1][i] = twid(o[0][q], o[1][q], tw[i][q].x, tw[i][q].y);
    }
    if (lane == 0) asm volatile("cp.async.bulk.wait_group.read 0;" ::: "memory");
    __syncwarp();
#pragma unroll
    for (int c = 0; c < 4; c++) {
      dft_b(D, y[c], o);
#pragma unroll
      for (int ri = 0; ri < 2; ri++)
        stsm4((oa ^ (c << 4)) + (1 - ri) * 2048, pack2(o[ri][0], o[ri][1]), pack2(o[ri][2], o[ri][3]), pack2(o[ri][4], o[ri][5]), pack2(o[ri][6], o[ri][7]));
    }
    fence_async();
    __syncwarp();
    if (lane == 0) {
      const int m = 256 * w4 + 32 * ((it >> 1) & 7) + 8 * (it >> 5) + 4 * (it & 1) + 2 * hf + ((it >> 4) & 1);
      asm volatile("cp.async.bulk.tensor.3d.global.shared::cta.bulk_group [%0, {0, 0, %2}], [%1];" :: "l"(om), "r"(ob), "r"(2 * m) : "memory");
      asm volatile("cp.async.bulk.commit_group;" ::: "memory");
    }
    put((buf ^ 1) * F_TSZ + hf * 512);
  }
  if (lane == 0) asm volatile("cp.async.bulk.wait_group 0;" ::: "memory");
}
__device__ __forceinline__ void grid_arrive(unsigned* ctr) {
  __syncthreads();
  if (threadIdx.x == 0) { __threadfence(); atomicAdd(ctr, 1u); }
}
__device__ __forceinline__ void grid_wait(unsigned* ctr, unsigned n) {
  if (threadIdx.x == 0) {
    int it = 0;
    while (*reinterpret_cast<volatile unsigned*>(ctr) < n) { __nanosleep(200); if (++it > SPIN_LIMIT) { g_err = 3; break; } }
    __threadfence();
  }
  __syncthreads();
}

struct RecMaps { CUtensorMap wq, wk, wv, wo, x, k, q, v, fo; };
#define NSW 16
#define EXP 0
#define NPB 2
#define NPC 0
#define WOP 2
#define HOME 7
#define DL0 14
#define PD1 4
#define NE4 6
#define NE6 0
#define NA4 14
#define NA6 18
#define NB1 24
#define TQL 7
#define NQ 16
#define TQP (NQ - 1)
#define OXPOS 4
#define KVPOS 2
#define NK0 0
#define FLPOS 1
#define XWPOS 10
#define FSPOS 28
#define RL0 4
#define RLS 6
#define RLB 4
#define VL0 3
#define RI 9
#define RJ 8
#define NPRE 22
#define PFD 4
#define PD0 4
#define VB NV0
#define NPA 0
#define N1 16
#define DL1 16
#define PACE 0
#define RE0 0
#define RE1 0
#define RP1 23
#define UNP 1
#define X2 2
#define X3 2
#define SPOS 2
#ifndef NV0
#define NV0 4
#endif
#define TGP 3
#define FENP 0
#define LW0 8
#define X1 4
#define X0 4
constexpr int R_WO = 0, R_X = 65536, R_MEM = 131072, R_WC = 147456, R_RED = R_WC + NSW * 2048, R_O = R_RED, R_S = R_O + 2048, R_P = R_S + 3072, R_STAGE = R_P + 2048,
              R_K = R_STAGE + 8192, R_Q = R_K + 8192, R_V = R_Q + 2048, R_ID = R_V + 16384, R_T = R_ID + 512, R_DST = R_T + 512, R_RD = R_DST + 2048, R_BAR = R_RD + 2048, R_TS = R_BAR + 128,
              R_TOTAL = R_TS;
#define TS(i)
#define LOG(i, v)
constexpr int B_KV = R_BAR, B_W = R_BAR + 8, B_X = R_BAR + 80, B_PK = R_BAR + 24, B_C = R_BAR + 32, B_B = R_BAR + 40, B_DUE = R_BAR + 48, B_ONE = R_BAR + 64;
#define DLY_A 150
#define DLY_V 150
#define DLY_C 200
#define DLY_L 90
#define NS_B 1088
#define NS_C 1728
#define NS_P 2656
#define NS_V 128
#define NS_F 896
#define NS_K 128
#define NS_M 32
#define NS_X 128
#define NS_Z 192
#define NS_Y 704
#define NS_PEN 1024
__device__ __forceinline__ float rcp(float x) { float r; asm("rcp.approx.ftz.f32 %0, %1;" : "=f"(r) : "f"(x)); return r; }
__device__ __forceinline__ uint32_t movm(uint32_t a) { uint32_t d; asm volatile("movmatrix.sync.aligned.m8n8.trans.b16 %0, %1;" : "=r"(d) : "r"(a)); return d; }
__device__ __forceinline__ uint32_t hadd2(uint32_t a, uint32_t b) { uint32_t d; asm("add.rn.bf16x2 %0, %1, %2;" : "=r"(d) : "r"(a), "r"(b)); return d; }
__device__ __forceinline__ void mma_a(float (&d)[4], const uint32_t (&a)[4], uint32_t b0, uint32_t b1) { mma16816(d, a[0], a[1], a[2], a[3], b0, b1); }
__device__ __forceinline__ bool elect() {
  uint32_t p; asm volatile("{.reg .pred p; elect.sync _|p, 0xffffffff; selp.u32 %0, 1, 0, p;}" : "=r"(p)); return p; }
__device__ __forceinline__ void tma3d(uint32_t dst, const CUtensorMap* m, int c1, int c2, uint32_t bar) {
  asm volatile("cp.async.bulk.tensor.3d.shared::cluster.global.mbarrier::complete_tx::bytes [%0], [%1, {0, %3, %4}], [%2];"
    :: "r"(dst), "l"(m), "r"(bar), "r"(c1), "r"(c2) : "memory"); }
__device__ __forceinline__ void tma4d(uint32_t dst, const CUtensorMap* m, int c1, int c2, uint32_t bar) {
  asm volatile("cp.async.bulk.tensor.4d.shared::cluster.global.mbarrier::complete_tx::bytes [%0], [%1, {0, %3, %4, 0}], [%2];"
    :: "r"(dst), "l"(m), "r"(bar), "r"(c1), "r"(c2) : "memory"); }
template <int OFF, int ACC>
__device__ __forceinline__ void wg_rs32(float (&d)[16], const uint32_t (&a)[4], uint32_t db) {
  if (ACC)
    asm volatile("{.reg .b64 db; .reg .b32 lo; add.u32 lo, %20, %21; mov.b64 db, {lo, 0x40000040};\n"
      "wgmma.mma_async.sync.aligned.m64n32k16.f32.bf16.bf16 {%0,%1,%2,%3,%4,%5,%6,%7,%8,%9,%10,%11,%12,%13,%14,%15}, {%16,%17,%18,%19}, db, 1, 1, 1, 0;}"
      : "+f"(d[0]), "+f"(d[1]), "+f"(d[2]), "+f"(d[3]), "+f"(d[4]), "+f"(d[5]), "+f"(d[6]), "+f"(d[7]), "+f"(d[8]), "+f"(d[9]), "+f"(d[10]), "+f"(d[11]), "+f"(d[12]), "+f"(d[13]), "+f"(d[14]), "+f"(d[15])
      : "r"(a[0]), "r"(a[1]), "r"(a[2]), "r"(a[3]), "r"(db), "n"(OFF));
  else
    asm volatile("{.reg .b64 db; .reg .b32 lo; add.u32 lo, %20, %21; mov.b64 db, {lo, 0x40000040};\n"
      "wgmma.mma_async.sync.aligned.m64n32k16.f32.bf16.bf16 {%0,%1,%2,%3,%4,%5,%6,%7,%8,%9,%10,%11,%12,%13,%14,%15}, {%16,%17,%18,%19}, db, 0, 1, 1, 0;}"
      : "=f"(d[0]), "=f"(d[1]), "=f"(d[2]), "=f"(d[3]), "=f"(d[4]), "=f"(d[5]), "=f"(d[6]), "=f"(d[7]), "=f"(d[8]), "=f"(d[9]), "=f"(d[10]), "=f"(d[11]), "=f"(d[12]), "=f"(d[13]), "=f"(d[14]), "=f"(d[15])
      : "r"(a[0]), "r"(a[1]), "r"(a[2]), "r"(a[3]), "r"(db), "n"(OFF));
}
template <int I> using IC = std::integral_constant<int, I>;
template <int I, int N, class F> __device__ __forceinline__ void sfor(F&& f) {
  if constexpr (I < N) { f(std::integral_constant<int, I>{}); sfor<I + 1, N>(f); }
}
__device__ __forceinline__ void keep(float (&d)[16]) {
  asm volatile("" : "+f"(d[0]), "+f"(d[1]), "+f"(d[2]), "+f"(d[3]), "+f"(d[4]), "+f"(d[5]), "+f"(d[6]), "+f"(d[7]),
      "+f"(d[8]), "+f"(d[9]), "+f"(d[10]), "+f"(d[11]), "+f"(d[12]), "+f"(d[13]), "+f"(d[14]), "+f"(d[15]) :: "memory");
}

template <int N, int S2 = 1024> __device__ __forceinline__ void ldx(uint32_t (&v)[N][4], const uint8_t* p) {
#pragma unroll
  for (int k = 0; k < 2 * N; k++) {
    const int i = k;
    asm volatile("ld.relaxed.gpu.global.v2.b32 {%0,%1}, [%2];" : "=r"(v[i >> 1][2 * (i & 1)]), "=r"(v[i >> 1][2 * (i & 1) + 1]) : "l"(p + (i & 3) * 256 + (i >> 2) * S2) : "memory");
  }
}
__device__ __forceinline__ uint32_t dif2(uint32_t a, uint32_t b, uint32_t tag) { uint32_t r; asm("lop3.b32 %0, %1, %2, %3, 0x7e;" : "=r"(r) : "r"(a), "r"(b), "r"(tag)); return r; }
__device__ __forceinline__ uint32_t dif2v(uint32_t a, uint32_t b, uint32_t tag) { uint32_t r; asm volatile("lop3.b32 %0, %1, %2, %3, 0x7e;" : "=r"(r) : "r"(a), "r"(b), "r"(tag)); return r; }
__device__ __forceinline__ uint32_t or3(uint32_t a, uint32_t b, uint32_t c) { uint32_t r; asm("lop3.b32 %0, %1, %2, %3, 0xfe;" : "=r"(r) : "r"(a), "r"(b), "r"(c)); return r; }
__device__ __forceinline__ uint32_t after(uint32_t x, float f, uint32_t z) { uint32_t r; asm("lop3.b32 %0, %1, %2, %3, 0xea;" : "=r"(r) : "r"(__float_as_uint(f)), "r"(z), "r"(x)); return r; }
__device__ __forceinline__ bool any_bit(uint32_t a, uint32_t b, uint32_t m) {
  uint32_t r; asm("lop3.b32 %0, %1, %2, %3, 0xa8;" : "=r"(r) : "r"(a), "r"(b), "r"(m)); return __any_sync(0xffffffffu, r); }
template <int W, int N> __device__ __forceinline__ bool stale(const uint32_t (&v)[N][4], uint32_t tag) {
  uint32_t x = dif2(v[0][0], v[0][2], tag);
  if (N == 4) x = or3(x, dif2(v[1][0], v[1][2], tag), dif2(v[2 % N][0], v[2 % N][2], tag));
  return any_bit(x, dif2(v[N - 1][0], v[N - 1][2], tag), 1);
}
template <int W, int N, int S2 = 1024> __device__ __forceinline__ void retry(uint32_t (&v)[N][4], const uint8_t* p, uint32_t tag, int& it) {
#pragma unroll 1
  do { ldx<N, S2>(v, p); it += INC_A; } while (stale<W>(v, tag) && it < SPIN_LIMIT);
}
__device__ __forceinline__ void mma_h(float (&d)[4], const uint32_t (&a)[4], const uint32_t (&b)[4], int hf) { mma16816(d, a[0], a[1], a[2], a[3], b[2 * hf], b[2 * hf + 1]); }
__device__ __forceinline__ void sts128(uint32_t a, const uint32_t (&r)[4]) { sts128(a, r[0], r[1], r[2], r[3]); }
__device__ __forceinline__ void sts128f(uint32_t a, const float* r) { sts128(a, __float_as_uint(r[0]), __float_as_uint(r[1]), __float_as_uint(r[2]), __float_as_uint(r[3])); }
__device__ __forceinline__ void mbar_spin(uint32_t bar, uint32_t par, int& it) {
  asm volatile("{.reg .pred p; .reg .b32 par; mov.b32 par, %2;\nLOOP: mbarrier.try_wait.parity.shared::cta.b64 p, [%1], par; @p bra.uni DONE;\n"
               "add.s32 %0, %0, 1; setp.le.s32 p, %0, %3; @p bra.uni LOOP;\nDONE: }" : "+r"(it) : "r"(bar), "r"(par), "n"(SPIN_LIMIT) : "memory"); }
__device__ __forceinline__ void warp_arrive(uint32_t bar) {
  __syncwarp(); asm volatile("{.reg .pred p; elect.sync _|p, 0xffffffff; @p mbarrier.arrive.shared::cta.b64 _, [%0];}" :: "r"(bar) : "memory"); }
__device__ __forceinline__ void delay_until(unsigned t) {
  asm volatile("{.reg .pred p; .reg .b64 c; .reg .b32 lo, hi;\nLOOP: mov.u64 c, %%clock64; mov.b64 {lo, hi}, c; sub.s32 lo, lo, %0; setp.lt.s32 p, lo, 0; @p bra.uni LOOP;}" :: "r"(t) : "memory"); }
__device__ __forceinline__ void cut(int it) { asm volatile("{.reg .pred p; setp.lt.s32 p, %0, 0;\nL: @p st.volatile.shared.u32 [%0], %0; @p bra.uni L;}" :: "r"(it) : "memory"); }
__device__ __forceinline__ void zero(float (&c)[4][4]) {
#pragma unroll
  for (int i = 0; i < 4; i++) c[i][0] = c[i][1] = c[i][2] = c[i][3] = 0.f;
}

__device__ __forceinline__ void sched() { asm volatile("griddepcontrol.launch_dependents;" ::: "memory"); }
__device__ __forceinline__ const uint8_t* pinp(const uint8_t* p) { return reinterpret_cast<const uint8_t*>(__shfl_xor_sync(0xffffffffu, reinterpret_cast<unsigned long long>(p), 0)); }
__device__ __forceinline__ uint32_t bar_or(int id, uint32_t x) {
  uint32_t r; asm volatile("{.reg .pred p, q; setp.ne.u32 p, %2, 0; bar.red.or.pred q, %1, 256, p; selp.u32 %0, 1, 0, q;}" : "=r"(r) : "r"(id), "r"(x) : "memory"); return r; }
__device__ __forceinline__ void bar_sync_unless(int id, uint32_t x) { asm volatile("{.reg .pred p; setp.eq.u32 p, %1, 0; @p bar.sync %0, 256;}" :: "r"(id), "r"((uint32_t)x) : "memory"); }
__device__ __forceinline__ void bar_arrive_unless(int id, uint32_t x) { asm volatile("{.reg .pred p; setp.eq.u32 p, %1, 0; @p bar.arrive %0, 256;}" :: "r"(id), "r"((uint32_t)x) : "memory"); }
__device__ __forceinline__ void stsm2t(uint32_t a, uint32_t r0, uint32_t r1, uint32_t x) {
  asm volatile("{.reg .pred p; setp.eq.u32 p, %3, 0; @p stmatrix.sync.aligned.m8n8.x2.trans.shared.b16 [%0], {%1,%2};}" :: "r"(a), "r"(r0), "r"(r1), "r"((uint32_t)x) : "memory"); }
__device__ __forceinline__ uint32_t or_and(uint32_t a, uint32_t b, uint32_t m) { uint32_t r; asm("lop3.b32 %0, %1, %2, %3, 0xa8;" : "=r"(r) : "r"(a), "r"(b), "r"(m)); return r; }
#define rare(x) __builtin_expect(!!(x), 0)
__device__ __forceinline__ uint32_t gtime() { unsigned long long g; asm volatile("mov.u64 %0, %%globaltimer;" : "=l"(g) :: "memory"); return (uint32_t)g; }
__device__ __forceinline__ void wait_time(uint32_t t) {
  asm volatile("{.reg .pred p; .reg .b32 g; .reg .b64 c;\nLOOP: mov.u64 c, %%globaltimer; cvt.u32.u64 g, c; sub.s32 g, %0, g; setp.lt.u32 p, g, 16384; @p bra.uni LOOP;}" :: "r"(t - 1) : "memory"); }
__device__ __forceinline__ uint32_t ldx32(const void* p) { uint32_t v; asm volatile("ld.relaxed.gpu.global.b32 %0, [%1];" : "=r"(v) : "l"(p) : "memory"); return v; }
__device__ __forceinline__ void stx32(const void* p, uint32_t v) { asm volatile("st.relaxed.gpu.global.b32 [%0], %1;" :: "l"(p), "r"(v) : "memory"); }

__global__ void __launch_bounds__(256, 1)
rec_kernel(const __grid_constant__ RecMaps maps, const bf16* __restrict__ xin, const bf16* __restrict__ mem0, Xchg* const gx,
           const bf16* __restrict__ fx, const bf16* __restrict__ wr, const bf16* __restrict__ wi) {
  extern __shared__ __align__(1024) uint8_t smem_raw[];
  const uint32_t sb = smem_u32(smem_raw);
  int role = blockIdx.x;
  {
    uint32_t smid, nsm; asm volatile("mov.u32 %0, %%smid;" : "=r"(smid)); asm volatile("mov.u32 %0, %%nsmid;" : "=r"(nsm));
    const int p = smid >> 1, u = p - 32;
    if (nsm == gridDim.x)
      role = (smid & 1) + (p < 32 ? 4 * ((p & 7) + 8 * (p >> 4)) + 2 * ((p >> 3) & 1) : p < 60 ? 4 * (16 + u % 7 + 7 * (u / 14)) + 2 * ((u / 7) & 1)
                         : p < 62 ? 2 * p + 8 : 2 * p - 4);
    role = uni(role);
  }
  if (role >= 128) {
    grid_wait(&gx->ctr[33], 128);
    fft_cols(sb, role - 128, 4);
    grid_arrive(&gx->ctr[32]); grid_wait(&gx->ctr[32], 4);
    fft_rows_inv(&maps.fo, sb, role - 128, 4);
    return;
  }
  const int tid = threadIdx.x, warp = uni(tid >> 5), lane = tid & 31, wg = warp >> 2, w4 = warp & 3, g = lane >> 2, t = lane & 3;
  const int h = role >> 2, j = role & 3, jh = j & 1;
  uint32_t w[48][4];
  float aq[16], av[16];
  int it = 0;

#define PT(k)
  auto pf_wo = [&]() {
    for (int i = 0; i < 4; i++)
      asm volatile("cp.async.bulk.prefetch.tensor.2d.L2.global [%0, {%1, %2}];" :: "l"(&maps.wo), "r"(256 * j + 64 * i), "r"(h * DH) : "memory");
  };
  fft_rows_fwd(fx, wr, wi, sb + R_MEM + 49152, role, [&]() {
    if (tid == 224) {
      mbar_init(sb + B_KV, 1); mbar_init(sb + B_W, 1); mbar_init(sb + B_X, 1); mbar_init(sb + B_X + 8, 1); mbar_init(sb + B_X + 16, 1); mbar_init(sb + B_X + 24, 1); mbar_init(sb + B_C, 4); mbar_init(sb + B_PK, 4); mbar_init(sb + B_B, 1);
      asm volatile("fence.mbarrier_init.release.cluster;" ::: "memory");
      mbar_expect_tx(sb + B_W, 3 * 65536);
      for (int i = 0; i < 4; i++) {
        tma2d(sb + R_X + i * 16384, &maps.wq, h * DH + 32 * j, i * 256, sb + B_W);
        if (i < 3) tma2d(sb + R_MEM + i * 16384, &maps.wk, h * DH + 32 * j, i * 256, sb + B_W);
        else asm volatile("cp.async.bulk.prefetch.tensor.2d.L2.global [%0, {%1, %2}];" :: "l"(&maps.wk), "r"(h * DH + 32 * j), "r"(768) : "memory");
      }
      for (int i = 0; i < 2; i++) tma2d(sb + R_WO + i * 32768, &maps.wv, h * DH + 64 * (j >> 1), jh * 512 + i * 256, sb + B_W);
      if (PFD) asm volatile("cp.async.bulk.prefetch.L2.global [%0], 2048;" :: "l"(xin + role * DM) : "memory");
      else for (int i = 0; i < 4; i++) asm volatile("cp.async.bulk.prefetch.L2.global [%0], 8192;" :: "l"(xin + role * 16384 + i * 4096) : "memory");
      if (WOP == 0) pf_wo();
    }
    __syncwarp();
  });
  if (tid < 16) sts32(sb + R_T + tid * 4, ~0u);
  fence_async();
  PT(0);
  grid_arrive(&gx->ctr[33]);
  PT(1);
  if (tid == 224) { tma2d(sb + R_MEM + 49152, &maps.wk, h * DH + 32 * j, 768, sb + B_W); if (WOP == 1) pf_wo(); }
  __syncwarp();
  uint8_t* const xb = reinterpret_cast<uint8_t*>(gx);
  auto probe_at = [&](int n) { return xb + (n ? offsetof(Xchg, C) + w4 * 8192 + role * 32 : offsetof(Xchg, B) + role * 8192 + warp * 128); };
  if (lane < 8) stx128(probe_at(lane >> 2) + (lane & 2) * 2048 + (lane & 1) * 16, 0, 0, 0, 0);
  uint32_t m0[4][4];
#pragma unroll
  for (int i = 0; i < 16; i++) m0[i >> 2][i & 3] = ldnc32(mem0 + g * DM + 128 * warp + 8 * i + 2 * t);
  mbar_spin(sb + B_W, 0, it);
  PT(2);
  const int lrow = (lane & 7) + ((lane >> 4) << 3), lhi = (lane >> 3) & 1;
  const int kq = wg ? 3 - 3 * jh : 3 * jh;
  const uint32_t LW = lrow * 128 + ((lhi ^ (lane & 7)) << 4);
  {
    const int chunk = w4 < 2 ? w4 + 2 * lhi : 2 * (w4 & 1) + lhi;
    uint32_t a = sb + (w4 < 2 ? R_X : R_MEM) + kq * 16384 + lrow * 64 + ((chunk ^ ((lrow >> 1) & 3)) << 4);
#pragma unroll
    for (int i = 0; i < 16; i++) ldsm4t(w[i], a + i * 1024);
    const uint32_t st = wg ? 1024 : 2048, av0 = sb + R_WO + (LW ^ (w4 << 5));
    const uint32_t a1 = wg ? a + (2 * jh - 1) * 16384 : av0 + jh * 32768, a2 = wg ? a + (2 * jh - 1) * 32768 : av0 + (1 - jh) * 32768;
#pragma unroll
    for (int i = 0; i < 16; i++) { ldsm4t(w[16 + i], a1 + i * st); ldsm4t(w[32 + i], a2 + i * st); }
  }
  uint32_t L16 = pin(lane * 16);
  const uint32_t uW = uni(sb + w4 * 512), uWo = uni(sb + R_WO + w4 * 16384), uMem = uni(sb + R_MEM + kq * 4096);
  const uint32_t dX = uni(((sb + R_X + kq * 16384) >> 4) | 0x10000u);
  auto load_wo = [&](uint32_t (&d)[32][4], int i0, int i1) {
#pragma unroll
    for (int i = i0; i < i1; i++) lds128(d[i], uWo + L16 + (i & 1) * 512 + (i >> 4) * 1024 + (i & 14) * 1024);
  };
  auto issue_x = [&](int n, int k) {
    const uint32_t bar = sb + B_X + 8 * k, q = k ^ (3 - 3 * jh);
    mbar_expect_tx(bar, 16384); tma3d(sb + R_X + q * 16384, &maps.x, n * SEG, 4 * q, bar);
  };
  auto store_stage = [&](int n) {
    asm volatile("cp.async.bulk.global.shared::cta.bulk_group [%0], [%1], 8192; cp.async.bulk.commit_group;"
                 :: "l"(g_kqv[n & 3][role]), "r"(sb + R_STAGE) : "memory");
  };
  auto issue_kqv = [&](int n) {
    const int p = (n & 3) * 128 + 4 * h;
    mbar_expect_tx(sb + B_KV, 26624);
    tma3d(sb + R_K, &maps.k, 0, p, sb + B_KV); tma3d(sb + R_Q, &maps.q, 8 + 2 * j, p, sb + B_KV); tma3d(sb + R_V, &maps.v, 16, p, sb + B_KV);
  };
  auto fetch4k = [&](uint32_t dst, uint32_t off, uint32_t bar, uint32_t t) {
    asm volatile("{.reg .pred p, q; .reg .b32 g; .reg .b64 c; elect.sync _|q, 0xffffffff; @q mbarrier.arrive.expect_tx.shared::cta.b64 _, [%2], 4096;\n"
                 "LOOP: mov.u64 c, %%globaltimer; cvt.u32.u64 g, c; sub.s32 g, %3, g; setp.lt.u32 p, g, 16384; @p bra.uni LOOP;\n"
                 "@q cp.async.bulk.shared::cluster.global.mbarrier::complete_tx::bytes [%0], [%1], 4096, [%2];}" :: "r"(dst), "l"(xb + off), "r"(bar), "r"(t - 1) : "memory");
  };
  uint32_t uS;
  auto my_b = [&]() { return offsetof(Xchg, B) + role * 8192 + ((uS + ((uint32_t)it >> 31)) & 1) * 4096; };
  auto issue_c = [&](uint32_t t) { fetch4k(sb + R_MEM + w4 * 4096, offsetof(Xchg, C) + w4 * 8192 + ((uS + ((uint32_t)it >> 31)) & 4096), sb + B_C, t); };
  auto wait_x = [&](int n, int i) { if (!(EXP & 1) || n < 2) mbar_spin(sb + B_X + 8 * i, n & 1, it); };
#define PACED(d0) uint32_t dz = d0; const uint32_t z = (uint32_t)it >> 31; auto pace = [&]() { for (int k = 0; k < PACE; k++) { if (k & 1) asm("add.u32 %0, %0, %1;" : "+r"(dz) : "r"(z)); else asm("xor.b32 %0, %0, %1;" : "+r"(dz) : "r"(z)); } };
  auto project_v = [&](auto I0, auto I1, auto&& mid) {
    PACED(decltype(I0)::value < 16 ? dX : dX ^ 1024);
    wg_fence();
    sfor<decltype(I0)::value, decltype(I1)::value>([&](auto I) {
      constexpr int i = decltype(I)::value;
      mid(i);
      if (i == 16 && decltype(I0)::value < 16) dz ^= 1024;
      wg_rs32<((i >> 2) & 3) * 256 + (i & 3) * 2, (i > 0)>(av, w[16 + i], dz);
      pace();
    });
    wg_commit();
  };
  auto project_qk = [&](auto I0, auto I1, auto first, auto&& mid) {
    PACED((dX ^ (decltype(I0)::value >> 4 << 10)) + ((uint32_t)it >> 31));
    wg_fence();
    sfor<decltype(I0)::value, decltype(I1)::value>([&](auto I) {
      constexpr int i = decltype(I)::value;
      mid(i);
      wg_rs32<((i >> 2) & 3) * 256 + (i & 3) * 2, !decltype(first)::value || i != decltype(I0)::value>(aq, w[i], dz);
      pace();
    });
    wg_commit();
  };
  const uint32_t uP = uni(sb + R_X + 3 * jh * 16384 + w4 * 512);
  auto park = [&]() {
    bar_sync(1, 128);
#pragma unroll
    for (int i = 0; i < 4; i++) sts128f(uP + L16 + i * 2048, aq + 4 * i);
    warp_arrive(sb + B_PK);
  };
  auto unpark = [&]() {
#pragma unroll
    for (int i = 0; i < 4; i++) {
      const float4 p = lds128f(uP + L16 + i * 2048);
      av[4 * i] = p.x; av[4 * i + 1] = p.y; av[4 * i + 2] = p.z; av[4 * i + 3] = p.w;
    }
  };
  auto fin_qk = [&]() {
#pragma unroll
    for (int i = 0; i < 16; i++) aq[i] += av[i];
    const uint32_t a = sb + R_STAGE + (w4 < 2 ? 2048 + w4 * 128 : (w4 & 1) * 256) + (L16 & 112) + (L16 >> 7) * 512;
    stsm4t(a, pack2(aq[0], aq[1]), pack2(aq[4], aq[5]), pack2(aq[8], aq[9]), pack2(aq[12], aq[13]));
    stsm4t(a + (w4 < 2 ? 256 : 128), pack2(aq[2], aq[3]), pack2(aq[6], aq[7]), pack2(aq[10], aq[11]), pack2(aq[14], aq[15]));
  };
  auto fin_v = [&]() {
#pragma unroll
    for (int a = 0; a < 2; a++)
      sts128(sb + R_STAGE + 4096 + w4 * 1024 + a * 512 + L16, pack2(av[8 * a], av[8 * a + 1]), pack2(av[8 * a + 2], av[8 * a + 3]),
             pack2(av[8 * a + 4], av[8 * a + 5]), pack2(av[8 * a + 6], av[8 * a + 7]));
  };
  __syncthreads();
  if (tid == 224) {
#pragma unroll 1
    for (int i = 0; i < 4; i++) issue_x(0, i);
    mbar_expect_tx(sb + B_W, 65536);
    for (int i = 0; i < 4; i++) tma2d(sb + R_WO + i * 16384, &maps.wo, 256 * j + 64 * i, h * DH, sb + B_W);
  }
  __syncwarp();
  if (wg) {
#pragma unroll
    for (int i = 0; i < NSW; i++) sts128(uW + R_WC + L16 + i * 2048, w[i]);
  }
#pragma unroll
  for (int i = 0; i < 4; i++) sts128(sb + R_MEM + warp * 2048 + i * 512 + (g >> 1) * 128 + t * 32 + (g & 1) * 16, m0[i]);
  auto probe = [&](int n, int cnt) {
    if (lane == 0) {
#pragma unroll 1
      for (int i = role >> 7; i < cnt; i++) {
        const int k = (i ^ wg) & 1;
        const unsigned t0 = clk();
        uint32_t v; asm volatile("atom.relaxed.gpu.global.exch.b32 %0, [%1], 0;" : "=r"(v) : "l"(probe_at(n) + k * 4096) : "memory");
        if (v == 0) asm volatile("red.shared.min.u32 [%0], %1;" :: "r"(sb + R_T + (n ? w4 * 8 : 32) + k * 4), "r"(clk() - t0) : "memory");
      }
    }
    __syncwarp();
  };
#pragma unroll 1
  for (int n = 0; n < 2; n++) {
    probe(0, NPB);
    PT(3 + 3 * n);
    wait_x(n, 2);
    PT(4 + 3 * n);
    if (wg == 0) {
      wait_x(n, 3);
      project_qk(IC<0>{}, IC<16>{}, IC<1>{}, [](int) {});
      project_v(IC<0>{}, IC<32>{}, [](int) {});
      if (tid == 96 && n == 1) {
        asm volatile("cp.async.bulk.wait_group 0;" ::: "memory");
        __threadfence(); atomicAdd(&gx->ctr[h], 1u);
      }
      __syncwarp();
      wg_wait<0>(); keep(aq); keep(av);
      park();
      fin_v();
      fence_async();
    } else {
      wait_x(n, 0); wait_x(n, 1);
      project_qk(IC<32>{}, IC<48>{}, IC<1>{}, [](int) {});
      project_qk(IC<16>{}, IC<32>{}, IC<0>{}, [](int) {});
      project_qk(IC<0>{}, IC<16>{}, IC<0>{}, [](int) {});
      mbar_spin(sb + B_PK, n, it);
      unpark();
      wg_wait<0>(); keep(aq);
      fin_qk();
      fence_async();
    }
    __syncthreads();
    if (tid == 0 && n) stx32(&gx->S[role], 1 + (HOME & 2 && lds32(sb + R_T + 36) < lds32(sb + R_T + 32)));
    PT(5 + 3 * n);
    if (tid == 96 && n == 0) store_stage(0);
    if (tid == 128 && n == 0) {
#pragma unroll 1
      for (int i = 0; i < 4; i++) issue_x(1, i);
    }
    if (warp == 5 && n == 1) {
#pragma unroll 1
      while (__any_sync(0xffffffffu, ldx32(&gx->ctr[h]) < 4) && ++it < SPIN_LIMIT) {}
      __threadfence(); asm volatile("fence.proxy.async;" ::: "memory");
      if (elect()) issue_kqv(0);
    }
    __syncwarp();
  }
  mbar_spin(sb + B_W, 1, it);
  PT(9);
#pragma unroll
  for (int i = 0; i < 4; i++) {
    uint32_t f[4][4];
    const uint32_t a = sb + R_WO + warp * 8192 + i * 2048;
#pragma unroll
    for (int q = 0; q < 4; q++) ldsm4t(f[q], a + (LW ^ (q << 5)));
    __syncwarp();
#pragma unroll
    for (int q = 0; q < 4; q++) sts128(a + q * 512 + L16, f[q]);
  }
  if (NPC) probe(1, NPC);
  {
    const int o = 32 * w4 + 16 * wg + 4 * t + j;
    uint32_t v;
#pragma unroll 1
    while (__any_sync(0xffffffffu, (v = ldx32(&gx->S[o])) == 0) && ++it < SPIN_LIMIT) {}
    asm volatile("st.shared.u64 [%0], %1;" :: "r"(sb + R_DST + wg * 1024 + w4 * 256 + lane * 8), "l"(xb + offsetof(Xchg, B) + o * 8192 + (v >> 1) * 4096 + h * 128 + ((g ^ h) & 7) * 16) : "memory");
  }
  if (wg == 0) {
    const uint64_t cd = reinterpret_cast<uint64_t>(xb + (offsetof(Xchg, C) + j * 8192 + h * 128 + w4 * 32 + (L16 & 16) * 256 + (L16 & 64) / 4 + (L16 >> 7) * 4));
    sts128(uW + R_RD + L16, (uint32_t)cd, (uint32_t)(cd >> 32), sb + R_MEM + (L16 & 112) * 8 + (L16 >> 8) * 1024 + ((w4 * 32 + ((L16 >> 3) & 16)) ^ (L16 & 112)),
           (L16 >> 6) == (h & 3) * 2 + ((h >> 2) & 1) ? 0xFFFE0000u : 0xFFFFFFFFu);
  }
  if (tid == 0) sts32(sb + B_DUE + 8, gtime() & ~31u);
  PT(10);
  mbar_spin(sb + B_KV, 0, it);
  PT(11);
  if (tid < 4) sts32(sb + B_ONE + tid * 4, 0x3F803F80u);
  if (warp == 1) { const uint32_t e = g >> 1 == t ? 0x3F80u << (16 * (g & 1)) : 0u; sts128(sb + R_ID + L16, e, 0, 0, e); }
  __syncthreads();
  {
    const uint32_t kb = lds32(sb + R_T + 36) < lds32(sb + R_T + 32);
    uS = uni((HOME & 4 ? (__popc(((offsetof(Xchg, B) / 4096 + 2 * role) ^ (offsetof(Xchg, C) / 4096 + 2 * w4)) & 0xb3) ^ kb) & 1 : lds32(sb + R_T + w4 * 8 + 4) < lds32(sb + R_T + w4 * 8)) * 4096 + kb);
  }

  const float sc = 0.08838834764831845f * 1.4426950408889634f;
  uint8_t* const xa = xb + uni(h * 16384);
  const uint32_t uA = uni(wg ? (w4 >> 1) * 2048 + j * 512 + (w4 & 1) * 256 : 8192 + (4 * (j >> 1) + w4) * 512 + jh * 256);
  const uint32_t uP2 = uni(sb + R_P + w4 * 256);
  uint32_t nc = 1;
  uint32_t ma;
  const uint8_t* adst;
  auto pin_mem = [&]() { adst = pinp(xa + uA + L16 / 2); ma = pin(uMem + (L16 & 384) + (L16 & 48) * 2 + (L16 & 64) / 4); };
  pin_mem();

#pragma unroll 1
  for (int s = 0;; nc++) {
    const uint32_t tag = (s + 1) & 1;
    auto fresh = [&]() { L16 += (uint32_t)it >> 31; };
    auto get_due = [&]() { return lds32(sb + B_DUE + 4 + tag * 4); };
    float c[4][4], r4[4];
    auto fold = [&]() {
#pragma unroll
      for (int i = 0; i < 4; i++) r4[i] = ((c[0][i] + c[1][i]) + c[2][i]) + c[3][i];
    };
    auto mma4 = [&](int n, const uint32_t (&b0)[4], const uint32_t (&b1)[4]) {
      mma_h(c[0], w[n + 2], b1, 0); mma_h(c[1], w[n + 3], b1, 1); mma_h(c[2], w[n], b0, 0); mma_h(c[3], w[n + 1], b0, 1);
    };
    auto xpos = [&](int pos, int wp) {
      if ((pos == X0 || pos == X1 || pos == X2 || pos == X3) && warp == wp && s + 1 < NSEG && elect()) {
        const int z = (uint32_t)it >> 31;
        if (pos == X2) issue_x(s + 2, 2 + z);
        if (pos == X3) issue_x(s + 2, 3 + z);
        if (pos == X1) issue_x(s + 2, 1 + z);
        if (pos == X0) issue_x(s + 2, z);
      }
      __syncwarp();
    };
    if (wg == 0) {
      mbar_spin(sb + B_C, nc & 1, it);
      TS(13);
      uint32_t b[16][4], tg[4];
#pragma unroll
      for (int i = 0; i < PD0; i++) { lds128(b[i], ma + i * 512); __syncwarp(); }
      sched();
      zero(c);
#pragma unroll
      for (int i = 0; i < 8; i++) {
        const int k = i ^ 1;
        mma_h(c[0], w[2 * k], b[k], 0); mma_h(c[1], w[2 * k + 1], b[k], 1);
        if (i < 2 * NV0) { mma_h(c[2], w[16 + 2 * k], b[k], 0); mma_h(c[3], w[17 + 2 * k], b[k], 1); }
        sched();
        if ((i & 1) && i + PD0 < 9) { lds128(b[i + PD0 - 1], ma + (i + PD0 - 1) * 512); __syncwarp(); lds128(b[i + PD0], ma + (i + PD0) * 512); sched(); }
        if (i == TGP) {
          fresh();
#pragma unroll
          for (int k = 0; k < 4; k++) tg[k] = lds32((uW * 4 + L16) * 2 + (L16 >> 6) * 4 + (R_MEM + k * 1024 - 7 * sb));
          sched();
        }
      }
#pragma unroll
      for (int i = 0; i < 4; i++) { r4[i] = c[0][i] + c[1][i]; c[0][i] = c[1][i] = 0.f; }
      sts128f(uW + R_RED + L16, r4);
      TS(1);
      const uint32_t old = bar_or(4, (dif2(tg[0], tg[1], s) | dif2(tg[2], tg[3], s)) & (s > 0));
      TS(0);
#pragma unroll
      for (int i = 0; i < 2 * NV0; i++) { lds128(b[8 + i], (ma ^ 4096) + i * 512); __syncwarp(); }
      sched();
#pragma unroll
      for (int i = NV0; i < 8; i++) {
        if (VB && i == VB) bar_sync(7, 256);
        mma4(16 + 4 * i, b[2 * i], b[2 * i + 1]);
        if (i < 7) sched();
        if (i < 4) { lds128(b[8 + 2 * i], (ma ^ 4096) + i * 1024); __syncwarp(); lds128(b[9 + 2 * i], (ma ^ 4096) + i * 1024 + 512); sched(); }
      }
      fold();
      asm volatile("{.reg .pred p; setp.eq.u32 p, %3, 0; @p st.relaxed.gpu.global.v2.b32 [%0], {%1,%2};}" :: "l"(adst), "r"((pack2(r4[0], r4[1]) & ~1u) | tag), "r"(pack2(r4[2], r4[3])), "r"(old) : "memory");
      sched();
      const unsigned tpub = clk();
      if (__any_sync(0xffffffffu, old) && nc < NC_MAX) {
        bar_sync(3, 256);
        issue_c(gtime());
        continue;
      }
      TS(3);
      xpos(0, 0);
      const uint32_t due = get_due();
      uint32_t vf[4][4], vm[2][4], p[4], pm, o[4];
      const uint32_t va = sb + R_V + (w4 >> 1) * 8192 + (w4 & 1) * 2048 + L16;
#pragma unroll
      for (int i = 0; i < 4; i++) {
        uint32_t q[4]; lds128(vf[i], va + i * 512); lds128(q, va + 4096 + i * 512);
#pragma unroll
        for (int e = 0; e < 4; e++) vf[i][e] = hadd2(vf[i][e], q[e]);
      }
      const uint32_t pa = pin(sb + R_P + (L16 >> 1));
      const uint8_t* vsrc = pinp(xa + 8192 + w4 * 1024 + L16 / 2);
      uint32_t one[4];
      lds128(one, sb + B_ONE);
      auto pv_x = [&]() {
        zero(c);
        mma_a(c[2], one, p[0], p[1]);
        mma_a(c[0], vf[0], p[0], p[1]); mma_a(c[1], vf[2], p[0], p[1]);
        sched();
        mma_a(c[2], one, p[2], p[3]);
        mma_a(c[0], vf[1], p[2], p[3]); mma_a(c[1], vf[3], p[2], p[3]);
        sched();
      };
      auto pv_m = [&]() {
        mma1688(c[2], one[0], one[1], pm);
        mma_a(c[0], vm[0], pm, pm);
        sched();
        mma_a(c[1], vm[1], pm, pm);
      };
      auto norm = [&]() {
        const float n0 = rcp(c[2][0]), n1 = rcp(c[2][1]);
#pragma unroll
        for (int i = 0; i < 4; i++) o[i] = pack2(c[i >> 1][2 * (i & 1)] * n0, c[i >> 1][2 * (i & 1) + 1] * n1);
        return ((__float_as_uint(c[2][0]) - 0x1F800000u) | (__float_as_uint(c[2][1]) - 0x1F800000u)) >> 30;
      };
      auto load_m = [&](int x) { const float2 e0 = lds64f(pa + 512 + x * 1024), e1 = lds64f(pa + 768 + x * 1024); pm = pack2(e0.x * e1.x, e0.y * e1.y); };
      auto attend_max = [&](int x) {
        float2 sv[6];
#pragma unroll
        for (int i = 0; i < 6; i++) sv[i] = lds64f(pa - 3072 + x * 1536 + i * 256);
        sv[4].x += sv[5].x; sv[4].y += sv[5].y;
        const int dq = (int)(L16 >> 6) - (int)((L16 >> 3) & 6) + 8 * j;
        float m = fmaxf(sv[4].x, sv[4].y);
#pragma unroll
        for (int i = 0; i < 4; i++) {
          if (x && 8 * i > dq) sv[i].x = -INFINITY;
          if (x && 8 * i + 1 > dq) sv[i].y = -INFINITY;
          m = fmaxf(m, fmaxf(sv[i].x, sv[i].y));
        }
        m = fmaxf(m, __shfl_xor_sync(0xffffffffu, m, 1));
        m = fmaxf(m, __shfl_xor_sync(0xffffffffu, m, 2));
#pragma unroll
        for (int i = 0; i < 5; i++) (i < 4 ? p[i] : pm) = pack2(ex2(sv[i].x - m), ex2(sv[i].y - m));
        pv_x(); pv_m(); norm();
      };
      uint32_t tq[4];
      auto get_t = [&]() {
        tq[0] = tq[1] = tq[2] = tq[3] = 0;
        asm volatile("{.reg .pred p; setp.eq.u32 p, %5, 0; @p ld.relaxed.gpu.global.v4.b32 {%0,%1,%2,%3}, [%4];}"
                     : "+r"(tq[0]), "+r"(tq[1]), "+r"(tq[2]), "+r"(tq[3]) : "l"(xb + offsetof(Xchg, T) + L16 * 8), "r"(warp) : "memory");
      };
      delay_until(tpub + DLY_V);
      wait_time(due + NS_V);
      TS(4);
      ldx(vm, vsrc);
      sched();
      xpos(2, 2);
      auto store_kqv = [&]() {
        fence_async();
        if (!(EXP & 4))
          asm volatile("{.reg .pred p; elect.sync _|p, 0xffffffff; @p cp.async.bulk.global.shared::cta.bulk_group [%0], [%1], 2048; cp.async.bulk.commit_group;}"
                       :: "l"(g_kqv[(s + 1) & 3][role] + w4 * 128), "r"(sb + R_STAGE + w4 * 2048) : "memory");
      };
      if (SPOS == 2) store_kqv();
      sched();
      bar_sync(5, 256);
      ldsm4(p, sb + R_P + L16);
      load_m(0);
      pv_x();
      ldsm4(p, sb + R_P + 1024 + L16);
      pv_m();
      const uint32_t r = norm(), tl = after(tag, c[2][0], (uint32_t)it >> 31);
      const bool redo = __any_sync(0xffffffffu, r | ((dif2(vm[0][0], vm[0][2], tl) | dif2(vm[1][0], vm[1][2], tl)) & 1));
      TS(6);
      stsm4t(uW + R_O + L16, o[0], o[1], o[2], o[3]);
      bar_arrive_unless(6, redo);
      sched();
      if (TQL == 7) get_t();
      TS(7);
      pv_x();
      if (rare(redo)) retry<2>(vm, vsrc, tag, it);
      bar_sync(8, 256);
      load_m(1);
      pv_m();
      if (rare(__any_sync(0xffffffffu, norm()) || redo)) {
        fresh();
#pragma unroll 1
        for (int x = !redo; x < 2; x++) {
          attend_max(x);
          if (x == 0) { stsm4t(uW + R_O + L16, o[0], o[1], o[2], o[3]); bar_arrive(6, 256); }
        }
      }
      TS(8);
      if (TQL == 8) get_t();
      const bool xok = mbar_test(sb + B_X + 16, s & 1) & mbar_test(sb + B_X + 24, s & 1);
      xpos(4, 2);
      fresh();
      const uint32_t ob = uni(sb + R_MEM + 4096 + w4 * 1024);
      stsm4t(ob + (L16 & 112) * 4 + (((L16 >> 3) ^ (L16 >> 1)) & 48), o[0], o[1], o[2], o[3]);
      __syncwarp();
      uint32_t rd[4];
      lds128(rd, uW + R_RD + L16);
      lds128(o, ob + (L16 ^ ((L16 >> 3) & 48)));
      auto put_o = [&]() {
        *reinterpret_cast<uint4*>(reinterpret_cast<uint8_t*>(g_ox) + (((s * SEG + 8 * j) * HD + h * DH + 32 * w4) * 2 + (L16 >> 6) * (HD * 2) + (L16 & 48))) = make_uint4(o[0], o[1], o[2], o[3]);
      };
      if (s + 1 == NSEG) { put_o(); asm volatile("cp.async.bulk.wait_group 0;" ::: "memory"); break; }
      asm volatile("cp.async.bulk.wait_group 0;" ::: "memory");
      if (elect()) stx32(xa + 4096 + j * 16 + w4 * 4, s + 1);
      __syncwarp();
      if (rare(!xok)) { wait_x(s + 2, 3); wait_x(s + 2, 2); }
      TS(9);
      fresh();
      const uint32_t e = due | ((s + 1) & 31);
      project_qk(IC<0>{}, IC<NQ>{}, IC<1>{}, [&](int n) {
        if (n == OXPOS) { __syncwarp(); put_o(); __syncwarp(); }
        if (n == TQP) { __syncwarp(); tq[0] = dif2v(tq[0], tq[1], e) | dif2v(tq[2], tq[3], e); __syncwarp(); }
      });
      if (NPA) project_v(IC<0>{}, IC<NPA>{}, [](int) {});
      TS(2);
      if (warp == 0) {
        uint32_t last = due, nx = NS_P;
        if (rare(__any_sync(0xffffffffu, tq[0]))) {
          const uint32_t ref = gtime();
#pragma unroll 1
          do ldx128(o, xb + offsetof(Xchg, T) + L16 * 8); while (any_bit(or3(o[0] - s - 1, o[1] - s - 1, o[2] - s - 1), o[3] - s - 1, 30) && ++it < SPIN_LIMIT);
          const int d = max(max((int)(o[0] - ref), (int)(o[1] - ref)), max((int)(o[2] - ref), (int)(o[3] - ref)));
          last = (ref + __reduce_max_sync(0xffffffffu, d)) & ~31u;
          if (last != due) nx += NS_X;
        }
        const uint32_t bdue = last + NS_B;
        if (s == 0) { last += NS_Y; nx += NS_Z; }
        sts32(sb + B_DUE, last);
        sts32(sb + B_DUE + 8 - tag * 4, last + nx);
        fetch4k(sb + R_MEM, my_b(), sb + B_B, bdue);
        LOG(13, tl - last);
        LOG(9, last);
      }
      if (NQ < 16) project_qk(IC<NQ>{}, IC<16>{}, IC<0>{}, [](int) {});
      project_v(IC<NPA>{}, IC<NPRE>{}, [](int) {});
      const uint32_t ba = rd[2], msk = rd[3];
      const uint8_t* cdst = reinterpret_cast<const uint8_t*>(rd[0] | (uint64_t)rd[1] << 32);
      TS(14);
      mbar_spin(sb + B_B, s & 1, it);
      TS(10);
      uint32_t bq[2][4];
      auto sum_b = [&]() {
        ldsm4t(bq[0], ba); ldsm4t(bq[1], ba + 2048);
        sched();
#pragma unroll
        for (int i = 0; i < 8; i++) c[i >> 2][i & 3] = 0.f;
        mma_a(c[0], bq[0], 0x3F803F80u, 0x3F803F80u); mma_a(c[1], bq[1], 0x3F803F80u, 0x3F803F80u);
        const uint32_t t2 = tag * 0x10001u;
        const bool old = any_bit(or3(dif2(bq[0][0], bq[0][1], t2), dif2(bq[0][2], bq[0][3], t2), dif2(bq[1][0], bq[1][1], t2)), dif2(bq[1][2], bq[1][3], t2), L16 < 64 ? 0x10001u : 0u);
        const uint32_t T = (tag << 16) & ~msk, u = ((__float_as_uint(c[0][0] + c[1][0]) + ((0x10000u & ~msk) - T)) & msk) | T;
        asm volatile("{.reg .pred p; setp.eq.u32 p, %2, 0; @p st.relaxed.gpu.global.b32 [%0], %1;}"
                     :: "l"(cdst), "r"(pack2(__uint_as_float(u), c[0][2] + c[1][2])), "r"((uint32_t)(old || (L16 & 32))) : "memory");
        return old;
      };
      if (rare(sum_b())) {
#pragma unroll 1
        do {
          const uint8_t* p = xb + (my_b() + (ba - sb - R_MEM));
          ldx128(bq[0], p); ldx128(bq[1], p + 2048);
          sts128(ba, bq[0]); sts128(ba + 2048, bq[1]);
          __syncwarp();
          it += INC_B;
        } while (sum_b() && it < SPIN_LIMIT);
      }
      sched();
      TS(11);
      bar_arrive(0, 256);
      const unsigned tc = clk();
      const uint32_t cdue = lds32(sb + B_DUE) + NS_C;
      if (warp == 3) LOG(11, gtime() - cdue);
      fresh();
      wg_wait<0>(); keep(aq); keep(av);
      park();
      if (NPRE < 32) project_v(IC<NPRE>{}, IC<32>{}, [](int) {}); else fin_v();
      TS(12);
      delay_until(tc + DLY_C);
      issue_c(cdue);
      TS(5);
      LOG(warp, it);
      pin_mem();
      if (NPRE < 32) { wg_wait<0>(); keep(av); fin_v(); }
      if (!(EXP & 2)) mbar_spin(sb + B_KV, tag, it);
      TS(15);
    } else {
      uint32_t kf[8][4];
      auto load_k = [&]() {
        const uint32_t ka = sb + R_K + w4 * 1024 + (L16 & 112) + (L16 & 128) * 4 + (L16 & 256);
#pragma unroll
        for (int i = 0; i < 8; i++) ldsm4(kf[i], ka + (i >> 1) * 2048 + (i & 1) * 128);
      };
      auto put_p = [&](int x, uint32_t old, uint32_t again) {
        float e[4];
        const int dq = (int)((L16 >> 3) & 6) + 8 * j - (int)(L16 >> 6) - 16 * w4;
#pragma unroll
        for (int i = 0; i < 4; i++) { r4[i] = fmaf(c[3][i], sc, fmaf(c[2][i], sc, fmaf(c[0][i] + c[1][i], sc, __uint_as_float(i == 3 ? 0u - old : 0u)))); e[i] = x && dq + (i & 1) < 8 * (i >> 1) ? 0.f : ex2(r4[i]); }
        stsm2t(uP2 + x * 1024 + L16, pack2(e[0], e[1]), pack2(e[2], e[3]), again);
      };
      auto put_s = [&](int x) {
#pragma unroll
        for (int i = 0; i < 4; i++) sts32f(uW + R_S + x * 1536 + (L16 & 48) * 4 + (L16 >> 6) * 4 + (i & 1) * 32 + (i >> 1) * 256, r4[i]);
      };
      auto load_q = [&](uint32_t (&q)[4], uint32_t off) { ldsm4(q, sb + R_Q + (L16 & 112) + (L16 & 128) * 2 + (L16 >> 8) * 128 + off); };
      mbar_spin(sb + B_C, nc & 1, it);
      TS(13);
      float4 o4;
      uint32_t id[4], old;
      {
        uint32_t b[24][4];
#pragma unroll
        for (int i = 0; i < 2 * PD1; i++) { lds128(b[i], ma + i * 512); __syncwarp(); }
        sched();
        zero(c);
#pragma unroll
        for (int i = 0; i < 12; i++) {
          mma4(4 * i, b[2 * i], b[2 * i + 1]);
          if (i < 11) sched();
          if (i + PD1 < 12) { const int k = i + PD1; const uint32_t a = (ma ^ (k >> 2 << 12)) + (k & 3) * 1024; lds128(b[2 * k], a); __syncwarp(); lds128(b[2 * k + 1], a + 512); sched(); }
          if (i == RJ) { lds128(id, sb + R_ID + L16); sched(); }
          if (i == RI) { old = bar_or(4, 0); o4 = lds128f(uW + R_RED + L16); sched(); }
        }
      }
      TS(0);
      {
        float e[4] = {o4.x, o4.y, o4.z, o4.w};
#pragma unroll
        for (int i = 0; i < 4; i++) { r4[i] = (((e[i] + c[0][i]) + c[1][i]) + c[2][i]) + c[3][i]; e[i] = 0.f; }
        mma_a(e, id, pack2(r4[0], r4[1]), pack2(r4[2], r4[3]));
        sched();
        if (VB) bar_arrive(7, 256);
        sched();
        asm volatile("{.reg .pred p; setp.eq.u32 p, %3, 0; @p st.relaxed.gpu.global.v2.b32 [%0], {%1,%2};}" :: "l"(adst),
                     "r"((__byte_perm(__float_as_uint(e[0]), __float_as_uint(e[1]), 0x7632) & ~1u) | tag), "r"(__byte_perm(__float_as_uint(e[2]), __float_as_uint(e[3]), 0x7632)), "r"(old) : "memory");
        sched();
      }
      const unsigned tpub = clk(), now = gtime(), due = get_due();
      if (__any_sync(0xffffffffu, old) && nc < NC_MAX) { bar_sync(3, 256); continue; }
      TS(2);
      const uint8_t* asrc = pinp(adst + ((warp == 7) * 1024 - (int)uA));
      fresh();
      uint32_t wo[32][4];
      bool xok;
      auto reload = [&]() {
        sched();
#pragma unroll
        for (int i = RE0 + RE1; i < NSW; i++) lds128(w[i], uW + R_WC + L16 + i * 2048);
        sched();
      };
      auto out_proj = [&]() {
        uint32_t b[4][4];
        float d[4][4];
        uint8_t* dst[2];
        const uint32_t da = pin(uP2 + (R_DST - R_P) + L16 / 2);
        sched();
        TS(7);
        bar_sync(6, 256);
#pragma unroll
        for (int i = 0; i < 4; i++) { ldsm4(b[i], sb + R_O + i * 512 + L16); __syncwarp(); }
        sched();
        auto put_b = [&](uint8_t* a, const float (&e)[4][4]) {
          stx128(a, (pack2(e[0][0] + e[2][0], e[0][1] + e[2][1]) & ~1u) | tag, pack2(e[0][2] + e[2][2], e[0][3] + e[2][3]),
                 pack2(e[1][0] + e[3][0], e[1][1] + e[3][1]), pack2(e[1][2] + e[3][2], e[1][3] + e[3][3]));
        };
        zero(c); zero(d);
#pragma unroll
        for (int i = 0; i < 32; i++) {
          mma_h(i < 16 ? c[i & 3] : d[i & 3], wo[i], b[(i >> 2) & 3], (i >> 1) & 1);
          if (i >= LW0 && NB1 + i - LW0 < 32) { load_wo(wo, (NB1 + i - LW0) ^ 1, ((NB1 + i - LW0) ^ 1) + 1); __syncwarp(); }
          if (i == DL0 || i == DL1) asm volatile("ld.shared.u64 %0, [%1];" : "=l"(dst[i > DL0]) : "r"(da + (i > DL0) * 1024) : "memory");
          if (i >= 16 && i < 16 + RE0) { lds128(w[i - 16], uW + R_WC + L16 + (i - 16) * 2048); __syncwarp(); }
          if (i >= RP1 && i < RP1 + RE1) { lds128(w[i - RP1 + RE0], uW + R_WC + L16 + (i - RP1 + RE0) * 2048); __syncwarp(); }
          if (i == 22) put_b(dst[0], c);
          if ((i & 1) && (i < 20 || i > 22)) sched();
        }
        put_b(dst[1], d);
        sched();
        TS(6);
      };
      if (warp < 6) {
        delay_until(tpub + DLY_A);
        const int it0 = it;
        bool redo;
#pragma unroll 1
        do {
          uint32_t q[4][4], y[4];
          float d[4][4];
          wait_time(due);
          TS(4);
          ldx(q, asrc);
          sched();
          load_k();
          uint32_t qx[4][4];
#pragma unroll
          for (int i = 0; i < 4; i++) load_q(qx[i], i * 512);
          sched();
          load_wo(wo, 0, NE4);
          sched();
          zero(c);
#pragma unroll
          for (int i = 0; i < 8; i++) mma_h(c[i & 3], kf[i], qx[i >> 1], i & 1);
          put_p(1, 0, 0); put_s(1);
          sched();
          load_wo(wo, NE4, NA4);
          sched();
          zero(c); zero(d);
#pragma unroll
          for (int i = 0; i < 8; i++) {
            if (i == 0) { y[0] = dif2v(q[0][0], q[0][2], q[1][0]); sched(); }
            if (i == 3) { y[1] = dif2v(q[1][2], q[2][0], q[2][2]); sched(); }
            if (i == 6) { y[2] = dif2v(q[3][0], q[3][2], tag); sched(); }
            mma_h(i % 6 < 2 ? c[2 + i % 6] : d[i - 2], kf[i], q[i >> 1], i & 1);
            if (i == 2 || i == 5 || i == 7) sched();
          }
          y[0] = or_and(or3(y[0], y[1], dif2v(q[0][0], q[2][0], tag)), y[2], it < SPIN_LIMIT);
#pragma unroll
          for (int i = 0; i < 4; i++) { c[0][i] = d[0][i] + d[1][i]; c[1][i] = d[2][i] + d[3][i]; }
          put_p(0, y[0], it - it0);
          TS(5);
          bar_sync_unless(5, it - it0);
          redo = __any_sync(0xffffffffu, y[0]);
          it += INC_A;
        } while (redo);
        it -= INC_A;
        put_s(0);
        bar_arrive(8, 256);
        load_wo(wo, NA4, NB1);
        out_proj();
        if (warp == 4) LOG(12, tb);
      } else {
        uint32_t qx[2][4], q[4][4];
        if (warp == 6) {
          const uint32_t t1 = (now & ~31u) + NS_M;
          LOG(10, now - due);
          if (elect()) stx32(&gx->T[h][j], ((int)(t1 - due) > 0 ? t1 + NS_PEN : due) | ((s + 1) & 31));
          __syncwarp();
        }
        auto score = [&](const uint32_t (&a0)[4], const uint32_t (&a1)[4]) {
          zero(c);
#pragma unroll
          for (int i = 0; i < 4; i++) mma_h(c[i], i < 2 ? a0 : a1, q[2 + (i >> 1)], i & 1);
        };
        auto put_m = [&](uint32_t a, uint32_t old, uint32_t again) {
#pragma unroll
          for (int i = 0; i < 2; i++) { r4[i] = fmaf(c[3][2 + i], sc, fmaf((c[0][i] + c[1][2 + i]) + c[2][i], sc, __uint_as_float(i ? 0u - old : 0u))); r4[2 + i] = fmaf(r4[i] * 0x1p122f, 0.f, ex2(r4[i])); }
          asm volatile("{.reg .pred p; setp.eq.u32 p, %3, 0; @p st.shared.v2.f32 [%0], {%1,%2};}" :: "r"(a), "f"(r4[2]), "f"(r4[3]), "r"(again) : "memory");
        };
        delay_until(tpub + DLY_A);
        const uint32_t sa = sb + R_S + 512 + w4 * 256 + (L16 >> 1);
        const int it0 = it;
        bool redo;
#pragma unroll 1
        do {
          wait_time(due);
          TS(4);
          ldx<4, 2048>(q, asrc);
          sched();
          load_q(qx[0], (w4 & 1) * 1024); load_q(qx[1], (w4 & 1) * 1024 + 512);
          load_wo(wo, 0, NA6);
          sched();
          score(q[0], q[1]);
          sched();
          const uint32_t y = or_and(or3(dif2v(q[0][0], q[0][2], tag), dif2v(q[1][0], q[1][2], tag), dif2v(q[2][0], q[2][2], tag)), dif2v(q[3][0], q[3][2], tag), it < SPIN_LIMIT);
          put_m(sa + 2560, y, it - it0);
          TS(5);
          bar_arrive_unless(5, it - it0);
          redo = __any_sync(0xffffffffu, y);
          it += INC_A;
        } while (redo);
        it -= INC_A;
        sts64f(sa, r4[0], r4[1]);
        score(qx[0], qx[1]);
        put_m(sa + 3584, 0, 0);
        sts64f(sa + 1536, r4[0], r4[1]);
        bar_arrive(8, 256);
        load_wo(wo, NA6, NB1);
        out_proj();
      }
      TS(8);
      if (s + 1 == NSEG) break;
      wait_x(s + 2, 2);
      TS(9);
      fresh();
      if (N1) project_qk(IC<32>{}, IC<32 + N1>{}, IC<1>{}, [](int) {});
      TS(10);
      xpos(6, 6);
      uint32_t fl = s + 1;
      if (warp == 5) { wait_time(due + NS_F); fl = ldx32(xa + 4096 + ((L16 >> 2) & 60)); }
      reload();
      TS(14);
      pin_mem();
      wait_x(s + 2, 1); wait_x(s + 2, 0);
      if (warp == 5) {
#pragma unroll 1
        while (__any_sync(0xffffffffu, fl != s + 1) && !(EXP & 4) && ++it < SPIN_LIMIT) fl = ldx32(xa + 4096 + ((L16 >> 2) & 60));
        wait_time(due + (NS_B + NS_K));
        if (!(EXP & 2) && elect()) issue_kqv(s + 1);
        __syncwarp();
      }
      if (PFD && warp == 6 && s + PFD < NSEG && elect())
        asm volatile("cp.async.bulk.prefetch.L2.global [%0], 2048;" :: "l"(xin + ((s + PFD) * SEG + ((role + 4 * (role >> 5)) & 31)) * DM) : "memory");
      __syncwarp();
      TS(11);
      LOG(warp, it);
      if (warp == 4) LOG(8, nc);
      bar_sync(0, 256);
      if (N1 < 16) project_qk(IC<32 + N1>{}, IC<48>{}, IC<!N1>{}, [](int) {});
      project_qk(IC<16>{}, IC<32>{}, IC<0>{}, [&](int n) { if ((n & 15) == XWPOS) { __syncwarp(); xok = mbar_test(sb + B_PK, s & 1); __syncwarp(); } });
      if (rare(!xok)) mbar_spin(sb + B_PK, s & 1, it);
      unpark();
      project_qk(IC<0>{}, IC<16>{}, IC<0>{}, [](int) {});
      TS(12);
      wg_wait<0>(); keep(aq);
      TS(1);
      fin_qk();
      TS(15);
    }
    s++;
  }
  if (it >= SPIN_LIMIT || nc >= NC_MAX) g_err = 2;
}

typedef CUresult (*EncodeFn)(CUtensorMap*, CUtensorMapDataType, cuuint32_t, void*, const cuuint64_t*, const cuuint64_t*, const cuuint32_t*,
                             const cuuint32_t*, CUtensorMapInterleave, CUtensorMapSwizzle, CUtensorMapL2promotion, CUtensorMapFloatOOBfill);
static void make_map(EncodeFn fn, CUtensorMap* m, const void* p, uint64_t cols, uint64_t rows, uint64_t pitch, uint32_t bc, uint32_t br, CUtensorMapSwizzle sw) {
  cuuint64_t dims[2] = {cols, rows}, strides[1] = {pitch * 2};
  cuuint32_t box[2] = {bc, br}, es[2] = {1, 1};
  fn(m, CU_TENSOR_MAP_DATA_TYPE_BFLOAT16, 2, const_cast<void*>(p), dims, strides, box, es, CU_TENSOR_MAP_INTERLEAVE_NONE, sw,
     CU_TENSOR_MAP_L2_PROMOTION_L2_256B, CU_TENSOR_MAP_FLOAT_OOB_FILL_NONE);
}

extern "C" void kernel_launch(void* const* d_in, const int* in_sizes, int n_in, void* d_out, int out_size) {
  const bf16* Ax = (const bf16*)d_in[0]; const bf16* mem0 = (const bf16*)d_in[1];
  const bf16* Wq = (const bf16*)d_in[2]; const bf16* Wk = (const bf16*)d_in[3]; const bf16* Wv = (const bf16*)d_in[4];
  const bf16* Wo = (const bf16*)d_in[5];
  const bf16* Bx = (const bf16*)d_in[7]; const bf16* wr = (const bf16*)d_in[8]; const bf16* wi = (const bf16*)d_in[9];
  bf16* out = (bf16*)d_out;

  void* fp = nullptr; cudaDriverEntryPointQueryResult qr;
  cudaGetDriverEntryPoint("cuTensorMapEncodeTiled", &fp, cudaEnableDefault, &qr);
  EncodeFn fn = (EncodeFn)fp;
  void *kqv, *ox, *xr;
  cudaGetSymbolAddress(&xr, g_xraw);
  cudaGetSymbolAddress(&kqv, g_kqv); cudaGetSymbolAddress(&ox, g_ox);
  const CUtensorMapSwizzle S128 = CU_TENSOR_MAP_SWIZZLE_128B, S64 = CU_TENSOR_MAP_SWIZZLE_64B;

  GemmMaps m3; RecMaps mr;
  make_map(fn, &m3.a, ox, HD, S_LEN, HD, 64, 128, S128);
  make_map(fn, &m3.b[0], Wo, DM, HD, DM, 64, 64, S128);
  m3.b[1] = m3.b[0]; m3.b[2] = m3.b[0];
  make_map(fn, &m3.c, out, DM, S_LEN, 2 * DM, 64, 64, S128);
  make_map(fn, &mr.wq, Wq, HD, DM, HD, 32, 256, S64);
  make_map(fn, &mr.wk, Wk, HD, DM, HD, 32, 256, S64);
  make_map(fn, &mr.wv, Wv, HD, DM, HD, 64, 256, S128);
  make_map(fn, &mr.wo, Wo, DM, HD, DM, 64, 128, S128);
  {
    cuuint64_t dims[3] = {64, S_LEN, 16}, strides[2] = {DM * 2, 128};
    cuuint32_t box[3] = {64, 32, 4}, es[3] = {1, 1, 1};
    fn(&mr.x, CU_TENSOR_MAP_DATA_TYPE_BFLOAT16, 3, const_cast<bf16*>(Ax), dims, strides, box, es, CU_TENSOR_MAP_INTERLEAVE_NONE, S128,
       CU_TENSOR_MAP_L2_PROMOTION_L2_256B, CU_TENSOR_MAP_FLOAT_OOB_FILL_NONE);
  }
  for (int i = 0; i < 3; i++) {
    cuuint64_t dims[3] = {128, 32, 512}, strides[2] = {256, 8192};
    cuuint32_t box[3] = {128, i == 0 ? 8u : i == 1 ? 2u : 16u, 4}, es[3] = {1, 1, 1};
    fn(i == 0 ? &mr.k : i == 1 ? &mr.q : &mr.v, CU_TENSOR_MAP_DATA_TYPE_BFLOAT16, 3, kqv, dims, strides, box, es, CU_TENSOR_MAP_INTERLEAVE_NONE,
       CU_TENSOR_MAP_SWIZZLE_NONE, CU_TENSOR_MAP_L2_PROMOTION_L2_256B, CU_TENSOR_MAP_FLOAT_OOB_FILL_NONE);
  }
  {
    cuuint64_t dims[3] = {64, 16, S_LEN}, strides[2] = {128, 2 * DM * 2};
    cuuint32_t box[3] = {64, 16, 2}, es[3] = {1, 1, 1};
    fn(&mr.fo, CU_TENSOR_MAP_DATA_TYPE_BFLOAT16, 3, out + DM, dims, strides, box, es, CU_TENSOR_MAP_INTERLEAVE_NONE, S128,
       CU_TENSOR_MAP_L2_PROMOTION_NONE, CU_TENSOR_MAP_FLOAT_OOB_FILL_NONE);
  }
  constexpr int SM3 = 6 * 32768 + 32768 + 256 + 1024;
  cudaFuncSetAttribute(gemm_kernel<128, 6>, cudaFuncAttributeMaxDynamicSharedMemorySize, SM3);
  cudaFuncSetAttribute(rec_kernel, cudaFuncAttributeMaxDynamicSharedMemorySize, R_TOTAL);

  cudaStream_t st = cudaStreamPerThread;
  Xchg* gx = reinterpret_cast<Xchg*>((reinterpret_cast<uintptr_t>(xr) + 0x1FFFFF) & ~(uintptr_t)0x1FFFFF);
  rec_kernel<<<132, 256, R_TOTAL, st>>>(mr, Ax, mem0, gx, Bx, wr, wi);
  gemm_kernel<128, 6><<<128, 384, SM3, st>>>(m3, 16, 8, 64, 8, reinterpret_cast<uint4*>(gx));
}
```

```cpp
#include <cuda_runtime.h>
#include <cuda_bf16.h>
#include <cuda.h>
#include <stdint.h>
#include <stddef.h>
#include <type_traits>

typedef __nv_bfloat16 bf16;

constexpr int S_LEN = 2048, DM = 1024, NH = 32, DH = 128, MEM = 8, SEG = 32, NSEG = 64;
constexpr int HD = NH * DH;
#define SPIN 20
constexpr int SPIN_LIMIT = 1 << SPIN, INC_A = 1, INC_B = 1;

constexpr unsigned NC_MAX = 4096;
__device__ __align__(1024) uint4 g_kqv[4][128][512];
__device__ __align__(1024) bf16 g_ox[(size_t)S_LEN * HD];
struct Xchg {
  uint4 A[32][4][256];
  uint4 C[4][2][256];
  uint4 B[128][2][256];
  uint32_t T[32][32];
  uint32_t S[128];
  unsigned ctr[64];
};
__device__ __align__(1024) uint4 g_xraw[(sizeof(Xchg) + (1 << 21)) / 16];
__device__ __align__(1024) uint4 g_y[1024 * 256];
__device__ __align__(1024) uint4 g_wt[513 * 512];
__device__ int g_err;

__device__ __forceinline__ unsigned clk() { unsigned long long c; asm volatile("mov.u64 %0, %%clock64;" : "=l"(c)); return (unsigned)c; }
__device__ __forceinline__ uint32_t smem_u32(const void* p) { return (uint32_t)__cvta_generic_to_shared(p); }
__device__ __forceinline__ void mbar_init(uint32_t bar, int cnt) { asm volatile("mbarrier.init.shared::cta.b64 [%0], %1;" :: "r"(bar), "r"(cnt) : "memory"); }
__device__ __forceinline__ void mbar_expect_tx(uint32_t bar, int bytes) { asm volatile("mbarrier.arrive.expect_tx.shared::cta.b64 _, [%0], %1;" :: "r"(bar), "r"(bytes) : "memory"); }
__device__ __forceinline__ void mbar_arrive(uint32_t bar) { asm volatile("mbarrier.arrive.shared::cta.b64 _, [%0];" :: "r"(bar) : "memory"); }
__device__ __forceinline__ void mbar_arrive_cluster(uint32_t bar, int cta) {
  asm volatile("{.reg .b32 r; mapa.shared::cluster.u32 r, %0, %1; mbarrier.arrive.shared::cluster.b64 _, [r];}" :: "r"(bar), "r"(cta) : "memory"); }
__device__ __forceinline__ bool mbar_try(uint32_t bar, int par) {
  uint32_t ok; asm volatile("{.reg .pred p; mbarrier.try_wait.parity.shared::cta.b64 p, [%1], %2; selp.u32 %0, 1, 0, p;}" : "=r"(ok) : "r"(bar), "r"(par) : "memory"); return ok; }
__device__ __forceinline__ bool mbar_test(uint32_t bar, int par) {
  uint32_t ok; asm volatile("{.reg .pred p; mbarrier.test_wait.parity.shared::cta.b64 p, [%1], %2; selp.u32 %0, 1, 0, p;}" : "=r"(ok) : "r"(bar), "r"(par) : "memory"); return ok; }
__device__ __forceinline__ void mbar_wait(uint32_t bar, int par) {
  int it = 0;
  while (!mbar_try(bar, par)) { if (++it > SPIN_LIMIT) { g_err = 1; break; } }
}
__device__ __forceinline__ void tma2d(uint32_t dst, const CUtensorMap* m, int c0, int c1, uint32_t bar) {
  asm volatile("cp.async.bulk.tensor.2d.shared::cluster.global.mbarrier::complete_tx::bytes [%0], [%1, {%3, %4}], [%2];"
    :: "r"(dst), "l"(m), "r"(bar), "r"(c0), "r"(c1) : "memory"); }
__device__ __forceinline__ void tma2d_mc(uint32_t dst, const CUtensorMap* m, int c0, int c1, uint32_t bar, uint16_t mask) {
  asm volatile("cp.async.bulk.tensor.2d.shared::cluster.global.mbarrier::complete_tx::bytes.multicast::cluster [%0], [%1, {%3, %4}], [%2], %5;"
    :: "r"(dst), "l"(m), "r"(bar), "r"(c0), "r"(c1), "h"(mask) : "memory"); }
__device__ __forceinline__ void tma2d_store(const CUtensorMap* m, uint32_t src, int c0, int c1) {
  asm volatile("cp.async.bulk.tensor.2d.global.shared::cta.bulk_group [%0, {%2, %3}], [%1];" :: "l"(m), "r"(src), "r"(c0), "r"(c1) : "memory"); }
__device__ __forceinline__ void fence_async() { asm volatile("fence.proxy.async.shared::cta;" ::: "memory"); }
__device__ __forceinline__ void bar_sync(int id, int n) { asm volatile("bar.sync %0, %1;" :: "r"(id), "r"(n) : "memory"); }
__device__ __forceinline__ void bar_arrive(int id, int n) { asm volatile("bar.arrive %0, %1;" :: "r"(id), "r"(n) : "memory"); }
__device__ __forceinline__ uint32_t pack2(float lo, float hi) { uint32_t r; asm("cvt.rn.bf16x2.f32 %0, %1, %2;" : "=r"(r) : "f"(hi), "f"(lo)); return r; }
__device__ __forceinline__ uint32_t pack2_tag(float lo, float hi, uint32_t T) {
  uint32_t u = ((__float_as_uint(lo) - T + 0x10000u) & 0xFFFE0000u) + T;
  return __byte_perm(u, pack2(0.f, hi), 0x7632); }
__device__ __forceinline__ void ldsm4(uint32_t (&r)[4], uint32_t a) {
  asm volatile("ldmatrix.sync.aligned.m8n8.x4.shared.b16 {%0,%1,%2,%3}, [%4];" : "=r"(r[0]), "=r"(r[1]), "=r"(r[2]), "=r"(r[3]) : "r"(a) : "memory"); }
__device__ __forceinline__ void ldsm4t(uint32_t (&r)[4], uint32_t a) {
  asm volatile("ldmatrix.sync.aligned.m8n8.x4.trans.shared.b16 {%0,%1,%2,%3}, [%4];" : "=r"(r[0]), "=r"(r[1]), "=r"(r[2]), "=r"(r[3]) : "r"(a) : "memory"); }
__device__ __forceinline__ void stsm4(uint32_t a, uint32_t r0, uint32_t r1, uint32_t r2, uint32_t r3) {
  asm volatile("stmatrix.sync.aligned.m8n8.x4.shared.b16 [%0], {%1,%2,%3,%4};" :: "r"(a), "r"(r0), "r"(r1), "r"(r2), "r"(r3) : "memory"); }
__device__ __forceinline__ void stsm4t(uint32_t a, uint32_t r0, uint32_t r1, uint32_t r2, uint32_t r3) {
  asm volatile("stmatrix.sync.aligned.m8n8.x4.trans.shared.b16 [%0], {%1,%2,%3,%4};" :: "r"(a), "r"(r0), "r"(r1), "r"(r2), "r"(r3) : "memory"); }
__device__ __forceinline__ void lds128(uint32_t (&r)[4], uint32_t a) {
  asm volatile("ld.shared.v4.u32 {%0,%1,%2,%3}, [%4];" : "=r"(r[0]), "=r"(r[1]), "=r"(r[2]), "=r"(r[3]) : "r"(a) : "memory"); }
__device__ __forceinline__ float4 lds128f(uint32_t a) { float4 r;
  asm volatile("ld.shared.v4.f32 {%0,%1,%2,%3}, [%4];" : "=f"(r.x), "=f"(r.y), "=f"(r.z), "=f"(r.w) : "r"(a) : "memory"); return r; }
__device__ __forceinline__ float2 lds64f(uint32_t a) { float2 r;
  asm volatile("ld.shared.v2.f32 {%0,%1}, [%2];" : "=f"(r.x), "=f"(r.y) : "r"(a) : "memory"); return r; }
__device__ __forceinline__ void sts128(uint32_t a, uint32_t r0, uint32_t r1, uint32_t r2, uint32_t r3) {
  asm volatile("st.shared.v4.u32 [%0], {%1,%2,%3,%4};" :: "r"(a), "r"(r0), "r"(r1), "r"(r2), "r"(r3) : "memory"); }
__device__ __forceinline__ void sts64f(uint32_t a, float x, float y) { asm volatile("st.shared.v2.f32 [%0], {%1,%2};" :: "r"(a), "f"(x), "f"(y) : "memory"); }
__device__ __forceinline__ void sts32f(uint32_t a, float x) { asm volatile("st.shared.f32 [%0], %1;" :: "r"(a), "f"(x) : "memory"); }
__device__ __forceinline__ void mma16816(float (&d)[4], uint32_t a0, uint32_t a1, uint32_t a2, uint32_t a3, uint32_t b0, uint32_t b1) {
  asm volatile("mma.sync.aligned.m16n8k16.row.col.f32.bf16.bf16.f32 {%0,%1,%2,%3}, {%4,%5,%6,%7}, {%8,%9}, {%0,%1,%2,%3};"
    : "+f"(d[0]), "+f"(d[1]), "+f"(d[2]), "+f"(d[3]) : "r"(a0), "r"(a1), "r"(a2), "r"(a3), "r"(b0), "r"(b1)); }
__device__ __forceinline__ void mma1688(float (&d)[4], uint32_t a0, uint32_t a1, uint32_t b0) {
  asm volatile("mma.sync.aligned.m16n8k8.row.col.f32.bf16.bf16.f32 {%0,%1,%2,%3}, {%4,%5}, {%6}, {%0,%1,%2,%3};"
    : "+f"(d[0]), "+f"(d[1]), "+f"(d[2]), "+f"(d[3]) : "r"(a0), "r"(a1), "r"(b0)); }
__device__ __forceinline__ void ldx128(uint32_t (&r)[4], const void* p) {
  asm volatile("{.reg .b128 t; .reg .b64 a, b; ld.relaxed.gpu.global.b128 t, [%4]; mov.b128 {a, b}, t; mov.b64 {%0,%1}, a; mov.b64 {%2,%3}, b;}"
    : "=r"(r[0]), "=r"(r[1]), "=r"(r[2]), "=r"(r[3]) : "l"(p) : "memory"); }
__device__ __forceinline__ void ldx2x64(uint32_t (&r)[4], const void* p) {
  asm volatile("{.reg .b64 a, b; ld.relaxed.gpu.global.v2.b64 {a, b}, [%4]; mov.b64 {%0,%1}, a; mov.b64 {%2,%3}, b;}"
    : "=r"(r[0]), "=r"(r[1]), "=r"(r[2]), "=r"(r[3]) : "l"(p) : "memory"); }
__device__ __forceinline__ void stx128(void* p, uint32_t r0, uint32_t r1, uint32_t r2, uint32_t r3) {
  asm volatile("{.reg .b128 t; .reg .b64 a, b; mov.b64 a, {%1,%2}; mov.b64 b, {%3,%4}; mov.b128 t, {a, b}; st.relaxed.gpu.global.b128 [%0], t;}"
    :: "l"(p), "r"(r0), "r"(r1), "r"(r2), "r"(r3) : "memory"); }
__device__ __forceinline__ void stx64(void* p, uint32_t r0, uint32_t r1) {
  asm volatile("{.reg .b64 a; mov.b64 a, {%1,%2}; st.relaxed.gpu.global.b64 [%0], a;}" :: "l"(p), "r"(r0), "r"(r1) : "memory"); }
__device__ __forceinline__ uint32_t uni(uint32_t x) { return __shfl_sync(0xffffffffu, x, 0); }
__device__ __forceinline__ uint32_t pin(uint32_t x) { return __shfl_xor_sync(0xffffffffu, x, 0); }
__device__ __forceinline__ float ex2(float x) { float r; asm("ex2.approx.ftz.f32 %0, %1;" : "=f"(r) : "f"(x)); return r; }
__device__ __forceinline__ void wg_fence() { asm volatile("wgmma.fence.sync.aligned;" ::: "memory"); }
__device__ __forceinline__ void wg_commit() { asm volatile("wgmma.commit_group.sync.aligned;" ::: "memory"); }
template <int N> __device__ __forceinline__ void wg_wait() { asm volatile("wgmma.wait_group.sync.aligned %0;" :: "n"(N) : "memory"); }

__device__ __forceinline__ void wgmma_ss_n256_tb1(float (&d)[128], uint64_t da, uint64_t db, int sc) {
  asm volatile("{.reg .pred p; setp.ne.b32 p, %130, 0;\n"
    "wgmma.mma_async.sync.aligned.m64n256k16.f32.bf16.bf16 {%0,%1,%2,%3,%4,%5,%6,%7,%8,%9,%10,%11,%12,%13,%14,%15,%16,%17,%18,%19,%20,%21,%22,%23,%24,%25,%26,%27,%28,%29,%30,%31,%32,%33,%34,%35,%36,%37,%38,%39,%40,%41,%42,%43,%44,%45,%46,%47,%48,%49,%50,%51,%52,%53,%54,%55,%56,%57,%58,%59,%60,%61,%62,%63,%64,%65,%66,%67,%68,%69,%70,%71,%72,%73,%74,%75,%76,%77,%78,%79,%80,%81,%82,%83,%84,%85,%86,%87,%88,%89,%90,%91,%92,%93,%94,%95,%96,%97,%98,%99,%100,%101,%102,%103,%104,%105,%106,%107,%108,%109,%110,%111,%112,%113,%114,%115,%116,%117,%118,%119,%120,%121,%122,%123,%124,%125,%126,%127}, %128, %129, p, 1, 1, 0, 1;}\n"
    : "+f"(d[0]),"+f"(d[1]),"+f"(d[2]),"+f"(d[3]),"+f"(d[4]),"+f"(d[5]),"+f"(d[6]),"+f"(d[7]),"+f"(d[8]),"+f"(d[9]),"+f"(d[10]),"+f"(d[11]),"+f"(d[12]),"+f"(d[13]),"+f"(d[14]),"+f"(d[15]),"+f"(d[16]),"+f"(d[17]),"+f"(d[18]),"+f"(d[19]),"+f"(d[20]),"+f"(d[21]),"+f"(d[22]),"+f"(d[23]),"+f"(d[24]),"+f"(d[25]),"+f"(d[26]),"+f"(d[27]),"+f"(d[28]),"+f"(d[29]),"+f"(d[30]),"+f"(d[31]),"+f"(d[32]),"+f"(d[33]),"+f"(d[34]),"+f"(d[35]),"+f"(d[36]),"+f"(d[37]),"+f"(d[38]),"+f"(d[39]),"+f"(d[40]),"+f"(d[41]),"+f"(d[42]),"+f"(d[43]),"+f"(d[44]),"+f"(d[45]),"+f"(d[46]),"+f"(d[47]),"+f"(d[48]),"+f"(d[49]),"+f"(d[50]),"+f"(d[51]),"+f"(d[52]),"+f"(d[53]),"+f"(d[54]),"+f"(d[55]),"+f"(d[56]),"+f"(d[57]),"+f"(d[58]),"+f"(d[59]),"+f"(d[60]),"+f"(d[61]),"+f"(d[62]),"+f"(d[63]),"+f"(d[64]),"+f"(d[65]),"+f"(d[66]),"+f"(d[67]),"+f"(d[68]),"+f"(d[69]),"+f"(d[70]),"+f"(d[71]),"+f"(d[72]),"+f"(d[73]),"+f"(d[74]),"+f"(d[75]),"+f"(d[76]),"+f"(d[77]),"+f"(d[78]),"+f"(d[79]),"+f"(d[80]),"+f"(d[81]),"+f"(d[82]),"+f"(d[83]),"+f"(d[84]),"+f"(d[85]),"+f"(d[86]),"+f"(d[87]),"+f"(d[88]),"+f"(d[89]),"+f"(d[90]),"+f"(d[91]),"+f"(d[92]),"+f"(d[93]),"+f"(d[94]),"+f"(d[95]),"+f"(d[96]),"+f"(d[97]),"+f"(d[98]),"+f"(d[99]),"+f"(d[100]),"+f"(d[101]),"+f"(d[102]),"+f"(d[103]),"+f"(d[104]),"+f"(d[105]),"+f"(d[106]),"+f"(d[107]),"+f"(d[108]),"+f"(d[109]),"+f"(d[110]),"+f"(d[111]),"+f"(d[112]),"+f"(d[113]),"+f"(d[114]),"+f"(d[115]),"+f"(d[116]),"+f"(d[117]),"+f"(d[118]),"+f"(d[119]),"+f"(d[120]),"+f"(d[121]),"+f"(d[122]),"+f"(d[123]),"+f"(d[124]),"+f"(d[125]),"+f"(d[126]),"+f"(d[127])
    : "l"(da), "l"(db), "r"(sc));
}

__device__ __forceinline__ void wgmma_ss_n128_tb1(float (&d)[64], uint64_t da, uint64_t db, int sc) {
  asm volatile("{.reg .pred p; setp.ne.b32 p, %66, 0;\n"
    "wgmma.mma_async.sync.aligned.m64n128k16.f32.bf16.bf16 {%0,%1,%2,%3,%4,%5,%6,%7,%8,%9,%10,%11,%12,%13,%14,%15,%16,%17,%18,%19,%20,%21,%22,%23,%24,%25,%26,%27,%28,%29,%30,%31,%32,%33,%34,%35,%36,%37,%38,%39,%40,%41,%42,%43,%44,%45,%46,%47,%48,%49,%50,%51,%52,%53,%54,%55,%56,%57,%58,%59,%60,%61,%62,%63}, %64, %65, p, 1, 1, 0, 1;}\n"
    : "+f"(d[0]),"+f"(d[1]),"+f"(d[2]),"+f"(d[3]),"+f"(d[4]),"+f"(d[5]),"+f"(d[6]),"+f"(d[7]),"+f"(d[8]),"+f"(d[9]),"+f"(d[10]),"+f"(d[11]),"+f"(d[12]),"+f"(d[13]),"+f"(d[14]),"+f"(d[15]),"+f"(d[16]),"+f"(d[17]),"+f"(d[18]),"+f"(d[19]),"+f"(d[20]),"+f"(d[21]),"+f"(d[22]),"+f"(d[23]),"+f"(d[24]),"+f"(d[25]),"+f"(d[26]),"+f"(d[27]),"+f"(d[28]),"+f"(d[29]),"+f"(d[30]),"+f"(d[31]),"+f"(d[32]),"+f"(d[33]),"+f"(d[34]),"+f"(d[35]),"+f"(d[36]),"+f"(d[37]),"+f"(d[38]),"+f"(d[39]),"+f"(d[40]),"+f"(d[41]),"+f"(d[42]),"+f"(d[43]),"+f"(d[44]),"+f"(d[45]),"+f"(d[46]),"+f"(d[47]),"+f"(d[48]),"+f"(d[49]),"+f"(d[50]),"+f"(d[51]),"+f"(d[52]),"+f"(d[53]),"+f"(d[54]),"+f"(d[55]),"+f"(d[56]),"+f"(d[57]),"+f"(d[58]),"+f"(d[59]),"+f"(d[60]),"+f"(d[61]),"+f"(d[62]),"+f"(d[63])
    : "l"(da), "l"(db), "r"(sc));
}

template <int BN> struct WG;
template <> struct WG<256> { static __device__ __forceinline__ void mma(float (&d)[128], uint64_t a, uint64_t b, int sc) { wgmma_ss_n256_tb1(d, a, b, sc); } };
template <> struct WG<128> { static __device__ __forceinline__ void mma(float (&d)[64], uint64_t a, uint64_t b, int sc) { wgmma_ss_n128_tb1(d, a, b, sc); } };

struct GemmMaps { CUtensorMap a, b[3], c; };
template <int BN, int STAGES>
__global__ void __cluster_dims__(2, 1, 1) __launch_bounds__(384, 1)
gemm_kernel(const __grid_constant__ GemmMaps maps, int tilesM, int tilesN, int kblocks, int nPerB, uint4* __restrict__ clearX) {
  extern __shared__ __align__(1024) uint8_t smem_raw[];
  constexpr int STAGE_BYTES = 16384 + BN * 128;
  constexpr int NBOX = BN / 64;
  const uint32_t sbase = (smem_u32(smem_raw) + 1023) & ~1023u;
  const uint32_t sEpi = sbase + STAGES * STAGE_BYTES;
  const uint32_t sBar = sEpi + 32768;
  const int warp = threadIdx.x >> 5, lane = threadIdx.x & 31, wg = warp >> 2;
  uint32_t crank; asm("mov.u32 %0, %%cluster_ctarank;" : "=r"(crank));
  if (threadIdx.x == 0) {
    for (int i = 0; i < STAGES; i++) { mbar_init(sBar + 8 * i, 1); mbar_init(sBar + 8 * (STAGES + i), 4); }
    asm volatile("fence.mbarrier_init.release.cluster;" ::: "memory");
  }
  for (int i = blockIdx.x * 384 + threadIdx.x; i < (int)(sizeof(Xchg) / 16); i += gridDim.x * 384) clearX[i] = make_uint4(0, 0, 0, 0);
  asm volatile("barrier.cluster.arrive.release.aligned; barrier.cluster.wait.acquire.aligned;" ::: "memory");
  const int npairs = (tilesM >> 1) * tilesN, pair0 = blockIdx.x >> 1, pstep = gridDim.x >> 1;
  if (wg == 2) {
    asm volatile("setmaxnreg.dec.sync.aligned.u32 40;");
    if (warp == 8 && lane == 0) {
      int st = 0, ph = 1;
      for (int p = pair0; p < npairs; p += pstep) {
        const int tm = (p % (tilesM >> 1)) * 2 + crank, tn = p / (tilesM >> 1);
        const CUtensorMap* mb = &maps.b[tn / nPerB];
        const int n0 = (tn % nPerB) * BN;
        for (int kb = 0; kb < kblocks; kb++) {
          mbar_wait(sBar + 8 * (STAGES + st), ph);
          const uint32_t a = sbase + st * STAGE_BYTES, full = sBar + 8 * st;
          mbar_expect_tx(full, STAGE_BYTES);
          tma2d(a, &maps.a, kb * 64, tm * 128, full);
#pragma unroll
          for (int i = 0; i < NBOX / 2; i++) {
            const int bx = crank * (NBOX / 2) + i;
            tma2d_mc(a + 16384 + bx * 8192, mb, n0 + bx * 64, kb * 64, full, (uint16_t)3);
          }
          if (++st == STAGES) { st = 0; ph ^= 1; }
        }
      }
      for (int i = 0; i < STAGES; i++) { mbar_wait(sBar + 8 * (STAGES + st), ph); if (++st == STAGES) { st = 0; ph ^= 1; } }
    }
  } else {
    asm volatile("setmaxnreg.inc.sync.aligned.u32 232;");
    int st = 0, ph = 0;
    float acc[BN / 2];
    const uint64_t descA0 = (uint64_t)(((sbase + wg * 8192) & 0x3FFFF) >> 4) | (1ull << 16) | (64ull << 32) | (1ull << 62);
    const uint64_t descB0 = (uint64_t)(((sbase + 16384) & 0x3FFFF) >> 4) | (512ull << 16) | (64ull << 32) | (1ull << 62);
    const uint32_t epi = sEpi + wg * 16384;
    for (int p = pair0; p < npairs; p += pstep) {
      const int tm = (p % (tilesM >> 1)) * 2 + crank, tn = p / (tilesM >> 1);
      int prev = -1;
      for (int kb = 0; kb < kblocks; kb++) {
        mbar_wait(sBar + 8 * st, ph);
        wg_fence();
        const uint64_t so = (uint64_t)(st * (STAGE_BYTES >> 4));
#pragma unroll
        for (int k = 0; k < 4; k++) WG<BN>::mma(acc, descA0 + so + k * 2, descB0 + so + k * 128, kb | k);
        wg_commit();
        if (prev >= 0) {
          wg_wait<1>();
          if ((threadIdx.x & 127) < 2) mbar_arrive_cluster(sBar + 8 * (STAGES + prev), threadIdx.x & 1);
        }
        prev = st;
        if (++st == STAGES) { st = 0; ph ^= 1; }
      }
      wg_wait<0>();
      if ((threadIdx.x & 127) < 2) mbar_arrive_cluster(sBar + 8 * (STAGES + prev), threadIdx.x & 1);
#pragma unroll
      for (int r = 0; r < BN / 128; r++) {
        if ((threadIdx.x & 127) == 0) asm volatile("cp.async.bulk.wait_group.read 0;" ::: "memory");
        bar_sync(1 + wg, 128);
        const int row = (warp & 3) * 16 + (lane & 15);
#pragma unroll
        for (int i = 0; i < 8; i++) {
          const int c = 2 * (i & 3) + (lane >> 4);
          const float* q = &acc[r * 64 + i * 8];
          stsm4(epi + (i >> 2) * 8192 + row * 128 + ((c ^ (row & 7)) << 4), pack2(q[0], q[1]), pack2(q[2], q[3]), pack2(q[4], q[5]), pack2(q[6], q[7]));
        }
        fence_async();
        bar_sync(1 + wg, 128);
        if ((threadIdx.x & 127) == 0) {
          tma2d_store(&maps.c, epi, tn * BN + r * 128, tm * 128 + wg * 64);
          tma2d_store(&maps.c, epi + 8192, tn * BN + r * 128 + 64, tm * 128 + wg * 64);
          asm volatile("cp.async.bulk.commit_group;" ::: "memory");
        }
      }
    }
    if ((threadIdx.x & 127) == 0) asm volatile("cp.async.bulk.wait_group 0;" ::: "memory");
  }
}

struct Dft { uint32_t m[2][2][2][4]; };
template <bool P4> __device__ __forceinline__ int fidx(int tile, int x) { return P4 ? 4 * (x >> 1) + 2 * (tile & 1) + (x & 1) + 16 * (tile >> 1) : x + 8 * tile; }
__device__ __forceinline__ float2 cis(int k, int n) {
  k &= n - 1; if (2 * k > n) k -= n;
  const float a = (float)k * (6.283185307179586f / (float)n);
  return make_float2(__cosf(a), __sinf(a));
}
template <bool OUT4> __device__ __forceinline__ void make_dft(Dft& D, int g, int t) {
#pragma unroll
  for (int q = 0; q < 16; q++) {
    const int b = q >> 3, u = (q >> 2) & 1, r = (q >> 1) & 1, v = q & 1;
    const float2 w = cis(fidx<OUT4>(v, g) * fidx<false>(2 * u + r, 2 * t + b), 32);
    D.m[b][u][0][q & 3] = pack2(w.x, w.y); D.m[b][u][1][q & 3] = pack2(-w.y, w.x);
  }
}
__device__ __forceinline__ void mma_dc(float (&d)[4], uint32_t a0, uint32_t a1, uint32_t a2, uint32_t a3, uint32_t b0, uint32_t b1, const float (&c)[4]) {
  asm("mma.sync.aligned.m16n8k16.row.col.f32.bf16.bf16.f32 {%0,%1,%2,%3}, {%4,%5,%6,%7}, {%8,%9}, {%10,%11,%12,%13};"
    : "=f"(d[0]), "=f"(d[1]), "=f"(d[2]), "=f"(d[3]) : "r"(a0), "r"(a1), "r"(a2), "r"(a3), "r"(b0), "r"(b1), "f"(c[0]), "f"(c[1]), "f"(c[2]), "f"(c[3])); }
__device__ __forceinline__ void dft_b(const Dft& D, const uint32_t (&x)[2][4], float (&o)[2][8]) {
#pragma unroll
  for (int ri = 0; ri < 2; ri++) {
    float z[4] = {0.f, 0.f, 0.f, 0.f}, e[4], p[4];
    mma_dc(e, D.m[0][0][ri][0], D.m[0][0][ri][1], D.m[0][0][ri][2], D.m[0][0][ri][3], x[0][0], x[0][1], z);
    mma_dc(e, D.m[0][1][ri][0], D.m[0][1][ri][1], D.m[0][1][ri][2], D.m[0][1][ri][3], x[0][2], x[0][3], e);
    mma_dc(p, D.m[1][0][ri][0], D.m[1][0][ri][1], D.m[1][0][ri][2], D.m[1][0][ri][3], x[1][0], x[1][1], e);
    mma_dc(p, D.m[1][1][ri][0], D.m[1][1][ri][1], D.m[1][1][ri][2], D.m[1][1][ri][3], x[1][2], x[1][3], p);
#pragma unroll
    for (int q = 0; q < 4; q++) { o[ri][q] = p[q]; o[ri][4 + q] = fmaf(2.f, e[q], -p[q]); }
  }
}
__device__ __forceinline__ void dft_a(const uint32_t (&m)[2][2][4], const uint32_t (&x0)[2][4], const uint32_t (&x1)[2][4], float (&o)[2][8]) {
#pragma unroll
  for (int ri = 0; ri < 2; ri++) {
    float z[4] = {0.f, 0.f, 0.f, 0.f}, e[4], p[4];
    mma_dc(e, x0[0][0], x1[0][0], x0[0][1], x1[0][1], m[0][ri][0], m[0][ri][1], z);
    mma_dc(e, x0[0][2], x1[0][2], x0[0][3], x1[0][3], m[0][ri][2], m[0][ri][3], e);
    mma_dc(p, x0[1][0], x1[1][0], x0[1][1], x1[1][1], m[1][ri][0], m[1][ri][1], e);
    mma_dc(p, x0[1][2], x1[1][2], x0[1][3], x1[1][3], m[1][ri][2], m[1][ri][3], p);
#pragma unroll
    for (int q = 0; q < 4; q++) { o[ri][q] = p[q]; o[ri][4 + q] = fmaf(2.f, e[q], -p[q]); }
  }
}
__device__ __forceinline__ uint32_t twid(float re, float im, float c, float s) { return pack2(fmaf(re, c, im * s), fmaf(im, c, -re * s)); }
__device__ __forceinline__ void cpa16(uint32_t d, const void* s) { asm volatile("cp.async.cg.shared.global [%0], [%1], 16;" :: "r"(d), "l"(s) : "memory"); }
__device__ __forceinline__ void sts32(uint32_t a, uint32_t x) { asm volatile("st.shared.u32 [%0], %1;" :: "r"(a), "r"(x) : "memory"); }
__device__ __forceinline__ void cpa_commit() { asm volatile("cp.async.commit_group;" ::: "memory"); }
template <int N> __device__ __forceinline__ void cpa_wait() { asm volatile("cp.async.wait_group %0;" :: "n"(N) : "memory"); }
__device__ __forceinline__ uint32_t lds32(uint32_t a) { uint32_t r; asm volatile("ld.shared.u32 %0, [%1];" : "=r"(r) : "r"(a) : "memory"); return r; }
#define FMID 0
constexpr int F_TP = 4112, F_TSZ = 8 * F_TP;

__device__ __forceinline__ uint32_t ldnc32(const void* p) { uint32_t v; asm volatile("ld.global.nc.b32 %0, [%1];" : "=r"(v) : "l"(p) : "memory"); return v; }
template <class F>
__device__ __forceinline__ void fft_wprep(const bf16* __restrict__ wr, const bf16* __restrict__ wi, int cta, F&& mid) {
  const int tid = threadIdx.x, g = (cta >> 1) & 7, c = (cta >> 4) & 3, t = 2 * (cta & 1) + (tid & 1);
  const int k0 = g + 8 * (cta >> 6) + 32 * (8 * c + 2 * t), l0 = (tid & ~1) + (g & 1);
  uint32_t a[4][4], b[4][4];
#pragma unroll
  for (int q = 0; q < 16; q++) {
    const int o = (k0 + 16 * (q >> 3) + 32 * ((q >> 1) & 1) + 1024 * (q & 1)) * 513 + l0 + 256 * ((q >> 2) & 1);
    a[q >> 2][q & 3] = ldnc32(wr + o);
    b[q >> 2][q & 3] = ldnc32(wi + o);
  }
  const int e = cta * 32 + (tid & 31), lh = (e >> 11) * 512, k = e & 2047, k2 = (k >> 5) & 31;
  uint32_t hz[4];
#pragma unroll
  for (int q = 0; q < 4; q++) asm volatile("ld.global.nc.u16 %0, [%1];" : "=r"(hz[q]) : "l"((q < 2 ? wr : wi) + (q & 1 ? (2048 - k) & 2047 : k) * 513 + lh) : "memory");
  mid();
  uint4* dst = g_wt + l0 * 512 + cta * 2 + (tid & 1);
#pragma unroll
  for (int q = 0; q < 8; q++) {
    const int hf = q >> 1, l = l0 + 256 * (hf & 1) + (q & 1);
    const uint32_t sel = (q & 1) ? 0x7632 : 0x5410;
    if (l & 511) dst[(256 * (hf & 1) + (q & 1)) * 512 + 256 * (q >> 2)] = make_uint4(__byte_perm(a[hf][0], b[hf][0], sel), __byte_perm(a[hf][1], b[hf][1], sel),
                                                                                   __byte_perm(a[hf][2], b[hf][2], sel), __byte_perm(a[hf][3], b[hf][3], sel));
  }
  if (tid < 32) reinterpret_cast<uint32_t*>(g_wt)[(64 * ((k >> 3) & 3) + 16 * (k2 >> 3) + 2 * (k & 7) + ((k2 >> 2) & 1)) * 8 + lh * 2048 + 2 * (k2 & 3) + (k >> 10)] =
      pack2(0.5f * (__uint_as_float(hz[0] << 16) + __uint_as_float(hz[1] << 16)), 0.5f * (__uint_as_float(hz[2] << 16) - __uint_as_float(hz[3] << 16)));
}

template <class F>
__device__ __forceinline__ void fft_rows_fwd(const bf16* __restrict__ x, const bf16* __restrict__ wr, const bf16* __restrict__ wi, uint32_t tb, int it, F&& mid) {
  const int warp = threadIdx.x >> 5, lane = threadIdx.x & 31, g = lane >> 2, t = lane & 3;
  const uint32_t in = tb + warp * 4096;
  const uint32_t f0 = in + (lane >> 3) * 256 + (((lane & 7) ^ (2 * (lane >> 3))) << 4);
  const bf16* src = x + ((256 * (warp & 3) + 64 * (warp >> 2) + 128 * (it & 1) + 32 * ((it >> 4) & 1) + 8 * (it >> 5) + ((it >> 1) & 7)) * 2048 + lane * 8);
#pragma unroll
  for (int q = 0; q < 8; q++) cpa16((f0 ^ ((q >> 2) * 144)) + (q & 3) * 1024, src + q * 256);
  cpa_commit();
  Dft D;
  float2 tw[4][8];
  fft_wprep(wr, wi, it, [&]() {
    if (FMID == 0) mid();
    make_dft<true>(D, g, t);
#pragma unroll
    for (int q = 0; q < 32; q++) {
      tw[q >> 3][q & 7] = cis(fidx<true>((q >> 1) & 3, g) * fidx<false>(q >> 3, 2 * t + (q & 1)), 1024);
      if (FMID) asm volatile("" : "+f"(tw[q >> 3][q & 7].x), "+f"(tw[q >> 3][q & 7].y) :: "memory");
    }
    if (FMID == 1) mid();
  });
  if (FMID == 2) mid();
  cpa_wait<0>(); __syncwarp();
  uint32_t a[4][2][4], y[4][2][4];
#pragma unroll
  for (int q = 0; q < 8; q++) ldsm4t(a[q & 3][q >> 2], (in + lane * 128 + ((lane & 7) << 4)) ^ (q << 4));
  float o[2][8];
#pragma unroll
  for (int i = 0; i < 4; i++) {
    dft_b(D, a[i], o);
#pragma unroll
    for (int q = 0; q < 8; q++) y[q >> 1][q & 1][i] = twid(o[0][q], o[1][q], tw[i][q].x, tw[i][q].y);
  }
  __syncthreads();
  const uint32_t w0 = tb + warp * F_TP + fidx<true>(0, g) * 128 + t * 16 + ((g & 1) << 6), wz = (g & 1) ? -64 : 64;
#pragma unroll
  for (int z = 0; z < 2; z++) {
    float o2[2][8];
    dft_b(D, y[2 * z], o); dft_b(D, y[2 * z + 1], o2);
#pragma unroll
    for (int i = 0; i < 4; i++) {
      const float sg = i < 2 ? 1.f : -1.f;
      sts128(w0 + z * wz + fidx<true>(i, 0) * 128, pack2(o[0][2 * i], sg * o[1][2 * i]), pack2(o[0][2 * i + 1], sg * o[1][2 * i + 1]),
             pack2(o2[0][2 * i], sg * o2[1][2 * i]), pack2(o2[0][2 * i + 1], sg * o2[1][2 * i + 1]));
    }
  }
  __syncthreads();
  const uint32_t ra = tb + (lane & 1) * 4 * F_TP + ((lane >> 1) + 16 * (warp ^ ((warp >> 1) & 1))) * 4;
  uint4* dst = g_y + (threadIdx.x >> 1) * 256 + (lane & 1) + it * 2;
#pragma unroll
  for (int q = 0; q < 8; q++) { const uint32_t r = ra + q * 512; dst[q * 32768] = make_uint4(lds32(r), lds32(r + F_TP), lds32(r + 2 * F_TP), lds32(r + 3 * F_TP)); }
}

__device__ __forceinline__ void fft_cols(uint32_t sb, int cta, int ncta) {
  const int warp = threadIdx.x >> 5, lane = threadIdx.x & 31, g = lane >> 2, t = lane & 3;
  const uint32_t in = sb + warp * 16384 + lane * 16, tab = sb + 131072 + lane * 16;
  auto fetch_y = [&](int l) {
#pragma unroll
    for (int q = 0; q < 16; q++) cpa16(in + q * 512, g_y + (q < 8 ? l : (1024 - l) & 1023) * 256 + (q & 7) * 32 + lane);
  };
  auto fetch_w = [&](int l) {
#pragma unroll
    for (int q = 0; q < 16; q++) cpa16(in + 8192 + q * 512, g_wt + l * 512 + q * 32 + lane);
  };
  const int l0 = cta * 8 + warp, dl = ncta * 8;
  if (l0 <= 512) fetch_y(l0);
  cpa_commit();
  if (l0 <= 512) fetch_w(l0);
  cpa_commit();
  Dft D; make_dft<false>(D, g, t);
#pragma unroll
  for (int q = 2 * warp; q < 2 * warp + 2; q++) {
    const int r = fidx<false>(q & 3, g), c = fidx<false>(q >> 2, 2 * t);
    const float2 w0 = cis(r * c, 1024), w1 = cis(r * c + r, 1024), p0 = cis(r + 32 * c, 2048), p1 = cis(r + 32 * c + 32, 2048);
    sts128(tab + q * 512, __float_as_uint(w0.x), __float_as_uint(w0.y), __float_as_uint(w1.x), __float_as_uint(w1.y));
    sts128(tab + 8192 + q * 512, __float_as_uint(p0.x), __float_as_uint(p0.y), __float_as_uint(p1.x), __float_as_uint(p1.y));
  }
  if (warp == 0) {
#pragma unroll
    for (int q = 0; q < 8; q++) {
      const int v = q >> 2, b = (q >> 1) & 1, ri = q & 1;
      sts128(tab + 16384 + q * 512, D.m[b][0][ri][v], D.m[b][0][ri][v + 2], D.m[b][1][ri][v], D.m[b][1][ri][v + 2]);
    }
  }
  __syncthreads();
#pragma unroll 1
  for (int l = l0; l <= 512; l += dl) {
    uint32_t a[2][4][2][4], y[2][4][2][4];
    float o[2][2][8];
    cpa_wait<1>();
#pragma unroll
    for (int q = 0; q < 16; q++) lds128(a[q >> 3][(q >> 1) & 3][q & 1], in + q * 512);
    if (!(l & 511)) {
      const uint32_t m0 = l ? 0x80000000u : 0u;
#pragma unroll
      for (int q = 0; q < 32; q++) { a[0][q >> 3][(q >> 2) & 1][q & 3] ^= m0; a[1][q >> 3][(q >> 2) & 1][q & 3] ^= m0 ^ 0x80000000u; }
    }
    auto first = [&]() {
#pragma unroll
      for (int i = 0; i < 4; i++) {
        dft_b(D, a[0][i], o[0]); dft_b(D, a[1][i], o[1]);
#pragma unroll
        for (int r = 0; r < 4; r++) {
          const float4 w = lds128f(tab + (4 * i + r) * 512);
#pragma unroll
          for (int s = 0; s < 2; s++) {
            y[s][r][0][i] = twid(o[s][0][2 * r], o[s][1][2 * r], w.x, w.y);
            y[s][r][1][i] = twid(o[s][0][2 * r + 1], o[s][1][2 * r + 1], w.z, w.w);
          }
        }
      }
    };
    first();
    if (l + dl <= 512) fetch_y(l + dl);
    cpa_commit();
    cpa_wait<1>();
#pragma unroll
    for (int zv = 0; zv < 4; zv++) {
      const int z = zv >> 1, v = zv & 1;
      uint32_t m[2][2][4];
#pragma unroll
      for (int q = 0; q < 4; q++) lds128(m[q >> 1][q & 1], tab + 16384 + (4 * v + q) * 512);
      dft_a(m, y[0][2 * z], y[0][2 * z + 1], o[0]); dft_a(m, y[1][2 * z], y[1][2 * z + 1], o[1]);
#pragma unroll
      for (int q = 0; q < 4; q++) {
        const int i = 2 * z + (q & 1), c = v + (q & 2);
        uint32_t w[4]; lds128(w, in + 8192 + (4 * i + c) * 512);
        const float4 ph = lds128f(tab + 8192 + (4 * c + i) * 512);
#pragma unroll
        for (int b = 0; b < 2; b++) {
          const float cs = b ? ph.z : ph.x, sn = b ? ph.w : ph.y;
          const float r1 = __uint_as_float(w[2 * b] << 16), i1 = __uint_as_float(w[2 * b] & 0xFFFF0000u);
          const float r2 = __uint_as_float(w[2 * b + 1] << 16), i2 = __uint_as_float(w[2 * b + 1] & 0xFFFF0000u);
          const float Sr = r1 + r2, Si = i1 + i2, Dr = r1 - r2, Di = i1 - i2;
          const float ar = fmaf(-Dr, sn, Sr), ai = fmaf(-Di, sn, Si), dr = fmaf(Dr, sn, Sr), di = fmaf(Di, sn, Si), br = -Di * cs, bi = Dr * cs;
          const float Ar = o[0][0][2 * q + b], Ai = o[0][1][2 * q + b], Br = o[1][0][2 * q + b], Bi = o[1][1][2 * q + b];
          a[0][i][b][c] = pack2(fmaf(ar, Ai, fmaf(ai, Ar, fmaf(br, Bi, bi * Br))), fmaf(ar, Ar, fmaf(-ai, Ai, fmaf(br, Br, -bi * Bi))));
          a[1][i][b][c] = pack2(fmaf(dr, Bi, fmaf(di, Br, fmaf(-br, Ai, -bi * Ar))), fmaf(dr, Br, fmaf(-di, Bi, fmaf(-br, Ar, bi * Ai))));
        }
      }
    }
    if (l + dl <= 512) fetch_w(l + dl);
    cpa_commit();
    first();
#pragma unroll
    for (int s = 0; s < 2; s++) {
      uint4* dst = g_y + (s ? (1024 - l) & 1023 : l) * 256 + lane;
      const float sg = s ? -1.f : 1.f;
#pragma unroll
      for (int i = 0; i < 4; i++) {
        dft_b(D, y[s][i], o[0]);
#pragma unroll
        for (int b = 0; b < 2; b++)
          dst[(2 * i + b) * 32] = make_uint4(pack2(sg * o[0][0][b], o[0][1][b]), pack2(sg * o[0][0][2 + b], o[0][1][2 + b]),
                                             pack2(sg * o[0][0][4 + b], o[0][1][4 + b]), pack2(sg * o[0][0][6 + b], o[0][1][6 + b]));
      }
    }
  }
}

__device__ __forceinline__ void fft_rows_inv(const CUtensorMap* om, uint32_t sb, int cta, int ncta) {
  const int warp = threadIdx.x >> 5, lane = threadIdx.x & 31, g = lane >> 2, t = lane & 3, wg = warp >> 2, w4 = warp & 3;
  const uint32_t tb = sb + 32768 + wg * 2 * F_TSZ;
  const uint4* src = g_y + pin((256 * ((lane >> 1) & 3) + 64 * (lane >> 3) + 8 * w4) * 256 + (lane & 1));
  const uint32_t wa = pin(tb + (lane & 1) * 4 * F_TP + w4 * 1024 + (lane >> 1) * 4);
  uint4 pf[8];
  auto fetch = [&](int it, int hf) {
#pragma unroll
    for (int q = 0; q < 8; q++) pf[q] = __ldcg(src + (it * 2 + hf * 8192) + q * 256);
  };
  auto put = [&](uint32_t off) {
#pragma unroll
    for (int q = 0; q < 8; q++) {
      sts32(wa + off + q * 64, pf[q].x); sts32(wa + off + q * 64 + F_TP, pf[q].y);
      sts32(wa + off + q * 64 + 2 * F_TP, pf[q].z); sts32(wa + off + q * 64 + 3 * F_TP, pf[q].w);
    }
  };
  const int it0 = 2 * cta + wg;
  if (it0 >= 128) return;
  fetch(it0, 0); put(0); fetch(it0, 1); put(512);
  Dft D; make_dft<false>(D, g, t);
  float2 tw[4][8];
#pragma unroll
  for (int q = 0; q < 32; q++) {
    tw[q >> 3][q & 7] = cis(fidx<false>((q >> 1) & 3, g) * fidx<false>(q >> 3, 2 * t + (q & 1)), 1024);
    tw[q >> 3][q & 7].x *= 1.f / 2097152.f; tw[q >> 3][q & 7].y *= 1.f / 2097152.f;
  }
  const uint32_t la = pin(tb + w4 * F_TP + lane * 16), ob = uni(sb + warp * 4096);
  const uint32_t oa = pin(ob + (lane >> 1) * 128 + (((4 * (lane & 1)) ^ ((lane >> 1) & 7)) << 4));
#pragma unroll 1
  for (int n = 0;; n++) {
    const int it = it0 + (n >> 1) * 2 * ncta, hf = n & 1, buf = (n >> 1) & 1;
    if (it >= 128) break;
    if (!hf) bar_sync(1 + wg, 128);
    uint32_t a[4][2][4], y[4][2][4];
#pragma unroll
    for (int q = 0; q < 8; q++) lds128(a[q >> 1][q & 1], la + buf * F_TSZ + hf * 4 * F_TP + q * 512);
    fetch(min(it + 2 * ncta, 127), hf);
    float o[2][8];
#pragma unroll
    for (int i = 0; i < 4; i++) {
      dft_b(D, a[i], o);
#pragma unroll
      for (int q = 0; q < 8; q++) y[q >> 1][q & 1][i] = twid(o[0][q], o[1][q], tw[i][q].x, tw[i][q].y);
    }
    if (lane == 0) asm volatile("cp.async.bulk.wait_group.read 0;" ::: "memory");
    __syncwarp();
#pragma unroll
    for (int c = 0; c < 4; c++) {
      dft_b(D, y[c], o);
#pragma unroll
      for (int ri = 0; ri < 2; ri++)
        stsm4((oa ^ (c << 4)) + (1 - ri) * 2048, pack2(o[ri][0], o[ri][1]), pack2(o[ri][2], o[ri][3]), pack2(o[ri][4], o[ri][5]), pack2(o[ri][6], o[ri][7]));
    }
    fence_async();
    __syncwarp();
    if (lane == 0) {
      const int m = 256 * w4 + 32 * ((it >> 1) & 7) + 8 * (it >> 5) + 4 * (it & 1) + 2 * hf + ((it >> 4) & 1);
      asm volatile("cp.async.bulk.tensor.3d.global.shared::cta.bulk_group [%0, {0, 0, %2}], [%1];" :: "l"(om), "r"(ob), "r"(2 * m) : "memory");
      asm volatile("cp.async.bulk.commit_group;" ::: "memory");
    }
    put((buf ^ 1) * F_TSZ + hf * 512);
  }
  if (lane == 0) asm volatile("cp.async.bulk.wait_group 0;" ::: "memory");
}
__device__ __forceinline__ void grid_arrive(unsigned* ctr) {
  __syncthreads();
  if (threadIdx.x == 0) { __threadfence(); atomicAdd(ctr, 1u); }
}
__device__ __forceinline__ void grid_wait(unsigned* ctr, unsigned n) {
  if (threadIdx.x == 0) {
    int it = 0;
    while (*reinterpret_cast<volatile unsigned*>(ctr) < n) { __nanosleep(200); if (++it > SPIN_LIMIT) { g_err = 3; break; } }
    __threadfence();
  }
  __syncthreads();
}

struct RecMaps { CUtensorMap wq, wk, wv, wo, x, k, q, v, fo; };
#define NSW 16
#define EXP 0
#define NPB 3
#define NPB0 3
#define NPC 0
#define WOP 2
#define HOME 7
#define DL0 14
#define PD1 4
#define NE4 6
#define NE6 0
#define NA4 14
#define NA6 18
#define NB1 24
#define TQL 7
#define NQ 16
#define TQP (NQ - 1)
#define OXPOS 4
#define KVPOS 2
#define NK0 0
#define FLPOS 1
#define XWPOS 10
#define FSPOS 28
#define RL0 4
#define RLS 6
#define RLB 4
#define VL0 3
#define RI 9
#define RJ 8
#define NPRE 22
#define PFD 4
#define PD0 4
#define VB NV0
#define NPA 0
#define N1 16
#define DL1 16
#define PACE 0
#define RE0 0
#define RE1 0
#define RP1 23
#define UNP 1
#define X2 2
#define X3 2
#define SPOS 2
#ifndef NV0
#define NV0 4
#endif
#define TGP 3
#define FENP 0
#define LW0 8
#define X1 4
#define X0 4
constexpr int R_WO = 0, R_X = 65536, R_MEM = 131072, R_WC = 147456, R_RED = R_WC + NSW * 2048, R_O = R_RED, R_S = R_O + 2048, R_P = R_S + 3072, R_STAGE = R_P + 2048,
              R_K = R_STAGE + 8192, R_Q = R_K + 8192, R_V = R_Q + 2048, R_ID = R_V + 16384, R_T = R_ID + 512, R_DST = R_T + 512, R_RD = R_DST + 2048, R_BAR = R_RD + 2048, R_TS = R_BAR + 128,
              R_TOTAL = R_TS;
#define TS(i)
#define LOG(i, v)
constexpr int B_KV = R_BAR, B_W = R_BAR + 8, B_X = R_BAR + 80, B_PK = R_BAR + 24, B_C = R_BAR + 32, B_B = R_BAR + 40, B_DUE = R_BAR + 48, B_ONE = R_BAR + 64;
#define DLY_A 150
#define DLY_V 150
#define DLY_C 200
#define DLY_L 90
#define NS_B 1088
#define NS_C 1728
#define NS_P 2624
#define NS_V 128
#define NS_F 896
#define NS_K 128
#define NS_M 32
#define NS_X 128
#define NS_Z 192
#define NS_Y 704
#define NS_PEN 1024
__device__ __forceinline__ float rcp(float x) { float r; asm("rcp.approx.ftz.f32 %0, %1;" : "=f"(r) : "f"(x)); return r; }
__device__ __forceinline__ uint32_t movm(uint32_t a) { uint32_t d; asm volatile("movmatrix.sync.aligned.m8n8.trans.b16 %0, %1;" : "=r"(d) : "r"(a)); return d; }
__device__ __forceinline__ uint32_t hadd2(uint32_t a, uint32_t b) { uint32_t d; asm("add.rn.bf16x2 %0, %1, %2;" : "=r"(d) : "r"(a), "r"(b)); return d; }
__device__ __forceinline__ void mma_a(float (&d)[4], const uint32_t (&a)[4], uint32_t b0, uint32_t b1) { mma16816(d, a[0], a[1], a[2], a[3], b0, b1); }
__device__ __forceinline__ bool elect() {
  uint32_t p; asm volatile("{.reg .pred p; elect.sync _|p, 0xffffffff; selp.u32 %0, 1, 0, p;}" : "=r"(p)); return p; }
__device__ __forceinline__ void tma3d(uint32_t dst, const CUtensorMap* m, int c1, int c2, uint32_t bar) {
  asm volatile("cp.async.bulk.tensor.3d.shared::cluster.global.mbarrier::complete_tx::bytes [%0], [%1, {0, %3, %4}], [%2];"
    :: "r"(dst), "l"(m), "r"(bar), "r"(c1), "r"(c2) : "memory"); }
__device__ __forceinline__ void tma4d(uint32_t dst, const CUtensorMap* m, int c1, int c2, uint32_t bar) {
  asm volatile("cp.async.bulk.tensor.4d.shared::cluster.global.mbarrier::complete_tx::bytes [%0], [%1, {0, %3, %4, 0}], [%2];"
    :: "r"(dst), "l"(m), "r"(bar), "r"(c1), "r"(c2) : "memory"); }
template <int OFF, int ACC>
__device__ __forceinline__ void wg_rs32(float (&d)[16], const uint32_t (&a)[4], uint32_t db) {
  if (ACC)
    asm volatile("{.reg .b64 db; .reg .b32 lo; add.u32 lo, %20, %21; mov.b64 db, {lo, 0x40000040};\n"
      "wgmma.mma_async.sync.aligned.m64n32k16.f32.bf16.bf16 {%0,%1,%2,%3,%4,%5,%6,%7,%8,%9,%10,%11,%12,%13,%14,%15}, {%16,%17,%18,%19}, db, 1, 1, 1, 0;}"
      : "+f"(d[0]), "+f"(d[1]), "+f"(d[2]), "+f"(d[3]), "+f"(d[4]), "+f"(d[5]), "+f"(d[6]), "+f"(d[7]), "+f"(d[8]), "+f"(d[9]), "+f"(d[10]), "+f"(d[11]), "+f"(d[12]), "+f"(d[13]), "+f"(d[14]), "+f"(d[15])
      : "r"(a[0]), "r"(a[1]), "r"(a[2]), "r"(a[3]), "r"(db), "n"(OFF));
  else
    asm volatile("{.reg .b64 db; .reg .b32 lo; add.u32 lo, %20, %21; mov.b64 db, {lo, 0x40000040};\n"
      "wgmma.mma_async.sync.aligned.m64n32k16.f32.bf16.bf16 {%0,%1,%2,%3,%4,%5,%6,%7,%8,%9,%10,%11,%12,%13,%14,%15}, {%16,%17,%18,%19}, db, 0, 1, 1, 0;}"
      : "=f"(d[0]), "=f"(d[1]), "=f"(d[2]), "=f"(d[3]), "=f"(d[4]), "=f"(d[5]), "=f"(d[6]), "=f"(d[7]), "=f"(d[8]), "=f"(d[9]), "=f"(d[10]), "=f"(d[11]), "=f"(d[12]), "=f"(d[13]), "=f"(d[14]), "=f"(d[15])
      : "r"(a[0]), "r"(a[1]), "r"(a[2]), "r"(a[3]), "r"(db), "n"(OFF));
}
template <int I> using IC = std::integral_constant<int, I>;
template <int I, int N, class F> __device__ __forceinline__ void sfor(F&& f) {
  if constexpr (I < N) { f(std::integral_constant<int, I>{}); sfor<I + 1, N>(f); }
}
__device__ __forceinline__ void keep(float (&d)[16]) {
  asm volatile("" : "+f"(d[0]), "+f"(d[1]), "+f"(d[2]), "+f"(d[3]), "+f"(d[4]), "+f"(d[5]), "+f"(d[6]), "+f"(d[7]),
      "+f"(d[8]), "+f"(d[9]), "+f"(d[10]), "+f"(d[11]), "+f"(d[12]), "+f"(d[13]), "+f"(d[14]), "+f"(d[15]) :: "memory");
}

template <int N, int S2 = 1024> __device__ __forceinline__ void ldx(uint32_t (&v)[N][4], const uint8_t* p) {
#pragma unroll
  for (int k = 0; k < 2 * N; k++) {
    const int i = k;
    asm volatile("ld.relaxed.gpu.global.v2.b32 {%0,%1}, [%2];" : "=r"(v[i >> 1][2 * (i & 1)]), "=r"(v[i >> 1][2 * (i & 1) + 1]) : "l"(p + (i & 3) * 256 + (i >> 2) * S2) : "memory");
  }
}
__device__ __forceinline__ uint32_t dif2(uint32_t a, uint32_t b, uint32_t tag) { uint32_t r; asm("lop3.b32 %0, %1, %2, %3, 0x7e;" : "=r"(r) : "r"(a), "r"(b), "r"(tag)); return r; }
__device__ __forceinline__ uint32_t dif2v(uint32_t a, uint32_t b, uint32_t tag) { uint32_t r; asm volatile("lop3.b32 %0, %1, %2, %3, 0x7e;" : "=r"(r) : "r"(a), "r"(b), "r"(tag)); return r; }
__device__ __forceinline__ uint32_t or3(uint32_t a, uint32_t b, uint32_t c) { uint32_t r; asm("lop3.b32 %0, %1, %2, %3, 0xfe;" : "=r"(r) : "r"(a), "r"(b), "r"(c)); return r; }
__device__ __forceinline__ uint32_t after(uint32_t x, float f, uint32_t z) { uint32_t r; asm("lop3.b32 %0, %1, %2, %3, 0xea;" : "=r"(r) : "r"(__float_as_uint(f)), "r"(z), "r"(x)); return r; }
__device__ __forceinline__ bool any_bit(uint32_t a, uint32_t b, uint32_t m) {
  uint32_t r; asm("lop3.b32 %0, %1, %2, %3, 0xa8;" : "=r"(r) : "r"(a), "r"(b), "r"(m)); return __any_sync(0xffffffffu, r); }
template <int W, int N> __device__ __forceinline__ bool stale(const uint32_t (&v)[N][4], uint32_t tag) {
  uint32_t x = dif2(v[0][0], v[0][2], tag);
  if (N == 4) x = or3(x, dif2(v[1][0], v[1][2], tag), dif2(v[2 % N][0], v[2 % N][2], tag));
  return any_bit(x, dif2(v[N - 1][0], v[N - 1][2], tag), 1);
}
template <int W, int N, int S2 = 1024> __device__ __forceinline__ void retry(uint32_t (&v)[N][4], const uint8_t* p, uint32_t tag, int& it) {
#pragma unroll 1
  do { ldx<N, S2>(v, p); it += INC_A; } while (stale<W>(v, tag) && it < SPIN_LIMIT);
}
__device__ __forceinline__ void mma_h(float (&d)[4], const uint32_t (&a)[4], const uint32_t (&b)[4], int hf) { mma16816(d, a[0], a[1], a[2], a[3], b[2 * hf], b[2 * hf + 1]); }
__device__ __forceinline__ void sts128(uint32_t a, const uint32_t (&r)[4]) { sts128(a, r[0], r[1], r[2], r[3]); }
__device__ __forceinline__ void sts128f(uint32_t a, const float* r) { sts128(a, __float_as_uint(r[0]), __float_as_uint(r[1]), __float_as_uint(r[2]), __float_as_uint(r[3])); }
__device__ __forceinline__ void mbar_spin(uint32_t bar, uint32_t par, int& it) {
  asm volatile("{.reg .pred p; .reg .b32 par; mov.b32 par, %2;\nLOOP: mbarrier.try_wait.parity.shared::cta.b64 p, [%1], par; @p bra.uni DONE;\n"
               "add.s32 %0, %0, 1; setp.le.s32 p, %0, %3; @p bra.uni LOOP;\nDONE: }" : "+r"(it) : "r"(bar), "r"(par), "n"(SPIN_LIMIT) : "memory"); }
__device__ __forceinline__ void warp_arrive(uint32_t bar) {
  __syncwarp(); asm volatile("{.reg .pred p; elect.sync _|p, 0xffffffff; @p mbarrier.arrive.shared::cta.b64 _, [%0];}" :: "r"(bar) : "memory"); }
__device__ __forceinline__ void delay_until(unsigned t) {
  asm volatile("{.reg .pred p; .reg .b64 c; .reg .b32 lo, hi;\nLOOP: mov.u64 c, %%clock64; mov.b64 {lo, hi}, c; sub.s32 lo, lo, %0; setp.lt.s32 p, lo, 0; @p bra.uni LOOP;}" :: "r"(t) : "memory"); }
__device__ __forceinline__ void cut(int it) { asm volatile("{.reg .pred p; setp.lt.s32 p, %0, 0;\nL: @p st.volatile.shared.u32 [%0], %0; @p bra.uni L;}" :: "r"(it) : "memory"); }
__device__ __forceinline__ void zero(float (&c)[4][4]) {
#pragma unroll
  for (int i = 0; i < 4; i++) c[i][0] = c[i][1] = c[i][2] = c[i][3] = 0.f;
}

__device__ __forceinline__ void sched() { asm volatile("griddepcontrol.launch_dependents;" ::: "memory"); }
__device__ __forceinline__ const uint8_t* pinp(const uint8_t* p) { return reinterpret_cast<const uint8_t*>(__shfl_xor_sync(0xffffffffu, reinterpret_cast<unsigned long long>(p), 0)); }
__device__ __forceinline__ uint32_t bar_or(int id, uint32_t x) {
  uint32_t r; asm volatile("{.reg .pred p, q; setp.ne.u32 p, %2, 0; bar.red.or.pred q, %1, 256, p; selp.u32 %0, 1, 0, q;}" : "=r"(r) : "r"(id), "r"(x) : "memory"); return r; }
__device__ __forceinline__ void bar_sync_unless(int id, uint32_t x) { asm volatile("{.reg .pred p; setp.eq.u32 p, %1, 0; @p bar.sync %0, 256;}" :: "r"(id), "r"((uint32_t)x) : "memory"); }
__device__ __forceinline__ void bar_arrive_unless(int id, uint32_t x) { asm volatile("{.reg .pred p; setp.eq.u32 p, %1, 0; @p bar.arrive %0, 256;}" :: "r"(id), "r"((uint32_t)x) : "memory"); }
__device__ __forceinline__ void stsm2t(uint32_t a, uint32_t r0, uint32_t r1, uint32_t x) {
  asm volatile("{.reg .pred p; setp.eq.u32 p, %3, 0; @p stmatrix.sync.aligned.m8n8.x2.trans.shared.b16 [%0], {%1,%2};}" :: "r"(a), "r"(r0), "r"(r1), "r"((uint32_t)x) : "memory"); }
__device__ __forceinline__ uint32_t or_and(uint32_t a, uint32_t b, uint32_t m) { uint32_t r; asm("lop3.b32 %0, %1, %2, %3, 0xa8;" : "=r"(r) : "r"(a), "r"(b), "r"(m)); return r; }
#define rare(x) __builtin_expect(!!(x), 0)
__device__ __forceinline__ uint32_t gtime() { unsigned long long g; asm volatile("mov.u64 %0, %%globaltimer;" : "=l"(g) :: "memory"); return (uint32_t)g; }
__device__ __forceinline__ void wait_time(uint32_t t) {
  asm volatile("{.reg .pred p; .reg .b32 g; .reg .b64 c;\nLOOP: mov.u64 c, %%globaltimer; cvt.u32.u64 g, c; sub.s32 g, %0, g; setp.lt.u32 p, g, 16384; @p bra.uni LOOP;}" :: "r"(t - 1) : "memory"); }
__device__ __forceinline__ uint32_t ldx32(const void* p) { uint32_t v; asm volatile("ld.relaxed.gpu.global.b32 %0, [%1];" : "=r"(v) : "l"(p) : "memory"); return v; }
__device__ __forceinline__ void stx32(const void* p, uint32_t v) { asm volatile("st.relaxed.gpu.global.b32 [%0], %1;" :: "l"(p), "r"(v) : "memory"); }

__global__ void __launch_bounds__(256, 1)
rec_kernel(const __grid_constant__ RecMaps maps, const bf16* __restrict__ xin, const bf16* __restrict__ mem0, Xchg* const gx,
           const bf16* __restrict__ fx, const bf16* __restrict__ wr, const bf16* __restrict__ wi) {
  extern __shared__ __align__(1024) uint8_t smem_raw[];
  const uint32_t sb = smem_u32(smem_raw);
  int role = blockIdx.x;
  {
    uint32_t smid, nsm; asm volatile("mov.u32 %0, %%smid;" : "=r"(smid)); asm volatile("mov.u32 %0, %%nsmid;" : "=r"(nsm));
    const int p = smid >> 1, u = p - 32;
    if (nsm == gridDim.x)
      role = (smid & 1) + (p < 32 ? 4 * ((p & 7) + 8 * (p >> 4)) + 2 * ((p >> 3) & 1) : p < 60 ? 4 * (16 + u % 7 + 7 * (u / 14)) + 2 * ((u / 7) & 1)
                         : p < 62 ? 2 * p + 8 : 2 * p - 4);
    role = uni(role);
  }
  if (role >= 128) {
    grid_wait(&gx->ctr[33], 128);
    fft_cols(sb, role - 128, 4);
    grid_arrive(&gx->ctr[32]); grid_wait(&gx->ctr[32], 4);
    fft_rows_inv(&maps.fo, sb, role - 128, 4);
    return;
  }
  const int tid = threadIdx.x, warp = uni(tid >> 5), lane = tid & 31, wg = warp >> 2, w4 = warp & 3, g = lane >> 2, t = lane & 3;
  const int h = role >> 2, j = role & 3, jh = j & 1;
  uint32_t w[48][4];
  float aq[16], av[16];
  int it = 0;

#define PT(k)
  auto pf_wo = [&]() {
    for (int i = 0; i < 4; i++)
      asm volatile("cp.async.bulk.prefetch.tensor.2d.L2.global [%0, {%1, %2}];" :: "l"(&maps.wo), "r"(256 * j + 64 * i), "r"(h * DH) : "memory");
  };
  fft_rows_fwd(fx, wr, wi, sb + R_MEM + 49152, role, [&]() {
    if (tid == 224) {
      mbar_init(sb + B_KV, 1); mbar_init(sb + B_W, 1); mbar_init(sb + B_X, 1); mbar_init(sb + B_X + 8, 1); mbar_init(sb + B_X + 16, 1); mbar_init(sb + B_X + 24, 1); mbar_init(sb + B_C, 4); mbar_init(sb + B_PK, 4); mbar_init(sb + B_B, 1);
      asm volatile("fence.mbarrier_init.release.cluster;" ::: "memory");
      mbar_expect_tx(sb + B_W, 3 * 65536);
      for (int i = 0; i < 4; i++) {
        tma2d(sb + R_X + i * 16384, &maps.wq, h * DH + 32 * j, i * 256, sb + B_W);
        if (i < 3) tma2d(sb + R_MEM + i * 16384, &maps.wk, h * DH + 32 * j, i * 256, sb + B_W);
        else asm volatile("cp.async.bulk.prefetch.tensor.2d.L2.global [%0, {%1, %2}];" :: "l"(&maps.wk), "r"(h * DH + 32 * j), "r"(768) : "memory");
      }
      for (int i = 0; i < 2; i++) tma2d(sb + R_WO + i * 32768, &maps.wv, h * DH + 64 * (j >> 1), jh * 512 + i * 256, sb + B_W);
      if (PFD) asm volatile("cp.async.bulk.prefetch.L2.global [%0], 2048;" :: "l"(xin + role * DM) : "memory");
      else for (int i = 0; i < 4; i++) asm volatile("cp.async.bulk.prefetch.L2.global [%0], 8192;" :: "l"(xin + role * 16384 + i * 4096) : "memory");
      if (WOP == 0) pf_wo();
    }
    __syncwarp();
  });
  if (tid < 16) sts32(sb + R_T + tid * 4, ~0u);
  fence_async();
  PT(0);
  grid_arrive(&gx->ctr[33]);
  PT(1);
  if (tid == 224) { tma2d(sb + R_MEM + 49152, &maps.wk, h * DH + 32 * j, 768, sb + B_W); if (WOP == 1) pf_wo(); }
  __syncwarp();
  uint8_t* const xb = reinterpret_cast<uint8_t*>(gx);
  auto probe_at = [&](int n) { return xb + (n ? offsetof(Xchg, C) + w4 * 8192 + role * 32 : offsetof(Xchg, B) + role * 8192 + warp * 128); };
  if (lane < 8) stx128(probe_at(lane >> 2) + (lane & 2) * 2048 + (lane & 1) * 16, 0, 0, 0, 0);
  uint32_t m0[4][4];
#pragma unroll
  for (int i = 0; i < 16; i++) m0[i >> 2][i & 3] = ldnc32(mem0 + g * DM + 128 * warp + 8 * i + 2 * t);
  mbar_spin(sb + B_W, 0, it);
  PT(2);
  const int lrow = (lane & 7) + ((lane >> 4) << 3), lhi = (lane >> 3) & 1;
  const int kq = wg ? 3 - 3 * jh : 3 * jh;
  const uint32_t LW = lrow * 128 + ((lhi ^ (lane & 7)) << 4);
  {
    const int chunk = w4 < 2 ? w4 + 2 * lhi : 2 * (w4 & 1) + lhi;
    uint32_t a = sb + (w4 < 2 ? R_X : R_MEM) + kq * 16384 + lrow * 64 + ((chunk ^ ((lrow >> 1) & 3)) << 4);
#pragma unroll
    for (int i = 0; i < 16; i++) ldsm4t(w[i], a + i * 1024);
    const uint32_t st = wg ? 1024 : 2048, av0 = sb + R_WO + (LW ^ (w4 << 5));
    const uint32_t a1 = wg ? a + (2 * jh - 1) * 16384 : av0 + jh * 32768, a2 = wg ? a + (2 * jh - 1) * 32768 : av0 + (1 - jh) * 32768;
#pragma unroll
    for (int i = 0; i < 16; i++) { ldsm4t(w[16 + i], a1 + i * st); ldsm4t(w[32 + i], a2 + i * st); }
  }
  uint32_t L16 = pin(lane * 16);
  const uint32_t uW = uni(sb + w4 * 512), uWo = uni(sb + R_WO + w4 * 16384), uMem = uni(sb + R_MEM + kq * 4096);
  const uint32_t dX = uni(((sb + R_X + kq * 16384) >> 4) | 0x10000u);
  auto load_wo = [&](uint32_t (&d)[32][4], int i0, int i1) {
#pragma unroll
    for (int i = i0; i < i1; i++) lds128(d[i], uWo + L16 + (i & 1) * 512 + (i >> 4) * 1024 + (i & 14) * 1024);
  };
  auto issue_x = [&](int n, int k) {
    const uint32_t bar = sb + B_X + 8 * k, q = k ^ (3 - 3 * jh);
    mbar_expect_tx(bar, 16384); tma3d(sb + R_X + q * 16384, &maps.x, n * SEG, 4 * q, bar);
  };
  auto store_stage = [&](int n) {
    asm volatile("cp.async.bulk.global.shared::cta.bulk_group [%0], [%1], 8192; cp.async.bulk.commit_group;"
                 :: "l"(g_kqv[n & 3][role]), "r"(sb + R_STAGE) : "memory");
  };
  auto issue_kqv = [&](int n) {
    const int p = (n & 3) * 128 + 4 * h;
    mbar_expect_tx(sb + B_KV, 26624);
    tma3d(sb + R_K, &maps.k, 0, p, sb + B_KV); tma3d(sb + R_Q, &maps.q, 8 + 2 * j, p, sb + B_KV); tma3d(sb + R_V, &maps.v, 16, p, sb + B_KV);
  };
  auto fetch4k = [&](uint32_t dst, uint32_t off, uint32_t bar, uint32_t t) {
    asm volatile("{.reg .pred p, q; .reg .b32 g; .reg .b64 c; elect.sync _|q, 0xffffffff; @q mbarrier.arrive.expect_tx.shared::cta.b64 _, [%2], 4096;\n"
                 "LOOP: mov.u64 c, %%globaltimer; cvt.u32.u64 g, c; sub.s32 g, %3, g; setp.lt.u32 p, g, 16384; @p bra.uni LOOP;\n"
                 "@q cp.async.bulk.shared::cluster.global.mbarrier::complete_tx::bytes [%0], [%1], 4096, [%2];}" :: "r"(dst), "l"(xb + off), "r"(bar), "r"(t - 1) : "memory");
  };
  uint32_t uS;
  auto my_b = [&]() { return offsetof(Xchg, B) + role * 8192 + ((uS + ((uint32_t)it >> 31)) & 1) * 4096; };
  auto issue_c = [&](uint32_t t) { fetch4k(sb + R_MEM + w4 * 4096, offsetof(Xchg, C) + w4 * 8192 + ((uS + ((uint32_t)it >> 31)) & 4096), sb + B_C, t); };
  auto wait_x = [&](int n, int i) { if (!(EXP & 1) || n < 2) mbar_spin(sb + B_X + 8 * i, n & 1, it); };
#define PACED(d0) uint32_t dz = d0; const uint32_t z = (uint32_t)it >> 31; auto pace = [&]() { for (int k = 0; k < PACE; k++) { if (k & 1) asm("add.u32 %0, %0, %1;" : "+r"(dz) : "r"(z)); else asm("xor.b32 %0, %0, %1;" : "+r"(dz) : "r"(z)); } };
  auto project_v = [&](auto I0, auto I1, auto&& mid) {
    PACED(decltype(I0)::value < 16 ? dX : dX ^ 1024);
    wg_fence();
    sfor<decltype(I0)::value, decltype(I1)::value>([&](auto I) {
      constexpr int i = decltype(I)::value;
      mid(i);
      if (i == 16 && decltype(I0)::value < 16) dz ^= 1024;
      wg_rs32<((i >> 2) & 3) * 256 + (i & 3) * 2, (i > 0)>(av, w[16 + i], dz);
      pace();
    });
    wg_commit();
  };
  auto project_qk = [&](auto I0, auto I1, auto first, auto&& mid) {
    PACED((dX ^ (decltype(I0)::value >> 4 << 10)) + ((uint32_t)it >> 31));
    wg_fence();
    sfor<decltype(I0)::value, decltype(I1)::value>([&](auto I) {
      constexpr int i = decltype(I)::value;
      mid(i);
      wg_rs32<((i >> 2) & 3) * 256 + (i & 3) * 2, !decltype(first)::value || i != decltype(I0)::value>(aq, w[i], dz);
      pace();
    });
    wg_commit();
  };
  const uint32_t uP = uni(sb + R_X + 3 * jh * 16384 + w4 * 512);
  auto park = [&]() {
    bar_sync(1, 128);
#pragma unroll
    for (int i = 0; i < 4; i++) sts128f(uP + L16 + i * 2048, aq + 4 * i);
    warp_arrive(sb + B_PK);
  };
  auto unpark = [&]() {
#pragma unroll
    for (int i = 0; i < 4; i++) {
      const float4 p = lds128f(uP + L16 + i * 2048);
      av[4 * i] = p.x; av[4 * i + 1] = p.y; av[4 * i + 2] = p.z; av[4 * i + 3] = p.w;
    }
  };
  auto fin_qk = [&]() {
#pragma unroll
    for (int i = 0; i < 16; i++) aq[i] += av[i];
    const uint32_t a = sb + R_STAGE + (w4 < 2 ? 2048 + w4 * 128 : (w4 & 1) * 256) + (L16 & 112) + (L16 >> 7) * 512;
    stsm4t(a, pack2(aq[0], aq[1]), pack2(aq[4], aq[5]), pack2(aq[8], aq[9]), pack2(aq[12], aq[13]));
    stsm4t(a + (w4 < 2 ? 256 : 128), pack2(aq[2], aq[3]), pack2(aq[6], aq[7]), pack2(aq[10], aq[11]), pack2(aq[14], aq[15]));
  };
  auto fin_v = [&]() {
#pragma unroll
    for (int a = 0; a < 2; a++)
      sts128(sb + R_STAGE + 4096 + w4 * 1024 + a * 512 + L16, pack2(av[8 * a], av[8 * a + 1]), pack2(av[8 * a + 2], av[8 * a + 3]),
             pack2(av[8 * a + 4], av[8 * a + 5]), pack2(av[8 * a + 6], av[8 * a + 7]));
  };
  __syncthreads();
  if (tid == 224) {
#pragma unroll 1
    for (int i = 0; i < 4; i++) issue_x(0, i);
    mbar_expect_tx(sb + B_W, 65536);
    for (int i = 0; i < 4; i++) tma2d(sb + R_WO + i * 16384, &maps.wo, 256 * j + 64 * i, h * DH, sb + B_W);
  }
  __syncwarp();
  if (wg) {
#pragma unroll
    for (int i = 0; i < NSW; i++) sts128(uW + R_WC + L16 + i * 2048, w[i]);
  }
#pragma unroll
  for (int i = 0; i < 4; i++) sts128(sb + R_MEM + warp * 2048 + i * 512 + (g >> 1) * 128 + t * 32 + (g & 1) * 16, m0[i]);
  auto probe = [&](int n, int cnt) {
    if (lane == 0) {
#pragma unroll 1
      for (int i = role >> 7; i < cnt; i++) {
        const int k = (i ^ wg) & 1;
        const unsigned t0 = clk();
        uint32_t v; asm volatile("atom.relaxed.gpu.global.exch.b32 %0, [%1], 0;" : "=r"(v) : "l"(probe_at(n) + k * 4096) : "memory");
        if (v == 0) asm volatile("red.shared.min.u32 [%0], %1;" :: "r"(sb + R_T + (n ? w4 * 8 : 32) + k * 4), "r"(clk() - t0) : "memory");
      }
    }
    __syncwarp();
  };
#pragma unroll 1
  for (int n = 0; n < 2; n++) {
    probe(0, n ? NPB : NPB0);
    PT(3 + 3 * n);
    wait_x(n, 2);
    PT(4 + 3 * n);
    if (wg == 0) {
      wait_x(n, 3);
      project_qk(IC<0>{}, IC<16>{}, IC<1>{}, [](int) {});
      project_v(IC<0>{}, IC<32>{}, [](int) {});
      if (tid == 96 && n == 1) {
        asm volatile("cp.async.bulk.wait_group 0;" ::: "memory");
        __threadfence(); atomicAdd(&gx->ctr[h], 1u);
      }
      __syncwarp();
      wg_wait<0>(); keep(aq); keep(av);
      park();
      fin_v();
      fence_async();
    } else {
      wait_x(n, 0); wait_x(n, 1);
      project_qk(IC<32>{}, IC<48>{}, IC<1>{}, [](int) {});
      project_qk(IC<16>{}, IC<32>{}, IC<0>{}, [](int) {});
      project_qk(IC<0>{}, IC<16>{}, IC<0>{}, [](int) {});
      mbar_spin(sb + B_PK, n, it);
      unpark();
      wg_wait<0>(); keep(aq);
      fin_qk();
      fence_async();
    }
    __syncthreads();
    if (tid == 0 && n) stx32(&gx->S[role], 1 + (HOME & 2 && lds32(sb + R_T + 36) < lds32(sb + R_T + 32)));
    PT(5 + 3 * n);
    if (tid == 96 && n == 0) store_stage(0);
    if (tid == 128 && n == 0) {
#pragma unroll 1
      for (int i = 0; i < 4; i++) issue_x(1, i);
    }
    if (warp == 5 && n == 1) {
#pragma unroll 1
      while (__any_sync(0xffffffffu, ldx32(&gx->ctr[h]) < 4) && ++it < SPIN_LIMIT) {}
      __threadfence(); asm volatile("fence.proxy.async;" ::: "memory");
      if (elect()) issue_kqv(0);
    }
    __syncwarp();
  }
  mbar_spin(sb + B_W, 1, it);
  PT(9);
#pragma unroll
  for (int i = 0; i < 4; i++) {
    uint32_t f[4][4];
    const uint32_t a = sb + R_WO + warp * 8192 + i * 2048;
#pragma unroll
    for (int q = 0; q < 4; q++) ldsm4t(f[q], a + (LW ^ (q << 5)));
    __syncwarp();
#pragma unroll
    for (int q = 0; q < 4; q++) sts128(a + q * 512 + L16, f[q]);
  }
  if (NPC) probe(1, NPC);
  {
    const int o = 32 * w4 + 16 * wg + 4 * t + j;
    uint32_t v;
#pragma unroll 1
    while (__any_sync(0xffffffffu, (v = ldx32(&gx->S[o])) == 0) && ++it < SPIN_LIMIT) {}
    asm volatile("st.shared.u64 [%0], %1;" :: "r"(sb + R_DST + wg * 1024 + w4 * 256 + lane * 8), "l"(xb + offsetof(Xchg, B) + o * 8192 + (v >> 1) * 4096 + h * 128 + ((g ^ h) & 7) * 16) : "memory");
  }
  if (wg == 0) {
    const uint64_t cd = reinterpret_cast<uint64_t>(xb + (offsetof(Xchg, C) + j * 8192 + h * 128 + w4 * 32 + (L16 & 16) * 256 + (L16 & 64) / 4 + (L16 >> 7) * 4));
    sts128(uW + R_RD + L16, (uint32_t)cd, (uint32_t)(cd >> 32), sb + R_MEM + (L16 & 112) * 8 + (L16 >> 8) * 1024 + ((w4 * 32 + ((L16 >> 3) & 16)) ^ (L16 & 112)),
           (L16 >> 6) == (h & 3) * 2 + ((h >> 2) & 1) ? 0xFFFE0000u : 0xFFFFFFFFu);
  }
  if (tid == 0) sts32(sb + B_DUE + 8, gtime() & ~31u);
  PT(10);
  mbar_spin(sb + B_KV, 0, it);
  PT(11);
  if (tid < 4) sts32(sb + B_ONE + tid * 4, 0x3F803F80u);
  if (warp == 1) { const uint32_t e = g >> 1 == t ? 0x3F80u << (16 * (g & 1)) : 0u; sts128(sb + R_ID + L16, e, 0, 0, e); }
  __syncthreads();
  {
    const uint32_t kb = lds32(sb + R_T + 36) < lds32(sb + R_T + 32);
    uS = uni((HOME & 4 ? (__popc(((offsetof(Xchg, B) / 4096 + 2 * role) ^ (offsetof(Xchg, C) / 4096 + 2 * w4)) & 0xb3) ^ kb) & 1 : lds32(sb + R_T + w4 * 8 + 4) < lds32(sb + R_T + w4 * 8)) * 4096 + kb);
  }

  const float sc = 0.08838834764831845f * 1.4426950408889634f;
  uint8_t* const xa = xb + uni(h * 16384);
  const uint32_t uA = uni(wg ? (w4 >> 1) * 2048 + j * 512 + (w4 & 1) * 256 : 8192 + (4 * (j >> 1) + w4) * 512 + jh * 256);
  const uint32_t uP2 = uni(sb + R_P + w4 * 256);
  uint32_t nc = 1;
  uint32_t ma;
  const uint8_t* adst;
  auto pin_mem = [&]() { adst = pinp(xa + uA + L16 / 2); ma = pin(uMem + (L16 & 384) + (L16 & 48) * 2 + (L16 & 64) / 4); };
  pin_mem();

#pragma unroll 1
  for (int s = 0;; nc++) {
    const uint32_t tag = (s + 1) & 1;
    auto fresh = [&]() { L16 += (uint32_t)it >> 31; };
    auto get_due = [&]() { return lds32(sb + B_DUE + 4 + tag * 4); };
    float c[4][4], r4[4];
    auto fold = [&]() {
#pragma unroll
      for (int i = 0; i < 4; i++) r4[i] = ((c[0][i] + c[1][i]) + c[2][i]) + c[3][i];
    };
    auto mma4 = [&](int n, const uint32_t (&b0)[4], const uint32_t (&b1)[4]) {
      mma_h(c[0], w[n + 2], b1, 0); mma_h(c[1], w[n + 3], b1, 1); mma_h(c[2], w[n], b0, 0); mma_h(c[3], w[n + 1], b0, 1);
    };
    auto xpos = [&](int pos, int wp) {
      if ((pos == X0 || pos == X1 || pos == X2 || pos == X3) && warp == wp && s + 1 < NSEG && elect()) {
        const int z = (uint32_t)it >> 31;
        if (pos == X2) issue_x(s + 2, 2 + z);
        if (pos == X3) issue_x(s + 2, 3 + z);
        if (pos == X1) issue_x(s + 2, 1 + z);
        if (pos == X0) issue_x(s + 2, z);
      }
      __syncwarp();
    };
    if (wg == 0) {
      mbar_spin(sb + B_C, nc & 1, it);
      TS(13);
      uint32_t b[16][4], tg[4];
#pragma unroll
      for (int i = 0; i < PD0; i++) { lds128(b[i], ma + i * 512); __syncwarp(); }
      sched();
      zero(c);
#pragma unroll
      for (int i = 0; i < 8; i++) {
        const int k = i ^ 1;
        mma_h(c[0], w[2 * k], b[k], 0); mma_h(c[1], w[2 * k + 1], b[k], 1);
        if (i < 2 * NV0) { mma_h(c[2], w[16 + 2 * k], b[k], 0); mma_h(c[3], w[17 + 2 * k], b[k], 1); }
        sched();
        if ((i & 1) && i + PD0 < 9) { lds128(b[i + PD0 - 1], ma + (i + PD0 - 1) * 512); __syncwarp(); lds128(b[i + PD0], ma + (i + PD0) * 512); sched(); }
        if (i == TGP) {
          fresh();
#pragma unroll
          for (int k = 0; k < 4; k++) tg[k] = lds32((uW * 4 + L16) * 2 + (L16 >> 6) * 4 + (R_MEM + k * 1024 - 7 * sb));
          sched();
        }
      }
#pragma unroll
      for (int i = 0; i < 4; i++) { r4[i] = c[0][i] + c[1][i]; c[0][i] = c[1][i] = 0.f; }
      sts128f(uW + R_RED + L16, r4);
      TS(1);
      const uint32_t old = bar_or(4, (dif2(tg[0], tg[1], s) | dif2(tg[2], tg[3], s)) & (s > 0));
      TS(0);
#pragma unroll
      for (int i = 0; i < 2 * NV0; i++) { lds128(b[8 + i], (ma ^ 4096) + i * 512); __syncwarp(); }
      sched();
#pragma unroll
      for (int i = NV0; i < 8; i++) {
        if (VB && i == VB) bar_sync(7, 256);
        mma4(16 + 4 * i, b[2 * i], b[2 * i + 1]);
        if (i < 7) sched();
        if (i < 4) { lds128(b[8 + 2 * i], (ma ^ 4096) + i * 1024); __syncwarp(); lds128(b[9 + 2 * i], (ma ^ 4096) + i * 1024 + 512); sched(); }
      }
      fold();
      asm volatile("{.reg .pred p; setp.eq.u32 p, %3, 0; @p st.relaxed.gpu.global.v2.b32 [%0], {%1,%2};}" :: "l"(adst), "r"((pack2(r4[0], r4[1]) & ~1u) | tag), "r"(pack2(r4[2], r4[3])), "r"(old) : "memory");
      sched();
      const unsigned tpub = clk();
      if (__any_sync(0xffffffffu, old) && nc < NC_MAX) {
        bar_sync(3, 256);
        issue_c(gtime());
        continue;
      }
      TS(3);
      xpos(0, 0);
      const uint32_t due = get_due();
      uint32_t vf[4][4], vm[2][4], p[4], pm, o[4];
      const uint32_t va = sb + R_V + (w4 >> 1) * 8192 + (w4 & 1) * 2048 + L16;
#pragma unroll
      for (int i = 0; i < 4; i++) {
        uint32_t q[4]; lds128(vf[i], va + i * 512); lds128(q, va + 4096 + i * 512);
#pragma unroll
        for (int e = 0; e < 4; e++) vf[i][e] = hadd2(vf[i][e], q[e]);
      }
      const uint32_t pa = pin(sb + R_P + (L16 >> 1));
      const uint8_t* vsrc = pinp(xa + 8192 + w4 * 1024 + L16 / 2);
      uint32_t one[4];
      lds128(one, sb + B_ONE);
      auto pv_x = [&]() {
        zero(c);
        mma_a(c[2], one, p[0], p[1]);
        mma_a(c[0], vf[0], p[0], p[1]); mma_a(c[1], vf[2], p[0], p[1]);
        sched();
        mma_a(c[2], one, p[2], p[3]);
        mma_a(c[0], vf[1], p[2], p[3]); mma_a(c[1], vf[3], p[2], p[3]);
        sched();
      };
      auto pv_m = [&]() {
        mma1688(c[2], one[0], one[1], pm);
        mma_a(c[0], vm[0], pm, pm);
        sched();
        mma_a(c[1], vm[1], pm, pm);
      };
      auto norm = [&]() {
        const float n0 = rcp(c[2][0]), n1 = rcp(c[2][1]);
#pragma unroll
        for (int i = 0; i < 4; i++) o[i] = pack2(c[i >> 1][2 * (i & 1)] * n0, c[i >> 1][2 * (i & 1) + 1] * n1);
        return ((__float_as_uint(c[2][0]) - 0x1F800000u) | (__float_as_uint(c[2][1]) - 0x1F800000u)) >> 30;
      };
      auto load_m = [&](int x) { const float2 e0 = lds64f(pa + 512 + x * 1024), e1 = lds64f(pa + 768 + x * 1024); pm = pack2(e0.x * e1.x, e0.y * e1.y); };
      auto attend_max = [&](int x) {
        float2 sv[6];
#pragma unroll
        for (int i = 0; i < 6; i++) sv[i] = lds64f(pa - 3072 + x * 1536 + i * 256);
        sv[4].x += sv[5].x; sv[4].y += sv[5].y;
        const int dq = (int)(L16 >> 6) - (int)((L16 >> 3) & 6) + 8 * j;
        float m = fmaxf(sv[4].x, sv[4].y);
#pragma unroll
        for (int i = 0; i < 4; i++) {
          if (x && 8 * i > dq) sv[i].x = -INFINITY;
          if (x && 8 * i + 1 > dq) sv[i].y = -INFINITY;
          m = fmaxf(m, fmaxf(sv[i].x, sv[i].y));
        }
        m = fmaxf(m, __shfl_xor_sync(0xffffffffu, m, 1));
        m = fmaxf(m, __shfl_xor_sync(0xffffffffu, m, 2));
#pragma unroll
        for (int i = 0; i < 5; i++) (i < 4 ? p[i] : pm) = pack2(ex2(sv[i].x - m), ex2(sv[i].y - m));
        pv_x(); pv_m(); norm();
      };
      uint32_t tq[4];
      auto get_t = [&]() {
        tq[0] = tq[1] = tq[2] = tq[3] = 0;
        asm volatile("{.reg .pred p; setp.eq.u32 p, %5, 0; @p ld.relaxed.gpu.global.v4.b32 {%0,%1,%2,%3}, [%4];}"
                     : "+r"(tq[0]), "+r"(tq[1]), "+r"(tq[2]), "+r"(tq[3]) : "l"(xb + offsetof(Xchg, T) + L16 * 8), "r"(warp) : "memory");
      };
      delay_until(tpub + DLY_V);
      wait_time(due + NS_V);
      TS(4);
      ldx(vm, vsrc);
      sched();
      xpos(2, 2);
      auto store_kqv = [&]() {
        fence_async();
        if (!(EXP & 4))
          asm volatile("{.reg .pred p; elect.sync _|p, 0xffffffff; @p cp.async.bulk.global.shared::cta.bulk_group [%0], [%1], 2048; cp.async.bulk.commit_group;}"
                       :: "l"(g_kqv[(s + 1) & 3][role] + w4 * 128), "r"(sb + R_STAGE + w4 * 2048) : "memory");
      };
      if (SPOS == 2) store_kqv();
      sched();
      bar_sync(5, 256);
      ldsm4(p, sb + R_P + L16);
      load_m(0);
      pv_x();
      ldsm4(p, sb + R_P + 1024 + L16);
      pv_m();
      const uint32_t r = norm(), tl = after(tag, c[2][0], (uint32_t)it >> 31);
      const bool redo = __any_sync(0xffffffffu, r | ((dif2(vm[0][0], vm[0][2], tl) | dif2(vm[1][0], vm[1][2], tl)) & 1));
      TS(6);
      stsm4t(uW + R_O + L16, o[0], o[1], o[2], o[3]);
      bar_arrive_unless(6, redo);
      sched();
      if (TQL == 7) get_t();
      TS(7);
      pv_x();
      if (rare(redo)) retry<2>(vm, vsrc, tag, it);
      bar_sync(8, 256);
      load_m(1);
      pv_m();
      if (rare(__any_sync(0xffffffffu, norm()) || redo)) {
        fresh();
#pragma unroll 1
        for (int x = !redo; x < 2; x++) {
          attend_max(x);
          if (x == 0) { stsm4t(uW + R_O + L16, o[0], o[1], o[2], o[3]); bar_arrive(6, 256); }
        }
      }
      TS(8);
      if (TQL == 8) get_t();
      const bool xok = mbar_test(sb + B_X + 16, s & 1) & mbar_test(sb + B_X + 24, s & 1);
      xpos(4, 2);
      fresh();
      const uint32_t ob = uni(sb + R_MEM + 4096 + w4 * 1024);
      stsm4t(ob + (L16 & 112) * 4 + (((L16 >> 3) ^ (L16 >> 1)) & 48), o[0], o[1], o[2], o[3]);
      __syncwarp();
      uint32_t rd[4];
      lds128(rd, uW + R_RD + L16);
      lds128(o, ob + (L16 ^ ((L16 >> 3) & 48)));
      auto put_o = [&]() {
        *reinterpret_cast<uint4*>(reinterpret_cast<uint8_t*>(g_ox) + (((s * SEG + 8 * j) * HD + h * DH + 32 * w4) * 2 + (L16 >> 6) * (HD * 2) + (L16 & 48))) = make_uint4(o[0], o[1], o[2], o[3]);
      };
      if (s + 1 == NSEG) { put_o(); asm volatile("cp.async.bulk.wait_group 0;" ::: "memory"); break; }
      asm volatile("cp.async.bulk.wait_group 0;" ::: "memory");
      if (elect()) stx32(xa + 4096 + j * 16 + w4 * 4, s + 1);
      __syncwarp();
      if (rare(!xok)) { wait_x(s + 2, 3); wait_x(s + 2, 2); }
      TS(9);
      fresh();
      const uint32_t e = due | ((s + 1) & 31);
      project_qk(IC<0>{}, IC<NQ>{}, IC<1>{}, [&](int n) {
        if (n == OXPOS) { __syncwarp(); put_o(); __syncwarp(); }
        if (n == TQP) { __syncwarp(); tq[0] = dif2v(tq[0], tq[1], e) | dif2v(tq[2], tq[3], e); __syncwarp(); }
      });
      if (NPA) project_v(IC<0>{}, IC<NPA>{}, [](int) {});
      TS(2);
      if (warp == 0) {
        uint32_t last = due, nx = NS_P;
        if (rare(__any_sync(0xffffffffu, tq[0]))) {
          const uint32_t ref = gtime();
#pragma unroll 1
          do ldx128(o, xb + offsetof(Xchg, T) + L16 * 8); while (any_bit(or3(o[0] - s - 1, o[1] - s - 1, o[2] - s - 1), o[3] - s - 1, 30) && ++it < SPIN_LIMIT);
          const int d = max(max((int)(o[0] - ref), (int)(o[1] - ref)), max((int)(o[2] - ref), (int)(o[3] - ref)));
          last = (ref + __reduce_max_sync(0xffffffffu, d)) & ~31u;
          if (last != due) nx += NS_X;
        }
        const uint32_t bdue = last + NS_B;
        if (s == 0) { last += NS_Y; nx += NS_Z; }
        sts32(sb + B_DUE, last);
        sts32(sb + B_DUE + 8 - tag * 4, last + nx);
        fetch4k(sb + R_MEM, my_b(), sb + B_B, bdue);
        LOG(13, tl - last);
        LOG(9, last);
      }
      if (NQ < 16) project_qk(IC<NQ>{}, IC<16>{}, IC<0>{}, [](int) {});
      project_v(IC<NPA>{}, IC<NPRE>{}, [](int) {});
      const uint32_t ba = rd[2], msk = rd[3];
      const uint8_t* cdst = reinterpret_cast<const uint8_t*>(rd[0] | (uint64_t)rd[1] << 32);
      TS(14);
      mbar_spin(sb + B_B, s & 1, it);
      TS(10);
      uint32_t bq[2][4];
      auto sum_b = [&]() {
        ldsm4t(bq[0], ba); ldsm4t(bq[1], ba + 2048);
        sched();
#pragma unroll
        for (int i = 0; i < 8; i++) c[i >> 2][i & 3] = 0.f;
        mma_a(c[0], bq[0], 0x3F803F80u, 0x3F803F80u); mma_a(c[1], bq[1], 0x3F803F80u, 0x3F803F80u);
        const uint32_t t2 = tag * 0x10001u;
        const bool old = any_bit(or3(dif2(bq[0][0], bq[0][1], t2), dif2(bq[0][2], bq[0][3], t2), dif2(bq[1][0], bq[1][1], t2)), dif2(bq[1][2], bq[1][3], t2), L16 < 64 ? 0x10001u : 0u);
        const uint32_t T = (tag << 16) & ~msk, u = ((__float_as_uint(c[0][0] + c[1][0]) + ((0x10000u & ~msk) - T)) & msk) | T;
        asm volatile("{.reg .pred p; setp.eq.u32 p, %2, 0; @p st.relaxed.gpu.global.b32 [%0], %1;}"
                     :: "l"(cdst), "r"(pack2(__uint_as_float(u), c[0][2] + c[1][2])), "r"((uint32_t)(old || (L16 & 32))) : "memory");
        return old;
      };
      if (rare(sum_b())) {
#pragma unroll 1
        do {
          const uint8_t* p = xb + (my_b() + (ba - sb - R_MEM));
          ldx128(bq[0], p); ldx128(bq[1], p + 2048);
          sts128(ba, bq[0]); sts128(ba + 2048, bq[1]);
          __syncwarp();
          it += INC_B;
        } while (sum_b() && it < SPIN_LIMIT);
      }
      sched();
      TS(11);
      bar_arrive(0, 256);
      const unsigned tc = clk();
      const uint32_t cdue = lds32(sb + B_DUE) + NS_C;
      if (warp == 3) LOG(11, gtime() - cdue);
      fresh();
      wg_wait<0>(); keep(aq); keep(av);
      park();
      if (NPRE < 32) project_v(IC<NPRE>{}, IC<32>{}, [](int) {}); else fin_v();
      TS(12);
      delay_until(tc + DLY_C);
      issue_c(cdue);
      TS(5);
      LOG(warp, it);
      pin_mem();
      if (NPRE < 32) { wg_wait<0>(); keep(av); fin_v(); }
      if (!(EXP & 2)) mbar_spin(sb + B_KV, tag, it);
      TS(15);
    } else {
      uint32_t kf[8][4];
      auto load_k = [&]() {
        const uint32_t ka = sb + R_K + w4 * 1024 + (L16 & 112) + (L16 & 128) * 4 + (L16 & 256);
#pragma unroll
        for (int i = 0; i < 8; i++) ldsm4(kf[i], ka + (i >> 1) * 2048 + (i & 1) * 128);
      };
      auto put_p = [&](int x, uint32_t old, uint32_t again) {
        float e[4];
        const int dq = (int)((L16 >> 3) & 6) + 8 * j - (int)(L16 >> 6) - 16 * w4;
#pragma unroll
        for (int i = 0; i < 4; i++) { r4[i] = fmaf(c[3][i], sc, fmaf(c[2][i], sc, fmaf(c[0][i] + c[1][i], sc, __uint_as_float(i == 3 ? 0u - old : 0u)))); e[i] = x && dq + (i & 1) < 8 * (i >> 1) ? 0.f : ex2(r4[i]); }
        stsm2t(uP2 + x * 1024 + L16, pack2(e[0], e[1]), pack2(e[2], e[3]), again);
      };
      auto put_s = [&](int x) {
#pragma unroll
        for (int i = 0; i < 4; i++) sts32f(uW + R_S + x * 1536 + (L16 & 48) * 4 + (L16 >> 6) * 4 + (i & 1) * 32 + (i >> 1) * 256, r4[i]);
      };
      auto load_q = [&](uint32_t (&q)[4], uint32_t off) { ldsm4(q, sb + R_Q + (L16 & 112) + (L16 & 128) * 2 + (L16 >> 8) * 128 + off); };
      mbar_spin(sb + B_C, nc & 1, it);
      TS(13);
      float4 o4;
      uint32_t id[4], old;
      {
        uint32_t b[24][4];
#pragma unroll
        for (int i = 0; i < 2 * PD1; i++) { lds128(b[i], ma + i * 512); __syncwarp(); }
        sched();
        zero(c);
#pragma unroll
        for (int i = 0; i < 12; i++) {
          mma4(4 * i, b[2 * i], b[2 * i + 1]);
          if (i < 11) sched();
          if (i + PD1 < 12) { const int k = i + PD1; const uint32_t a = (ma ^ (k >> 2 << 12)) + (k & 3) * 1024; lds128(b[2 * k], a); __syncwarp(); lds128(b[2 * k + 1], a + 512); sched(); }
          if (i == RJ) { lds128(id, sb + R_ID + L16); sched(); }
          if (i == RI) { old = bar_or(4, 0); o4 = lds128f(uW + R_RED + L16); sched(); }
        }
      }
      TS(0);
      {
        float e[4] = {o4.x, o4.y, o4.z, o4.w};
#pragma unroll
        for (int i = 0; i < 4; i++) { r4[i] = (((e[i] + c[0][i]) + c[1][i]) + c[2][i]) + c[3][i]; e[i] = 0.f; }
        mma_a(e, id, pack2(r4[0], r4[1]), pack2(r4[2], r4[3]));
        sched();
        if (VB) bar_arrive(7, 256);
        sched();
        asm volatile("{.reg .pred p; setp.eq.u32 p, %3, 0; @p st.relaxed.gpu.global.v2.b32 [%0], {%1,%2};}" :: "l"(adst),
                     "r"((__byte_perm(__float_as_uint(e[0]), __float_as_uint(e[1]), 0x7632) & ~1u) | tag), "r"(__byte_perm(__float_as_uint(e[2]), __float_as_uint(e[3]), 0x7632)), "r"(old) : "memory");
        sched();
      }
      const unsigned tpub = clk(), now = gtime(), due = get_due();
      if (__any_sync(0xffffffffu, old) && nc < NC_MAX) { bar_sync(3, 256); continue; }
      TS(2);
      const uint8_t* asrc = pinp(adst + ((warp == 7) * 1024 - (int)uA));
      fresh();
      uint32_t wo[32][4];
      bool xok;
      auto reload = [&]() {
        sched();
#pragma unroll
        for (int i = RE0 + RE1; i < NSW; i++) lds128(w[i], uW + R_WC + L16 + i * 2048);
        sched();
      };
      auto out_proj = [&]() {
        uint32_t b[4][4];
        float d[4][4];
        uint8_t* dst[2];
        const uint32_t da = pin(uP2 + (R_DST - R_P) + L16 / 2);
        sched();
        TS(7);
        bar_sync(6, 256);
#pragma unroll
        for (int i = 0; i < 4; i++) { ldsm4(b[i], sb + R_O + i * 512 + L16); __syncwarp(); }
        sched();
        auto put_b = [&](uint8_t* a, const float (&e)[4][4]) {
          stx128(a, (pack2(e[0][0] + e[2][0], e[0][1] + e[2][1]) & ~1u) | tag, pack2(e[0][2] + e[2][2], e[0][3] + e[2][3]),
                 pack2(e[1][0] + e[3][0], e[1][1] + e[3][1]), pack2(e[1][2] + e[3][2], e[1][3] + e[3][3]));
        };
        zero(c); zero(d);
#pragma unroll
        for (int i = 0; i < 32; i++) {
          mma_h(i < 16 ? c[i & 3] : d[i & 3], wo[i], b[(i >> 2) & 3], (i >> 1) & 1);
          if (i >= LW0 && NB1 + i - LW0 < 32) { load_wo(wo, (NB1 + i - LW0) ^ 1, ((NB1 + i - LW0) ^ 1) + 1); __syncwarp(); }
          if (i == DL0 || i == DL1) asm volatile("ld.shared.u64 %0, [%1];" : "=l"(dst[i > DL0]) : "r"(da + (i > DL0) * 1024) : "memory");
          if (i >= 16 && i < 16 + RE0) { lds128(w[i - 16], uW + R_WC + L16 + (i - 16) * 2048); __syncwarp(); }
          if (i >= RP1 && i < RP1 + RE1) { lds128(w[i - RP1 + RE0], uW + R_WC + L16 + (i - RP1 + RE0) * 2048); __syncwarp(); }
          if (i == 22) put_b(dst[0], c);
          if ((i & 1) && (i < 20 || i > 22)) sched();
        }
        put_b(dst[1], d);
        sched();
        TS(6);
      };
      if (warp < 6) {
        delay_until(tpub + DLY_A);
        const int it0 = it;
        bool redo;
#pragma unroll 1
        do {
          uint32_t q[4][4], y[4];
          float d[4][4];
          wait_time(due);
          TS(4);
          ldx(q, asrc);
          sched();
          load_k();
          uint32_t qx[4][4];
#pragma unroll
          for (int i = 0; i < 4; i++) load_q(qx[i], i * 512);
          sched();
          load_wo(wo, 0, NE4);
          sched();
          zero(c);
#pragma unroll
          for (int i = 0; i < 8; i++) mma_h(c[i & 3], kf[i], qx[i >> 1], i & 1);
          put_p(1, 0, 0); put_s(1);
          sched();
          load_wo(wo, NE4, NA4);
          sched();
          zero(c); zero(d);
#pragma unroll
          for (int i = 0; i < 8; i++) {
            if (i == 0) { y[0] = dif2v(q[0][0], q[0][2], q[1][0]); sched(); }
            if (i == 3) { y[1] = dif2v(q[1][2], q[2][0], q[2][2]); sched(); }
            if (i == 6) { y[2] = dif2v(q[3][0], q[3][2], tag); sched(); }
            mma_h(i % 6 < 2 ? c[2 + i % 6] : d[i - 2], kf[i], q[i >> 1], i & 1);
            if (i == 2 || i == 5 || i == 7) sched();
          }
          y[0] = or_and(or3(y[0], y[1], dif2v(q[0][0], q[2][0], tag)), y[2], it < SPIN_LIMIT);
#pragma unroll
          for (int i = 0; i < 4; i++) { c[0][i] = d[0][i] + d[1][i]; c[1][i] = d[2][i] + d[3][i]; }
          put_p(0, y[0], it - it0);
          TS(5);
          bar_sync_unless(5, it - it0);
          redo = __any_sync(0xffffffffu, y[0]);
          it += INC_A;
        } while (redo);
        it -= INC_A;
        put_s(0);
        bar_arrive(8, 256);
        load_wo(wo, NA4, NB1);
        out_proj();
        if (warp == 4) LOG(12, tb);
      } else {
        uint32_t qx[2][4], q[4][4];
        if (warp == 6) {
          const uint32_t t1 = (now & ~31u) + NS_M;
          LOG(10, now - due);
          if (elect()) stx32(&gx->T[h][j], ((int)(t1 - due) > 0 ? t1 + NS_PEN : due) | ((s + 1) & 31));
          __syncwarp();
        }
        auto score = [&](const uint32_t (&a0)[4], const uint32_t (&a1)[4]) {
          zero(c);
#pragma unroll
          for (int i = 0; i < 4; i++) mma_h(c[i], i < 2 ? a0 : a1, q[2 + (i >> 1)], i & 1);
        };
        auto put_m = [&](uint32_t a, uint32_t old, uint32_t again) {
#pragma unroll
          for (int i = 0; i < 2; i++) { r4[i] = fmaf(c[3][2 + i], sc, fmaf((c[0][i] + c[1][2 + i]) + c[2][i], sc, __uint_as_float(i ? 0u - old : 0u))); r4[2 + i] = fmaf(r4[i] * 0x1p122f, 0.f, ex2(r4[i])); }
          asm volatile("{.reg .pred p; setp.eq.u32 p, %3, 0; @p st.shared.v2.f32 [%0], {%1,%2};}" :: "r"(a), "f"(r4[2]), "f"(r4[3]), "r"(again) : "memory");
        };
        delay_until(tpub + DLY_A);
        const uint32_t sa = sb + R_S + 512 + w4 * 256 + (L16 >> 1);
        const int it0 = it;
        bool redo;
#pragma unroll 1
        do {
          wait_time(due);
          TS(4);
          ldx<4, 2048>(q, asrc);
          sched();
          load_q(qx[0], (w4 & 1) * 1024); load_q(qx[1], (w4 & 1) * 1024 + 512);
          load_wo(wo, 0, NA6);
          sched();
          score(q[0], q[1]);
          sched();
          const uint32_t y = or_and(or3(dif2v(q[0][0], q[0][2], tag), dif2v(q[1][0], q[1][2], tag), dif2v(q[2][0], q[2][2], tag)), dif2v(q[3][0], q[3][2], tag), it < SPIN_LIMIT);
          put_m(sa + 2560, y, it - it0);
          TS(5);
          bar_arrive_unless(5, it - it0);
          redo = __any_sync(0xffffffffu, y);
          it += INC_A;
        } while (redo);
        it -= INC_A;
        sts64f(sa, r4[0], r4[1]);
        score(qx[0], qx[1]);
        put_m(sa + 3584, 0, 0);
        sts64f(sa + 1536, r4[0], r4[1]);
        bar_arrive(8, 256);
        load_wo(wo, NA6, NB1);
        out_proj();
      }
      TS(8);
      if (s + 1 == NSEG) break;
      wait_x(s + 2, 2);
      TS(9);
      fresh();
      if (N1) project_qk(IC<32>{}, IC<32 + N1>{}, IC<1>{}, [](int) {});
      TS(10);
      xpos(6, 6);
      uint32_t fl = s + 1;
      if (warp == 5) { wait_time(due + NS_F); fl = ldx32(xa + 4096 + ((L16 >> 2) & 60)); }
      reload();
      TS(14);
      pin_mem();
      wait_x(s + 2, 1); wait_x(s + 2, 0);
      if (warp == 5) {
#pragma unroll 1
        while (__any_sync(0xffffffffu, fl != s + 1) && !(EXP & 4) && ++it < SPIN_LIMIT) fl = ldx32(xa + 4096 + ((L16 >> 2) & 60));
        wait_time(due + (NS_B + NS_K));
        if (!(EXP & 2) && elect()) issue_kqv(s + 1);
        __syncwarp();
      }
      if (PFD && warp == 6 && s + PFD < NSEG && elect())
        asm volatile("cp.async.bulk.prefetch.L2.global [%0], 2048;" :: "l"(xin + ((s + PFD) * SEG + ((role + 4 * (role >> 5)) & 31)) * DM) : "memory");
      __syncwarp();
      TS(11);
      LOG(warp, it);
      if (warp == 4) LOG(8, nc);
      bar_sync(0, 256);
      if (N1 < 16) project_qk(IC<32 + N1>{}, IC<48>{}, IC<!N1>{}, [](int) {});
      project_qk(IC<16>{}, IC<32>{}, IC<0>{}, [&](int n) { if ((n & 15) == XWPOS) { __syncwarp(); xok = mbar_test(sb + B_PK, s & 1); __syncwarp(); } });
      if (rare(!xok)) mbar_spin(sb + B_PK, s & 1, it);
      unpark();
      project_qk(IC<0>{}, IC<16>{}, IC<0>{}, [](int) {});
      TS(12);
      wg_wait<0>(); keep(aq);
      TS(1);
      fin_qk();
      TS(15);
    }
    s++;
  }
  if (it >= SPIN_LIMIT || nc >= NC_MAX) g_err = 2;
}

typedef CUresult (*EncodeFn)(CUtensorMap*, CUtensorMapDataType, cuuint32_t, void*, const cuuint64_t*, const cuuint64_t*, const cuuint32_t*,
                             const cuuint32_t*, CUtensorMapInterleave, CUtensorMapSwizzle, CUtensorMapL2promotion, CUtensorMapFloatOOBfill);
static void make_map(EncodeFn fn, CUtensorMap* m, const void* p, uint64_t cols, uint64_t rows, uint64_t pitch, uint32_t bc, uint32_t br, CUtensorMapSwizzle sw) {
  cuuint64_t dims[2] = {cols, rows}, strides[1] = {pitch * 2};
  cuuint32_t box[2] = {bc, br}, es[2] = {1, 1};
  fn(m, CU_TENSOR_MAP_DATA_TYPE_BFLOAT16, 2, const_cast<void*>(p), dims, strides, box, es, CU_TENSOR_MAP_INTERLEAVE_NONE, sw,
     CU_TENSOR_MAP_L2_PROMOTION_L2_256B, CU_TENSOR_MAP_FLOAT_OOB_FILL_NONE);
}

extern "C" void kernel_launch(void* const* d_in, const int* in_sizes, int n_in, void* d_out, int out_size) {
  const bf16* Ax = (const bf16*)d_in[0]; const bf16* mem0 = (const bf16*)d_in[1];
  const bf16* Wq = (const bf16*)d_in[2]; const bf16* Wk = (const bf16*)d_in[3]; const bf16* Wv = (const bf16*)d_in[4];
  const bf16* Wo = (const bf16*)d_in[5];
  const bf16* Bx = (const bf16*)d_in[7]; const bf16* wr = (const bf16*)d_in[8]; const bf16* wi = (const bf16*)d_in[9];
  bf16* out = (bf16*)d_out;

  void* fp = nullptr; cudaDriverEntryPointQueryResult qr;
  cudaGetDriverEntryPoint("cuTensorMapEncodeTiled", &fp, cudaEnableDefault, &qr);
  EncodeFn fn = (EncodeFn)fp;
  void *kqv, *ox, *xr;
  cudaGetSymbolAddress(&xr, g_xraw);
  cudaGetSymbolAddress(&kqv, g_kqv); cudaGetSymbolAddress(&ox, g_ox);
  const CUtensorMapSwizzle S128 = CU_TENSOR_MAP_SWIZZLE_128B, S64 = CU_TENSOR_MAP_SWIZZLE_64B;

  GemmMaps m3; RecMaps mr;
  make_map(fn, &m3.a, ox, HD, S_LEN, HD, 64, 128, S128);
  make_map(fn, &m3.b[0], Wo, DM, HD, DM, 64, 64, S128);
  m3.b[1] = m3.b[0]; m3.b[2] = m3.b[0];
  make_map(fn, &m3.c, out, DM, S_LEN, 2 * DM, 64, 64, S128);
  make_map(fn, &mr.wq, Wq, HD, DM, HD, 32, 256, S64);
  make_map(fn, &mr.wk, Wk, HD, DM, HD, 32, 256, S64);
  make_map(fn, &mr.wv, Wv, HD, DM, HD, 64, 256, S128);
  make_map(fn, &mr.wo, Wo, DM, HD, DM, 64, 128, S128);
  {
    cuuint64_t dims[3] = {64, S_LEN, 16}, strides[2] = {DM * 2, 128};
    cuuint32_t box[3] = {64, 32, 4}, es[3] = {1, 1, 1};
    fn(&mr.x, CU_TENSOR_MAP_DATA_TYPE_BFLOAT16, 3, const_cast<bf16*>(Ax), dims, strides, box, es, CU_TENSOR_MAP_INTERLEAVE_NONE, S128,
       CU_TENSOR_MAP_L2_PROMOTION_L2_256B, CU_TENSOR_MAP_FLOAT_OOB_FILL_NONE);
  }
  for (int i = 0; i < 3; i++) {
    cuuint64_t dims[3] = {128, 32, 512}, strides[2] = {256, 8192};
    cuuint32_t box[3] = {128, i == 0 ? 8u : i == 1 ? 2u : 16u, 4}, es[3] = {1, 1, 1};
    fn(i == 0 ? &mr.k : i == 1 ? &mr.q : &mr.v, CU_TENSOR_MAP_DATA_TYPE_BFLOAT16, 3, kqv, dims, strides, box, es, CU_TENSOR_MAP_INTERLEAVE_NONE,
       CU_TENSOR_MAP_SWIZZLE_NONE, CU_TENSOR_MAP_L2_PROMOTION_L2_256B, CU_TENSOR_MAP_FLOAT_OOB_FILL_NONE);
  }
  {
    cuuint64_t dims[3] = {64, 16, S_LEN}, strides[2] = {128, 2 * DM * 2};
    cuuint32_t box[3] = {64, 16, 2}, es[3] = {1, 1, 1};
    fn(&mr.fo, CU_TENSOR_MAP_DATA_TYPE_BFLOAT16, 3, out + DM, dims, strides, box, es, CU_TENSOR_MAP_INTERLEAVE_NONE, S128,
       CU_TENSOR_MAP_L2_PROMOTION_NONE, CU_TENSOR_MAP_FLOAT_OOB_FILL_NONE);
  }
  constexpr int SM3 = 6 * 32768 + 32768 + 256 + 1024;
  cudaFuncSetAttribute(gemm_kernel<128, 6>, cudaFuncAttributeMaxDynamicSharedMemorySize, SM3);
  cudaFuncSetAttribute(rec_kernel, cudaFuncAttributeMaxDynamicSharedMemorySize, R_TOTAL);

  cudaStream_t st = cudaStreamPerThread;
  Xchg* gx = reinterpret_cast<Xchg*>((reinterpret_cast<uintptr_t>(xr) + 0x1FFFFF) & ~(uintptr_t)0x1FFFFF);
  rec_kernel<<<132, 256, R_TOTAL, st>>>(mr, Ax, mem0, gx, Bx, wr, wi);
  gemm_kernel<128, 6><<<128, 384, SM3, st>>>(m3, 16, 8, 64, 8, reinterpret_cast<uint4*>(gx));
}
```

```cpp
#include <cuda_runtime.h>
#include <cuda_bf16.h>
#include <cuda.h>
#include <stdint.h>
#include <stddef.h>
#include <type_traits>

typedef __nv_bfloat16 bf16;

constexpr int S_LEN = 2048, DM = 1024, NH = 32, DH = 128, MEM = 8, SEG = 32, NSEG = 64;
constexpr int HD = NH * DH;
#define SPIN 20
constexpr int SPIN_LIMIT = 1 << SPIN, INC_A = 1, INC_B = 1;

constexpr unsigned NC_MAX = 4096;
__device__ __align__(1024) uint4 g_kqv[4][128][512];
__device__ __align__(1024) bf16 g_ox[(size_t)S_LEN * HD];
struct Xchg {
  uint4 A[32][4][256];
  uint4 C[4][2][256];
  uint4 B[128][2][256];
  uint32_t T[32][32];
  uint32_t S[128];
  unsigned ctr[64];
};
__device__ __align__(1024) uint4 g_xraw[(sizeof(Xchg) + (1 << 21)) / 16];
__device__ __align__(1024) uint4 g_y[1024 * 256];
__device__ __align__(1024) uint4 g_wt[513 * 512];
__device__ int g_err;

__device__ __forceinline__ unsigned clk() { unsigned long long c; asm volatile("mov.u64 %0, %%clock64;" : "=l"(c)); return (unsigned)c; }
__device__ __forceinline__ uint32_t smem_u32(const void* p) { return (uint32_t)__cvta_generic_to_shared(p); }
__device__ __forceinline__ void mbar_init(uint32_t bar, int cnt) { asm volatile("mbarrier.init.shared::cta.b64 [%0], %1;" :: "r"(bar), "r"(cnt) : "memory"); }
__device__ __forceinline__ void mbar_expect_tx(uint32_t bar, int bytes) { asm volatile("mbarrier.arrive.expect_tx.shared::cta.b64 _, [%0], %1;" :: "r"(bar), "r"(bytes) : "memory"); }
__device__ __forceinline__ void mbar_arrive(uint32_t bar) { asm volatile("mbarrier.arrive.shared::cta.b64 _, [%0];" :: "r"(bar) : "memory"); }
__device__ __forceinline__ void mbar_arrive_cluster(uint32_t bar, int cta) {
  asm volatile("{.reg .b32 r; mapa.shared::cluster.u32 r, %0, %1; mbarrier.arrive.shared::cluster.b64 _, [r];}" :: "r"(bar), "r"(cta) : "memory"); }
__device__ __forceinline__ bool mbar_try(uint32_t bar, int par) {
  uint32_t ok; asm volatile("{.reg .pred p; mbarrier.try_wait.parity.shared::cta.b64 p, [%1], %2; selp.u32 %0, 1, 0, p;}" : "=r"(ok) : "r"(bar), "r"(par) : "memory"); return ok; }
__device__ __forceinline__ bool mbar_test(uint32_t bar, int par) {
  uint32_t ok; asm volatile("{.reg .pred p; mbarrier.test_wait.parity.shared::cta.b64 p, [%1], %2; selp.u32 %0, 1, 0, p;}" : "=r"(ok) : "r"(bar), "r"(par) : "memory"); return ok; }
__device__ __forceinline__ void mbar_wait(uint32_t bar, int par) {
  int it = 0;
  while (!mbar_try(bar, par)) { if (++it > SPIN_LIMIT) { g_err = 1; break; } }
}
__device__ __forceinline__ void tma2d(uint32_t dst, const CUtensorMap* m, int c0, int c1, uint32_t bar) {
  asm volatile("cp.async.bulk.tensor.2d.shared::cluster.global.mbarrier::complete_tx::bytes [%0], [%1, {%3, %4}], [%2];"
    :: "r"(dst), "l"(m), "r"(bar), "r"(c0), "r"(c1) : "memory"); }
__device__ __forceinline__ void tma2d_mc(uint32_t dst, const CUtensorMap* m, int c0, int c1, uint32_t bar, uint16_t mask) {
  asm volatile("cp.async.bulk.tensor.2d.shared::cluster.global.mbarrier::complete_tx::bytes.multicast::cluster [%0], [%1, {%3, %4}], [%2], %5;"
    :: "r"(dst), "l"(m), "r"(bar), "r"(c0), "r"(c1), "h"(mask) : "memory"); }
__device__ __forceinline__ void tma2d_store(const CUtensorMap* m, uint32_t src, int c0, int c1) {
  asm volatile("cp.async.bulk.tensor.2d.global.shared::cta.bulk_group [%0, {%2, %3}], [%1];" :: "l"(m), "r"(src), "r"(c0), "r"(c1) : "memory"); }
__device__ __forceinline__ void fence_async() { asm volatile("fence.proxy.async.shared::cta;" ::: "memory"); }
__device__ __forceinline__ void bar_sync(int id, int n) { asm volatile("bar.sync %0, %1;" :: "r"(id), "r"(n) : "memory"); }
__device__ __forceinline__ void bar_arrive(int id, int n) { asm volatile("bar.arrive %0, %1;" :: "r"(id), "r"(n) : "memory"); }
__device__ __forceinline__ uint32_t pack2(float lo, float hi) { uint32_t r; asm("cvt.rn.bf16x2.f32 %0, %1, %2;" : "=r"(r) : "f"(hi), "f"(lo)); return r; }
__device__ __forceinline__ uint32_t pack2_tag(float lo, float hi, uint32_t T) {
  uint32_t u = ((__float_as_uint(lo) - T + 0x10000u) & 0xFFFE0000u) + T;
  return __byte_perm(u, pack2(0.f, hi), 0x7632); }
__device__ __forceinline__ void ldsm4(uint32_t (&r)[4], uint32_t a) {
  asm volatile("ldmatrix.sync.aligned.m8n8.x4.shared.b16 {%0,%1,%2,%3}, [%4];" : "=r"(r[0]), "=r"(r[1]), "=r"(r[2]), "=r"(r[3]) : "r"(a) : "memory"); }
__device__ __forceinline__ void ldsm4t(uint32_t (&r)[4], uint32_t a) {
  asm volatile("ldmatrix.sync.aligned.m8n8.x4.trans.shared.b16 {%0,%1,%2,%3}, [%4];" : "=r"(r[0]), "=r"(r[1]), "=r"(r[2]), "=r"(r[3]) : "r"(a) : "memory"); }
__device__ __forceinline__ void stsm4(uint32_t a, uint32_t r0, uint32_t r1, uint32_t r2, uint32_t r3) {
  asm volatile("stmatrix.sync.aligned.m8n8.x4.shared.b16 [%0], {%1,%2,%3,%4};" :: "r"(a), "r"(r0), "r"(r1), "r"(r2), "r"(r3) : "memory"); }
__device__ __forceinline__ void stsm4t(uint32_t a, uint32_t r0, uint32_t r1, uint32_t r2, uint32_t r3) {
  asm volatile("stmatrix.sync.aligned.m8n8.x4.trans.shared.b16 [%0], {%1,%2,%3,%4};" :: "r"(a), "r"(r0), "r"(r1), "r"(r2), "r"(r3) : "memory"); }
__device__ __forceinline__ void lds128(uint32_t (&r)[4], uint32_t a) {
  asm volatile("ld.shared.v4.u32 {%0,%1,%2,%3}, [%4];" : "=r"(r[0]), "=r"(r[1]), "=r"(r[2]), "=r"(r[3]) : "r"(a) : "memory"); }
__device__ __forceinline__ float4 lds128f(uint32_t a) { float4 r;
  asm volatile("ld.shared.v4.f32 {%0,%1,%2,%3}, [%4];" : "=f"(r.x), "=f"(r.y), "=f"(r.z), "=f"(r.w) : "r"(a) : "memory"); return r; }
__device__ __forceinline__ float2 lds64f(uint32_t a) { float2 r;
  asm volatile("ld.shared.v2.f32 {%0,%1}, [%2];" : "=f"(r.x), "=f"(r.y) : "r"(a) : "memory"); return r; }
__device__ __forceinline__ void sts128(uint32_t a, uint32_t r0, uint32_t r1, uint32_t r2, uint32_t r3) {
  asm volatile("st.shared.v4.u32 [%0], {%1,%2,%3,%4};" :: "r"(a), "r"(r0), "r"(r1), "r"(r2), "r"(r3) : "memory"); }
__device__ __forceinline__ void sts64f(uint32_t a, float x, float y) { asm volatile("st.shared.v2.f32 [%0], {%1,%2};" :: "r"(a), "f"(x), "f"(y) : "memory"); }
__device__ __forceinline__ void sts32f(uint32_t a, float x) { asm volatile("st.shared.f32 [%0], %1;" :: "r"(a), "f"(x) : "memory"); }
__device__ __forceinline__ void mma16816(float (&d)[4], uint32_t a0, uint32_t a1, uint32_t a2, uint32_t a3, uint32_t b0, uint32_t b1) {
  asm volatile("mma.sync.aligned.m16n8k16.row.col.f32.bf16.bf16.f32 {%0,%1,%2,%3}, {%4,%5,%6,%7}, {%8,%9}, {%0,%1,%2,%3};"
    : "+f"(d[0]), "+f"(d[1]), "+f"(d[2]), "+f"(d[3]) : "r"(a0), "r"(a1), "r"(a2), "r"(a3), "r"(b0), "r"(b1)); }
__device__ __forceinline__ void mma1688(float (&d)[4], uint32_t a0, uint32_t a1, uint32_t b0) {
  asm volatile("mma.sync.aligned.m16n8k8.row.col.f32.bf16.bf16.f32 {%0,%1,%2,%3}, {%4,%5}, {%6}, {%0,%1,%2,%3};"
    : "+f"(d[0]), "+f"(d[1]), "+f"(d[2]), "+f"(d[3]) : "r"(a0), "r"(a1), "r"(b0)); }
__device__ __forceinline__ void ldx128(uint32_t (&r)[4], const void* p) {
  asm volatile("{.reg .b128 t; .reg .b64 a, b; ld.relaxed.gpu.global.b128 t, [%4]; mov.b128 {a, b}, t; mov.b64 {%0,%1}, a; mov.b64 {%2,%3}, b;}"
    : "=r"(r[0]), "=r"(r[1]), "=r"(r[2]), "=r"(r[3]) : "l"(p) : "memory"); }
__device__ __forceinline__ void ldx2x64(uint32_t (&r)[4], const void* p) {
  asm volatile("{.reg .b64 a, b; ld.relaxed.gpu.global.v2.b64 {a, b}, [%4]; mov.b64 {%0,%1}, a; mov.b64 {%2,%3}, b;}"
    : "=r"(r[0]), "=r"(r[1]), "=r"(r[2]), "=r"(r[3]) : "l"(p) : "memory"); }
__device__ __forceinline__ void stx128(void* p, uint32_t r0, uint32_t r1, uint32_t r2, uint32_t r3) {
  asm volatile("{.reg .b128 t; .reg .b64 a, b; mov.b64 a, {%1,%2}; mov.b64 b, {%3,%4}; mov.b128 t, {a, b}; st.relaxed.gpu.global.b128 [%0], t;}"
    :: "l"(p), "r"(r0), "r"(r1), "r"(r2), "r"(r3) : "memory"); }
__device__ __forceinline__ void stx64(void* p, uint32_t r0, uint32_t r1) {
  asm volatile("{.reg .b64 a; mov.b64 a, {%1,%2}; st.relaxed.gpu.global.b64 [%0], a;}" :: "l"(p), "r"(r0), "r"(r1) : "memory"); }
__device__ __forceinline__ uint32_t uni(uint32_t x) { return __shfl_sync(0xffffffffu, x, 0); }
__device__ __forceinline__ uint32_t pin(uint32_t x) { return __shfl_xor_sync(0xffffffffu, x, 0); }
__device__ __forceinline__ float ex2(float x) { float r; asm("ex2.approx.ftz.f32 %0, %1;" : "=f"(r) : "f"(x)); return r; }
__device__ __forceinline__ void wg_fence() { asm volatile("wgmma.fence.sync.aligned;" ::: "memory"); }
__device__ __forceinline__ void wg_commit() { asm volatile("wgmma.commit_group.sync.aligned;" ::: "memory"); }
template <int N> __device__ __forceinline__ void wg_wait() { asm volatile("wgmma.wait_group.sync.aligned %0;" :: "n"(N) : "memory"); }

__device__ __forceinline__ void wgmma_ss_n256_tb1(float (&d)[128], uint64_t da, uint64_t db, int sc) {
  asm volatile("{.reg .pred p; setp.ne.b32 p, %130, 0;\n"
    "wgmma.mma_async.sync.aligned.m64n256k16.f32.bf16.bf16 {%0,%1,%2,%3,%4,%5,%6,%7,%8,%9,%10,%11,%12,%13,%14,%15,%16,%17,%18,%19,%20,%21,%22,%23,%24,%25,%26,%27,%28,%29,%30,%31,%32,%33,%34,%35,%36,%37,%38,%39,%40,%41,%42,%43,%44,%45,%46,%47,%48,%49,%50,%51,%52,%53,%54,%55,%56,%57,%58,%59,%60,%61,%62,%63,%64,%65,%66,%67,%68,%69,%70,%71,%72,%73,%74,%75,%76,%77,%78,%79,%80,%81,%82,%83,%84,%85,%86,%87,%88,%89,%90,%91,%92,%93,%94,%95,%96,%97,%98,%99,%100,%101,%102,%103,%104,%105,%106,%107,%108,%109,%110,%111,%112,%113,%114,%115,%116,%117,%118,%119,%120,%121,%122,%123,%124,%125,%126,%127}, %128, %129, p, 1, 1, 0, 1;}\n"
    : "+f"(d[0]),"+f"(d[1]),"+f"(d[2]),"+f"(d[3]),"+f"(d[4]),"+f"(d[5]),"+f"(d[6]),"+f"(d[7]),"+f"(d[8]),"+f"(d[9]),"+f"(d[10]),"+f"(d[11]),"+f"(d[12]),"+f"(d[13]),"+f"(d[14]),"+f"(d[15]),"+f"(d[16]),"+f"(d[17]),"+f"(d[18]),"+f"(d[19]),"+f"(d[20]),"+f"(d[21]),"+f"(d[22]),"+f"(d[23]),"+f"(d[24]),"+f"(d[25]),"+f"(d[26]),"+f"(d[27]),"+f"(d[28]),"+f"(d[29]),"+f"(d[30]),"+f"(d[31]),"+f"(d[32]),"+f"(d[33]),"+f"(d[34]),"+f"(d[35]),"+f"(d[36]),"+f"(d[37]),"+f"(d[38]),"+f"(d[39]),"+f"(d[40]),"+f"(d[41]),"+f"(d[42]),"+f"(d[43]),"+f"(d[44]),"+f"(d[45]),"+f"(d[46]),"+f"(d[47]),"+f"(d[48]),"+f"(d[49]),"+f"(d[50]),"+f"(d[51]),"+f"(d[52]),"+f"(d[53]),"+f"(d[54]),"+f"(d[55]),"+f"(d[56]),"+f"(d[57]),"+f"(d[58]),"+f"(d[59]),"+f"(d[60]),"+f"(d[61]),"+f"(d[62]),"+f"(d[63]),"+f"(d[64]),"+f"(d[65]),"+f"(d[66]),"+f"(d[67]),"+f"(d[68]),"+f"(d[69]),"+f"(d[70]),"+f"(d[71]),"+f"(d[72]),"+f"(d[73]),"+f"(d[74]),"+f"(d[75]),"+f"(d[76]),"+f"(d[77]),"+f"(d[78]),"+f"(d[79]),"+f"(d[80]),"+f"(d[81]),"+f"(d[82]),"+f"(d[83]),"+f"(d[84]),"+f"(d[85]),"+f"(d[86]),"+f"(d[87]),"+f"(d[88]),"+f"(d[89]),"+f"(d[90]),"+f"(d[91]),"+f"(d[92]),"+f"(d[93]),"+f"(d[94]),"+f"(d[95]),"+f"(d[96]),"+f"(d[97]),"+f"(d[98]),"+f"(d[99]),"+f"(d[100]),"+f"(d[101]),"+f"(d[102]),"+f"(d[103]),"+f"(d[104]),"+f"(d[105]),"+f"(d[106]),"+f"(d[107]),"+f"(d[108]),"+f"(d[109]),"+f"(d[110]),"+f"(d[111]),"+f"(d[112]),"+f"(d[113]),"+f"(d[114]),"+f"(d[115]),"+f"(d[116]),"+f"(d[117]),"+f"(d[118]),"+f"(d[119]),"+f"(d[120]),"+f"(d[121]),"+f"(d[122]),"+f"(d[123]),"+f"(d[124]),"+f"(d[125]),"+f"(d[126]),"+f"(d[127])
    : "l"(da), "l"(db), "r"(sc));
}

__device__ __forceinline__ void wgmma_ss_n128_tb1(float (&d)[64], uint64_t da, uint64_t db, int sc) {
  asm volatile("{.reg .pred p; setp.ne.b32 p, %66, 0;\n"
    "wgmma.mma_async.sync.aligned.m64n128k16.f32.bf16.bf16 {%0,%1,%2,%3,%4,%5,%6,%7,%8,%9,%10,%11,%12,%13,%14,%15,%16,%17,%18,%19,%20,%21,%22,%23,%24,%25,%26,%27,%28,%29,%30,%31,%32,%33,%34,%35,%36,%37,%38,%39,%40,%41,%42,%43,%44,%45,%46,%47,%48,%49,%50,%51,%52,%53,%54,%55,%56,%57,%58,%59,%60,%61,%62,%63}, %64, %65, p, 1, 1, 0, 1;}\n"
    : "+f"(d[0]),"+f"(d[1]),"+f"(d[2]),"+f"(d[3]),"+f"(d[4]),"+f"(d[5]),"+f"(d[6]),"+f"(d[7]),"+f"(d[8]),"+f"(d[9]),"+f"(d[10]),"+f"(d[11]),"+f"(d[12]),"+f"(d[13]),"+f"(d[14]),"+f"(d[15]),"+f"(d[16]),"+f"(d[17]),"+f"(d[18]),"+f"(d[19]),"+f"(d[20]),"+f"(d[21]),"+f"(d[22]),"+f"(d[23]),"+f"(d[24]),"+f"(d[25]),"+f"(d[26]),"+f"(d[27]),"+f"(d[28]),"+f"(d[29]),"+f"(d[30]),"+f"(d[31]),"+f"(d[32]),"+f"(d[33]),"+f"(d[34]),"+f"(d[35]),"+f"(d[36]),"+f"(d[37]),"+f"(d[38]),"+f"(d[39]),"+f"(d[40]),"+f"(d[41]),"+f"(d[42]),"+f"(d[43]),"+f"(d[44]),"+f"(d[45]),"+f"(d[46]),"+f"(d[47]),"+f"(d[48]),"+f"(d[49]),"+f"(d[50]),"+f"(d[51]),"+f"(d[52]),"+f"(d[53]),"+f"(d[54]),"+f"(d[55]),"+f"(d[56]),"+f"(d[57]),"+f"(d[58]),"+f"(d[59]),"+f"(d[60]),"+f"(d[61]),"+f"(d[62]),"+f"(d[63])
    : "l"(da), "l"(db), "r"(sc));
}

template <int BN> struct WG;
template <> struct WG<256> { static __device__ __forceinline__ void mma(float (&d)[128], uint64_t a, uint64_t b, int sc) { wgmma_ss_n256_tb1(d, a, b, sc); } };
template <> struct WG<128> { static __device__ __forceinline__ void mma(float (&d)[64], uint64_t a, uint64_t b, int sc) { wgmma_ss_n128_tb1(d, a, b, sc); } };

struct GemmMaps { CUtensorMap a, b[3], c; };
template <int BN, int STAGES>
__global__ void __cluster_dims__(2, 1, 1) __launch_bounds__(384, 1)
gemm_kernel(const __grid_constant__ GemmMaps maps, int tilesM, int tilesN, int kblocks, int nPerB, uint4* __restrict__ clearX) {
  extern __shared__ __align__(1024) uint8_t smem_raw[];
  constexpr int STAGE_BYTES = 16384 + BN * 128;
  constexpr int NBOX = BN / 64;
  const uint32_t sbase = (smem_u32(smem_raw) + 1023) & ~1023u;
  const uint32_t sEpi = sbase + STAGES * STAGE_BYTES;
  const uint32_t sBar = sEpi + 32768;
  const int warp = threadIdx.x >> 5, lane = threadIdx.x & 31, wg = warp >> 2;
  uint32_t crank; asm("mov.u32 %0, %%cluster_ctarank;" : "=r"(crank));
  if (threadIdx.x == 0) {
    for (int i = 0; i < STAGES; i++) { mbar_init(sBar + 8 * i, 1); mbar_init(sBar + 8 * (STAGES + i), 4); }
    asm volatile("fence.mbarrier_init.release.cluster;" ::: "memory");
  }
  for (int i = blockIdx.x * 384 + threadIdx.x; i < (int)(sizeof(Xchg) / 16); i += gridDim.x * 384) clearX[i] = make_uint4(0, 0, 0, 0);
  asm volatile("barrier.cluster.arrive.release.aligned; barrier.cluster.wait.acquire.aligned;" ::: "memory");
  const int npairs = (tilesM >> 1) * tilesN, pair0 = blockIdx.x >> 1, pstep = gridDim.x >> 1;
  if (wg == 2) {
    asm volatile("setmaxnreg.dec.sync.aligned.u32 40;");
    if (warp == 8 && lane == 0) {
      int st = 0, ph = 1;
      for (int p = pair0; p < npairs; p += pstep) {
        const int tm = (p % (tilesM >> 1)) * 2 + crank, tn = p / (tilesM >> 1);
        const CUtensorMap* mb = &maps.b[tn / nPerB];
        const int n0 = (tn % nPerB) * BN;
        for (int kb = 0; kb < kblocks; kb++) {
          mbar_wait(sBar + 8 * (STAGES + st), ph);
          const uint32_t a = sbase + st * STAGE_BYTES, full = sBar + 8 * st;
          mbar_expect_tx(full, STAGE_BYTES);
          tma2d(a, &maps.a, kb * 64, tm * 128, full);
#pragma unroll
          for (int i = 0; i < NBOX / 2; i++) {
            const int bx = crank * (NBOX / 2) + i;
            tma2d_mc(a + 16384 + bx * 8192, mb, n0 + bx * 64, kb * 64, full, (uint16_t)3);
          }
          if (++st == STAGES) { st = 0; ph ^= 1; }
        }
      }
      for (int i = 0; i < STAGES; i++) { mbar_wait(sBar + 8 * (STAGES + st), ph); if (++st == STAGES) { st = 0; ph ^= 1; } }
    }
  } else {
    asm volatile("setmaxnreg.inc.sync.aligned.u32 232;");
    int st = 0, ph = 0;
    float acc[BN / 2];
    const uint64_t descA0 = (uint64_t)(((sbase + wg * 8192) & 0x3FFFF) >> 4) | (1ull << 16) | (64ull << 32) | (1ull << 62);
    const uint64_t descB0 = (uint64_t)(((sbase + 16384) & 0x3FFFF) >> 4) | (512ull << 16) | (64ull << 32) | (1ull << 62);
    const uint32_t epi = sEpi + wg * 16384;
    for (int p = pair0; p < npairs; p += pstep) {
      const int tm = (p % (tilesM >> 1)) * 2 + crank, tn = p / (tilesM >> 1);
      int prev = -1;
      for (int kb = 0; kb < kblocks; kb++) {
        mbar_wait(sBar + 8 * st, ph);
        wg_fence();
        const uint64_t so = (uint64_t)(st * (STAGE_BYTES >> 4));
#pragma unroll
        for (int k = 0; k < 4; k++) WG<BN>::mma(acc, descA0 + so + k * 2, descB0 + so + k * 128, kb | k);
        wg_commit();
        if (prev >= 0) {
          wg_wait<1>();
          if ((threadIdx.x & 127) < 2) mbar_arrive_cluster(sBar + 8 * (STAGES + prev), threadIdx.x & 1);
        }
        prev = st;
        if (++st == STAGES) { st = 0; ph ^= 1; }
      }
      wg_wait<0>();
      if ((threadIdx.x & 127) < 2) mbar_arrive_cluster(sBar + 8 * (STAGES + prev), threadIdx.x & 1);
#pragma unroll
      for (int r = 0; r < BN / 128; r++) {
        if ((threadIdx.x & 127) == 0) asm volatile("cp.async.bulk.wait_group.read 0;" ::: "memory");
        bar_sync(1 + wg, 128);
        const int row = (warp & 3) * 16 + (lane & 15);
#pragma unroll
        for (int i = 0; i < 8; i++) {
          const int c = 2 * (i & 3) + (lane >> 4);
          const float* q = &acc[r * 64 + i * 8];
          stsm4(epi + (i >> 2) * 8192 + row * 128 + ((c ^ (row & 7)) << 4), pack2(q[0], q[1]), pack2(q[2], q[3]), pack2(q[4], q[5]), pack2(q[6], q[7]));
        }
        fence_async();
        bar_sync(1 + wg, 128);
        if ((threadIdx.x & 127) == 0) {
          tma2d_store(&maps.c, epi, tn * BN + r * 128, tm * 128 + wg * 64);
          tma2d_store(&maps.c, epi + 8192, tn * BN + r * 128 + 64, tm * 128 + wg * 64);
          asm volatile("cp.async.bulk.commit_group;" ::: "memory");
        }
      }
    }
    if ((threadIdx.x & 127) == 0) asm volatile("cp.async.bulk.wait_group 0;" ::: "memory");
  }
}

struct Dft { uint32_t m[2][2][2][4]; };
template <bool P4> __device__ __forceinline__ int fidx(int tile, int x) { return P4 ? 4 * (x >> 1) + 2 * (tile & 1) + (x & 1) + 16 * (tile >> 1) : x + 8 * tile; }
__device__ __forceinline__ float2 cis(int k, int n) {
  k &= n - 1; if (2 * k > n) k -= n;
  const float a = (float)k * (6.283185307179586f / (float)n);
  return make_float2(__cosf(a), __sinf(a));
}
template <bool OUT4> __device__ __forceinline__ void make_dft(Dft& D, int g, int t) {
#pragma unroll
  for (int q = 0; q < 16; q++) {
    const int b = q >> 3, u = (q >> 2) & 1, r = (q >> 1) & 1, v = q & 1;
    const float2 w = cis(fidx<OUT4>(v, g) * fidx<false>(2 * u + r, 2 * t + b), 32);
    D.m[b][u][0][q & 3] = pack2(w.x, w.y); D.m[b][u][1][q & 3] = pack2(-w.y, w.x);
  }
}
__device__ __forceinline__ void mma_dc(float (&d)[4], uint32_t a0, uint32_t a1, uint32_t a2, uint32_t a3, uint32_t b0, uint32_t b1, const float (&c)[4]) {
  asm("mma.sync.aligned.m16n8k16.row.col.f32.bf16.bf16.f32 {%0,%1,%2,%3}, {%4,%5,%6,%7}, {%8,%9}, {%10,%11,%12,%13};"
    : "=f"(d[0]), "=f"(d[1]), "=f"(d[2]), "=f"(d[3]) : "r"(a0), "r"(a1), "r"(a2), "r"(a3), "r"(b0), "r"(b1), "f"(c[0]), "f"(c[1]), "f"(c[2]), "f"(c[3])); }
__device__ __forceinline__ void dft_b(const Dft& D, const uint32_t (&x)[2][4], float (&o)[2][8]) {
#pragma unroll
  for (int ri = 0; ri < 2; ri++) {
    float z[4] = {0.f, 0.f, 0.f, 0.f}, e[4], p[4];
    mma_dc(e, D.m[0][0][ri][0], D.m[0][0][ri][1], D.m[0][0][ri][2], D.m[0][0][ri][3], x[0][0], x[0][1], z);
    mma_dc(e, D.m[0][1][ri][0], D.m[0][1][ri][1], D.m[0][1][ri][2], D.m[0][1][ri][3], x[0][2], x[0][3], e);
    mma_dc(p, D.m[1][0][ri][0], D.m[1][0][ri][1], D.m[1][0][ri][2], D.m[1][0][ri][3], x[1][0], x[1][1], e);
    mma_dc(p, D.m[1][1][ri][0], D.m[1][1][ri][1], D.m[1][1][ri][2], D.m[1][1][ri][3], x[1][2], x[1][3], p);
#pragma unroll
    for (int q = 0; q < 4; q++) { o[ri][q] = p[q]; o[ri][4 + q] = fmaf(2.f, e[q], -p[q]); }
  }
}
__device__ __forceinline__ void dft_a(const uint32_t (&m)[2][2][4], const uint32_t (&x0)[2][4], const uint32_t (&x1)[2][4], float (&o)[2][8]) {
#pragma unroll
  for (int ri = 0; ri < 2; ri++) {
    float z[4] = {0.f, 0.f, 0.f, 0.f}, e[4], p[4];
    mma_dc(e, x0[0][0], x1[0][0], x0[0][1], x1[0][1], m[0][ri][0], m[0][ri][1], z);
    mma_dc(e, x0[0][2], x1[0][2], x0[0][3], x1[0][3], m[0][ri][2], m[0][ri][3], e);
    mma_dc(p, x0[1][0], x1[1][0], x0[1][1], x1[1][1], m[1][ri][0], m[1][ri][1], e);
    mma_dc(p, x0[1][2], x1[1][2], x0[1][3], x1[1][3], m[1][ri][2], m[1][ri][3], p);
#pragma unroll
    for (int q = 0; q < 4; q++) { o[ri][q] = p[q]; o[ri][4 + q] = fmaf(2.f, e[q], -p[q]); }
  }
}
__device__ __forceinline__ uint32_t twid(float re, float im, float c, float s) { return pack2(fmaf(re, c, im * s), fmaf(im, c, -re * s)); }
__device__ __forceinline__ void cpa16(uint32_t d, const void* s) { asm volatile("cp.async.cg.shared.global [%0], [%1], 16;" :: "r"(d), "l"(s) : "memory"); }
__device__ __forceinline__ void sts32(uint32_t a, uint32_t x) { asm volatile("st.shared.u32 [%0], %1;" :: "r"(a), "r"(x) : "memory"); }
__device__ __forceinline__ void cpa_commit() { asm volatile("cp.async.commit_group;" ::: "memory"); }
template <int N> __device__ __forceinline__ void cpa_wait() { asm volatile("cp.async.wait_group %0;" :: "n"(N) : "memory"); }
__device__ __forceinline__ uint32_t lds32(uint32_t a) { uint32_t r; asm volatile("ld.shared.u32 %0, [%1];" : "=r"(r) : "r"(a) : "memory"); return r; }
#define FMID 0
constexpr int F_TP = 4112, F_TSZ = 8 * F_TP;

__device__ __forceinline__ uint32_t ldnc32(const void* p) { uint32_t v; asm volatile("ld.global.nc.b32 %0, [%1];" : "=r"(v) : "l"(p) : "memory"); return v; }
template <class F>
__device__ __forceinline__ void fft_wprep(const bf16* __restrict__ wr, const bf16* __restrict__ wi, int cta, F&& mid) {
  const int tid = threadIdx.x, g = (cta >> 1) & 7, c = (cta >> 4) & 3, t = 2 * (cta & 1) + (tid & 1);
  const int k0 = g + 8 * (cta >> 6) + 32 * (8 * c + 2 * t), l0 = (tid & ~1) + (g & 1);
  uint32_t a[4][4], b[4][4];
#pragma unroll
  for (int q = 0; q < 16; q++) {
    const int o = (k0 + 16 * (q >> 3) + 32 * ((q >> 1) & 1) + 1024 * (q & 1)) * 513 + l0 + 256 * ((q >> 2) & 1);
    a[q >> 2][q & 3] = ldnc32(wr + o);
    b[q >> 2][q & 3] = ldnc32(wi + o);
  }
  const int e = cta * 32 + (tid & 31), lh = (e >> 11) * 512, k = e & 2047, k2 = (k >> 5) & 31;
  uint32_t hz[4];
#pragma unroll
  for (int q = 0; q < 4; q++) asm volatile("ld.global.nc.u16 %0, [%1];" : "=r"(hz[q]) : "l"((q < 2 ? wr : wi) + (q & 1 ? (2048 - k) & 2047 : k) * 513 + lh) : "memory");
  mid();
  uint4* dst = g_wt + l0 * 512 + cta * 2 + (tid & 1);
#pragma unroll
  for (int q = 0; q < 8; q++) {
    const int hf = q >> 1, l = l0 + 256 * (hf & 1) + (q & 1);
    const uint32_t sel = (q & 1) ? 0x7632 : 0x5410;
    if (l & 511) dst[(256 * (hf & 1) + (q & 1)) * 512 + 256 * (q >> 2)] = make_uint4(__byte_perm(a[hf][0], b[hf][0], sel), __byte_perm(a[hf][1], b[hf][1], sel),
                                                                                   __byte_perm(a[hf][2], b[hf][2], sel), __byte_perm(a[hf][3], b[hf][3], sel));
  }
  if (tid < 32) reinterpret_cast<uint32_t*>(g_wt)[(64 * ((k >> 3) & 3) + 16 * (k2 >> 3) + 2 * (k & 7) + ((k2 >> 2) & 1)) * 8 + lh * 2048 + 2 * (k2 & 3) + (k >> 10)] =
      pack2(0.5f * (__uint_as_float(hz[0] << 16) + __uint_as_float(hz[1] << 16)), 0.5f * (__uint_as_float(hz[2] << 16) - __uint_as_float(hz[3] << 16)));
}

template <class F>
__device__ __forceinline__ void fft_rows_fwd(const bf16* __restrict__ x, const bf16* __restrict__ wr, const bf16* __restrict__ wi, uint32_t tb, int it, F&& mid) {
  const int warp = threadIdx.x >> 5, lane = threadIdx.x & 31, g = lane >> 2, t = lane & 3;
  const uint32_t in = tb + warp * 4096;
  const uint32_t f0 = in + (lane >> 3) * 256 + (((lane & 7) ^ (2 * (lane >> 3))) << 4);
  const bf16* src = x + ((256 * (warp & 3) + 64 * (warp >> 2) + 128 * (it & 1) + 32 * ((it >> 4) & 1) + 8 * (it >> 5) + ((it >> 1) & 7)) * 2048 + lane * 8);
#pragma unroll
  for (int q = 0; q < 8; q++) cpa16((f0 ^ ((q >> 2) * 144)) + (q & 3) * 1024, src + q * 256);
  cpa_commit();
  Dft D;
  float2 tw[4][8];
  fft_wprep(wr, wi, it, [&]() {
    if (FMID == 0) mid();
    make_dft<true>(D, g, t);
#pragma unroll
    for (int q = 0; q < 32; q++) {
      tw[q >> 3][q & 7] = cis(fidx<true>((q >> 1) & 3, g) * fidx<false>(q >> 3, 2 * t + (q & 1)), 1024);
      if (FMID) asm volatile("" : "+f"(tw[q >> 3][q & 7].x), "+f"(tw[q >> 3][q & 7].y) :: "memory");
    }
    if (FMID == 1) mid();
  });
  if (FMID == 2) mid();
  cpa_wait<0>(); __syncwarp();
  uint32_t a[4][2][4], y[4][2][4];
#pragma unroll
  for (int q = 0; q < 8; q++) ldsm4t(a[q & 3][q >> 2], (in + lane * 128 + ((lane & 7) << 4)) ^ (q << 4));
  float o[2][8];
#pragma unroll
  for (int i = 0; i < 4; i++) {
    dft_b(D, a[i], o);
#pragma unroll
    for (int q = 0; q < 8; q++) y[q >> 1][q & 1][i] = twid(o[0][q], o[1][q], tw[i][q].x, tw[i][q].y);
  }
  __syncthreads();
  const uint32_t w0 = tb + warp * F_TP + fidx<true>(0, g) * 128 + t * 16 + ((g & 1) << 6), wz = (g & 1) ? -64 : 64;
#pragma unroll
  for (int z = 0; z < 2; z++) {
    float o2[2][8];
    dft_b(D, y[2 * z], o); dft_b(D, y[2 * z + 1], o2);
#pragma unroll
    for (int i = 0; i < 4; i++) {
      const float sg = i < 2 ? 1.f : -1.f;
      sts128(w0 + z * wz + fidx<true>(i, 0) * 128, pack2(o[0][2 * i], sg * o[1][2 * i]), pack2(o[0][2 * i + 1], sg * o[1][2 * i + 1]),
             pack2(o2[0][2 * i], sg * o2[1][2 * i]), pack2(o2[0][2 * i + 1], sg * o2[1][2 * i + 1]));
    }
  }
  __syncthreads();
  const uint32_t ra = tb + (lane & 1) * 4 * F_TP + ((lane >> 1) + 16 * (warp ^ ((warp >> 1) & 1))) * 4;
  uint4* dst = g_y + (threadIdx.x >> 1) * 256 + (lane & 1) + it * 2;
#pragma unroll
  for (int q = 0; q < 8; q++) { const uint32_t r = ra + q * 512; dst[q * 32768] = make_uint4(lds32(r), lds32(r + F_TP), lds32(r + 2 * F_TP), lds32(r + 3 * F_TP)); }
}

template <class F>
__device__ __forceinline__ void fft_cols(uint32_t sb, int cta, int ncta, F&& ready) {
  const int warp = threadIdx.x >> 5, lane = threadIdx.x & 31, g = lane >> 2, t = lane & 3;
  const uint32_t in = sb + warp * 16384 + lane * 16, tab = sb + 131072 + lane * 16;
  auto fetch_y = [&](int l) {
#pragma unroll
    for (int q = 0; q < 16; q++) cpa16(in + q * 512, g_y + (q < 8 ? l : (1024 - l) & 1023) * 256 + (q & 7) * 32 + lane);
  };
  auto fetch_w = [&](int l) {
#pragma unroll
    for (int q = 0; q < 16; q++) cpa16(in + 8192 + q * 512, g_wt + l * 512 + q * 32 + lane);
  };
  const int l0 = cta * 8 + warp, dl = ncta * 8;
  Dft D; make_dft<false>(D, g, t);
#pragma unroll
  for (int q = 2 * warp; q < 2 * warp + 2; q++) {
    const int r = fidx<false>(q & 3, g), c = fidx<false>(q >> 2, 2 * t);
    const float2 w0 = cis(r * c, 1024), w1 = cis(r * c + r, 1024), p0 = cis(r + 32 * c, 2048), p1 = cis(r + 32 * c + 32, 2048);
    sts128(tab + q * 512, __float_as_uint(w0.x), __float_as_uint(w0.y), __float_as_uint(w1.x), __float_as_uint(w1.y));
    sts128(tab + 8192 + q * 512, __float_as_uint(p0.x), __float_as_uint(p0.y), __float_as_uint(p1.x), __float_as_uint(p1.y));
  }
  if (warp == 0) {
#pragma unroll
    for (int q = 0; q < 8; q++) {
      const int v = q >> 2, b = (q >> 1) & 1, ri = q & 1;
      sts128(tab + 16384 + q * 512, D.m[b][0][ri][v], D.m[b][0][ri][v + 2], D.m[b][1][ri][v], D.m[b][1][ri][v + 2]);
    }
  }
  ready();
  fetch_y(l0); cpa_commit();
  fetch_w(l0); cpa_commit();
#pragma unroll 1
  for (int l = l0; l <= 512; l += dl) {
    uint32_t a[2][4][2][4], y[2][4][2][4];
    float o[2][2][8];
    cpa_wait<1>();
#pragma unroll
    for (int q = 0; q < 16; q++) lds128(a[q >> 3][(q >> 1) & 3][q & 1], in + q * 512);
    if (!(l & 511)) {
      const uint32_t m0 = l ? 0x80000000u : 0u;
#pragma unroll
      for (int q = 0; q < 32; q++) { a[0][q >> 3][(q >> 2) & 1][q & 3] ^= m0; a[1][q >> 3][(q >> 2) & 1][q & 3] ^= m0 ^ 0x80000000u; }
    }
    auto first = [&]() {
#pragma unroll
      for (int i = 0; i < 4; i++) {
        dft_b(D, a[0][i], o[0]); dft_b(D, a[1][i], o[1]);
#pragma unroll
        for (int r = 0; r < 4; r++) {
          const float4 w = lds128f(tab + (4 * i + r) * 512);
#pragma unroll
          for (int s = 0; s < 2; s++) {
            y[s][r][0][i] = twid(o[s][0][2 * r], o[s][1][2 * r], w.x, w.y);
            y[s][r][1][i] = twid(o[s][0][2 * r + 1], o[s][1][2 * r + 1], w.z, w.w);
          }
        }
      }
    };
    first();
    if (l + dl <= 512) fetch_y(l + dl);
    cpa_commit();
    cpa_wait<1>();
#pragma unroll
    for (int zv = 0; zv < 4; zv++) {
      const int z = zv >> 1, v = zv & 1;
      uint32_t m[2][2][4];
#pragma unroll
      for (int q = 0; q < 4; q++) lds128(m[q >> 1][q & 1], tab + 16384 + (4 * v + q) * 512);
      dft_a(m, y[0][2 * z], y[0][2 * z + 1], o[0]); dft_a(m, y[1][2 * z], y[1][2 * z + 1], o[1]);
#pragma unroll
      for (int q = 0; q < 4; q++) {
        const int i = 2 * z + (q & 1), c = v + (q & 2);
        uint32_t w[4]; lds128(w, in + 8192 + (4 * i + c) * 512);
        const float4 ph = lds128f(tab + 8192 + (4 * c + i) * 512);
#pragma unroll
        for (int b = 0; b < 2; b++) {
          const float cs = b ? ph.z : ph.x, sn = b ? ph.w : ph.y;
          const float r1 = __uint_as_float(w[2 * b] << 16), i1 = __uint_as_float(w[2 * b] & 0xFFFF0000u);
          const float r2 = __uint_as_float(w[2 * b + 1] << 16), i2 = __uint_as_float(w[2 * b + 1] & 0xFFFF0000u);
          const float Sr = r1 + r2, Si = i1 + i2, Dr = r1 - r2, Di = i1 - i2;
          const float ar = fmaf(-Dr, sn, Sr), ai = fmaf(-Di, sn, Si), dr = fmaf(Dr, sn, Sr), di = fmaf(Di, sn, Si), br = -Di * cs, bi = Dr * cs;
          const float Ar = o[0][0][2 * q + b], Ai = o[0][1][2 * q + b], Br = o[1][0][2 * q + b], Bi = o[1][1][2 * q + b];
          a[0][i][b][c] = pack2(fmaf(ar, Ai, fmaf(ai, Ar, fmaf(br, Bi, bi * Br))), fmaf(ar, Ar, fmaf(-ai, Ai, fmaf(br, Br, -bi * Bi))));
          a[1][i][b][c] = pack2(fmaf(dr, Bi, fmaf(di, Br, fmaf(-br, Ai, -bi * Ar))), fmaf(dr, Br, fmaf(-di, Bi, fmaf(-br, Ar, bi * Ai))));
        }
      }
    }
    if (l + dl <= 512) fetch_w(l + dl);
    cpa_commit();
    first();
#pragma unroll
    for (int s = 0; s < 2; s++) {
      uint4* dst = g_y + (s ? (1024 - l) & 1023 : l) * 256 + lane;
      const float sg = s ? -1.f : 1.f;
#pragma unroll
      for (int i = 0; i < 4; i++) {
        dft_b(D, y[s][i], o[0]);
#pragma unroll
        for (int b = 0; b < 2; b++)
          dst[(2 * i + b) * 32] = make_uint4(pack2(sg * o[0][0][b], o[0][1][b]), pack2(sg * o[0][0][2 + b], o[0][1][2 + b]),
                                             pack2(sg * o[0][0][4 + b], o[0][1][4 + b]), pack2(sg * o[0][0][6 + b], o[0][1][6 + b]));
      }
    }
  }
}

template <class F>
__device__ __forceinline__ void fft_rows_inv(const CUtensorMap* om, uint32_t sb, int cta, int ncta, F&& ready) {
  const int warp = threadIdx.x >> 5, lane = threadIdx.x & 31, g = lane >> 2, t = lane & 3, wg = warp >> 2, w4 = warp & 3;
  const uint32_t tb = sb + 32768 + wg * 2 * F_TSZ;
  const uint4* src = g_y + pin((256 * ((lane >> 1) & 3) + 64 * (lane >> 3) + 8 * w4) * 256 + (lane & 1));
  const uint32_t wa = pin(tb + (lane & 1) * 4 * F_TP + w4 * 1024 + (lane >> 1) * 4);
  uint4 pf[8];
  auto fetch = [&](int it, int hf) {
#pragma unroll
    for (int q = 0; q < 8; q++) pf[q] = __ldcg(src + (it * 2 + hf * 8192) + q * 256);
  };
  auto put = [&](uint32_t off) {
#pragma unroll
    for (int q = 0; q < 8; q++) {
      sts32(wa + off + q * 64, pf[q].x); sts32(wa + off + q * 64 + F_TP, pf[q].y);
      sts32(wa + off + q * 64 + 2 * F_TP, pf[q].z); sts32(wa + off + q * 64 + 3 * F_TP, pf[q].w);
    }
  };
  const int it0 = 2 * cta + wg;
  Dft D; make_dft<false>(D, g, t);
  float2 tw[4][8];
#pragma unroll
  for (int q = 0; q < 32; q++) {
    tw[q >> 3][q & 7] = cis(fidx<false>((q >> 1) & 3, g) * fidx<false>(q >> 3, 2 * t + (q & 1)), 1024);
    tw[q >> 3][q & 7].x *= 1.f / 2097152.f; tw[q >> 3][q & 7].y *= 1.f / 2097152.f;
    asm volatile("" : "+f"(tw[q >> 3][q & 7].x), "+f"(tw[q >> 3][q & 7].y) :: "memory");
  }
  ready();
  fetch(it0, 0); put(0); fetch(it0, 1); put(512);
  const uint32_t la = pin(tb + w4 * F_TP + lane * 16), ob = uni(sb + warp * 4096);
  const uint32_t oa = pin(ob + (lane >> 1) * 128 + (((4 * (lane & 1)) ^ ((lane >> 1) & 7)) << 4));
#pragma unroll 1
  for (int n = 0;; n++) {
    const int it = it0 + (n >> 1) * 2 * ncta, hf = n & 1, buf = (n >> 1) & 1;
    if (it >= 128) break;
    if (!hf) bar_sync(1 + wg, 128);
    uint32_t a[4][2][4], y[4][2][4];
#pragma unroll
    for (int q = 0; q < 8; q++) lds128(a[q >> 1][q & 1], la + buf * F_TSZ + hf * 4 * F_TP + q * 512);
    fetch(min(it + 2 * ncta, 127), hf);
    float o[2][8];
#pragma unroll
    for (int i = 0; i < 4; i++) {
      dft_b(D, a[i], o);
#pragma unroll
      for (int q = 0; q < 8; q++) y[q >> 1][q & 1][i] = twid(o[0][q], o[1][q], tw[i][q].x, tw[i][q].y);
    }
    if (lane == 0) asm volatile("cp.async.bulk.wait_group.read 0;" ::: "memory");
    __syncwarp();
#pragma unroll
    for (int c = 0; c < 4; c++) {
      dft_b(D, y[c], o);
#pragma unroll
      for (int ri = 0; ri < 2; ri++)
        stsm4((oa ^ (c << 4)) + (1 - ri) * 2048, pack2(o[ri][0], o[ri][1]), pack2(o[ri][2], o[ri][3]), pack2(o[ri][4], o[ri][5]), pack2(o[ri][6], o[ri][7]));
    }
    fence_async();
    __syncwarp();
    if (lane == 0) {
      const int m = 256 * w4 + 32 * ((it >> 1) & 7) + 8 * (it >> 5) + 4 * (it & 1) + 2 * hf + ((it >> 4) & 1);
      asm volatile("cp.async.bulk.tensor.3d.global.shared::cta.bulk_group [%0, {0, 0, %2}], [%1];" :: "l"(om), "r"(ob), "r"(2 * m) : "memory");
      asm volatile("cp.async.bulk.commit_group;" ::: "memory");
    }
    put((buf ^ 1) * F_TSZ + hf * 512);
  }
  if (lane == 0) asm volatile("cp.async.bulk.wait_group 0;" ::: "memory");
}
__device__ __forceinline__ void grid_arrive(unsigned* ctr) {
  __syncthreads();
  if (threadIdx.x == 0) { __threadfence(); atomicAdd(ctr, 1u); }
}
__device__ __forceinline__ void grid_wait(unsigned* ctr, unsigned n) {
  if (threadIdx.x == 224) {
    int it = 0;
    while (*reinterpret_cast<volatile unsigned*>(ctr) < n) { __nanosleep(100); if (++it > SPIN_LIMIT) { g_err = 3; break; } }
    __threadfence();
  }
  __syncthreads();
}

struct RecMaps { CUtensorMap wq, wk, wv, wo, x, k, q, v, fo; };
#define NSW 16
#define EXP 0
#define NPB 3
#define NPB0 3
#define NPC 0
#define WOP 2
#define HOME 7
#define DL0 14
#define PD1 4
#define NE4 6
#define NE6 0
#define NA4 14
#define NA6 18
#define NB1 24
#define TQL 7
#define NQ 16
#define TQP (NQ - 1)
#define OXPOS 4
#define KVPOS 2
#define NK0 0
#define FLPOS 1
#define XWPOS 10
#define FSPOS 28
#define RL0 4
#define RLS 6
#define RLB 4
#define VL0 3
#define RI 9
#define RJ 8
#define NPRE 22
#define PFD 4
#define PD0 4
#define VB NV0
#define NPA 0
#define N1 16
#define DL1 16
#define PACE 0
#define RE0 0
#define RE1 0
#define RP1 23
#define UNP 1
#define X2 2
#define X3 2
#define SPOS 2
#ifndef NV0
#define NV0 4
#endif
#define TGP 3
#define FENP 0
#define LW0 8
#define X1 4
#define X0 4
constexpr int R_WO = 0, R_X = 65536, R_MEM = 131072, R_WC = 147456, R_RED = R_WC + NSW * 2048, R_O = R_RED, R_S = R_O + 2048, R_P = R_S + 3072, R_STAGE = R_P + 2048,
              R_K = R_STAGE + 8192, R_Q = R_K + 8192, R_V = R_Q + 2048, R_ID = R_V + 16384, R_T = R_ID + 512, R_DST = R_T + 512, R_RD = R_DST + 2048, R_BAR = R_RD + 2048, R_TS = R_BAR + 128,
              R_TOTAL = R_TS;
#define TS(i)
#define LOG(i, v)
constexpr int B_KV = R_BAR, B_W = R_BAR + 8, B_X = R_BAR + 80, B_PK = R_BAR + 24, B_C = R_BAR + 32, B_B = R_BAR + 40, B_DUE = R_BAR + 48, B_ONE = R_BAR + 64;
#define DLY_A 150
#define DLY_V 150
#define DLY_C 200
#define DLY_L 90
#define NS_B 1120
#define NS_C 1728
#define NS_P 2624
#define NS_V 128
#define NS_F 896
#define NS_K 128
#define NS_M 32
#define NS_X 128
#define MG_Z 0x00010206
#define MG_Y 0x00010512
#define NS_PEN 1024
__device__ __forceinline__ float rcp(float x) { float r; asm("rcp.approx.ftz.f32 %0, %1;" : "=f"(r) : "f"(x)); return r; }
__device__ __forceinline__ uint32_t movm(uint32_t a) { uint32_t d; asm volatile("movmatrix.sync.aligned.m8n8.trans.b16 %0, %1;" : "=r"(d) : "r"(a)); return d; }
__device__ __forceinline__ uint32_t hadd2(uint32_t a, uint32_t b) { uint32_t d; asm("add.rn.bf16x2 %0, %1, %2;" : "=r"(d) : "r"(a), "r"(b)); return d; }
__device__ __forceinline__ void mma_a(float (&d)[4], const uint32_t (&a)[4], uint32_t b0, uint32_t b1) { mma16816(d, a[0], a[1], a[2], a[3], b0, b1); }
__device__ __forceinline__ bool elect() {
  uint32_t p; asm volatile("{.reg .pred p; elect.sync _|p, 0xffffffff; selp.u32 %0, 1, 0, p;}" : "=r"(p)); return p; }
__device__ __forceinline__ void tma3d(uint32_t dst, const CUtensorMap* m, int c1, int c2, uint32_t bar) {
  asm volatile("cp.async.bulk.tensor.3d.shared::cluster.global.mbarrier::complete_tx::bytes [%0], [%1, {0, %3, %4}], [%2];"
    :: "r"(dst), "l"(m), "r"(bar), "r"(c1), "r"(c2) : "memory"); }
__device__ __forceinline__ void tma4d(uint32_t dst, const CUtensorMap* m, int c1, int c2, uint32_t bar) {
  asm volatile("cp.async.bulk.tensor.4d.shared::cluster.global.mbarrier::complete_tx::bytes [%0], [%1, {0, %3, %4, 0}], [%2];"
    :: "r"(dst), "l"(m), "r"(bar), "r"(c1), "r"(c2) : "memory"); }
template <int OFF, int ACC>
__device__ __forceinline__ void wg_rs32(float (&d)[16], const uint32_t (&a)[4], uint32_t db) {
  if (ACC)
    asm volatile("{.reg .b64 db; .reg .b32 lo; add.u32 lo, %20, %21; mov.b64 db, {lo, 0x40000040};\n"
      "wgmma.mma_async.sync.aligned.m64n32k16.f32.bf16.bf16 {%0,%1,%2,%3,%4,%5,%6,%7,%8,%9,%10,%11,%12,%13,%14,%15}, {%16,%17,%18,%19}, db, 1, 1, 1, 0;}"
      : "+f"(d[0]), "+f"(d[1]), "+f"(d[2]), "+f"(d[3]), "+f"(d[4]), "+f"(d[5]), "+f"(d[6]), "+f"(d[7]), "+f"(d[8]), "+f"(d[9]), "+f"(d[10]), "+f"(d[11]), "+f"(d[12]), "+f"(d[13]), "+f"(d[14]), "+f"(d[15])
      : "r"(a[0]), "r"(a[1]), "r"(a[2]), "r"(a[3]), "r"(db), "n"(OFF));
  else
    asm volatile("{.reg .b64 db; .reg .b32 lo; add.u32 lo, %20, %21; mov.b64 db, {lo, 0x40000040};\n"
      "wgmma.mma_async.sync.aligned.m64n32k16.f32.bf16.bf16 {%0,%1,%2,%3,%4,%5,%6,%7,%8,%9,%10,%11,%12,%13,%14,%15}, {%16,%17,%18,%19}, db, 0, 1, 1, 0;}"
      : "=f"(d[0]), "=f"(d[1]), "=f"(d[2]), "=f"(d[3]), "=f"(d[4]), "=f"(d[5]), "=f"(d[6]), "=f"(d[7]), "=f"(d[8]), "=f"(d[9]), "=f"(d[10]), "=f"(d[11]), "=f"(d[12]), "=f"(d[13]), "=f"(d[14]), "=f"(d[15])
      : "r"(a[0]), "r"(a[1]), "r"(a[2]), "r"(a[3]), "r"(db), "n"(OFF));
}
template <int I> using IC = std::integral_constant<int, I>;
template <int I, int N, class F> __device__ __forceinline__ void sfor(F&& f) {
  if constexpr (I < N) { f(std::integral_constant<int, I>{}); sfor<I + 1, N>(f); }
}
__device__ __forceinline__ void keep(float (&d)[16]) {
  asm volatile("" : "+f"(d[0]), "+f"(d[1]), "+f"(d[2]), "+f"(d[3]), "+f"(d[4]), "+f"(d[5]), "+f"(d[6]), "+f"(d[7]),
      "+f"(d[8]), "+f"(d[9]), "+f"(d[10]), "+f"(d[11]), "+f"(d[12]), "+f"(d[13]), "+f"(d[14]), "+f"(d[15]) :: "memory");
}

template <int N, int S2 = 1024> __device__ __forceinline__ void ldx(uint32_t (&v)[N][4], const uint8_t* p) {
#pragma unroll
  for (int k = 0; k < 2 * N; k++) {
    const int i = k;
    asm volatile("ld.relaxed.gpu.global.v2.b32 {%0,%1}, [%2];" : "=r"(v[i >> 1][2 * (i & 1)]), "=r"(v[i >> 1][2 * (i & 1) + 1]) : "l"(p + (i & 3) * 256 + (i >> 2) * S2) : "memory");
  }
}
__device__ __forceinline__ uint32_t dif2(uint32_t a, uint32_t b, uint32_t tag) { uint32_t r; asm("lop3.b32 %0, %1, %2, %3, 0x7e;" : "=r"(r) : "r"(a), "r"(b), "r"(tag)); return r; }
__device__ __forceinline__ uint32_t dif2v(uint32_t a, uint32_t b, uint32_t tag) { uint32_t r; asm volatile("lop3.b32 %0, %1, %2, %3, 0x7e;" : "=r"(r) : "r"(a), "r"(b), "r"(tag)); return r; }
__device__ __forceinline__ uint32_t or3(uint32_t a, uint32_t b, uint32_t c) { uint32_t r; asm("lop3.b32 %0, %1, %2, %3, 0xfe;" : "=r"(r) : "r"(a), "r"(b), "r"(c)); return r; }
__device__ __forceinline__ uint32_t after(uint32_t x, float f, uint32_t z) { uint32_t r; asm("lop3.b32 %0, %1, %2, %3, 0xea;" : "=r"(r) : "r"(__float_as_uint(f)), "r"(z), "r"(x)); return r; }
__device__ __forceinline__ bool any_bit(uint32_t a, uint32_t b, uint32_t m) {
  uint32_t r; asm("lop3.b32 %0, %1, %2, %3, 0xa8;" : "=r"(r) : "r"(a), "r"(b), "r"(m)); return __any_sync(0xffffffffu, r); }
template <int W, int N> __device__ __forceinline__ bool stale(const uint32_t (&v)[N][4], uint32_t tag) {
  uint32_t x = dif2(v[0][0], v[0][2], tag);
  if (N == 4) x = or3(x, dif2(v[1][0], v[1][2], tag), dif2(v[2 % N][0], v[2 % N][2], tag));
  return any_bit(x, dif2(v[N - 1][0], v[N - 1][2], tag), 1);
}
template <int W, int N, int S2 = 1024> __device__ __forceinline__ void retry(uint32_t (&v)[N][4], const uint8_t* p, uint32_t tag, int& it) {
#pragma unroll 1
  do { ldx<N, S2>(v, p); it += INC_A; } while (stale<W>(v, tag) && it < SPIN_LIMIT);
}
__device__ __forceinline__ void mma_h(float (&d)[4], const uint32_t (&a)[4], const uint32_t (&b)[4], int hf) { mma16816(d, a[0], a[1], a[2], a[3], b[2 * hf], b[2 * hf + 1]); }
__device__ __forceinline__ void sts128(uint32_t a, const uint32_t (&r)[4]) { sts128(a, r[0], r[1], r[2], r[3]); }
__device__ __forceinline__ void sts128f(uint32_t a, const float* r) { sts128(a, __float_as_uint(r[0]), __float_as_uint(r[1]), __float_as_uint(r[2]), __float_as_uint(r[3])); }
__device__ __forceinline__ void mbar_spin(uint32_t bar, uint32_t par, int& it) {
  asm volatile("{.reg .pred p; .reg .b32 par; mov.b32 par, %2;\nLOOP: mbarrier.try_wait.parity.shared::cta.b64 p, [%1], par; @p bra.uni DONE;\n"
               "add.s32 %0, %0, 1; setp.le.s32 p, %0, %3; @p bra.uni LOOP;\nDONE: }" : "+r"(it) : "r"(bar), "r"(par), "n"(SPIN_LIMIT) : "memory"); }
__device__ __forceinline__ void warp_arrive(uint32_t bar) {
  __syncwarp(); asm volatile("{.reg .pred p; elect.sync _|p, 0xffffffff; @p mbarrier.arrive.shared::cta.b64 _, [%0];}" :: "r"(bar) : "memory"); }
__device__ __forceinline__ void delay_until(unsigned t) {
  asm volatile("{.reg .pred p; .reg .b64 c; .reg .b32 lo, hi;\nLOOP: mov.u64 c, %%clock64; mov.b64 {lo, hi}, c; sub.s32 lo, lo, %0; setp.lt.s32 p, lo, 0; @p bra.uni LOOP;}" :: "r"(t) : "memory"); }
__device__ __forceinline__ void cut(int it) { asm volatile("{.reg .pred p; setp.lt.s32 p, %0, 0;\nL: @p st.volatile.shared.u32 [%0], %0; @p bra.uni L;}" :: "r"(it) : "memory"); }
__device__ __forceinline__ void zero(float (&c)[4][4]) {
#pragma unroll
  for (int i = 0; i < 4; i++) c[i][0] = c[i][1] = c[i][2] = c[i][3] = 0.f;
}

__device__ __forceinline__ void sched() { asm volatile("griddepcontrol.launch_dependents;" ::: "memory"); }
__device__ __forceinline__ const uint8_t* pinp(const uint8_t* p) { return reinterpret_cast<const uint8_t*>(__shfl_xor_sync(0xffffffffu, reinterpret_cast<unsigned long long>(p), 0)); }
__device__ __forceinline__ uint32_t bar_or(int id, uint32_t x) {
  uint32_t r; asm volatile("{.reg .pred p, q; setp.ne.u32 p, %2, 0; bar.red.or.pred q, %1, 256, p; selp.u32 %0, 1, 0, q;}" : "=r"(r) : "r"(id), "r"(x) : "memory"); return r; }
__device__ __forceinline__ void bar_sync_unless(int id, uint32_t x) { asm volatile("{.reg .pred p; setp.eq.u32 p, %1, 0; @p bar.sync %0, 256;}" :: "r"(id), "r"((uint32_t)x) : "memory"); }
__device__ __forceinline__ void bar_arrive_unless(int id, uint32_t x) { asm volatile("{.reg .pred p; setp.eq.u32 p, %1, 0; @p bar.arrive %0, 256;}" :: "r"(id), "r"((uint32_t)x) : "memory"); }
__device__ __forceinline__ void stsm2t(uint32_t a, uint32_t r0, uint32_t r1, uint32_t x) {
  asm volatile("{.reg .pred p; setp.eq.u32 p, %3, 0; @p stmatrix.sync.aligned.m8n8.x2.trans.shared.b16 [%0], {%1,%2};}" :: "r"(a), "r"(r0), "r"(r1), "r"((uint32_t)x) : "memory"); }
__device__ __forceinline__ uint32_t or_and(uint32_t a, uint32_t b, uint32_t m) { uint32_t r; asm("lop3.b32 %0, %1, %2, %3, 0xa8;" : "=r"(r) : "r"(a), "r"(b), "r"(m)); return r; }
#define rare(x) __builtin_expect(!!(x), 0)
__device__ __forceinline__ uint32_t gtime() { unsigned long long g; asm volatile("mov.u64 %0, %%globaltimer;" : "=l"(g) :: "memory"); return (uint32_t)g; }
__device__ __forceinline__ void wait_time(uint32_t t) {
  asm volatile("{.reg .pred p; .reg .b32 g; .reg .b64 c;\nLOOP: mov.u64 c, %%globaltimer; cvt.u32.u64 g, c; sub.s32 g, %0, g; setp.lt.u32 p, g, 16384; @p bra.uni LOOP;}" :: "r"(t - 1) : "memory"); }
__device__ __forceinline__ uint32_t ldx32(const void* p) { uint32_t v; asm volatile("ld.relaxed.gpu.global.b32 %0, [%1];" : "=r"(v) : "l"(p) : "memory"); return v; }
__device__ __forceinline__ void stx32(const void* p, uint32_t v) { asm volatile("st.relaxed.gpu.global.b32 [%0], %1;" :: "l"(p), "r"(v) : "memory"); }

__global__ void __launch_bounds__(256, 1)
rec_kernel(const __grid_constant__ RecMaps maps, const bf16* __restrict__ xin, const bf16* __restrict__ mem0, Xchg* const gx,
           const bf16* __restrict__ fx, const bf16* __restrict__ wr, const bf16* __restrict__ wi) {
  extern __shared__ __align__(1024) uint8_t smem_raw[];
  const uint32_t sb = smem_u32(smem_raw);
  int role = blockIdx.x;
  {
    uint32_t smid, nsm; asm volatile("mov.u32 %0, %%smid;" : "=r"(smid)); asm volatile("mov.u32 %0, %%nsmid;" : "=r"(nsm));
    const int p = smid >> 1, u = p - 32;
    if (nsm == gridDim.x)
      role = (smid & 1) + (p < 32 ? 4 * ((p & 7) + 8 * (p >> 4)) + 2 * ((p >> 3) & 1) : p < 60 ? 4 * (16 + u % 7 + 7 * (u / 14)) + 2 * ((u / 7) & 1)
                         : p < 62 ? 2 * p + 8 : 2 * p - 4);
    role = uni(role);
  }
  if (role >= 128) {
    fft_cols(sb, role - 128, 4, [&]() { grid_wait(&gx->ctr[33], 128); });
    __threadfence(); __syncwarp();
    if ((threadIdx.x & 31) == 0) atomicAdd(&gx->ctr[32], 1u);
    __syncwarp();
    fft_rows_inv(&maps.fo, sb, role - 128, 4, [&]() { grid_wait(&gx->ctr[32], 32); });
    return;
  }
  const int tid = threadIdx.x, warp = uni(tid >> 5), lane = tid & 31, wg = warp >> 2, w4 = warp & 3, g = lane >> 2, t = lane & 3;
  const int h = role >> 2, j = role & 3, jh = j & 1;
  uint32_t w[48][4];
  float aq[16], av[16];
  int it = 0;

#define PT(k)
  auto pf_wo = [&]() {
    for (int i = 0; i < 4; i++)
      asm volatile("cp.async.bulk.prefetch.tensor.2d.L2.global [%0, {%1, %2}];" :: "l"(&maps.wo), "r"(256 * j + 64 * i), "r"(h * DH) : "memory");
  };
  fft_rows_fwd(fx, wr, wi, sb + R_MEM + 49152, role, [&]() {
    if (tid == 224) {
      mbar_init(sb + B_KV, 1); mbar_init(sb + B_W, 1); mbar_init(sb + B_X, 1); mbar_init(sb + B_X + 8, 1); mbar_init(sb + B_X + 16, 1); mbar_init(sb + B_X + 24, 1); mbar_init(sb + B_C, 4); mbar_init(sb + B_PK, 4); mbar_init(sb + B_B, 1);
      asm volatile("fence.mbarrier_init.release.cluster;" ::: "memory");
      mbar_expect_tx(sb + B_W, 3 * 65536);
      for (int i = 0; i < 4; i++) {
        tma2d(sb + R_X + i * 16384, &maps.wq, h * DH + 32 * j, i * 256, sb + B_W);
        if (i < 3) tma2d(sb + R_MEM + i * 16384, &maps.wk, h * DH + 32 * j, i * 256, sb + B_W);
        else asm volatile("cp.async.bulk.prefetch.tensor.2d.L2.global [%0, {%1, %2}];" :: "l"(&maps.wk), "r"(h * DH + 32 * j), "r"(768) : "memory");
      }
      for (int i = 0; i < 2; i++) tma2d(sb + R_WO + i * 32768, &maps.wv, h * DH + 64 * (j >> 1), jh * 512 + i * 256, sb + B_W);
      if (PFD) asm volatile("cp.async.bulk.prefetch.L2.global [%0], 2048;" :: "l"(xin + role * DM) : "memory");
      else for (int i = 0; i < 4; i++) asm volatile("cp.async.bulk.prefetch.L2.global [%0], 8192;" :: "l"(xin + role * 16384 + i * 4096) : "memory");
      if (WOP == 0) pf_wo();
    }
    __syncwarp();
  });
  if (tid < 16) sts32(sb + R_T + tid * 4, ~0u);
  fence_async();
  PT(0);
  grid_arrive(&gx->ctr[33]);
  PT(1);
  if (tid == 224) { tma2d(sb + R_MEM + 49152, &maps.wk, h * DH + 32 * j, 768, sb + B_W); if (WOP == 1) pf_wo(); }
  __syncwarp();
  uint8_t* const xb = reinterpret_cast<uint8_t*>(gx);
  auto probe_at = [&](int n) { return xb + (n ? offsetof(Xchg, C) + w4 * 8192 + role * 32 : offsetof(Xchg, B) + role * 8192 + warp * 128); };
  if (lane < 8) stx128(probe_at(lane >> 2) + (lane & 2) * 2048 + (lane & 1) * 16, 0, 0, 0, 0);
  uint32_t m0[4][4];
#pragma unroll
  for (int i = 0; i < 16; i++) m0[i >> 2][i & 3] = ldnc32(mem0 + g * DM + 128 * warp + 8 * i + 2 * t);
  mbar_spin(sb + B_W, 0, it);
  PT(2);
  const int lrow = (lane & 7) + ((lane >> 4) << 3), lhi = (lane >> 3) & 1;
  const int kq = wg ? 3 - 3 * jh : 3 * jh;
  const uint32_t LW = lrow * 128 + ((lhi ^ (lane & 7)) << 4);
  {
    const int chunk = w4 < 2 ? w4 + 2 * lhi : 2 * (w4 & 1) + lhi;
    uint32_t a = sb + (w4 < 2 ? R_X : R_MEM) + kq * 16384 + lrow * 64 + ((chunk ^ ((lrow >> 1) & 3)) << 4);
#pragma unroll
    for (int i = 0; i < 16; i++) ldsm4t(w[i], a + i * 1024);
    const uint32_t st = wg ? 1024 : 2048, av0 = sb + R_WO + (LW ^ (w4 << 5));
    const uint32_t a1 = wg ? a + (2 * jh - 1) * 16384 : av0 + jh * 32768, a2 = wg ? a + (2 * jh - 1) * 32768 : av0 + (1 - jh) * 32768;
#pragma unroll
    for (int i = 0; i < 16; i++) { ldsm4t(w[16 + i], a1 + i * st); ldsm4t(w[32 + i], a2 + i * st); }
  }
  uint32_t L16 = pin(lane * 16);
  const uint32_t uW = uni(sb + w4 * 512), uWo = uni(sb + R_WO + w4 * 16384), uMem = uni(sb + R_MEM + kq * 4096);
  const uint32_t dX = uni(((sb + R_X + kq * 16384) >> 4) | 0x10000u);
  auto load_wo = [&](uint32_t (&d)[32][4], int i0, int i1) {
#pragma unroll
    for (int i = i0; i < i1; i++) lds128(d[i], uWo + L16 + (i & 1) * 512 + (i >> 4) * 1024 + (i & 14) * 1024);
  };
  auto issue_x = [&](int n, int k) {
    const uint32_t bar = sb + B_X + 8 * k, q = k ^ (3 - 3 * jh);
    mbar_expect_tx(bar, 16384); tma3d(sb + R_X + q * 16384, &maps.x, n * SEG, 4 * q, bar);
  };
  auto store_stage = [&](int n) {
    asm volatile("cp.async.bulk.global.shared::cta.bulk_group [%0], [%1], 8192; cp.async.bulk.commit_group;"
                 :: "l"(g_kqv[n & 3][role]), "r"(sb + R_STAGE) : "memory");
  };
  auto issue_kqv = [&](int n) {
    const int p = (n & 3) * 128 + 4 * h;
    mbar_expect_tx(sb + B_KV, 26624);
    tma3d(sb + R_K, &maps.k, 0, p, sb + B_KV); tma3d(sb + R_Q, &maps.q, 8 + 2 * j, p, sb + B_KV); tma3d(sb + R_V, &maps.v, 16, p, sb + B_KV);
  };
  auto fetch4k = [&](uint32_t dst, uint32_t off, uint32_t bar, uint32_t t) {
    asm volatile("{.reg .pred p, q; .reg .b32 g; .reg .b64 c; elect.sync _|q, 0xffffffff; @q mbarrier.arrive.expect_tx.shared::cta.b64 _, [%2], 4096;\n"
                 "LOOP: mov.u64 c, %%globaltimer; cvt.u32.u64 g, c; sub.s32 g, %3, g; setp.lt.u32 p, g, 16384; @p bra.uni LOOP;\n"
                 "@q cp.async.bulk.shared::cluster.global.mbarrier::complete_tx::bytes [%0], [%1], 4096, [%2];}" :: "r"(dst), "l"(xb + off), "r"(bar), "r"(t - 1) : "memory");
  };
  uint32_t uS;
  auto my_b = [&]() { return offsetof(Xchg, B) + role * 8192 + ((uS + ((uint32_t)it >> 31)) & 1) * 4096; };
  auto issue_c = [&](uint32_t t) { fetch4k(sb + R_MEM + w4 * 4096, offsetof(Xchg, C) + w4 * 8192 + ((uS + ((uint32_t)it >> 31)) & 4096), sb + B_C, t); };
  auto wait_x = [&](int n, int i) { if (!(EXP & 1) || n < 2) mbar_spin(sb + B_X + 8 * i, n & 1, it); };
#define PACED(d0) uint32_t dz = d0; const uint32_t z = (uint32_t)it >> 31; auto pace = [&]() { for (int k = 0; k < PACE; k++) { if (k & 1) asm("add.u32 %0, %0, %1;" : "+r"(dz) : "r"(z)); else asm("xor.b32 %0, %0, %1;" : "+r"(dz) : "r"(z)); } };
  auto project_v = [&](auto I0, auto I1, auto&& mid) {
    PACED(decltype(I0)::value < 16 ? dX : dX ^ 1024);
    wg_fence();
    sfor<decltype(I0)::value, decltype(I1)::value>([&](auto I) {
      constexpr int i = decltype(I)::value;
      mid(i);
      if (i == 16 && decltype(I0)::value < 16) dz ^= 1024;
      wg_rs32<((i >> 2) & 3) * 256 + (i & 3) * 2, (i > 0)>(av, w[16 + i], dz);
      pace();
    });
    wg_commit();
  };
  auto project_qk = [&](auto I0, auto I1, auto first, auto&& mid) {
    PACED((dX ^ (decltype(I0)::value >> 4 << 10)) + ((uint32_t)it >> 31));
    wg_fence();
    sfor<decltype(I0)::value, decltype(I1)::value>([&](auto I) {
      constexpr int i = decltype(I)::value;
      mid(i);
      wg_rs32<((i >> 2) & 3) * 256 + (i & 3) * 2, !decltype(first)::value || i != decltype(I0)::value>(aq, w[i], dz);
      pace();
    });
    wg_commit();
  };
  const uint32_t uP = uni(sb + R_X + 3 * jh * 16384 + w4 * 512);
  auto park = [&]() {
    bar_sync(1, 128);
#pragma unroll
    for (int i = 0; i < 4; i++) sts128f(uP + L16 + i * 2048, aq + 4 * i);
    warp_arrive(sb + B_PK);
  };
  auto unpark = [&]() {
#pragma unroll
    for (int i = 0; i < 4; i++) {
      const float4 p = lds128f(uP + L16 + i * 2048);
      av[4 * i] = p.x; av[4 * i + 1] = p.y; av[4 * i + 2] = p.z; av[4 * i + 3] = p.w;
    }
  };
  auto fin_qk = [&]() {
#pragma unroll
    for (int i = 0; i < 16; i++) aq[i] += av[i];
    const uint32_t a = sb + R_STAGE + (w4 < 2 ? 2048 + w4 * 128 : (w4 & 1) * 256) + (L16 & 112) + (L16 >> 7) * 512;
    stsm4t(a, pack2(aq[0], aq[1]), pack2(aq[4], aq[5]), pack2(aq[8], aq[9]), pack2(aq[12], aq[13]));
    stsm4t(a + (w4 < 2 ? 256 : 128), pack2(aq[2], aq[3]), pack2(aq[6], aq[7]), pack2(aq[10], aq[11]), pack2(aq[14], aq[15]));
  };
  auto fin_v = [&]() {
#pragma unroll
    for (int a = 0; a < 2; a++)
      sts128(sb + R_STAGE + 4096 + w4 * 1024 + a * 512 + L16, pack2(av[8 * a], av[8 * a + 1]), pack2(av[8 * a + 2], av[8 * a + 3]),
             pack2(av[8 * a + 4], av[8 * a + 5]), pack2(av[8 * a + 6], av[8 * a + 7]));
  };
  __syncthreads();
  if (tid == 224) {
#pragma unroll 1
    for (int i = 0; i < 4; i++) issue_x(0, i);
    mbar_expect_tx(sb + B_W, 65536);
    for (int i = 0; i < 4; i++) tma2d(sb + R_WO + i * 16384, &maps.wo, 256 * j + 64 * i, h * DH, sb + B_W);
  }
  __syncwarp();
  if (wg) {
#pragma unroll
    for (int i = 0; i < NSW; i++) sts128(uW + R_WC + L16 + i * 2048, w[i]);
  }
#pragma unroll
  for (int i = 0; i < 4; i++) sts128(sb + R_MEM + warp * 2048 + i * 512 + (g >> 1) * 128 + t * 32 + (g & 1) * 16, m0[i]);
  auto probe = [&](int n, int cnt) {
    if (lane == 0) {
#pragma unroll 1
      for (int i = role >> 7; i < cnt; i++) {
        const int k = (i ^ wg) & 1;
        const unsigned t0 = clk();
        uint32_t v; asm volatile("atom.relaxed.gpu.global.exch.b32 %0, [%1], 0;" : "=r"(v) : "l"(probe_at(n) + k * 4096) : "memory");
        if (v == 0) asm volatile("red.shared.min.u32 [%0], %1;" :: "r"(sb + R_T + (n ? w4 * 8 : 32) + k * 4), "r"(clk() - t0) : "memory");
      }
    }
    __syncwarp();
  };
#pragma unroll 1
  for (int n = 0; n < 2; n++) {
    probe(0, n ? NPB : NPB0);
    PT(3 + 3 * n);
    wait_x(n, 2);
    PT(4 + 3 * n);
    if (wg == 0) {
      wait_x(n, 3);
      project_qk(IC<0>{}, IC<16>{}, IC<1>{}, [](int) {});
      project_v(IC<0>{}, IC<32>{}, [](int) {});
      if (tid == 96 && n == 1) {
        asm volatile("cp.async.bulk.wait_group 0;" ::: "memory");
        __threadfence(); atomicAdd(&gx->ctr[h], 1u);
      }
      __syncwarp();
      wg_wait<0>(); keep(aq); keep(av);
      park();
      fin_v();
      fence_async();
    } else {
      wait_x(n, 0); wait_x(n, 1);
      project_qk(IC<32>{}, IC<48>{}, IC<1>{}, [](int) {});
      project_qk(IC<16>{}, IC<32>{}, IC<0>{}, [](int) {});
      project_qk(IC<0>{}, IC<16>{}, IC<0>{}, [](int) {});
      mbar_spin(sb + B_PK, n, it);
      unpark();
      wg_wait<0>(); keep(aq);
      fin_qk();
      fence_async();
    }
    __syncthreads();
    if (tid == 0 && n) stx32(&gx->S[role], 1 + (HOME & 2 && lds32(sb + R_T + 36) < lds32(sb + R_T + 32)));
    PT(5 + 3 * n);
    if (tid == 96 && n == 0) store_stage(0);
    if (tid == 128 && n == 0) {
#pragma unroll 1
      for (int i = 0; i < 4; i++) issue_x(1, i);
    }
    if (warp == 5 && n == 1) {
#pragma unroll 1
      while (__any_sync(0xffffffffu, ldx32(&gx->ctr[h]) < 4) && ++it < SPIN_LIMIT) {}
      __threadfence(); asm volatile("fence.proxy.async;" ::: "memory");
      if (elect()) issue_kqv(0);
    }
    __syncwarp();
  }
  mbar_spin(sb + B_W, 1, it);
  PT(9);
#pragma unroll
  for (int i = 0; i < 4; i++) {
    uint32_t f[4][4];
    const uint32_t a = sb + R_WO + warp * 8192 + i * 2048;
#pragma unroll
    for (int q = 0; q < 4; q++) ldsm4t(f[q], a + (LW ^ (q << 5)));
    __syncwarp();
#pragma unroll
    for (int q = 0; q < 4; q++) sts128(a + q * 512 + L16, f[q]);
  }
  if (NPC) probe(1, NPC);
  {
    const int o = 32 * w4 + 16 * wg + 4 * t + j;
    uint32_t v;
#pragma unroll 1
    while (__any_sync(0xffffffffu, (v = ldx32(&gx->S[o])) == 0) && ++it < SPIN_LIMIT) {}
    asm volatile("st.shared.u64 [%0], %1;" :: "r"(sb + R_DST + wg * 1024 + w4 * 256 + lane * 8), "l"(xb + offsetof(Xchg, B) + o * 8192 + (v >> 1) * 4096 + h * 128 + ((g ^ h) & 7) * 16) : "memory");
  }
  if (wg == 0) {
    const uint64_t cd = reinterpret_cast<uint64_t>(xb + (offsetof(Xchg, C) + j * 8192 + h * 128 + w4 * 32 + (L16 & 16) * 256 + (L16 & 64) / 4 + (L16 >> 7) * 4));
    sts128(uW + R_RD + L16, (uint32_t)cd, (uint32_t)(cd >> 32), sb + R_MEM + (L16 & 112) * 8 + (L16 >> 8) * 1024 + ((w4 * 32 + ((L16 >> 3) & 16)) ^ (L16 & 112)),
           (L16 >> 6) == (h & 3) * 2 + ((h >> 2) & 1) ? 0xFFFE0000u : 0xFFFFFFFFu);
  }
  if (tid == 0) sts32(sb + B_DUE + 8, gtime() & ~31u);
  PT(10);
  mbar_spin(sb + B_KV, 0, it);
  PT(11);
  if (tid < 4) sts32(sb + B_ONE + tid * 4, 0x3F803F80u);
  if (warp == 1) { const uint32_t e = g >> 1 == t ? 0x3F80u << (16 * (g & 1)) : 0u; sts128(sb + R_ID + L16, e, 0, 0, e); }
  __syncthreads();
  {
    const uint32_t kb = lds32(sb + R_T + 36) < lds32(sb + R_T + 32);
    uS = uni((HOME & 4 ? (__popc(((offsetof(Xchg, B) / 4096 + 2 * role) ^ (offsetof(Xchg, C) / 4096 + 2 * w4)) & 0xb3) ^ kb) & 1 : lds32(sb + R_T + w4 * 8 + 4) < lds32(sb + R_T + w4 * 8)) * 4096 + kb);
  }

  const float sc = 0.08838834764831845f * 1.4426950408889634f;
  uint8_t* const xa = xb + uni(h * 16384);
  const uint32_t uA = uni(wg ? (w4 >> 1) * 2048 + j * 512 + (w4 & 1) * 256 : 8192 + (4 * (j >> 1) + w4) * 512 + jh * 256);
  const uint32_t uP2 = uni(sb + R_P + w4 * 256);
  uint32_t nc = 1;
  uint32_t ma;
  const uint8_t* adst;
  auto pin_mem = [&]() { adst = pinp(xa + uA + L16 / 2); ma = pin(uMem + (L16 & 384) + (L16 & 48) * 2 + (L16 & 64) / 4); };
  pin_mem();

#pragma unroll 1
  for (int s = 0;; nc++) {
    const uint32_t tag = (s + 1) & 1;
    auto fresh = [&]() { L16 += (uint32_t)it >> 31; };
    auto get_due = [&]() { return lds32(sb + B_DUE + 4 + tag * 4); };
    float c[4][4], r4[4];
    auto fold = [&]() {
#pragma unroll
      for (int i = 0; i < 4; i++) r4[i] = ((c[0][i] + c[1][i]) + c[2][i]) + c[3][i];
    };
    auto mma4 = [&](int n, const uint32_t (&b0)[4], const uint32_t (&b1)[4]) {
      mma_h(c[0], w[n + 2], b1, 0); mma_h(c[1], w[n + 3], b1, 1); mma_h(c[2], w[n], b0, 0); mma_h(c[3], w[n + 1], b0, 1);
    };
    auto xpos = [&](int pos, int wp) {
      if ((pos == X0 || pos == X1 || pos == X2 || pos == X3) && warp == wp && s + 1 < NSEG && elect()) {
        const int z = (uint32_t)it >> 31;
        if (pos == X2) issue_x(s + 2, 2 + z);
        if (pos == X3) issue_x(s + 2, 3 + z);
        if (pos == X1) issue_x(s + 2, 1 + z);
        if (pos == X0) issue_x(s + 2, z);
      }
      __syncwarp();
    };
    if (wg == 0) {
      mbar_spin(sb + B_C, nc & 1, it);
      TS(13);
      uint32_t b[16][4], tg[4];
#pragma unroll
      for (int i = 0; i < PD0; i++) { lds128(b[i], ma + i * 512); __syncwarp(); }
      sched();
      zero(c);
#pragma unroll
      for (int i = 0; i < 8; i++) {
        const int k = i ^ 1;
        mma_h(c[0], w[2 * k], b[k], 0); mma_h(c[1], w[2 * k + 1], b[k], 1);
        if (i < 2 * NV0) { mma_h(c[2], w[16 + 2 * k], b[k], 0); mma_h(c[3], w[17 + 2 * k], b[k], 1); }
        sched();
        if ((i & 1) && i + PD0 < 9) { lds128(b[i + PD0 - 1], ma + (i + PD0 - 1) * 512); __syncwarp(); lds128(b[i + PD0], ma + (i + PD0) * 512); sched(); }
        if (i == TGP) {
          fresh();
#pragma unroll
          for (int k = 0; k < 4; k++) tg[k] = lds32((uW * 4 + L16) * 2 + (L16 >> 6) * 4 + (R_MEM + k * 1024 - 7 * sb));
          sched();
        }
      }
#pragma unroll
      for (int i = 0; i < 4; i++) { r4[i] = c[0][i] + c[1][i]; c[0][i] = c[1][i] = 0.f; }
      sts128f(uW + R_RED + L16, r4);
      TS(1);
      const uint32_t old = bar_or(4, (dif2(tg[0], tg[1], s) | dif2(tg[2], tg[3], s)) & (s > 0));
      TS(0);
#pragma unroll
      for (int i = 0; i < 2 * NV0; i++) { lds128(b[8 + i], (ma ^ 4096) + i * 512); __syncwarp(); }
      sched();
#pragma unroll
      for (int i = NV0; i < 8; i++) {
        if (VB && i == VB) bar_sync(7, 256);
        mma4(16 + 4 * i, b[2 * i], b[2 * i + 1]);
        if (i < 7) sched();
        if (i < 4) { lds128(b[8 + 2 * i], (ma ^ 4096) + i * 1024); __syncwarp(); lds128(b[9 + 2 * i], (ma ^ 4096) + i * 1024 + 512); sched(); }
      }
      fold();
      asm volatile("{.reg .pred p; setp.eq.u32 p, %3, 0; @p st.relaxed.gpu.global.v2.b32 [%0], {%1,%2};}" :: "l"(adst), "r"((pack2(r4[0], r4[1]) & ~1u) | tag), "r"(pack2(r4[2], r4[3])), "r"(old) : "memory");
      sched();
      const unsigned tpub = clk();
      if (__any_sync(0xffffffffu, old) && nc < NC_MAX) {
        bar_sync(3, 256);
        issue_c(gtime());
        continue;
      }
      TS(3);
      xpos(0, 0);
      const uint32_t due = get_due();
      uint32_t vf[4][4], vm[2][4], p[4], pm, o[4];
      const uint32_t va = sb + R_V + (w4 >> 1) * 8192 + (w4 & 1) * 2048 + L16;
#pragma unroll
      for (int i = 0; i < 4; i++) {
        uint32_t q[4]; lds128(vf[i], va + i * 512); lds128(q, va + 4096 + i * 512);
#pragma unroll
        for (int e = 0; e < 4; e++) vf[i][e] = hadd2(vf[i][e], q[e]);
      }
      const uint32_t pa = pin(sb + R_P + (L16 >> 1));
      const uint8_t* vsrc = pinp(xa + 8192 + w4 * 1024 + L16 / 2);
      uint32_t one[4];
      lds128(one, sb + B_ONE);
      auto pv_x = [&]() {
        zero(c);
        mma_a(c[2], one, p[0], p[1]);
        mma_a(c[0], vf[0], p[0], p[1]); mma_a(c[1], vf[2], p[0], p[1]);
        sched();
        mma_a(c[2], one, p[2], p[3]);
        mma_a(c[0], vf[1], p[2], p[3]); mma_a(c[1], vf[3], p[2], p[3]);
        sched();
      };
      auto pv_m = [&]() {
        mma1688(c[2], one[0], one[1], pm);
        mma_a(c[0], vm[0], pm, pm);
        sched();
        mma_a(c[1], vm[1], pm, pm);
      };
      auto norm = [&]() {
        const float n0 = rcp(c[2][0]), n1 = rcp(c[2][1]);
#pragma unroll
        for (int i = 0; i < 4; i++) o[i] = pack2(c[i >> 1][2 * (i & 1)] * n0, c[i >> 1][2 * (i & 1) + 1] * n1);
        return ((__float_as_uint(c[2][0]) - 0x1F800000u) | (__float_as_uint(c[2][1]) - 0x1F800000u)) >> 30;
      };
      auto load_m = [&](int x) { const float2 e0 = lds64f(pa + 512 + x * 1024), e1 = lds64f(pa + 768 + x * 1024); pm = pack2(e0.x * e1.x, e0.y * e1.y); };
      auto attend_max = [&](int x) {
        float2 sv[6];
#pragma unroll
        for (int i = 0; i < 6; i++) sv[i] = lds64f(pa - 3072 + x * 1536 + i * 256);
        sv[4].x += sv[5].x; sv[4].y += sv[5].y;
        const int dq = (int)(L16 >> 6) - (int)((L16 >> 3) & 6) + 8 * j;
        float m = fmaxf(sv[4].x, sv[4].y);
#pragma unroll
        for (int i = 0; i < 4; i++) {
          if (x && 8 * i > dq) sv[i].x = -INFINITY;
          if (x && 8 * i + 1 > dq) sv[i].y = -INFINITY;
          m = fmaxf(m, fmaxf(sv[i].x, sv[i].y));
        }
        m = fmaxf(m, __shfl_xor_sync(0xffffffffu, m, 1));
        m = fmaxf(m, __shfl_xor_sync(0xffffffffu, m, 2));
#pragma unroll
        for (int i = 0; i < 5; i++) (i < 4 ? p[i] : pm) = pack2(ex2(sv[i].x - m), ex2(sv[i].y - m));
        pv_x(); pv_m(); norm();
      };
      uint32_t tq[4];
      auto get_t = [&]() {
        tq[0] = tq[1] = tq[2] = tq[3] = 0;
        asm volatile("{.reg .pred p; setp.eq.u32 p, %5, 0; @p ld.relaxed.gpu.global.v4.b32 {%0,%1,%2,%3}, [%4];}"
                     : "+r"(tq[0]), "+r"(tq[1]), "+r"(tq[2]), "+r"(tq[3]) : "l"(xb + offsetof(Xchg, T) + L16 * 8), "r"(warp) : "memory");
      };
      delay_until(tpub + DLY_V);
      wait_time(due + NS_V);
      TS(4);
      ldx(vm, vsrc);
      sched();
      xpos(2, 2);
      auto store_kqv = [&]() {
        fence_async();
        if (!(EXP & 4))
          asm volatile("{.reg .pred p; elect.sync _|p, 0xffffffff; @p cp.async.bulk.global.shared::cta.bulk_group [%0], [%1], 2048; cp.async.bulk.commit_group;}"
                       :: "l"(g_kqv[(s + 1) & 3][role] + w4 * 128), "r"(sb + R_STAGE + w4 * 2048) : "memory");
      };
      if (SPOS == 2) store_kqv();
      sched();
      bar_sync(5, 256);
      ldsm4(p, sb + R_P + L16);
      load_m(0);
      pv_x();
      ldsm4(p, sb + R_P + 1024 + L16);
      pv_m();
      const uint32_t r = norm(), tl = after(tag, c[2][0], (uint32_t)it >> 31);
      const bool redo = __any_sync(0xffffffffu, r | ((dif2(vm[0][0], vm[0][2], tl) | dif2(vm[1][0], vm[1][2], tl)) & 1));
      TS(6);
      stsm4t(uW + R_O + L16, o[0], o[1], o[2], o[3]);
      bar_arrive_unless(6, redo);
      sched();
      if (TQL == 7) get_t();
      TS(7);
      pv_x();
      if (rare(redo)) retry<2>(vm, vsrc, tag, it);
      bar_sync(8, 256);
      load_m(1);
      pv_m();
      if (rare(__any_sync(0xffffffffu, norm()) || redo)) {
        fresh();
#pragma unroll 1
        for (int x = !redo; x < 2; x++) {
          attend_max(x);
          if (x == 0) { stsm4t(uW + R_O + L16, o[0], o[1], o[2], o[3]); bar_arrive(6, 256); }
        }
      }
      TS(8);
      if (TQL == 8) get_t();
      const bool xok = mbar_test(sb + B_X + 16, s & 1) & mbar_test(sb + B_X + 24, s & 1);
      xpos(4, 2);
      fresh();
      const uint32_t ob = uni(sb + R_MEM + 4096 + w4 * 1024);
      stsm4t(ob + (L16 & 112) * 4 + (((L16 >> 3) ^ (L16 >> 1)) & 48), o[0], o[1], o[2], o[3]);
      __syncwarp();
      uint32_t rd[4];
      lds128(rd, uW + R_RD + L16);
      lds128(o, ob + (L16 ^ ((L16 >> 3) & 48)));
      auto put_o = [&]() {
        *reinterpret_cast<uint4*>(reinterpret_cast<uint8_t*>(g_ox) + (((s * SEG + 8 * j) * HD + h * DH + 32 * w4) * 2 + (L16 >> 6) * (HD * 2) + (L16 & 48))) = make_uint4(o[0], o[1], o[2], o[3]);
      };
      if (s + 1 == NSEG) { put_o(); asm volatile("cp.async.bulk.wait_group 0;" ::: "memory"); break; }
      asm volatile("cp.async.bulk.wait_group 0;" ::: "memory");
      if (elect()) stx32(xa + 4096 + j * 16 + w4 * 4, s + 1);
      __syncwarp();
      if (rare(!xok)) { wait_x(s + 2, 3); wait_x(s + 2, 2); }
      TS(9);
      fresh();
      const uint32_t e = due | ((s + 1) & 31);
      project_qk(IC<0>{}, IC<NQ>{}, IC<1>{}, [&](int n) {
        if (n == OXPOS) { __syncwarp(); put_o(); __syncwarp(); }
        if (n == TQP) { __syncwarp(); tq[0] = dif2v(tq[0], tq[1], e) | dif2v(tq[2], tq[3], e); __syncwarp(); }
      });
      if (NPA) project_v(IC<0>{}, IC<NPA>{}, [](int) {});
      TS(2);
      if (warp == 0) {
        uint32_t last = due, nx = NS_P;
        if (rare(__any_sync(0xffffffffu, tq[0]))) {
          const uint32_t ref = gtime();
#pragma unroll 1
          do ldx128(o, xb + offsetof(Xchg, T) + L16 * 8); while (any_bit(or3(o[0] - s - 1, o[1] - s - 1, o[2] - s - 1), o[3] - s - 1, 30) && ++it < SPIN_LIMIT);
          const int d = max(max((int)(o[0] - ref), (int)(o[1] - ref)), max((int)(o[2] - ref), (int)(o[3] - ref)));
          last = (ref + __reduce_max_sync(0xffffffffu, d)) & ~31u;
          if (last != due) nx += NS_X;
        }
        const uint32_t bdue = last + NS_B;
        if (s < 4) { last += (MG_Y >> 8 * s & 255) * 32; nx += (MG_Z >> 8 * s & 255) * 32; }
        sts32(sb + B_DUE, last);
        sts32(sb + B_DUE + 8 - tag * 4, last + nx);
        fetch4k(sb + R_MEM, my_b(), sb + B_B, bdue);
        LOG(13, tl - last);
        LOG(9, last);
      }
      if (NQ < 16) project_qk(IC<NQ>{}, IC<16>{}, IC<0>{}, [](int) {});
      project_v(IC<NPA>{}, IC<NPRE>{}, [](int) {});
      const uint32_t ba = rd[2], msk = rd[3];
      const uint8_t* cdst = reinterpret_cast<const uint8_t*>(rd[0] | (uint64_t)rd[1] << 32);
      TS(14);
      mbar_spin(sb + B_B, s & 1, it);
      TS(10);
      uint32_t bq[2][4];
      auto sum_b = [&]() {
        ldsm4t(bq[0], ba); ldsm4t(bq[1], ba + 2048);
        sched();
#pragma unroll
        for (int i = 0; i < 8; i++) c[i >> 2][i & 3] = 0.f;
        mma_a(c[0], bq[0], 0x3F803F80u, 0x3F803F80u); mma_a(c[1], bq[1], 0x3F803F80u, 0x3F803F80u);
        const uint32_t t2 = tag * 0x10001u;
        const bool old = any_bit(or3(dif2(bq[0][0], bq[0][1], t2), dif2(bq[0][2], bq[0][3], t2), dif2(bq[1][0], bq[1][1], t2)), dif2(bq[1][2], bq[1][3], t2), L16 < 64 ? 0x10001u : 0u);
        const uint32_t T = (tag << 16) & ~msk, u = ((__float_as_uint(c[0][0] + c[1][0]) + ((0x10000u & ~msk) - T)) & msk) | T;
        asm volatile("{.reg .pred p; setp.eq.u32 p, %2, 0; @p st.relaxed.gpu.global.b32 [%0], %1;}"
                     :: "l"(cdst), "r"(pack2(__uint_as_float(u), c[0][2] + c[1][2])), "r"((uint32_t)(old || (L16 & 32))) : "memory");
        return old;
      };
      if (rare(sum_b())) {
#pragma unroll 1
        do {
          const uint8_t* p = xb + (my_b() + (ba - sb - R_MEM));
          ldx128(bq[0], p); ldx128(bq[1], p + 2048);
          sts128(ba, bq[0]); sts128(ba + 2048, bq[1]);
          __syncwarp();
          it += INC_B;
        } while (sum_b() && it < SPIN_LIMIT);
      }
      sched();
      TS(11);
      bar_arrive(0, 256);
      const unsigned tc = clk();
      const uint32_t cdue = lds32(sb + B_DUE) + NS_C;
      if (warp == 3) LOG(11, gtime() - cdue);
      fresh();
      wg_wait<0>(); keep(aq); keep(av);
      park();
      if (NPRE < 32) project_v(IC<NPRE>{}, IC<32>{}, [](int) {}); else fin_v();
      TS(12);
      delay_until(tc + DLY_C);
      issue_c(cdue);
      TS(5);
      LOG(warp, it);
      pin_mem();
      if (NPRE < 32) { wg_wait<0>(); keep(av); fin_v(); }
      if (!(EXP & 2)) mbar_spin(sb + B_KV, tag, it);
      TS(15);
    } else {
      uint32_t kf[8][4];
      auto load_k = [&]() {
        const uint32_t ka = sb + R_K + w4 * 1024 + (L16 & 112) + (L16 & 128) * 4 + (L16 & 256);
#pragma unroll
        for (int i = 0; i < 8; i++) ldsm4(kf[i], ka + (i >> 1) * 2048 + (i & 1) * 128);
      };
      auto put_p = [&](int x, uint32_t old, uint32_t again) {
        float e[4];
        const int dq = (int)((L16 >> 3) & 6) + 8 * j - (int)(L16 >> 6) - 16 * w4;
#pragma unroll
        for (int i = 0; i < 4; i++) { r4[i] = fmaf(c[3][i], sc, fmaf(c[2][i], sc, fmaf(c[0][i] + c[1][i], sc, __uint_as_float(i == 3 ? 0u - old : 0u)))); e[i] = x && dq + (i & 1) < 8 * (i >> 1) ? 0.f : ex2(r4[i]); }
        stsm2t(uP2 + x * 1024 + L16, pack2(e[0], e[1]), pack2(e[2], e[3]), again);
      };
      auto put_s = [&](int x) {
#pragma unroll
        for (int i = 0; i < 4; i++) sts32f(uW + R_S + x * 1536 + (L16 & 48) * 4 + (L16 >> 6) * 4 + (i & 1) * 32 + (i >> 1) * 256, r4[i]);
      };
      auto load_q = [&](uint32_t (&q)[4], uint32_t off) { ldsm4(q, sb + R_Q + (L16 & 112) + (L16 & 128) * 2 + (L16 >> 8) * 128 + off); };
      mbar_spin(sb + B_C, nc & 1, it);
      TS(13);
      float4 o4;
      uint32_t id[4], old;
      {
        uint32_t b[24][4];
#pragma unroll
        for (int i = 0; i < 2 * PD1; i++) { lds128(b[i], ma + i * 512); __syncwarp(); }
        sched();
        zero(c);
#pragma unroll
        for (int i = 0; i < 12; i++) {
          mma4(4 * i, b[2 * i], b[2 * i + 1]);
          if (i < 11) sched();
          if (i + PD1 < 12) { const int k = i + PD1; const uint32_t a = (ma ^ (k >> 2 << 12)) + (k & 3) * 1024; lds128(b[2 * k], a); __syncwarp(); lds128(b[2 * k + 1], a + 512); sched(); }
          if (i == RJ) { lds128(id, sb + R_ID + L16); sched(); }
          if (i == RI) { old = bar_or(4, 0); o4 = lds128f(uW + R_RED + L16); sched(); }
        }
      }
      TS(0);
      {
        float e[4] = {o4.x, o4.y, o4.z, o4.w};
#pragma unroll
        for (int i = 0; i < 4; i++) { r4[i] = (((e[i] + c[0][i]) + c[1][i]) + c[2][i]) + c[3][i]; e[i] = 0.f; }
        mma_a(e, id, pack2(r4[0], r4[1]), pack2(r4[2], r4[3]));
        sched();
        if (VB) bar_arrive(7, 256);
        sched();
        asm volatile("{.reg .pred p; setp.eq.u32 p, %3, 0; @p st.relaxed.gpu.global.v2.b32 [%0], {%1,%2};}" :: "l"(adst),
                     "r"((__byte_perm(__float_as_uint(e[0]), __float_as_uint(e[1]), 0x7632) & ~1u) | tag), "r"(__byte_perm(__float_as_uint(e[2]), __float_as_uint(e[3]), 0x7632)), "r"(old) : "memory");
        sched();
      }
      const unsigned tpub = clk(), now = gtime(), due = get_due();
      if (__any_sync(0xffffffffu, old) && nc < NC_MAX) { bar_sync(3, 256); continue; }
      TS(2);
      const uint8_t* asrc = pinp(adst + ((warp == 7) * 1024 - (int)uA));
      fresh();
      uint32_t wo[32][4];
      bool xok;
      auto reload = [&]() {
        sched();
#pragma unroll
        for (int i = RE0 + RE1; i < NSW; i++) lds128(w[i], uW + R_WC + L16 + i * 2048);
        sched();
      };
      auto out_proj = [&]() {
        uint32_t b[4][4];
        float d[4][4];
        uint8_t* dst[2];
        const uint32_t da = pin(uP2 + (R_DST - R_P) + L16 / 2);
        sched();
        TS(7);
        bar_sync(6, 256);
#pragma unroll
        for (int i = 0; i < 4; i++) { ldsm4(b[i], sb + R_O + i * 512 + L16); __syncwarp(); }
        sched();
        auto put_b = [&](uint8_t* a, const float (&e)[4][4]) {
          stx128(a, (pack2(e[0][0] + e[2][0], e[0][1] + e[2][1]) & ~1u) | tag, pack2(e[0][2] + e[2][2], e[0][3] + e[2][3]),
                 pack2(e[1][0] + e[3][0], e[1][1] + e[3][1]), pack2(e[1][2] + e[3][2], e[1][3] + e[3][3]));
        };
        zero(c); zero(d);
#pragma unroll
        for (int i = 0; i < 32; i++) {
          mma_h(i < 16 ? c[i & 3] : d[i & 3], wo[i], b[(i >> 2) & 3], (i >> 1) & 1);
          if (i >= LW0 && NB1 + i - LW0 < 32) { load_wo(wo, (NB1 + i - LW0) ^ 1, ((NB1 + i - LW0) ^ 1) + 1); __syncwarp(); }
          if (i == DL0 || i == DL1) asm volatile("ld.shared.u64 %0, [%1];" : "=l"(dst[i > DL0]) : "r"(da + (i > DL0) * 1024) : "memory");
          if (i >= 16 && i < 16 + RE0) { lds128(w[i - 16], uW + R_WC + L16 + (i - 16) * 2048); __syncwarp(); }
          if (i >= RP1 && i < RP1 + RE1) { lds128(w[i - RP1 + RE0], uW + R_WC + L16 + (i - RP1 + RE0) * 2048); __syncwarp(); }
          if (i == 22) put_b(dst[0], c);
          if ((i & 1) && (i < 20 || i > 22)) sched();
        }
        put_b(dst[1], d);
        sched();
        TS(6);
      };
      if (warp < 6) {
        delay_until(tpub + DLY_A);
        const int it0 = it;
        bool redo;
#pragma unroll 1
        do {
          uint32_t q[4][4], y[4];
          float d[4][4];
          wait_time(due);
          TS(4);
          ldx(q, asrc);
          sched();
          load_k();
          uint32_t qx[4][4];
#pragma unroll
          for (int i = 0; i < 4; i++) load_q(qx[i], i * 512);
          sched();
          load_wo(wo, 0, NE4);
          sched();
          zero(c);
#pragma unroll
          for (int i = 0; i < 8; i++) mma_h(c[i & 3], kf[i], qx[i >> 1], i & 1);
          put_p(1, 0, 0); put_s(1);
          sched();
          load_wo(wo, NE4, NA4);
          sched();
          zero(c); zero(d);
#pragma unroll
          for (int i = 0; i < 8; i++) {
            if (i == 0) { y[0] = dif2v(q[0][0], q[0][2], q[1][0]); sched(); }
            if (i == 3) { y[1] = dif2v(q[1][2], q[2][0], q[2][2]); sched(); }
            if (i == 6) { y[2] = dif2v(q[3][0], q[3][2], tag); sched(); }
            mma_h(i % 6 < 2 ? c[2 + i % 6] : d[i - 2], kf[i], q[i >> 1], i & 1);
            if (i == 2 || i == 5 || i == 7) sched();
          }
          y[0] = or_and(or3(y[0], y[1], dif2v(q[0][0], q[2][0], tag)), y[2], it < SPIN_LIMIT);
#pragma unroll
          for (int i = 0; i < 4; i++) { c[0][i] = d[0][i] + d[1][i]; c[1][i] = d[2][i] + d[3][i]; }
          put_p(0, y[0], it - it0);
          TS(5);
          bar_sync_unless(5, it - it0);
          redo = __any_sync(0xffffffffu, y[0]);
          it += INC_A;
        } while (redo);
        it -= INC_A;
        put_s(0);
        bar_arrive(8, 256);
        load_wo(wo, NA4, NB1);
        out_proj();
        if (warp == 4) LOG(12, tb);
      } else {
        uint32_t qx[2][4], q[4][4];
        if (warp == 6) {
          const uint32_t t1 = (now & ~31u) + NS_M;
          LOG(10, now - due);
          if (elect()) stx32(&gx->T[h][j], ((int)(t1 - due) > 0 ? t1 + NS_PEN : due) | ((s + 1) & 31));
          __syncwarp();
        }
        auto score = [&](const uint32_t (&a0)[4], const uint32_t (&a1)[4]) {
          zero(c);
#pragma unroll
          for (int i = 0; i < 4; i++) mma_h(c[i], i < 2 ? a0 : a1, q[2 + (i >> 1)], i & 1);
        };
        auto put_m = [&](uint32_t a, uint32_t old, uint32_t again) {
#pragma unroll
          for (int i = 0; i < 2; i++) { r4[i] = fmaf(c[3][2 + i], sc, fmaf((c[0][i] + c[1][2 + i]) + c[2][i], sc, __uint_as_float(i ? 0u - old : 0u))); r4[2 + i] = fmaf(r4[i] * 0x1p122f, 0.f, ex2(r4[i])); }
          asm volatile("{.reg .pred p; setp.eq.u32 p, %3, 0; @p st.shared.v2.f32 [%0], {%1,%2};}" :: "r"(a), "f"(r4[2]), "f"(r4[3]), "r"(again) : "memory");
        };
        delay_until(tpub + DLY_A);
        const uint32_t sa = sb + R_S + 512 + w4 * 256 + (L16 >> 1);
        const int it0 = it;
        bool redo;
#pragma unroll 1
        do {
          wait_time(due);
          TS(4);
          ldx<4, 2048>(q, asrc);
          sched();
          load_q(qx[0], (w4 & 1) * 1024); load_q(qx[1], (w4 & 1) * 1024 + 512);
          load_wo(wo, 0, NA6);
          sched();
          score(q[0], q[1]);
          sched();
          const uint32_t y = or_and(or3(dif2v(q[0][0], q[0][2], tag), dif2v(q[1][0], q[1][2], tag), dif2v(q[2][0], q[2][2], tag)), dif2v(q[3][0], q[3][2], tag), it < SPIN_LIMIT);
          put_m(sa + 2560, y, it - it0);
          TS(5);
          bar_arrive_unless(5, it - it0);
          redo = __any_sync(0xffffffffu, y);
          it += INC_A;
        } while (redo);
        it -= INC_A;
        sts64f(sa, r4[0], r4[1]);
        score(qx[0], qx[1]);
        put_m(sa + 3584, 0, 0);
        sts64f(sa + 1536, r4[0], r4[1]);
        bar_arrive(8, 256);
        load_wo(wo, NA6, NB1);
        out_proj();
      }
      TS(8);
      if (s + 1 == NSEG) break;
      wait_x(s + 2, 2);
      TS(9);
      fresh();
      if (N1) project_qk(IC<32>{}, IC<32 + N1>{}, IC<1>{}, [](int) {});
      TS(10);
      xpos(6, 6);
      uint32_t fl = s + 1;
      if (warp == 5) { wait_time(due + NS_F); fl = ldx32(xa + 4096 + ((L16 >> 2) & 60)); }
      reload();
      TS(14);
      pin_mem();
      wait_x(s + 2, 1); wait_x(s + 2, 0);
      if (warp == 5) {
#pragma unroll 1
        while (__any_sync(0xffffffffu, fl != s + 1) && !(EXP & 4) && ++it < SPIN_LIMIT) fl = ldx32(xa + 4096 + ((L16 >> 2) & 60));
        wait_time(due + (NS_B + NS_K));
        if (!(EXP & 2) && elect()) issue_kqv(s + 1);
        __syncwarp();
      }
      if (PFD && warp == 6 && s + PFD < NSEG && elect())
        asm volatile("cp.async.bulk.prefetch.L2.global [%0], 2048;" :: "l"(xin + ((s + PFD) * SEG + ((role + 4 * (role >> 5)) & 31)) * DM) : "memory");
      __syncwarp();
      TS(11);
      LOG(warp, it);
      if (warp == 4) LOG(8, nc);
      bar_sync(0, 256);
      if (N1 < 16) project_qk(IC<32 + N1>{}, IC<48>{}, IC<!N1>{}, [](int) {});
      project_qk(IC<16>{}, IC<32>{}, IC<0>{}, [&](int n) { if ((n & 15) == XWPOS) { __syncwarp(); xok = mbar_test(sb + B_PK, s & 1); __syncwarp(); } });
      if (rare(!xok)) mbar_spin(sb + B_PK, s & 1, it);
      unpark();
      project_qk(IC<0>{}, IC<16>{}, IC<0>{}, [](int) {});
      TS(12);
      wg_wait<0>(); keep(aq);
      TS(1);
      fin_qk();
      TS(15);
    }
    s++;
  }
  if (it >= SPIN_LIMIT || nc >= NC_MAX) g_err = 2;
}

typedef CUresult (*EncodeFn)(CUtensorMap*, CUtensorMapDataType, cuuint32_t, void*, const cuuint64_t*, const cuuint64_t*, const cuuint32_t*,
                             const cuuint32_t*, CUtensorMapInterleave, CUtensorMapSwizzle, CUtensorMapL2promotion, CUtensorMapFloatOOBfill);
static void make_map(EncodeFn fn, CUtensorMap* m, const void* p, uint64_t cols, uint64_t rows, uint64_t pitch, uint32_t bc, uint32_t br, CUtensorMapSwizzle sw) {
  cuuint64_t dims[2] = {cols, rows}, strides[1] = {pitch * 2};
  cuuint32_t box[2] = {bc, br}, es[2] = {1, 1};
  fn(m, CU_TENSOR_MAP_DATA_TYPE_BFLOAT16, 2, const_cast<void*>(p), dims, strides, box, es, CU_TENSOR_MAP_INTERLEAVE_NONE, sw,
     CU_TENSOR_MAP_L2_PROMOTION_L2_256B, CU_TENSOR_MAP_FLOAT_OOB_FILL_NONE);
}

extern "C" void kernel_launch(void* const* d_in, const int* in_sizes, int n_in, void* d_out, int out_size) {
  const bf16* Ax = (const bf16*)d_in[0]; const bf16* mem0 = (const bf16*)d_in[1];
  const bf16* Wq = (const bf16*)d_in[2]; const bf16* Wk = (const bf16*)d_in[3]; const bf16* Wv = (const bf16*)d_in[4];
  const bf16* Wo = (const bf16*)d_in[5];
  const bf16* Bx = (const bf16*)d_in[7]; const bf16* wr = (const bf16*)d_in[8]; const bf16* wi = (const bf16*)d_in[9];
  bf16* out = (bf16*)d_out;

  void* fp = nullptr; cudaDriverEntryPointQueryResult qr;
  cudaGetDriverEntryPoint("cuTensorMapEncodeTiled", &fp, cudaEnableDefault, &qr);
  EncodeFn fn = (EncodeFn)fp;
  void *kqv, *ox, *xr;
  cudaGetSymbolAddress(&xr, g_xraw);
  cudaGetSymbolAddress(&kqv, g_kqv); cudaGetSymbolAddress(&ox, g_ox);
  const CUtensorMapSwizzle S128 = CU_TENSOR_MAP_SWIZZLE_128B, S64 = CU_TENSOR_MAP_SWIZZLE_64B;

  GemmMaps m3; RecMaps mr;
  make_map(fn, &m3.a, ox, HD, S_LEN, HD, 64, 128, S128);
  make_map(fn, &m3.b[0], Wo, DM, HD, DM, 64, 64, S128);
  m3.b[1] = m3.b[0]; m3.b[2] = m3.b[0];
  make_map(fn, &m3.c, out, DM, S_LEN, 2 * DM, 64, 64, S128);
  make_map(fn, &mr.wq, Wq, HD, DM, HD, 32, 256, S64);
  make_map(fn, &mr.wk, Wk, HD, DM, HD, 32, 256, S64);
  make_map(fn, &mr.wv, Wv, HD, DM, HD, 64, 256, S128);
  make_map(fn, &mr.wo, Wo, DM, HD, DM, 64, 128, S128);
  {
    cuuint64_t dims[3] = {64, S_LEN, 16}, strides[2] = {DM * 2, 128};
    cuuint32_t box[3] = {64, 32, 4}, es[3] = {1, 1, 1};
    fn(&mr.x, CU_TENSOR_MAP_DATA_TYPE_BFLOAT16, 3, const_cast<bf16*>(Ax), dims, strides, box, es, CU_TENSOR_MAP_INTERLEAVE_NONE, S128,
       CU_TENSOR_MAP_L2_PROMOTION_L2_256B, CU_TENSOR_MAP_FLOAT_OOB_FILL_NONE);
  }
  for (int i = 0; i < 3; i++) {
    cuuint64_t dims[3] = {128, 32, 512}, strides[2] = {256, 8192};
    cuuint32_t box[3] = {128, i == 0 ? 8u : i == 1 ? 2u : 16u, 4}, es[3] = {1, 1, 1};
    fn(i == 0 ? &mr.k : i == 1 ? &mr.q : &mr.v, CU_TENSOR_MAP_DATA_TYPE_BFLOAT16, 3, kqv, dims, strides, box, es, CU_TENSOR_MAP_INTERLEAVE_NONE,
       CU_TENSOR_MAP_SWIZZLE_NONE, CU_TENSOR_MAP_L2_PROMOTION_L2_256B, CU_TENSOR_MAP_FLOAT_OOB_FILL_NONE);
  }
  {
    cuuint64_t dims[3] = {64, 16, S_LEN}, strides[2] = {128, 2 * DM * 2};
    cuuint32_t box[3] = {64, 16, 2}, es[3] = {1, 1, 1};
    fn(&mr.fo, CU_TENSOR_MAP_DATA_TYPE_BFLOAT16, 3, out + DM, dims, strides, box, es, CU_TENSOR_MAP_INTERLEAVE_NONE, S128,
       CU_TENSOR_MAP_L2_PROMOTION_NONE, CU_TENSOR_MAP_FLOAT_OOB_FILL_NONE);
  }
  constexpr int SM3 = 6 * 32768 + 32768 + 256 + 1024;
  cudaFuncSetAttribute(gemm_kernel<128, 6>, cudaFuncAttributeMaxDynamicSharedMemorySize, SM3);
  cudaFuncSetAttribute(rec_kernel, cudaFuncAttributeMaxDynamicSharedMemorySize, R_TOTAL);

  cudaStream_t st = cudaStreamPerThread;
  Xchg* gx = reinterpret_cast<Xchg*>((reinterpret_cast<uintptr_t>(xr) + 0x1FFFFF) & ~(uintptr_t)0x1FFFFF);
  rec_kernel<<<132, 256, R_TOTAL, st>>>(mr, Ax, mem0, gx, Bx, wr, wi);
  gemm_kernel<128, 6><<<128, 384, SM3, st>>>(m3, 16, 8, 64, 8, reinterpret_cast<uint4*>(gx));
}
```

```cpp
#include <cuda_runtime.h>
#include <cuda_bf16.h>
#include <cuda.h>
#include <stdint.h>
#include <stddef.h>
#include <type_traits>

typedef __nv_bfloat16 bf16;

constexpr int S_LEN = 2048, DM = 1024, NH = 32, DH = 128, MEM = 8, SEG = 32, NSEG = 64;
constexpr int HD = NH * DH;
#define SPIN 20
constexpr int SPIN_LIMIT = 1 << SPIN, INC_A = 1, INC_B = 1;

constexpr unsigned NC_MAX = 4096;
__device__ __align__(1024) uint4 g_kqv[4][128][512];
__device__ __align__(1024) bf16 g_ox[(size_t)S_LEN * HD];
struct Xchg {
  uint4 A[32][4][256];
  uint4 C[4][2][256];
  uint4 B[128][2][256];
  uint32_t T[32][32];
  uint32_t S[128];
  unsigned ctr[64];
};
__device__ __align__(1024) uint4 g_xraw[(sizeof(Xchg) + (1 << 21)) / 16];
__device__ __align__(1024) uint4 g_y[1024 * 256];
__device__ __align__(1024) uint4 g_wt[513 * 512];
__device__ int g_err;

__device__ __forceinline__ unsigned clk() { unsigned long long c; asm volatile("mov.u64 %0, %%clock64;" : "=l"(c)); return (unsigned)c; }
__device__ __forceinline__ uint32_t smem_u32(const void* p) { return (uint32_t)__cvta_generic_to_shared(p); }
__device__ __forceinline__ void mbar_init(uint32_t bar, int cnt) { asm volatile("mbarrier.init.shared::cta.b64 [%0], %1;" :: "r"(bar), "r"(cnt) : "memory"); }
__device__ __forceinline__ void mbar_expect_tx(uint32_t bar, int bytes) { asm volatile("mbarrier.arrive.expect_tx.shared::cta.b64 _, [%0], %1;" :: "r"(bar), "r"(bytes) : "memory"); }
__device__ __forceinline__ void mbar_arrive(uint32_t bar) { asm volatile("mbarrier.arrive.shared::cta.b64 _, [%0];" :: "r"(bar) : "memory"); }
__device__ __forceinline__ void mbar_arrive_cluster(uint32_t bar, int cta) {
  asm volatile("{.reg .b32 r; mapa.shared::cluster.u32 r, %0, %1; mbarrier.arrive.shared::cluster.b64 _, [r];}" :: "r"(bar), "r"(cta) : "memory"); }
__device__ __forceinline__ bool mbar_try(uint32_t bar, int par) {
  uint32_t ok; asm volatile("{.reg .pred p; mbarrier.try_wait.parity.shared::cta.b64 p, [%1], %2; selp.u32 %0, 1, 0, p;}" : "=r"(ok) : "r"(bar), "r"(par) : "memory"); return ok; }
__device__ __forceinline__ bool mbar_test(uint32_t bar, int par) {
  uint32_t ok; asm volatile("{.reg .pred p; mbarrier.test_wait.parity.shared::cta.b64 p, [%1], %2; selp.u32 %0, 1, 0, p;}" : "=r"(ok) : "r"(bar), "r"(par) : "memory"); return ok; }
__device__ __forceinline__ void mbar_wait(uint32_t bar, int par) {
  int it = 0;
  while (!mbar_try(bar, par)) { if (++it > SPIN_LIMIT) { g_err = 1; break; } }
}
__device__ __forceinline__ void tma2d(uint32_t dst, const CUtensorMap* m, int c0, int c1, uint32_t bar) {
  asm volatile("cp.async.bulk.tensor.2d.shared::cluster.global.mbarrier::complete_tx::bytes [%0], [%1, {%3, %4}], [%2];"
    :: "r"(dst), "l"(m), "r"(bar), "r"(c0), "r"(c1) : "memory"); }
__device__ __forceinline__ void tma2d_mc(uint32_t dst, const CUtensorMap* m, int c0, int c1, uint32_t bar, uint16_t mask) {
  asm volatile("cp.async.bulk.tensor.2d.shared::cluster.global.mbarrier::complete_tx::bytes.multicast::cluster [%0], [%1, {%3, %4}], [%2], %5;"
    :: "r"(dst), "l"(m), "r"(bar), "r"(c0), "r"(c1), "h"(mask) : "memory"); }
__device__ __forceinline__ void tma2d_store(const CUtensorMap* m, uint32_t src, int c0, int c1) {
  asm volatile("cp.async.bulk.tensor.2d.global.shared::cta.bulk_group [%0, {%2, %3}], [%1];" :: "l"(m), "r"(src), "r"(c0), "r"(c1) : "memory"); }
__device__ __forceinline__ void fence_async() { asm volatile("fence.proxy.async.shared::cta;" ::: "memory"); }
__device__ __forceinline__ void bar_sync(int id, int n) { asm volatile("bar.sync %0, %1;" :: "r"(id), "r"(n) : "memory"); }
__device__ __forceinline__ void bar_arrive(int id, int n) { asm volatile("bar.arrive %0, %1;" :: "r"(id), "r"(n) : "memory"); }
__device__ __forceinline__ uint32_t pack2(float lo, float hi) { uint32_t r; asm("cvt.rn.bf16x2.f32 %0, %1, %2;" : "=r"(r) : "f"(hi), "f"(lo)); return r; }
__device__ __forceinline__ uint32_t pack2_tag(float lo, float hi, uint32_t T) {
  uint32_t u = ((__float_as_uint(lo) - T + 0x10000u) & 0xFFFE0000u) + T;
  return __byte_perm(u, pack2(0.f, hi), 0x7632); }
__device__ __forceinline__ void ldsm4(uint32_t (&r)[4], uint32_t a) {
  asm volatile("ldmatrix.sync.aligned.m8n8.x4.shared.b16 {%0,%1,%2,%3}, [%4];" : "=r"(r[0]), "=r"(r[1]), "=r"(r[2]), "=r"(r[3]) : "r"(a) : "memory"); }
__device__ __forceinline__ void ldsm4t(uint32_t (&r)[4], uint32_t a) {
  asm volatile("ldmatrix.sync.aligned.m8n8.x4.trans.shared.b16 {%0,%1,%2,%3}, [%4];" : "=r"(r[0]), "=r"(r[1]), "=r"(r[2]), "=r"(r[3]) : "r"(a) : "memory"); }
__device__ __forceinline__ void stsm4(uint32_t a, uint32_t r0, uint32_t r1, uint32_t r2, uint32_t r3) {
  asm volatile("stmatrix.sync.aligned.m8n8.x4.shared.b16 [%0], {%1,%2,%3,%4};" :: "r"(a), "r"(r0), "r"(r1), "r"(r2), "r"(r3) : "memory"); }
__device__ __forceinline__ void stsm4t(uint32_t a, uint32_t r0, uint32_t r1, uint32_t r2, uint32_t r3) {
  asm volatile("stmatrix.sync.aligned.m8n8.x4.trans.shared.b16 [%0], {%1,%2,%3,%4};" :: "r"(a), "r"(r0), "r"(r1), "r"(r2), "r"(r3) : "memory"); }
__device__ __forceinline__ void lds128(uint32_t (&r)[4], uint32_t a) {
  asm volatile("ld.shared.v4.u32 {%0,%1,%2,%3}, [%4];" : "=r"(r[0]), "=r"(r[1]), "=r"(r[2]), "=r"(r[3]) : "r"(a) : "memory"); }
__device__ __forceinline__ float4 lds128f(uint32_t a) { float4 r;
  asm volatile("ld.shared.v4.f32 {%0,%1,%2,%3}, [%4];" : "=f"(r.x), "=f"(r.y), "=f"(r.z), "=f"(r.w) : "r"(a) : "memory"); return r; }
__device__ __forceinline__ float2 lds64f(uint32_t a) { float2 r;
  asm volatile("ld.shared.v2.f32 {%0,%1}, [%2];" : "=f"(r.x), "=f"(r.y) : "r"(a) : "memory"); return r; }
__device__ __forceinline__ void sts128(uint32_t a, uint32_t r0, uint32_t r1, uint32_t r2, uint32_t r3) {
  asm volatile("st.shared.v4.u32 [%0], {%1,%2,%3,%4};" :: "r"(a), "r"(r0), "r"(r1), "r"(r2), "r"(r3) : "memory"); }
__device__ __forceinline__ void sts64f(uint32_t a, float x, float y) { asm volatile("st.shared.v2.f32 [%0], {%1,%2};" :: "r"(a), "f"(x), "f"(y) : "memory"); }
__device__ __forceinline__ void sts32f(uint32_t a, float x) { asm volatile("st.shared.f32 [%0], %1;" :: "r"(a), "f"(x) : "memory"); }
__device__ __forceinline__ void mma16816(float (&d)[4], uint32_t a0, uint32_t a1, uint32_t a2, uint32_t a3, uint32_t b0, uint32_t b1) {
  asm volatile("mma.sync.aligned.m16n8k16.row.col.f32.bf16.bf16.f32 {%0,%1,%2,%3}, {%4,%5,%6,%7}, {%8,%9}, {%0,%1,%2,%3};"
    : "+f"(d[0]), "+f"(d[1]), "+f"(d[2]), "+f"(d[3]) : "r"(a0), "r"(a1), "r"(a2), "r"(a3), "r"(b0), "r"(b1)); }
__device__ __forceinline__ void mma1688(float (&d)[4], uint32_t a0, uint32_t a1, uint32_t b0) {
  asm volatile("mma.sync.aligned.m16n8k8.row.col.f32.bf16.bf16.f32 {%0,%1,%2,%3}, {%4,%5}, {%6}, {%0,%1,%2,%3};"
    : "+f"(d[0]), "+f"(d[1]), "+f"(d[2]), "+f"(d[3]) : "r"(a0), "r"(a1), "r"(b0)); }
__device__ __forceinline__ void ldx128(uint32_t (&r)[4], const void* p) {
  asm volatile("{.reg .b128 t; .reg .b64 a, b; ld.relaxed.gpu.global.b128 t, [%4]; mov.b128 {a, b}, t; mov.b64 {%0,%1}, a; mov.b64 {%2,%3}, b;}"
    : "=r"(r[0]), "=r"(r[1]), "=r"(r[2]), "=r"(r[3]) : "l"(p) : "memory"); }
__device__ __forceinline__ void ldx2x64(uint32_t (&r)[4], const void* p) {
  asm volatile("{.reg .b64 a, b; ld.relaxed.gpu.global.v2.b64 {a, b}, [%4]; mov.b64 {%0,%1}, a; mov.b64 {%2,%3}, b;}"
    : "=r"(r[0]), "=r"(r[1]), "=r"(r[2]), "=r"(r[3]) : "l"(p) : "memory"); }
__device__ __forceinline__ void stx128(void* p, uint32_t r0, uint32_t r1, uint32_t r2, uint32_t r3) {
  asm volatile("{.reg .b128 t; .reg .b64 a, b; mov.b64 a, {%1,%2}; mov.b64 b, {%3,%4}; mov.b128 t, {a, b}; st.relaxed.gpu.global.b128 [%0], t;}"
    :: "l"(p), "r"(r0), "r"(r1), "r"(r2), "r"(r3) : "memory"); }
__device__ __forceinline__ void stx64(void* p, uint32_t r0, uint32_t r1) {
  asm volatile("{.reg .b64 a; mov.b64 a, {%1,%2}; st.relaxed.gpu.global.b64 [%0], a;}" :: "l"(p), "r"(r0), "r"(r1) : "memory"); }
__device__ __forceinline__ uint32_t uni(uint32_t x) { return __shfl_sync(0xffffffffu, x, 0); }
__device__ __forceinline__ uint32_t pin(uint32_t x) { return __shfl_xor_sync(0xffffffffu, x, 0); }
__device__ __forceinline__ float ex2(float x) { float r; asm("ex2.approx.ftz.f32 %0, %1;" : "=f"(r) : "f"(x)); return r; }
__device__ __forceinline__ void wg_fence() { asm volatile("wgmma.fence.sync.aligned;" ::: "memory"); }
__device__ __forceinline__ void wg_commit() { asm volatile("wgmma.commit_group.sync.aligned;" ::: "memory"); }
template <int N> __device__ __forceinline__ void wg_wait() { asm volatile("wgmma.wait_group.sync.aligned %0;" :: "n"(N) : "memory"); }

__device__ __forceinline__ void wgmma_ss_n256_tb1(float (&d)[128], uint64_t da, uint64_t db, int sc) {
  asm volatile("{.reg .pred p; setp.ne.b32 p, %130, 0;\n"
    "wgmma.mma_async.sync.aligned.m64n256k16.f32.bf16.bf16 {%0,%1,%2,%3,%4,%5,%6,%7,%8,%9,%10,%11,%12,%13,%14,%15,%16,%17,%18,%19,%20,%21,%22,%23,%24,%25,%26,%27,%28,%29,%30,%31,%32,%33,%34,%35,%36,%37,%38,%39,%40,%41,%42,%43,%44,%45,%46,%47,%48,%49,%50,%51,%52,%53,%54,%55,%56,%57,%58,%59,%60,%61,%62,%63,%64,%65,%66,%67,%68,%69,%70,%71,%72,%73,%74,%75,%76,%77,%78,%79,%80,%81,%82,%83,%84,%85,%86,%87,%88,%89,%90,%91,%92,%93,%94,%95,%96,%97,%98,%99,%100,%101,%102,%103,%104,%105,%106,%107,%108,%109,%110,%111,%112,%113,%114,%115,%116,%117,%118,%119,%120,%121,%122,%123,%124,%125,%126,%127}, %128, %129, p, 1, 1, 0, 1;}\n"
    : "+f"(d[0]),"+f"(d[1]),"+f"(d[2]),"+f"(d[3]),"+f"(d[4]),"+f"(d[5]),"+f"(d[6]),"+f"(d[7]),"+f"(d[8]),"+f"(d[9]),"+f"(d[10]),"+f"(d[11]),"+f"(d[12]),"+f"(d[13]),"+f"(d[14]),"+f"(d[15]),"+f"(d[16]),"+f"(d[17]),"+f"(d[18]),"+f"(d[19]),"+f"(d[20]),"+f"(d[21]),"+f"(d[22]),"+f"(d[23]),"+f"(d[24]),"+f"(d[25]),"+f"(d[26]),"+f"(d[27]),"+f"(d[28]),"+f"(d[29]),"+f"(d[30]),"+f"(d[31]),"+f"(d[32]),"+f"(d[33]),"+f"(d[34]),"+f"(d[35]),"+f"(d[36]),"+f"(d[37]),"+f"(d[38]),"+f"(d[39]),"+f"(d[40]),"+f"(d[41]),"+f"(d[42]),"+f"(d[43]),"+f"(d[44]),"+f"(d[45]),"+f"(d[46]),"+f"(d[47]),"+f"(d[48]),"+f"(d[49]),"+f"(d[50]),"+f"(d[51]),"+f"(d[52]),"+f"(d[53]),"+f"(d[54]),"+f"(d[55]),"+f"(d[56]),"+f"(d[57]),"+f"(d[58]),"+f"(d[59]),"+f"(d[60]),"+f"(d[61]),"+f"(d[62]),"+f"(d[63]),"+f"(d[64]),"+f"(d[65]),"+f"(d[66]),"+f"(d[67]),"+f"(d[68]),"+f"(d[69]),"+f"(d[70]),"+f"(d[71]),"+f"(d[72]),"+f"(d[73]),"+f"(d[74]),"+f"(d[75]),"+f"(d[76]),"+f"(d[77]),"+f"(d[78]),"+f"(d[79]),"+f"(d[80]),"+f"(d[81]),"+f"(d[82]),"+f"(d[83]),"+f"(d[84]),"+f"(d[85]),"+f"(d[86]),"+f"(d[87]),"+f"(d[88]),"+f"(d[89]),"+f"(d[90]),"+f"(d[91]),"+f"(d[92]),"+f"(d[93]),"+f"(d[94]),"+f"(d[95]),"+f"(d[96]),"+f"(d[97]),"+f"(d[98]),"+f"(d[99]),"+f"(d[100]),"+f"(d[101]),"+f"(d[102]),"+f"(d[103]),"+f"(d[104]),"+f"(d[105]),"+f"(d[106]),"+f"(d[107]),"+f"(d[108]),"+f"(d[109]),"+f"(d[110]),"+f"(d[111]),"+f"(d[112]),"+f"(d[113]),"+f"(d[114]),"+f"(d[115]),"+f"(d[116]),"+f"(d[117]),"+f"(d[118]),"+f"(d[119]),"+f"(d[120]),"+f"(d[121]),"+f"(d[122]),"+f"(d[123]),"+f"(d[124]),"+f"(d[125]),"+f"(d[126]),"+f"(d[127])
    : "l"(da), "l"(db), "r"(sc));
}

__device__ __forceinline__ void wgmma_ss_n128_tb1(float (&d)[64], uint64_t da, uint64_t db, int sc) {
  asm volatile("{.reg .pred p; setp.ne.b32 p, %66, 0;\n"
    "wgmma.mma_async.sync.aligned.m64n128k16.f32.bf16.bf16 {%0,%1,%2,%3,%4,%5,%6,%7,%8,%9,%10,%11,%12,%13,%14,%15,%16,%17,%18,%19,%20,%21,%22,%23,%24,%25,%26,%27,%28,%29,%30,%31,%32,%33,%34,%35,%36,%37,%38,%39,%40,%41,%42,%43,%44,%45,%46,%47,%48,%49,%50,%51,%52,%53,%54,%55,%56,%57,%58,%59,%60,%61,%62,%63}, %64, %65, p, 1, 1, 0, 1;}\n"
    : "+f"(d[0]),"+f"(d[1]),"+f"(d[2]),"+f"(d[3]),"+f"(d[4]),"+f"(d[5]),"+f"(d[6]),"+f"(d[7]),"+f"(d[8]),"+f"(d[9]),"+f"(d[10]),"+f"(d[11]),"+f"(d[12]),"+f"(d[13]),"+f"(d[14]),"+f"(d[15]),"+f"(d[16]),"+f"(d[17]),"+f"(d[18]),"+f"(d[19]),"+f"(d[20]),"+f"(d[21]),"+f"(d[22]),"+f"(d[23]),"+f"(d[24]),"+f"(d[25]),"+f"(d[26]),"+f"(d[27]),"+f"(d[28]),"+f"(d[29]),"+f"(d[30]),"+f"(d[31]),"+f"(d[32]),"+f"(d[33]),"+f"(d[34]),"+f"(d[35]),"+f"(d[36]),"+f"(d[37]),"+f"(d[38]),"+f"(d[39]),"+f"(d[40]),"+f"(d[41]),"+f"(d[42]),"+f"(d[43]),"+f"(d[44]),"+f"(d[45]),"+f"(d[46]),"+f"(d[47]),"+f"(d[48]),"+f"(d[49]),"+f"(d[50]),"+f"(d[51]),"+f"(d[52]),"+f"(d[53]),"+f"(d[54]),"+f"(d[55]),"+f"(d[56]),"+f"(d[57]),"+f"(d[58]),"+f"(d[59]),"+f"(d[60]),"+f"(d[61]),"+f"(d[62]),"+f"(d[63])
    : "l"(da), "l"(db), "r"(sc));
}

template <int BN> struct WG;
template <> struct WG<256> { static __device__ __forceinline__ void mma(float (&d)[128], uint64_t a, uint64_t b, int sc) { wgmma_ss_n256_tb1(d, a, b, sc); } };
template <> struct WG<128> { static __device__ __forceinline__ void mma(float (&d)[64], uint64_t a, uint64_t b, int sc) { wgmma_ss_n128_tb1(d, a, b, sc); } };

struct GemmMaps { CUtensorMap a, b[3], c; };
template <int BN, int STAGES>
__global__ void __cluster_dims__(2, 1, 1) __launch_bounds__(384, 1)
gemm_kernel(const __grid_constant__ GemmMaps maps, int tilesM, int tilesN, int kblocks, int nPerB, uint4* __restrict__ clearX) {
  extern __shared__ __align__(1024) uint8_t smem_raw[];
  constexpr int STAGE_BYTES = 16384 + BN * 128;
  constexpr int NBOX = BN / 64;
  const uint32_t sbase = (smem_u32(smem_raw) + 1023) & ~1023u;
  const uint32_t sEpi = sbase + STAGES * STAGE_BYTES;
  const uint32_t sBar = sEpi + 32768;
  const int warp = threadIdx.x >> 5, lane = threadIdx.x & 31, wg = warp >> 2;
  uint32_t crank; asm("mov.u32 %0, %%cluster_ctarank;" : "=r"(crank));
  if (threadIdx.x == 0) {
    for (int i = 0; i < STAGES; i++) { mbar_init(sBar + 8 * i, 1); mbar_init(sBar + 8 * (STAGES + i), 4); }
    asm volatile("fence.mbarrier_init.release.cluster;" ::: "memory");
  }
  for (int i = blockIdx.x * 384 + threadIdx.x; i < (int)(sizeof(Xchg) / 16); i += gridDim.x * 384) clearX[i] = make_uint4(0, 0, 0, 0);
  asm volatile("barrier.cluster.arrive.release.aligned; barrier.cluster.wait.acquire.aligned;" ::: "memory");
  const int npairs = (tilesM >> 1) * tilesN, pair0 = blockIdx.x >> 1, pstep = gridDim.x >> 1;
  if (wg == 2) {
    asm volatile("setmaxnreg.dec.sync.aligned.u32 40;");
    if (warp == 8 && lane == 0) {
      int st = 0, ph = 1;
      for (int p = pair0; p < npairs; p += pstep) {
        const int tm = (p % (tilesM >> 1)) * 2 + crank, tn = p / (tilesM >> 1);
        const CUtensorMap* mb = &maps.b[tn / nPerB];
        const int n0 = (tn % nPerB) * BN;
        for (int kb = 0; kb < kblocks; kb++) {
          mbar_wait(sBar + 8 * (STAGES + st), ph);
          const uint32_t a = sbase + st * STAGE_BYTES, full = sBar + 8 * st;
          mbar_expect_tx(full, STAGE_BYTES);
          tma2d(a, &maps.a, kb * 64, tm * 128, full);
#pragma unroll
          for (int i = 0; i < NBOX / 2; i++) {
            const int bx = crank * (NBOX / 2) + i;
            tma2d_mc(a + 16384 + bx * 8192, mb, n0 + bx * 64, kb * 64, full, (uint16_t)3);
          }
          if (++st == STAGES) { st = 0; ph ^= 1; }
        }
      }
      for (int i = 0; i < STAGES; i++) { mbar_wait(sBar + 8 * (STAGES + st), ph); if (++st == STAGES) { st = 0; ph ^= 1; } }
    }
  } else {
    asm volatile("setmaxnreg.inc.sync.aligned.u32 232;");
    int st = 0, ph = 0;
    float acc[BN / 2];
    const uint64_t descA0 = (uint64_t)(((sbase + wg * 8192) & 0x3FFFF) >> 4) | (1ull << 16) | (64ull << 32) | (1ull << 62);
    const uint64_t descB0 = (uint64_t)(((sbase + 16384) & 0x3FFFF) >> 4) | (512ull << 16) | (64ull << 32) | (1ull << 62);
    const uint32_t epi = sEpi + wg * 16384;
    for (int p = pair0; p < npairs; p += pstep) {
      const int tm = (p % (tilesM >> 1)) * 2 + crank, tn = p / (tilesM >> 1);
      int prev = -1;
      for (int kb = 0; kb < kblocks; kb++) {
        mbar_wait(sBar + 8 * st, ph);
        wg_fence();
        const uint64_t so = (uint64_t)(st * (STAGE_BYTES >> 4));
#pragma unroll
        for (int k = 0; k < 4; k++) WG<BN>::mma(acc, descA0 + so + k * 2, descB0 + so + k * 128, kb | k);
        wg_commit();
        if (prev >= 0) {
          wg_wait<1>();
          if ((threadIdx.x & 127) < 2) mbar_arrive_cluster(sBar + 8 * (STAGES + prev), threadIdx.x & 1);
        }
        prev = st;
        if (++st == STAGES) { st = 0; ph ^= 1; }
      }
      wg_wait<0>();
      if ((threadIdx.x & 127) < 2) mbar_arrive_cluster(sBar + 8 * (STAGES + prev), threadIdx.x & 1);
#pragma unroll
      for (int r = 0; r < BN / 128; r++) {
        if ((threadIdx.x & 127) == 0) asm volatile("cp.async.bulk.wait_group.read 0;" ::: "memory");
        bar_sync(1 + wg, 128);
        const int row = (warp & 3) * 16 + (lane & 15);
#pragma unroll
        for (int i = 0; i < 8; i++) {
          const int c = 2 * (i & 3) + (lane >> 4);
          const float* q = &acc[r * 64 + i * 8];
          stsm4(epi + (i >> 2) * 8192 + row * 128 + ((c ^ (row & 7)) << 4), pack2(q[0], q[1]), pack2(q[2], q[3]), pack2(q[4], q[5]), pack2(q[6], q[7]));
        }
        fence_async();
        bar_sync(1 + wg, 128);
        if ((threadIdx.x & 127) == 0) {
          tma2d_store(&maps.c, epi, tn * BN + r * 128, tm * 128 + wg * 64);
          tma2d_store(&maps.c, epi + 8192, tn * BN + r * 128 + 64, tm * 128 + wg * 64);
          asm volatile("cp.async.bulk.commit_group;" ::: "memory");
        }
      }
    }
    if ((threadIdx.x & 127) == 0) asm volatile("cp.async.bulk.wait_group 0;" ::: "memory");
  }
}

struct Dft { uint32_t m[2][2][2][4]; };
template <bool P4> __device__ __forceinline__ int fidx(int tile, int x) { return P4 ? 4 * (x >> 1) + 2 * (tile & 1) + (x & 1) + 16 * (tile >> 1) : x + 8 * tile; }
__device__ __forceinline__ float2 cis(int k, int n) {
  k &= n - 1; if (2 * k > n) k -= n;
  const float a = (float)k * (6.283185307179586f / (float)n);
  return make_float2(__cosf(a), __sinf(a));
}
template <bool OUT4> __device__ __forceinline__ void make_dft(Dft& D, int g, int t) {
#pragma unroll
  for (int q = 0; q < 16; q++) {
    const int b = q >> 3, u = (q >> 2) & 1, r = (q >> 1) & 1, v = q & 1;
    const float2 w = cis(fidx<OUT4>(v, g) * fidx<false>(2 * u + r, 2 * t + b), 32);
    D.m[b][u][0][q & 3] = pack2(w.x, w.y); D.m[b][u][1][q & 3] = pack2(-w.y, w.x);
  }
}
__device__ __forceinline__ void mma_dc(float (&d)[4], uint32_t a0, uint32_t a1, uint32_t a2, uint32_t a3, uint32_t b0, uint32_t b1, const float (&c)[4]) {
  asm("mma.sync.aligned.m16n8k16.row.col.f32.bf16.bf16.f32 {%0,%1,%2,%3}, {%4,%5,%6,%7}, {%8,%9}, {%10,%11,%12,%13};"
    : "=f"(d[0]), "=f"(d[1]), "=f"(d[2]), "=f"(d[3]) : "r"(a0), "r"(a1), "r"(a2), "r"(a3), "r"(b0), "r"(b1), "f"(c[0]), "f"(c[1]), "f"(c[2]), "f"(c[3])); }
__device__ __forceinline__ void dft_b(const Dft& D, const uint32_t (&x)[2][4], float (&o)[2][8]) {
#pragma unroll
  for (int ri = 0; ri < 2; ri++) {
    float z[4] = {0.f, 0.f, 0.f, 0.f}, e[4], p[4];
    mma_dc(e, D.m[0][0][ri][0], D.m[0][0][ri][1], D.m[0][0][ri][2], D.m[0][0][ri][3], x[0][0], x[0][1], z);
    mma_dc(e, D.m[0][1][ri][0], D.m[0][1][ri][1], D.m[0][1][ri][2], D.m[0][1][ri][3], x[0][2], x[0][3], e);
    mma_dc(p, D.m[1][0][ri][0], D.m[1][0][ri][1], D.m[1][0][ri][2], D.m[1][0][ri][3], x[1][0], x[1][1], e);
    mma_dc(p, D.m[1][1][ri][0], D.m[1][1][ri][1], D.m[1][1][ri][2], D.m[1][1][ri][3], x[1][2], x[1][3], p);
#pragma unroll
    for (int q = 0; q < 4; q++) { o[ri][q] = p[q]; o[ri][4 + q] = fmaf(2.f, e[q], -p[q]); }
  }
}
__device__ __forceinline__ void dft_a(const uint32_t (&m)[2][2][4], const uint32_t (&x0)[2][4], const uint32_t (&x1)[2][4], float (&o)[2][8]) {
#pragma unroll
  for (int ri = 0; ri < 2; ri++) {
    float z[4] = {0.f, 0.f, 0.f, 0.f}, e[4], p[4];
    mma_dc(e, x0[0][0], x1[0][0], x0[0][1], x1[0][1], m[0][ri][0], m[0][ri][1], z);
    mma_dc(e, x0[0][2], x1[0][2], x0[0][3], x1[0][3], m[0][ri][2], m[0][ri][3], e);
    mma_dc(p, x0[1][0], x1[1][0], x0[1][1], x1[1][1], m[1][ri][0], m[1][ri][1], e);
    mma_dc(p, x0[1][2], x1[1][2], x0[1][3], x1[1][3], m[1][ri][2], m[1][ri][3], p);
#pragma unroll
    for (int q = 0; q < 4; q++) { o[ri][q] = p[q]; o[ri][4 + q] = fmaf(2.f, e[q], -p[q]); }
  }
}
__device__ __forceinline__ uint32_t twid(float re, float im, float c, float s) { return pack2(fmaf(re, c, im * s), fmaf(im, c, -re * s)); }
__device__ __forceinline__ void cpa16(uint32_t d, const void* s) { asm volatile("cp.async.cg.shared.global [%0], [%1], 16;" :: "r"(d), "l"(s) : "memory"); }
__device__ __forceinline__ void sts32(uint32_t a, uint32_t x) { asm volatile("st.shared.u32 [%0], %1;" :: "r"(a), "r"(x) : "memory"); }
__device__ __forceinline__ void cpa_commit() { asm volatile("cp.async.commit_group;" ::: "memory"); }
template <int N> __device__ __forceinline__ void cpa_wait() { asm volatile("cp.async.wait_group %0;" :: "n"(N) : "memory"); }
__device__ __forceinline__ uint32_t lds32(uint32_t a) { uint32_t r; asm volatile("ld.shared.u32 %0, [%1];" : "=r"(r) : "r"(a) : "memory"); return r; }
#define FMID 0
constexpr int F_TP = 4112, F_TSZ = 8 * F_TP;

__device__ __forceinline__ uint32_t ldnc32(const void* p) { uint32_t v; asm volatile("ld.global.nc.b32 %0, [%1];" : "=r"(v) : "l"(p) : "memory"); return v; }
template <class F>
__device__ __forceinline__ void fft_wprep(const bf16* __restrict__ wr, const bf16* __restrict__ wi, int cta, F&& mid) {
  const int tid = threadIdx.x, g = (cta >> 1) & 7, c = (cta >> 4) & 3, t = 2 * (cta & 1) + (tid & 1);
  const int k0 = g + 8 * (cta >> 6) + 32 * (8 * c + 2 * t), l0 = (tid & ~1) + (g & 1);
  uint32_t a[4][4], b[4][4];
#pragma unroll
  for (int q = 0; q < 16; q++) {
    const int o = (k0 + 16 * (q >> 3) + 32 * ((q >> 1) & 1) + 1024 * (q & 1)) * 513 + l0 + 256 * ((q >> 2) & 1);
    a[q >> 2][q & 3] = ldnc32(wr + o);
    b[q >> 2][q & 3] = ldnc32(wi + o);
  }
  const int e = cta * 32 + (tid & 31), lh = (e >> 11) * 512, k = e & 2047, k2 = (k >> 5) & 31;
  uint32_t hz[4];
#pragma unroll
  for (int q = 0; q < 4; q++) asm volatile("ld.global.nc.u16 %0, [%1];" : "=r"(hz[q]) : "l"((q < 2 ? wr : wi) + (q & 1 ? (2048 - k) & 2047 : k) * 513 + lh) : "memory");
  mid();
  uint4* dst = g_wt + l0 * 512 + cta * 2 + (tid & 1);
#pragma unroll
  for (int q = 0; q < 8; q++) {
    const int hf = q >> 1, l = l0 + 256 * (hf & 1) + (q & 1);
    const uint32_t sel = (q & 1) ? 0x7632 : 0x5410;
    if (l & 511) dst[(256 * (hf & 1) + (q & 1)) * 512 + 256 * (q >> 2)] = make_uint4(__byte_perm(a[hf][0], b[hf][0], sel), __byte_perm(a[hf][1], b[hf][1], sel),
                                                                                   __byte_perm(a[hf][2], b[hf][2], sel), __byte_perm(a[hf][3], b[hf][3], sel));
  }
  if (tid < 32) reinterpret_cast<uint32_t*>(g_wt)[(64 * ((k >> 3) & 3) + 16 * (k2 >> 3) + 2 * (k & 7) + ((k2 >> 2) & 1)) * 8 + lh * 2048 + 2 * (k2 & 3) + (k >> 10)] =
      pack2(0.5f * (__uint_as_float(hz[0] << 16) + __uint_as_float(hz[1] << 16)), 0.5f * (__uint_as_float(hz[2] << 16) - __uint_as_float(hz[3] << 16)));
}

template <class F>
__device__ __forceinline__ void fft_rows_fwd(const bf16* __restrict__ x, const bf16* __restrict__ wr, const bf16* __restrict__ wi, uint32_t tb, int it, F&& mid) {
  const int warp = threadIdx.x >> 5, lane = threadIdx.x & 31, g = lane >> 2, t = lane & 3;
  const uint32_t in = tb + warp * 4096;
  const uint32_t f0 = in + (lane >> 3) * 256 + (((lane & 7) ^ (2 * (lane >> 3))) << 4);
  const bf16* src = x + ((256 * (warp & 3) + 64 * (warp >> 2) + 128 * (it & 1) + 32 * ((it >> 4) & 1) + 8 * (it >> 5) + ((it >> 1) & 7)) * 2048 + lane * 8);
#pragma unroll
  for (int q = 0; q < 8; q++) cpa16((f0 ^ ((q >> 2) * 144)) + (q & 3) * 1024, src + q * 256);
  cpa_commit();
  Dft D;
  float2 tw[4][8];
  fft_wprep(wr, wi, it, [&]() {
    if (FMID == 0) mid();
    make_dft<true>(D, g, t);
#pragma unroll
    for (int q = 0; q < 32; q++) {
      tw[q >> 3][q & 7] = cis(fidx<true>((q >> 1) & 3, g) * fidx<false>(q >> 3, 2 * t + (q & 1)), 1024);
      if (FMID) asm volatile("" : "+f"(tw[q >> 3][q & 7].x), "+f"(tw[q >> 3][q & 7].y) :: "memory");
    }
    if (FMID == 1) mid();
  });
  if (FMID == 2) mid();
  cpa_wait<0>(); __syncwarp();
  uint32_t a[4][2][4], y[4][2][4];
#pragma unroll
  for (int q = 0; q < 8; q++) ldsm4t(a[q & 3][q >> 2], (in + lane * 128 + ((lane & 7) << 4)) ^ (q << 4));
  float o[2][8];
#pragma unroll
  for (int i = 0; i < 4; i++) {
    dft_b(D, a[i], o);
#pragma unroll
    for (int q = 0; q < 8; q++) y[q >> 1][q & 1][i] = twid(o[0][q], o[1][q], tw[i][q].x, tw[i][q].y);
  }
  __syncthreads();
  const uint32_t w0 = tb + warp * F_TP + fidx<true>(0, g) * 128 + t * 16 + ((g & 1) << 6), wz = (g & 1) ? -64 : 64;
#pragma unroll
  for (int z = 0; z < 2; z++) {
    float o2[2][8];
    dft_b(D, y[2 * z], o); dft_b(D, y[2 * z + 1], o2);
#pragma unroll
    for (int i = 0; i < 4; i++) {
      const float sg = i < 2 ? 1.f : -1.f;
      sts128(w0 + z * wz + fidx<true>(i, 0) * 128, pack2(o[0][2 * i], sg * o[1][2 * i]), pack2(o[0][2 * i + 1], sg * o[1][2 * i + 1]),
             pack2(o2[0][2 * i], sg * o2[1][2 * i]), pack2(o2[0][2 * i + 1], sg * o2[1][2 * i + 1]));
    }
  }
  __syncthreads();
  const uint32_t ra = tb + (lane & 1) * 4 * F_TP + ((lane >> 1) + 16 * (warp ^ ((warp >> 1) & 1))) * 4;
  uint4* dst = g_y + (threadIdx.x >> 1) * 256 + (lane & 1) + it * 2;
#pragma unroll
  for (int q = 0; q < 8; q++) { const uint32_t r = ra + q * 512; dst[q * 32768] = make_uint4(lds32(r), lds32(r + F_TP), lds32(r + 2 * F_TP), lds32(r + 3 * F_TP)); }
}

template <class F>
__device__ __forceinline__ void fft_cols(uint32_t sb, int cta, int ncta, F&& ready) {
  const int warp = threadIdx.x >> 5, lane = threadIdx.x & 31, g = lane >> 2, t = lane & 3;
  const uint32_t in = sb + warp * 16384 + lane * 16, tab = sb + 131072 + lane * 16;
  auto fetch_y = [&](int l) {
#pragma unroll
    for (int q = 0; q < 16; q++) cpa16(in + q * 512, g_y + (q < 8 ? l : (1024 - l) & 1023) * 256 + (q & 7) * 32 + lane);
  };
  auto fetch_w = [&](int l) {
#pragma unroll
    for (int q = 0; q < 16; q++) cpa16(in + 8192 + q * 512, g_wt + l * 512 + q * 32 + lane);
  };
  const int l0 = cta * 8 + warp, dl = ncta * 8;
  Dft D; make_dft<false>(D, g, t);
#pragma unroll
  for (int q = 2 * warp; q < 2 * warp + 2; q++) {
    const int r = fidx<false>(q & 3, g), c = fidx<false>(q >> 2, 2 * t);
    const float2 w0 = cis(r * c, 1024), w1 = cis(r * c + r, 1024), p0 = cis(r + 32 * c, 2048), p1 = cis(r + 32 * c + 32, 2048);
    sts128(tab + q * 512, __float_as_uint(w0.x), __float_as_uint(w0.y), __float_as_uint(w1.x), __float_as_uint(w1.y));
    sts128(tab + 8192 + q * 512, __float_as_uint(p0.x), __float_as_uint(p0.y), __float_as_uint(p1.x), __float_as_uint(p1.y));
  }
  if (warp == 0) {
#pragma unroll
    for (int q = 0; q < 8; q++) {
      const int v = q >> 2, b = (q >> 1) & 1, ri = q & 1;
      sts128(tab + 16384 + q * 512, D.m[b][0][ri][v], D.m[b][0][ri][v + 2], D.m[b][1][ri][v], D.m[b][1][ri][v + 2]);
    }
  }
  ready();
  fetch_y(l0); cpa_commit();
  fetch_w(l0); cpa_commit();
#pragma unroll 1
  for (int l = l0; l <= 512; l += dl) {
    uint32_t a[2][4][2][4], y[2][4][2][4];
    float o[2][2][8];
    cpa_wait<1>();
#pragma unroll
    for (int q = 0; q < 16; q++) lds128(a[q >> 3][(q >> 1) & 3][q & 1], in + q * 512);
    if (!(l & 511)) {
      const uint32_t m0 = l ? 0x80000000u : 0u;
#pragma unroll
      for (int q = 0; q < 32; q++) { a[0][q >> 3][(q >> 2) & 1][q & 3] ^= m0; a[1][q >> 3][(q >> 2) & 1][q & 3] ^= m0 ^ 0x80000000u; }
    }
    auto first = [&]() {
#pragma unroll
      for (int i = 0; i < 4; i++) {
        dft_b(D, a[0][i], o[0]); dft_b(D, a[1][i], o[1]);
#pragma unroll
        for (int r = 0; r < 4; r++) {
          const float4 w = lds128f(tab + (4 * i + r) * 512);
#pragma unroll
          for (int s = 0; s < 2; s++) {
            y[s][r][0][i] = twid(o[s][0][2 * r], o[s][1][2 * r], w.x, w.y);
            y[s][r][1][i] = twid(o[s][0][2 * r + 1], o[s][1][2 * r + 1], w.z, w.w);
          }
        }
      }
    };
    first();
    if (l + dl <= 512) fetch_y(l + dl);
    cpa_commit();
    cpa_wait<1>();
#pragma unroll
    for (int zv = 0; zv < 4; zv++) {
      const int z = zv >> 1, v = zv & 1;
      uint32_t m[2][2][4];
#pragma unroll
      for (int q = 0; q < 4; q++) lds128(m[q >> 1][q & 1], tab + 16384 + (4 * v + q) * 512);
      dft_a(m, y[0][2 * z], y[0][2 * z + 1], o[0]); dft_a(m, y[1][2 * z], y[1][2 * z + 1], o[1]);
#pragma unroll
      for (int q = 0; q < 4; q++) {
        const int i = 2 * z + (q & 1), c = v + (q & 2);
        uint32_t w[4]; lds128(w, in + 8192 + (4 * i + c) * 512);
        const float4 ph = lds128f(tab + 8192 + (4 * c + i) * 512);
#pragma unroll
        for (int b = 0; b < 2; b++) {
          const float cs = b ? ph.z : ph.x, sn = b ? ph.w : ph.y;
          const float r1 = __uint_as_float(w[2 * b] << 16), i1 = __uint_as_float(w[2 * b] & 0xFFFF0000u);
          const float r2 = __uint_as_float(w[2 * b + 1] << 16), i2 = __uint_as_float(w[2 * b + 1] & 0xFFFF0000u);
          const float Sr = r1 + r2, Si = i1 + i2, Dr = r1 - r2, Di = i1 - i2;
          const float ar = fmaf(-Dr, sn, Sr), ai = fmaf(-Di, sn, Si), dr = fmaf(Dr, sn, Sr), di = fmaf(Di, sn, Si), br = -Di * cs, bi = Dr * cs;
          const float Ar = o[0][0][2 * q + b], Ai = o[0][1][2 * q + b], Br = o[1][0][2 * q + b], Bi = o[1][1][2 * q + b];
          a[0][i][b][c] = pack2(fmaf(ar, Ai, fmaf(ai, Ar, fmaf(br, Bi, bi * Br))), fmaf(ar, Ar, fmaf(-ai, Ai, fmaf(br, Br, -bi * Bi))));
          a[1][i][b][c] = pack2(fmaf(dr, Bi, fmaf(di, Br, fmaf(-br, Ai, -bi * Ar))), fmaf(dr, Br, fmaf(-di, Bi, fmaf(-br, Ar, bi * Ai))));
        }
      }
    }
    if (l + dl <= 512) fetch_w(l + dl);
    cpa_commit();
    first();
#pragma unroll
    for (int s = 0; s < 2; s++) {
      uint4* dst = g_y + (s ? (1024 - l) & 1023 : l) * 256 + lane;
      const float sg = s ? -1.f : 1.f;
#pragma unroll
      for (int i = 0; i < 4; i++) {
        dft_b(D, y[s][i], o[0]);
#pragma unroll
        for (int b = 0; b < 2; b++)
          dst[(2 * i + b) * 32] = make_uint4(pack2(sg * o[0][0][b], o[0][1][b]), pack2(sg * o[0][0][2 + b], o[0][1][2 + b]),
                                             pack2(sg * o[0][0][4 + b], o[0][1][4 + b]), pack2(sg * o[0][0][6 + b], o[0][1][6 + b]));
      }
    }
  }
}

template <class F>
__device__ __forceinline__ void fft_rows_inv(const CUtensorMap* om, uint32_t sb, int cta, int ncta, F&& ready) {
  const int warp = threadIdx.x >> 5, lane = threadIdx.x & 31, g = lane >> 2, t = lane & 3, wg = warp >> 2, w4 = warp & 3;
  const uint32_t tb = sb + 32768 + wg * 2 * F_TSZ;
  const uint4* src = g_y + pin((256 * ((lane >> 1) & 3) + 64 * (lane >> 3) + 8 * w4) * 256 + (lane & 1));
  const uint32_t wa = pin(tb + (lane & 1) * 4 * F_TP + w4 * 1024 + (lane >> 1) * 4);
  uint4 pf[8];
  auto fetch = [&](int it, int hf) {
#pragma unroll
    for (int q = 0; q < 8; q++) pf[q] = __ldcg(src + (it * 2 + hf * 8192) + q * 256);
  };
  auto put = [&](uint32_t off) {
#pragma unroll
    for (int q = 0; q < 8; q++) {
      sts32(wa + off + q * 64, pf[q].x); sts32(wa + off + q * 64 + F_TP, pf[q].y);
      sts32(wa + off + q * 64 + 2 * F_TP, pf[q].z); sts32(wa + off + q * 64 + 3 * F_TP, pf[q].w);
    }
  };
  const int it0 = 2 * cta + wg;
  Dft D; make_dft<false>(D, g, t);
  float2 tw[4][8];
#pragma unroll
  for (int q = 0; q < 32; q++) {
    tw[q >> 3][q & 7] = cis(fidx<false>((q >> 1) & 3, g) * fidx<false>(q >> 3, 2 * t + (q & 1)), 1024);
    tw[q >> 3][q & 7].x *= 1.f / 2097152.f; tw[q >> 3][q & 7].y *= 1.f / 2097152.f;
    asm volatile("" : "+f"(tw[q >> 3][q & 7].x), "+f"(tw[q >> 3][q & 7].y) :: "memory");
  }
  ready();
  fetch(it0, 0); put(0); fetch(it0, 1); put(512);
  const uint32_t la = pin(tb + w4 * F_TP + lane * 16), ob = uni(sb + warp * 4096);
  const uint32_t oa = pin(ob + (lane >> 1) * 128 + (((4 * (lane & 1)) ^ ((lane >> 1) & 7)) << 4));
#pragma unroll 1
  for (int n = 0;; n++) {
    const int it = it0 + (n >> 1) * 2 * ncta, hf = n & 1, buf = (n >> 1) & 1;
    if (it >= 128) break;
    if (!hf) bar_sync(1 + wg, 128);
    uint32_t a[4][2][4], y[4][2][4];
#pragma unroll
    for (int q = 0; q < 8; q++) lds128(a[q >> 1][q & 1], la + buf * F_TSZ + hf * 4 * F_TP + q * 512);
    fetch(min(it + 2 * ncta, 127), hf);
    float o[2][8];
#pragma unroll
    for (int i = 0; i < 4; i++) {
      dft_b(D, a[i], o);
#pragma unroll
      for (int q = 0; q < 8; q++) y[q >> 1][q & 1][i] = twid(o[0][q], o[1][q], tw[i][q].x, tw[i][q].y);
    }
    if (lane == 0) asm volatile("cp.async.bulk.wait_group.read 0;" ::: "memory");
    __syncwarp();
#pragma unroll
    for (int c = 0; c < 4; c++) {
      dft_b(D, y[c], o);
#pragma unroll
      for (int ri = 0; ri < 2; ri++)
        stsm4((oa ^ (c << 4)) + (1 - ri) * 2048, pack2(o[ri][0], o[ri][1]), pack2(o[ri][2], o[ri][3]), pack2(o[ri][4], o[ri][5]), pack2(o[ri][6], o[ri][7]));
    }
    fence_async();
    __syncwarp();
    if (lane == 0) {
      const int m = 256 * w4 + 32 * ((it >> 1) & 7) + 8 * (it >> 5) + 4 * (it & 1) + 2 * hf + ((it >> 4) & 1);
      asm volatile("cp.async.bulk.tensor.3d.global.shared::cta.bulk_group [%0, {0, 0, %2}], [%1];" :: "l"(om), "r"(ob), "r"(2 * m) : "memory");
      asm volatile("cp.async.bulk.commit_group;" ::: "memory");
    }
    put((buf ^ 1) * F_TSZ + hf * 512);
  }
  if (lane == 0) asm volatile("cp.async.bulk.wait_group 0;" ::: "memory");
}
__device__ __forceinline__ void grid_arrive(unsigned* ctr) {
  __syncthreads();
  if (threadIdx.x == 0) { __threadfence(); atomicAdd(ctr, 1u); }
}
__device__ __forceinline__ void grid_wait(unsigned* ctr, unsigned n) {
  if (threadIdx.x == 224) {
    int it = 0;
    while (*reinterpret_cast<volatile unsigned*>(ctr) < n) { __nanosleep(100); if (++it > SPIN_LIMIT) { g_err = 3; break; } }
    __threadfence();
  }
  __syncthreads();
}

struct RecMaps { CUtensorMap wq, wk, wv, wo, x, k, q, v, fo; };
#define NSW 16
#define EXP 0
#define NPB 3
#define NPB0 3
#define NPC 0
#define WOP 2
#define HOME 7
#define DL0 14
#define PD1 4
#define NE4 6
#define NE6 0
#define NA4 14
#define NA6 18
#define NB1 24
#define TQL 7
#define NQ 16
#define TQP (NQ - 1)
#define OXPOS 4
#define KVPOS 2
#define NK0 0
#define FLPOS 1
#define XWPOS 10
#define FSPOS 28
#define RL0 4
#define RLS 6
#define RLB 4
#define VL0 3
#define RI 9
#define RJ 8
#define NPRE 22
#define PFD 4
#define PD0 4
#define VB NV0
#define NPA 0
#define N1 16
#define DL1 16
#define PACE 0
#define RE0 0
#define RE1 0
#define RP1 23
#define UNP 1
#define X2 2
#define X3 2
#define SPOS 2
#ifndef NV0
#define NV0 4
#endif
#define TGP 3
#define FENP 0
#define LW0 8
#define X1 4
#define X0 4
constexpr int R_WO = 0, R_X = 65536, R_MEM = 131072, R_WC = 147456, R_RED = R_WC + NSW * 2048, R_O = R_RED, R_S = R_O + 2048, R_P = R_S + 3072, R_STAGE = R_P + 2048,
              R_K = R_STAGE + 8192, R_Q = R_K + 8192, R_V = R_Q + 2048, R_ID = R_V + 16384, R_T = R_ID + 512, R_DST = R_T + 512, R_RD = R_DST + 2048, R_BAR = R_RD + 2048, R_TS = R_BAR + 128,
              R_TOTAL = R_TS;
#define TS(i)
#define LOG(i, v)
constexpr int B_KV = R_BAR, B_W = R_BAR + 8, B_X = R_BAR + 80, B_PK = R_BAR + 24, B_C = R_BAR + 32, B_B = R_BAR + 40, B_DUE = R_BAR + 48, B_ONE = R_BAR + 64;
#define DLY_A 150
#define DLY_V 150
#define DLY_C 200
#define DLY_L 90
#define NS_B 1120
#define NS_C 1728
#define NS_P 2624
#define NS_V 128
#define NS_F 896
#define NS_K 128
#define NS_M 32
#define NS_X 128
#define MG_Z 0x00010206
#define MG_Y 0x00010512
#define NS_PEN 1024
__device__ __forceinline__ float rcp(float x) { float r; asm("rcp.approx.ftz.f32 %0, %1;" : "=f"(r) : "f"(x)); return r; }
__device__ __forceinline__ uint32_t movm(uint32_t a) { uint32_t d; asm volatile("movmatrix.sync.aligned.m8n8.trans.b16 %0, %1;" : "=r"(d) : "r"(a)); return d; }
__device__ __forceinline__ uint32_t hadd2(uint32_t a, uint32_t b) { uint32_t d; asm("add.rn.bf16x2 %0, %1, %2;" : "=r"(d) : "r"(a), "r"(b)); return d; }
__device__ __forceinline__ void mma_a(float (&d)[4], const uint32_t (&a)[4], uint32_t b0, uint32_t b1) { mma16816(d, a[0], a[1], a[2], a[3], b0, b1); }
__device__ __forceinline__ bool elect() {
  uint32_t p; asm volatile("{.reg .pred p; elect.sync _|p, 0xffffffff; selp.u32 %0, 1, 0, p;}" : "=r"(p)); return p; }
__device__ __forceinline__ void tma3d(uint32_t dst, const CUtensorMap* m, int c1, int c2, uint32_t bar) {
  asm volatile("cp.async.bulk.tensor.3d.shared::cluster.global.mbarrier::complete_tx::bytes [%0], [%1, {0, %3, %4}], [%2];"
    :: "r"(dst), "l"(m), "r"(bar), "r"(c1), "r"(c2) : "memory"); }
__device__ __forceinline__ void tma4d(uint32_t dst, const CUtensorMap* m, int c1, int c2, uint32_t bar) {
  asm volatile("cp.async.bulk.tensor.4d.shared::cluster.global.mbarrier::complete_tx::bytes [%0], [%1, {0, %3, %4, 0}], [%2];"
    :: "r"(dst), "l"(m), "r"(bar), "r"(c1), "r"(c2) : "memory"); }
template <int OFF, int ACC>
__device__ __forceinline__ void wg_rs32(float (&d)[16], const uint32_t (&a)[4], uint32_t db) {
  if (ACC)
    asm volatile("{.reg .b64 db; .reg .b32 lo; add.u32 lo, %20, %21; mov.b64 db, {lo, 0x40000040};\n"
      "wgmma.mma_async.sync.aligned.m64n32k16.f32.bf16.bf16 {%0,%1,%2,%3,%4,%5,%6,%7,%8,%9,%10,%11,%12,%13,%14,%15}, {%16,%17,%18,%19}, db, 1, 1, 1, 0;}"
      : "+f"(d[0]), "+f"(d[1]), "+f"(d[2]), "+f"(d[3]), "+f"(d[4]), "+f"(d[5]), "+f"(d[6]), "+f"(d[7]), "+f"(d[8]), "+f"(d[9]), "+f"(d[10]), "+f"(d[11]), "+f"(d[12]), "+f"(d[13]), "+f"(d[14]), "+f"(d[15])
      : "r"(a[0]), "r"(a[1]), "r"(a[2]), "r"(a[3]), "r"(db), "n"(OFF));
  else
    asm volatile("{.reg .b64 db; .reg .b32 lo; add.u32 lo, %20, %21; mov.b64 db, {lo, 0x40000040};\n"
      "wgmma.mma_async.sync.aligned.m64n32k16.f32.bf16.bf16 {%0,%1,%2,%3,%4,%5,%6,%7,%8,%9,%10,%11,%12,%13,%14,%15}, {%16,%17,%18,%19}, db, 0, 1, 1, 0;}"
      : "=f"(d[0]), "=f"(d[1]), "=f"(d[2]), "=f"(d[3]), "=f"(d[4]), "=f"(d[5]), "=f"(d[6]), "=f"(d[7]), "=f"(d[8]), "=f"(d[9]), "=f"(d[10]), "=f"(d[11]), "=f"(d[12]), "=f"(d[13]), "=f"(d[14]), "=f"(d[15])
      : "r"(a[0]), "r"(a[1]), "r"(a[2]), "r"(a[3]), "r"(db), "n"(OFF));
}
template <int I> using IC = std::integral_constant<int, I>;
template <int I, int N, class F> __device__ __forceinline__ void sfor(F&& f) {
  if constexpr (I < N) { f(std::integral_constant<int, I>{}); sfor<I + 1, N>(f); }
}
__device__ __forceinline__ void keep(float (&d)[16]) {
  asm volatile("" : "+f"(d[0]), "+f"(d[1]), "+f"(d[2]), "+f"(d[3]), "+f"(d[4]), "+f"(d[5]), "+f"(d[6]), "+f"(d[7]),
      "+f"(d[8]), "+f"(d[9]), "+f"(d[10]), "+f"(d[11]), "+f"(d[12]), "+f"(d[13]), "+f"(d[14]), "+f"(d[15]) :: "memory");
}

template <int N, int S2 = 1024> __device__ __forceinline__ void ldx(uint32_t (&v)[N][4], const uint8_t* p) {
#pragma unroll
  for (int k = 0; k < 2 * N; k++) {
    const int i = k;
    asm volatile("ld.relaxed.gpu.global.v2.b32 {%0,%1}, [%2];" : "=r"(v[i >> 1][2 * (i & 1)]), "=r"(v[i >> 1][2 * (i & 1) + 1]) : "l"(p + (i & 3) * 256 + (i >> 2) * S2) : "memory");
  }
}
__device__ __forceinline__ uint32_t dif2(uint32_t a, uint32_t b, uint32_t tag) { uint32_t r; asm("lop3.b32 %0, %1, %2, %3, 0x7e;" : "=r"(r) : "r"(a), "r"(b), "r"(tag)); return r; }
__device__ __forceinline__ uint32_t dif2v(uint32_t a, uint32_t b, uint32_t tag) { uint32_t r; asm volatile("lop3.b32 %0, %1, %2, %3, 0x7e;" : "=r"(r) : "r"(a), "r"(b), "r"(tag)); return r; }
__device__ __forceinline__ uint32_t or3(uint32_t a, uint32_t b, uint32_t c) { uint32_t r; asm("lop3.b32 %0, %1, %2, %3, 0xfe;" : "=r"(r) : "r"(a), "r"(b), "r"(c)); return r; }
__device__ __forceinline__ uint32_t after(uint32_t x, float f, uint32_t z) { uint32_t r; asm("lop3.b32 %0, %1, %2, %3, 0xea;" : "=r"(r) : "r"(__float_as_uint(f)), "r"(z), "r"(x)); return r; }
__device__ __forceinline__ bool any_bit(uint32_t a, uint32_t b, uint32_t m) {
  uint32_t r; asm("lop3.b32 %0, %1, %2, %3, 0xa8;" : "=r"(r) : "r"(a), "r"(b), "r"(m)); return __any_sync(0xffffffffu, r); }
template <int W, int N> __device__ __forceinline__ bool stale(const uint32_t (&v)[N][4], uint32_t tag) {
  uint32_t x = dif2(v[0][0], v[0][2], tag);
  if (N == 4) x = or3(x, dif2(v[1][0], v[1][2], tag), dif2(v[2 % N][0], v[2 % N][2], tag));
  return any_bit(x, dif2(v[N - 1][0], v[N - 1][2], tag), 1);
}
template <int W, int N, int S2 = 1024> __device__ __forceinline__ void retry(uint32_t (&v)[N][4], const uint8_t* p, uint32_t tag, int& it) {
#pragma unroll 1
  do { ldx<N, S2>(v, p); it += INC_A; } while (stale<W>(v, tag) && it < SPIN_LIMIT);
}
__device__ __forceinline__ void mma_h(float (&d)[4], const uint32_t (&a)[4], const uint32_t (&b)[4], int hf) { mma16816(d, a[0], a[1], a[2], a[3], b[2 * hf], b[2 * hf + 1]); }
__device__ __forceinline__ void sts128(uint32_t a, const uint32_t (&r)[4]) { sts128(a, r[0], r[1], r[2], r[3]); }
__device__ __forceinline__ void sts128f(uint32_t a, const float* r) { sts128(a, __float_as_uint(r[0]), __float_as_uint(r[1]), __float_as_uint(r[2]), __float_as_uint(r[3])); }
__device__ __forceinline__ void mbar_spin(uint32_t bar, uint32_t par, int& it) {
  asm volatile("{.reg .pred p; .reg .b32 par; mov.b32 par, %2;\nLOOP: mbarrier.try_wait.parity.shared::cta.b64 p, [%1], par; @p bra.uni DONE;\n"
               "add.s32 %0, %0, 1; setp.le.s32 p, %0, %3; @p bra.uni LOOP;\nDONE: }" : "+r"(it) : "r"(bar), "r"(par), "n"(SPIN_LIMIT) : "memory"); }
__device__ __forceinline__ void warp_arrive(uint32_t bar) {
  __syncwarp(); asm volatile("{.reg .pred p; elect.sync _|p, 0xffffffff; @p mbarrier.arrive.shared::cta.b64 _, [%0];}" :: "r"(bar) : "memory"); }
__device__ __forceinline__ void delay_until(unsigned t) {
  asm volatile("{.reg .pred p; .reg .b64 c; .reg .b32 lo, hi;\nLOOP: mov.u64 c, %%clock64; mov.b64 {lo, hi}, c; sub.s32 lo, lo, %0; setp.lt.s32 p, lo, 0; @p bra.uni LOOP;}" :: "r"(t) : "memory"); }
__device__ __forceinline__ void cut(int it) { asm volatile("{.reg .pred p; setp.lt.s32 p, %0, 0;\nL: @p st.volatile.shared.u32 [%0], %0; @p bra.uni L;}" :: "r"(it) : "memory"); }
__device__ __forceinline__ void zero(float (&c)[4][4]) {
#pragma unroll
  for (int i = 0; i < 4; i++) c[i][0] = c[i][1] = c[i][2] = c[i][3] = 0.f;
}

__device__ __forceinline__ void sched() { asm volatile("griddepcontrol.launch_dependents;" ::: "memory"); }
__device__ __forceinline__ const uint8_t* pinp(const uint8_t* p) { return reinterpret_cast<const uint8_t*>(__shfl_xor_sync(0xffffffffu, reinterpret_cast<unsigned long long>(p), 0)); }
__device__ __forceinline__ uint32_t bar_or(int id, uint32_t x) {
  uint32_t r; asm volatile("{.reg .pred p, q; setp.ne.u32 p, %2, 0; bar.red.or.pred q, %1, 256, p; selp.u32 %0, 1, 0, q;}" : "=r"(r) : "r"(id), "r"(x) : "memory"); return r; }
__device__ __forceinline__ void bar_sync_unless(int id, uint32_t x) { asm volatile("{.reg .pred p; setp.eq.u32 p, %1, 0; @p bar.sync %0, 256;}" :: "r"(id), "r"((uint32_t)x) : "memory"); }
__device__ __forceinline__ void bar_arrive_unless(int id, uint32_t x) { asm volatile("{.reg .pred p; setp.eq.u32 p, %1, 0; @p bar.arrive %0, 256;}" :: "r"(id), "r"((uint32_t)x) : "memory"); }
__device__ __forceinline__ void stsm2t(uint32_t a, uint32_t r0, uint32_t r1, uint32_t x) {
  asm volatile("{.reg .pred p; setp.eq.u32 p, %3, 0; @p stmatrix.sync.aligned.m8n8.x2.trans.shared.b16 [%0], {%1,%2};}" :: "r"(a), "r"(r0), "r"(r1), "r"((uint32_t)x) : "memory"); }
__device__ __forceinline__ uint32_t or_and(uint32_t a, uint32_t b, uint32_t m) { uint32_t r; asm("lop3.b32 %0, %1, %2, %3, 0xa8;" : "=r"(r) : "r"(a), "r"(b), "r"(m)); return r; }
#define rare(x) __builtin_expect(!!(x), 0)
__device__ __forceinline__ uint32_t gtime() { unsigned long long g; asm volatile("mov.u64 %0, %%globaltimer;" : "=l"(g) :: "memory"); return (uint32_t)g; }
__device__ __forceinline__ void wait_time(uint32_t t) {
  asm volatile("{.reg .pred p; .reg .b32 g; .reg .b64 c;\nLOOP: mov.u64 c, %%globaltimer; cvt.u32.u64 g, c; sub.s32 g, %0, g; setp.lt.u32 p, g, 16384; @p bra.uni LOOP;}" :: "r"(t - 1) : "memory"); }
__device__ __forceinline__ uint32_t ldx32(const void* p) { uint32_t v; asm volatile("ld.relaxed.gpu.global.b32 %0, [%1];" : "=r"(v) : "l"(p) : "memory"); return v; }
__device__ __forceinline__ void stx32(const void* p, uint32_t v) { asm volatile("st.relaxed.gpu.global.b32 [%0], %1;" :: "l"(p), "r"(v) : "memory"); }

__global__ void __launch_bounds__(256, 1)
rec_kernel(const __grid_constant__ RecMaps maps, const bf16* __restrict__ xin, const bf16* __restrict__ mem0, Xchg* const gx,
           const bf16* __restrict__ fx, const bf16* __restrict__ wr, const bf16* __restrict__ wi) {
  extern __shared__ __align__(1024) uint8_t smem_raw[];
  const uint32_t sb = smem_u32(smem_raw);
  int role = blockIdx.x;
  {
    uint32_t smid, nsm; asm volatile("mov.u32 %0, %%smid;" : "=r"(smid)); asm volatile("mov.u32 %0, %%nsmid;" : "=r"(nsm));
    const int p = smid >> 1, u = p - 32;
    if (nsm == gridDim.x)
      role = (smid & 1) + (p < 32 ? 4 * ((p & 7) + 8 * (p >> 4)) + 2 * ((p >> 3) & 1) : p < 60 ? 4 * (16 + u % 7 + 7 * (u / 14)) + 2 * ((u / 7) & 1)
                         : p < 62 ? 2 * p + 8 : 2 * p - 4);
    role = uni(role);
  }
  if (role >= 128) {
    fft_cols(sb, role - 128, 4, [&]() { grid_wait(&gx->ctr[33], 128); });
    __threadfence(); __syncwarp();
    if ((threadIdx.x & 31) == 0) atomicAdd(&gx->ctr[32], 1u);
    __syncwarp();
    fft_rows_inv(&maps.fo, sb, role - 128, 4, [&]() { grid_wait(&gx->ctr[32], 32); });
    return;
  }
  const int tid = threadIdx.x, warp = uni(tid >> 5), lane = tid & 31, wg = warp >> 2, w4 = warp & 3, g = lane >> 2, t = lane & 3;
  const int h = role >> 2, j = role & 3, jh = j & 1;
  uint32_t w[48][4];
  float aq[16], av[16];
  int it = 0;

#define PT(k)
  auto pf_wo = [&]() {
    for (int i = 0; i < 4; i++)
      asm volatile("cp.async.bulk.prefetch.tensor.2d.L2.global [%0, {%1, %2}];" :: "l"(&maps.wo), "r"(256 * j + 64 * i), "r"(h * DH) : "memory");
  };
  fft_rows_fwd(fx, wr, wi, sb + R_MEM + 49152, role, [&]() {
    if (tid == 224) {
      mbar_init(sb + B_KV, 1); mbar_init(sb + B_W, 1); mbar_init(sb + B_X, 1); mbar_init(sb + B_X + 8, 1); mbar_init(sb + B_X + 16, 1); mbar_init(sb + B_X + 24, 1); mbar_init(sb + B_C, 4); mbar_init(sb + B_PK, 4); mbar_init(sb + B_B, 1);
      asm volatile("fence.mbarrier_init.release.cluster;" ::: "memory");
      mbar_expect_tx(sb + B_W, 3 * 65536);
      for (int i = 0; i < 4; i++) {
        tma2d(sb + R_X + i * 16384, &maps.wq, h * DH + 32 * j, i * 256, sb + B_W);
        if (i < 3) tma2d(sb + R_MEM + i * 16384, &maps.wk, h * DH + 32 * j, i * 256, sb + B_W);
        else asm volatile("cp.async.bulk.prefetch.tensor.2d.L2.global [%0, {%1, %2}];" :: "l"(&maps.wk), "r"(h * DH + 32 * j), "r"(768) : "memory");
      }
      for (int i = 0; i < 2; i++) tma2d(sb + R_WO + i * 32768, &maps.wv, h * DH + 64 * (j >> 1), jh * 512 + i * 256, sb + B_W);
      if (PFD) asm volatile("cp.async.bulk.prefetch.L2.global [%0], 2048;" :: "l"(xin + role * DM) : "memory");
      else for (int i = 0; i < 4; i++) asm volatile("cp.async.bulk.prefetch.L2.global [%0], 8192;" :: "l"(xin + role * 16384 + i * 4096) : "memory");
      if (WOP == 0) pf_wo();
      for (int i = 0; i < 5; i++) asm volatile("prefetch.tensormap [%0];" :: "l"(&maps.wo + i) : "memory");
    }
    __syncwarp();
  });
  if (tid < 16) sts32(sb + R_T + tid * 4, ~0u);
  fence_async();
  PT(0);
  grid_arrive(&gx->ctr[33]);
  PT(1);
  if (tid == 224) { tma2d(sb + R_MEM + 49152, &maps.wk, h * DH + 32 * j, 768, sb + B_W); if (WOP == 1) pf_wo(); }
  __syncwarp();
  uint8_t* const xb = reinterpret_cast<uint8_t*>(gx);
  auto probe_at = [&](int n) { return xb + (n ? offsetof(Xchg, C) + w4 * 8192 + role * 32 : offsetof(Xchg, B) + role * 8192 + warp * 128); };
  if (lane < 8) stx128(probe_at(lane >> 2) + (lane & 2) * 2048 + (lane & 1) * 16, 0, 0, 0, 0);
  uint32_t m0[4][4];
#pragma unroll
  for (int i = 0; i < 16; i++) m0[i >> 2][i & 3] = ldnc32(mem0 + g * DM + 128 * warp + 8 * i + 2 * t);
  mbar_spin(sb + B_W, 0, it);
  PT(2);
  const int lrow = (lane & 7) + ((lane >> 4) << 3), lhi = (lane >> 3) & 1;
  const int kq = wg ? 3 - 3 * jh : 3 * jh;
  const uint32_t LW = lrow * 128 + ((lhi ^ (lane & 7)) << 4);
  {
    const int chunk = w4 < 2 ? w4 + 2 * lhi : 2 * (w4 & 1) + lhi;
    uint32_t a = sb + (w4 < 2 ? R_X : R_MEM) + kq * 16384 + lrow * 64 + ((chunk ^ ((lrow >> 1) & 3)) << 4);
#pragma unroll
    for (int i = 0; i < 16; i++) ldsm4t(w[i], a + i * 1024);
    const uint32_t st = wg ? 1024 : 2048, av0 = sb + R_WO + (LW ^ (w4 << 5));
    const uint32_t a1 = wg ? a + (2 * jh - 1) * 16384 : av0 + jh * 32768, a2 = wg ? a + (2 * jh - 1) * 32768 : av0 + (1 - jh) * 32768;
#pragma unroll
    for (int i = 0; i < 16; i++) { ldsm4t(w[16 + i], a1 + i * st); ldsm4t(w[32 + i], a2 + i * st); }
  }
  uint32_t L16 = pin(lane * 16);
  const uint32_t uW = uni(sb + w4 * 512), uWo = uni(sb + R_WO + w4 * 16384), uMem = uni(sb + R_MEM + kq * 4096);
  const uint32_t dX = uni(((sb + R_X + kq * 16384) >> 4) | 0x10000u);
  auto load_wo = [&](uint32_t (&d)[32][4], int i0, int i1) {
#pragma unroll
    for (int i = i0; i < i1; i++) lds128(d[i], uWo + L16 + (i & 1) * 512 + (i >> 4) * 1024 + (i & 14) * 1024);
  };
  auto issue_x = [&](int n, int k) {
    const uint32_t bar = sb + B_X + 8 * k, q = k ^ (3 - 3 * jh);
    mbar_expect_tx(bar, 16384); tma3d(sb + R_X + q * 16384, &maps.x, n * SEG, 4 * q, bar);
  };
  auto store_stage = [&](int n) {
    asm volatile("cp.async.bulk.global.shared::cta.bulk_group [%0], [%1], 8192; cp.async.bulk.commit_group;"
                 :: "l"(g_kqv[n & 3][role]), "r"(sb + R_STAGE) : "memory");
  };
  auto issue_kqv = [&](int n) {
    const int p = (n & 3) * 128 + 4 * h;
    mbar_expect_tx(sb + B_KV, 26624);
    tma3d(sb + R_K, &maps.k, 0, p, sb + B_KV); tma3d(sb + R_Q, &maps.q, 8 + 2 * j, p, sb + B_KV); tma3d(sb + R_V, &maps.v, 16, p, sb + B_KV);
  };
  auto fetch4k = [&](uint32_t dst, uint32_t off, uint32_t bar, uint32_t t) {
    asm volatile("{.reg .pred p, q; .reg .b32 g; .reg .b64 c; elect.sync _|q, 0xffffffff; @q mbarrier.arrive.expect_tx.shared::cta.b64 _, [%2], 4096;\n"
                 "LOOP: mov.u64 c, %%globaltimer; cvt.u32.u64 g, c; sub.s32 g, %3, g; setp.lt.u32 p, g, 16384; @p bra.uni LOOP;\n"
                 "@q cp.async.bulk.shared::cluster.global.mbarrier::complete_tx::bytes [%0], [%1], 4096, [%2];}" :: "r"(dst), "l"(xb + off), "r"(bar), "r"(t - 1) : "memory");
  };
  uint32_t uS;
  auto my_b = [&]() { return offsetof(Xchg, B) + role * 8192 + ((uS + ((uint32_t)it >> 31)) & 1) * 4096; };
  auto issue_c = [&](uint32_t t) { fetch4k(sb + R_MEM + w4 * 4096, offsetof(Xchg, C) + w4 * 8192 + ((uS + ((uint32_t)it >> 31)) & 4096), sb + B_C, t); };
  auto wait_x = [&](int n, int i) { if (!(EXP & 1) || n < 2) mbar_spin(sb + B_X + 8 * i, n & 1, it); };
#define PACED(d0) uint32_t dz = d0; const uint32_t z = (uint32_t)it >> 31; auto pace = [&]() { for (int k = 0; k < PACE; k++) { if (k & 1) asm("add.u32 %0, %0, %1;" : "+r"(dz) : "r"(z)); else asm("xor.b32 %0, %0, %1;" : "+r"(dz) : "r"(z)); } };
  auto project_v = [&](auto I0, auto I1, auto&& mid) {
    PACED(decltype(I0)::value < 16 ? dX : dX ^ 1024);
    wg_fence();
    sfor<decltype(I0)::value, decltype(I1)::value>([&](auto I) {
      constexpr int i = decltype(I)::value;
      mid(i);
      if (i == 16 && decltype(I0)::value < 16) dz ^= 1024;
      wg_rs32<((i >> 2) & 3) * 256 + (i & 3) * 2, (i > 0)>(av, w[16 + i], dz);
      pace();
    });
    wg_commit();
  };
  auto project_qk = [&](auto I0, auto I1, auto first, auto&& mid) {
    PACED((dX ^ (decltype(I0)::value >> 4 << 10)) + ((uint32_t)it >> 31));
    wg_fence();
    sfor<decltype(I0)::value, decltype(I1)::value>([&](auto I) {
      constexpr int i = decltype(I)::value;
      mid(i);
      wg_rs32<((i >> 2) & 3) * 256 + (i & 3) * 2, !decltype(first)::value || i != decltype(I0)::value>(aq, w[i], dz);
      pace();
    });
    wg_commit();
  };
  const uint32_t uP = uni(sb + R_X + 3 * jh * 16384 + w4 * 512);
  auto park = [&]() {
    bar_sync(1, 128);
#pragma unroll
    for (int i = 0; i < 4; i++) sts128f(uP + L16 + i * 2048, aq + 4 * i);
    warp_arrive(sb + B_PK);
  };
  auto unpark = [&]() {
#pragma unroll
    for (int i = 0; i < 4; i++) {
      const float4 p = lds128f(uP + L16 + i * 2048);
      av[4 * i] = p.x; av[4 * i + 1] = p.y; av[4 * i + 2] = p.z; av[4 * i + 3] = p.w;
    }
  };
  auto fin_qk = [&]() {
#pragma unroll
    for (int i = 0; i < 16; i++) aq[i] += av[i];
    const uint32_t a = sb + R_STAGE + (w4 < 2 ? 2048 + w4 * 128 : (w4 & 1) * 256) + (L16 & 112) + (L16 >> 7) * 512;
    stsm4t(a, pack2(aq[0], aq[1]), pack2(aq[4], aq[5]), pack2(aq[8], aq[9]), pack2(aq[12], aq[13]));
    stsm4t(a + (w4 < 2 ? 256 : 128), pack2(aq[2], aq[3]), pack2(aq[6], aq[7]), pack2(aq[10], aq[11]), pack2(aq[14], aq[15]));
  };
  auto fin_v = [&]() {
#pragma unroll
    for (int a = 0; a < 2; a++)
      sts128(sb + R_STAGE + 4096 + w4 * 1024 + a * 512 + L16, pack2(av[8 * a], av[8 * a + 1]), pack2(av[8 * a + 2], av[8 * a + 3]),
             pack2(av[8 * a + 4], av[8 * a + 5]), pack2(av[8 * a + 6], av[8 * a + 7]));
  };
  __syncthreads();
  if (tid == 224) {
#pragma unroll 1
    for (int i = 0; i < 4; i++) issue_x(0, i);
    mbar_expect_tx(sb + B_W, 65536);
    for (int i = 0; i < 4; i++) tma2d(sb + R_WO + i * 16384, &maps.wo, 256 * j + 64 * i, h * DH, sb + B_W);
  }
  __syncwarp();
  if (wg) {
#pragma unroll
    for (int i = 0; i < NSW; i++) sts128(uW + R_WC + L16 + i * 2048, w[i]);
  }
#pragma unroll
  for (int i = 0; i < 4; i++) sts128(sb + R_MEM + warp * 2048 + i * 512 + (g >> 1) * 128 + t * 32 + (g & 1) * 16, m0[i]);
  auto probe = [&](int n, int cnt) {
    if (lane == 0) {
#pragma unroll 1
      for (int i = role >> 7; i < cnt; i++) {
        const int k = (i ^ wg) & 1;
        const unsigned t0 = clk();
        uint32_t v; asm volatile("atom.relaxed.gpu.global.exch.b32 %0, [%1], 0;" : "=r"(v) : "l"(probe_at(n) + k * 4096) : "memory");
        if (v == 0) asm volatile("red.shared.min.u32 [%0], %1;" :: "r"(sb + R_T + (n ? w4 * 8 : 32) + k * 4), "r"(clk() - t0) : "memory");
      }
    }
    __syncwarp();
  };
#pragma unroll 1
  for (int n = 0; n < 2; n++) {
    probe(0, n ? NPB : NPB0);
    asm volatile("{.reg .pred p; cp.async.bulk.wait_group 0; setp.eq.u32 p, %1, 97; @p red.relaxed.gpu.global.add.u32 [%0], 1;}" :: "l"(&gx->ctr[h]), "r"(tid ^ n ^ (1 - n) << 9) : "memory");
    PT(3 + 3 * n);
    wait_x(n, 2);
    PT(4 + 3 * n);
    if (wg == 0) {
      wait_x(n, 3);
      project_qk(IC<0>{}, IC<16>{}, IC<1>{}, [](int) {});
      project_v(IC<0>{}, IC<32>{}, [](int) {});
      wg_wait<0>(); keep(aq); keep(av);
      park();
      fin_v();
      fence_async();
    } else {
      wait_x(n, 0); wait_x(n, 1);
      project_qk(IC<32>{}, IC<48>{}, IC<1>{}, [](int) {});
      project_qk(IC<16>{}, IC<32>{}, IC<0>{}, [](int) {});
      project_qk(IC<0>{}, IC<16>{}, IC<0>{}, [](int) {});
      mbar_spin(sb + B_PK, n, it);
      unpark();
      wg_wait<0>(); keep(aq);
      fin_qk();
      fence_async();
    }
    __syncthreads();
    if (tid == 0 && n) stx32(&gx->S[role], 1 + (HOME & 2 && lds32(sb + R_T + 36) < lds32(sb + R_T + 32)));
    PT(5 + 3 * n);
    if (tid == 96 && n == 0) store_stage(0);
    if (tid == 128 && n == 0) {
#pragma unroll 1
      for (int i = 0; i < 4; i++) issue_x(1, i);
    }
    if (warp == 5 && n == 1) {
#pragma unroll 1
      while (__any_sync(0xffffffffu, ldx32(&gx->ctr[h]) < 4) && ++it < SPIN_LIMIT) {}
      if (elect()) issue_kqv(0);
    }
    __syncwarp();
  }
  mbar_spin(sb + B_W, 1, it);
  PT(9);
#pragma unroll
  for (int i = 0; i < 4; i++) {
    uint32_t f[4][4];
    const uint32_t a = sb + R_WO + warp * 8192 + i * 2048;
#pragma unroll
    for (int q = 0; q < 4; q++) ldsm4t(f[q], a + (LW ^ (q << 5)));
    __syncwarp();
#pragma unroll
    for (int q = 0; q < 4; q++) sts128(a + q * 512 + L16, f[q]);
  }
  if (NPC) probe(1, NPC);
  {
    const int o = 32 * w4 + 16 * wg + 4 * t + j;
    uint32_t v;
#pragma unroll 1
    while (__any_sync(0xffffffffu, (v = ldx32(&gx->S[o])) == 0) && ++it < SPIN_LIMIT) {}
    asm volatile("st.shared.u64 [%0], %1;" :: "r"(sb + R_DST + wg * 1024 + w4 * 256 + lane * 8), "l"(xb + offsetof(Xchg, B) + o * 8192 + (v >> 1) * 4096 + h * 128 + ((g ^ h) & 7) * 16) : "memory");
  }
  if (wg == 0) {
    const uint64_t cd = reinterpret_cast<uint64_t>(xb + (offsetof(Xchg, C) + j * 8192 + h * 128 + w4 * 32 + (L16 & 16) * 256 + (L16 & 64) / 4 + (L16 >> 7) * 4));
    sts128(uW + R_RD + L16, (uint32_t)cd, (uint32_t)(cd >> 32), sb + R_MEM + (L16 & 112) * 8 + (L16 >> 8) * 1024 + ((w4 * 32 + ((L16 >> 3) & 16)) ^ (L16 & 112)),
           (L16 >> 6) == (h & 3) * 2 + ((h >> 2) & 1) ? 0xFFFE0000u : 0xFFFFFFFFu);
  }
  if (tid == 0) sts32(sb + B_DUE + 8, gtime() & ~31u);
  PT(10);
  mbar_spin(sb + B_KV, 0, it);
  PT(11);
  if (tid < 4) sts32(sb + B_ONE + tid * 4, 0x3F803F80u);
  if (warp == 1) { const uint32_t e = g >> 1 == t ? 0x3F80u << (16 * (g & 1)) : 0u; sts128(sb + R_ID + L16, e, 0, 0, e); }
  __syncthreads();
  {
    const uint32_t kb = lds32(sb + R_T + 36) < lds32(sb + R_T + 32);
    uS = uni((HOME & 4 ? (__popc(((offsetof(Xchg, B) / 4096 + 2 * role) ^ (offsetof(Xchg, C) / 4096 + 2 * w4)) & 0xb3) ^ kb) & 1 : lds32(sb + R_T + w4 * 8 + 4) < lds32(sb + R_T + w4 * 8)) * 4096 + kb);
  }

  const float sc = 0.08838834764831845f * 1.4426950408889634f;
  uint8_t* const xa = xb + uni(h * 16384);
  const uint32_t uA = uni(wg ? (w4 >> 1) * 2048 + j * 512 + (w4 & 1) * 256 : 8192 + (4 * (j >> 1) + w4) * 512 + jh * 256);
  const uint32_t uP2 = uni(sb + R_P + w4 * 256);
  uint32_t nc = 1;
  uint32_t ma;
  const uint8_t* adst;
  auto pin_mem = [&]() { adst = pinp(xa + uA + L16 / 2); ma = pin(uMem + (L16 & 384) + (L16 & 48) * 2 + (L16 & 64) / 4); };
  pin_mem();

#pragma unroll 1
  for (int s = 0;; nc++) {
    const uint32_t tag = (s + 1) & 1;
    auto fresh = [&]() { L16 += (uint32_t)it >> 31; };
    auto get_due = [&]() { return lds32(sb + B_DUE + 4 + tag * 4); };
    float c[4][4], r4[4];
    auto fold = [&]() {
#pragma unroll
      for (int i = 0; i < 4; i++) r4[i] = ((c[0][i] + c[1][i]) + c[2][i]) + c[3][i];
    };
    auto mma4 = [&](int n, const uint32_t (&b0)[4], const uint32_t (&b1)[4]) {
      mma_h(c[0], w[n + 2], b1, 0); mma_h(c[1], w[n + 3], b1, 1); mma_h(c[2], w[n], b0, 0); mma_h(c[3], w[n + 1], b0, 1);
    };
    auto xpos = [&](int pos, int wp) {
      if ((pos == X0 || pos == X1 || pos == X2 || pos == X3) && warp == wp && s + 1 < NSEG && elect()) {
        const int z = (uint32_t)it >> 31;
        if (pos == X2) issue_x(s + 2, 2 + z);
        if (pos == X3) issue_x(s + 2, 3 + z);
        if (pos == X1) issue_x(s + 2, 1 + z);
        if (pos == X0) issue_x(s + 2, z);
      }
      __syncwarp();
    };
    if (wg == 0) {
      mbar_spin(sb + B_C, nc & 1, it);
      TS(13);
      uint32_t b[16][4], tg[4];
#pragma unroll
      for (int i = 0; i < PD0; i++) { lds128(b[i], ma + i * 512); __syncwarp(); }
      sched();
      zero(c);
#pragma unroll
      for (int i = 0; i < 8; i++) {
        const int k = i ^ 1;
        mma_h(c[0], w[2 * k], b[k], 0); mma_h(c[1], w[2 * k + 1], b[k], 1);
        if (i < 2 * NV0) { mma_h(c[2], w[16 + 2 * k], b[k], 0); mma_h(c[3], w[17 + 2 * k], b[k], 1); }
        sched();
        if ((i & 1) && i + PD0 < 9) { lds128(b[i + PD0 - 1], ma + (i + PD0 - 1) * 512); __syncwarp(); lds128(b[i + PD0], ma + (i + PD0) * 512); sched(); }
        if (i == TGP) {
          fresh();
#pragma unroll
          for (int k = 0; k < 4; k++) tg[k] = lds32((uW * 4 + L16) * 2 + (L16 >> 6) * 4 + (R_MEM + k * 1024 - 7 * sb));
          sched();
        }
      }
#pragma unroll
      for (int i = 0; i < 4; i++) { r4[i] = c[0][i] + c[1][i]; c[0][i] = c[1][i] = 0.f; }
      sts128f(uW + R_RED + L16, r4);
      TS(1);
      const uint32_t old = bar_or(4, (dif2(tg[0], tg[1], s) | dif2(tg[2], tg[3], s)) & (s > 0));
      TS(0);
#pragma unroll
      for (int i = 0; i < 2 * NV0; i++) { lds128(b[8 + i], (ma ^ 4096) + i * 512); __syncwarp(); }
      sched();
#pragma unroll
      for (int i = NV0; i < 8; i++) {
        if (VB && i == VB) bar_sync(7, 256);
        mma4(16 + 4 * i, b[2 * i], b[2 * i + 1]);
        if (i < 7) sched();
        if (i < 4) { lds128(b[8 + 2 * i], (ma ^ 4096) + i * 1024); __syncwarp(); lds128(b[9 + 2 * i], (ma ^ 4096) + i * 1024 + 512); sched(); }
      }
      fold();
      asm volatile("{.reg .pred p; setp.eq.u32 p, %3, 0; @p st.relaxed.gpu.global.v2.b32 [%0], {%1,%2};}" :: "l"(adst), "r"((pack2(r4[0], r4[1]) & ~1u) | tag), "r"(pack2(r4[2], r4[3])), "r"(old) : "memory");
      sched();
      const unsigned tpub = clk();
      if (__any_sync(0xffffffffu, old) && nc < NC_MAX) {
        bar_sync(3, 256);
        issue_c(gtime());
        continue;
      }
      TS(3);
      xpos(0, 0);
      const uint32_t due = get_due();
      uint32_t vf[4][4], vm[2][4], p[4], pm, o[4];
      const uint32_t va = sb + R_V + (w4 >> 1) * 8192 + (w4 & 1) * 2048 + L16;
#pragma unroll
      for (int i = 0; i < 4; i++) {
        uint32_t q[4]; lds128(vf[i], va + i * 512); lds128(q, va + 4096 + i * 512);
#pragma unroll
        for (int e = 0; e < 4; e++) vf[i][e] = hadd2(vf[i][e], q[e]);
      }
      const uint32_t pa = pin(sb + R_P + (L16 >> 1));
      const uint8_t* vsrc = pinp(xa + 8192 + w4 * 1024 + L16 / 2);
      uint32_t one[4];
      lds128(one, sb + B_ONE);
      auto pv_x = [&]() {
        zero(c);
        mma_a(c[2], one, p[0], p[1]);
        mma_a(c[0], vf[0], p[0], p[1]); mma_a(c[1], vf[2], p[0], p[1]);
        sched();
        mma_a(c[2], one, p[2], p[3]);
        mma_a(c[0], vf[1], p[2], p[3]); mma_a(c[1], vf[3], p[2], p[3]);
        sched();
      };
      auto pv_m = [&]() {
        mma1688(c[2], one[0], one[1], pm);
        mma_a(c[0], vm[0], pm, pm);
        sched();
        mma_a(c[1], vm[1], pm, pm);
      };
      auto norm = [&]() {
        const float n0 = rcp(c[2][0]), n1 = rcp(c[2][1]);
#pragma unroll
        for (int i = 0; i < 4; i++) o[i] = pack2(c[i >> 1][2 * (i & 1)] * n0, c[i >> 1][2 * (i & 1) + 1] * n1);
        return ((__float_as_uint(c[2][0]) - 0x1F800000u) | (__float_as_uint(c[2][1]) - 0x1F800000u)) >> 30;
      };
      auto load_m = [&](int x) { const float2 e0 = lds64f(pa + 512 + x * 1024), e1 = lds64f(pa + 768 + x * 1024); pm = pack2(e0.x * e1.x, e0.y * e1.y); };
      auto attend_max = [&](int x) {
        float2 sv[6];
#pragma unroll
        for (int i = 0; i < 6; i++) sv[i] = lds64f(pa - 3072 + x * 1536 + i * 256);
        sv[4].x += sv[5].x; sv[4].y += sv[5].y;
        const int dq = (int)(L16 >> 6) - (int)((L16 >> 3) & 6) + 8 * j;
        float m = fmaxf(sv[4].x, sv[4].y);
#pragma unroll
        for (int i = 0; i < 4; i++) {
          if (x && 8 * i > dq) sv[i].x = -INFINITY;
          if (x && 8 * i + 1 > dq) sv[i].y = -INFINITY;
          m = fmaxf(m, fmaxf(sv[i].x, sv[i].y));
        }
        m = fmaxf(m, __shfl_xor_sync(0xffffffffu, m, 1));
        m = fmaxf(m, __shfl_xor_sync(0xffffffffu, m, 2));
#pragma unroll
        for (int i = 0; i < 5; i++) (i < 4 ? p[i] : pm) = pack2(ex2(sv[i].x - m), ex2(sv[i].y - m));
        pv_x(); pv_m(); norm();
      };
      uint32_t tq[4];
      auto get_t = [&]() {
        tq[0] = tq[1] = tq[2] = tq[3] = 0;
        asm volatile("{.reg .pred p; setp.eq.u32 p, %5, 0; @p ld.relaxed.gpu.global.v4.b32 {%0,%1,%2,%3}, [%4];}"
                     : "+r"(tq[0]), "+r"(tq[1]), "+r"(tq[2]), "+r"(tq[3]) : "l"(xb + offsetof(Xchg, T) + L16 * 8), "r"(warp) : "memory");
      };
      delay_until(tpub + DLY_V);
      wait_time(due + NS_V);
      TS(4);
      ldx(vm, vsrc);
      sched();
      xpos(2, 2);
      auto store_kqv = [&]() {
        fence_async();
        if (!(EXP & 4))
          asm volatile("{.reg .pred p; elect.sync _|p, 0xffffffff; @p cp.async.bulk.global.shared::cta.bulk_group [%0], [%1], 2048; cp.async.bulk.commit_group;}"
                       :: "l"(g_kqv[(s + 1) & 3][role] + w4 * 128), "r"(sb + R_STAGE + w4 * 2048) : "memory");
      };
      if (SPOS == 2) store_kqv();
      sched();
      bar_sync(5, 256);
      ldsm4(p, sb + R_P + L16);
      load_m(0);
      pv_x();
      ldsm4(p, sb + R_P + 1024 + L16);
      pv_m();
      const uint32_t r = norm(), tl = after(tag, c[2][0], (uint32_t)it >> 31);
      const bool redo = __any_sync(0xffffffffu, r | ((dif2(vm[0][0], vm[0][2], tl) | dif2(vm[1][0], vm[1][2], tl)) & 1));
      TS(6);
      stsm4t(uW + R_O + L16, o[0], o[1], o[2], o[3]);
      bar_arrive_unless(6, redo);
      sched();
      if (TQL == 7) get_t();
      TS(7);
      pv_x();
      if (rare(redo)) retry<2>(vm, vsrc, tag, it);
      bar_sync(8, 256);
      load_m(1);
      pv_m();
      if (rare(__any_sync(0xffffffffu, norm()) || redo)) {
        fresh();
#pragma unroll 1
        for (int x = !redo; x < 2; x++) {
          attend_max(x);
          if (x == 0) { stsm4t(uW + R_O + L16, o[0], o[1], o[2], o[3]); bar_arrive(6, 256); }
        }
      }
      TS(8);
      if (TQL == 8) get_t();
      const bool xok = mbar_test(sb + B_X + 16, s & 1) & mbar_test(sb + B_X + 24, s & 1);
      xpos(4, 2);
      fresh();
      const uint32_t ob = uni(sb + R_MEM + 4096 + w4 * 1024);
      stsm4t(ob + (L16 & 112) * 4 + (((L16 >> 3) ^ (L16 >> 1)) & 48), o[0], o[1], o[2], o[3]);
      __syncwarp();
      uint32_t rd[4];
      lds128(rd, uW + R_RD + L16);
      lds128(o, ob + (L16 ^ ((L16 >> 3) & 48)));
      auto put_o = [&]() {
        *reinterpret_cast<uint4*>(reinterpret_cast<uint8_t*>(g_ox) + (((s * SEG + 8 * j) * HD + h * DH + 32 * w4) * 2 + (L16 >> 6) * (HD * 2) + (L16 & 48))) = make_uint4(o[0], o[1], o[2], o[3]);
      };
      if (s + 1 == NSEG) { put_o(); asm volatile("cp.async.bulk.wait_group 0;" ::: "memory"); break; }
      asm volatile("cp.async.bulk.wait_group 0;" ::: "memory");
      if (elect()) stx32(xa + 4096 + j * 16 + w4 * 4, s + 1);
      __syncwarp();
      if (rare(!xok)) { wait_x(s + 2, 3); wait_x(s + 2, 2); }
      TS(9);
      fresh();
      const uint32_t e = due | ((s + 1) & 31);
      project_qk(IC<0>{}, IC<NQ>{}, IC<1>{}, [&](int n) {
        if (n == OXPOS) { __syncwarp(); put_o(); __syncwarp(); }
        if (n == TQP) { __syncwarp(); tq[0] = dif2v(tq[0], tq[1], e) | dif2v(tq[2], tq[3], e); __syncwarp(); }
      });
      if (NPA) project_v(IC<0>{}, IC<NPA>{}, [](int) {});
      TS(2);
      if (warp == 0) {
        uint32_t last = due, nx = NS_P;
        if (rare(__any_sync(0xffffffffu, tq[0]))) {
          const uint32_t ref = gtime();
#pragma unroll 1
          do ldx128(o, xb + offsetof(Xchg, T) + L16 * 8); while (any_bit(or3(o[0] - s - 1, o[1] - s - 1, o[2] - s - 1), o[3] - s - 1, 30) && ++it < SPIN_LIMIT);
          const int d = max(max((int)(o[0] - ref), (int)(o[1] - ref)), max((int)(o[2] - ref), (int)(o[3] - ref)));
          last = (ref + __reduce_max_sync(0xffffffffu, d)) & ~31u;
          if (last != due) nx += NS_X;
        }
        const uint32_t bdue = last + NS_B;
        if (s < 4) { last += (MG_Y >> 8 * s & 255) * 32; nx += (MG_Z >> 8 * s & 255) * 32; }
        sts32(sb + B_DUE, last);
        sts32(sb + B_DUE + 8 - tag * 4, last + nx);
        fetch4k(sb + R_MEM, my_b(), sb + B_B, bdue);
        LOG(13, tl - last);
        LOG(9, last);
      }
      if (NQ < 16) project_qk(IC<NQ>{}, IC<16>{}, IC<0>{}, [](int) {});
      project_v(IC<NPA>{}, IC<NPRE>{}, [](int) {});
      const uint32_t ba = rd[2], msk = rd[3];
      const uint8_t* cdst = reinterpret_cast<const uint8_t*>(rd[0] | (uint64_t)rd[1] << 32);
      TS(14);
      mbar_spin(sb + B_B, s & 1, it);
      TS(10);
      uint32_t bq[2][4];
      auto sum_b = [&]() {
        ldsm4t(bq[0], ba); ldsm4t(bq[1], ba + 2048);
        sched();
#pragma unroll
        for (int i = 0; i < 8; i++) c[i >> 2][i & 3] = 0.f;
        mma_a(c[0], bq[0], 0x3F803F80u, 0x3F803F80u); mma_a(c[1], bq[1], 0x3F803F80u, 0x3F803F80u);
        const uint32_t t2 = tag * 0x10001u;
        const bool old = any_bit(or3(dif2(bq[0][0], bq[0][1], t2), dif2(bq[0][2], bq[0][3], t2), dif2(bq[1][0], bq[1][1], t2)), dif2(bq[1][2], bq[1][3], t2), L16 < 64 ? 0x10001u : 0u);
        const uint32_t T = (tag << 16) & ~msk, u = ((__float_as_uint(c[0][0] + c[1][0]) + ((0x10000u & ~msk) - T)) & msk) | T;
        asm volatile("{.reg .pred p; setp.eq.u32 p, %2, 0; @p st.relaxed.gpu.global.b32 [%0], %1;}"
                     :: "l"(cdst), "r"(pack2(__uint_as_float(u), c[0][2] + c[1][2])), "r"((uint32_t)(old || (L16 & 32))) : "memory");
        return old;
      };
      if (rare(sum_b())) {
#pragma unroll 1
        do {
          const uint8_t* p = xb + (my_b() + (ba - sb - R_MEM));
          ldx128(bq[0], p); ldx128(bq[1], p + 2048);
          sts128(ba, bq[0]); sts128(ba + 2048, bq[1]);
          __syncwarp();
          it += INC_B;
        } while (sum_b() && it < SPIN_LIMIT);
      }
      sched();
      TS(11);
      bar_arrive(0, 256);
      const unsigned tc = clk();
      const uint32_t cdue = lds32(sb + B_DUE) + NS_C;
      if (warp == 3) LOG(11, gtime() - cdue);
      fresh();
      wg_wait<0>(); keep(aq); keep(av);
      park();
      if (NPRE < 32) project_v(IC<NPRE>{}, IC<32>{}, [](int) {}); else fin_v();
      TS(12);
      delay_until(tc + DLY_C);
      issue_c(cdue);
      TS(5);
      LOG(warp, it);
      pin_mem();
      if (NPRE < 32) { wg_wait<0>(); keep(av); fin_v(); }
      if (!(EXP & 2)) mbar_spin(sb + B_KV, tag, it);
      TS(15);
    } else {
      uint32_t kf[8][4];
      auto load_k = [&]() {
        const uint32_t ka = sb + R_K + w4 * 1024 + (L16 & 112) + (L16 & 128) * 4 + (L16 & 256);
#pragma unroll
        for (int i = 0; i < 8; i++) ldsm4(kf[i], ka + (i >> 1) * 2048 + (i & 1) * 128);
      };
      auto put_p = [&](int x, uint32_t old, uint32_t again) {
        float e[4];
        const int dq = (int)((L16 >> 3) & 6) + 8 * j - (int)(L16 >> 6) - 16 * w4;
#pragma unroll
        for (int i = 0; i < 4; i++) { r4[i] = fmaf(c[3][i], sc, fmaf(c[2][i], sc, fmaf(c[0][i] + c[1][i], sc, __uint_as_float(i == 3 ? 0u - old : 0u)))); e[i] = x && dq + (i & 1) < 8 * (i >> 1) ? 0.f : ex2(r4[i]); }
        stsm2t(uP2 + x * 1024 + L16, pack2(e[0], e[1]), pack2(e[2], e[3]), again);
      };
      auto put_s = [&](int x) {
#pragma unroll
        for (int i = 0; i < 4; i++) sts32f(uW + R_S + x * 1536 + (L16 & 48) * 4 + (L16 >> 6) * 4 + (i & 1) * 32 + (i >> 1) * 256, r4[i]);
      };
      auto load_q = [&](uint32_t (&q)[4], uint32_t off) { ldsm4(q, sb + R_Q + (L16 & 112) + (L16 & 128) * 2 + (L16 >> 8) * 128 + off); };
      mbar_spin(sb + B_C, nc & 1, it);
      TS(13);
      float4 o4;
      uint32_t id[4], old;
      {
        uint32_t b[24][4];
#pragma unroll
        for (int i = 0; i < 2 * PD1; i++) { lds128(b[i], ma + i * 512); __syncwarp(); }
        sched();
        zero(c);
#pragma unroll
        for (int i = 0; i < 12; i++) {
          mma4(4 * i, b[2 * i], b[2 * i + 1]);
          if (i < 11) sched();
          if (i + PD1 < 12) { const int k = i + PD1; const uint32_t a = (ma ^ (k >> 2 << 12)) + (k & 3) * 1024; lds128(b[2 * k], a); __syncwarp(); lds128(b[2 * k + 1], a + 512); sched(); }
          if (i == RJ) { lds128(id, sb + R_ID + L16); sched(); }
          if (i == RI) { old = bar_or(4, 0); o4 = lds128f(uW + R_RED + L16); sched(); }
        }
      }
      TS(0);
      {
        float e[4] = {o4.x, o4.y, o4.z, o4.w};
#pragma unroll
        for (int i = 0; i < 4; i++) { r4[i] = (((e[i] + c[0][i]) + c[1][i]) + c[2][i]) + c[3][i]; e[i] = 0.f; }
        mma_a(e, id, pack2(r4[0], r4[1]), pack2(r4[2], r4[3]));
        sched();
        if (VB) bar_arrive(7, 256);
        sched();
        asm volatile("{.reg .pred p; setp.eq.u32 p, %3, 0; @p st.relaxed.gpu.global.v2.b32 [%0], {%1,%2};}" :: "l"(adst),
                     "r"((__byte_perm(__float_as_uint(e[0]), __float_as_uint(e[1]), 0x7632) & ~1u) | tag), "r"(__byte_perm(__float_as_uint(e[2]), __float_as_uint(e[3]), 0x7632)), "r"(old) : "memory");
        sched();
      }
      const unsigned tpub = clk(), now = gtime(), due = get_due();
      if (__any_sync(0xffffffffu, old) && nc < NC_MAX) { bar_sync(3, 256); continue; }
      TS(2);
      const uint8_t* asrc = pinp(adst + ((warp == 7) * 1024 - (int)uA));
      fresh();
      uint32_t wo[32][4];
      bool xok;
      auto reload = [&]() {
        sched();
#pragma unroll
        for (int i = RE0 + RE1; i < NSW; i++) lds128(w[i], uW + R_WC + L16 + i * 2048);
        sched();
      };
      auto out_proj = [&]() {
        uint32_t b[4][4];
        float d[4][4];
        uint8_t* dst[2];
        const uint32_t da = pin(uP2 + (R_DST - R_P) + L16 / 2);
        sched();
        TS(7);
        bar_sync(6, 256);
#pragma unroll
        for (int i = 0; i < 4; i++) { ldsm4(b[i], sb + R_O + i * 512 + L16); __syncwarp(); }
        sched();
        auto put_b = [&](uint8_t* a, const float (&e)[4][4]) {
          stx128(a, (pack2(e[0][0] + e[2][0], e[0][1] + e[2][1]) & ~1u) | tag, pack2(e[0][2] + e[2][2], e[0][3] + e[2][3]),
                 pack2(e[1][0] + e[3][0], e[1][1] + e[3][1]), pack2(e[1][2] + e[3][2], e[1][3] + e[3][3]));
        };
        zero(c); zero(d);
#pragma unroll
        for (int i = 0; i < 32; i++) {
          mma_h(i < 16 ? c[i & 3] : d[i & 3], wo[i], b[(i >> 2) & 3], (i >> 1) & 1);
          if (i >= LW0 && NB1 + i - LW0 < 32) { load_wo(wo, (NB1 + i - LW0) ^ 1, ((NB1 + i - LW0) ^ 1) + 1); __syncwarp(); }
          if (i == DL0 || i == DL1) asm volatile("ld.shared.u64 %0, [%1];" : "=l"(dst[i > DL0]) : "r"(da + (i > DL0) * 1024) : "memory");
          if (i >= 16 && i < 16 + RE0) { lds128(w[i - 16], uW + R_WC + L16 + (i - 16) * 2048); __syncwarp(); }
          if (i >= RP1 && i < RP1 + RE1) { lds128(w[i - RP1 + RE0], uW + R_WC + L16 + (i - RP1 + RE0) * 2048); __syncwarp(); }
          if (i == 22) put_b(dst[0], c);
          if ((i & 1) && (i < 20 || i > 22)) sched();
        }
        put_b(dst[1], d);
        sched();
        TS(6);
      };
      if (warp < 6) {
        delay_until(tpub + DLY_A);
        const int it0 = it;
        bool redo;
#pragma unroll 1
        do {
          uint32_t q[4][4], y[4];
          float d[4][4];
          wait_time(due);
          TS(4);
          ldx(q, asrc);
          sched();
          load_k();
          uint32_t qx[4][4];
#pragma unroll
          for (int i = 0; i < 4; i++) load_q(qx[i], i * 512);
          sched();
          load_wo(wo, 0, NE4);
          sched();
          zero(c);
#pragma unroll
          for (int i = 0; i < 8; i++) mma_h(c[i & 3], kf[i], qx[i >> 1], i & 1);
          put_p(1, 0, 0); put_s(1);
          sched();
          load_wo(wo, NE4, NA4);
          sched();
          zero(c); zero(d);
#pragma unroll
          for (int i = 0; i < 8; i++) {
            if (i == 0) { y[0] = dif2v(q[0][0], q[0][2], q[1][0]); sched(); }
            if (i == 3) { y[1] = dif2v(q[1][2], q[2][0], q[2][2]); sched(); }
            if (i == 6) { y[2] = dif2v(q[3][0], q[3][2], tag); sched(); }
            mma_h(i % 6 < 2 ? c[2 + i % 6] : d[i - 2], kf[i], q[i >> 1], i & 1);
            if (i == 2 || i == 5 || i == 7) sched();
          }
          y[0] = or_and(or3(y[0], y[1], dif2v(q[0][0], q[2][0], tag)), y[2], it < SPIN_LIMIT);
#pragma unroll
          for (int i = 0; i < 4; i++) { c[0][i] = d[0][i] + d[1][i]; c[1][i] = d[2][i] + d[3][i]; }
          put_p(0, y[0], it - it0);
          TS(5);
          bar_sync_unless(5, it - it0);
          redo = __any_sync(0xffffffffu, y[0]);
          it += INC_A;
        } while (redo);
        it -= INC_A;
        put_s(0);
        bar_arrive(8, 256);
        load_wo(wo, NA4, NB1);
        out_proj();
        if (warp == 4) LOG(12, tb);
      } else {
        uint32_t qx[2][4], q[4][4];
        if (warp == 6) {
          const uint32_t t1 = (now & ~31u) + NS_M;
          LOG(10, now - due);
          if (elect()) stx32(&gx->T[h][j], ((int)(t1 - due) > 0 ? t1 + NS_PEN : due) | ((s + 1) & 31));
          __syncwarp();
        }
        auto score = [&](const uint32_t (&a0)[4], const uint32_t (&a1)[4]) {
          zero(c);
#pragma unroll
          for (int i = 0; i < 4; i++) mma_h(c[i], i < 2 ? a0 : a1, q[2 + (i >> 1)], i & 1);
        };
        auto put_m = [&](uint32_t a, uint32_t old, uint32_t again) {
#pragma unroll
          for (int i = 0; i < 2; i++) { r4[i] = fmaf(c[3][2 + i], sc, fmaf((c[0][i] + c[1][2 + i]) + c[2][i], sc, __uint_as_float(i ? 0u - old : 0u))); r4[2 + i] = fmaf(r4[i] * 0x1p122f, 0.f, ex2(r4[i])); }
          asm volatile("{.reg .pred p; setp.eq.u32 p, %3, 0; @p st.shared.v2.f32 [%0], {%1,%2};}" :: "r"(a), "f"(r4[2]), "f"(r4[3]), "r"(again) : "memory");
        };
        delay_until(tpub + DLY_A);
        const uint32_t sa = sb + R_S + 512 + w4 * 256 + (L16 >> 1);
        const int it0 = it;
        bool redo;
#pragma unroll 1
        do {
          wait_time(due);
          TS(4);
          ldx<4, 2048>(q, asrc);
          sched();
          load_q(qx[0], (w4 & 1) * 1024); load_q(qx[1], (w4 & 1) * 1024 + 512);
          load_wo(wo, 0, NA6);
          sched();
          score(q[0], q[1]);
          sched();
          const uint32_t y = or_and(or3(dif2v(q[0][0], q[0][2], tag), dif2v(q[1][0], q[1][2], tag), dif2v(q[2][0], q[2][2], tag)), dif2v(q[3][0], q[3][2], tag), it < SPIN_LIMIT);
          put_m(sa + 2560, y, it - it0);
          TS(5);
          bar_arrive_unless(5, it - it0);
          redo = __any_sync(0xffffffffu, y);
          it += INC_A;
        } while (redo);
        it -= INC_A;
        sts64f(sa, r4[0], r4[1]);
        score(qx[0], qx[1]);
        put_m(sa + 3584, 0, 0);
        sts64f(sa + 1536, r4[0], r4[1]);
        bar_arrive(8, 256);
        load_wo(wo, NA6, NB1);
        out_proj();
      }
      TS(8);
      if (s + 1 == NSEG) break;
      wait_x(s + 2, 2);
      TS(9);
      fresh();
      if (N1) project_qk(IC<32>{}, IC<32 + N1>{}, IC<1>{}, [](int) {});
      TS(10);
      xpos(6, 6);
      uint32_t fl = s + 1;
      if (warp == 5) { wait_time(due + NS_F); fl = ldx32(xa + 4096 + ((L16 >> 2) & 60)); }
      reload();
      TS(14);
      pin_mem();
      wait_x(s + 2, 1); wait_x(s + 2, 0);
      if (warp == 5) {
#pragma unroll 1
        while (__any_sync(0xffffffffu, fl != s + 1) && !(EXP & 4) && ++it < SPIN_LIMIT) fl = ldx32(xa + 4096 + ((L16 >> 2) & 60));
        wait_time(due + (NS_B + NS_K));
        if (!(EXP & 2) && elect()) issue_kqv(s + 1);
        __syncwarp();
      }
      if (PFD && warp == 6 && s + PFD < NSEG && elect())
        asm volatile("cp.async.bulk.prefetch.L2.global [%0], 2048;" :: "l"(xin + ((s + PFD) * SEG + ((role + 4 * (role >> 5)) & 31)) * DM) : "memory");
      __syncwarp();
      TS(11);
      LOG(warp, it);
      if (warp == 4) LOG(8, nc);
      bar_sync(0, 256);
      if (N1 < 16) project_qk(IC<32 + N1>{}, IC<48>{}, IC<!N1>{}, [](int) {});
      project_qk(IC<16>{}, IC<32>{}, IC<0>{}, [&](int n) { if ((n & 15) == XWPOS) { __syncwarp(); xok = mbar_test(sb + B_PK, s & 1); __syncwarp(); } });
      if (rare(!xok)) mbar_spin(sb + B_PK, s & 1, it);
      unpark();
      project_qk(IC<0>{}, IC<16>{}, IC<0>{}, [](int) {});
      TS(12);
      wg_wait<0>(); keep(aq);
      TS(1);
      fin_qk();
      TS(15);
    }
    s++;
  }
  if (it >= SPIN_LIMIT || nc >= NC_MAX) g_err = 2;
}

typedef CUresult (*EncodeFn)(CUtensorMap*, CUtensorMapDataType, cuuint32_t, void*, const cuuint64_t*, const cuuint64_t*, const cuuint32_t*,
                             const cuuint32_t*, CUtensorMapInterleave, CUtensorMapSwizzle, CUtensorMapL2promotion, CUtensorMapFloatOOBfill);
static void make_map(EncodeFn fn, CUtensorMap* m, const void* p, uint64_t cols, uint64_t rows, uint64_t pitch, uint32_t bc, uint32_t br, CUtensorMapSwizzle sw) {
  cuuint64_t dims[2] = {cols, rows}, strides[1] = {pitch * 2};
  cuuint32_t box[2] = {bc, br}, es[2] = {1, 1};
  fn(m, CU_TENSOR_MAP_DATA_TYPE_BFLOAT16, 2, const_cast<void*>(p), dims, strides, box, es, CU_TENSOR_MAP_INTERLEAVE_NONE, sw,
     CU_TENSOR_MAP_L2_PROMOTION_L2_256B, CU_TENSOR_MAP_FLOAT_OOB_FILL_NONE);
}

extern "C" void kernel_launch(void* const* d_in, const int* in_sizes, int n_in, void* d_out, int out_size) {
  const bf16* Ax = (const bf16*)d_in[0]; const bf16* mem0 = (const bf16*)d_in[1];
  const bf16* Wq = (const bf16*)d_in[2]; const bf16* Wk = (const bf16*)d_in[3]; const bf16* Wv = (const bf16*)d_in[4];
  const bf16* Wo = (const bf16*)d_in[5];
  const bf16* Bx = (const bf16*)d_in[7]; const bf16* wr = (const bf16*)d_in[8]; const bf16* wi = (const bf16*)d_in[9];
  bf16* out = (bf16*)d_out;

  void* fp = nullptr; cudaDriverEntryPointQueryResult qr;
  cudaGetDriverEntryPoint("cuTensorMapEncodeTiled", &fp, cudaEnableDefault, &qr);
  EncodeFn fn = (EncodeFn)fp;
  void *kqv, *ox, *xr;
  cudaGetSymbolAddress(&xr, g_xraw);
  cudaGetSymbolAddress(&kqv, g_kqv); cudaGetSymbolAddress(&ox, g_ox);
  const CUtensorMapSwizzle S128 = CU_TENSOR_MAP_SWIZZLE_128B, S64 = CU_TENSOR_MAP_SWIZZLE_64B;

  GemmMaps m3; RecMaps mr;
  make_map(fn, &m3.a, ox, HD, S_LEN, HD, 64, 128, S128);
  make_map(fn, &m3.b[0], Wo, DM, HD, DM, 64, 64, S128);
  m3.b[1] = m3.b[0]; m3.b[2] = m3.b[0];
  make_map(fn, &m3.c, out, DM, S_LEN, 2 * DM, 64, 64, S128);
  make_map(fn, &mr.wq, Wq, HD, DM, HD, 32, 256, S64);
  make_map(fn, &mr.wk, Wk, HD, DM, HD, 32, 256, S64);
  make_map(fn, &mr.wv, Wv, HD, DM, HD, 64, 256, S128);
  make_map(fn, &mr.wo, Wo, DM, HD, DM, 64, 128, S128);
  {
    cuuint64_t dims[3] = {64, S_LEN, 16}, strides[2] = {DM * 2, 128};
    cuuint32_t box[3] = {64, 32, 4}, es[3] = {1, 1, 1};
    fn(&mr.x, CU_TENSOR_MAP_DATA_TYPE_BFLOAT16, 3, const_cast<bf16*>(Ax), dims, strides, box, es, CU_TENSOR_MAP_INTERLEAVE_NONE, S128,
       CU_TENSOR_MAP_L2_PROMOTION_L2_256B, CU_TENSOR_MAP_FLOAT_OOB_FILL_NONE);
  }
  for (int i = 0; i < 3; i++) {
    cuuint64_t dims[3] = {128, 32, 512}, strides[2] = {256, 8192};
    cuuint32_t box[3] = {128, i == 0 ? 8u : i == 1 ? 2u : 16u, 4}, es[3] = {1, 1, 1};
    fn(i == 0 ? &mr.k : i == 1 ? &mr.q : &mr.v, CU_TENSOR_MAP_DATA_TYPE_BFLOAT16, 3, kqv, dims, strides, box, es, CU_TENSOR_MAP_INTERLEAVE_NONE,
       CU_TENSOR_MAP_SWIZZLE_NONE, CU_TENSOR_MAP_L2_PROMOTION_L2_256B, CU_TENSOR_MAP_FLOAT_OOB_FILL_NONE);
  }
  {
    cuuint64_t dims[3] = {64, 16, S_LEN}, strides[2] = {128, 2 * DM * 2};
    cuuint32_t box[3] = {64, 16, 2}, es[3] = {1, 1, 1};
    fn(&mr.fo, CU_TENSOR_MAP_DATA_TYPE_BFLOAT16, 3, out + DM, dims, strides, box, es, CU_TENSOR_MAP_INTERLEAVE_NONE, S128,
       CU_TENSOR_MAP_L2_PROMOTION_NONE, CU_TENSOR_MAP_FLOAT_OOB_FILL_NONE);
  }
  constexpr int SM3 = 6 * 32768 + 32768 + 256 + 1024;
  cudaFuncSetAttribute(gemm_kernel<128, 6>, cudaFuncAttributeMaxDynamicSharedMemorySize, SM3);
  cudaFuncSetAttribute(rec_kernel, cudaFuncAttributeMaxDynamicSharedMemorySize, R_TOTAL);

  cudaStream_t st = cudaStreamPerThread;
  Xchg* gx = reinterpret_cast<Xchg*>((reinterpret_cast<uintptr_t>(xr) + 0x1FFFFF) & ~(uintptr_t)0x1FFFFF);
  rec_kernel<<<132, 256, R_TOTAL, st>>>(mr, Ax, mem0, gx, Bx, wr, wi);
  gemm_kernel<128, 6><<<128, 384, SM3, st>>>(m3, 16, 8, 64, 8, reinterpret_cast<uint4*>(gx));
}
```

```cpp
#include <cuda_runtime.h>
#include <cuda_bf16.h>
#include <cuda.h>
#include <stdint.h>
#include <stddef.h>
#include <type_traits>

typedef __nv_bfloat16 bf16;

constexpr int S_LEN = 2048, DM = 1024, NH = 32, DH = 128, MEM = 8, SEG = 32, NSEG = 64;
constexpr int HD = NH * DH;
#define SPIN 20
constexpr int SPIN_LIMIT = 1 << SPIN, INC_A = 1, INC_B = 1;

constexpr unsigned NC_MAX = 4096;
__device__ __align__(1024) uint4 g_kqv[4][128][512];
__device__ __align__(1024) bf16 g_ox[(size_t)S_LEN * HD];
struct Xchg {
  uint4 A[32][4][256];
  uint4 C[4][2][256];
  uint4 B[128][2][256];
  uint32_t T[32][32];
  uint32_t S[128];
  unsigned ctr[64];
};
__device__ __align__(1024) uint4 g_xraw[(sizeof(Xchg) + (1 << 21)) / 16];
__device__ __align__(1024) uint4 g_y[1024 * 256];
__device__ __align__(1024) uint4 g_wt[513 * 512];
__device__ int g_err;

__device__ __forceinline__ unsigned clk() { unsigned long long c; asm volatile("mov.u64 %0, %%clock64;" : "=l"(c)); return (unsigned)c; }
__device__ __forceinline__ uint32_t smem_u32(const void* p) { return (uint32_t)__cvta_generic_to_shared(p); }
__device__ __forceinline__ void mbar_init(uint32_t bar, int cnt) { asm volatile("mbarrier.init.shared::cta.b64 [%0], %1;" :: "r"(bar), "r"(cnt) : "memory"); }
__device__ __forceinline__ void mbar_expect_tx(uint32_t bar, int bytes) { asm volatile("mbarrier.arrive.expect_tx.shared::cta.b64 _, [%0], %1;" :: "r"(bar), "r"(bytes) : "memory"); }
__device__ __forceinline__ void mbar_arrive(uint32_t bar) { asm volatile("mbarrier.arrive.shared::cta.b64 _, [%0];" :: "r"(bar) : "memory"); }
__device__ __forceinline__ void mbar_arrive_cluster(uint32_t bar, int cta) {
  asm volatile("{.reg .b32 r; mapa.shared::cluster.u32 r, %0, %1; mbarrier.arrive.shared::cluster.b64 _, [r];}" :: "r"(bar), "r"(cta) : "memory"); }
__device__ __forceinline__ bool mbar_try(uint32_t bar, int par) {
  uint32_t ok; asm volatile("{.reg .pred p; mbarrier.try_wait.parity.shared::cta.b64 p, [%1], %2; selp.u32 %0, 1, 0, p;}" : "=r"(ok) : "r"(bar), "r"(par) : "memory"); return ok; }
__device__ __forceinline__ bool mbar_test(uint32_t bar, int par) {
  uint32_t ok; asm volatile("{.reg .pred p; mbarrier.test_wait.parity.shared::cta.b64 p, [%1], %2; selp.u32 %0, 1, 0, p;}" : "=r"(ok) : "r"(bar), "r"(par) : "memory"); return ok; }
__device__ __forceinline__ void mbar_wait(uint32_t bar, int par) {
  int it = 0;
  while (!mbar_try(bar, par)) { if (++it > SPIN_LIMIT) { g_err = 1; break; } }
}
__device__ __forceinline__ void tma2d(uint32_t dst, const CUtensorMap* m, int c0, int c1, uint32_t bar) {
  asm volatile("cp.async.bulk.tensor.2d.shared::cluster.global.mbarrier::complete_tx::bytes [%0], [%1, {%3, %4}], [%2];"
    :: "r"(dst), "l"(m), "r"(bar), "r"(c0), "r"(c1) : "memory"); }
__device__ __forceinline__ void tma2d_mc(uint32_t dst, const CUtensorMap* m, int c0, int c1, uint32_t bar, uint16_t mask) {
  asm volatile("cp.async.bulk.tensor.2d.shared::cluster.global.mbarrier::complete_tx::bytes.multicast::cluster [%0], [%1, {%3, %4}], [%2], %5;"
    :: "r"(dst), "l"(m), "r"(bar), "r"(c0), "r"(c1), "h"(mask) : "memory"); }
__device__ __forceinline__ void tma2d_store(const CUtensorMap* m, uint32_t src, int c0, int c1) {
  asm volatile("cp.async.bulk.tensor.2d.global.shared::cta.bulk_group [%0, {%2, %3}], [%1];" :: "l"(m), "r"(src), "r"(c0), "r"(c1) : "memory"); }
__device__ __forceinline__ void fence_async() { asm volatile("fence.proxy.async.shared::cta;" ::: "memory"); }
__device__ __forceinline__ void bar_sync(int id, int n) { asm volatile("bar.sync %0, %1;" :: "r"(id), "r"(n) : "memory"); }
__device__ __forceinline__ void bar_arrive(int id, int n) { asm volatile("bar.arrive %0, %1;" :: "r"(id), "r"(n) : "memory"); }
__device__ __forceinline__ uint32_t pack2(float lo, float hi) { uint32_t r; asm("cvt.rn.bf16x2.f32 %0, %1, %2;" : "=r"(r) : "f"(hi), "f"(lo)); return r; }
__device__ __forceinline__ uint32_t pack2_tag(float lo, float hi, uint32_t T) {
  uint32_t u = ((__float_as_uint(lo) - T + 0x10000u) & 0xFFFE0000u) + T;
  return __byte_perm(u, pack2(0.f, hi), 0x7632); }
__device__ __forceinline__ void ldsm4(uint32_t (&r)[4], uint32_t a) {
  asm volatile("ldmatrix.sync.aligned.m8n8.x4.shared.b16 {%0,%1,%2,%3}, [%4];" : "=r"(r[0]), "=r"(r[1]), "=r"(r[2]), "=r"(r[3]) : "r"(a) : "memory"); }
__device__ __forceinline__ void ldsm4t(uint32_t (&r)[4], uint32_t a) {
  asm volatile("ldmatrix.sync.aligned.m8n8.x4.trans.shared.b16 {%0,%1,%2,%3}, [%4];" : "=r"(r[0]), "=r"(r[1]), "=r"(r[2]), "=r"(r[3]) : "r"(a) : "memory"); }
__device__ __forceinline__ void stsm4(uint32_t a, uint32_t r0, uint32_t r1, uint32_t r2, uint32_t r3) {
  asm volatile("stmatrix.sync.aligned.m8n8.x4.shared.b16 [%0], {%1,%2,%3,%4};" :: "r"(a), "r"(r0), "r"(r1), "r"(r2), "r"(r3) : "memory"); }
__device__ __forceinline__ void stsm4t(uint32_t a, uint32_t r0, uint32_t r1, uint32_t r2, uint32_t r3) {
  asm volatile("stmatrix.sync.aligned.m8n8.x4.trans.shared.b16 [%0], {%1,%2,%3,%4};" :: "r"(a), "r"(r0), "r"(r1), "r"(r2), "r"(r3) : "memory"); }
__device__ __forceinline__ void lds128(uint32_t (&r)[4], uint32_t a) {
  asm volatile("ld.shared.v4.u32 {%0,%1,%2,%3}, [%4];" : "=r"(r[0]), "=r"(r[1]), "=r"(r[2]), "=r"(r[3]) : "r"(a) : "memory"); }
__device__ __forceinline__ float4 lds128f(uint32_t a) { float4 r;
  asm volatile("ld.shared.v4.f32 {%0,%1,%2,%3}, [%4];" : "=f"(r.x), "=f"(r.y), "=f"(r.z), "=f"(r.w) : "r"(a) : "memory"); return r; }
__device__ __forceinline__ float2 lds64f(uint32_t a) { float2 r;
  asm volatile("ld.shared.v2.f32 {%0,%1}, [%2];" : "=f"(r.x), "=f"(r.y) : "r"(a) : "memory"); return r; }
__device__ __forceinline__ void sts128(uint32_t a, uint32_t r0, uint32_t r1, uint32_t r2, uint32_t r3) {
  asm volatile("st.shared.v4.u32 [%0], {%1,%2,%3,%4};" :: "r"(a), "r"(r0), "r"(r1), "r"(r2), "r"(r3) : "memory"); }
__device__ __forceinline__ void sts64f(uint32_t a, float x, float y) { asm volatile("st.shared.v2.f32 [%0], {%1,%2};" :: "r"(a), "f"(x), "f"(y) : "memory"); }
__device__ __forceinline__ void sts32f(uint32_t a, float x) { asm volatile("st.shared.f32 [%0], %1;" :: "r"(a), "f"(x) : "memory"); }
__device__ __forceinline__ void mma16816(float (&d)[4], uint32_t a0, uint32_t a1, uint32_t a2, uint32_t a3, uint32_t b0, uint32_t b1) {
  asm volatile("mma.sync.aligned.m16n8k16.row.col.f32.bf16.bf16.f32 {%0,%1,%2,%3}, {%4,%5,%6,%7}, {%8,%9}, {%0,%1,%2,%3};"
    : "+f"(d[0]), "+f"(d[1]), "+f"(d[2]), "+f"(d[3]) : "r"(a0), "r"(a1), "r"(a2), "r"(a3), "r"(b0), "r"(b1)); }
__device__ __forceinline__ void mma1688(float (&d)[4], uint32_t a0, uint32_t a1, uint32_t b0) {
  asm volatile("mma.sync.aligned.m16n8k8.row.col.f32.bf16.bf16.f32 {%0,%1,%2,%3}, {%4,%5}, {%6}, {%0,%1,%2,%3};"
    : "+f"(d[0]), "+f"(d[1]), "+f"(d[2]), "+f"(d[3]) : "r"(a0), "r"(a1), "r"(b0)); }
__device__ __forceinline__ void ldx128(uint32_t (&r)[4], const void* p) {
  asm volatile("{.reg .b128 t; .reg .b64 a, b; ld.relaxed.gpu.global.b128 t, [%4]; mov.b128 {a, b}, t; mov.b64 {%0,%1}, a; mov.b64 {%2,%3}, b;}"
    : "=r"(r[0]), "=r"(r[1]), "=r"(r[2]), "=r"(r[3]) : "l"(p) : "memory"); }
__device__ __forceinline__ void ldx2x64(uint32_t (&r)[4], const void* p) {
  asm volatile("{.reg .b64 a, b; ld.relaxed.gpu.global.v2.b64 {a, b}, [%4]; mov.b64 {%0,%1}, a; mov.b64 {%2,%3}, b;}"
    : "=r"(r[0]), "=r"(r[1]), "=r"(r[2]), "=r"(r[3]) : "l"(p) : "memory"); }
__device__ __forceinline__ void stx128(void* p, uint32_t r0, uint32_t r1, uint32_t r2, uint32_t r3) {
  asm volatile("{.reg .b128 t; .reg .b64 a, b; mov.b64 a, {%1,%2}; mov.b64 b, {%3,%4}; mov.b128 t, {a, b}; st.relaxed.gpu.global.b128 [%0], t;}"
    :: "l"(p), "r"(r0), "r"(r1), "r"(r2), "r"(r3) : "memory"); }
__device__ __forceinline__ void stx64(void* p, uint32_t r0, uint32_t r1) {
  asm volatile("{.reg .b64 a; mov.b64 a, {%1,%2}; st.relaxed.gpu.global.b64 [%0], a;}" :: "l"(p), "r"(r0), "r"(r1) : "memory"); }
__device__ __forceinline__ uint32_t uni(uint32_t x) { return __shfl_sync(0xffffffffu, x, 0); }
__device__ __forceinline__ uint32_t pin(uint32_t x) { return __shfl_xor_sync(0xffffffffu, x, 0); }
__device__ __forceinline__ float ex2(float x) { float r; asm("ex2.approx.ftz.f32 %0, %1;" : "=f"(r) : "f"(x)); return r; }
__device__ __forceinline__ void wg_fence() { asm volatile("wgmma.fence.sync.aligned;" ::: "memory"); }
__device__ __forceinline__ void wg_commit() { asm volatile("wgmma.commit_group.sync.aligned;" ::: "memory"); }
template <int N> __device__ __forceinline__ void wg_wait() { asm volatile("wgmma.wait_group.sync.aligned %0;" :: "n"(N) : "memory"); }

__device__ __forceinline__ void wgmma_ss_n256_tb1(float (&d)[128], uint64_t da, uint64_t db, int sc) {
  asm volatile("{.reg .pred p; setp.ne.b32 p, %130, 0;\n"
    "wgmma.mma_async.sync.aligned.m64n256k16.f32.bf16.bf16 {%0,%1,%2,%3,%4,%5,%6,%7,%8,%9,%10,%11,%12,%13,%14,%15,%16,%17,%18,%19,%20,%21,%22,%23,%24,%25,%26,%27,%28,%29,%30,%31,%32,%33,%34,%35,%36,%37,%38,%39,%40,%41,%42,%43,%44,%45,%46,%47,%48,%49,%50,%51,%52,%53,%54,%55,%56,%57,%58,%59,%60,%61,%62,%63,%64,%65,%66,%67,%68,%69,%70,%71,%72,%73,%74,%75,%76,%77,%78,%79,%80,%81,%82,%83,%84,%85,%86,%87,%88,%89,%90,%91,%92,%93,%94,%95,%96,%97,%98,%99,%100,%101,%102,%103,%104,%105,%106,%107,%108,%109,%110,%111,%112,%113,%114,%115,%116,%117,%118,%119,%120,%121,%122,%123,%124,%125,%126,%127}, %128, %129, p, 1, 1, 0, 1;}\n"
    : "+f"(d[0]),"+f"(d[1]),"+f"(d[2]),"+f"(d[3]),"+f"(d[4]),"+f"(d[5]),"+f"(d[6]),"+f"(d[7]),"+f"(d[8]),"+f"(d[9]),"+f"(d[10]),"+f"(d[11]),"+f"(d[12]),"+f"(d[13]),"+f"(d[14]),"+f"(d[15]),"+f"(d[16]),"+f"(d[17]),"+f"(d[18]),"+f"(d[19]),"+f"(d[20]),"+f"(d[21]),"+f"(d[22]),"+f"(d[23]),"+f"(d[24]),"+f"(d[25]),"+f"(d[26]),"+f"(d[27]),"+f"(d[28]),"+f"(d[29]),"+f"(d[30]),"+f"(d[31]),"+f"(d[32]),"+f"(d[33]),"+f"(d[34]),"+f"(d[35]),"+f"(d[36]),"+f"(d[37]),"+f"(d[38]),"+f"(d[39]),"+f"(d[40]),"+f"(d[41]),"+f"(d[42]),"+f"(d[43]),"+f"(d[44]),"+f"(d[45]),"+f"(d[46]),"+f"(d[47]),"+f"(d[48]),"+f"(d[49]),"+f"(d[50]),"+f"(d[51]),"+f"(d[52]),"+f"(d[53]),"+f"(d[54]),"+f"(d[55]),"+f"(d[56]),"+f"(d[57]),"+f"(d[58]),"+f"(d[59]),"+f"(d[60]),"+f"(d[61]),"+f"(d[62]),"+f"(d[63]),"+f"(d[64]),"+f"(d[65]),"+f"(d[66]),"+f"(d[67]),"+f"(d[68]),"+f"(d[69]),"+f"(d[70]),"+f"(d[71]),"+f"(d[72]),"+f"(d[73]),"+f"(d[74]),"+f"(d[75]),"+f"(d[76]),"+f"(d[77]),"+f"(d[78]),"+f"(d[79]),"+f"(d[80]),"+f"(d[81]),"+f"(d[82]),"+f"(d[83]),"+f"(d[84]),"+f"(d[85]),"+f"(d[86]),"+f"(d[87]),"+f"(d[88]),"+f"(d[89]),"+f"(d[90]),"+f"(d[91]),"+f"(d[92]),"+f"(d[93]),"+f"(d[94]),"+f"(d[95]),"+f"(d[96]),"+f"(d[97]),"+f"(d[98]),"+f"(d[99]),"+f"(d[100]),"+f"(d[101]),"+f"(d[102]),"+f"(d[103]),"+f"(d[104]),"+f"(d[105]),"+f"(d[106]),"+f"(d[107]),"+f"(d[108]),"+f"(d[109]),"+f"(d[110]),"+f"(d[111]),"+f"(d[112]),"+f"(d[113]),"+f"(d[114]),"+f"(d[115]),"+f"(d[116]),"+f"(d[117]),"+f"(d[118]),"+f"(d[119]),"+f"(d[120]),"+f"(d[121]),"+f"(d[122]),"+f"(d[123]),"+f"(d[124]),"+f"(d[125]),"+f"(d[126]),"+f"(d[127])
    : "l"(da), "l"(db), "r"(sc));
}

__device__ __forceinline__ void wgmma_ss_n128_tb1(float (&d)[64], uint64_t da, uint64_t db, int sc) {
  asm volatile("{.reg .pred p; setp.ne.b32 p, %66, 0;\n"
    "wgmma.mma_async.sync.aligned.m64n128k16.f32.bf16.bf16 {%0,%1,%2,%3,%4,%5,%6,%7,%8,%9,%10,%11,%12,%13,%14,%15,%16,%17,%18,%19,%20,%21,%22,%23,%24,%25,%26,%27,%28,%29,%30,%31,%32,%33,%34,%35,%36,%37,%38,%39,%40,%41,%42,%43,%44,%45,%46,%47,%48,%49,%50,%51,%52,%53,%54,%55,%56,%57,%58,%59,%60,%61,%62,%63}, %64, %65, p, 1, 1, 0, 1;}\n"
    : "+f"(d[0]),"+f"(d[1]),"+f"(d[2]),"+f"(d[3]),"+f"(d[4]),"+f"(d[5]),"+f"(d[6]),"+f"(d[7]),"+f"(d[8]),"+f"(d[9]),"+f"(d[10]),"+f"(d[11]),"+f"(d[12]),"+f"(d[13]),"+f"(d[14]),"+f"(d[15]),"+f"(d[16]),"+f"(d[17]),"+f"(d[18]),"+f"(d[19]),"+f"(d[20]),"+f"(d[21]),"+f"(d[22]),"+f"(d[23]),"+f"(d[24]),"+f"(d[25]),"+f"(d[26]),"+f"(d[27]),"+f"(d[28]),"+f"(d[29]),"+f"(d[30]),"+f"(d[31]),"+f"(d[32]),"+f"(d[33]),"+f"(d[34]),"+f"(d[35]),"+f"(d[36]),"+f"(d[37]),"+f"(d[38]),"+f"(d[39]),"+f"(d[40]),"+f"(d[41]),"+f"(d[42]),"+f"(d[43]),"+f"(d[44]),"+f"(d[45]),"+f"(d[46]),"+f"(d[47]),"+f"(d[48]),"+f"(d[49]),"+f"(d[50]),"+f"(d[51]),"+f"(d[52]),"+f"(d[53]),"+f"(d[54]),"+f"(d[55]),"+f"(d[56]),"+f"(d[57]),"+f"(d[58]),"+f"(d[59]),"+f"(d[60]),"+f"(d[61]),"+f"(d[62]),"+f"(d[63])
    : "l"(da), "l"(db), "r"(sc));
}

template <int BN> struct WG;
template <> struct WG<256> { static __device__ __forceinline__ void mma(float (&d)[128], uint64_t a, uint64_t b, int sc) { wgmma_ss_n256_tb1(d, a, b, sc); } };
template <> struct WG<128> { static __device__ __forceinline__ void mma(float (&d)[64], uint64_t a, uint64_t b, int sc) { wgmma_ss_n128_tb1(d, a, b, sc); } };

struct GemmMaps { CUtensorMap a, b[3], c; };
template <int BN, int STAGES>
__global__ void __cluster_dims__(2, 1, 1) __launch_bounds__(384, 1)
gemm_kernel(const __grid_constant__ GemmMaps maps, int tilesM, int tilesN, int kblocks, int nPerB, uint4* __restrict__ clearX) {
  extern __shared__ __align__(1024) uint8_t smem_raw[];
  constexpr int STAGE_BYTES = 16384 + BN * 128;
  constexpr int NBOX = BN / 64;
  const uint32_t sbase = (smem_u32(smem_raw) + 1023) & ~1023u;
  const uint32_t sEpi = sbase + STAGES * STAGE_BYTES;
  const uint32_t sBar = sEpi + 32768;
  const int warp = threadIdx.x >> 5, lane = threadIdx.x & 31, wg = warp >> 2;
  uint32_t crank; asm("mov.u32 %0, %%cluster_ctarank;" : "=r"(crank));
#define GT(k)
  const int npairs = (tilesM >> 1) * tilesN, pair0 = blockIdx.x >> 1, pstep = gridDim.x >> 1;
  if (threadIdx.x == 256) {
    asm volatile("prefetch.tensormap [%0];" :: "l"(&maps.b[0]) : "memory");
    for (int i = 0; i < STAGES; i++) { mbar_init(sBar + 8 * i, 1); mbar_init(sBar + 8 * (STAGES + i), 4); }
    asm volatile("fence.mbarrier_init.release.cluster;" ::: "memory");
    asm volatile("barrier.cluster.arrive.relaxed;" ::: "memory");
    for (int i = 0; i < STAGES; i++) {
      mbar_expect_tx(sBar + 8 * i, STAGE_BYTES);
      tma2d(sbase + i * STAGE_BYTES, &maps.a, i * 64, ((pair0 % (tilesM >> 1)) * 2 + crank) * 128, sBar + 8 * i);
    }
    asm volatile("prefetch.tensormap [%0];" :: "l"(&maps.c) : "memory");
  } else asm volatile("barrier.cluster.arrive.relaxed;" ::: "memory");
  asm volatile("barrier.cluster.wait.acquire;" ::: "memory");
  __syncwarp();
  if (wg == 2) {
    asm volatile("setmaxnreg.dec.sync.aligned.u32 40;");
    if (warp > 8) {
      __nanosleep(4000);
      for (int i = blockIdx.x * 96 + threadIdx.x - 288; i < (int)(sizeof(Xchg) / 16); i += gridDim.x * 96) clearX[i] = make_uint4(0, 0, 0, 0);
    }
    if (warp == 8 && lane == 0) {
      int st = 0, ph = 1;
      for (int p = pair0; p < npairs; p += pstep) {
        const int tm = (p % (tilesM >> 1)) * 2 + crank, tn = p / (tilesM >> 1);
        const CUtensorMap* mb = &maps.b[tn / nPerB];
        const int n0 = (tn % nPerB) * BN;
        for (int kb = 0; kb < kblocks; kb++) {
          const uint32_t a = sbase + st * STAGE_BYTES, full = sBar + 8 * st;
          if (p > pair0 || kb >= STAGES) {
            mbar_wait(sBar + 8 * (STAGES + st), ph);
            mbar_expect_tx(full, STAGE_BYTES);
            tma2d(a, &maps.a, kb * 64, tm * 128, full);
          }
#pragma unroll
          for (int i = 0; i < NBOX / 2; i++) {
            const int bx = crank * (NBOX / 2) + i;
            tma2d_mc(a + 16384 + bx * 8192, mb, n0 + bx * 64, kb * 64, full, (uint16_t)3);
          }
          if (++st == STAGES) { st = 0; ph ^= 1; }
        }
      }
      for (int i = 0; i < STAGES; i++) { mbar_wait(sBar + 8 * (STAGES + st), ph); if (++st == STAGES) { st = 0; ph ^= 1; } }
    }
  } else {
    asm volatile("setmaxnreg.inc.sync.aligned.u32 232;");
    int st = 0, ph = 0;
    float acc[BN / 2];
    const uint64_t descA0 = (uint64_t)(((sbase + wg * 8192) & 0x3FFFF) >> 4) | (1ull << 16) | (64ull << 32) | (1ull << 62);
    const uint64_t descB0 = (uint64_t)(((sbase + 16384) & 0x3FFFF) >> 4) | (512ull << 16) | (64ull << 32) | (1ull << 62);
    const uint32_t epi = sEpi + wg * 16384;
    for (int p = pair0; p < npairs; p += pstep) {
      const int tm = (p % (tilesM >> 1)) * 2 + crank, tn = p / (tilesM >> 1);
      int prev = -1;
      for (int kb = 0; kb < kblocks; kb++) {
        mbar_wait(sBar + 8 * st, ph);
        if ((kb & 15) == 0) { GT(kb >> 4); }
        wg_fence();
        const uint64_t so = (uint64_t)(st * (STAGE_BYTES >> 4));
#pragma unroll
        for (int k = 0; k < 4; k++) WG<BN>::mma(acc, descA0 + so + k * 2, descB0 + so + k * 128, kb | k);
        wg_commit();
        if (prev >= 0) {
          wg_wait<1>();
          if ((threadIdx.x & 127) < 2) mbar_arrive_cluster(sBar + 8 * (STAGES + prev), threadIdx.x & 1);
        }
        prev = st;
        if (++st == STAGES) { st = 0; ph ^= 1; }
      }
      wg_wait<0>();
      if ((threadIdx.x & 127) < 2) mbar_arrive_cluster(sBar + 8 * (STAGES + prev), threadIdx.x & 1);
      GT(4);
#pragma unroll
      for (int r = 0; r < BN / 128; r++) {
        if ((threadIdx.x & 127) == 0) asm volatile("cp.async.bulk.wait_group.read 0;" ::: "memory");
        bar_sync(1 + wg, 128);
        const int row = (warp & 3) * 16 + (lane & 15);
#pragma unroll
        for (int i = 0; i < 8; i++) {
          const int c = 2 * (i & 3) + (lane >> 4);
          const float* q = &acc[r * 64 + i * 8];
          stsm4(epi + (i >> 2) * 8192 + row * 128 + ((c ^ (row & 7)) << 4), pack2(q[0], q[1]), pack2(q[2], q[3]), pack2(q[4], q[5]), pack2(q[6], q[7]));
        }
        fence_async();
        bar_sync(1 + wg, 128);
        if ((threadIdx.x & 127) == 0) {
          tma2d_store(&maps.c, epi, tn * BN + r * 128, tm * 128 + wg * 64);
          tma2d_store(&maps.c, epi + 8192, tn * BN + r * 128 + 64, tm * 128 + wg * 64);
          asm volatile("cp.async.bulk.commit_group;" ::: "memory");
        }
      }
    }
    GT(5);
    if ((threadIdx.x & 127) == 0) asm volatile("cp.async.bulk.wait_group 0;" ::: "memory");
    GT(6);
  }
}

struct Dft { uint32_t m[2][2][2][4]; };
template <bool P4> __device__ __forceinline__ int fidx(int tile, int x) { return P4 ? 4 * (x >> 1) + 2 * (tile & 1) + (x & 1) + 16 * (tile >> 1) : x + 8 * tile; }
__device__ __forceinline__ float2 cis(int k, int n) {
  k &= n - 1; if (2 * k > n) k -= n;
  const float a = (float)k * (6.283185307179586f / (float)n);
  return make_float2(__cosf(a), __sinf(a));
}
template <bool OUT4> __device__ __forceinline__ void make_dft(Dft& D, int g, int t) {
#pragma unroll
  for (int q = 0; q < 16; q++) {
    const int b = q >> 3, u = (q >> 2) & 1, r = (q >> 1) & 1, v = q & 1;
    const float2 w = cis(fidx<OUT4>(v, g) * fidx<false>(2 * u + r, 2 * t + b), 32);
    D.m[b][u][0][q & 3] = pack2(w.x, w.y); D.m[b][u][1][q & 3] = pack2(-w.y, w.x);
  }
}
__device__ __forceinline__ void mma_dc(float (&d)[4], uint32_t a0, uint32_t a1, uint32_t a2, uint32_t a3, uint32_t b0, uint32_t b1, const float (&c)[4]) {
  asm("mma.sync.aligned.m16n8k16.row.col.f32.bf16.bf16.f32 {%0,%1,%2,%3}, {%4,%5,%6,%7}, {%8,%9}, {%10,%11,%12,%13};"
    : "=f"(d[0]), "=f"(d[1]), "=f"(d[2]), "=f"(d[3]) : "r"(a0), "r"(a1), "r"(a2), "r"(a3), "r"(b0), "r"(b1), "f"(c[0]), "f"(c[1]), "f"(c[2]), "f"(c[3])); }
__device__ __forceinline__ void dft_b(const Dft& D, const uint32_t (&x)[2][4], float (&o)[2][8]) {
#pragma unroll
  for (int ri = 0; ri < 2; ri++) {
    float z[4] = {0.f, 0.f, 0.f, 0.f}, e[4], p[4];
    mma_dc(e, D.m[0][0][ri][0], D.m[0][0][ri][1], D.m[0][0][ri][2], D.m[0][0][ri][3], x[0][0], x[0][1], z);
    mma_dc(e, D.m[0][1][ri][0], D.m[0][1][ri][1], D.m[0][1][ri][2], D.m[0][1][ri][3], x[0][2], x[0][3], e);
    mma_dc(p, D.m[1][0][ri][0], D.m[1][0][ri][1], D.m[1][0][ri][2], D.m[1][0][ri][3], x[1][0], x[1][1], e);
    mma_dc(p, D.m[1][1][ri][0], D.m[1][1][ri][1], D.m[1][1][ri][2], D.m[1][1][ri][3], x[1][2], x[1][3], p);
#pragma unroll
    for (int q = 0; q < 4; q++) { o[ri][q] = p[q]; o[ri][4 + q] = fmaf(2.f, e[q], -p[q]); }
  }
}
__device__ __forceinline__ void dft_a(const uint32_t (&m)[2][2][4], const uint32_t (&x0)[2][4], const uint32_t (&x1)[2][4], float (&o)[2][8]) {
#pragma unroll
  for (int ri = 0; ri < 2; ri++) {
    float z[4] = {0.f, 0.f, 0.f, 0.f}, e[4], p[4];
    mma_dc(e, x0[0][0], x1[0][0], x0[0][1], x1[0][1], m[0][ri][0], m[0][ri][1], z);
    mma_dc(e, x0[0][2], x1[0][2], x0[0][3], x1[0][3], m[0][ri][2], m[0][ri][3], e);
    mma_dc(p, x0[1][0], x1[1][0], x0[1][1], x1[1][1], m[1][ri][0], m[1][ri][1], e);
    mma_dc(p, x0[1][2], x1[1][2], x0[1][3], x1[1][3], m[1][ri][2], m[1][ri][3], p);
#pragma unroll
    for (int q = 0; q < 4; q++) { o[ri][q] = p[q]; o[ri][4 + q] = fmaf(2.f, e[q], -p[q]); }
  }
}
__device__ __forceinline__ uint32_t twid(float re, float im, float c, float s) { return pack2(fmaf(re, c, im * s), fmaf(im, c, -re * s)); }
__device__ __forceinline__ void cpa16(uint32_t d, const void* s) { asm volatile("cp.async.cg.shared.global [%0], [%1], 16;" :: "r"(d), "l"(s) : "memory"); }
__device__ __forceinline__ void sts32(uint32_t a, uint32_t x) { asm volatile("st.shared.u32 [%0], %1;" :: "r"(a), "r"(x) : "memory"); }
__device__ __forceinline__ void cpa_commit() { asm volatile("cp.async.commit_group;" ::: "memory"); }
template <int N> __device__ __forceinline__ void cpa_wait() { asm volatile("cp.async.wait_group %0;" :: "n"(N) : "memory"); }
__device__ __forceinline__ uint32_t lds32(uint32_t a) { uint32_t r; asm volatile("ld.shared.u32 %0, [%1];" : "=r"(r) : "r"(a) : "memory"); return r; }
#define FMID 0
constexpr int F_TP = 4112, F_TSZ = 8 * F_TP;

__device__ __forceinline__ uint32_t ldnc32(const void* p) { uint32_t v; asm volatile("ld.global.nc.b32 %0, [%1];" : "=r"(v) : "l"(p) : "memory"); return v; }
template <class F>
__device__ __forceinline__ void fft_wprep(const bf16* __restrict__ wr, const bf16* __restrict__ wi, int cta, F&& mid) {
  const int tid = threadIdx.x, g = (cta >> 1) & 7, c = (cta >> 4) & 3, t = 2 * (cta & 1) + (tid & 1);
  const int k0 = g + 8 * (cta >> 6) + 32 * (8 * c + 2 * t), l0 = (tid & ~1) + (g & 1);
  uint32_t a[4][4], b[4][4];
#pragma unroll
  for (int q = 0; q < 16; q++) {
    const int o = (k0 + 16 * (q >> 3) + 32 * ((q >> 1) & 1) + 1024 * (q & 1)) * 513 + l0 + 256 * ((q >> 2) & 1);
    a[q >> 2][q & 3] = ldnc32(wr + o);
    b[q >> 2][q & 3] = ldnc32(wi + o);
  }
  const int e = cta * 32 + (tid & 31), lh = (e >> 11) * 512, k = e & 2047, k2 = (k >> 5) & 31;
  uint32_t hz[4];
#pragma unroll
  for (int q = 0; q < 4; q++) asm volatile("ld.global.nc.u16 %0, [%1];" : "=r"(hz[q]) : "l"((q < 2 ? wr : wi) + (q & 1 ? (2048 - k) & 2047 : k) * 513 + lh) : "memory");
  mid();
  uint4* dst = g_wt + l0 * 512 + cta * 2 + (tid & 1);
#pragma unroll
  for (int q = 0; q < 8; q++) {
    const int hf = q >> 1, l = l0 + 256 * (hf & 1) + (q & 1);
    const uint32_t sel = (q & 1) ? 0x7632 : 0x5410;
    if (l & 511) dst[(256 * (hf & 1) + (q & 1)) * 512 + 256 * (q >> 2)] = make_uint4(__byte_perm(a[hf][0], b[hf][0], sel), __byte_perm(a[hf][1], b[hf][1], sel),
                                                                                   __byte_perm(a[hf][2], b[hf][2], sel), __byte_perm(a[hf][3], b[hf][3], sel));
  }
  if (tid < 32) reinterpret_cast<uint32_t*>(g_wt)[(64 * ((k >> 3) & 3) + 16 * (k2 >> 3) + 2 * (k & 7) + ((k2 >> 2) & 1)) * 8 + lh * 2048 + 2 * (k2 & 3) + (k >> 10)] =
      pack2(0.5f * (__uint_as_float(hz[0] << 16) + __uint_as_float(hz[1] << 16)), 0.5f * (__uint_as_float(hz[2] << 16) - __uint_as_float(hz[3] << 16)));
}

template <class F>
__device__ __forceinline__ void fft_rows_fwd(const bf16* __restrict__ x, const bf16* __restrict__ wr, const bf16* __restrict__ wi, uint32_t tb, int it, F&& mid) {
  const int warp = threadIdx.x >> 5, lane = threadIdx.x & 31, g = lane >> 2, t = lane & 3;
  const uint32_t in = tb + warp * 4096;
  const uint32_t f0 = in + (lane >> 3) * 256 + (((lane & 7) ^ (2 * (lane >> 3))) << 4);
  const bf16* src = x + ((256 * (warp & 3) + 64 * (warp >> 2) + 128 * (it & 1) + 32 * ((it >> 4) & 1) + 8 * (it >> 5) + ((it >> 1) & 7)) * 2048 + lane * 8);
#pragma unroll
  for (int q = 0; q < 8; q++) cpa16((f0 ^ ((q >> 2) * 144)) + (q & 3) * 1024, src + q * 256);
  cpa_commit();
  Dft D;
  float2 tw[4][8];
  fft_wprep(wr, wi, it, [&]() {
    if (FMID == 0) mid();
    make_dft<true>(D, g, t);
#pragma unroll
    for (int q = 0; q < 32; q++) {
      tw[q >> 3][q & 7] = cis(fidx<true>((q >> 1) & 3, g) * fidx<false>(q >> 3, 2 * t + (q & 1)), 1024);
      if (FMID) asm volatile("" : "+f"(tw[q >> 3][q & 7].x), "+f"(tw[q >> 3][q & 7].y) :: "memory");
    }
    if (FMID == 1) mid();
  });
  if (FMID == 2) mid();
  cpa_wait<0>(); __syncwarp();
  uint32_t a[4][2][4], y[4][2][4];
#pragma unroll
  for (int q = 0; q < 8; q++) ldsm4t(a[q & 3][q >> 2], (in + lane * 128 + ((lane & 7) << 4)) ^ (q << 4));
  float o[2][8];
#pragma unroll
  for (int i = 0; i < 4; i++) {
    dft_b(D, a[i], o);
#pragma unroll
    for (int q = 0; q < 8; q++) y[q >> 1][q & 1][i] = twid(o[0][q], o[1][q], tw[i][q].x, tw[i][q].y);
  }
  __syncthreads();
  const uint32_t w0 = tb + warp * F_TP + fidx<true>(0, g) * 128 + t * 16 + ((g & 1) << 6), wz = (g & 1) ? -64 : 64;
#pragma unroll
  for (int z = 0; z < 2; z++) {
    float o2[2][8];
    dft_b(D, y[2 * z], o); dft_b(D, y[2 * z + 1], o2);
#pragma unroll
    for (int i = 0; i < 4; i++) {
      const float sg = i < 2 ? 1.f : -1.f;
      sts128(w0 + z * wz + fidx<true>(i, 0) * 128, pack2(o[0][2 * i], sg * o[1][2 * i]), pack2(o[0][2 * i + 1], sg * o[1][2 * i + 1]),
             pack2(o2[0][2 * i], sg * o2[1][2 * i]), pack2(o2[0][2 * i + 1], sg * o2[1][2 * i + 1]));
    }
  }
  __syncthreads();
  const uint32_t ra = tb + (lane & 1) * 4 * F_TP + ((lane >> 1) + 16 * (warp ^ ((warp >> 1) & 1))) * 4;
  uint4* dst = g_y + (threadIdx.x >> 1) * 256 + (lane & 1) + it * 2;
#pragma unroll
  for (int q = 0; q < 8; q++) { const uint32_t r = ra + q * 512; dst[q * 32768] = make_uint4(lds32(r), lds32(r + F_TP), lds32(r + 2 * F_TP), lds32(r + 3 * F_TP)); }
}

template <class F>
__device__ __forceinline__ void fft_cols(uint32_t sb, int cta, int ncta, F&& ready) {
  const int warp = threadIdx.x >> 5, lane = threadIdx.x & 31, g = lane >> 2, t = lane & 3;
  const uint32_t in = sb + warp * 16384 + lane * 16, tab = sb + 131072 + lane * 16;
  auto fetch_y = [&](int l) {
#pragma unroll
    for (int q = 0; q < 16; q++) cpa16(in + q * 512, g_y + (q < 8 ? l : (1024 - l) & 1023) * 256 + (q & 7) * 32 + lane);
  };
  auto fetch_w = [&](int l) {
#pragma unroll
    for (int q = 0; q < 16; q++) cpa16(in + 8192 + q * 512, g_wt + l * 512 + q * 32 + lane);
  };
  const int l0 = cta * 8 + warp, dl = ncta * 8;
  Dft D; make_dft<false>(D, g, t);
#pragma unroll
  for (int q = 2 * warp; q < 2 * warp + 2; q++) {
    const int r = fidx<false>(q & 3, g), c = fidx<false>(q >> 2, 2 * t);
    const float2 w0 = cis(r * c, 1024), w1 = cis(r * c + r, 1024), p0 = cis(r + 32 * c, 2048), p1 = cis(r + 32 * c + 32, 2048);
    sts128(tab + q * 512, __float_as_uint(w0.x), __float_as_uint(w0.y), __float_as_uint(w1.x), __float_as_uint(w1.y));
    sts128(tab + 8192 + q * 512, __float_as_uint(p0.x), __float_as_uint(p0.y), __float_as_uint(p1.x), __float_as_uint(p1.y));
  }
  if (warp == 0) {
#pragma unroll
    for (int q = 0; q < 8; q++) {
      const int v = q >> 2, b = (q >> 1) & 1, ri = q & 1;
      sts128(tab + 16384 + q * 512, D.m[b][0][ri][v], D.m[b][0][ri][v + 2], D.m[b][1][ri][v], D.m[b][1][ri][v + 2]);
    }
  }
  ready();
  fetch_y(l0); cpa_commit();
  fetch_w(l0); cpa_commit();
#pragma unroll 1
  for (int l = l0; l <= 512; l += dl) {
    uint32_t a[2][4][2][4], y[2][4][2][4];
    float o[2][2][8];
    cpa_wait<1>();
#pragma unroll
    for (int q = 0; q < 16; q++) lds128(a[q >> 3][(q >> 1) & 3][q & 1], in + q * 512);
    if (!(l & 511)) {
      const uint32_t m0 = l ? 0x80000000u : 0u;
#pragma unroll
      for (int q = 0; q < 32; q++) { a[0][q >> 3][(q >> 2) & 1][q & 3] ^= m0; a[1][q >> 3][(q >> 2) & 1][q & 3] ^= m0 ^ 0x80000000u; }
    }
    auto first = [&]() {
#pragma unroll
      for (int i = 0; i < 4; i++) {
        dft_b(D, a[0][i], o[0]); dft_b(D, a[1][i], o[1]);
#pragma unroll
        for (int r = 0; r < 4; r++) {
          const float4 w = lds128f(tab + (4 * i + r) * 512);
#pragma unroll
          for (int s = 0; s < 2; s++) {
            y[s][r][0][i] = twid(o[s][0][2 * r], o[s][1][2 * r], w.x, w.y);
            y[s][r][1][i] = twid(o[s][0][2 * r + 1], o[s][1][2 * r + 1], w.z, w.w);
          }
        }
      }
    };
    first();
    if (l + dl <= 512) fetch_y(l + dl);
    cpa_commit();
    cpa_wait<1>();
#pragma unroll
    for (int zv = 0; zv < 4; zv++) {
      const int z = zv >> 1, v = zv & 1;
      uint32_t m[2][2][4];
#pragma unroll
      for (int q = 0; q < 4; q++) lds128(m[q >> 1][q & 1], tab + 16384 + (4 * v + q) * 512);
      dft_a(m, y[0][2 * z], y[0][2 * z + 1], o[0]); dft_a(m, y[1][2 * z], y[1][2 * z + 1], o[1]);
#pragma unroll
      for (int q = 0; q < 4; q++) {
        const int i = 2 * z + (q & 1), c = v + (q & 2);
        uint32_t w[4]; lds128(w, in + 8192 + (4 * i + c) * 512);
        const float4 ph = lds128f(tab + 8192 + (4 * c + i) * 512);
#pragma unroll
        for (int b = 0; b < 2; b++) {
          const float cs = b ? ph.z : ph.x, sn = b ? ph.w : ph.y;
          const float r1 = __uint_as_float(w[2 * b] << 16), i1 = __uint_as_float(w[2 * b] & 0xFFFF0000u);
          const float r2 = __uint_as_float(w[2 * b + 1] << 16), i2 = __uint_as_float(w[2 * b + 1] & 0xFFFF0000u);
          const float Sr = r1 + r2, Si = i1 + i2, Dr = r1 - r2, Di = i1 - i2;
          const float ar = fmaf(-Dr, sn, Sr), ai = fmaf(-Di, sn, Si), dr = fmaf(Dr, sn, Sr), di = fmaf(Di, sn, Si), br = -Di * cs, bi = Dr * cs;
          const float Ar = o[0][0][2 * q + b], Ai = o[0][1][2 * q + b], Br = o[1][0][2 * q + b], Bi = o[1][1][2 * q + b];
          a[0][i][b][c] = pack2(fmaf(ar, Ai, fmaf(ai, Ar, fmaf(br, Bi, bi * Br))), fmaf(ar, Ar, fmaf(-ai, Ai, fmaf(br, Br, -bi * Bi))));
          a[1][i][b][c] = pack2(fmaf(dr, Bi, fmaf(di, Br, fmaf(-br, Ai, -bi * Ar))), fmaf(dr, Br, fmaf(-di, Bi, fmaf(-br, Ar, bi * Ai))));
        }
      }
    }
    if (l + dl <= 512) fetch_w(l + dl);
    cpa_commit();
    first();
#pragma unroll
    for (int s = 0; s < 2; s++) {
      uint4* dst = g_y + (s ? (1024 - l) & 1023 : l) * 256 + lane;
      const float sg = s ? -1.f : 1.f;
#pragma unroll
      for (int i = 0; i < 4; i++) {
        dft_b(D, y[s][i], o[0]);
#pragma unroll
        for (int b = 0; b < 2; b++)
          dst[(2 * i + b) * 32] = make_uint4(pack2(sg * o[0][0][b], o[0][1][b]), pack2(sg * o[0][0][2 + b], o[0][1][2 + b]),
                                             pack2(sg * o[0][0][4 + b], o[0][1][4 + b]), pack2(sg * o[0][0][6 + b], o[0][1][6 + b]));
      }
    }
  }
}

template <class F>
__device__ __forceinline__ void fft_rows_inv(const CUtensorMap* om, uint32_t sb, int cta, int ncta, F&& ready) {
  const int warp = threadIdx.x >> 5, lane = threadIdx.x & 31, g = lane >> 2, t = lane & 3, wg = warp >> 2, w4 = warp & 3;
  const uint32_t tb = sb + 32768 + wg * 2 * F_TSZ;
  const uint4* src = g_y + pin((256 * ((lane >> 1) & 3) + 64 * (lane >> 3) + 8 * w4) * 256 + (lane & 1));
  const uint32_t wa = pin(tb + (lane & 1) * 4 * F_TP + w4 * 1024 + (lane >> 1) * 4);
  uint4 pf[8];
  auto fetch = [&](int it, int hf) {
#pragma unroll
    for (int q = 0; q < 8; q++) pf[q] = __ldcg(src + (it * 2 + hf * 8192) + q * 256);
  };
  auto put = [&](uint32_t off) {
#pragma unroll
    for (int q = 0; q < 8; q++) {
      sts32(wa + off + q * 64, pf[q].x); sts32(wa + off + q * 64 + F_TP, pf[q].y);
      sts32(wa + off + q * 64 + 2 * F_TP, pf[q].z); sts32(wa + off + q * 64 + 3 * F_TP, pf[q].w);
    }
  };
  const int it0 = 2 * cta + wg;
  Dft D; make_dft<false>(D, g, t);
  float2 tw[4][8];
#pragma unroll
  for (int q = 0; q < 32; q++) {
    tw[q >> 3][q & 7] = cis(fidx<false>((q >> 1) & 3, g) * fidx<false>(q >> 3, 2 * t + (q & 1)), 1024);
    tw[q >> 3][q & 7].x *= 1.f / 2097152.f; tw[q >> 3][q & 7].y *= 1.f / 2097152.f;
    asm volatile("" : "+f"(tw[q >> 3][q & 7].x), "+f"(tw[q >> 3][q & 7].y) :: "memory");
  }
  ready();
  fetch(it0, 0); put(0); fetch(it0, 1); put(512);
  const uint32_t la = pin(tb + w4 * F_TP + lane * 16), ob = uni(sb + warp * 4096);
  const uint32_t oa = pin(ob + (lane >> 1) * 128 + (((4 * (lane & 1)) ^ ((lane >> 1) & 7)) << 4));
#pragma unroll 1
  for (int n = 0;; n++) {
    const int it = it0 + (n >> 1) * 2 * ncta, hf = n & 1, buf = (n >> 1) & 1;
    if (it >= 128) break;
    if (!hf) bar_sync(1 + wg, 128);
    uint32_t a[4][2][4], y[4][2][4];
#pragma unroll
    for (int q = 0; q < 8; q++) lds128(a[q >> 1][q & 1], la + buf * F_TSZ + hf * 4 * F_TP + q * 512);
    fetch(min(it + 2 * ncta, 127), hf);
    float o[2][8];
#pragma unroll
    for (int i = 0; i < 4; i++) {
      dft_b(D, a[i], o);
#pragma unroll
      for (int q = 0; q < 8; q++) y[q >> 1][q & 1][i] = twid(o[0][q], o[1][q], tw[i][q].x, tw[i][q].y);
    }
    if (lane == 0) asm volatile("cp.async.bulk.wait_group.read 0;" ::: "memory");
    __syncwarp();
#pragma unroll
    for (int c = 0; c < 4; c++) {
      dft_b(D, y[c], o);
#pragma unroll
      for (int ri = 0; ri < 2; ri++)
        stsm4((oa ^ (c << 4)) + (1 - ri) * 2048, pack2(o[ri][0], o[ri][1]), pack2(o[ri][2], o[ri][3]), pack2(o[ri][4], o[ri][5]), pack2(o[ri][6], o[ri][7]));
    }
    fence_async();
    __syncwarp();
    if (lane == 0) {
      const int m = 256 * w4 + 32 * ((it >> 1) & 7) + 8 * (it >> 5) + 4 * (it & 1) + 2 * hf + ((it >> 4) & 1);
      asm volatile("cp.async.bulk.tensor.3d.global.shared::cta.bulk_group [%0, {0, 0, %2}], [%1];" :: "l"(om), "r"(ob), "r"(2 * m) : "memory");
      asm volatile("cp.async.bulk.commit_group;" ::: "memory");
    }
    put((buf ^ 1) * F_TSZ + hf * 512);
  }
  if (lane == 0) asm volatile("cp.async.bulk.wait_group 0;" ::: "memory");
}
__device__ __forceinline__ void grid_arrive(unsigned* ctr) {
  __syncthreads();
  if (threadIdx.x == 0) { __threadfence(); atomicAdd(ctr, 1u); }
}
__device__ __forceinline__ void grid_wait(unsigned* ctr, unsigned n) {
  if (threadIdx.x == 224) {
    int it = 0;
    while (*reinterpret_cast<volatile unsigned*>(ctr) < n) { __nanosleep(100); if (++it > SPIN_LIMIT) { g_err = 3; break; } }
    __threadfence();
  }
  __syncthreads();
}

struct RecMaps { CUtensorMap wq, wk, wv, wo, x, k, q, v, fo; };
#define NSW 16
#define EXP 0
#define NPB 3
#define NPB0 2
#define NPC 0
#define WOP 2
#define HOME 7
#define DL0 14
#define PD1 4
#define NE4 6
#define NE6 0
#define NA4 14
#define NA6 18
#define NB1 24
#define TQL 7
#define NQ 16
#define TQP (NQ - 1)
#define OXPOS 4
#define KVPOS 2
#define NK0 0
#define FLPOS 1
#define XWPOS 10
#define FSPOS 28
#define RL0 4
#define RLS 6
#define RLB 4
#define VL0 3
#define RI 9
#define RJ 8
#define NPRE 22
#define PFD 4
#define PD0 4
#define VB NV0
#define NPA 0
#define N1 16
#define DL1 16
#define PACE 0
#define RE0 0
#define RE1 0
#define RP1 23
#define UNP 1
#define X2 2
#define X3 2
#define SPOS 2
#ifndef NV0
#define NV0 4
#endif
#define TGP 3
#define FENP 0
#define LW0 8
#define X1 4
#define X0 4
constexpr int R_WO = 0, R_X = 65536, R_MEM = 131072, R_WC = 147456, R_RED = R_WC + NSW * 2048, R_O = R_RED, R_S = R_O + 2048, R_P = R_S + 3072, R_STAGE = R_P + 2048,
              R_K = R_STAGE + 8192, R_Q = R_K + 8192, R_V = R_Q + 2048, R_ID = R_V + 16384, R_T = R_ID + 512, R_DST = R_T + 512, R_RD = R_DST + 2048, R_BAR = R_RD + 2048, R_TS = R_BAR + 128,
              R_TOTAL = R_TS;
#define TS(i)
#define LOG(i, v)
constexpr int B_KV = R_BAR, B_W = R_BAR + 8, B_X = R_BAR + 80, B_PK = R_BAR + 24, B_C = R_BAR + 32, B_B = R_BAR + 40, B_DUE = R_BAR + 48, B_ONE = R_BAR + 64;
#define DLY_A 150
#define DLY_V 150
#define DLY_C 200
#define DLY_L 90
#define NS_B 1120
#define NS_C 1728
#define NS_P 2624
#define NS_V 128
#define NS_F 896
#define NS_K 128
#define NS_M 32
#define NS_X 128
#define MG_Z 0x00010206
#define MG_Y 0x00010512
#define NS_PEN 1024
__device__ __forceinline__ float rcp(float x) { float r; asm("rcp.approx.ftz.f32 %0, %1;" : "=f"(r) : "f"(x)); return r; }
__device__ __forceinline__ uint32_t movm(uint32_t a) { uint32_t d; asm volatile("movmatrix.sync.aligned.m8n8.trans.b16 %0, %1;" : "=r"(d) : "r"(a)); return d; }
__device__ __forceinline__ uint32_t hadd2(uint32_t a, uint32_t b) { uint32_t d; asm("add.rn.bf16x2 %0, %1, %2;" : "=r"(d) : "r"(a), "r"(b)); return d; }
__device__ __forceinline__ void mma_a(float (&d)[4], const uint32_t (&a)[4], uint32_t b0, uint32_t b1) { mma16816(d, a[0], a[1], a[2], a[3], b0, b1); }
__device__ __forceinline__ bool elect() {
  uint32_t p; asm volatile("{.reg .pred p; elect.sync _|p, 0xffffffff; selp.u32 %0, 1, 0, p;}" : "=r"(p)); return p; }
__device__ __forceinline__ void tma3d(uint32_t dst, const CUtensorMap* m, int c1, int c2, uint32_t bar) {
  asm volatile("cp.async.bulk.tensor.3d.shared::cluster.global.mbarrier::complete_tx::bytes [%0], [%1, {0, %3, %4}], [%2];"
    :: "r"(dst), "l"(m), "r"(bar), "r"(c1), "r"(c2) : "memory"); }
__device__ __forceinline__ void tma4d(uint32_t dst, const CUtensorMap* m, int c1, int c2, uint32_t bar) {
  asm volatile("cp.async.bulk.tensor.4d.shared::cluster.global.mbarrier::complete_tx::bytes [%0], [%1, {0, %3, %4, 0}], [%2];"
    :: "r"(dst), "l"(m), "r"(bar), "r"(c1), "r"(c2) : "memory"); }
template <int OFF, int ACC>
__device__ __forceinline__ void wg_rs32(float (&d)[16], const uint32_t (&a)[4], uint32_t db) {
  if (ACC)
    asm volatile("{.reg .b64 db; .reg .b32 lo; add.u32 lo, %20, %21; mov.b64 db, {lo, 0x40000040};\n"
      "wgmma.mma_async.sync.aligned.m64n32k16.f32.bf16.bf16 {%0,%1,%2,%3,%4,%5,%6,%7,%8,%9,%10,%11,%12,%13,%14,%15}, {%16,%17,%18,%19}, db, 1, 1, 1, 0;}"
      : "+f"(d[0]), "+f"(d[1]), "+f"(d[2]), "+f"(d[3]), "+f"(d[4]), "+f"(d[5]), "+f"(d[6]), "+f"(d[7]), "+f"(d[8]), "+f"(d[9]), "+f"(d[10]), "+f"(d[11]), "+f"(d[12]), "+f"(d[13]), "+f"(d[14]), "+f"(d[15])
      : "r"(a[0]), "r"(a[1]), "r"(a[2]), "r"(a[3]), "r"(db), "n"(OFF));
  else
    asm volatile("{.reg .b64 db; .reg .b32 lo; add.u32 lo, %20, %21; mov.b64 db, {lo, 0x40000040};\n"
      "wgmma.mma_async.sync.aligned.m64n32k16.f32.bf16.bf16 {%0,%1,%2,%3,%4,%5,%6,%7,%8,%9,%10,%11,%12,%13,%14,%15}, {%16,%17,%18,%19}, db, 0, 1, 1, 0;}"
      : "=f"(d[0]), "=f"(d[1]), "=f"(d[2]), "=f"(d[3]), "=f"(d[4]), "=f"(d[5]), "=f"(d[6]), "=f"(d[7]), "=f"(d[8]), "=f"(d[9]), "=f"(d[10]), "=f"(d[11]), "=f"(d[12]), "=f"(d[13]), "=f"(d[14]), "=f"(d[15])
      : "r"(a[0]), "r"(a[1]), "r"(a[2]), "r"(a[3]), "r"(db), "n"(OFF));
}
template <int I> using IC = std::integral_constant<int, I>;
template <int I, int N, class F> __device__ __forceinline__ void sfor(F&& f) {
  if constexpr (I < N) { f(std::integral_constant<int, I>{}); sfor<I + 1, N>(f); }
}
__device__ __forceinline__ void keep(float (&d)[16]) {
  asm volatile("" : "+f"(d[0]), "+f"(d[1]), "+f"(d[2]), "+f"(d[3]), "+f"(d[4]), "+f"(d[5]), "+f"(d[6]), "+f"(d[7]),
      "+f"(d[8]), "+f"(d[9]), "+f"(d[10]), "+f"(d[11]), "+f"(d[12]), "+f"(d[13]), "+f"(d[14]), "+f"(d[15]) :: "memory");
}

template <int N, int S2 = 1024> __device__ __forceinline__ void ldx(uint32_t (&v)[N][4], const uint8_t* p) {
#pragma unroll
  for (int k = 0; k < 2 * N; k++) {
    const int i = k;
    asm volatile("ld.relaxed.gpu.global.v2.b32 {%0,%1}, [%2];" : "=r"(v[i >> 1][2 * (i & 1)]), "=r"(v[i >> 1][2 * (i & 1) + 1]) : "l"(p + (i & 3) * 256 + (i >> 2) * S2) : "memory");
  }
}
__device__ __forceinline__ uint32_t dif2(uint32_t a, uint32_t b, uint32_t tag) { uint32_t r; asm("lop3.b32 %0, %1, %2, %3, 0x7e;" : "=r"(r) : "r"(a), "r"(b), "r"(tag)); return r; }
__device__ __forceinline__ uint32_t dif2v(uint32_t a, uint32_t b, uint32_t tag) { uint32_t r; asm volatile("lop3.b32 %0, %1, %2, %3, 0x7e;" : "=r"(r) : "r"(a), "r"(b), "r"(tag)); return r; }
__device__ __forceinline__ uint32_t or3(uint32_t a, uint32_t b, uint32_t c) { uint32_t r; asm("lop3.b32 %0, %1, %2, %3, 0xfe;" : "=r"(r) : "r"(a), "r"(b), "r"(c)); return r; }
__device__ __forceinline__ uint32_t after(uint32_t x, float f, uint32_t z) { uint32_t r; asm("lop3.b32 %0, %1, %2, %3, 0xea;" : "=r"(r) : "r"(__float_as_uint(f)), "r"(z), "r"(x)); return r; }
__device__ __forceinline__ bool any_bit(uint32_t a, uint32_t b, uint32_t m) {
  uint32_t r; asm("lop3.b32 %0, %1, %2, %3, 0xa8;" : "=r"(r) : "r"(a), "r"(b), "r"(m)); return __any_sync(0xffffffffu, r); }
template <int W, int N> __device__ __forceinline__ bool stale(const uint32_t (&v)[N][4], uint32_t tag) {
  uint32_t x = dif2(v[0][0], v[0][2], tag);
  if (N == 4) x = or3(x, dif2(v[1][0], v[1][2], tag), dif2(v[2 % N][0], v[2 % N][2], tag));
  return any_bit(x, dif2(v[N - 1][0], v[N - 1][2], tag), 1);
}
template <int W, int N, int S2 = 1024> __device__ __forceinline__ void retry(uint32_t (&v)[N][4], const uint8_t* p, uint32_t tag, int& it) {
#pragma unroll 1
  do { ldx<N, S2>(v, p); it += INC_A; } while (stale<W>(v, tag) && it < SPIN_LIMIT);
}
__device__ __forceinline__ void mma_h(float (&d)[4], const uint32_t (&a)[4], const uint32_t (&b)[4], int hf) { mma16816(d, a[0], a[1], a[2], a[3], b[2 * hf], b[2 * hf + 1]); }
__device__ __forceinline__ void sts128(uint32_t a, const uint32_t (&r)[4]) { sts128(a, r[0], r[1], r[2], r[3]); }
__device__ __forceinline__ void sts128f(uint32_t a, const float* r) { sts128(a, __float_as_uint(r[0]), __float_as_uint(r[1]), __float_as_uint(r[2]), __float_as_uint(r[3])); }
__device__ __forceinline__ void mbar_spin(uint32_t bar, uint32_t par, int& it) {
  asm volatile("{.reg .pred p; .reg .b32 par; mov.b32 par, %2;\nLOOP: mbarrier.try_wait.parity.shared::cta.b64 p, [%1], par; @p bra.uni DONE;\n"
               "add.s32 %0, %0, 1; setp.le.s32 p, %0, %3; @p bra.uni LOOP;\nDONE: }" : "+r"(it) : "r"(bar), "r"(par), "n"(SPIN_LIMIT) : "memory"); }
__device__ __forceinline__ void warp_arrive(uint32_t bar) {
  __syncwarp(); asm volatile("{.reg .pred p; elect.sync _|p, 0xffffffff; @p mbarrier.arrive.shared::cta.b64 _, [%0];}" :: "r"(bar) : "memory"); }
__device__ __forceinline__ void delay_until(unsigned t) {
  asm volatile("{.reg .pred p; .reg .b64 c; .reg .b32 lo, hi;\nLOOP: mov.u64 c, %%clock64; mov.b64 {lo, hi}, c; sub.s32 lo, lo, %0; setp.lt.s32 p, lo, 0; @p bra.uni LOOP;}" :: "r"(t) : "memory"); }
__device__ __forceinline__ void cut(int it) { asm volatile("{.reg .pred p; setp.lt.s32 p, %0, 0;\nL: @p st.volatile.shared.u32 [%0], %0; @p bra.uni L;}" :: "r"(it) : "memory"); }
__device__ __forceinline__ void zero(float (&c)[4][4]) {
#pragma unroll
  for (int i = 0; i < 4; i++) c[i][0] = c[i][1] = c[i][2] = c[i][3] = 0.f;
}

__device__ __forceinline__ void sched() { asm volatile("griddepcontrol.launch_dependents;" ::: "memory"); }
__device__ __forceinline__ const uint8_t* pinp(const uint8_t* p) { return reinterpret_cast<const uint8_t*>(__shfl_xor_sync(0xffffffffu, reinterpret_cast<unsigned long long>(p), 0)); }
__device__ __forceinline__ uint32_t bar_or(int id, uint32_t x) {
  uint32_t r; asm volatile("{.reg .pred p, q; setp.ne.u32 p, %2, 0; bar.red.or.pred q, %1, 256, p; selp.u32 %0, 1, 0, q;}" : "=r"(r) : "r"(id), "r"(x) : "memory"); return r; }
__device__ __forceinline__ void bar_sync_unless(int id, uint32_t x) { asm volatile("{.reg .pred p; setp.eq.u32 p, %1, 0; @p bar.sync %0, 256;}" :: "r"(id), "r"((uint32_t)x) : "memory"); }
__device__ __forceinline__ void bar_arrive_unless(int id, uint32_t x) { asm volatile("{.reg .pred p; setp.eq.u32 p, %1, 0; @p bar.arrive %0, 256;}" :: "r"(id), "r"((uint32_t)x) : "memory"); }
__device__ __forceinline__ void stsm2t(uint32_t a, uint32_t r0, uint32_t r1, uint32_t x) {
  asm volatile("{.reg .pred p; setp.eq.u32 p, %3, 0; @p stmatrix.sync.aligned.m8n8.x2.trans.shared.b16 [%0], {%1,%2};}" :: "r"(a), "r"(r0), "r"(r1), "r"((uint32_t)x) : "memory"); }
__device__ __forceinline__ uint32_t or_and(uint32_t a, uint32_t b, uint32_t m) { uint32_t r; asm("lop3.b32 %0, %1, %2, %3, 0xa8;" : "=r"(r) : "r"(a), "r"(b), "r"(m)); return r; }
#define rare(x) __builtin_expect(!!(x), 0)
__device__ __forceinline__ uint32_t gtime() { unsigned long long g; asm volatile("mov.u64 %0, %%globaltimer;" : "=l"(g) :: "memory"); return (uint32_t)g; }
__device__ __forceinline__ void wait_time(uint32_t t) {
  asm volatile("{.reg .pred p; .reg .b32 g; .reg .b64 c;\nLOOP: mov.u64 c, %%globaltimer; cvt.u32.u64 g, c; sub.s32 g, %0, g; setp.lt.u32 p, g, 16384; @p bra.uni LOOP;}" :: "r"(t - 1) : "memory"); }
__device__ __forceinline__ uint32_t ldx32(const void* p) { uint32_t v; asm volatile("ld.relaxed.gpu.global.b32 %0, [%1];" : "=r"(v) : "l"(p) : "memory"); return v; }
__device__ __forceinline__ void stx32(const void* p, uint32_t v) { asm volatile("st.relaxed.gpu.global.b32 [%0], %1;" :: "l"(p), "r"(v) : "memory"); }

__global__ void __launch_bounds__(256, 1)
rec_kernel(const __grid_constant__ RecMaps maps, const bf16* __restrict__ xin, const bf16* __restrict__ mem0, Xchg* const gx,
           const bf16* __restrict__ fx, const bf16* __restrict__ wr, const bf16* __restrict__ wi) {
  extern __shared__ __align__(1024) uint8_t smem_raw[];
  const uint32_t sb = smem_u32(smem_raw);
  int role = blockIdx.x;
  {
    uint32_t smid, nsm; asm volatile("mov.u32 %0, %%smid;" : "=r"(smid)); asm volatile("mov.u32 %0, %%nsmid;" : "=r"(nsm));
    const int p = smid >> 1, u = p - 32;
    if (nsm == gridDim.x)
      role = (smid & 1) + (p < 32 ? 4 * ((p & 7) + 8 * (p >> 4)) + 2 * ((p >> 3) & 1) : p < 60 ? 4 * (16 + u % 7 + 7 * (u / 14)) + 2 * ((u / 7) & 1)
                         : p < 62 ? 2 * p + 8 : 2 * p - 4);
    role = uni(role);
  }
  if (role >= 128) {
    fft_cols(sb, role - 128, 4, [&]() { grid_wait(&gx->ctr[33], 128); });
    __threadfence(); __syncwarp();
    if ((threadIdx.x & 31) == 0) atomicAdd(&gx->ctr[32], 1u);
    __syncwarp();
    fft_rows_inv(&maps.fo, sb, role - 128, 4, [&]() { grid_wait(&gx->ctr[32], 32); });
    return;
  }
  const int tid = threadIdx.x, warp = uni(tid >> 5), lane = tid & 31, wg = warp >> 2, w4 = warp & 3, g = lane >> 2, t = lane & 3;
  const int h = role >> 2, j = role & 3, jh = j & 1;
  uint32_t w[48][4];
  float aq[16], av[16];
  int it = 0;

#define PT(k)
  auto pf_wo = [&]() {
    for (int i = 0; i < 4; i++)
      asm volatile("cp.async.bulk.prefetch.tensor.2d.L2.global [%0, {%1, %2}];" :: "l"(&maps.wo), "r"(256 * j + 64 * i), "r"(h * DH) : "memory");
  };
  fft_rows_fwd(fx, wr, wi, sb + R_MEM + 49152, role, [&]() {
    if (tid == 224) {
      mbar_init(sb + B_KV, 1); mbar_init(sb + B_W, 1); mbar_init(sb + B_X, 1); mbar_init(sb + B_X + 8, 1); mbar_init(sb + B_X + 16, 1); mbar_init(sb + B_X + 24, 1); mbar_init(sb + B_C, 4); mbar_init(sb + B_PK, 4); mbar_init(sb + B_B, 1);
      asm volatile("fence.mbarrier_init.release.cluster;" ::: "memory");
      mbar_expect_tx(sb + B_W, 3 * 65536);
      for (int i = 0; i < 4; i++) {
        tma2d(sb + R_X + i * 16384, &maps.wq, h * DH + 32 * j, i * 256, sb + B_W);
        if (i < 3) tma2d(sb + R_MEM + i * 16384, &maps.wk, h * DH + 32 * j, i * 256, sb + B_W);
        else asm volatile("cp.async.bulk.prefetch.tensor.2d.L2.global [%0, {%1, %2}];" :: "l"(&maps.wk), "r"(h * DH + 32 * j), "r"(768) : "memory");
      }
      for (int i = 0; i < 2; i++) tma2d(sb + R_WO + i * 32768, &maps.wv, h * DH + 64 * (j >> 1), jh * 512 + i * 256, sb + B_W);
      if (PFD) asm volatile("cp.async.bulk.prefetch.L2.global [%0], 2048;" :: "l"(xin + role * DM) : "memory");
      else for (int i = 0; i < 4; i++) asm volatile("cp.async.bulk.prefetch.L2.global [%0], 8192;" :: "l"(xin + role * 16384 + i * 4096) : "memory");
      if (WOP == 0) pf_wo();
      for (int i = 0; i < 5; i++) asm volatile("prefetch.tensormap [%0];" :: "l"(&maps.wo + i) : "memory");
    }
    __syncwarp();
  });
  if (tid < 16) sts32(sb + R_T + tid * 4, ~0u);
  fence_async();
  PT(0);
  grid_arrive(&gx->ctr[33]);
  PT(1);
  if (tid == 224) { tma2d(sb + R_MEM + 49152, &maps.wk, h * DH + 32 * j, 768, sb + B_W); if (WOP == 1) pf_wo(); }
  __syncwarp();
  uint8_t* const xb = reinterpret_cast<uint8_t*>(gx);
  auto probe_at = [&](int n) { return xb + (n ? offsetof(Xchg, C) + w4 * 8192 + role * 32 : offsetof(Xchg, B) + role * 8192 + warp * 128); };
  if (lane < 8) stx128(probe_at(lane >> 2) + (lane & 2) * 2048 + (lane & 1) * 16, 0, 0, 0, 0);
  uint32_t m0[4][4];
#pragma unroll
  for (int i = 0; i < 16; i++) m0[i >> 2][i & 3] = ldnc32(mem0 + g * DM + 128 * warp + 8 * i + 2 * t);
  mbar_spin(sb + B_W, 0, it);
  PT(2);
  const int lrow = (lane & 7) + ((lane >> 4) << 3), lhi = (lane >> 3) & 1;
  const int kq = wg ? 3 - 3 * jh : 3 * jh;
  const uint32_t LW = lrow * 128 + ((lhi ^ (lane & 7)) << 4);
  {
    const int chunk = w4 < 2 ? w4 + 2 * lhi : 2 * (w4 & 1) + lhi;
    uint32_t a = sb + (w4 < 2 ? R_X : R_MEM) + kq * 16384 + lrow * 64 + ((chunk ^ ((lrow >> 1) & 3)) << 4);
#pragma unroll
    for (int i = 0; i < 16; i++) ldsm4t(w[i], a + i * 1024);
    const uint32_t st = wg ? 1024 : 2048, av0 = sb + R_WO + (LW ^ (w4 << 5));
    const uint32_t a1 = wg ? a + (2 * jh - 1) * 16384 : av0 + jh * 32768, a2 = wg ? a + (2 * jh - 1) * 32768 : av0 + (1 - jh) * 32768;
#pragma unroll
    for (int i = 0; i < 16; i++) { ldsm4t(w[16 + i], a1 + i * st); ldsm4t(w[32 + i], a2 + i * st); }
  }
  uint32_t L16 = pin(lane * 16);
  const uint32_t uW = uni(sb + w4 * 512), uWo = uni(sb + R_WO + w4 * 16384), uMem = uni(sb + R_MEM + kq * 4096);
  const uint32_t dX = uni(((sb + R_X + kq * 16384) >> 4) | 0x10000u);
  auto load_wo = [&](uint32_t (&d)[32][4], int i0, int i1) {
#pragma unroll
    for (int i = i0; i < i1; i++) lds128(d[i], uWo + L16 + (i & 1) * 512 + (i >> 4) * 1024 + (i & 14) * 1024);
  };
  auto issue_x = [&](int n, int k) {
    const uint32_t bar = sb + B_X + 8 * k, q = k ^ (3 - 3 * jh);
    mbar_expect_tx(bar, 16384); tma3d(sb + R_X + q * 16384, &maps.x, n * SEG, 4 * q, bar);
  };
  auto store_stage = [&](int n) {
    asm volatile("cp.async.bulk.global.shared::cta.bulk_group [%0], [%1], 8192; cp.async.bulk.commit_group;"
                 :: "l"(g_kqv[n & 3][role]), "r"(sb + R_STAGE) : "memory");
  };
  auto issue_kqv = [&](int n) {
    const int p = (n & 3) * 128 + 4 * h;
    mbar_expect_tx(sb + B_KV, 26624);
    tma3d(sb + R_K, &maps.k, 0, p, sb + B_KV); tma3d(sb + R_Q, &maps.q, 8 + 2 * j, p, sb + B_KV); tma3d(sb + R_V, &maps.v, 16, p, sb + B_KV);
  };
  auto fetch4k = [&](uint32_t dst, uint32_t off, uint32_t bar, uint32_t t) {
    asm volatile("{.reg .pred p, q; .reg .b32 g; .reg .b64 c; elect.sync _|q, 0xffffffff; @q mbarrier.arrive.expect_tx.shared::cta.b64 _, [%2], 4096;\n"
                 "LOOP: mov.u64 c, %%globaltimer; cvt.u32.u64 g, c; sub.s32 g, %3, g; setp.lt.u32 p, g, 16384; @p bra.uni LOOP;\n"
                 "@q cp.async.bulk.shared::cluster.global.mbarrier::complete_tx::bytes [%0], [%1], 4096, [%2];}" :: "r"(dst), "l"(xb + off), "r"(bar), "r"(t - 1) : "memory");
  };
  uint32_t uS;
  auto my_b = [&]() { return offsetof(Xchg, B) + role * 8192 + ((uS + ((uint32_t)it >> 31)) & 1) * 4096; };
  auto issue_c = [&](uint32_t t) { fetch4k(sb + R_MEM + w4 * 4096, offsetof(Xchg, C) + w4 * 8192 + ((uS + ((uint32_t)it >> 31)) & 4096), sb + B_C, t); };
  auto wait_x = [&](int n, int i) { if (!(EXP & 1) || n < 2) mbar_spin(sb + B_X + 8 * i, n & 1, it); };
#define PACED(d0) uint32_t dz = d0; const uint32_t z = (uint32_t)it >> 31; auto pace = [&]() { for (int k = 0; k < PACE; k++) { if (k & 1) asm("add.u32 %0, %0, %1;" : "+r"(dz) : "r"(z)); else asm("xor.b32 %0, %0, %1;" : "+r"(dz) : "r"(z)); } };
  auto project_v = [&](auto I0, auto I1, auto&& mid) {
    PACED(decltype(I0)::value < 16 ? dX : dX ^ 1024);
    wg_fence();
    sfor<decltype(I0)::value, decltype(I1)::value>([&](auto I) {
      constexpr int i = decltype(I)::value;
      mid(i);
      if (i == 16 && decltype(I0)::value < 16) dz ^= 1024;
      wg_rs32<((i >> 2) & 3) * 256 + (i & 3) * 2, (i > 0)>(av, w[16 + i], dz);
      pace();
    });
    wg_commit();
  };
  auto project_qk = [&](auto I0, auto I1, auto first, auto&& mid) {
    PACED((dX ^ (decltype(I0)::value >> 4 << 10)) + ((uint32_t)it >> 31));
    wg_fence();
    sfor<decltype(I0)::value, decltype(I1)::value>([&](auto I) {
      constexpr int i = decltype(I)::value;
      mid(i);
      wg_rs32<((i >> 2) & 3) * 256 + (i & 3) * 2, !decltype(first)::value || i != decltype(I0)::value>(aq, w[i], dz);
      pace();
    });
    wg_commit();
  };
  const uint32_t uP = uni(sb + R_X + 3 * jh * 16384 + w4 * 512);
  auto park = [&]() {
    bar_sync(1, 128);
#pragma unroll
    for (int i = 0; i < 4; i++) sts128f(uP + L16 + i * 2048, aq + 4 * i);
    warp_arrive(sb + B_PK);
  };
  auto unpark = [&]() {
#pragma unroll
    for (int i = 0; i < 4; i++) {
      const float4 p = lds128f(uP + L16 + i * 2048);
      av[4 * i] = p.x; av[4 * i + 1] = p.y; av[4 * i + 2] = p.z; av[4 * i + 3] = p.w;
    }
  };
  auto fin_qk = [&]() {
#pragma unroll
    for (int i = 0; i < 16; i++) aq[i] += av[i];
    const uint32_t a = sb + R_STAGE + (w4 < 2 ? 2048 + w4 * 128 : (w4 & 1) * 256) + (L16 & 112) + (L16 >> 7) * 512;
    stsm4t(a, pack2(aq[0], aq[1]), pack2(aq[4], aq[5]), pack2(aq[8], aq[9]), pack2(aq[12], aq[13]));
    stsm4t(a + (w4 < 2 ? 256 : 128), pack2(aq[2], aq[3]), pack2(aq[6], aq[7]), pack2(aq[10], aq[11]), pack2(aq[14], aq[15]));
  };
  auto fin_v = [&]() {
#pragma unroll
    for (int a = 0; a < 2; a++)
      sts128(sb + R_STAGE + 4096 + w4 * 1024 + a * 512 + L16, pack2(av[8 * a], av[8 * a + 1]), pack2(av[8 * a + 2], av[8 * a + 3]),
             pack2(av[8 * a + 4], av[8 * a + 5]), pack2(av[8 * a + 6], av[8 * a + 7]));
  };
  __syncthreads();
  if (tid == 224) {
#pragma unroll 1
    for (int i = 0; i < 4; i++) issue_x(0, i);
    mbar_expect_tx(sb + B_W, 65536);
    for (int i = 0; i < 4; i++) tma2d(sb + R_WO + i * 16384, &maps.wo, 256 * j + 64 * i, h * DH, sb + B_W);
  }
  __syncwarp();
  if (wg) {
#pragma unroll
    for (int i = 0; i < NSW; i++) sts128(uW + R_WC + L16 + i * 2048, w[i]);
  }
#pragma unroll
  for (int i = 0; i < 4; i++) sts128(sb + R_MEM + warp * 2048 + i * 512 + (g >> 1) * 128 + t * 32 + (g & 1) * 16, m0[i]);
  auto probe = [&](int n, int cnt) {
    if (lane == 0) {
#pragma unroll 1
      for (int i = role >> 7; i < cnt; i++) {
        const int k = (i ^ wg) & 1;
        const unsigned t0 = clk();
        uint32_t v; asm volatile("atom.relaxed.gpu.global.exch.b32 %0, [%1], 0;" : "=r"(v) : "l"(probe_at(n) + k * 4096) : "memory");
        if (v == 0) asm volatile("red.shared.min.u32 [%0], %1;" :: "r"(sb + R_T + (n ? w4 * 8 : 32) + k * 4), "r"(clk() - t0) : "memory");
      }
    }
    __syncwarp();
  };
#pragma unroll 1
  for (int n = 0; n < 2; n++) {
    probe(0, n ? NPB : NPB0);
    asm volatile("{.reg .pred p; cp.async.bulk.wait_group 0; setp.eq.u32 p, %1, 97; @p red.relaxed.gpu.global.add.u32 [%0], 1;}" :: "l"(&gx->ctr[h]), "r"(tid ^ n ^ (1 - n) << 9) : "memory");
    PT(3 + 3 * n);
    wait_x(n, 2);
    PT(4 + 3 * n);
    if (wg == 0) {
      wait_x(n, 3);
      project_qk(IC<0>{}, IC<16>{}, IC<1>{}, [](int) {});
      project_v(IC<0>{}, IC<32>{}, [](int) {});
      wg_wait<0>(); keep(aq); keep(av);
      park();
      fin_v();
      fence_async();
    } else {
      wait_x(n, 0); wait_x(n, 1);
      project_qk(IC<32>{}, IC<48>{}, IC<1>{}, [](int) {});
      project_qk(IC<16>{}, IC<32>{}, IC<0>{}, [](int) {});
      project_qk(IC<0>{}, IC<16>{}, IC<0>{}, [](int) {});
      mbar_spin(sb + B_PK, n, it);
      unpark();
      wg_wait<0>(); keep(aq);
      fin_qk();
      fence_async();
    }
    __syncthreads();
    if (tid == 0 && n) stx32(&gx->S[role], 1 + (HOME & 2 && lds32(sb + R_T + 36) < lds32(sb + R_T + 32)));
    PT(5 + 3 * n);
    if (tid == 96 && n == 0) store_stage(0);
    if (tid == 128 && n == 0) {
#pragma unroll 1
      for (int i = 0; i < 4; i++) issue_x(1, i);
    }
    if (warp == 5 && n == 1) {
#pragma unroll 1
      while (__any_sync(0xffffffffu, ldx32(&gx->ctr[h]) < 4) && ++it < SPIN_LIMIT) {}
      if (elect()) issue_kqv(0);
    }
    __syncwarp();
  }
  mbar_spin(sb + B_W, 1, it);
  PT(9);
#pragma unroll
  for (int i = 0; i < 4; i++) {
    uint32_t f[4][4];
    const uint32_t a = sb + R_WO + warp * 8192 + i * 2048;
#pragma unroll
    for (int q = 0; q < 4; q++) ldsm4t(f[q], a + (LW ^ (q << 5)));
    __syncwarp();
#pragma unroll
    for (int q = 0; q < 4; q++) sts128(a + q * 512 + L16, f[q]);
  }
  if (NPC) probe(1, NPC);
  {
    const int o = 32 * w4 + 16 * wg + 4 * t + j;
    uint32_t v;
#pragma unroll 1
    while (__any_sync(0xffffffffu, (v = ldx32(&gx->S[o])) == 0) && ++it < SPIN_LIMIT) {}
    asm volatile("st.shared.u64 [%0], %1;" :: "r"(sb + R_DST + wg * 1024 + w4 * 256 + lane * 8), "l"(xb + offsetof(Xchg, B) + o * 8192 + (v >> 1) * 4096 + h * 128 + ((g ^ h) & 7) * 16) : "memory");
  }
  if (wg == 0) {
    const uint64_t cd = reinterpret_cast<uint64_t>(xb + (offsetof(Xchg, C) + j * 8192 + h * 128 + w4 * 32 + (L16 & 16) * 256 + (L16 & 64) / 4 + (L16 >> 7) * 4));
    sts128(uW + R_RD + L16, (uint32_t)cd, (uint32_t)(cd >> 32), sb + R_MEM + (L16 & 112) * 8 + (L16 >> 8) * 1024 + ((w4 * 32 + ((L16 >> 3) & 16)) ^ (L16 & 112)),
           (L16 >> 6) == (h & 3) * 2 + ((h >> 2) & 1) ? 0xFFFE0000u : 0xFFFFFFFFu);
  }
  if (tid == 0) sts32(sb + B_DUE + 8, gtime() & ~31u);
  PT(10);
  mbar_spin(sb + B_KV, 0, it);
  PT(11);
  if (tid < 4) sts32(sb + B_ONE + tid * 4, 0x3F803F80u);
  if (warp == 1) { const uint32_t e = g >> 1 == t ? 0x3F80u << (16 * (g & 1)) : 0u; sts128(sb + R_ID + L16, e, 0, 0, e); }
  __syncthreads();
  {
    const uint32_t kb = lds32(sb + R_T + 36) < lds32(sb + R_T + 32);
    uS = uni((HOME & 4 ? (__popc(((offsetof(Xchg, B) / 4096 + 2 * role) ^ (offsetof(Xchg, C) / 4096 + 2 * w4)) & 0xb3) ^ kb) & 1 : lds32(sb + R_T + w4 * 8 + 4) < lds32(sb + R_T + w4 * 8)) * 4096 + kb);
  }

  const float sc = 0.08838834764831845f * 1.4426950408889634f;
  uint8_t* const xa = xb + uni(h * 16384);
  const uint32_t uA = uni(wg ? (w4 >> 1) * 2048 + j * 512 + (w4 & 1) * 256 : 8192 + (4 * (j >> 1) + w4) * 512 + jh * 256);
  const uint32_t uP2 = uni(sb + R_P + w4 * 256);
  uint32_t nc = 1;
  uint32_t ma;
  const uint8_t* adst;
  auto pin_mem = [&]() { adst = pinp(xa + uA + L16 / 2); ma = pin(uMem + (L16 & 384) + (L16 & 48) * 2 + (L16 & 64) / 4); };
  pin_mem();

#pragma unroll 1
  for (int s = 0;; nc++) {
    const uint32_t tag = (s + 1) & 1;
    auto fresh = [&]() { L16 += (uint32_t)it >> 31; };
    auto get_due = [&]() { return lds32(sb + B_DUE + 4 + tag * 4); };
    float c[4][4], r4[4];
    auto fold = [&]() {
#pragma unroll
      for (int i = 0; i < 4; i++) r4[i] = ((c[0][i] + c[1][i]) + c[2][i]) + c[3][i];
    };
    auto mma4 = [&](int n, const uint32_t (&b0)[4], const uint32_t (&b1)[4]) {
      mma_h(c[0], w[n + 2], b1, 0); mma_h(c[1], w[n + 3], b1, 1); mma_h(c[2], w[n], b0, 0); mma_h(c[3], w[n + 1], b0, 1);
    };
    auto xpos = [&](int pos, int wp) {
      if ((pos == X0 || pos == X1 || pos == X2 || pos == X3) && warp == wp && s + 1 < NSEG && elect()) {
        const int z = (uint32_t)it >> 31;
        if (pos == X2) issue_x(s + 2, 2 + z);
        if (pos == X3) issue_x(s + 2, 3 + z);
        if (pos == X1) issue_x(s + 2, 1 + z);
        if (pos == X0) issue_x(s + 2, z);
      }
      __syncwarp();
    };
    if (wg == 0) {
      mbar_spin(sb + B_C, nc & 1, it);
      TS(13);
      uint32_t b[16][4], tg[4];
#pragma unroll
      for (int i = 0; i < PD0; i++) { lds128(b[i], ma + i * 512); __syncwarp(); }
      sched();
      zero(c);
#pragma unroll
      for (int i = 0; i < 8; i++) {
        const int k = i ^ 1;
        mma_h(c[0], w[2 * k], b[k], 0); mma_h(c[1], w[2 * k + 1], b[k], 1);
        if (i < 2 * NV0) { mma_h(c[2], w[16 + 2 * k], b[k], 0); mma_h(c[3], w[17 + 2 * k], b[k], 1); }
        sched();
        if ((i & 1) && i + PD0 < 9) { lds128(b[i + PD0 - 1], ma + (i + PD0 - 1) * 512); __syncwarp(); lds128(b[i + PD0], ma + (i + PD0) * 512); sched(); }
        if (i == TGP) {
          fresh();
#pragma unroll
          for (int k = 0; k < 4; k++) tg[k] = lds32((uW * 4 + L16) * 2 + (L16 >> 6) * 4 + (R_MEM + k * 1024 - 7 * sb));
          sched();
        }
      }
#pragma unroll
      for (int i = 0; i < 4; i++) { r4[i] = c[0][i] + c[1][i]; c[0][i] = c[1][i] = 0.f; }
      sts128f(uW + R_RED + L16, r4);
      TS(1);
      const uint32_t old = bar_or(4, (dif2(tg[0], tg[1], s) | dif2(tg[2], tg[3], s)) & (s > 0));
      TS(0);
#pragma unroll
      for (int i = 0; i < 2 * NV0; i++) { lds128(b[8 + i], (ma ^ 4096) + i * 512); __syncwarp(); }
      sched();
#pragma unroll
      for (int i = NV0; i < 8; i++) {
        if (VB && i == VB) bar_sync(7, 256);
        mma4(16 + 4 * i, b[2 * i], b[2 * i + 1]);
        if (i < 7) sched();
        if (i < 4) { lds128(b[8 + 2 * i], (ma ^ 4096) + i * 1024); __syncwarp(); lds128(b[9 + 2 * i], (ma ^ 4096) + i * 1024 + 512); sched(); }
      }
      fold();
      asm volatile("{.reg .pred p; setp.eq.u32 p, %3, 0; @p st.relaxed.gpu.global.v2.b32 [%0], {%1,%2};}" :: "l"(adst), "r"((pack2(r4[0], r4[1]) & ~1u) | tag), "r"(pack2(r4[2], r4[3])), "r"(old) : "memory");
      sched();
      const unsigned tpub = clk();
      if (__any_sync(0xffffffffu, old) && nc < NC_MAX) {
        bar_sync(3, 256);
        issue_c(gtime());
        continue;
      }
      TS(3);
      xpos(0, 0);
      const uint32_t due = get_due();
      uint32_t vf[4][4], vm[2][4], p[4], pm, o[4];
      const uint32_t va = sb + R_V + (w4 >> 1) * 8192 + (w4 & 1) * 2048 + L16;
#pragma unroll
      for (int i = 0; i < 4; i++) {
        uint32_t q[4]; lds128(vf[i], va + i * 512); lds128(q, va + 4096 + i * 512);
#pragma unroll
        for (int e = 0; e < 4; e++) vf[i][e] = hadd2(vf[i][e], q[e]);
      }
      const uint32_t pa = pin(sb + R_P + (L16 >> 1));
      const uint8_t* vsrc = pinp(xa + 8192 + w4 * 1024 + L16 / 2);
      uint32_t one[4];
      lds128(one, sb + B_ONE);
      auto pv_x = [&]() {
        zero(c);
        mma_a(c[2], one, p[0], p[1]);
        mma_a(c[0], vf[0], p[0], p[1]); mma_a(c[1], vf[2], p[0], p[1]);
        sched();
        mma_a(c[2], one, p[2], p[3]);
        mma_a(c[0], vf[1], p[2], p[3]); mma_a(c[1], vf[3], p[2], p[3]);
        sched();
      };
      auto pv_m = [&]() {
        mma1688(c[2], one[0], one[1], pm);
        mma_a(c[0], vm[0], pm, pm);
        sched();
        mma_a(c[1], vm[1], pm, pm);
      };
      auto norm = [&]() {
        const float n0 = rcp(c[2][0]), n1 = rcp(c[2][1]);
#pragma unroll
        for (int i = 0; i < 4; i++) o[i] = pack2(c[i >> 1][2 * (i & 1)] * n0, c[i >> 1][2 * (i & 1) + 1] * n1);
        return ((__float_as_uint(c[2][0]) - 0x1F800000u) | (__float_as_uint(c[2][1]) - 0x1F800000u)) >> 30;
      };
      auto load_m = [&](int x) { const float2 e0 = lds64f(pa + 512 + x * 1024), e1 = lds64f(pa + 768 + x * 1024); pm = pack2(e0.x * e1.x, e0.y * e1.y); };
      auto attend_max = [&](int x) {
        float2 sv[6];
#pragma unroll
        for (int i = 0; i < 6; i++) sv[i] = lds64f(pa - 3072 + x * 1536 + i * 256);
        sv[4].x += sv[5].x; sv[4].y += sv[5].y;
        const int dq = (int)(L16 >> 6) - (int)((L16 >> 3) & 6) + 8 * j;
        float m = fmaxf(sv[4].x, sv[4].y);
#pragma unroll
        for (int i = 0; i < 4; i++) {
          if (x && 8 * i > dq) sv[i].x = -INFINITY;
          if (x && 8 * i + 1 > dq) sv[i].y = -INFINITY;
          m = fmaxf(m, fmaxf(sv[i].x, sv[i].y));
        }
        m = fmaxf(m, __shfl_xor_sync(0xffffffffu, m, 1));
        m = fmaxf(m, __shfl_xor_sync(0xffffffffu, m, 2));
#pragma unroll
        for (int i = 0; i < 5; i++) (i < 4 ? p[i] : pm) = pack2(ex2(sv[i].x - m), ex2(sv[i].y - m));
        pv_x(); pv_m(); norm();
      };
      uint32_t tq[4];
      auto get_t = [&]() {
        tq[0] = tq[1] = tq[2] = tq[3] = 0;
        asm volatile("{.reg .pred p; setp.eq.u32 p, %5, 0; @p ld.relaxed.gpu.global.v4.b32 {%0,%1,%2,%3}, [%4];}"
                     : "+r"(tq[0]), "+r"(tq[1]), "+r"(tq[2]), "+r"(tq[3]) : "l"(xb + offsetof(Xchg, T) + L16 * 8), "r"(warp) : "memory");
      };
      delay_until(tpub + DLY_V);
      wait_time(due + NS_V);
      TS(4);
      ldx(vm, vsrc);
      sched();
      xpos(2, 2);
      auto store_kqv = [&]() {
        fence_async();
        if (!(EXP & 4))
          asm volatile("{.reg .pred p; elect.sync _|p, 0xffffffff; @p cp.async.bulk.global.shared::cta.bulk_group [%0], [%1], 2048; cp.async.bulk.commit_group;}"
                       :: "l"(g_kqv[(s + 1) & 3][role] + w4 * 128), "r"(sb + R_STAGE + w4 * 2048) : "memory");
      };
      if (SPOS == 2) store_kqv();
      sched();
      bar_sync(5, 256);
      ldsm4(p, sb + R_P + L16);
      load_m(0);
      pv_x();
      ldsm4(p, sb + R_P + 1024 + L16);
      pv_m();
      const uint32_t r = norm(), tl = after(tag, c[2][0], (uint32_t)it >> 31);
      const bool redo = __any_sync(0xffffffffu, r | ((dif2(vm[0][0], vm[0][2], tl) | dif2(vm[1][0], vm[1][2], tl)) & 1));
      TS(6);
      stsm4t(uW + R_O + L16, o[0], o[1], o[2], o[3]);
      bar_arrive_unless(6, redo);
      sched();
      if (TQL == 7) get_t();
      TS(7);
      pv_x();
      if (rare(redo)) retry<2>(vm, vsrc, tag, it);
      bar_sync(8, 256);
      load_m(1);
      pv_m();
      if (rare(__any_sync(0xffffffffu, norm()) || redo)) {
        fresh();
#pragma unroll 1
        for (int x = !redo; x < 2; x++) {
          attend_max(x);
          if (x == 0) { stsm4t(uW + R_O + L16, o[0], o[1], o[2], o[3]); bar_arrive(6, 256); }
        }
      }
      TS(8);
      if (TQL == 8) get_t();
      const bool xok = mbar_test(sb + B_X + 16, s & 1) & mbar_test(sb + B_X + 24, s & 1);
      xpos(4, 2);
      fresh();
      const uint32_t ob = uni(sb + R_MEM + 4096 + w4 * 1024);
      stsm4t(ob + (L16 & 112) * 4 + (((L16 >> 3) ^ (L16 >> 1)) & 48), o[0], o[1], o[2], o[3]);
      __syncwarp();
      uint32_t rd[4];
      lds128(rd, uW + R_RD + L16);
      lds128(o, ob + (L16 ^ ((L16 >> 3) & 48)));
      auto put_o = [&]() {
        *reinterpret_cast<uint4*>(reinterpret_cast<uint8_t*>(g_ox) + (((s * SEG + 8 * j) * HD + h * DH + 32 * w4) * 2 + (L16 >> 6) * (HD * 2) + (L16 & 48))) = make_uint4(o[0], o[1], o[2], o[3]);
      };
      if (s + 1 == NSEG) { put_o(); asm volatile("cp.async.bulk.wait_group 0;" ::: "memory"); break; }
      asm volatile("cp.async.bulk.wait_group 0;" ::: "memory");
      if (elect()) stx32(xa + 4096 + j * 16 + w4 * 4, s + 1);
      __syncwarp();
      if (rare(!xok)) { wait_x(s + 2, 3); wait_x(s + 2, 2); }
      TS(9);
      fresh();
      const uint32_t e = due | ((s + 1) & 31);
      project_qk(IC<0>{}, IC<NQ>{}, IC<1>{}, [&](int n) {
        if (n == OXPOS) { __syncwarp(); put_o(); __syncwarp(); }
        if (n == TQP) { __syncwarp(); tq[0] = dif2v(tq[0], tq[1], e) | dif2v(tq[2], tq[3], e); __syncwarp(); }
      });
      if (NPA) project_v(IC<0>{}, IC<NPA>{}, [](int) {});
      TS(2);
      if (warp == 0) {
        uint32_t last = due, nx = NS_P;
        if (rare(__any_sync(0xffffffffu, tq[0]))) {
          const uint32_t ref = gtime();
#pragma unroll 1
          do ldx128(o, xb + offsetof(Xchg, T) + L16 * 8); while (any_bit(or3(o[0] - s - 1, o[1] - s - 1, o[2] - s - 1), o[3] - s - 1, 30) && ++it < SPIN_LIMIT);
          const int d = max(max((int)(o[0] - ref), (int)(o[1] - ref)), max((int)(o[2] - ref), (int)(o[3] - ref)));
          last = (ref + __reduce_max_sync(0xffffffffu, d)) & ~31u;
          if (last != due) nx += NS_X;
        }
        const uint32_t bdue = last + NS_B;
        if (s < 4) { last += (MG_Y >> 8 * s & 255) * 32; nx += (MG_Z >> 8 * s & 255) * 32; }
        sts32(sb + B_DUE, last);
        sts32(sb + B_DUE + 8 - tag * 4, last + nx);
        fetch4k(sb + R_MEM, my_b(), sb + B_B, bdue);
        LOG(13, tl - last);
        LOG(9, last);
      }
      if (NQ < 16) project_qk(IC<NQ>{}, IC<16>{}, IC<0>{}, [](int) {});
      project_v(IC<NPA>{}, IC<NPRE>{}, [](int) {});
      const uint32_t ba = rd[2], msk = rd[3];
      const uint8_t* cdst = reinterpret_cast<const uint8_t*>(rd[0] | (uint64_t)rd[1] << 32);
      TS(14);
      mbar_spin(sb + B_B, s & 1, it);
      TS(10);
      uint32_t bq[2][4];
      auto sum_b = [&]() {
        ldsm4t(bq[0], ba); ldsm4t(bq[1], ba + 2048);
        sched();
#pragma unroll
        for (int i = 0; i < 8; i++) c[i >> 2][i & 3] = 0.f;
        mma_a(c[0], bq[0], 0x3F803F80u, 0x3F803F80u); mma_a(c[1], bq[1], 0x3F803F80u, 0x3F803F80u);
        const uint32_t t2 = tag * 0x10001u;
        const bool old = any_bit(or3(dif2(bq[0][0], bq[0][1], t2), dif2(bq[0][2], bq[0][3], t2), dif2(bq[1][0], bq[1][1], t2)), dif2(bq[1][2], bq[1][3], t2), L16 < 64 ? 0x10001u : 0u);
        const uint32_t T = (tag << 16) & ~msk, u = ((__float_as_uint(c[0][0] + c[1][0]) + ((0x10000u & ~msk) - T)) & msk) | T;
        asm volatile("{.reg .pred p; setp.eq.u32 p, %2, 0; @p st.relaxed.gpu.global.b32 [%0], %1;}"
                     :: "l"(cdst), "r"(pack2(__uint_as_float(u), c[0][2] + c[1][2])), "r"((uint32_t)(old || (L16 & 32))) : "memory");
        return old;
      };
      if (rare(sum_b())) {
#pragma unroll 1
        do {
          const uint8_t* p = xb + (my_b() + (ba - sb - R_MEM));
          ldx128(bq[0], p); ldx128(bq[1], p + 2048);
          sts128(ba, bq[0]); sts128(ba + 2048, bq[1]);
          __syncwarp();
          it += INC_B;
        } while (sum_b() && it < SPIN_LIMIT);
      }
      sched();
      TS(11);
      bar_arrive(0, 256);
      const unsigned tc = clk();
      const uint32_t cdue = lds32(sb + B_DUE) + NS_C;
      if (warp == 3) LOG(11, gtime() - cdue);
      fresh();
      wg_wait<0>(); keep(aq); keep(av);
      park();
      if (NPRE < 32) project_v(IC<NPRE>{}, IC<32>{}, [](int) {}); else fin_v();
      TS(12);
      delay_until(tc + DLY_C);
      issue_c(cdue);
      TS(5);
      LOG(warp, it);
      pin_mem();
      if (NPRE < 32) { wg_wait<0>(); keep(av); fin_v(); }
      if (!(EXP & 2)) mbar_spin(sb + B_KV, tag, it);
      TS(15);
    } else {
      uint32_t kf[8][4];
      auto load_k = [&]() {
        const uint32_t ka = sb + R_K + w4 * 1024 + (L16 & 112) + (L16 & 128) * 4 + (L16 & 256);
#pragma unroll
        for (int i = 0; i < 8; i++) ldsm4(kf[i], ka + (i >> 1) * 2048 + (i & 1) * 128);
      };
      auto put_p = [&](int x, uint32_t old, uint32_t again) {
        float e[4];
        const int dq = (int)((L16 >> 3) & 6) + 8 * j - (int)(L16 >> 6) - 16 * w4;
#pragma unroll
        for (int i = 0; i < 4; i++) { r4[i] = fmaf(c[3][i], sc, fmaf(c[2][i], sc, fmaf(c[0][i] + c[1][i], sc, __uint_as_float(i == 3 ? 0u - old : 0u)))); e[i] = x && dq + (i & 1) < 8 * (i >> 1) ? 0.f : ex2(r4[i]); }
        stsm2t(uP2 + x * 1024 + L16, pack2(e[0], e[1]), pack2(e[2], e[3]), again);
      };
      auto put_s = [&](int x) {
#pragma unroll
        for (int i = 0; i < 4; i++) sts32f(uW + R_S + x * 1536 + (L16 & 48) * 4 + (L16 >> 6) * 4 + (i & 1) * 32 + (i >> 1) * 256, r4[i]);
      };
      auto load_q = [&](uint32_t (&q)[4], uint32_t off) { ldsm4(q, sb + R_Q + (L16 & 112) + (L16 & 128) * 2 + (L16 >> 8) * 128 + off); };
      mbar_spin(sb + B_C, nc & 1, it);
      TS(13);
      float4 o4;
      uint32_t id[4], old;
      {
        uint32_t b[24][4];
#pragma unroll
        for (int i = 0; i < 2 * PD1; i++) { lds128(b[i], ma + i * 512); __syncwarp(); }
        sched();
        zero(c);
#pragma unroll
        for (int i = 0; i < 12; i++) {
          mma4(4 * i, b[2 * i], b[2 * i + 1]);
          if (i < 11) sched();
          if (i + PD1 < 12) { const int k = i + PD1; const uint32_t a = (ma ^ (k >> 2 << 12)) + (k & 3) * 1024; lds128(b[2 * k], a); __syncwarp(); lds128(b[2 * k + 1], a + 512); sched(); }
          if (i == RJ) { lds128(id, sb + R_ID + L16); sched(); }
          if (i == RI) { old = bar_or(4, 0); o4 = lds128f(uW + R_RED + L16); sched(); }
        }
      }
      TS(0);
      {
        float e[4] = {o4.x, o4.y, o4.z, o4.w};
#pragma unroll
        for (int i = 0; i < 4; i++) { r4[i] = (((e[i] + c[0][i]) + c[1][i]) + c[2][i]) + c[3][i]; e[i] = 0.f; }
        mma_a(e, id, pack2(r4[0], r4[1]), pack2(r4[2], r4[3]));
        sched();
        if (VB) bar_arrive(7, 256);
        sched();
        asm volatile("{.reg .pred p; setp.eq.u32 p, %3, 0; @p st.relaxed.gpu.global.v2.b32 [%0], {%1,%2};}" :: "l"(adst),
                     "r"((__byte_perm(__float_as_uint(e[0]), __float_as_uint(e[1]), 0x7632) & ~1u) | tag), "r"(__byte_perm(__float_as_uint(e[2]), __float_as_uint(e[3]), 0x7632)), "r"(old) : "memory");
        sched();
      }
      const unsigned tpub = clk(), now = gtime(), due = get_due();
      if (__any_sync(0xffffffffu, old) && nc < NC_MAX) { bar_sync(3, 256); continue; }
      TS(2);
      const uint8_t* asrc = pinp(adst + ((warp == 7) * 1024 - (int)uA));
      fresh();
      uint32_t wo[32][4];
      bool xok;
      auto reload = [&]() {
        sched();
#pragma unroll
        for (int i = RE0 + RE1; i < NSW; i++) lds128(w[i], uW + R_WC + L16 + i * 2048);
        sched();
      };
      auto out_proj = [&]() {
        uint32_t b[4][4];
        float d[4][4];
        uint8_t* dst[2];
        const uint32_t da = pin(uP2 + (R_DST - R_P) + L16 / 2);
        sched();
        TS(7);
        bar_sync(6, 256);
#pragma unroll
        for (int i = 0; i < 4; i++) { ldsm4(b[i], sb + R_O + i * 512 + L16); __syncwarp(); }
        sched();
        auto put_b = [&](uint8_t* a, const float (&e)[4][4]) {
          stx128(a, (pack2(e[0][0] + e[2][0], e[0][1] + e[2][1]) & ~1u) | tag, pack2(e[0][2] + e[2][2], e[0][3] + e[2][3]),
                 pack2(e[1][0] + e[3][0], e[1][1] + e[3][1]), pack2(e[1][2] + e[3][2], e[1][3] + e[3][3]));
        };
        zero(c); zero(d);
#pragma unroll
        for (int i = 0; i < 32; i++) {
          mma_h(i < 16 ? c[i & 3] : d[i & 3], wo[i], b[(i >> 2) & 3], (i >> 1) & 1);
          if (i >= LW0 && NB1 + i - LW0 < 32) { load_wo(wo, (NB1 + i - LW0) ^ 1, ((NB1 + i - LW0) ^ 1) + 1); __syncwarp(); }
          if (i == DL0 || i == DL1) asm volatile("ld.shared.u64 %0, [%1];" : "=l"(dst[i > DL0]) : "r"(da + (i > DL0) * 1024) : "memory");
          if (i >= 16 && i < 16 + RE0) { lds128(w[i - 16], uW + R_WC + L16 + (i - 16) * 2048); __syncwarp(); }
          if (i >= RP1 && i < RP1 + RE1) { lds128(w[i - RP1 + RE0], uW + R_WC + L16 + (i - RP1 + RE0) * 2048); __syncwarp(); }
          if (i == 22) put_b(dst[0], c);
          if ((i & 1) && (i < 20 || i > 22)) sched();
        }
        put_b(dst[1], d);
        sched();
        TS(6);
      };
      if (warp < 6) {
        delay_until(tpub + DLY_A);
        const int it0 = it;
        bool redo;
#pragma unroll 1
        do {
          uint32_t q[4][4], y[4];
          float d[4][4];
          wait_time(due);
          TS(4);
          ldx(q, asrc);
          sched();
          load_k();
          uint32_t qx[4][4];
#pragma unroll
          for (int i = 0; i < 4; i++) load_q(qx[i], i * 512);
          sched();
          load_wo(wo, 0, NE4);
          sched();
          zero(c);
#pragma unroll
          for (int i = 0; i < 8; i++) mma_h(c[i & 3], kf[i], qx[i >> 1], i & 1);
          put_p(1, 0, 0); put_s(1);
          sched();
          load_wo(wo, NE4, NA4);
          sched();
          zero(c); zero(d);
#pragma unroll
          for (int i = 0; i < 8; i++) {
            if (i == 0) { y[0] = dif2v(q[0][0], q[0][2], q[1][0]); sched(); }
            if (i == 3) { y[1] = dif2v(q[1][2], q[2][0], q[2][2]); sched(); }
            if (i == 6) { y[2] = dif2v(q[3][0], q[3][2], tag); sched(); }
            mma_h(i % 6 < 2 ? c[2 + i % 6] : d[i - 2], kf[i], q[i >> 1], i & 1);
            if (i == 2 || i == 5 || i == 7) sched();
          }
          y[0] = or_and(or3(y[0], y[1], dif2v(q[0][0], q[2][0], tag)), y[2], it < SPIN_LIMIT);
#pragma unroll
          for (int i = 0; i < 4; i++) { c[0][i] = d[0][i] + d[1][i]; c[1][i] = d[2][i] + d[3][i]; }
          put_p(0, y[0], it - it0);
          TS(5);
          bar_sync_unless(5, it - it0);
          redo = __any_sync(0xffffffffu, y[0]);
          it += INC_A;
        } while (redo);
        it -= INC_A;
        put_s(0);
        bar_arrive(8, 256);
        load_wo(wo, NA4, NB1);
        out_proj();
        if (warp == 4) LOG(12, tb);
      } else {
        uint32_t qx[2][4], q[4][4];
        if (warp == 6) {
          const uint32_t t1 = (now & ~31u) + NS_M;
          LOG(10, now - due);
          if (elect()) stx32(&gx->T[h][j], ((int)(t1 - due) > 0 ? t1 + NS_PEN : due) | ((s + 1) & 31));
          __syncwarp();
        }
        auto score = [&](const uint32_t (&a0)[4], const uint32_t (&a1)[4]) {
          zero(c);
#pragma unroll
          for (int i = 0; i < 4; i++) mma_h(c[i], i < 2 ? a0 : a1, q[2 + (i >> 1)], i & 1);
        };
        auto put_m = [&](uint32_t a, uint32_t old, uint32_t again) {
#pragma unroll
          for (int i = 0; i < 2; i++) { r4[i] = fmaf(c[3][2 + i], sc, fmaf((c[0][i] + c[1][2 + i]) + c[2][i], sc, __uint_as_float(i ? 0u - old : 0u))); r4[2 + i] = fmaf(r4[i] * 0x1p122f, 0.f, ex2(r4[i])); }
          asm volatile("{.reg .pred p; setp.eq.u32 p, %3, 0; @p st.shared.v2.f32 [%0], {%1,%2};}" :: "r"(a), "f"(r4[2]), "f"(r4[3]), "r"(again) : "memory");
        };
        delay_until(tpub + DLY_A);
        const uint32_t sa = sb + R_S + 512 + w4 * 256 + (L16 >> 1);
        const int it0 = it;
        bool redo;
#pragma unroll 1
        do {
          wait_time(due);
          TS(4);
          ldx<4, 2048>(q, asrc);
          sched();
          load_q(qx[0], (w4 & 1) * 1024); load_q(qx[1], (w4 & 1) * 1024 + 512);
          load_wo(wo, 0, NA6);
          sched();
          score(q[0], q[1]);
          sched();
          const uint32_t y = or_and(or3(dif2v(q[0][0], q[0][2], tag), dif2v(q[1][0], q[1][2], tag), dif2v(q[2][0], q[2][2], tag)), dif2v(q[3][0], q[3][2], tag), it < SPIN_LIMIT);
          put_m(sa + 2560, y, it - it0);
          TS(5);
          bar_arrive_unless(5, it - it0);
          redo = __any_sync(0xffffffffu, y);
          it += INC_A;
        } while (redo);
        it -= INC_A;
        sts64f(sa, r4[0], r4[1]);
        score(qx[0], qx[1]);
        put_m(sa + 3584, 0, 0);
        sts64f(sa + 1536, r4[0], r4[1]);
        bar_arrive(8, 256);
        load_wo(wo, NA6, NB1);
        out_proj();
      }
      TS(8);
      if (s + 1 == NSEG) break;
      wait_x(s + 2, 2);
      TS(9);
      fresh();
      if (N1) project_qk(IC<32>{}, IC<32 + N1>{}, IC<1>{}, [](int) {});
      TS(10);
      xpos(6, 6);
      uint32_t fl = s + 1;
      if (warp == 5) { wait_time(due + NS_F); fl = ldx32(xa + 4096 + ((L16 >> 2) & 60)); }
      reload();
      TS(14);
      pin_mem();
      wait_x(s + 2, 1); wait_x(s + 2, 0);
      if (warp == 5) {
#pragma unroll 1
        while (__any_sync(0xffffffffu, fl != s + 1) && !(EXP & 4) && ++it < SPIN_LIMIT) fl = ldx32(xa + 4096 + ((L16 >> 2) & 60));
        wait_time(due + (NS_B + NS_K));
        if (!(EXP & 2) && elect()) issue_kqv(s + 1);
        __syncwarp();
      }
      if (PFD && warp == 6 && s + PFD < NSEG && elect())
        asm volatile("cp.async.bulk.prefetch.L2.global [%0], 2048;" :: "l"(xin + ((s + PFD) * SEG + ((role + 4 * (role >> 5)) & 31)) * DM) : "memory");
      __syncwarp();
      TS(11);
      LOG(warp, it);
      if (warp == 4) LOG(8, nc);
      bar_sync(0, 256);
      if (N1 < 16) project_qk(IC<32 + N1>{}, IC<48>{}, IC<!N1>{}, [](int) {});
      project_qk(IC<16>{}, IC<32>{}, IC<0>{}, [&](int n) { if ((n & 15) == XWPOS) { __syncwarp(); xok = mbar_test(sb + B_PK, s & 1); __syncwarp(); } });
      if (rare(!xok)) mbar_spin(sb + B_PK, s & 1, it);
      unpark();
      project_qk(IC<0>{}, IC<16>{}, IC<0>{}, [](int) {});
      TS(12);
      wg_wait<0>(); keep(aq);
      TS(1);
      fin_qk();
      TS(15);
    }
    s++;
  }
  if (it >= SPIN_LIMIT || nc >= NC_MAX) g_err = 2;
}

typedef CUresult (*EncodeFn)(CUtensorMap*, CUtensorMapDataType, cuuint32_t, void*, const cuuint64_t*, const cuuint64_t*, const cuuint32_t*,
                             const cuuint32_t*, CUtensorMapInterleave, CUtensorMapSwizzle, CUtensorMapL2promotion, CUtensorMapFloatOOBfill);
static void make_map(EncodeFn fn, CUtensorMap* m, const void* p, uint64_t cols, uint64_t rows, uint64_t pitch, uint32_t bc, uint32_t br, CUtensorMapSwizzle sw) {
  cuuint64_t dims[2] = {cols, rows}, strides[1] = {pitch * 2};
  cuuint32_t box[2] = {bc, br}, es[2] = {1, 1};
  fn(m, CU_TENSOR_MAP_DATA_TYPE_BFLOAT16, 2, const_cast<void*>(p), dims, strides, box, es, CU_TENSOR_MAP_INTERLEAVE_NONE, sw,
     CU_TENSOR_MAP_L2_PROMOTION_L2_256B, CU_TENSOR_MAP_FLOAT_OOB_FILL_NONE);
}

extern "C" void kernel_launch(void* const* d_in, const int* in_sizes, int n_in, void* d_out, int out_size) {
  const bf16* Ax = (const bf16*)d_in[0]; const bf16* mem0 = (const bf16*)d_in[1];
  const bf16* Wq = (const bf16*)d_in[2]; const bf16* Wk = (const bf16*)d_in[3]; const bf16* Wv = (const bf16*)d_in[4];
  const bf16* Wo = (const bf16*)d_in[5];
  const bf16* Bx = (const bf16*)d_in[7]; const bf16* wr = (const bf16*)d_in[8]; const bf16* wi = (const bf16*)d_in[9];
  bf16* out = (bf16*)d_out;

  void* fp = nullptr; cudaDriverEntryPointQueryResult qr;
  cudaGetDriverEntryPoint("cuTensorMapEncodeTiled", &fp, cudaEnableDefault, &qr);
  EncodeFn fn = (EncodeFn)fp;
  void *kqv, *ox, *xr;
  cudaGetSymbolAddress(&xr, g_xraw);
  cudaGetSymbolAddress(&kqv, g_kqv); cudaGetSymbolAddress(&ox, g_ox);
  const CUtensorMapSwizzle S128 = CU_TENSOR_MAP_SWIZZLE_128B, S64 = CU_TENSOR_MAP_SWIZZLE_64B;

  GemmMaps m3; RecMaps mr;
  make_map(fn, &m3.a, ox, HD, S_LEN, HD, 64, 128, S128);
  make_map(fn, &m3.b[0], Wo, DM, HD, DM, 64, 64, S128);
  m3.b[1] = m3.b[0]; m3.b[2] = m3.b[0];
  make_map(fn, &m3.c, out, DM, S_LEN, 2 * DM, 64, 64, S128);
  make_map(fn, &mr.wq, Wq, HD, DM, HD, 32, 256, S64);
  make_map(fn, &mr.wk, Wk, HD, DM, HD, 32, 256, S64);
  make_map(fn, &mr.wv, Wv, HD, DM, HD, 64, 256, S128);
  make_map(fn, &mr.wo, Wo, DM, HD, DM, 64, 128, S128);
  {
    cuuint64_t dims[3] = {64, S_LEN, 16}, strides[2] = {DM * 2, 128};
    cuuint32_t box[3] = {64, 32, 4}, es[3] = {1, 1, 1};
    fn(&mr.x, CU_TENSOR_MAP_DATA_TYPE_BFLOAT16, 3, const_cast<bf16*>(Ax), dims, strides, box, es, CU_TENSOR_MAP_INTERLEAVE_NONE, S128,
       CU_TENSOR_MAP_L2_PROMOTION_L2_256B, CU_TENSOR_MAP_FLOAT_OOB_FILL_NONE);
  }
  for (int i = 0; i < 3; i++) {
    cuuint64_t dims[3] = {128, 32, 512}, strides[2] = {256, 8192};
    cuuint32_t box[3] = {128, i == 0 ? 8u : i == 1 ? 2u : 16u, 4}, es[3] = {1, 1, 1};
    fn(i == 0 ? &mr.k : i == 1 ? &mr.q : &mr.v, CU_TENSOR_MAP_DATA_TYPE_BFLOAT16, 3, kqv, dims, strides, box, es, CU_TENSOR_MAP_INTERLEAVE_NONE,
       CU_TENSOR_MAP_SWIZZLE_NONE, CU_TENSOR_MAP_L2_PROMOTION_L2_256B, CU_TENSOR_MAP_FLOAT_OOB_FILL_NONE);
  }
  {
    cuuint64_t dims[3] = {64, 16, S_LEN}, strides[2] = {128, 2 * DM * 2};
    cuuint32_t box[3] = {64, 16, 2}, es[3] = {1, 1, 1};
    fn(&mr.fo, CU_TENSOR_MAP_DATA_TYPE_BFLOAT16, 3, out + DM, dims, strides, box, es, CU_TENSOR_MAP_INTERLEAVE_NONE, S128,
       CU_TENSOR_MAP_L2_PROMOTION_NONE, CU_TENSOR_MAP_FLOAT_OOB_FILL_NONE);
  }
  constexpr int SM3 = 6 * 32768 + 32768 + 256 + 1024;
  cudaFuncSetAttribute(gemm_kernel<128, 6>, cudaFuncAttributeMaxDynamicSharedMemorySize, SM3);
  cudaFuncSetAttribute(rec_kernel, cudaFuncAttributeMaxDynamicSharedMemorySize, R_TOTAL);

  cudaStream_t st = cudaStreamPerThread;
  Xchg* gx = reinterpret_cast<Xchg*>((reinterpret_cast<uintptr_t>(xr) + 0x1FFFFF) & ~(uintptr_t)0x1FFFFF);
  rec_kernel<<<132, 256, R_TOTAL, st>>>(mr, Ax, mem0, gx, Bx, wr, wi);
  gemm_kernel<128, 6><<<128, 384, SM3, st>>>(m3, 16, 8, 64, 8, reinterpret_cast<uint4*>(gx));
}
```

```cpp
#include <cuda_runtime.h>
#include <cuda_bf16.h>
#include <cuda.h>
#include <stdint.h>
#include <stddef.h>
#include <type_traits>

typedef __nv_bfloat16 bf16;

constexpr int S_LEN = 2048, DM = 1024, NH = 32, DH = 128, MEM = 8, SEG = 32, NSEG = 64;
constexpr int HD = NH * DH;
#define SPIN 20
constexpr int SPIN_LIMIT = 1 << SPIN, INC_A = 1, INC_B = 1;

constexpr unsigned NC_MAX = 4096;
__device__ __align__(1024) uint4 g_kqv[4][128][512];
__device__ __align__(1024) bf16 g_ox[(size_t)S_LEN * HD];
struct Xchg {
  uint4 A[32][4][256];
  uint4 C[4][2][256];
  uint4 B[128][2][256];
  uint32_t T[32][32];
  uint32_t S[128];
  unsigned ctr[64];
};
__device__ __align__(1024) uint4 g_xraw[(sizeof(Xchg) + (1 << 21)) / 16];
__device__ __align__(1024) uint4 g_y[1024 * 256];
__device__ __align__(1024) uint4 g_wt[513 * 512];
__device__ int g_err;

__device__ __forceinline__ unsigned clk() { unsigned long long c; asm volatile("mov.u64 %0, %%clock64;" : "=l"(c)); return (unsigned)c; }
__device__ __forceinline__ uint32_t smem_u32(const void* p) { return (uint32_t)__cvta_generic_to_shared(p); }
__device__ __forceinline__ void mbar_init(uint32_t bar, int cnt) { asm volatile("mbarrier.init.shared::cta.b64 [%0], %1;" :: "r"(bar), "r"(cnt) : "memory"); }
__device__ __forceinline__ void mbar_expect_tx(uint32_t bar, int bytes) { asm volatile("mbarrier.arrive.expect_tx.shared::cta.b64 _, [%0], %1;" :: "r"(bar), "r"(bytes) : "memory"); }
__device__ __forceinline__ void mbar_arrive(uint32_t bar) { asm volatile("mbarrier.arrive.shared::cta.b64 _, [%0];" :: "r"(bar) : "memory"); }
__device__ __forceinline__ void mbar_arrive_cluster(uint32_t bar, int cta) {
  asm volatile("{.reg .b32 r; mapa.shared::cluster.u32 r, %0, %1; mbarrier.arrive.shared::cluster.b64 _, [r];}" :: "r"(bar), "r"(cta) : "memory"); }
__device__ __forceinline__ bool mbar_try(uint32_t bar, int par) {
  uint32_t ok; asm volatile("{.reg .pred p; mbarrier.try_wait.parity.shared::cta.b64 p, [%1], %2; selp.u32 %0, 1, 0, p;}" : "=r"(ok) : "r"(bar), "r"(par) : "memory"); return ok; }
__device__ __forceinline__ bool mbar_test(uint32_t bar, int par) {
  uint32_t ok; asm volatile("{.reg .pred p; mbarrier.test_wait.parity.shared::cta.b64 p, [%1], %2; selp.u32 %0, 1, 0, p;}" : "=r"(ok) : "r"(bar), "r"(par) : "memory"); return ok; }
__device__ __forceinline__ void mbar_wait(uint32_t bar, int par) {
  int it = 0;
  while (!mbar_try(bar, par)) { if (++it > SPIN_LIMIT) { g_err = 1; break; } }
}
__device__ __forceinline__ void tma2d(uint32_t dst, const CUtensorMap* m, int c0, int c1, uint32_t bar) {
  asm volatile("cp.async.bulk.tensor.2d.shared::cluster.global.mbarrier::complete_tx::bytes [%0], [%1, {%3, %4}], [%2];"
    :: "r"(dst), "l"(m), "r"(bar), "r"(c0), "r"(c1) : "memory"); }
__device__ __forceinline__ void tma2d_mc(uint32_t dst, const CUtensorMap* m, int c0, int c1, uint32_t bar, uint16_t mask) {
  asm volatile("cp.async.bulk.tensor.2d.shared::cluster.global.mbarrier::complete_tx::bytes.multicast::cluster [%0], [%1, {%3, %4}], [%2], %5;"
    :: "r"(dst), "l"(m), "r"(bar), "r"(c0), "r"(c1), "h"(mask) : "memory"); }
__device__ __forceinline__ void tma2d_store(const CUtensorMap* m, uint32_t src, int c0, int c1) {
  asm volatile("cp.async.bulk.tensor.2d.global.shared::cta.bulk_group [%0, {%2, %3}], [%1];" :: "l"(m), "r"(src), "r"(c0), "r"(c1) : "memory"); }
__device__ __forceinline__ void fence_async() { asm volatile("fence.proxy.async.shared::cta;" ::: "memory"); }
__device__ __forceinline__ void bar_sync(int id, int n) { asm volatile("bar.sync %0, %1;" :: "r"(id), "r"(n) : "memory"); }
__device__ __forceinline__ void bar_arrive(int id, int n) { asm volatile("bar.arrive %0, %1;" :: "r"(id), "r"(n) : "memory"); }
__device__ __forceinline__ uint32_t pack2(float lo, float hi) { uint32_t r; asm("cvt.rn.bf16x2.f32 %0, %1, %2;" : "=r"(r) : "f"(hi), "f"(lo)); return r; }
__device__ __forceinline__ uint32_t pack2_tag(float lo, float hi, uint32_t T) {
  uint32_t u = ((__float_as_uint(lo) - T + 0x10000u) & 0xFFFE0000u) + T;
  return __byte_perm(u, pack2(0.f, hi), 0x7632); }
__device__ __forceinline__ void ldsm4(uint32_t (&r)[4], uint32_t a) {
  asm volatile("ldmatrix.sync.aligned.m8n8.x4.shared.b16 {%0,%1,%2,%3}, [%4];" : "=r"(r[0]), "=r"(r[1]), "=r"(r[2]), "=r"(r[3]) : "r"(a) : "memory"); }
__device__ __forceinline__ void ldsm4t(uint32_t (&r)[4], uint32_t a) {
  asm volatile("ldmatrix.sync.aligned.m8n8.x4.trans.shared.b16 {%0,%1,%2,%3}, [%4];" : "=r"(r[0]), "=r"(r[1]), "=r"(r[2]), "=r"(r[3]) : "r"(a) : "memory"); }
__device__ __forceinline__ void stsm4(uint32_t a, uint32_t r0, uint32_t r1, uint32_t r2, uint32_t r3) {
  asm volatile("stmatrix.sync.aligned.m8n8.x4.shared.b16 [%0], {%1,%2,%3,%4};" :: "r"(a), "r"(r0), "r"(r1), "r"(r2), "r"(r3) : "memory"); }
__device__ __forceinline__ void stsm4t(uint32_t a, uint32_t r0, uint32_t r1, uint32_t r2, uint32_t r3) {
  asm volatile("stmatrix.sync.aligned.m8n8.x4.trans.shared.b16 [%0], {%1,%2,%3,%4};" :: "r"(a), "r"(r0), "r"(r1), "r"(r2), "r"(r3) : "memory"); }
__device__ __forceinline__ void lds128(uint32_t (&r)[4], uint32_t a) {
  asm volatile("ld.shared.v4.u32 {%0,%1,%2,%3}, [%4];" : "=r"(r[0]), "=r"(r[1]), "=r"(r[2]), "=r"(r[3]) : "r"(a) : "memory"); }
__device__ __forceinline__ float4 lds128f(uint32_t a) { float4 r;
  asm volatile("ld.shared.v4.f32 {%0,%1,%2,%3}, [%4];" : "=f"(r.x), "=f"(r.y), "=f"(r.z), "=f"(r.w) : "r"(a) : "memory"); return r; }
__device__ __forceinline__ float2 lds64f(uint32_t a) { float2 r;
  asm volatile("ld.shared.v2.f32 {%0,%1}, [%2];" : "=f"(r.x), "=f"(r.y) : "r"(a) : "memory"); return r; }
__device__ __forceinline__ void sts128(uint32_t a, uint32_t r0, uint32_t r1, uint32_t r2, uint32_t r3) {
  asm volatile("st.shared.v4.u32 [%0], {%1,%2,%3,%4};" :: "r"(a), "r"(r0), "r"(r1), "r"(r2), "r"(r3) : "memory"); }
__device__ __forceinline__ void sts64f(uint32_t a, float x, float y) { asm volatile("st.shared.v2.f32 [%0], {%1,%2};" :: "r"(a), "f"(x), "f"(y) : "memory"); }
__device__ __forceinline__ void sts32f(uint32_t a, float x) { asm volatile("st.shared.f32 [%0], %1;" :: "r"(a), "f"(x) : "memory"); }
__device__ __forceinline__ void mma16816(float (&d)[4], uint32_t a0, uint32_t a1, uint32_t a2, uint32_t a3, uint32_t b0, uint32_t b1) {
  asm volatile("mma.sync.aligned.m16n8k16.row.col.f32.bf16.bf16.f32 {%0,%1,%2,%3}, {%4,%5,%6,%7}, {%8,%9}, {%0,%1,%2,%3};"
    : "+f"(d[0]), "+f"(d[1]), "+f"(d[2]), "+f"(d[3]) : "r"(a0), "r"(a1), "r"(a2), "r"(a3), "r"(b0), "r"(b1)); }
__device__ __forceinline__ void mma1688(float (&d)[4], uint32_t a0, uint32_t a1, uint32_t b0) {
  asm volatile("mma.sync.aligned.m16n8k8.row.col.f32.bf16.bf16.f32 {%0,%1,%2,%3}, {%4,%5}, {%6}, {%0,%1,%2,%3};"
    : "+f"(d[0]), "+f"(d[1]), "+f"(d[2]), "+f"(d[3]) : "r"(a0), "r"(a1), "r"(b0)); }
__device__ __forceinline__ void ldx128(uint32_t (&r)[4], const void* p) {
  asm volatile("{.reg .b128 t; .reg .b64 a, b; ld.relaxed.gpu.global.b128 t, [%4]; mov.b128 {a, b}, t; mov.b64 {%0,%1}, a; mov.b64 {%2,%3}, b;}"
    : "=r"(r[0]), "=r"(r[1]), "=r"(r[2]), "=r"(r[3]) : "l"(p) : "memory"); }
__device__ __forceinline__ void ldx2x64(uint32_t (&r)[4], const void* p) {
  asm volatile("{.reg .b64 a, b; ld.relaxed.gpu.global.v2.b64 {a, b}, [%4]; mov.b64 {%0,%1}, a; mov.b64 {%2,%3}, b;}"
    : "=r"(r[0]), "=r"(r[1]), "=r"(r[2]), "=r"(r[3]) : "l"(p) : "memory"); }
__device__ __forceinline__ void stx128(void* p, uint32_t r0, uint32_t r1, uint32_t r2, uint32_t r3) {
  asm volatile("{.reg .b128 t; .reg .b64 a, b; mov.b64 a, {%1,%2}; mov.b64 b, {%3,%4}; mov.b128 t, {a, b}; st.relaxed.gpu.global.b128 [%0], t;}"
    :: "l"(p), "r"(r0), "r"(r1), "r"(r2), "r"(r3) : "memory"); }
__device__ __forceinline__ void stx64(void* p, uint32_t r0, uint32_t r1) {
  asm volatile("{.reg .b64 a; mov.b64 a, {%1,%2}; st.relaxed.gpu.global.b64 [%0], a;}" :: "l"(p), "r"(r0), "r"(r1) : "memory"); }
__device__ __forceinline__ uint32_t uni(uint32_t x) { return __shfl_sync(0xffffffffu, x, 0); }
__device__ __forceinline__ uint32_t pin(uint32_t x) { return __shfl_xor_sync(0xffffffffu, x, 0); }
__device__ __forceinline__ float ex2(float x) { float r; asm("ex2.approx.ftz.f32 %0, %1;" : "=f"(r) : "f"(x)); return r; }
__device__ __forceinline__ void wg_fence() { asm volatile("wgmma.fence.sync.aligned;" ::: "memory"); }
__device__ __forceinline__ void wg_commit() { asm volatile("wgmma.commit_group.sync.aligned;" ::: "memory"); }
template <int N> __device__ __forceinline__ void wg_wait() { asm volatile("wgmma.wait_group.sync.aligned %0;" :: "n"(N) : "memory"); }

__device__ __forceinline__ void wgmma_ss_n256_tb1(float (&d)[128], uint64_t da, uint64_t db, int sc) {
  asm volatile("{.reg .pred p; setp.ne.b32 p, %130, 0;\n"
    "wgmma.mma_async.sync.aligned.m64n256k16.f32.bf16.bf16 {%0,%1,%2,%3,%4,%5,%6,%7,%8,%9,%10,%11,%12,%13,%14,%15,%16,%17,%18,%19,%20,%21,%22,%23,%24,%25,%26,%27,%28,%29,%30,%31,%32,%33,%34,%35,%36,%37,%38,%39,%40,%41,%42,%43,%44,%45,%46,%47,%48,%49,%50,%51,%52,%53,%54,%55,%56,%57,%58,%59,%60,%61,%62,%63,%64,%65,%66,%67,%68,%69,%70,%71,%72,%73,%74,%75,%76,%77,%78,%79,%80,%81,%82,%83,%84,%85,%86,%87,%88,%89,%90,%91,%92,%93,%94,%95,%96,%97,%98,%99,%100,%101,%102,%103,%104,%105,%106,%107,%108,%109,%110,%111,%112,%113,%114,%115,%116,%117,%118,%119,%120,%121,%122,%123,%124,%125,%126,%127}, %128, %129, p, 1, 1, 0, 1;}\n"
    : "+f"(d[0]),"+f"(d[1]),"+f"(d[2]),"+f"(d[3]),"+f"(d[4]),"+f"(d[5]),"+f"(d[6]),"+f"(d[7]),"+f"(d[8]),"+f"(d[9]),"+f"(d[10]),"+f"(d[11]),"+f"(d[12]),"+f"(d[13]),"+f"(d[14]),"+f"(d[15]),"+f"(d[16]),"+f"(d[17]),"+f"(d[18]),"+f"(d[19]),"+f"(d[20]),"+f"(d[21]),"+f"(d[22]),"+f"(d[23]),"+f"(d[24]),"+f"(d[25]),"+f"(d[26]),"+f"(d[27]),"+f"(d[28]),"+f"(d[29]),"+f"(d[30]),"+f"(d[31]),"+f"(d[32]),"+f"(d[33]),"+f"(d[34]),"+f"(d[35]),"+f"(d[36]),"+f"(d[37]),"+f"(d[38]),"+f"(d[39]),"+f"(d[40]),"+f"(d[41]),"+f"(d[42]),"+f"(d[43]),"+f"(d[44]),"+f"(d[45]),"+f"(d[46]),"+f"(d[47]),"+f"(d[48]),"+f"(d[49]),"+f"(d[50]),"+f"(d[51]),"+f"(d[52]),"+f"(d[53]),"+f"(d[54]),"+f"(d[55]),"+f"(d[56]),"+f"(d[57]),"+f"(d[58]),"+f"(d[59]),"+f"(d[60]),"+f"(d[61]),"+f"(d[62]),"+f"(d[63]),"+f"(d[64]),"+f"(d[65]),"+f"(d[66]),"+f"(d[67]),"+f"(d[68]),"+f"(d[69]),"+f"(d[70]),"+f"(d[71]),"+f"(d[72]),"+f"(d[73]),"+f"(d[74]),"+f"(d[75]),"+f"(d[76]),"+f"(d[77]),"+f"(d[78]),"+f"(d[79]),"+f"(d[80]),"+f"(d[81]),"+f"(d[82]),"+f"(d[83]),"+f"(d[84]),"+f"(d[85]),"+f"(d[86]),"+f"(d[87]),"+f"(d[88]),"+f"(d[89]),"+f"(d[90]),"+f"(d[91]),"+f"(d[92]),"+f"(d[93]),"+f"(d[94]),"+f"(d[95]),"+f"(d[96]),"+f"(d[97]),"+f"(d[98]),"+f"(d[99]),"+f"(d[100]),"+f"(d[101]),"+f"(d[102]),"+f"(d[103]),"+f"(d[104]),"+f"(d[105]),"+f"(d[106]),"+f"(d[107]),"+f"(d[108]),"+f"(d[109]),"+f"(d[110]),"+f"(d[111]),"+f"(d[112]),"+f"(d[113]),"+f"(d[114]),"+f"(d[115]),"+f"(d[116]),"+f"(d[117]),"+f"(d[118]),"+f"(d[119]),"+f"(d[120]),"+f"(d[121]),"+f"(d[122]),"+f"(d[123]),"+f"(d[124]),"+f"(d[125]),"+f"(d[126]),"+f"(d[127])
    : "l"(da), "l"(db), "r"(sc));
}

__device__ __forceinline__ void wgmma_ss_n128_tb1(float (&d)[64], uint64_t da, uint64_t db, int sc) {
  asm volatile("{.reg .pred p; setp.ne.b32 p, %66, 0;\n"
    "wgmma.mma_async.sync.aligned.m64n128k16.f32.bf16.bf16 {%0,%1,%2,%3,%4,%5,%6,%7,%8,%9,%10,%11,%12,%13,%14,%15,%16,%17,%18,%19,%20,%21,%22,%23,%24,%25,%26,%27,%28,%29,%30,%31,%32,%33,%34,%35,%36,%37,%38,%39,%40,%41,%42,%43,%44,%45,%46,%47,%48,%49,%50,%51,%52,%53,%54,%55,%56,%57,%58,%59,%60,%61,%62,%63}, %64, %65, p, 1, 1, 0, 1;}\n"
    : "+f"(d[0]),"+f"(d[1]),"+f"(d[2]),"+f"(d[3]),"+f"(d[4]),"+f"(d[5]),"+f"(d[6]),"+f"(d[7]),"+f"(d[8]),"+f"(d[9]),"+f"(d[10]),"+f"(d[11]),"+f"(d[12]),"+f"(d[13]),"+f"(d[14]),"+f"(d[15]),"+f"(d[16]),"+f"(d[17]),"+f"(d[18]),"+f"(d[19]),"+f"(d[20]),"+f"(d[21]),"+f"(d[22]),"+f"(d[23]),"+f"(d[24]),"+f"(d[25]),"+f"(d[26]),"+f"(d[27]),"+f"(d[28]),"+f"(d[29]),"+f"(d[30]),"+f"(d[31]),"+f"(d[32]),"+f"(d[33]),"+f"(d[34]),"+f"(d[35]),"+f"(d[36]),"+f"(d[37]),"+f"(d[38]),"+f"(d[39]),"+f"(d[40]),"+f"(d[41]),"+f"(d[42]),"+f"(d[43]),"+f"(d[44]),"+f"(d[45]),"+f"(d[46]),"+f"(d[47]),"+f"(d[48]),"+f"(d[49]),"+f"(d[50]),"+f"(d[51]),"+f"(d[52]),"+f"(d[53]),"+f"(d[54]),"+f"(d[55]),"+f"(d[56]),"+f"(d[57]),"+f"(d[58]),"+f"(d[59]),"+f"(d[60]),"+f"(d[61]),"+f"(d[62]),"+f"(d[63])
    : "l"(da), "l"(db), "r"(sc));
}

template <int BN> struct WG;
template <> struct WG<256> { static __device__ __forceinline__ void mma(float (&d)[128], uint64_t a, uint64_t b, int sc) { wgmma_ss_n256_tb1(d, a, b, sc); } };
template <> struct WG<128> { static __device__ __forceinline__ void mma(float (&d)[64], uint64_t a, uint64_t b, int sc) { wgmma_ss_n128_tb1(d, a, b, sc); } };

struct GemmMaps { CUtensorMap a, b[3], c; };
template <int BN, int STAGES>
__global__ void __cluster_dims__(2, 1, 1) __launch_bounds__(384, 1)
gemm_kernel(const __grid_constant__ GemmMaps maps, int tilesM, int tilesN, int kblocks, int nPerB, uint4* __restrict__ clearX) {
  extern __shared__ __align__(1024) uint8_t smem_raw[];
  constexpr int STAGE_BYTES = 16384 + BN * 128;
  constexpr int NBOX = BN / 64;
  const uint32_t sbase = (smem_u32(smem_raw) + 1023) & ~1023u;
  const uint32_t sEpi = sbase + STAGES * STAGE_BYTES;
  const uint32_t sBar = sEpi + 32768;
  const int warp = threadIdx.x >> 5, lane = threadIdx.x & 31, wg = warp >> 2;
  uint32_t crank; asm("mov.u32 %0, %%cluster_ctarank;" : "=r"(crank));
#define GT(k)
  const int npairs = (tilesM >> 1) * tilesN, pair0 = blockIdx.x >> 1, pstep = gridDim.x >> 1;
  if (threadIdx.x == 256) {
    asm volatile("prefetch.tensormap [%0];" :: "l"(&maps.b[0]) : "memory");
    for (int i = 0; i < STAGES; i++) { mbar_init(sBar + 8 * i, 1); mbar_init(sBar + 8 * (STAGES + i), 4); }
    asm volatile("fence.mbarrier_init.release.cluster;" ::: "memory");
    asm volatile("barrier.cluster.arrive.relaxed;" ::: "memory");
    for (int i = 0; i < STAGES; i++) {
      mbar_expect_tx(sBar + 8 * i, STAGE_BYTES);
      tma2d(sbase + i * STAGE_BYTES, &maps.a, i * 64, ((pair0 % (tilesM >> 1)) * 2 + crank) * 128, sBar + 8 * i);
    }
    asm volatile("prefetch.tensormap [%0];" :: "l"(&maps.c) : "memory");
  } else asm volatile("barrier.cluster.arrive.relaxed;" ::: "memory");
  asm volatile("barrier.cluster.wait.acquire;" ::: "memory");
  __syncwarp();
  if (wg == 2) {
    asm volatile("setmaxnreg.dec.sync.aligned.u32 40;");
    if (warp > 8) {
      __nanosleep(4000);
      for (int i = blockIdx.x * 96 + threadIdx.x - 288; i < (int)(sizeof(Xchg) / 16); i += gridDim.x * 96) clearX[i] = make_uint4(0, 0, 0, 0);
    }
    if (warp == 8 && lane == 0) {
      int st = 0, ph = 1;
      for (int p = pair0; p < npairs; p += pstep) {
        const int tm = (p % (tilesM >> 1)) * 2 + crank, tn = p / (tilesM >> 1);
        const CUtensorMap* mb = &maps.b[tn / nPerB];
        const int n0 = (tn % nPerB) * BN;
        for (int kb = 0; kb < kblocks; kb++) {
          const uint32_t a = sbase + st * STAGE_BYTES, full = sBar + 8 * st;
          if (p > pair0 || kb >= STAGES) {
            mbar_wait(sBar + 8 * (STAGES + st), ph);
            mbar_expect_tx(full, STAGE_BYTES);
            tma2d(a, &maps.a, kb * 64, tm * 128, full);
          }
#pragma unroll
          for (int i = 0; i < NBOX / 2; i++) {
            const int bx = crank * (NBOX / 2) + i;
            tma2d_mc(a + 16384 + bx * 8192, mb, n0 + bx * 64, kb * 64, full, (uint16_t)3);
          }
          if (++st == STAGES) { st = 0; ph ^= 1; }
        }
      }
      for (int i = 0; i < STAGES; i++) { mbar_wait(sBar + 8 * (STAGES + st), ph); if (++st == STAGES) { st = 0; ph ^= 1; } }
    }
  } else {
    asm volatile("setmaxnreg.inc.sync.aligned.u32 232;");
    int st = 0, ph = 0;
    float acc[BN / 2];
    const uint64_t descA0 = (uint64_t)(((sbase + wg * 8192) & 0x3FFFF) >> 4) | (1ull << 16) | (64ull << 32) | (1ull << 62);
    const uint64_t descB0 = (uint64_t)(((sbase + 16384) & 0x3FFFF) >> 4) | (512ull << 16) | (64ull << 32) | (1ull << 62);
    const uint32_t epi = sEpi + wg * 16384;
    for (int p = pair0; p < npairs; p += pstep) {
      const int tm = (p % (tilesM >> 1)) * 2 + crank, tn = p / (tilesM >> 1);
      int prev = -1;
      for (int kb = 0; kb < kblocks; kb++) {
        mbar_wait(sBar + 8 * st, ph);
        if ((kb & 15) == 0) { GT(kb >> 4); }
        wg_fence();
        const uint64_t so = (uint64_t)(st * (STAGE_BYTES >> 4));
#pragma unroll
        for (int k = 0; k < 4; k++) WG<BN>::mma(acc, descA0 + so + k * 2, descB0 + so + k * 128, kb | k);
        wg_commit();
        if (prev >= 0) {
          wg_wait<1>();
          if ((threadIdx.x & 127) < 2) mbar_arrive_cluster(sBar + 8 * (STAGES + prev), threadIdx.x & 1);
        }
        prev = st;
        if (++st == STAGES) { st = 0; ph ^= 1; }
      }
      wg_wait<0>();
      if ((threadIdx.x & 127) < 2) mbar_arrive_cluster(sBar + 8 * (STAGES + prev), threadIdx.x & 1);
      GT(4);
#pragma unroll
      for (int r = 0; r < BN / 128; r++) {
        if (r || p > pair0) {
          if ((threadIdx.x & 127) == 0) asm volatile("cp.async.bulk.wait_group.read 0;" ::: "memory");
          bar_sync(1 + wg, 128);
        }
        const int row = (warp & 3) * 16 + (lane & 15);
#pragma unroll
        for (int i = 0; i < 8; i++) {
          const int c = 2 * (i & 3) + (lane >> 4);
          const float* q = &acc[r * 64 + i * 8];
          stsm4(epi + (i >> 2) * 8192 + row * 128 + ((c ^ (row & 7)) << 4), pack2(q[0], q[1]), pack2(q[2], q[3]), pack2(q[4], q[5]), pack2(q[6], q[7]));
        }
        fence_async();
        bar_sync(1 + wg, 128);
        if ((threadIdx.x & 127) == 0) {
          tma2d_store(&maps.c, epi, tn * BN + r * 128, tm * 128 + wg * 64);
          tma2d_store(&maps.c, epi + 8192, tn * BN + r * 128 + 64, tm * 128 + wg * 64);
          asm volatile("cp.async.bulk.commit_group;" ::: "memory");
        }
      }
    }
    GT(5);
    if ((threadIdx.x & 127) == 0) asm volatile("cp.async.bulk.wait_group.read 0;" ::: "memory");
    GT(6);
  }
}

struct Dft { uint32_t m[2][2][2][4]; };
template <bool P4> __device__ __forceinline__ int fidx(int tile, int x) { return P4 ? 4 * (x >> 1) + 2 * (tile & 1) + (x & 1) + 16 * (tile >> 1) : x + 8 * tile; }
__device__ __forceinline__ float2 cis(int k, int n) {
  k &= n - 1; if (2 * k > n) k -= n;
  const float a = (float)k * (6.283185307179586f / (float)n);
  return make_float2(__cosf(a), __sinf(a));
}
template <bool OUT4> __device__ __forceinline__ void make_dft(Dft& D, int g, int t) {
#pragma unroll
  for (int q = 0; q < 16; q++) {
    const int b = q >> 3, u = (q >> 2) & 1, r = (q >> 1) & 1, v = q & 1;
    const float2 w = cis(fidx<OUT4>(v, g) * fidx<false>(2 * u + r, 2 * t + b), 32);
    D.m[b][u][0][q & 3] = pack2(w.x, w.y); D.m[b][u][1][q & 3] = pack2(-w.y, w.x);
  }
}
__device__ __forceinline__ void mma_dc(float (&d)[4], uint32_t a0, uint32_t a1, uint32_t a2, uint32_t a3, uint32_t b0, uint32_t b1, const float (&c)[4]) {
  asm("mma.sync.aligned.m16n8k16.row.col.f32.bf16.bf16.f32 {%0,%1,%2,%3}, {%4,%5,%6,%7}, {%8,%9}, {%10,%11,%12,%13};"
    : "=f"(d[0]), "=f"(d[1]), "=f"(d[2]), "=f"(d[3]) : "r"(a0), "r"(a1), "r"(a2), "r"(a3), "r"(b0), "r"(b1), "f"(c[0]), "f"(c[1]), "f"(c[2]), "f"(c[3])); }
__device__ __forceinline__ void dft_b(const Dft& D, const uint32_t (&x)[2][4], float (&o)[2][8]) {
#pragma unroll
  for (int ri = 0; ri < 2; ri++) {
    float z[4] = {0.f, 0.f, 0.f, 0.f}, e[4], p[4];
    mma_dc(e, D.m[0][0][ri][0], D.m[0][0][ri][1], D.m[0][0][ri][2], D.m[0][0][ri][3], x[0][0], x[0][1], z);
    mma_dc(e, D.m[0][1][ri][0], D.m[0][1][ri][1], D.m[0][1][ri][2], D.m[0][1][ri][3], x[0][2], x[0][3], e);
    mma_dc(p, D.m[1][0][ri][0], D.m[1][0][ri][1], D.m[1][0][ri][2], D.m[1][0][ri][3], x[1][0], x[1][1], e);
    mma_dc(p, D.m[1][1][ri][0], D.m[1][1][ri][1], D.m[1][1][ri][2], D.m[1][1][ri][3], x[1][2], x[1][3], p);
#pragma unroll
    for (int q = 0; q < 4; q++) { o[ri][q] = p[q]; o[ri][4 + q] = fmaf(2.f, e[q], -p[q]); }
  }
}
__device__ __forceinline__ void dft_a(const uint32_t (&m)[2][2][4], const uint32_t (&x0)[2][4], const uint32_t (&x1)[2][4], float (&o)[2][8]) {
#pragma unroll
  for (int ri = 0; ri < 2; ri++) {
    float z[4] = {0.f, 0.f, 0.f, 0.f}, e[4], p[4];
    mma_dc(e, x0[0][0], x1[0][0], x0[0][1], x1[0][1], m[0][ri][0], m[0][ri][1], z);
    mma_dc(e, x0[0][2], x1[0][2], x0[0][3], x1[0][3], m[0][ri][2], m[0][ri][3], e);
    mma_dc(p, x0[1][0], x1[1][0], x0[1][1], x1[1][1], m[1][ri][0], m[1][ri][1], e);
    mma_dc(p, x0[1][2], x1[1][2], x0[1][3], x1[1][3], m[1][ri][2], m[1][ri][3], p);
#pragma unroll
    for (int q = 0; q < 4; q++) { o[ri][q] = p[q]; o[ri][4 + q] = fmaf(2.f, e[q], -p[q]); }
  }
}
__device__ __forceinline__ uint32_t twid(float re, float im, float c, float s) { return pack2(fmaf(re, c, im * s), fmaf(im, c, -re * s)); }
__device__ __forceinline__ void cpa16(uint32_t d, const void* s) { asm volatile("cp.async.cg.shared.global [%0], [%1], 16;" :: "r"(d), "l"(s) : "memory"); }
__device__ __forceinline__ void sts32(uint32_t a, uint32_t x) { asm volatile("st.shared.u32 [%0], %1;" :: "r"(a), "r"(x) : "memory"); }
__device__ __forceinline__ void cpa_commit() { asm volatile("cp.async.commit_group;" ::: "memory"); }
template <int N> __device__ __forceinline__ void cpa_wait() { asm volatile("cp.async.wait_group %0;" :: "n"(N) : "memory"); }
__device__ __forceinline__ uint32_t lds32(uint32_t a) { uint32_t r; asm volatile("ld.shared.u32 %0, [%1];" : "=r"(r) : "r"(a) : "memory"); return r; }
#define FMID 0
constexpr int F_TP = 4112, F_TSZ = 8 * F_TP;

__device__ __forceinline__ uint32_t ldnc32(const void* p) { uint32_t v; asm volatile("ld.global.nc.b32 %0, [%1];" : "=r"(v) : "l"(p) : "memory"); return v; }
template <class F>
__device__ __forceinline__ void fft_wprep(const bf16* __restrict__ wr, const bf16* __restrict__ wi, int cta, F&& mid) {
  const int tid = threadIdx.x, g = (cta >> 1) & 7, c = (cta >> 4) & 3, t = 2 * (cta & 1) + (tid & 1);
  const int k0 = g + 8 * (cta >> 6) + 32 * (8 * c + 2 * t), l0 = (tid & ~1) + (g & 1);
  uint32_t a[4][4], b[4][4];
#pragma unroll
  for (int q = 0; q < 16; q++) {
    const int o = (k0 + 16 * (q >> 3) + 32 * ((q >> 1) & 1) + 1024 * (q & 1)) * 513 + l0 + 256 * ((q >> 2) & 1);
    a[q >> 2][q & 3] = ldnc32(wr + o);
    b[q >> 2][q & 3] = ldnc32(wi + o);
  }
  const int e = cta * 32 + (tid & 31), lh = (e >> 11) * 512, k = e & 2047, k2 = (k >> 5) & 31;
  uint32_t hz[4];
#pragma unroll
  for (int q = 0; q < 4; q++) asm volatile("ld.global.nc.u16 %0, [%1];" : "=r"(hz[q]) : "l"((q < 2 ? wr : wi) + (q & 1 ? (2048 - k) & 2047 : k) * 513 + lh) : "memory");
  mid();
  uint4* dst = g_wt + l0 * 512 + cta * 2 + (tid & 1);
#pragma unroll
  for (int q = 0; q < 8; q++) {
    const int hf = q >> 1, l = l0 + 256 * (hf & 1) + (q & 1);
    const uint32_t sel = (q & 1) ? 0x7632 : 0x5410;
    if (l & 511) dst[(256 * (hf & 1) + (q & 1)) * 512 + 256 * (q >> 2)] = make_uint4(__byte_perm(a[hf][0], b[hf][0], sel), __byte_perm(a[hf][1], b[hf][1], sel),
                                                                                   __byte_perm(a[hf][2], b[hf][2], sel), __byte_perm(a[hf][3], b[hf][3], sel));
  }
  if (tid < 32) reinterpret_cast<uint32_t*>(g_wt)[(64 * ((k >> 3) & 3) + 16 * (k2 >> 3) + 2 * (k & 7) + ((k2 >> 2) & 1)) * 8 + lh * 2048 + 2 * (k2 & 3) + (k >> 10)] =
      pack2(0.5f * (__uint_as_float(hz[0] << 16) + __uint_as_float(hz[1] << 16)), 0.5f * (__uint_as_float(hz[2] << 16) - __uint_as_float(hz[3] << 16)));
}

template <class F>
__device__ __forceinline__ void fft_rows_fwd(const bf16* __restrict__ x, const bf16* __restrict__ wr, const bf16* __restrict__ wi, uint32_t tb, int it, F&& mid) {
  const int warp = threadIdx.x >> 5, lane = threadIdx.x & 31, g = lane >> 2, t = lane & 3;
  const uint32_t in = tb + warp * 4096;
  const uint32_t f0 = in + (lane >> 3) * 256 + (((lane & 7) ^ (2 * (lane >> 3))) << 4);
  const bf16* src = x + ((256 * (warp & 3) + 64 * (warp >> 2) + 128 * (it & 1) + 32 * ((it >> 4) & 1) + 8 * (it >> 5) + ((it >> 1) & 7)) * 2048 + lane * 8);
#pragma unroll
  for (int q = 0; q < 8; q++) cpa16((f0 ^ ((q >> 2) * 144)) + (q & 3) * 1024, src + q * 256);
  cpa_commit();
  Dft D;
  float2 tw[4][8];
  fft_wprep(wr, wi, it, [&]() {
    if (FMID == 0) mid();
    make_dft<true>(D, g, t);
#pragma unroll
    for (int q = 0; q < 32; q++) {
      tw[q >> 3][q & 7] = cis(fidx<true>((q >> 1) & 3, g) * fidx<false>(q >> 3, 2 * t + (q & 1)), 1024);
      if (FMID) asm volatile("" : "+f"(tw[q >> 3][q & 7].x), "+f"(tw[q >> 3][q & 7].y) :: "memory");
    }
    if (FMID == 1) mid();
  });
  if (FMID == 2) mid();
  cpa_wait<0>(); __syncwarp();
  uint32_t a[4][2][4], y[4][2][4];
#pragma unroll
  for (int q = 0; q < 8; q++) ldsm4t(a[q & 3][q >> 2], (in + lane * 128 + ((lane & 7) << 4)) ^ (q << 4));
  float o[2][8];
#pragma unroll
  for (int i = 0; i < 4; i++) {
    dft_b(D, a[i], o);
#pragma unroll
    for (int q = 0; q < 8; q++) y[q >> 1][q & 1][i] = twid(o[0][q], o[1][q], tw[i][q].x, tw[i][q].y);
  }
  __syncthreads();
  const uint32_t w0 = tb + warp * F_TP + fidx<true>(0, g) * 128 + t * 16 + ((g & 1) << 6), wz = (g & 1) ? -64 : 64;
#pragma unroll
  for (int z = 0; z < 2; z++) {
    float o2[2][8];
    dft_b(D, y[2 * z], o); dft_b(D, y[2 * z + 1], o2);
#pragma unroll
    for (int i = 0; i < 4; i++) {
      const float sg = i < 2 ? 1.f : -1.f;
      sts128(w0 + z * wz + fidx<true>(i, 0) * 128, pack2(o[0][2 * i], sg * o[1][2 * i]), pack2(o[0][2 * i + 1], sg * o[1][2 * i + 1]),
             pack2(o2[0][2 * i], sg * o2[1][2 * i]), pack2(o2[0][2 * i + 1], sg * o2[1][2 * i + 1]));
    }
  }
  __syncthreads();
  const uint32_t ra = tb + (lane & 1) * 4 * F_TP + ((lane >> 1) + 16 * (warp ^ ((warp >> 1) & 1))) * 4;
  uint4* dst = g_y + (threadIdx.x >> 1) * 256 + (lane & 1) + it * 2;
#pragma unroll
  for (int q = 0; q < 8; q++) { const uint32_t r = ra + q * 512; dst[q * 32768] = make_uint4(lds32(r), lds32(r + F_TP), lds32(r + 2 * F_TP), lds32(r + 3 * F_TP)); }
}

template <class F>
__device__ __forceinline__ void fft_cols(uint32_t sb, int cta, int ncta, F&& ready) {
  const int warp = threadIdx.x >> 5, lane = threadIdx.x & 31, g = lane >> 2, t = lane & 3;
  const uint32_t in = sb + warp * 16384 + lane * 16, tab = sb + 131072 + lane * 16;
  auto fetch_y = [&](int l) {
#pragma unroll
    for (int q = 0; q < 16; q++) cpa16(in + q * 512, g_y + (q < 8 ? l : (1024 - l) & 1023) * 256 + (q & 7) * 32 + lane);
  };
  auto fetch_w = [&](int l) {
#pragma unroll
    for (int q = 0; q < 16; q++) cpa16(in + 8192 + q * 512, g_wt + l * 512 + q * 32 + lane);
  };
  const int l0 = cta * 8 + warp, dl = ncta * 8;
  Dft D; make_dft<false>(D, g, t);
#pragma unroll
  for (int q = 2 * warp; q < 2 * warp + 2; q++) {
    const int r = fidx<false>(q & 3, g), c = fidx<false>(q >> 2, 2 * t);
    const float2 w0 = cis(r * c, 1024), w1 = cis(r * c + r, 1024), p0 = cis(r + 32 * c, 2048), p1 = cis(r + 32 * c + 32, 2048);
    sts128(tab + q * 512, __float_as_uint(w0.x), __float_as_uint(w0.y), __float_as_uint(w1.x), __float_as_uint(w1.y));
    sts128(tab + 8192 + q * 512, __float_as_uint(p0.x), __float_as_uint(p0.y), __float_as_uint(p1.x), __float_as_uint(p1.y));
  }
  if (warp == 0) {
#pragma unroll
    for (int q = 0; q < 8; q++) {
      const int v = q >> 2, b = (q >> 1) & 1, ri = q & 1;
      sts128(tab + 16384 + q * 512, D.m[b][0][ri][v], D.m[b][0][ri][v + 2], D.m[b][1][ri][v], D.m[b][1][ri][v + 2]);
    }
  }
  ready();
  fetch_y(l0); cpa_commit();
  fetch_w(l0); cpa_commit();
#pragma unroll 1
  for (int l = l0; l <= 512; l += dl) {
    uint32_t a[2][4][2][4], y[2][4][2][4];
    float o[2][2][8];
    cpa_wait<1>();
#pragma unroll
    for (int q = 0; q < 16; q++) lds128(a[q >> 3][(q >> 1) & 3][q & 1], in + q * 512);
    if (!(l & 511)) {
      const uint32_t m0 = l ? 0x80000000u : 0u;
#pragma unroll
      for (int q = 0; q < 32; q++) { a[0][q >> 3][(q >> 2) & 1][q & 3] ^= m0; a[1][q >> 3][(q >> 2) & 1][q & 3] ^= m0 ^ 0x80000000u; }
    }
    auto first = [&]() {
#pragma unroll
      for (int i = 0; i < 4; i++) {
        dft_b(D, a[0][i], o[0]); dft_b(D, a[1][i], o[1]);
#pragma unroll
        for (int r = 0; r < 4; r++) {
          const float4 w = lds128f(tab + (4 * i + r) * 512);
#pragma unroll
          for (int s = 0; s < 2; s++) {
            y[s][r][0][i] = twid(o[s][0][2 * r], o[s][1][2 * r], w.x, w.y);
            y[s][r][1][i] = twid(o[s][0][2 * r + 1], o[s][1][2 * r + 1], w.z, w.w);
          }
        }
      }
    };
    first();
    if (l + dl <= 512) fetch_y(l + dl);
    cpa_commit();
    cpa_wait<1>();
#pragma unroll
    for (int zv = 0; zv < 4; zv++) {
      const int z = zv >> 1, v = zv & 1;
      uint32_t m[2][2][4];
#pragma unroll
      for (int q = 0; q < 4; q++) lds128(m[q >> 1][q & 1], tab + 16384 + (4 * v + q) * 512);
      dft_a(m, y[0][2 * z], y[0][2 * z + 1], o[0]); dft_a(m, y[1][2 * z], y[1][2 * z + 1], o[1]);
#pragma unroll
      for (int q = 0; q < 4; q++) {
        const int i = 2 * z + (q & 1), c = v + (q & 2);
        uint32_t w[4]; lds128(w, in + 8192 + (4 * i + c) * 512);
        const float4 ph = lds128f(tab + 8192 + (4 * c + i) * 512);
#pragma unroll
        for (int b = 0; b < 2; b++) {
          const float cs = b ? ph.z : ph.x, sn = b ? ph.w : ph.y;
          const float r1 = __uint_as_float(w[2 * b] << 16), i1 = __uint_as_float(w[2 * b] & 0xFFFF0000u);
          const float r2 = __uint_as_float(w[2 * b + 1] << 16), i2 = __uint_as_float(w[2 * b + 1] & 0xFFFF0000u);
          const float Sr = r1 + r2, Si = i1 + i2, Dr = r1 - r2, Di = i1 - i2;
          const float ar = fmaf(-Dr, sn, Sr), ai = fmaf(-Di, sn, Si), dr = fmaf(Dr, sn, Sr), di = fmaf(Di, sn, Si), br = -Di * cs, bi = Dr * cs;
          const float Ar = o[0][0][2 * q + b], Ai = o[0][1][2 * q + b], Br = o[1][0][2 * q + b], Bi = o[1][1][2 * q + b];
          a[0][i][b][c] = pack2(fmaf(ar, Ai, fmaf(ai, Ar, fmaf(br, Bi, bi * Br))), fmaf(ar, Ar, fmaf(-ai, Ai, fmaf(br, Br, -bi * Bi))));
          a[1][i][b][c] = pack2(fmaf(dr, Bi, fmaf(di, Br, fmaf(-br, Ai, -bi * Ar))), fmaf(dr, Br, fmaf(-di, Bi, fmaf(-br, Ar, bi * Ai))));
        }
      }
    }
    if (l + dl <= 512) fetch_w(l + dl);
    cpa_commit();
    first();
#pragma unroll
    for (int s = 0; s < 2; s++) {
      uint4* dst = g_y + (s ? (1024 - l) & 1023 : l) * 256 + lane;
      const float sg = s ? -1.f : 1.f;
#pragma unroll
      for (int i = 0; i < 4; i++) {
        dft_b(D, y[s][i], o[0]);
#pragma unroll
        for (int b = 0; b < 2; b++)
          dst[(2 * i + b) * 32] = make_uint4(pack2(sg * o[0][0][b], o[0][1][b]), pack2(sg * o[0][0][2 + b], o[0][1][2 + b]),
                                             pack2(sg * o[0][0][4 + b], o[0][1][4 + b]), pack2(sg * o[0][0][6 + b], o[0][1][6 + b]));
      }
    }
  }
}

template <class F>
__device__ __forceinline__ void fft_rows_inv(const CUtensorMap* om, uint32_t sb, int cta, int ncta, F&& ready) {
  const int warp = threadIdx.x >> 5, lane = threadIdx.x & 31, g = lane >> 2, t = lane & 3, wg = warp >> 2, w4 = warp & 3;
  const uint32_t tb = sb + 32768 + wg * 2 * F_TSZ;
  const uint4* src = g_y + pin((256 * ((lane >> 1) & 3) + 64 * (lane >> 3) + 8 * w4) * 256 + (lane & 1));
  const uint32_t wa = pin(tb + (lane & 1) * 4 * F_TP + w4 * 1024 + (lane >> 1) * 4);
  uint4 pf[8];
  auto fetch = [&](int it, int hf) {
#pragma unroll
    for (int q = 0; q < 8; q++) pf[q] = __ldcg(src + (it * 2 + hf * 8192) + q * 256);
  };
  auto put = [&](uint32_t off) {
#pragma unroll
    for (int q = 0; q < 8; q++) {
      sts32(wa + off + q * 64, pf[q].x); sts32(wa + off + q * 64 + F_TP, pf[q].y);
      sts32(wa + off + q * 64 + 2 * F_TP, pf[q].z); sts32(wa + off + q * 64 + 3 * F_TP, pf[q].w);
    }
  };
  const int it0 = 2 * cta + wg;
  Dft D; make_dft<false>(D, g, t);
  float2 tw[4][8];
#pragma unroll
  for (int q = 0; q < 32; q++) {
    tw[q >> 3][q & 7] = cis(fidx<false>((q >> 1) & 3, g) * fidx<false>(q >> 3, 2 * t + (q & 1)), 1024);
    tw[q >> 3][q & 7].x *= 1.f / 2097152.f; tw[q >> 3][q & 7].y *= 1.f / 2097152.f;
    asm volatile("" : "+f"(tw[q >> 3][q & 7].x), "+f"(tw[q >> 3][q & 7].y) :: "memory");
  }
  ready();
  fetch(it0, 0); put(0); fetch(it0, 1); put(512);
  const uint32_t la = pin(tb + w4 * F_TP + lane * 16), ob = uni(sb + warp * 4096);
  const uint32_t oa = pin(ob + (lane >> 1) * 128 + (((4 * (lane & 1)) ^ ((lane >> 1) & 7)) << 4));
#pragma unroll 1
  for (int n = 0;; n++) {
    const int it = it0 + (n >> 1) * 2 * ncta, hf = n & 1, buf = (n >> 1) & 1;
    if (it >= 128) break;
    if (!hf) bar_sync(1 + wg, 128);
    uint32_t a[4][2][4], y[4][2][4];
#pragma unroll
    for (int q = 0; q < 8; q++) lds128(a[q >> 1][q & 1], la + buf * F_TSZ + hf * 4 * F_TP + q * 512);
    fetch(min(it + 2 * ncta, 127), hf);
    float o[2][8];
#pragma unroll
    for (int i = 0; i < 4; i++) {
      dft_b(D, a[i], o);
#pragma unroll
      for (int q = 0; q < 8; q++) y[q >> 1][q & 1][i] = twid(o[0][q], o[1][q], tw[i][q].x, tw[i][q].y);
    }
    if (lane == 0) asm volatile("cp.async.bulk.wait_group.read 0;" ::: "memory");
    __syncwarp();
#pragma unroll
    for (int c = 0; c < 4; c++) {
      dft_b(D, y[c], o);
#pragma unroll
      for (int ri = 0; ri < 2; ri++)
        stsm4((oa ^ (c << 4)) + (1 - ri) * 2048, pack2(o[ri][0], o[ri][1]), pack2(o[ri][2], o[ri][3]), pack2(o[ri][4], o[ri][5]), pack2(o[ri][6], o[ri][7]));
    }
    fence_async();
    __syncwarp();
    if (lane == 0) {
      const int m = 256 * w4 + 32 * ((it >> 1) & 7) + 8 * (it >> 5) + 4 * (it & 1) + 2 * hf + ((it >> 4) & 1);
      asm volatile("cp.async.bulk.tensor.3d.global.shared::cta.bulk_group [%0, {0, 0, %2}], [%1];" :: "l"(om), "r"(ob), "r"(2 * m) : "memory");
      asm volatile("cp.async.bulk.commit_group;" ::: "memory");
    }
    put((buf ^ 1) * F_TSZ + hf * 512);
  }
  if (lane == 0) asm volatile("cp.async.bulk.wait_group 0;" ::: "memory");
}
__device__ __forceinline__ void grid_arrive(unsigned* ctr) {
  __syncthreads();
  if (threadIdx.x == 0) { __threadfence(); atomicAdd(ctr, 1u); }
}
__device__ __forceinline__ void grid_wait(unsigned* ctr, unsigned n) {
  if (threadIdx.x == 224) {
    int it = 0;
    while (*reinterpret_cast<volatile unsigned*>(ctr) < n) { __nanosleep(100); if (++it > SPIN_LIMIT) { g_err = 3; break; } }
    __threadfence();
  }
  __syncthreads();
}

struct RecMaps { CUtensorMap wq, wk, wv, wo, x, k, q, v, fo; };
#define NSW 16
#define EXP 0
#define NPB 3
#define NPB0 3
#define NPC 0
#define WOP 2
#define HOME 7
#define DL0 14
#define PD1 4
#define NE4 6
#define NE6 0
#define NA4 14
#define NA6 18
#define NB1 24
#define TQL 7
#define NQ 16
#define TQP (NQ - 1)
#define OXPOS 4
#define KVPOS 2
#define NK0 0
#define FLPOS 1
#define XWPOS 10
#define FSPOS 28
#define RL0 4
#define RLS 6
#define RLB 4
#define VL0 3
#define RI 9
#define RJ 8
#define NPRE 22
#define PFD 4
#define PD0 4
#define VB NV0
#define NPA 0
#define N1 16
#define DL1 16
#define PACE 0
#define RE0 0
#define RE1 0
#define RP1 23
#define UNP 1
#define X2 2
#define X3 2
#define SPOS 2
#ifndef NV0
#define NV0 4
#endif
#define TGP 3
#define FENP 0
#define LW0 8
#define X1 4
#define X0 4
constexpr int R_WO = 0, R_X = 65536, R_MEM = 131072, R_WC = 147456, R_RED = R_WC + NSW * 2048, R_O = R_RED, R_S = R_O + 2048, R_P = R_S + 3072, R_STAGE = R_P + 2048,
              R_K = R_STAGE + 8192, R_Q = R_K + 8192, R_V = R_Q + 2048, R_ID = R_V + 16384, R_T = R_ID + 512, R_DST = R_T + 512, R_RD = R_DST + 2048, R_BAR = R_RD + 2048, R_TS = R_BAR + 128,
              R_TOTAL = R_TS;
#define TS(i)
#define LOG(i, v)
constexpr int B_KV = R_BAR, B_W = R_BAR + 8, B_X = R_BAR + 80, B_PK = R_BAR + 24, B_C = R_BAR + 32, B_B = R_BAR + 40, B_DUE = R_BAR + 48, B_ONE = R_BAR + 64;
#define DLY_A 150
#define DLY_V 150
#define DLY_C 200
#define DLY_L 90
#define NS_B 1120
#define NS_C 1728
#define NS_P 2624
#define NS_V 128
#define NS_F 896
#define NS_K 128
#define NS_M 32
#define NS_X 128
#define MG_Z 0x00010206
#define MG_Y 0x00010512
#define NS_PEN 1024
__device__ __forceinline__ float rcp(float x) { float r; asm("rcp.approx.ftz.f32 %0, %1;" : "=f"(r) : "f"(x)); return r; }
__device__ __forceinline__ uint32_t movm(uint32_t a) { uint32_t d; asm volatile("movmatrix.sync.aligned.m8n8.trans.b16 %0, %1;" : "=r"(d) : "r"(a)); return d; }
__device__ __forceinline__ uint32_t hadd2(uint32_t a, uint32_t b) { uint32_t d; asm("add.rn.bf16x2 %0, %1, %2;" : "=r"(d) : "r"(a), "r"(b)); return d; }
__device__ __forceinline__ void mma_a(float (&d)[4], const uint32_t (&a)[4], uint32_t b0, uint32_t b1) { mma16816(d, a[0], a[1], a[2], a[3], b0, b1); }
__device__ __forceinline__ bool elect() {
  uint32_t p; asm volatile("{.reg .pred p; elect.sync _|p, 0xffffffff; selp.u32 %0, 1, 0, p;}" : "=r"(p)); return p; }
__device__ __forceinline__ void tma3d(uint32_t dst, const CUtensorMap* m, int c1, int c2, uint32_t bar) {
  asm volatile("cp.async.bulk.tensor.3d.shared::cluster.global.mbarrier::complete_tx::bytes [%0], [%1, {0, %3, %4}], [%2];"
    :: "r"(dst), "l"(m), "r"(bar), "r"(c1), "r"(c2) : "memory"); }
__device__ __forceinline__ void tma4d(uint32_t dst, const CUtensorMap* m, int c1, int c2, uint32_t bar) {
  asm volatile("cp.async.bulk.tensor.4d.shared::cluster.global.mbarrier::complete_tx::bytes [%0], [%1, {0, %3, %4, 0}], [%2];"
    :: "r"(dst), "l"(m), "r"(bar), "r"(c1), "r"(c2) : "memory"); }
template <int OFF, int ACC>
__device__ __forceinline__ void wg_rs32(float (&d)[16], const uint32_t (&a)[4], uint32_t db) {
  if (ACC)
    asm volatile("{.reg .b64 db; .reg .b32 lo; add.u32 lo, %20, %21; mov.b64 db, {lo, 0x40000040};\n"
      "wgmma.mma_async.sync.aligned.m64n32k16.f32.bf16.bf16 {%0,%1,%2,%3,%4,%5,%6,%7,%8,%9,%10,%11,%12,%13,%14,%15}, {%16,%17,%18,%19}, db, 1, 1, 1, 0;}"
      : "+f"(d[0]), "+f"(d[1]), "+f"(d[2]), "+f"(d[3]), "+f"(d[4]), "+f"(d[5]), "+f"(d[6]), "+f"(d[7]), "+f"(d[8]), "+f"(d[9]), "+f"(d[10]), "+f"(d[11]), "+f"(d[12]), "+f"(d[13]), "+f"(d[14]), "+f"(d[15])
      : "r"(a[0]), "r"(a[1]), "r"(a[2]), "r"(a[3]), "r"(db), "n"(OFF));
  else
    asm volatile("{.reg .b64 db; .reg .b32 lo; add.u32 lo, %20, %21; mov.b64 db, {lo, 0x40000040};\n"
      "wgmma.mma_async.sync.aligned.m64n32k16.f32.bf16.bf16 {%0,%1,%2,%3,%4,%5,%6,%7,%8,%9,%10,%11,%12,%13,%14,%15}, {%16,%17,%18,%19}, db, 0, 1, 1, 0;}"
      : "=f"(d[0]), "=f"(d[1]), "=f"(d[2]), "=f"(d[3]), "=f"(d[4]), "=f"(d[5]), "=f"(d[6]), "=f"(d[7]), "=f"(d[8]), "=f"(d[9]), "=f"(d[10]), "=f"(d[11]), "=f"(d[12]), "=f"(d[13]), "=f"(d[14]), "=f"(d[15])
      : "r"(a[0]), "r"(a[1]), "r"(a[2]), "r"(a[3]), "r"(db), "n"(OFF));
}
template <int I> using IC = std::integral_constant<int, I>;
template <int I, int N, class F> __device__ __forceinline__ void sfor(F&& f) {
  if constexpr (I < N) { f(std::integral_constant<int, I>{}); sfor<I + 1, N>(f); }
}
__device__ __forceinline__ void keep(float (&d)[16]) {
  asm volatile("" : "+f"(d[0]), "+f"(d[1]), "+f"(d[2]), "+f"(d[3]), "+f"(d[4]), "+f"(d[5]), "+f"(d[6]), "+f"(d[7]),
      "+f"(d[8]), "+f"(d[9]), "+f"(d[10]), "+f"(d[11]), "+f"(d[12]), "+f"(d[13]), "+f"(d[14]), "+f"(d[15]) :: "memory");
}

template <int N, int S2 = 1024> __device__ __forceinline__ void ldx(uint32_t (&v)[N][4], const uint8_t* p) {
#pragma unroll
  for (int k = 0; k < 2 * N; k++) {
    const int i = k;
    asm volatile("ld.relaxed.gpu.global.v2.b32 {%0,%1}, [%2];" : "=r"(v[i >> 1][2 * (i & 1)]), "=r"(v[i >> 1][2 * (i & 1) + 1]) : "l"(p + (i & 3) * 256 + (i >> 2) * S2) : "memory");
  }
}
__device__ __forceinline__ uint32_t dif2(uint32_t a, uint32_t b, uint32_t tag) { uint32_t r; asm("lop3.b32 %0, %1, %2, %3, 0x7e;" : "=r"(r) : "r"(a), "r"(b), "r"(tag)); return r; }
__device__ __forceinline__ uint32_t dif2v(uint32_t a, uint32_t b, uint32_t tag) { uint32_t r; asm volatile("lop3.b32 %0, %1, %2, %3, 0x7e;" : "=r"(r) : "r"(a), "r"(b), "r"(tag)); return r; }
__device__ __forceinline__ uint32_t or3(uint32_t a, uint32_t b, uint32_t c) { uint32_t r; asm("lop3.b32 %0, %1, %2, %3, 0xfe;" : "=r"(r) : "r"(a), "r"(b), "r"(c)); return r; }
__device__ __forceinline__ uint32_t after(uint32_t x, float f, uint32_t z) { uint32_t r; asm("lop3.b32 %0, %1, %2, %3, 0xea;" : "=r"(r) : "r"(__float_as_uint(f)), "r"(z), "r"(x)); return r; }
__device__ __forceinline__ bool any_bit(uint32_t a, uint32_t b, uint32_t m) {
  uint32_t r; asm("lop3.b32 %0, %1, %2, %3, 0xa8;" : "=r"(r) : "r"(a), "r"(b), "r"(m)); return __any_sync(0xffffffffu, r); }
template <int W, int N> __device__ __forceinline__ bool stale(const uint32_t (&v)[N][4], uint32_t tag) {
  uint32_t x = dif2(v[0][0], v[0][2], tag);
  if (N == 4) x = or3(x, dif2(v[1][0], v[1][2], tag), dif2(v[2 % N][0], v[2 % N][2], tag));
  return any_bit(x, dif2(v[N - 1][0], v[N - 1][2], tag), 1);
}
template <int W, int N, int S2 = 1024> __device__ __forceinline__ void retry(uint32_t (&v)[N][4], const uint8_t* p, uint32_t tag, int& it) {
#pragma unroll 1
  do { ldx<N, S2>(v, p); it += INC_A; } while (stale<W>(v, tag) && it < SPIN_LIMIT);
}
__device__ __forceinline__ void mma_h(float (&d)[4], const uint32_t (&a)[4], const uint32_t (&b)[4], int hf) { mma16816(d, a[0], a[1], a[2], a[3], b[2 * hf], b[2 * hf + 1]); }
__device__ __forceinline__ void sts128(uint32_t a, const uint32_t (&r)[4]) { sts128(a, r[0], r[1], r[2], r[3]); }
__device__ __forceinline__ void sts128f(uint32_t a, const float* r) { sts128(a, __float_as_uint(r[0]), __float_as_uint(r[1]), __float_as_uint(r[2]), __float_as_uint(r[3])); }
__device__ __forceinline__ void mbar_spin(uint32_t bar, uint32_t par, int& it) {
  asm volatile("{.reg .pred p; .reg .b32 par; mov.b32 par, %2;\nLOOP: mbarrier.try_wait.parity.shared::cta.b64 p, [%1], par; @p bra.uni DONE;\n"
               "add.s32 %0, %0, 1; setp.le.s32 p, %0, %3; @p bra.uni LOOP;\nDONE: }" : "+r"(it) : "r"(bar), "r"(par), "n"(SPIN_LIMIT) : "memory"); }
__device__ __forceinline__ void warp_arrive(uint32_t bar) {
  __syncwarp(); asm volatile("{.reg .pred p; elect.sync _|p, 0xffffffff; @p mbarrier.arrive.shared::cta.b64 _, [%0];}" :: "r"(bar) : "memory"); }
__device__ __forceinline__ void delay_until(unsigned t) {
  asm volatile("{.reg .pred p; .reg .b64 c; .reg .b32 lo, hi;\nLOOP: mov.u64 c, %%clock64; mov.b64 {lo, hi}, c; sub.s32 lo, lo, %0; setp.lt.s32 p, lo, 0; @p bra.uni LOOP;}" :: "r"(t) : "memory"); }
__device__ __forceinline__ void cut(int it) { asm volatile("{.reg .pred p; setp.lt.s32 p, %0, 0;\nL: @p st.volatile.shared.u32 [%0], %0; @p bra.uni L;}" :: "r"(it) : "memory"); }
__device__ __forceinline__ void zero(float (&c)[4][4]) {
#pragma unroll
  for (int i = 0; i < 4; i++) c[i][0] = c[i][1] = c[i][2] = c[i][3] = 0.f;
}

__device__ __forceinline__ void sched() { asm volatile("griddepcontrol.launch_dependents;" ::: "memory"); }
__device__ __forceinline__ const uint8_t* pinp(const uint8_t* p) { return reinterpret_cast<const uint8_t*>(__shfl_xor_sync(0xffffffffu, reinterpret_cast<unsigned long long>(p), 0)); }
__device__ __forceinline__ uint32_t bar_or(int id, uint32_t x) {
  uint32_t r; asm volatile("{.reg .pred p, q; setp.ne.u32 p, %2, 0; bar.red.or.pred q, %1, 256, p; selp.u32 %0, 1, 0, q;}" : "=r"(r) : "r"(id), "r"(x) : "memory"); return r; }
__device__ __forceinline__ void bar_sync_unless(int id, uint32_t x) { asm volatile("{.reg .pred p; setp.eq.u32 p, %1, 0; @p bar.sync %0, 256;}" :: "r"(id), "r"((uint32_t)x) : "memory"); }
__device__ __forceinline__ void bar_arrive_unless(int id, uint32_t x) { asm volatile("{.reg .pred p; setp.eq.u32 p, %1, 0; @p bar.arrive %0, 256;}" :: "r"(id), "r"((uint32_t)x) : "memory"); }
__device__ __forceinline__ void stsm2t(uint32_t a, uint32_t r0, uint32_t r1, uint32_t x) {
  asm volatile("{.reg .pred p; setp.eq.u32 p, %3, 0; @p stmatrix.sync.aligned.m8n8.x2.trans.shared.b16 [%0], {%1,%2};}" :: "r"(a), "r"(r0), "r"(r1), "r"((uint32_t)x) : "memory"); }
__device__ __forceinline__ uint32_t or_and(uint32_t a, uint32_t b, uint32_t m) { uint32_t r; asm("lop3.b32 %0, %1, %2, %3, 0xa8;" : "=r"(r) : "r"(a), "r"(b), "r"(m)); return r; }
#define rare(x) __builtin_expect(!!(x), 0)
__device__ __forceinline__ uint32_t gtime() { unsigned long long g; asm volatile("mov.u64 %0, %%globaltimer;" : "=l"(g) :: "memory"); return (uint32_t)g; }
__device__ __forceinline__ void wait_time(uint32_t t) {
  asm volatile("{.reg .pred p; .reg .b32 g; .reg .b64 c;\nLOOP: mov.u64 c, %%globaltimer; cvt.u32.u64 g, c; sub.s32 g, %0, g; setp.lt.u32 p, g, 16384; @p bra.uni LOOP;}" :: "r"(t - 1) : "memory"); }
__device__ __forceinline__ uint32_t ldx32(const void* p) { uint32_t v; asm volatile("ld.relaxed.gpu.global.b32 %0, [%1];" : "=r"(v) : "l"(p) : "memory"); return v; }
__device__ __forceinline__ void stx32(const void* p, uint32_t v) { asm volatile("st.relaxed.gpu.global.b32 [%0], %1;" :: "l"(p), "r"(v) : "memory"); }

__global__ void __launch_bounds__(256, 1)
rec_kernel(const __grid_constant__ RecMaps maps, const bf16* __restrict__ xin, const bf16* __restrict__ mem0, Xchg* const gx,
           const bf16* __restrict__ fx, const bf16* __restrict__ wr, const bf16* __restrict__ wi) {
  extern __shared__ __align__(1024) uint8_t smem_raw[];
  const uint32_t sb = smem_u32(smem_raw);
  int role = blockIdx.x;
  {
    uint32_t smid, nsm; asm volatile("mov.u32 %0, %%smid;" : "=r"(smid)); asm volatile("mov.u32 %0, %%nsmid;" : "=r"(nsm));
    const int p = smid >> 1, u = p - 32;
    if (nsm == gridDim.x)
      role = (smid & 1) + (p < 32 ? 4 * ((p & 7) + 8 * (p >> 4)) + 2 * ((p >> 3) & 1) : p < 60 ? 4 * (16 + u % 7 + 7 * (u / 14)) + 2 * ((u / 7) & 1)
                         : p < 62 ? 2 * p + 8 : 2 * p - 4);
    role = uni(role);
  }
  if (role >= 128) {
    fft_cols(sb, role - 128, 4, [&]() { grid_wait(&gx->ctr[33], 128); });
    __threadfence(); __syncwarp();
    if ((threadIdx.x & 31) == 0) atomicAdd(&gx->ctr[32], 1u);
    __syncwarp();
    fft_rows_inv(&maps.fo, sb, role - 128, 4, [&]() { grid_wait(&gx->ctr[32], 32); });
    return;
  }
  const int tid = threadIdx.x, warp = uni(tid >> 5), lane = tid & 31, wg = warp >> 2, w4 = warp & 3, g = lane >> 2, t = lane & 3;
  const int h = role >> 2, j = role & 3, jh = j & 1;
  uint32_t w[48][4];
  float aq[16], av[16];
  int it = 0;

#define PT(k)
  auto pf_wo = [&]() {
    for (int i = 0; i < 4; i++)
      asm volatile("cp.async.bulk.prefetch.tensor.2d.L2.global [%0, {%1, %2}];" :: "l"(&maps.wo), "r"(256 * j + 64 * i), "r"(h * DH) : "memory");
  };
  fft_rows_fwd(fx, wr, wi, sb + R_MEM + 49152, role, [&]() {
    if (tid == 224) {
      mbar_init(sb + B_KV, 1); mbar_init(sb + B_W, 1); mbar_init(sb + B_X, 1); mbar_init(sb + B_X + 8, 1); mbar_init(sb + B_X + 16, 1); mbar_init(sb + B_X + 24, 1); mbar_init(sb + B_C, 4); mbar_init(sb + B_PK, 4); mbar_init(sb + B_B, 1);
      asm volatile("fence.mbarrier_init.release.cluster;" ::: "memory");
      mbar_expect_tx(sb + B_W, 3 * 65536);
      for (int i = 0; i < 4; i++) {
        tma2d(sb + R_X + i * 16384, &maps.wq, h * DH + 32 * j, i * 256, sb + B_W);
        if (i < 3) tma2d(sb + R_MEM + i * 16384, &maps.wk, h * DH + 32 * j, i * 256, sb + B_W);
        else asm volatile("cp.async.bulk.prefetch.tensor.2d.L2.global [%0, {%1, %2}];" :: "l"(&maps.wk), "r"(h * DH + 32 * j), "r"(768) : "memory");
      }
      for (int i = 0; i < 2; i++) tma2d(sb + R_WO + i * 32768, &maps.wv, h * DH + 64 * (j >> 1), jh * 512 + i * 256, sb + B_W);
      if (PFD) asm volatile("cp.async.bulk.prefetch.L2.global [%0], 2048;" :: "l"(xin + role * DM) : "memory");
      else for (int i = 0; i < 4; i++) asm volatile("cp.async.bulk.prefetch.L2.global [%0], 8192;" :: "l"(xin + role * 16384 + i * 4096) : "memory");
      if (WOP == 0) pf_wo();
      for (int i = 0; i < 5; i++) asm volatile("prefetch.tensormap [%0];" :: "l"(&maps.wo + i) : "memory");
    }
    __syncwarp();
  });
  if (tid < 16) sts32(sb + R_T + tid * 4, ~0u);
  fence_async();
  PT(0);
  grid_arrive(&gx->ctr[33]);
  PT(1);
  if (tid == 224) { tma2d(sb + R_MEM + 49152, &maps.wk, h * DH + 32 * j, 768, sb + B_W); if (WOP == 1) pf_wo(); }
  __syncwarp();
  uint8_t* const xb = reinterpret_cast<uint8_t*>(gx);
  auto probe_at = [&](int n) { return xb + (n ? offsetof(Xchg, C) + w4 * 8192 + role * 32 : offsetof(Xchg, B) + role * 8192 + warp * 128); };
  if (lane < 8) stx128(probe_at(lane >> 2) + (lane & 2) * 2048 + (lane & 1) * 16, 0, 0, 0, 0);
  uint32_t m0[4][4];
#pragma unroll
  for (int i = 0; i < 16; i++) m0[i >> 2][i & 3] = ldnc32(mem0 + g * DM + 128 * warp + 8 * i + 2 * t);
  mbar_spin(sb + B_W, 0, it);
  PT(2);
  const int lrow = (lane & 7) + ((lane >> 4) << 3), lhi = (lane >> 3) & 1;
  const int kq = wg ? 3 - 3 * jh : 3 * jh;
  const uint32_t LW = lrow * 128 + ((lhi ^ (lane & 7)) << 4);
  {
    const int chunk = w4 < 2 ? w4 + 2 * lhi : 2 * (w4 & 1) + lhi;
    uint32_t a = sb + (w4 < 2 ? R_X : R_MEM) + kq * 16384 + lrow * 64 + ((chunk ^ ((lrow >> 1) & 3)) << 4);
#pragma unroll
    for (int i = 0; i < 16; i++) ldsm4t(w[i], a + i * 1024);
    const uint32_t st = wg ? 1024 : 2048, av0 = sb + R_WO + (LW ^ (w4 << 5));
    const uint32_t a1 = wg ? a + (2 * jh - 1) * 16384 : av0 + jh * 32768, a2 = wg ? a + (2 * jh - 1) * 32768 : av0 + (1 - jh) * 32768;
#pragma unroll
    for (int i = 0; i < 16; i++) { ldsm4t(w[16 + i], a1 + i * st); ldsm4t(w[32 + i], a2 + i * st); }
  }
  uint32_t L16 = pin(lane * 16);
  const uint32_t uW = uni(sb + w4 * 512), uWo = uni(sb + R_WO + w4 * 16384), uMem = uni(sb + R_MEM + kq * 4096);
  const uint32_t dX = uni(((sb + R_X + kq * 16384) >> 4) | 0x10000u);
  auto load_wo = [&](uint32_t (&d)[32][4], int i0, int i1) {
#pragma unroll
    for (int i = i0; i < i1; i++) lds128(d[i], uWo + L16 + (i & 1) * 512 + (i >> 4) * 1024 + (i & 14) * 1024);
  };
  auto issue_x = [&](int n, int k) {
    const uint32_t bar = sb + B_X + 8 * k, q = k ^ (3 - 3 * jh);
    mbar_expect_tx(bar, 16384); tma3d(sb + R_X + q * 16384, &maps.x, n * SEG, 4 * q, bar);
  };
  auto store_stage = [&](int n) {
    asm volatile("cp.async.bulk.global.shared::cta.bulk_group [%0], [%1], 8192; cp.async.bulk.commit_group;"
                 :: "l"(g_kqv[n & 3][role]), "r"(sb + R_STAGE) : "memory");
  };
  auto issue_kqv = [&](int n) {
    const int p = (n & 3) * 128 + 4 * h;
    mbar_expect_tx(sb + B_KV, 26624);
    tma3d(sb + R_K, &maps.k, 0, p, sb + B_KV); tma3d(sb + R_Q, &maps.q, 8 + 2 * j, p, sb + B_KV); tma3d(sb + R_V, &maps.v, 16, p, sb + B_KV);
  };
  auto fetch4k = [&](uint32_t dst, uint32_t off, uint32_t bar, uint32_t t) {
    asm volatile("{.reg .pred p, q; .reg .b32 g; .reg .b64 c; elect.sync _|q, 0xffffffff; @q mbarrier.arrive.expect_tx.shared::cta.b64 _, [%2], 4096;\n"
                 "LOOP: mov.u64 c, %%globaltimer; cvt.u32.u64 g, c; sub.s32 g, %3, g; setp.lt.u32 p, g, 16384; @p bra.uni LOOP;\n"
                 "@q cp.async.bulk.shared::cluster.global.mbarrier::complete_tx::bytes [%0], [%1], 4096, [%2];}" :: "r"(dst), "l"(xb + off), "r"(bar), "r"(t - 1) : "memory");
  };
  uint32_t uS;
  auto my_b = [&]() { return offsetof(Xchg, B) + role * 8192 + ((uS + ((uint32_t)it >> 31)) & 1) * 4096; };
  auto issue_c = [&](uint32_t t) { fetch4k(sb + R_MEM + w4 * 4096, offsetof(Xchg, C) + w4 * 8192 + ((uS + ((uint32_t)it >> 31)) & 4096), sb + B_C, t); };
  auto wait_x = [&](int n, int i) { if (!(EXP & 1) || n < 2) mbar_spin(sb + B_X + 8 * i, n & 1, it); };
#define PACED(d0) uint32_t dz = d0; const uint32_t z = (uint32_t)it >> 31; auto pace = [&]() { for (int k = 0; k < PACE; k++) { if (k & 1) asm("add.u32 %0, %0, %1;" : "+r"(dz) : "r"(z)); else asm("xor.b32 %0, %0, %1;" : "+r"(dz) : "r"(z)); } };
  auto project_v = [&](auto I0, auto I1, auto&& mid) {
    PACED(decltype(I0)::value < 16 ? dX : dX ^ 1024);
    wg_fence();
    sfor<decltype(I0)::value, decltype(I1)::value>([&](auto I) {
      constexpr int i = decltype(I)::value;
      mid(i);
      if (i == 16 && decltype(I0)::value < 16) dz ^= 1024;
      wg_rs32<((i >> 2) & 3) * 256 + (i & 3) * 2, (i > 0)>(av, w[16 + i], dz);
      pace();
    });
    wg_commit();
  };
  auto project_qk = [&](auto I0, auto I1, auto first, auto&& mid) {
    PACED((dX ^ (decltype(I0)::value >> 4 << 10)) + ((uint32_t)it >> 31));
    wg_fence();
    sfor<decltype(I0)::value, decltype(I1)::value>([&](auto I) {
      constexpr int i = decltype(I)::value;
      mid(i);
      wg_rs32<((i >> 2) & 3) * 256 + (i & 3) * 2, !decltype(first)::value || i != decltype(I0)::value>(aq, w[i], dz);
      pace();
    });
    wg_commit();
  };
  const uint32_t uP = uni(sb + R_X + 3 * jh * 16384 + w4 * 512);
  auto park = [&]() {
    bar_sync(1, 128);
#pragma unroll
    for (int i = 0; i < 4; i++) sts128f(uP + L16 + i * 2048, aq + 4 * i);
    warp_arrive(sb + B_PK);
  };
  auto unpark = [&]() {
#pragma unroll
    for (int i = 0; i < 4; i++) {
      const float4 p = lds128f(uP + L16 + i * 2048);
      av[4 * i] = p.x; av[4 * i + 1] = p.y; av[4 * i + 2] = p.z; av[4 * i + 3] = p.w;
    }
  };
  auto fin_qk = [&]() {
#pragma unroll
    for (int i = 0; i < 16; i++) aq[i] += av[i];
    const uint32_t a = sb + R_STAGE + (w4 < 2 ? 2048 + w4 * 128 : (w4 & 1) * 256) + (L16 & 112) + (L16 >> 7) * 512;
    stsm4t(a, pack2(aq[0], aq[1]), pack2(aq[4], aq[5]), pack2(aq[8], aq[9]), pack2(aq[12], aq[13]));
    stsm4t(a + (w4 < 2 ? 256 : 128), pack2(aq[2], aq[3]), pack2(aq[6], aq[7]), pack2(aq[10], aq[11]), pack2(aq[14], aq[15]));
  };
  auto fin_v = [&]() {
#pragma unroll
    for (int a = 0; a < 2; a++)
      sts128(sb + R_STAGE + 4096 + w4 * 1024 + a * 512 + L16, pack2(av[8 * a], av[8 * a + 1]), pack2(av[8 * a + 2], av[8 * a + 3]),
             pack2(av[8 * a + 4], av[8 * a + 5]), pack2(av[8 * a + 6], av[8 * a + 7]));
  };
  __syncthreads();
  if (tid == 224) {
#pragma unroll 1
    for (int i = 0; i < 4; i++) issue_x(0, i);
    mbar_expect_tx(sb + B_W, 65536);
    for (int i = 0; i < 4; i++) tma2d(sb + R_WO + i * 16384, &maps.wo, 256 * j + 64 * i, h * DH, sb + B_W);
  }
  __syncwarp();
  if (wg) {
#pragma unroll
    for (int i = 0; i < NSW; i++) sts128(uW + R_WC + L16 + i * 2048, w[i]);
  }
#pragma unroll
  for (int i = 0; i < 4; i++) sts128(sb + R_MEM + warp * 2048 + i * 512 + (g >> 1) * 128 + t * 32 + (g & 1) * 16, m0[i]);
  auto probe = [&](int n, int cnt) {
    if (lane == 0) {
#pragma unroll 1
      for (int i = role >> 7; i < cnt; i++) {
        const int k = (i ^ wg) & 1;
        const unsigned t0 = clk();
        uint32_t v; asm volatile("atom.relaxed.gpu.global.exch.b32 %0, [%1], 0;" : "=r"(v) : "l"(probe_at(n) + k * 4096) : "memory");
        if (v == 0) asm volatile("red.shared.min.u32 [%0], %1;" :: "r"(sb + R_T + (n ? w4 * 8 : 32) + k * 4), "r"(clk() - t0) : "memory");
      }
    }
    __syncwarp();
  };
#pragma unroll 1
  for (int n = 0; n < 2; n++) {
    probe(0, n ? NPB : NPB0);
    asm volatile("{.reg .pred p; cp.async.bulk.wait_group 0; setp.eq.u32 p, %1, 97; @p red.relaxed.gpu.global.add.u32 [%0], 1;}" :: "l"(&gx->ctr[h]), "r"(tid ^ n ^ (1 - n) << 9) : "memory");
    PT(3 + 3 * n);
    wait_x(n, 2);
    PT(4 + 3 * n);
    if (wg == 0) {
      wait_x(n, 3);
      project_qk(IC<0>{}, IC<16>{}, IC<1>{}, [](int) {});
      project_v(IC<0>{}, IC<32>{}, [](int) {});
      wg_wait<0>(); keep(aq); keep(av);
      park();
      fin_v();
      fence_async();
    } else {
      wait_x(n, 0); wait_x(n, 1);
      project_qk(IC<32>{}, IC<48>{}, IC<1>{}, [](int) {});
      project_qk(IC<16>{}, IC<32>{}, IC<0>{}, [](int) {});
      project_qk(IC<0>{}, IC<16>{}, IC<0>{}, [](int) {});
      mbar_spin(sb + B_PK, n, it);
      unpark();
      wg_wait<0>(); keep(aq);
      fin_qk();
      fence_async();
    }
    __syncthreads();
    if (tid == 0 && n) stx32(&gx->S[role], 1 + (HOME & 2 && lds32(sb + R_T + 36) < lds32(sb + R_T + 32)));
    PT(5 + 3 * n);
    if (tid == 96 && n == 0) store_stage(0);
    if (tid == 128 && n == 0) {
#pragma unroll 1
      for (int i = 0; i < 4; i++) issue_x(1, i);
    }
    if (warp == 5 && n == 1) {
#pragma unroll 1
      while (__any_sync(0xffffffffu, ldx32(&gx->ctr[h]) < 4) && ++it < SPIN_LIMIT) {}
      if (elect()) issue_kqv(0);
    }
    __syncwarp();
  }
  mbar_spin(sb + B_W, 1, it);
  PT(9);
#pragma unroll
  for (int i = 0; i < 4; i++) {
    uint32_t f[4][4];
    const uint32_t a = sb + R_WO + warp * 8192 + i * 2048;
#pragma unroll
    for (int q = 0; q < 4; q++) ldsm4t(f[q], a + (LW ^ (q << 5)));
    __syncwarp();
#pragma unroll
    for (int q = 0; q < 4; q++) sts128(a + q * 512 + L16, f[q]);
  }
  if (NPC) probe(1, NPC);
  {
    const int o = 32 * w4 + 16 * wg + 4 * t + j;
    uint32_t v;
#pragma unroll 1
    while (__any_sync(0xffffffffu, (v = ldx32(&gx->S[o])) == 0) && ++it < SPIN_LIMIT) {}
    asm volatile("st.shared.u64 [%0], %1;" :: "r"(sb + R_DST + wg * 1024 + w4 * 256 + lane * 8), "l"(xb + offsetof(Xchg, B) + o * 8192 + (v >> 1) * 4096 + h * 128 + ((g ^ h) & 7) * 16) : "memory");
  }
  if (wg == 0) {
    const uint64_t cd = reinterpret_cast<uint64_t>(xb + (offsetof(Xchg, C) + j * 8192 + h * 128 + w4 * 32 + (L16 & 16) * 256 + (L16 & 64) / 4 + (L16 >> 7) * 4));
    sts128(uW + R_RD + L16, (uint32_t)cd, (uint32_t)(cd >> 32), sb + R_MEM + (L16 & 112) * 8 + (L16 >> 8) * 1024 + ((w4 * 32 + ((L16 >> 3) & 16)) ^ (L16 & 112)),
           (L16 >> 6) == (h & 3) * 2 + ((h >> 2) & 1) ? 0xFFFE0000u : 0xFFFFFFFFu);
  }
  if (tid == 0) sts32(sb + B_DUE + 8, gtime() & ~31u);
  PT(10);
  mbar_spin(sb + B_KV, 0, it);
  PT(11);
  if (tid < 4) sts32(sb + B_ONE + tid * 4, 0x3F803F80u);
  if (warp == 1) { const uint32_t e = g >> 1 == t ? 0x3F80u << (16 * (g & 1)) : 0u; sts128(sb + R_ID + L16, e, 0, 0, e); }
  __syncthreads();
  {
    const uint32_t kb = lds32(sb + R_T + 36) < lds32(sb + R_T + 32);
    uS = uni((HOME & 4 ? (__popc(((offsetof(Xchg, B) / 4096 + 2 * role) ^ (offsetof(Xchg, C) / 4096 + 2 * w4)) & 0xb3) ^ kb) & 1 : lds32(sb + R_T + w4 * 8 + 4) < lds32(sb + R_T + w4 * 8)) * 4096 + kb);
  }

  const float sc = 0.08838834764831845f * 1.4426950408889634f;
  uint8_t* const xa = xb + uni(h * 16384);
  const uint32_t uA = uni(wg ? (w4 >> 1) * 2048 + j * 512 + (w4 & 1) * 256 : 8192 + (4 * (j >> 1) + w4) * 512 + jh * 256);
  const uint32_t uP2 = uni(sb + R_P + w4 * 256);
  uint32_t nc = 1;
  uint32_t ma;
  const uint8_t* adst;
  auto pin_mem = [&]() { adst = pinp(xa + uA + L16 / 2); ma = pin(uMem + (L16 & 384) + (L16 & 48) * 2 + (L16 & 64) / 4); };
  pin_mem();

#pragma unroll 1
  for (int s = 0;; nc++) {
    const uint32_t tag = (s + 1) & 1;
    auto fresh = [&]() { L16 += (uint32_t)it >> 31; };
    auto get_due = [&]() { return lds32(sb + B_DUE + 4 + tag * 4); };
    float c[4][4], r4[4];
    auto fold = [&]() {
#pragma unroll
      for (int i = 0; i < 4; i++) r4[i] = ((c[0][i] + c[1][i]) + c[2][i]) + c[3][i];
    };
    auto mma4 = [&](int n, const uint32_t (&b0)[4], const uint32_t (&b1)[4]) {
      mma_h(c[0], w[n + 2], b1, 0); mma_h(c[1], w[n + 3], b1, 1); mma_h(c[2], w[n], b0, 0); mma_h(c[3], w[n + 1], b0, 1);
    };
    auto xpos = [&](int pos, int wp) {
      if ((pos == X0 || pos == X1 || pos == X2 || pos == X3) && warp == wp && s + 1 < NSEG && elect()) {
        const int z = (uint32_t)it >> 31;
        if (pos == X2) issue_x(s + 2, 2 + z);
        if (pos == X3) issue_x(s + 2, 3 + z);
        if (pos == X1) issue_x(s + 2, 1 + z);
        if (pos == X0) issue_x(s + 2, z);
      }
      __syncwarp();
    };
    if (wg == 0) {
      mbar_spin(sb + B_C, nc & 1, it);
      TS(13);
      uint32_t b[16][4], tg[4];
#pragma unroll
      for (int i = 0; i < PD0; i++) { lds128(b[i], ma + i * 512); __syncwarp(); }
      sched();
      zero(c);
#pragma unroll
      for (int i = 0; i < 8; i++) {
        const int k = i ^ 1;
        mma_h(c[0], w[2 * k], b[k], 0); mma_h(c[1], w[2 * k + 1], b[k], 1);
        if (i < 2 * NV0) { mma_h(c[2], w[16 + 2 * k], b[k], 0); mma_h(c[3], w[17 + 2 * k], b[k], 1); }
        sched();
        if ((i & 1) && i + PD0 < 9) { lds128(b[i + PD0 - 1], ma + (i + PD0 - 1) * 512); __syncwarp(); lds128(b[i + PD0], ma + (i + PD0) * 512); sched(); }
        if (i == TGP) {
          fresh();
#pragma unroll
          for (int k = 0; k < 4; k++) tg[k] = lds32((uW * 4 + L16) * 2 + (L16 >> 6) * 4 + (R_MEM + k * 1024 - 7 * sb));
          sched();
        }
      }
#pragma unroll
      for (int i = 0; i < 4; i++) { r4[i] = c[0][i] + c[1][i]; c[0][i] = c[1][i] = 0.f; }
      sts128f(uW + R_RED + L16, r4);
      TS(1);
      const uint32_t old = bar_or(4, (dif2(tg[0], tg[1], s) | dif2(tg[2], tg[3], s)) & (s > 0));
      TS(0);
#pragma unroll
      for (int i = 0; i < 2 * NV0; i++) { lds128(b[8 + i], (ma ^ 4096) + i * 512); __syncwarp(); }
      sched();
#pragma unroll
      for (int i = NV0; i < 8; i++) {
        if (VB && i == VB) bar_sync(7, 256);
        mma4(16 + 4 * i, b[2 * i], b[2 * i + 1]);
        if (i < 7) sched();
        if (i < 4) { lds128(b[8 + 2 * i], (ma ^ 4096) + i * 1024); __syncwarp(); lds128(b[9 + 2 * i], (ma ^ 4096) + i * 1024 + 512); sched(); }
      }
      fold();
      asm volatile("{.reg .pred p; setp.eq.u32 p, %3, 0; @p st.relaxed.gpu.global.v2.b32 [%0], {%1,%2};}" :: "l"(adst), "r"((pack2(r4[0], r4[1]) & ~1u) | tag), "r"(pack2(r4[2], r4[3])), "r"(old) : "memory");
      sched();
      const unsigned tpub = clk();
      if (__any_sync(0xffffffffu, old) && nc < NC_MAX) {
        bar_sync(3, 256);
        issue_c(gtime());
        continue;
      }
      TS(3);
      xpos(0, 0);
      const uint32_t due = get_due();
      uint32_t vf[4][4], vm[2][4], p[4], pm, o[4];
      const uint32_t va = sb + R_V + (w4 >> 1) * 8192 + (w4 & 1) * 2048 + L16;
#pragma unroll
      for (int i = 0; i < 4; i++) {
        uint32_t q[4]; lds128(vf[i], va + i * 512); lds128(q, va + 4096 + i * 512);
#pragma unroll
        for (int e = 0; e < 4; e++) vf[i][e] = hadd2(vf[i][e], q[e]);
      }
      const uint32_t pa = pin(sb + R_P + (L16 >> 1));
      const uint8_t* vsrc = pinp(xa + 8192 + w4 * 1024 + L16 / 2);
      uint32_t one[4];
      lds128(one, sb + B_ONE);
      auto pv_x = [&]() {
        zero(c);
        mma_a(c[2], one, p[0], p[1]);
        mma_a(c[0], vf[0], p[0], p[1]); mma_a(c[1], vf[2], p[0], p[1]);
        sched();
        mma_a(c[2], one, p[2], p[3]);
        mma_a(c[0], vf[1], p[2], p[3]); mma_a(c[1], vf[3], p[2], p[3]);
        sched();
      };
      auto pv_m = [&]() {
        mma1688(c[2], one[0], one[1], pm);
        mma_a(c[0], vm[0], pm, pm);
        sched();
        mma_a(c[1], vm[1], pm, pm);
      };
      auto norm = [&]() {
        const float n0 = rcp(c[2][0]), n1 = rcp(c[2][1]);
#pragma unroll
        for (int i = 0; i < 4; i++) o[i] = pack2(c[i >> 1][2 * (i & 1)] * n0, c[i >> 1][2 * (i & 1) + 1] * n1);
        return ((__float_as_uint(c[2][0]) - 0x1F800000u) | (__float_as_uint(c[2][1]) - 0x1F800000u)) >> 30;
      };
      auto load_m = [&](int x) { const float2 e0 = lds64f(pa + 512 + x * 1024), e1 = lds64f(pa + 768 + x * 1024); pm = pack2(e0.x * e1.x, e0.y * e1.y); };
      auto attend_max = [&](int x) {
        float2 sv[6];
#pragma unroll
        for (int i = 0; i < 6; i++) sv[i] = lds64f(pa - 3072 + x * 1536 + i * 256);
        sv[4].x += sv[5].x; sv[4].y += sv[5].y;
        const int dq = (int)(L16 >> 6) - (int)((L16 >> 3) & 6) + 8 * j;
        float m = fmaxf(sv[4].x, sv[4].y);
#pragma unroll
        for (int i = 0; i < 4; i++) {
          if (x && 8 * i > dq) sv[i].x = -INFINITY;
          if (x && 8 * i + 1 > dq) sv[i].y = -INFINITY;
          m = fmaxf(m, fmaxf(sv[i].x, sv[i].y));
        }
        m = fmaxf(m, __shfl_xor_sync(0xffffffffu, m, 1));
        m = fmaxf(m, __shfl_xor_sync(0xffffffffu, m, 2));
#pragma unroll
        for (int i = 0; i < 5; i++) (i < 4 ? p[i] : pm) = pack2(ex2(sv[i].x - m), ex2(sv[i].y - m));
        pv_x(); pv_m(); norm();
      };
      uint32_t tq[4];
      auto get_t = [&]() {
        tq[0] = tq[1] = tq[2] = tq[3] = 0;
        asm volatile("{.reg .pred p; setp.eq.u32 p, %5, 0; @p ld.relaxed.gpu.global.v4.b32 {%0,%1,%2,%3}, [%4];}"
                     : "+r"(tq[0]), "+r"(tq[1]), "+r"(tq[2]), "+r"(tq[3]) : "l"(xb + offsetof(Xchg, T) + L16 * 8), "r"(warp) : "memory");
      };
      delay_until(tpub + DLY_V);
      wait_time(due + NS_V);
      TS(4);
      ldx(vm, vsrc);
      sched();
      xpos(2, 2);
      auto store_kqv = [&]() {
        fence_async();
        if (!(EXP & 4))
          asm volatile("{.reg .pred p; elect.sync _|p, 0xffffffff; @p cp.async.bulk.global.shared::cta.bulk_group [%0], [%1], 2048; cp.async.bulk.commit_group;}"
                       :: "l"(g_kqv[(s + 1) & 3][role] + w4 * 128), "r"(sb + R_STAGE + w4 * 2048) : "memory");
      };
      if (SPOS == 2) store_kqv();
      sched();
      bar_sync(5, 256);
      ldsm4(p, sb + R_P + L16);
      load_m(0);
      pv_x();
      ldsm4(p, sb + R_P + 1024 + L16);
      pv_m();
      const uint32_t r = norm(), tl = after(tag, c[2][0], (uint32_t)it >> 31);
      const bool redo = __any_sync(0xffffffffu, r | ((dif2(vm[0][0], vm[0][2], tl) | dif2(vm[1][0], vm[1][2], tl)) & 1));
      TS(6);
      stsm4t(uW + R_O + L16, o[0], o[1], o[2], o[3]);
      bar_arrive_unless(6, redo);
      sched();
      if (TQL == 7) get_t();
      TS(7);
      pv_x();
      if (rare(redo)) retry<2>(vm, vsrc, tag, it);
      bar_sync(8, 256);
      load_m(1);
      pv_m();
      if (rare(__any_sync(0xffffffffu, norm()) || redo)) {
        fresh();
#pragma unroll 1
        for (int x = !redo; x < 2; x++) {
          attend_max(x);
          if (x == 0) { stsm4t(uW + R_O + L16, o[0], o[1], o[2], o[3]); bar_arrive(6, 256); }
        }
      }
      TS(8);
      if (TQL == 8) get_t();
      const bool xok = mbar_test(sb + B_X + 16, s & 1) & mbar_test(sb + B_X + 24, s & 1);
      xpos(4, 2);
      fresh();
      const uint32_t ob = uni(sb + R_MEM + 4096 + w4 * 1024);
      stsm4t(ob + (L16 & 112) * 4 + (((L16 >> 3) ^ (L16 >> 1)) & 48), o[0], o[1], o[2], o[3]);
      __syncwarp();
      uint32_t rd[4];
      lds128(rd, uW + R_RD + L16);
      lds128(o, ob + (L16 ^ ((L16 >> 3) & 48)));
      auto put_o = [&]() {
        *reinterpret_cast<uint4*>(reinterpret_cast<uint8_t*>(g_ox) + (((s * SEG + 8 * j) * HD + h * DH + 32 * w4) * 2 + (L16 >> 6) * (HD * 2) + (L16 & 48))) = make_uint4(o[0], o[1], o[2], o[3]);
      };
      if (s + 1 == NSEG) { put_o(); asm volatile("cp.async.bulk.wait_group 0;" ::: "memory"); break; }
      asm volatile("cp.async.bulk.wait_group 0;" ::: "memory");
      if (elect()) stx32(xa + 4096 + j * 16 + w4 * 4, s + 1);
      __syncwarp();
      if (rare(!xok)) { wait_x(s + 2, 3); wait_x(s + 2, 2); }
      TS(9);
      fresh();
      const uint32_t e = due | ((s + 1) & 31);
      project_qk(IC<0>{}, IC<NQ>{}, IC<1>{}, [&](int n) {
        if (n == OXPOS) { __syncwarp(); put_o(); __syncwarp(); }
        if (n == TQP) { __syncwarp(); tq[0] = dif2v(tq[0], tq[1], e) | dif2v(tq[2], tq[3], e); __syncwarp(); }
      });
      if (NPA) project_v(IC<0>{}, IC<NPA>{}, [](int) {});
      TS(2);
      if (warp == 0) {
        uint32_t last = due, nx = NS_P;
        if (rare(__any_sync(0xffffffffu, tq[0]))) {
          const uint32_t ref = gtime();
#pragma unroll 1
          do ldx128(o, xb + offsetof(Xchg, T) + L16 * 8); while (any_bit(or3(o[0] - s - 1, o[1] - s - 1, o[2] - s - 1), o[3] - s - 1, 30) && ++it < SPIN_LIMIT);
          const int d = max(max((int)(o[0] - ref), (int)(o[1] - ref)), max((int)(o[2] - ref), (int)(o[3] - ref)));
          last = (ref + __reduce_max_sync(0xffffffffu, d)) & ~31u;
          if (last != due) nx += NS_X;
        }
        const uint32_t bdue = last + NS_B;
        if (s < 4) { last += (MG_Y >> 8 * s & 255) * 32; nx += (MG_Z >> 8 * s & 255) * 32; }
        sts32(sb + B_DUE, last);
        sts32(sb + B_DUE + 8 - tag * 4, last + nx);
        fetch4k(sb + R_MEM, my_b(), sb + B_B, bdue);
        LOG(13, tl - last);
        LOG(9, last);
      }
      if (NQ < 16) project_qk(IC<NQ>{}, IC<16>{}, IC<0>{}, [](int) {});
      project_v(IC<NPA>{}, IC<NPRE>{}, [](int) {});
      const uint32_t ba = rd[2], msk = rd[3];
      const uint8_t* cdst = reinterpret_cast<const uint8_t*>(rd[0] | (uint64_t)rd[1] << 32);
      TS(14);
      mbar_spin(sb + B_B, s & 1, it);
      TS(10);
      uint32_t bq[2][4];
      auto sum_b = [&]() {
        ldsm4t(bq[0], ba); ldsm4t(bq[1], ba + 2048);
        sched();
#pragma unroll
        for (int i = 0; i < 8; i++) c[i >> 2][i & 3] = 0.f;
        mma_a(c[0], bq[0], 0x3F803F80u, 0x3F803F80u); mma_a(c[1], bq[1], 0x3F803F80u, 0x3F803F80u);
        const uint32_t t2 = tag * 0x10001u;
        const bool old = any_bit(or3(dif2(bq[0][0], bq[0][1], t2), dif2(bq[0][2], bq[0][3], t2), dif2(bq[1][0], bq[1][1], t2)), dif2(bq[1][2], bq[1][3], t2), L16 < 64 ? 0x10001u : 0u);
        const uint32_t T = (tag << 16) & ~msk, u = ((__float_as_uint(c[0][0] + c[1][0]) + ((0x10000u & ~msk) - T)) & msk) | T;
        asm volatile("{.reg .pred p; setp.eq.u32 p, %2, 0; @p st.relaxed.gpu.global.b32 [%0], %1;}"
                     :: "l"(cdst), "r"(pack2(__uint_as_float(u), c[0][2] + c[1][2])), "r"((uint32_t)(old || (L16 & 32))) : "memory");
        return old;
      };
      if (rare(sum_b())) {
#pragma unroll 1
        do {
          const uint8_t* p = xb + (my_b() + (ba - sb - R_MEM));
          ldx128(bq[0], p); ldx128(bq[1], p + 2048);
          sts128(ba, bq[0]); sts128(ba + 2048, bq[1]);
          __syncwarp();
          it += INC_B;
        } while (sum_b() && it < SPIN_LIMIT);
      }
      sched();
      TS(11);
      bar_arrive(0, 256);
      const unsigned tc = clk();
      const uint32_t cdue = lds32(sb + B_DUE) + NS_C;
      if (warp == 3) LOG(11, gtime() - cdue);
      fresh();
      wg_wait<0>(); keep(aq); keep(av);
      park();
      if (NPRE < 32) project_v(IC<NPRE>{}, IC<32>{}, [](int) {}); else fin_v();
      TS(12);
      delay_until(tc + DLY_C);
      issue_c(cdue);
      TS(5);
      LOG(warp, it);
      pin_mem();
      if (NPRE < 32) { wg_wait<0>(); keep(av); fin_v(); }
      if (!(EXP & 2)) mbar_spin(sb + B_KV, tag, it);
      TS(15);
    } else {
      uint32_t kf[8][4];
      auto load_k = [&]() {
        const uint32_t ka = sb + R_K + w4 * 1024 + (L16 & 112) + (L16 & 128) * 4 + (L16 & 256);
#pragma unroll
        for (int i = 0; i < 8; i++) ldsm4(kf[i], ka + (i >> 1) * 2048 + (i & 1) * 128);
      };
      auto put_p = [&](int x, uint32_t old, uint32_t again) {
        float e[4];
        const int dq = (int)((L16 >> 3) & 6) + 8 * j - (int)(L16 >> 6) - 16 * w4;
#pragma unroll
        for (int i = 0; i < 4; i++) { r4[i] = fmaf(c[3][i], sc, fmaf(c[2][i], sc, fmaf(c[0][i] + c[1][i], sc, __uint_as_float(i == 3 ? 0u - old : 0u)))); e[i] = x && dq + (i & 1) < 8 * (i >> 1) ? 0.f : ex2(r4[i]); }
        stsm2t(uP2 + x * 1024 + L16, pack2(e[0], e[1]), pack2(e[2], e[3]), again);
      };
      auto put_s = [&](int x) {
#pragma unroll
        for (int i = 0; i < 4; i++) sts32f(uW + R_S + x * 1536 + (L16 & 48) * 4 + (L16 >> 6) * 4 + (i & 1) * 32 + (i >> 1) * 256, r4[i]);
      };
      auto load_q = [&](uint32_t (&q)[4], uint32_t off) { ldsm4(q, sb + R_Q + (L16 & 112) + (L16 & 128) * 2 + (L16 >> 8) * 128 + off); };
      mbar_spin(sb + B_C, nc & 1, it);
      TS(13);
      float4 o4;
      uint32_t id[4], old;
      {
        uint32_t b[24][4];
#pragma unroll
        for (int i = 0; i < 2 * PD1; i++) { lds128(b[i], ma + i * 512); __syncwarp(); }
        sched();
        zero(c);
#pragma unroll
        for (int i = 0; i < 12; i++) {
          mma4(4 * i, b[2 * i], b[2 * i + 1]);
          if (i < 11) sched();
          if (i + PD1 < 12) { const int k = i + PD1; const uint32_t a = (ma ^ (k >> 2 << 12)) + (k & 3) * 1024; lds128(b[2 * k], a); __syncwarp(); lds128(b[2 * k + 1], a + 512); sched(); }
          if (i == RJ) { lds128(id, sb + R_ID + L16); sched(); }
          if (i == RI) { old = bar_or(4, 0); o4 = lds128f(uW + R_RED + L16); sched(); }
        }
      }
      TS(0);
      {
        float e[4] = {o4.x, o4.y, o4.z, o4.w};
#pragma unroll
        for (int i = 0; i < 4; i++) { r4[i] = (((e[i] + c[0][i]) + c[1][i]) + c[2][i]) + c[3][i]; e[i] = 0.f; }
        mma_a(e, id, pack2(r4[0], r4[1]), pack2(r4[2], r4[3]));
        sched();
        if (VB) bar_arrive(7, 256);
        sched();
        asm volatile("{.reg .pred p; setp.eq.u32 p, %3, 0; @p st.relaxed.gpu.global.v2.b32 [%0], {%1,%2};}" :: "l"(adst),
                     "r"((__byte_perm(__float_as_uint(e[0]), __float_as_uint(e[1]), 0x7632) & ~1u) | tag), "r"(__byte_perm(__float_as_uint(e[2]), __float_as_uint(e[3]), 0x7632)), "r"(old) : "memory");
        sched();
      }
      const unsigned tpub = clk(), now = gtime(), due = get_due();
      if (__any_sync(0xffffffffu, old) && nc < NC_MAX) { bar_sync(3, 256); continue; }
      TS(2);
      const uint8_t* asrc = pinp(adst + ((warp == 7) * 1024 - (int)uA));
      fresh();
      uint32_t wo[32][4];
      bool xok;
      auto reload = [&]() {
        sched();
#pragma unroll
        for (int i = RE0 + RE1; i < NSW; i++) lds128(w[i], uW + R_WC + L16 + i * 2048);
        sched();
      };
      auto out_proj = [&]() {
        uint32_t b[4][4];
        float d[4][4];
        uint8_t* dst[2];
        const uint32_t da = pin(uP2 + (R_DST - R_P) + L16 / 2);
        sched();
        TS(7);
        bar_sync(6, 256);
#pragma unroll
        for (int i = 0; i < 4; i++) { ldsm4(b[i], sb + R_O + i * 512 + L16); __syncwarp(); }
        sched();
        auto put_b = [&](uint8_t* a, const float (&e)[4][4]) {
          stx128(a, (pack2(e[0][0] + e[2][0], e[0][1] + e[2][1]) & ~1u) | tag, pack2(e[0][2] + e[2][2], e[0][3] + e[2][3]),
                 pack2(e[1][0] + e[3][0], e[1][1] + e[3][1]), pack2(e[1][2] + e[3][2], e[1][3] + e[3][3]));
        };
        zero(c); zero(d);
#pragma unroll
        for (int i = 0; i < 32; i++) {
          mma_h(i < 16 ? c[i & 3] : d[i & 3], wo[i], b[(i >> 2) & 3], (i >> 1) & 1);
          if (i >= LW0 && NB1 + i - LW0 < 32) { load_wo(wo, (NB1 + i - LW0) ^ 1, ((NB1 + i - LW0) ^ 1) + 1); __syncwarp(); }
          if (i == DL0 || i == DL1) asm volatile("ld.shared.u64 %0, [%1];" : "=l"(dst[i > DL0]) : "r"(da + (i > DL0) * 1024) : "memory");
          if (i >= 16 && i < 16 + RE0) { lds128(w[i - 16], uW + R_WC + L16 + (i - 16) * 2048); __syncwarp(); }
          if (i >= RP1 && i < RP1 + RE1) { lds128(w[i - RP1 + RE0], uW + R_WC + L16 + (i - RP1 + RE0) * 2048); __syncwarp(); }
          if (i == 22) put_b(dst[0], c);
          if ((i & 1) && (i < 20 || i > 22)) sched();
        }
        put_b(dst[1], d);
        sched();
        TS(6);
      };
      if (warp < 6) {
        delay_until(tpub + DLY_A);
        const int it0 = it;
        bool redo;
#pragma unroll 1
        do {
          uint32_t q[4][4], y[4];
          float d[4][4];
          wait_time(due);
          TS(4);
          ldx(q, asrc);
          sched();
          load_k();
          uint32_t qx[4][4];
#pragma unroll
          for (int i = 0; i < 4; i++) load_q(qx[i], i * 512);
          sched();
          load_wo(wo, 0, NE4);
          sched();
          zero(c);
#pragma unroll
          for (int i = 0; i < 8; i++) mma_h(c[i & 3], kf[i], qx[i >> 1], i & 1);
          put_p(1, 0, 0); put_s(1);
          sched();
          load_wo(wo, NE4, NA4);
          sched();
          zero(c); zero(d);
#pragma unroll
          for (int i = 0; i < 8; i++) {
            if (i == 0) { y[0] = dif2v(q[0][0], q[0][2], q[1][0]); sched(); }
            if (i == 3) { y[1] = dif2v(q[1][2], q[2][0], q[2][2]); sched(); }
            if (i == 6) { y[2] = dif2v(q[3][0], q[3][2], tag); sched(); }
            mma_h(i % 6 < 2 ? c[2 + i % 6] : d[i - 2], kf[i], q[i >> 1], i & 1);
            if (i == 2 || i == 5 || i == 7) sched();
          }
          y[0] = or_and(or3(y[0], y[1], dif2v(q[0][0], q[2][0], tag)), y[2], it < SPIN_LIMIT);
#pragma unroll
          for (int i = 0; i < 4; i++) { c[0][i] = d[0][i] + d[1][i]; c[1][i] = d[2][i] + d[3][i]; }
          put_p(0, y[0], it - it0);
          TS(5);
          bar_sync_unless(5, it - it0);
          redo = __any_sync(0xffffffffu, y[0]);
          it += INC_A;
        } while (redo);
        it -= INC_A;
        put_s(0);
        bar_arrive(8, 256);
        load_wo(wo, NA4, NB1);
        out_proj();
        if (warp == 4) LOG(12, tb);
      } else {
        uint32_t qx[2][4], q[4][4];
        if (warp == 6) {
          const uint32_t t1 = (now & ~31u) + NS_M;
          LOG(10, now - due);
          if (elect()) stx32(&gx->T[h][j], ((int)(t1 - due) > 0 ? t1 + NS_PEN : due) | ((s + 1) & 31));
          __syncwarp();
        }
        auto score = [&](const uint32_t (&a0)[4], const uint32_t (&a1)[4]) {
          zero(c);
#pragma unroll
          for (int i = 0; i < 4; i++) mma_h(c[i], i < 2 ? a0 : a1, q[2 + (i >> 1)], i & 1);
        };
        auto put_m = [&](uint32_t a, uint32_t old, uint32_t again) {
#pragma unroll
          for (int i = 0; i < 2; i++) { r4[i] = fmaf(c[3][2 + i], sc, fmaf((c[0][i] + c[1][2 + i]) + c[2][i], sc, __uint_as_float(i ? 0u - old : 0u))); r4[2 + i] = fmaf(r4[i] * 0x1p122f, 0.f, ex2(r4[i])); }
          asm volatile("{.reg .pred p; setp.eq.u32 p, %3, 0; @p st.shared.v2.f32 [%0], {%1,%2};}" :: "r"(a), "f"(r4[2]), "f"(r4[3]), "r"(again) : "memory");
        };
        delay_until(tpub + DLY_A);
        const uint32_t sa = sb + R_S + 512 + w4 * 256 + (L16 >> 1);
        const int it0 = it;
        bool redo;
#pragma unroll 1
        do {
          wait_time(due);
          TS(4);
          ldx<4, 2048>(q, asrc);
          sched();
          load_q(qx[0], (w4 & 1) * 1024); load_q(qx[1], (w4 & 1) * 1024 + 512);
          load_wo(wo, 0, NA6);
          sched();
          score(q[0], q[1]);
          sched();
          const uint32_t y = or_and(or3(dif2v(q[0][0], q[0][2], tag), dif2v(q[1][0], q[1][2], tag), dif2v(q[2][0], q[2][2], tag)), dif2v(q[3][0], q[3][2], tag), it < SPIN_LIMIT);
          put_m(sa + 2560, y, it - it0);
          TS(5);
          bar_arrive_unless(5, it - it0);
          redo = __any_sync(0xffffffffu, y);
          it += INC_A;
        } while (redo);
        it -= INC_A;
        sts64f(sa, r4[0], r4[1]);
        score(qx[0], qx[1]);
        put_m(sa + 3584, 0, 0);
        sts64f(sa + 1536, r4[0], r4[1]);
        bar_arrive(8, 256);
        load_wo(wo, NA6, NB1);
        out_proj();
      }
      TS(8);
      if (s + 1 == NSEG) break;
      wait_x(s + 2, 2);
      TS(9);
      fresh();
      if (N1) project_qk(IC<32>{}, IC<32 + N1>{}, IC<1>{}, [](int) {});
      TS(10);
      xpos(6, 6);
      uint32_t fl = s + 1;
      if (warp == 5) { wait_time(due + NS_F); fl = ldx32(xa + 4096 + ((L16 >> 2) & 60)); }
      reload();
      TS(14);
      pin_mem();
      wait_x(s + 2, 1); wait_x(s + 2, 0);
      if (warp == 5) {
#pragma unroll 1
        while (__any_sync(0xffffffffu, fl != s + 1) && !(EXP & 4) && ++it < SPIN_LIMIT) fl = ldx32(xa + 4096 + ((L16 >> 2) & 60));
        wait_time(due + (NS_B + NS_K));
        if (!(EXP & 2) && elect()) issue_kqv(s + 1);
        __syncwarp();
      }
      if (PFD && warp == 6 && s + PFD < NSEG && elect())
        asm volatile("cp.async.bulk.prefetch.L2.global [%0], 2048;" :: "l"(xin + ((s + PFD) * SEG + ((role + 4 * (role >> 5)) & 31)) * DM) : "memory");
      __syncwarp();
      TS(11);
      LOG(warp, it);
      if (warp == 4) LOG(8, nc);
      bar_sync(0, 256);
      if (N1 < 16) project_qk(IC<32 + N1>{}, IC<48>{}, IC<!N1>{}, [](int) {});
      project_qk(IC<16>{}, IC<32>{}, IC<0>{}, [&](int n) { if ((n & 15) == XWPOS) { __syncwarp(); xok = mbar_test(sb + B_PK, s & 1); __syncwarp(); } });
      if (rare(!xok)) mbar_spin(sb + B_PK, s & 1, it);
      unpark();
      project_qk(IC<0>{}, IC<16>{}, IC<0>{}, [](int) {});
      TS(12);
      wg_wait<0>(); keep(aq);
      TS(1);
      fin_qk();
      TS(15);
    }
    s++;
  }
  if (it >= SPIN_LIMIT || nc >= NC_MAX) g_err = 2;
}

typedef CUresult (*EncodeFn)(CUtensorMap*, CUtensorMapDataType, cuuint32_t, void*, const cuuint64_t*, const cuuint64_t*, const cuuint32_t*,
                             const cuuint32_t*, CUtensorMapInterleave, CUtensorMapSwizzle, CUtensorMapL2promotion, CUtensorMapFloatOOBfill);
static void make_map(EncodeFn fn, CUtensorMap* m, const void* p, uint64_t cols, uint64_t rows, uint64_t pitch, uint32_t bc, uint32_t br, CUtensorMapSwizzle sw) {
  cuuint64_t dims[2] = {cols, rows}, strides[1] = {pitch * 2};
  cuuint32_t box[2] = {bc, br}, es[2] = {1, 1};
  fn(m, CU_TENSOR_MAP_DATA_TYPE_BFLOAT16, 2, const_cast<void*>(p), dims, strides, box, es, CU_TENSOR_MAP_INTERLEAVE_NONE, sw,
     CU_TENSOR_MAP_L2_PROMOTION_L2_256B, CU_TENSOR_MAP_FLOAT_OOB_FILL_NONE);
}

extern "C" void kernel_launch(void* const* d_in, const int* in_sizes, int n_in, void* d_out, int out_size) {
  const bf16* Ax = (const bf16*)d_in[0]; const bf16* mem0 = (const bf16*)d_in[1];
  const bf16* Wq = (const bf16*)d_in[2]; const bf16* Wk = (const bf16*)d_in[3]; const bf16* Wv = (const bf16*)d_in[4];
  const bf16* Wo = (const bf16*)d_in[5];
  const bf16* Bx = (const bf16*)d_in[7]; const bf16* wr = (const bf16*)d_in[8]; const bf16* wi = (const bf16*)d_in[9];
  bf16* out = (bf16*)d_out;

  void* fp = nullptr; cudaDriverEntryPointQueryResult qr;
  cudaGetDriverEntryPoint("cuTensorMapEncodeTiled", &fp, cudaEnableDefault, &qr);
  EncodeFn fn = (EncodeFn)fp;
  void *kqv, *ox, *xr;
  cudaGetSymbolAddress(&xr, g_xraw);
  cudaGetSymbolAddress(&kqv, g_kqv); cudaGetSymbolAddress(&ox, g_ox);
  const CUtensorMapSwizzle S128 = CU_TENSOR_MAP_SWIZZLE_128B, S64 = CU_TENSOR_MAP_SWIZZLE_64B;

  GemmMaps m3; RecMaps mr;
  make_map(fn, &m3.a, ox, HD, S_LEN, HD, 64, 128, S128);
  make_map(fn, &m3.b[0], Wo, DM, HD, DM, 64, 64, S128);
  m3.b[1] = m3.b[0]; m3.b[2] = m3.b[0];
  make_map(fn, &m3.c, out, DM, S_LEN, 2 * DM, 64, 64, S128);
  make_map(fn, &mr.wq, Wq, HD, DM, HD, 32, 256, S64);
  make_map(fn, &mr.wk, Wk, HD, DM, HD, 32, 256, S64);
  make_map(fn, &mr.wv, Wv, HD, DM, HD, 64, 256, S128);
  make_map(fn, &mr.wo, Wo, DM, HD, DM, 64, 128, S128);
  {
    cuuint64_t dims[3] = {64, S_LEN, 16}, strides[2] = {DM * 2, 128};
    cuuint32_t box[3] = {64, 32, 4}, es[3] = {1, 1, 1};
    fn(&mr.x, CU_TENSOR_MAP_DATA_TYPE_BFLOAT16, 3, const_cast<bf16*>(Ax), dims, strides, box, es, CU_TENSOR_MAP_INTERLEAVE_NONE, S128,
       CU_TENSOR_MAP_L2_PROMOTION_L2_256B, CU_TENSOR_MAP_FLOAT_OOB_FILL_NONE);
  }
  for (int i = 0; i < 3; i++) {
    cuuint64_t dims[3] = {128, 32, 512}, strides[2] = {256, 8192};
    cuuint32_t box[3] = {128, i == 0 ? 8u : i == 1 ? 2u : 16u, 4}, es[3] = {1, 1, 1};
    fn(i == 0 ? &mr.k : i == 1 ? &mr.q : &mr.v, CU_TENSOR_MAP_DATA_TYPE_BFLOAT16, 3, kqv, dims, strides, box, es, CU_TENSOR_MAP_INTERLEAVE_NONE,
       CU_TENSOR_MAP_SWIZZLE_NONE, CU_TENSOR_MAP_L2_PROMOTION_L2_256B, CU_TENSOR_MAP_FLOAT_OOB_FILL_NONE);
  }
  {
    cuuint64_t dims[3] = {64, 16, S_LEN}, strides[2] = {128, 2 * DM * 2};
    cuuint32_t box[3] = {64, 16, 2}, es[3] = {1, 1, 1};
    fn(&mr.fo, CU_TENSOR_MAP_DATA_TYPE_BFLOAT16, 3, out + DM, dims, strides, box, es, CU_TENSOR_MAP_INTERLEAVE_NONE, S128,
       CU_TENSOR_MAP_L2_PROMOTION_NONE, CU_TENSOR_MAP_FLOAT_OOB_FILL_NONE);
  }
  constexpr int SM3 = 6 * 32768 + 32768 + 256 + 1024;
  cudaFuncSetAttribute(gemm_kernel<128, 6>, cudaFuncAttributeMaxDynamicSharedMemorySize, SM3);
  cudaFuncSetAttribute(rec_kernel, cudaFuncAttributeMaxDynamicSharedMemorySize, R_TOTAL);

  cudaStream_t st = cudaStreamPerThread;
  Xchg* gx = reinterpret_cast<Xchg*>((reinterpret_cast<uintptr_t>(xr) + 0x1FFFFF) & ~(uintptr_t)0x1FFFFF);
  rec_kernel<<<132, 256, R_TOTAL, st>>>(mr, Ax, mem0, gx, Bx, wr, wi);
  gemm_kernel<128, 6><<<128, 384, SM3, st>>>(m3, 16, 8, 64, 8, reinterpret_cast<uint4*>(gx));
}
```

```cpp
#include <cuda_runtime.h>
#include <cuda_bf16.h>
#include <cuda.h>
#include <stdint.h>
#include <stddef.h>
#include <type_traits>

typedef __nv_bfloat16 bf16;

constexpr int S_LEN = 2048, DM = 1024, NH = 32, DH = 128, MEM = 8, SEG = 32, NSEG = 64;
constexpr int HD = NH * DH;
#define SPIN 20
constexpr int SPIN_LIMIT = 1 << SPIN, INC_A = 1, INC_B = 1;

constexpr unsigned NC_MAX = 4096;
__device__ __align__(1024) uint4 g_kqv[4][128][512];
__device__ __align__(1024) bf16 g_ox[(size_t)S_LEN * HD];
struct Xchg {
  uint4 A[32][4][256];
  uint4 C[4][2][256];
  uint4 B[128][2][256];
  uint32_t T[32][32];
  uint32_t S[128];
  unsigned ctr[64];
};
__device__ __align__(1024) uint4 g_xraw[(sizeof(Xchg) + (1 << 21)) / 16];
__device__ __align__(1024) uint4 g_y[1024 * 256];
__device__ __align__(1024) uint4 g_wt[513 * 512];
__device__ int g_err;

__device__ __forceinline__ unsigned clk() { unsigned long long c; asm volatile("mov.u64 %0, %%clock64;" : "=l"(c)); return (unsigned)c; }
__device__ __forceinline__ uint32_t smem_u32(const void* p) { return (uint32_t)__cvta_generic_to_shared(p); }
__device__ __forceinline__ void mbar_init(uint32_t bar, int cnt) { asm volatile("mbarrier.init.shared::cta.b64 [%0], %1;" :: "r"(bar), "r"(cnt) : "memory"); }
__device__ __forceinline__ void mbar_expect_tx(uint32_t bar, int bytes) { asm volatile("mbarrier.arrive.expect_tx.shared::cta.b64 _, [%0], %1;" :: "r"(bar), "r"(bytes) : "memory"); }
__device__ __forceinline__ void mbar_arrive(uint32_t bar) { asm volatile("mbarrier.arrive.shared::cta.b64 _, [%0];" :: "r"(bar) : "memory"); }
__device__ __forceinline__ void mbar_arrive_cluster(uint32_t bar, int cta) {
  asm volatile("{.reg .b32 r; mapa.shared::cluster.u32 r, %0, %1; mbarrier.arrive.shared::cluster.b64 _, [r];}" :: "r"(bar), "r"(cta) : "memory"); }
__device__ __forceinline__ bool mbar_try(uint32_t bar, int par) {
  uint32_t ok; asm volatile("{.reg .pred p; mbarrier.try_wait.parity.shared::cta.b64 p, [%1], %2; selp.u32 %0, 1, 0, p;}" : "=r"(ok) : "r"(bar), "r"(par) : "memory"); return ok; }
__device__ __forceinline__ bool mbar_test(uint32_t bar, int par) {
  uint32_t ok; asm volatile("{.reg .pred p; mbarrier.test_wait.parity.shared::cta.b64 p, [%1], %2; selp.u32 %0, 1, 0, p;}" : "=r"(ok) : "r"(bar), "r"(par) : "memory"); return ok; }
__device__ __forceinline__ void mbar_wait(uint32_t bar, int par) {
  int it = 0;
  while (!mbar_try(bar, par)) { if (++it > SPIN_LIMIT) { g_err = 1; break; } }
}
__device__ __forceinline__ void tma2d(uint32_t dst, const CUtensorMap* m, int c0, int c1, uint32_t bar) {
  asm volatile("cp.async.bulk.tensor.2d.shared::cluster.global.mbarrier::complete_tx::bytes [%0], [%1, {%3, %4}], [%2];"
    :: "r"(dst), "l"(m), "r"(bar), "r"(c0), "r"(c1) : "memory"); }
__device__ __forceinline__ void tma2d_mc(uint32_t dst, const CUtensorMap* m, int c0, int c1, uint32_t bar, uint16_t mask) {
  asm volatile("cp.async.bulk.tensor.2d.shared::cluster.global.mbarrier::complete_tx::bytes.multicast::cluster [%0], [%1, {%3, %4}], [%2], %5;"
    :: "r"(dst), "l"(m), "r"(bar), "r"(c0), "r"(c1), "h"(mask) : "memory"); }
__device__ __forceinline__ void tma2d_store(const CUtensorMap* m, uint32_t src, int c0, int c1) {
  asm volatile("cp.async.bulk.tensor.2d.global.shared::cta.bulk_group [%0, {%2, %3}], [%1];" :: "l"(m), "r"(src), "r"(c0), "r"(c1) : "memory"); }
__device__ __forceinline__ void fence_async() { asm volatile("fence.proxy.async.shared::cta;" ::: "memory"); }
__device__ __forceinline__ void bar_sync(int id, int n) { asm volatile("bar.sync %0, %1;" :: "r"(id), "r"(n) : "memory"); }
__device__ __forceinline__ void bar_arrive(int id, int n) { asm volatile("bar.arrive %0, %1;" :: "r"(id), "r"(n) : "memory"); }
__device__ __forceinline__ uint32_t pack2(float lo, float hi) { uint32_t r; asm("cvt.rn.bf16x2.f32 %0, %1, %2;" : "=r"(r) : "f"(hi), "f"(lo)); return r; }
__device__ __forceinline__ uint32_t pack2_tag(float lo, float hi, uint32_t T) {
  uint32_t u = ((__float_as_uint(lo) - T + 0x10000u) & 0xFFFE0000u) + T;
  return __byte_perm(u, pack2(0.f, hi), 0x7632); }
__device__ __forceinline__ void ldsm4(uint32_t (&r)[4], uint32_t a) {
  asm volatile("ldmatrix.sync.aligned.m8n8.x4.shared.b16 {%0,%1,%2,%3}, [%4];" : "=r"(r[0]), "=r"(r[1]), "=r"(r[2]), "=r"(r[3]) : "r"(a) : "memory"); }
__device__ __forceinline__ void ldsm4t(uint32_t (&r)[4], uint32_t a) {
  asm volatile("ldmatrix.sync.aligned.m8n8.x4.trans.shared.b16 {%0,%1,%2,%3}, [%4];" : "=r"(r[0]), "=r"(r[1]), "=r"(r[2]), "=r"(r[3]) : "r"(a) : "memory"); }
__device__ __forceinline__ void stsm4(uint32_t a, uint32_t r0, uint32_t r1, uint32_t r2, uint32_t r3) {
  asm volatile("stmatrix.sync.aligned.m8n8.x4.shared.b16 [%0], {%1,%2,%3,%4};" :: "r"(a), "r"(r0), "r"(r1), "r"(r2), "r"(r3) : "memory"); }
__device__ __forceinline__ void stsm4t(uint32_t a, uint32_t r0, uint32_t r1, uint32_t r2, uint32_t r3) {
  asm volatile("stmatrix.sync.aligned.m8n8.x4.trans.shared.b16 [%0], {%1,%2,%3,%4};" :: "r"(a), "r"(r0), "r"(r1), "r"(r2), "r"(r3) : "memory"); }
__device__ __forceinline__ void lds128(uint32_t (&r)[4], uint32_t a) {
  asm volatile("ld.shared.v4.u32 {%0,%1,%2,%3}, [%4];" : "=r"(r[0]), "=r"(r[1]), "=r"(r[2]), "=r"(r[3]) : "r"(a) : "memory"); }
__device__ __forceinline__ float4 lds128f(uint32_t a) { float4 r;
  asm volatile("ld.shared.v4.f32 {%0,%1,%2,%3}, [%4];" : "=f"(r.x), "=f"(r.y), "=f"(r.z), "=f"(r.w) : "r"(a) : "memory"); return r; }
__device__ __forceinline__ float2 lds64f(uint32_t a) { float2 r;
  asm volatile("ld.shared.v2.f32 {%0,%1}, [%2];" : "=f"(r.x), "=f"(r.y) : "r"(a) : "memory"); return r; }
__device__ __forceinline__ void sts128(uint32_t a, uint32_t r0, uint32_t r1, uint32_t r2, uint32_t r3) {
  asm volatile("st.shared.v4.u32 [%0], {%1,%2,%3,%4};" :: "r"(a), "r"(r0), "r"(r1), "r"(r2), "r"(r3) : "memory"); }
__device__ __forceinline__ void sts64f(uint32_t a, float x, float y) { asm volatile("st.shared.v2.f32 [%0], {%1,%2};" :: "r"(a), "f"(x), "f"(y) : "memory"); }
__device__ __forceinline__ void sts32f(uint32_t a, float x) { asm volatile("st.shared.f32 [%0], %1;" :: "r"(a), "f"(x) : "memory"); }
__device__ __forceinline__ void mma16816(float (&d)[4], uint32_t a0, uint32_t a1, uint32_t a2, uint32_t a3, uint32_t b0, uint32_t b1) {
  asm volatile("mma.sync.aligned.m16n8k16.row.col.f32.bf16.bf16.f32 {%0,%1,%2,%3}, {%4,%5,%6,%7}, {%8,%9}, {%0,%1,%2,%3};"
    : "+f"(d[0]), "+f"(d[1]), "+f"(d[2]), "+f"(d[3]) : "r"(a0), "r"(a1), "r"(a2), "r"(a3), "r"(b0), "r"(b1)); }
__device__ __forceinline__ void mma1688(float (&d)[4], uint32_t a0, uint32_t a1, uint32_t b0) {
  asm volatile("mma.sync.aligned.m16n8k8.row.col.f32.bf16.bf16.f32 {%0,%1,%2,%3}, {%4,%5}, {%6}, {%0,%1,%2,%3};"
    : "+f"(d[0]), "+f"(d[1]), "+f"(d[2]), "+f"(d[3]) : "r"(a0), "r"(a1), "r"(b0)); }
__device__ __forceinline__ void ldx128(uint32_t (&r)[4], const void* p) {
  asm volatile("{.reg .b128 t; .reg .b64 a, b; ld.relaxed.gpu.global.b128 t, [%4]; mov.b128 {a, b}, t; mov.b64 {%0,%1}, a; mov.b64 {%2,%3}, b;}"
    : "=r"(r[0]), "=r"(r[1]), "=r"(r[2]), "=r"(r[3]) : "l"(p) : "memory"); }
__device__ __forceinline__ void ldx2x64(uint32_t (&r)[4], const void* p) {
  asm volatile("{.reg .b64 a, b; ld.relaxed.gpu.global.v2.b64 {a, b}, [%4]; mov.b64 {%0,%1}, a; mov.b64 {%2,%3}, b;}"
    : "=r"(r[0]), "=r"(r[1]), "=r"(r[2]), "=r"(r[3]) : "l"(p) : "memory"); }
__device__ __forceinline__ void stx128(void* p, uint32_t r0, uint32_t r1, uint32_t r2, uint32_t r3) {
  asm volatile("{.reg .b128 t; .reg .b64 a, b; mov.b64 a, {%1,%2}; mov.b64 b, {%3,%4}; mov.b128 t, {a, b}; st.relaxed.gpu.global.b128 [%0], t;}"
    :: "l"(p), "r"(r0), "r"(r1), "r"(r2), "r"(r3) : "memory"); }
__device__ __forceinline__ void stx64(void* p, uint32_t r0, uint32_t r1) {
  asm volatile("{.reg .b64 a; mov.b64 a, {%1,%2}; st.relaxed.gpu.global.b64 [%0], a;}" :: "l"(p), "r"(r0), "r"(r1) : "memory"); }
__device__ __forceinline__ uint32_t uni(uint32_t x) { return __shfl_sync(0xffffffffu, x, 0); }
__device__ __forceinline__ uint32_t pin(uint32_t x) { return __shfl_xor_sync(0xffffffffu, x, 0); }
__device__ __forceinline__ float ex2(float x) { float r; asm("ex2.approx.ftz.f32 %0, %1;" : "=f"(r) : "f"(x)); return r; }
__device__ __forceinline__ void wg_fence() { asm volatile("wgmma.fence.sync.aligned;" ::: "memory"); }
__device__ __forceinline__ void wg_commit() { asm volatile("wgmma.commit_group.sync.aligned;" ::: "memory"); }
template <int N> __device__ __forceinline__ void wg_wait() { asm volatile("wgmma.wait_group.sync.aligned %0;" :: "n"(N) : "memory"); }

__device__ __forceinline__ void wgmma_ss_n256_tb1(float (&d)[128], uint64_t da, uint64_t db, int sc) {
  asm volatile("{.reg .pred p; setp.ne.b32 p, %130, 0;\n"
    "wgmma.mma_async.sync.aligned.m64n256k16.f32.bf16.bf16 {%0,%1,%2,%3,%4,%5,%6,%7,%8,%9,%10,%11,%12,%13,%14,%15,%16,%17,%18,%19,%20,%21,%22,%23,%24,%25,%26,%27,%28,%29,%30,%31,%32,%33,%34,%35,%36,%37,%38,%39,%40,%41,%42,%43,%44,%45,%46,%47,%48,%49,%50,%51,%52,%53,%54,%55,%56,%57,%58,%59,%60,%61,%62,%63,%64,%65,%66,%67,%68,%69,%70,%71,%72,%73,%74,%75,%76,%77,%78,%79,%80,%81,%82,%83,%84,%85,%86,%87,%88,%89,%90,%91,%92,%93,%94,%95,%96,%97,%98,%99,%100,%101,%102,%103,%104,%105,%106,%107,%108,%109,%110,%111,%112,%113,%114,%115,%116,%117,%118,%119,%120,%121,%122,%123,%124,%125,%126,%127}, %128, %129, p, 1, 1, 0, 1;}\n"
    : "+f"(d[0]),"+f"(d[1]),"+f"(d[2]),"+f"(d[3]),"+f"(d[4]),"+f"(d[5]),"+f"(d[6]),"+f"(d[7]),"+f"(d[8]),"+f"(d[9]),"+f"(d[10]),"+f"(d[11]),"+f"(d[12]),"+f"(d[13]),"+f"(d[14]),"+f"(d[15]),"+f"(d[16]),"+f"(d[17]),"+f"(d[18]),"+f"(d[19]),"+f"(d[20]),"+f"(d[21]),"+f"(d[22]),"+f"(d[23]),"+f"(d[24]),"+f"(d[25]),"+f"(d[26]),"+f"(d[27]),"+f"(d[28]),"+f"(d[29]),"+f"(d[30]),"+f"(d[31]),"+f"(d[32]),"+f"(d[33]),"+f"(d[34]),"+f"(d[35]),"+f"(d[36]),"+f"(d[37]),"+f"(d[38]),"+f"(d[39]),"+f"(d[40]),"+f"(d[41]),"+f"(d[42]),"+f"(d[43]),"+f"(d[44]),"+f"(d[45]),"+f"(d[46]),"+f"(d[47]),"+f"(d[48]),"+f"(d[49]),"+f"(d[50]),"+f"(d[51]),"+f"(d[52]),"+f"(d[53]),"+f"(d[54]),"+f"(d[55]),"+f"(d[56]),"+f"(d[57]),"+f"(d[58]),"+f"(d[59]),"+f"(d[60]),"+f"(d[61]),"+f"(d[62]),"+f"(d[63]),"+f"(d[64]),"+f"(d[65]),"+f"(d[66]),"+f"(d[67]),"+f"(d[68]),"+f"(d[69]),"+f"(d[70]),"+f"(d[71]),"+f"(d[72]),"+f"(d[73]),"+f"(d[74]),"+f"(d[75]),"+f"(d[76]),"+f"(d[77]),"+f"(d[78]),"+f"(d[79]),"+f"(d[80]),"+f"(d[81]),"+f"(d[82]),"+f"(d[83]),"+f"(d[84]),"+f"(d[85]),"+f"(d[86]),"+f"(d[87]),"+f"(d[88]),"+f"(d[89]),"+f"(d[90]),"+f"(d[91]),"+f"(d[92]),"+f"(d[93]),"+f"(d[94]),"+f"(d[95]),"+f"(d[96]),"+f"(d[97]),"+f"(d[98]),"+f"(d[99]),"+f"(d[100]),"+f"(d[101]),"+f"(d[102]),"+f"(d[103]),"+f"(d[104]),"+f"(d[105]),"+f"(d[106]),"+f"(d[107]),"+f"(d[108]),"+f"(d[109]),"+f"(d[110]),"+f"(d[111]),"+f"(d[112]),"+f"(d[113]),"+f"(d[114]),"+f"(d[115]),"+f"(d[116]),"+f"(d[117]),"+f"(d[118]),"+f"(d[119]),"+f"(d[120]),"+f"(d[121]),"+f"(d[122]),"+f"(d[123]),"+f"(d[124]),"+f"(d[125]),"+f"(d[126]),"+f"(d[127])
    : "l"(da), "l"(db), "r"(sc));
}

__device__ __forceinline__ void wgmma_ss_n128_tb1(float (&d)[64], uint64_t da, uint64_t db, int sc) {
  asm volatile("{.reg .pred p; setp.ne.b32 p, %66, 0;\n"
    "wgmma.mma_async.sync.aligned.m64n128k16.f32.bf16.bf16 {%0,%1,%2,%3,%4,%5,%6,%7,%8,%9,%10,%11,%12,%13,%14,%15,%16,%17,%18,%19,%20,%21,%22,%23,%24,%25,%26,%27,%28,%29,%30,%31,%32,%33,%34,%35,%36,%37,%38,%39,%40,%41,%42,%43,%44,%45,%46,%47,%48,%49,%50,%51,%52,%53,%54,%55,%56,%57,%58,%59,%60,%61,%62,%63}, %64, %65, p, 1, 1, 0, 1;}\n"
    : "+f"(d[0]),"+f"(d[1]),"+f"(d[2]),"+f"(d[3]),"+f"(d[4]),"+f"(d[5]),"+f"(d[6]),"+f"(d[7]),"+f"(d[8]),"+f"(d[9]),"+f"(d[10]),"+f"(d[11]),"+f"(d[12]),"+f"(d[13]),"+f"(d[14]),"+f"(d[15]),"+f"(d[16]),"+f"(d[17]),"+f"(d[18]),"+f"(d[19]),"+f"(d[20]),"+f"(d[21]),"+f"(d[22]),"+f"(d[23]),"+f"(d[24]),"+f"(d[25]),"+f"(d[26]),"+f"(d[27]),"+f"(d[28]),"+f"(d[29]),"+f"(d[30]),"+f"(d[31]),"+f"(d[32]),"+f"(d[33]),"+f"(d[34]),"+f"(d[35]),"+f"(d[36]),"+f"(d[37]),"+f"(d[38]),"+f"(d[39]),"+f"(d[40]),"+f"(d[41]),"+f"(d[42]),"+f"(d[43]),"+f"(d[44]),"+f"(d[45]),"+f"(d[46]),"+f"(d[47]),"+f"(d[48]),"+f"(d[49]),"+f"(d[50]),"+f"(d[51]),"+f"(d[52]),"+f"(d[53]),"+f"(d[54]),"+f"(d[55]),"+f"(d[56]),"+f"(d[57]),"+f"(d[58]),"+f"(d[59]),"+f"(d[60]),"+f"(d[61]),"+f"(d[62]),"+f"(d[63])
    : "l"(da), "l"(db), "r"(sc));
}

template <int BN> struct WG;
template <> struct WG<256> { static __device__ __forceinline__ void mma(float (&d)[128], uint64_t a, uint64_t b, int sc) { wgmma_ss_n256_tb1(d, a, b, sc); } };
template <> struct WG<128> { static __device__ __forceinline__ void mma(float (&d)[64], uint64_t a, uint64_t b, int sc) { wgmma_ss_n128_tb1(d, a, b, sc); } };

#define PDL 0
struct GemmMaps { CUtensorMap a, b[3], c; };
template <int BN, int STAGES>
__global__ void __cluster_dims__(2, 1, 1) __launch_bounds__(384, 1)
gemm_kernel(const __grid_constant__ GemmMaps maps, int tilesM, int tilesN, int kblocks, int nPerB, uint4* __restrict__ clearX) {
  extern __shared__ __align__(1024) uint8_t smem_raw[];
  constexpr int STAGE_BYTES = 16384 + BN * 128;
  constexpr int NBOX = BN / 64;
  const uint32_t sbase = (smem_u32(smem_raw) + 1023) & ~1023u;
  const uint32_t sEpi = sbase + STAGES * STAGE_BYTES;
  const uint32_t sBar = sEpi + 32768;
  const int warp = threadIdx.x >> 5, lane = threadIdx.x & 31, wg = warp >> 2;
  uint32_t crank; asm("mov.u32 %0, %%cluster_ctarank;" : "=r"(crank));
#define GT(k)
  const int npairs = (tilesM >> 1) * tilesN, pair0 = blockIdx.x >> 1, pstep = gridDim.x >> 1;
  if (threadIdx.x == 256) {
    asm volatile("prefetch.tensormap [%0];" :: "l"(&maps.b[0]) : "memory");
    for (int i = 0; i < STAGES; i++) { mbar_init(sBar + 8 * i, 1); mbar_init(sBar + 8 * (STAGES + i), 4); }
    asm volatile("fence.mbarrier_init.release.cluster;" ::: "memory");
    asm volatile("barrier.cluster.arrive.relaxed;" ::: "memory");
    for (int i = 0; i < STAGES; i++) {
      mbar_expect_tx(sBar + 8 * i, STAGE_BYTES);
      if (!PDL) tma2d(sbase + i * STAGE_BYTES, &maps.a, i * 64, ((pair0 % (tilesM >> 1)) * 2 + crank) * 128, sBar + 8 * i);
    }
    asm volatile("prefetch.tensormap [%0];" :: "l"(&maps.c) : "memory");
    if (PDL) asm volatile("prefetch.tensormap [%0];" :: "l"(&maps.a) : "memory");
  } else asm volatile("barrier.cluster.arrive.relaxed;" ::: "memory");
  asm volatile("barrier.cluster.wait.acquire;" ::: "memory");
  __syncwarp();
  if (wg == 2) {
    asm volatile("setmaxnreg.dec.sync.aligned.u32 40;");
    if (warp > 8) {
      if (PDL) asm volatile("griddepcontrol.wait;" ::: "memory");
      __nanosleep(4000);
      for (int i = blockIdx.x * 96 + threadIdx.x - 288; i < (int)(sizeof(Xchg) / 16); i += gridDim.x * 96) clearX[i] = make_uint4(0, 0, 0, 0);
    }
    if (warp == 8 && lane == 0) {
      int st = 0, ph = 1;
      for (int p = pair0; p < npairs; p += pstep) {
        const int tm = (p % (tilesM >> 1)) * 2 + crank, tn = p / (tilesM >> 1);
        const CUtensorMap* mb = &maps.b[tn / nPerB];
        const int n0 = (tn % nPerB) * BN;
        for (int kb = 0; kb < kblocks; kb++) {
          const uint32_t a = sbase + st * STAGE_BYTES, full = sBar + 8 * st;
          if (p > pair0 || kb >= STAGES) {
            mbar_wait(sBar + 8 * (STAGES + st), ph);
            mbar_expect_tx(full, STAGE_BYTES);
            tma2d(a, &maps.a, kb * 64, tm * 128, full);
          }
#pragma unroll
          for (int i = 0; i < NBOX / 2; i++) {
            const int bx = crank * (NBOX / 2) + i;
            tma2d_mc(a + 16384 + bx * 8192, mb, n0 + bx * 64, kb * 64, full, (uint16_t)3);
          }
          if (PDL && p == pair0 && kb == STAGES - 1) {
            asm volatile("griddepcontrol.wait;" ::: "memory");
            for (int i = 0; i < STAGES; i++) tma2d(sbase + i * STAGE_BYTES, &maps.a, i * 64, tm * 128, sBar + 8 * i);
          }
          if (++st == STAGES) { st = 0; ph ^= 1; }
        }
      }
      for (int i = 0; i < STAGES; i++) { mbar_wait(sBar + 8 * (STAGES + st), ph); if (++st == STAGES) { st = 0; ph ^= 1; } }
    }
  } else {
    asm volatile("setmaxnreg.inc.sync.aligned.u32 232;");
    int st = 0, ph = 0;
    float acc[BN / 2];
    const uint64_t descA0 = (uint64_t)(((sbase + wg * 8192) & 0x3FFFF) >> 4) | (1ull << 16) | (64ull << 32) | (1ull << 62);
    const uint64_t descB0 = (uint64_t)(((sbase + 16384) & 0x3FFFF) >> 4) | (512ull << 16) | (64ull << 32) | (1ull << 62);
    const uint32_t epi = sEpi + wg * 16384;
    for (int p = pair0; p < npairs; p += pstep) {
      const int tm = (p % (tilesM >> 1)) * 2 + crank, tn = p / (tilesM >> 1);
      int prev = -1;
      for (int kb = 0; kb < kblocks; kb++) {
        mbar_wait(sBar + 8 * st, ph);
        if ((kb & 15) == 0) { GT(kb >> 4); }
        wg_fence();
        const uint64_t so = (uint64_t)(st * (STAGE_BYTES >> 4));
#pragma unroll
        for (int k = 0; k < 4; k++) WG<BN>::mma(acc, descA0 + so + k * 2, descB0 + so + k * 128, kb | k);
        wg_commit();
        if (prev >= 0) {
          wg_wait<1>();
          if ((threadIdx.x & 127) < 2) mbar_arrive_cluster(sBar + 8 * (STAGES + prev), threadIdx.x & 1);
        }
        prev = st;
        if (++st == STAGES) { st = 0; ph ^= 1; }
      }
      wg_wait<0>();
      if ((threadIdx.x & 127) < 2) mbar_arrive_cluster(sBar + 8 * (STAGES + prev), threadIdx.x & 1);
      GT(4);
#pragma unroll
      for (int r = 0; r < BN / 128; r++) {
        if (r || p > pair0) {
          if ((threadIdx.x & 127) == 0) asm volatile("cp.async.bulk.wait_group.read 0;" ::: "memory");
          bar_sync(1 + wg, 128);
        }
        const int row = (warp & 3) * 16 + (lane & 15);
#pragma unroll
        for (int i = 0; i < 8; i++) {
          const int c = 2 * (i & 3) + (lane >> 4);
          const float* q = &acc[r * 64 + i * 8];
          stsm4(epi + (i >> 2) * 8192 + row * 128 + ((c ^ (row & 7)) << 4), pack2(q[0], q[1]), pack2(q[2], q[3]), pack2(q[4], q[5]), pack2(q[6], q[7]));
        }
        fence_async();
        bar_sync(1 + wg, 128);
        if ((threadIdx.x & 127) == 0) {
          tma2d_store(&maps.c, epi, tn * BN + r * 128, tm * 128 + wg * 64);
          tma2d_store(&maps.c, epi + 8192, tn * BN + r * 128 + 64, tm * 128 + wg * 64);
          asm volatile("cp.async.bulk.commit_group;" ::: "memory");
        }
      }
    }
    GT(5);
    if ((threadIdx.x & 127) == 0) asm volatile("cp.async.bulk.wait_group.read 0;" ::: "memory");
    GT(6);
  }
}

struct Dft { uint32_t m[2][2][2][4]; };
template <bool P4> __device__ __forceinline__ int fidx(int tile, int x) { return P4 ? 4 * (x >> 1) + 2 * (tile & 1) + (x & 1) + 16 * (tile >> 1) : x + 8 * tile; }
__device__ __forceinline__ float2 cis(int k, int n) {
  k &= n - 1; if (2 * k > n) k -= n;
  const float a = (float)k * (6.283185307179586f / (float)n);
  return make_float2(__cosf(a), __sinf(a));
}
template <bool OUT4> __device__ __forceinline__ void make_dft(Dft& D, int g, int t) {
#pragma unroll
  for (int q = 0; q < 16; q++) {
    const int b = q >> 3, u = (q >> 2) & 1, r = (q >> 1) & 1, v = q & 1;
    const float2 w = cis(fidx<OUT4>(v, g) * fidx<false>(2 * u + r, 2 * t + b), 32);
    D.m[b][u][0][q & 3] = pack2(w.x, w.y); D.m[b][u][1][q & 3] = pack2(-w.y, w.x);
  }
}
__device__ __forceinline__ void mma_dc(float (&d)[4], uint32_t a0, uint32_t a1, uint32_t a2, uint32_t a3, uint32_t b0, uint32_t b1, const float (&c)[4]) {
  asm("mma.sync.aligned.m16n8k16.row.col.f32.bf16.bf16.f32 {%0,%1,%2,%3}, {%4,%5,%6,%7}, {%8,%9}, {%10,%11,%12,%13};"
    : "=f"(d[0]), "=f"(d[1]), "=f"(d[2]), "=f"(d[3]) : "r"(a0), "r"(a1), "r"(a2), "r"(a3), "r"(b0), "r"(b1), "f"(c[0]), "f"(c[1]), "f"(c[2]), "f"(c[3])); }
__device__ __forceinline__ void dft_b(const Dft& D, const uint32_t (&x)[2][4], float (&o)[2][8]) {
#pragma unroll
  for (int ri = 0; ri < 2; ri++) {
    float z[4] = {0.f, 0.f, 0.f, 0.f}, e[4], p[4];
    mma_dc(e, D.m[0][0][ri][0], D.m[0][0][ri][1], D.m[0][0][ri][2], D.m[0][0][ri][3], x[0][0], x[0][1], z);
    mma_dc(e, D.m[0][1][ri][0], D.m[0][1][ri][1], D.m[0][1][ri][2], D.m[0][1][ri][3], x[0][2], x[0][3], e);
    mma_dc(p, D.m[1][0][ri][0], D.m[1][0][ri][1], D.m[1][0][ri][2], D.m[1][0][ri][3], x[1][0], x[1][1], e);
    mma_dc(p, D.m[1][1][ri][0], D.m[1][1][ri][1], D.m[1][1][ri][2], D.m[1][1][ri][3], x[1][2], x[1][3], p);
#pragma unroll
    for (int q = 0; q < 4; q++) { o[ri][q] = p[q]; o[ri][4 + q] = fmaf(2.f, e[q], -p[q]); }
  }
}
__device__ __forceinline__ void dft_a(const uint32_t (&m)[2][2][4], const uint32_t (&x0)[2][4], const uint32_t (&x1)[2][4], float (&o)[2][8]) {
#pragma unroll
  for (int ri = 0; ri < 2; ri++) {
    float z[4] = {0.f, 0.f, 0.f, 0.f}, e[4], p[4];
    mma_dc(e, x0[0][0], x1[0][0], x0[0][1], x1[0][1], m[0][ri][0], m[0][ri][1], z);
    mma_dc(e, x0[0][2], x1[0][2], x0[0][3], x1[0][3], m[0][ri][2], m[0][ri][3], e);
    mma_dc(p, x0[1][0], x1[1][0], x0[1][1], x1[1][1], m[1][ri][0], m[1][ri][1], e);
    mma_dc(p, x0[1][2], x1[1][2], x0[1][3], x1[1][3], m[1][ri][2], m[1][ri][3], p);
#pragma unroll
    for (int q = 0; q < 4; q++) { o[ri][q] = p[q]; o[ri][4 + q] = fmaf(2.f, e[q], -p[q]); }
  }
}
__device__ __forceinline__ uint32_t twid(float re, float im, float c, float s) { return pack2(fmaf(re, c, im * s), fmaf(im, c, -re * s)); }
__device__ __forceinline__ void cpa16(uint32_t d, const void* s) { asm volatile("cp.async.cg.shared.global [%0], [%1], 16;" :: "r"(d), "l"(s) : "memory"); }
__device__ __forceinline__ void sts32(uint32_t a, uint32_t x) { asm volatile("st.shared.u32 [%0], %1;" :: "r"(a), "r"(x) : "memory"); }
__device__ __forceinline__ void cpa_commit() { asm volatile("cp.async.commit_group;" ::: "memory"); }
template <int N> __device__ __forceinline__ void cpa_wait() { asm volatile("cp.async.wait_group %0;" :: "n"(N) : "memory"); }
__device__ __forceinline__ uint32_t lds32(uint32_t a) { uint32_t r; asm volatile("ld.shared.u32 %0, [%1];" : "=r"(r) : "r"(a) : "memory"); return r; }
#define FMID 0
constexpr int F_TP = 4112, F_TSZ = 8 * F_TP;

__device__ __forceinline__ uint32_t ldnc32(const void* p) { uint32_t v; asm volatile("ld.global.nc.b32 %0, [%1];" : "=r"(v) : "l"(p) : "memory"); return v; }
template <class F>
__device__ __forceinline__ void fft_wprep(const bf16* __restrict__ wr, const bf16* __restrict__ wi, int cta, F&& mid) {
  const int tid = threadIdx.x, g = (cta >> 1) & 7, c = (cta >> 4) & 3, t = 2 * (cta & 1) + (tid & 1);
  const int k0 = g + 8 * (cta >> 6) + 32 * (8 * c + 2 * t), l0 = (tid & ~1) + (g & 1);
  uint32_t a[4][4], b[4][4];
#pragma unroll
  for (int q = 0; q < 16; q++) {
    const int o = (k0 + 16 * (q >> 3) + 32 * ((q >> 1) & 1) + 1024 * (q & 1)) * 513 + l0 + 256 * ((q >> 2) & 1);
    a[q >> 2][q & 3] = ldnc32(wr + o);
    b[q >> 2][q & 3] = ldnc32(wi + o);
  }
  const int e = cta * 32 + (tid & 31), lh = (e >> 11) * 512, k = e & 2047, k2 = (k >> 5) & 31;
  uint32_t hz[4];
#pragma unroll
  for (int q = 0; q < 4; q++) asm volatile("ld.global.nc.u16 %0, [%1];" : "=r"(hz[q]) : "l"((q < 2 ? wr : wi) + (q & 1 ? (2048 - k) & 2047 : k) * 513 + lh) : "memory");
  mid();
  uint4* dst = g_wt + l0 * 512 + cta * 2 + (tid & 1);
#pragma unroll
  for (int q = 0; q < 8; q++) {
    const int hf = q >> 1, l = l0 + 256 * (hf & 1) + (q & 1);
    const uint32_t sel = (q & 1) ? 0x7632 : 0x5410;
    if (l & 511) dst[(256 * (hf & 1) + (q & 1)) * 512 + 256 * (q >> 2)] = make_uint4(__byte_perm(a[hf][0], b[hf][0], sel), __byte_perm(a[hf][1], b[hf][1], sel),
                                                                                   __byte_perm(a[hf][2], b[hf][2], sel), __byte_perm(a[hf][3], b[hf][3], sel));
  }
  if (tid < 32) reinterpret_cast<uint32_t*>(g_wt)[(64 * ((k >> 3) & 3) + 16 * (k2 >> 3) + 2 * (k & 7) + ((k2 >> 2) & 1)) * 8 + lh * 2048 + 2 * (k2 & 3) + (k >> 10)] =
      pack2(0.5f * (__uint_as_float(hz[0] << 16) + __uint_as_float(hz[1] << 16)), 0.5f * (__uint_as_float(hz[2] << 16) - __uint_as_float(hz[3] << 16)));
}

template <class F>
__device__ __forceinline__ void fft_rows_fwd(const bf16* __restrict__ x, const bf16* __restrict__ wr, const bf16* __restrict__ wi, uint32_t tb, int it, F&& mid) {
  const int warp = threadIdx.x >> 5, lane = threadIdx.x & 31, g = lane >> 2, t = lane & 3;
  const uint32_t in = tb + warp * 4096;
  const uint32_t f0 = in + (lane >> 3) * 256 + (((lane & 7) ^ (2 * (lane >> 3))) << 4);
  const bf16* src = x + ((256 * (warp & 3) + 64 * (warp >> 2) + 128 * (it & 1) + 32 * ((it >> 4) & 1) + 8 * (it >> 5) + ((it >> 1) & 7)) * 2048 + lane * 8);
#pragma unroll
  for (int q = 0; q < 8; q++) cpa16((f0 ^ ((q >> 2) * 144)) + (q & 3) * 1024, src + q * 256);
  cpa_commit();
  Dft D;
  float2 tw[4][8];
  fft_wprep(wr, wi, it, [&]() {
    if (FMID == 0) mid();
    make_dft<true>(D, g, t);
#pragma unroll
    for (int q = 0; q < 32; q++) {
      tw[q >> 3][q & 7] = cis(fidx<true>((q >> 1) & 3, g) * fidx<false>(q >> 3, 2 * t + (q & 1)), 1024);
      if (FMID) asm volatile("" : "+f"(tw[q >> 3][q & 7].x), "+f"(tw[q >> 3][q & 7].y) :: "memory");
    }
    if (FMID == 1) mid();
  });
  if (FMID == 2) mid();
  cpa_wait<0>(); __syncwarp();
  uint32_t a[4][2][4], y[4][2][4];
#pragma unroll
  for (int q = 0; q < 8; q++) ldsm4t(a[q & 3][q >> 2], (in + lane * 128 + ((lane & 7) << 4)) ^ (q << 4));
  float o[2][8];
#pragma unroll
  for (int i = 0; i < 4; i++) {
    dft_b(D, a[i], o);
#pragma unroll
    for (int q = 0; q < 8; q++) y[q >> 1][q & 1][i] = twid(o[0][q], o[1][q], tw[i][q].x, tw[i][q].y);
  }
  __syncthreads();
  const uint32_t w0 = tb + warp * F_TP + fidx<true>(0, g) * 128 + t * 16 + ((g & 1) << 6), wz = (g & 1) ? -64 : 64;
#pragma unroll
  for (int z = 0; z < 2; z++) {
    float o2[2][8];
    dft_b(D, y[2 * z], o); dft_b(D, y[2 * z + 1], o2);
#pragma unroll
    for (int i = 0; i < 4; i++) {
      const float sg = i < 2 ? 1.f : -1.f;
      sts128(w0 + z * wz + fidx<true>(i, 0) * 128, pack2(o[0][2 * i], sg * o[1][2 * i]), pack2(o[0][2 * i + 1], sg * o[1][2 * i + 1]),
             pack2(o2[0][2 * i], sg * o2[1][2 * i]), pack2(o2[0][2 * i + 1], sg * o2[1][2 * i + 1]));
    }
  }
  __syncthreads();
  const uint32_t ra = tb + (lane & 1) * 4 * F_TP + ((lane >> 1) + 16 * (warp ^ ((warp >> 1) & 1))) * 4;
  uint4* dst = g_y + (threadIdx.x >> 1) * 256 + (lane & 1) + it * 2;
#pragma unroll
  for (int q = 0; q < 8; q++) { const uint32_t r = ra + q * 512; dst[q * 32768] = make_uint4(lds32(r), lds32(r + F_TP), lds32(r + 2 * F_TP), lds32(r + 3 * F_TP)); }
}

template <class F>
__device__ __forceinline__ void fft_cols(uint32_t sb, int cta, int ncta, F&& ready) {
  const int warp = threadIdx.x >> 5, lane = threadIdx.x & 31, g = lane >> 2, t = lane & 3;
  const uint32_t in = sb + warp * 16384 + lane * 16, tab = sb + 131072 + lane * 16;
  auto fetch_y = [&](int l) {
#pragma unroll
    for (int q = 0; q < 16; q++) cpa16(in + q * 512, g_y + (q < 8 ? l : (1024 - l) & 1023) * 256 + (q & 7) * 32 + lane);
  };
  auto fetch_w = [&](int l) {
#pragma unroll
    for (int q = 0; q < 16; q++) cpa16(in + 8192 + q * 512, g_wt + l * 512 + q * 32 + lane);
  };
  const int l0 = cta * 8 + warp, dl = ncta * 8;
  Dft D; make_dft<false>(D, g, t);
#pragma unroll
  for (int q = 2 * warp; q < 2 * warp + 2; q++) {
    const int r = fidx<false>(q & 3, g), c = fidx<false>(q >> 2, 2 * t);
    const float2 w0 = cis(r * c, 1024), w1 = cis(r * c + r, 1024), p0 = cis(r + 32 * c, 2048), p1 = cis(r + 32 * c + 32, 2048);
    sts128(tab + q * 512, __float_as_uint(w0.x), __float_as_uint(w0.y), __float_as_uint(w1.x), __float_as_uint(w1.y));
    sts128(tab + 8192 + q * 512, __float_as_uint(p0.x), __float_as_uint(p0.y), __float_as_uint(p1.x), __float_as_uint(p1.y));
  }
  if (warp == 0) {
#pragma unroll
    for (int q = 0; q < 8; q++) {
      const int v = q >> 2, b = (q >> 1) & 1, ri = q & 1;
      sts128(tab + 16384 + q * 512, D.m[b][0][ri][v], D.m[b][0][ri][v + 2], D.m[b][1][ri][v], D.m[b][1][ri][v + 2]);
    }
  }
  ready();
  fetch_y(l0); cpa_commit();
  fetch_w(l0); cpa_commit();
#pragma unroll 1
  for (int l = l0; l <= 512; l += dl) {
    uint32_t a[2][4][2][4], y[2][4][2][4];
    float o[2][2][8];
    cpa_wait<1>();
#pragma unroll
    for (int q = 0; q < 16; q++) lds128(a[q >> 3][(q >> 1) & 3][q & 1], in + q * 512);
    if (!(l & 511)) {
      const uint32_t m0 = l ? 0x80000000u : 0u;
#pragma unroll
      for (int q = 0; q < 32; q++) { a[0][q >> 3][(q >> 2) & 1][q & 3] ^= m0; a[1][q >> 3][(q >> 2) & 1][q & 3] ^= m0 ^ 0x80000000u; }
    }
    auto first = [&]() {
#pragma unroll
      for (int i = 0; i < 4; i++) {
        dft_b(D, a[0][i], o[0]); dft_b(D, a[1][i], o[1]);
#pragma unroll
        for (int r = 0; r < 4; r++) {
          const float4 w = lds128f(tab + (4 * i + r) * 512);
#pragma unroll
          for (int s = 0; s < 2; s++) {
            y[s][r][0][i] = twid(o[s][0][2 * r], o[s][1][2 * r], w.x, w.y);
            y[s][r][1][i] = twid(o[s][0][2 * r + 1], o[s][1][2 * r + 1], w.z, w.w);
          }
        }
      }
    };
    first();
    if (l + dl <= 512) fetch_y(l + dl);
    cpa_commit();
    cpa_wait<1>();
#pragma unroll
    for (int zv = 0; zv < 4; zv++) {
      const int z = zv >> 1, v = zv & 1;
      uint32_t m[2][2][4];
#pragma unroll
      for (int q = 0; q < 4; q++) lds128(m[q >> 1][q & 1], tab + 16384 + (4 * v + q) * 512);
      dft_a(m, y[0][2 * z], y[0][2 * z + 1], o[0]); dft_a(m, y[1][2 * z], y[1][2 * z + 1], o[1]);
#pragma unroll
      for (int q = 0; q < 4; q++) {
        const int i = 2 * z + (q & 1), c = v + (q & 2);
        uint32_t w[4]; lds128(w, in + 8192 + (4 * i + c) * 512);
        const float4 ph = lds128f(tab + 8192 + (4 * c + i) * 512);
#pragma unroll
        for (int b = 0; b < 2; b++) {
          const float cs = b ? ph.z : ph.x, sn = b ? ph.w : ph.y;
          const float r1 = __uint_as_float(w[2 * b] << 16), i1 = __uint_as_float(w[2 * b] & 0xFFFF0000u);
          const float r2 = __uint_as_float(w[2 * b + 1] << 16), i2 = __uint_as_float(w[2 * b + 1] & 0xFFFF0000u);
          const float Sr = r1 + r2, Si = i1 + i2, Dr = r1 - r2, Di = i1 - i2;
          const float ar = fmaf(-Dr, sn, Sr), ai = fmaf(-Di, sn, Si), dr = fmaf(Dr, sn, Sr), di = fmaf(Di, sn, Si), br = -Di * cs, bi = Dr * cs;
          const float Ar = o[0][0][2 * q + b], Ai = o[0][1][2 * q + b], Br = o[1][0][2 * q + b], Bi = o[1][1][2 * q + b];
          a[0][i][b][c] = pack2(fmaf(ar, Ai, fmaf(ai, Ar, fmaf(br, Bi, bi * Br))), fmaf(ar, Ar, fmaf(-ai, Ai, fmaf(br, Br, -bi * Bi))));
          a[1][i][b][c] = pack2(fmaf(dr, Bi, fmaf(di, Br, fmaf(-br, Ai, -bi * Ar))), fmaf(dr, Br, fmaf(-di, Bi, fmaf(-br, Ar, bi * Ai))));
        }
      }
    }
    if (l + dl <= 512) fetch_w(l + dl);
    cpa_commit();
    first();
#pragma unroll
    for (int s = 0; s < 2; s++) {
      uint4* dst = g_y + (s ? (1024 - l) & 1023 : l) * 256 + lane;
      const float sg = s ? -1.f : 1.f;
#pragma unroll
      for (int i = 0; i < 4; i++) {
        dft_b(D, y[s][i], o[0]);
#pragma unroll
        for (int b = 0; b < 2; b++)
          dst[(2 * i + b) * 32] = make_uint4(pack2(sg * o[0][0][b], o[0][1][b]), pack2(sg * o[0][0][2 + b], o[0][1][2 + b]),
                                             pack2(sg * o[0][0][4 + b], o[0][1][4 + b]), pack2(sg * o[0][0][6 + b], o[0][1][6 + b]));
      }
    }
  }
}

template <class F>
__device__ __forceinline__ void fft_rows_inv(const CUtensorMap* om, uint32_t sb, int cta, int ncta, F&& ready) {
  const int warp = threadIdx.x >> 5, lane = threadIdx.x & 31, g = lane >> 2, t = lane & 3, wg = warp >> 2, w4 = warp & 3;
  const uint32_t tb = sb + 32768 + wg * 2 * F_TSZ;
  const uint4* src = g_y + pin((256 * ((lane >> 1) & 3) + 64 * (lane >> 3) + 8 * w4) * 256 + (lane & 1));
  const uint32_t wa = pin(tb + (lane & 1) * 4 * F_TP + w4 * 1024 + (lane >> 1) * 4);
  uint4 pf[8];
  auto fetch = [&](int it, int hf) {
#pragma unroll
    for (int q = 0; q < 8; q++) pf[q] = __ldcg(src + (it * 2 + hf * 8192) + q * 256);
  };
  auto put = [&](uint32_t off) {
#pragma unroll
    for (int q = 0; q < 8; q++) {
      sts32(wa + off + q * 64, pf[q].x); sts32(wa + off + q * 64 + F_TP, pf[q].y);
      sts32(wa + off + q * 64 + 2 * F_TP, pf[q].z); sts32(wa + off + q * 64 + 3 * F_TP, pf[q].w);
    }
  };
  const int it0 = 2 * cta + wg;
  Dft D; make_dft<false>(D, g, t);
  float2 tw[4][8];
#pragma unroll
  for (int q = 0; q < 32; q++) {
    tw[q >> 3][q & 7] = cis(fidx<false>((q >> 1) & 3, g) * fidx<false>(q >> 3, 2 * t + (q & 1)), 1024);
    tw[q >> 3][q & 7].x *= 1.f / 2097152.f; tw[q >> 3][q & 7].y *= 1.f / 2097152.f;
    asm volatile("" : "+f"(tw[q >> 3][q & 7].x), "+f"(tw[q >> 3][q & 7].y) :: "memory");
  }
  ready();
  fetch(it0, 0); put(0); fetch(it0, 1); put(512);
  const uint32_t la = pin(tb + w4 * F_TP + lane * 16), ob = uni(sb + warp * 4096);
  const uint32_t oa = pin(ob + (lane >> 1) * 128 + (((4 * (lane & 1)) ^ ((lane >> 1) & 7)) << 4));
#pragma unroll 1
  for (int n = 0;; n++) {
    const int it = it0 + (n >> 1) * 2 * ncta, hf = n & 1, buf = (n >> 1) & 1;
    if (it >= 128) break;
    if (!hf) bar_sync(1 + wg, 128);
    uint32_t a[4][2][4], y[4][2][4];
#pragma unroll
    for (int q = 0; q < 8; q++) lds128(a[q >> 1][q & 1], la + buf * F_TSZ + hf * 4 * F_TP + q * 512);
    fetch(min(it + 2 * ncta, 127), hf);
    float o[2][8];
#pragma unroll
    for (int i = 0; i < 4; i++) {
      dft_b(D, a[i], o);
#pragma unroll
      for (int q = 0; q < 8; q++) y[q >> 1][q & 1][i] = twid(o[0][q], o[1][q], tw[i][q].x, tw[i][q].y);
    }
    if (lane == 0) asm volatile("cp.async.bulk.wait_group.read 0;" ::: "memory");
    __syncwarp();
#pragma unroll
    for (int c = 0; c < 4; c++) {
      dft_b(D, y[c], o);
#pragma unroll
      for (int ri = 0; ri < 2; ri++)
        stsm4((oa ^ (c << 4)) + (1 - ri) * 2048, pack2(o[ri][0], o[ri][1]), pack2(o[ri][2], o[ri][3]), pack2(o[ri][4], o[ri][5]), pack2(o[ri][6], o[ri][7]));
    }
    fence_async();
    __syncwarp();
    if (lane == 0) {
      const int m = 256 * w4 + 32 * ((it >> 1) & 7) + 8 * (it >> 5) + 4 * (it & 1) + 2 * hf + ((it >> 4) & 1);
      asm volatile("cp.async.bulk.tensor.3d.global.shared::cta.bulk_group [%0, {0, 0, %2}], [%1];" :: "l"(om), "r"(ob), "r"(2 * m) : "memory");
      asm volatile("cp.async.bulk.commit_group;" ::: "memory");
    }
    put((buf ^ 1) * F_TSZ + hf * 512);
  }
  if (lane == 0) asm volatile("cp.async.bulk.wait_group 0;" ::: "memory");
}
__device__ __forceinline__ void grid_arrive(unsigned* ctr) {
  __syncthreads();
  if (threadIdx.x == 0) { __threadfence(); atomicAdd(ctr, 1u); }
}
__device__ __forceinline__ void grid_wait(unsigned* ctr, unsigned n) {
  if (threadIdx.x == 224) {
    int it = 0;
    while (*reinterpret_cast<volatile unsigned*>(ctr) < n) { __nanosleep(100); if (++it > SPIN_LIMIT) { g_err = 3; break; } }
    __threadfence();
  }
  __syncthreads();
}

struct RecMaps { CUtensorMap wq, wk, wv, wo, x, k, q, v, fo; };
#define NSW 16
#define EXP 0
#define NPB 3
#define NPB0 3
#define NPC 0
#define WOP 2
#define HOME 7
#define DL0 14
#define PD1 4
#define NE4 6
#define NE6 0
#define NA4 14
#define NA6 18
#define NB1 24
#define TQL 7
#define NQ 16
#define TQP (NQ - 1)
#define OXPOS 4
#define KVPOS 2
#define NK0 0
#define FLPOS 1
#define XWPOS 10
#define FSPOS 28
#define RL0 4
#define RLS 6
#define RLB 4
#define VL0 3
#define RI 9
#define RJ 8
#define NPRE 22
#define PFD 4
#define PD0 4
#define VB NV0
#define NPA 0
#define N1 16
#define DL1 16
#define PACE 0
#define RE0 0
#define RE1 0
#define RP1 23
#define UNP 1
#define X2 2
#define X3 2
#define SPOS 2
#ifndef NV0
#define NV0 4
#endif
#define TGP 3
#define FENP 0
#define LW0 8
#define X1 4
#define X0 4
constexpr int R_WO = 0, R_X = 65536, R_MEM = 131072, R_WC = 147456, R_RED = R_WC + NSW * 2048, R_O = R_RED, R_S = R_O + 2048, R_P = R_S + 3072, R_STAGE = R_P + 2048,
              R_K = R_STAGE + 8192, R_Q = R_K + 8192, R_V = R_Q + 2048, R_ID = R_V + 16384, R_T = R_ID + 512, R_DST = R_T + 512, R_RD = R_DST + 2048, R_BAR = R_RD + 2048, R_TS = R_BAR + 128,
              R_TOTAL = R_TS;
#define TS(i)
#define LOG(i, v)
constexpr int B_KV = R_BAR, B_W = R_BAR + 8, B_X = R_BAR + 80, B_PK = R_BAR + 24, B_C = R_BAR + 32, B_B = R_BAR + 40, B_DUE = R_BAR + 48, B_ONE = R_BAR + 64;
#define DLY_A 150
#define DLY_V 150
#define DLY_C 200
#define DLY_L 90
#define NS_B 1120
#define NS_C 1728
#define NS_P 2624
#define NS_V 128
#define NS_F 896
#define NS_K 128
#define NS_M 32
#define NS_X 128
#define MG_Z 0x00010206
#define MG_Y 0x00010512
#define NS_PEN 1024
__device__ __forceinline__ float rcp(float x) { float r; asm("rcp.approx.ftz.f32 %0, %1;" : "=f"(r) : "f"(x)); return r; }
__device__ __forceinline__ uint32_t movm(uint32_t a) { uint32_t d; asm volatile("movmatrix.sync.aligned.m8n8.trans.b16 %0, %1;" : "=r"(d) : "r"(a)); return d; }
__device__ __forceinline__ uint32_t hadd2(uint32_t a, uint32_t b) { uint32_t d; asm("add.rn.bf16x2 %0, %1, %2;" : "=r"(d) : "r"(a), "r"(b)); return d; }
__device__ __forceinline__ void mma_a(float (&d)[4], const uint32_t (&a)[4], uint32_t b0, uint32_t b1) { mma16816(d, a[0], a[1], a[2], a[3], b0, b1); }
__device__ __forceinline__ bool elect() {
  uint32_t p; asm volatile("{.reg .pred p; elect.sync _|p, 0xffffffff; selp.u32 %0, 1, 0, p;}" : "=r"(p)); return p; }
__device__ __forceinline__ void tma3d(uint32_t dst, const CUtensorMap* m, int c1, int c2, uint32_t bar) {
  asm volatile("cp.async.bulk.tensor.3d.shared::cluster.global.mbarrier::complete_tx::bytes [%0], [%1, {0, %3, %4}], [%2];"
    :: "r"(dst), "l"(m), "r"(bar), "r"(c1), "r"(c2) : "memory"); }
__device__ __forceinline__ void tma4d(uint32_t dst, const CUtensorMap* m, int c1, int c2, uint32_t bar) {
  asm volatile("cp.async.bulk.tensor.4d.shared::cluster.global.mbarrier::complete_tx::bytes [%0], [%1, {0, %3, %4, 0}], [%2];"
    :: "r"(dst), "l"(m), "r"(bar), "r"(c1), "r"(c2) : "memory"); }
template <int OFF, int ACC>
__device__ __forceinline__ void wg_rs32(float (&d)[16], const uint32_t (&a)[4], uint32_t db) {
  if (ACC)
    asm volatile("{.reg .b64 db; .reg .b32 lo; add.u32 lo, %20, %21; mov.b64 db, {lo, 0x40000040};\n"
      "wgmma.mma_async.sync.aligned.m64n32k16.f32.bf16.bf16 {%0,%1,%2,%3,%4,%5,%6,%7,%8,%9,%10,%11,%12,%13,%14,%15}, {%16,%17,%18,%19}, db, 1, 1, 1, 0;}"
      : "+f"(d[0]), "+f"(d[1]), "+f"(d[2]), "+f"(d[3]), "+f"(d[4]), "+f"(d[5]), "+f"(d[6]), "+f"(d[7]), "+f"(d[8]), "+f"(d[9]), "+f"(d[10]), "+f"(d[11]), "+f"(d[12]), "+f"(d[13]), "+f"(d[14]), "+f"(d[15])
      : "r"(a[0]), "r"(a[1]), "r"(a[2]), "r"(a[3]), "r"(db), "n"(OFF));
  else
    asm volatile("{.reg .b64 db; .reg .b32 lo; add.u32 lo, %20, %21; mov.b64 db, {lo, 0x40000040};\n"
      "wgmma.mma_async.sync.aligned.m64n32k16.f32.bf16.bf16 {%0,%1,%2,%3,%4,%5,%6,%7,%8,%9,%10,%11,%12,%13,%14,%15}, {%16,%17,%18,%19}, db, 0, 1, 1, 0;}"
      : "=f"(d[0]), "=f"(d[1]), "=f"(d[2]), "=f"(d[3]), "=f"(d[4]), "=f"(d[5]), "=f"(d[6]), "=f"(d[7]), "=f"(d[8]), "=f"(d[9]), "=f"(d[10]), "=f"(d[11]), "=f"(d[12]), "=f"(d[13]), "=f"(d[14]), "=f"(d[15])
      : "r"(a[0]), "r"(a[1]), "r"(a[2]), "r"(a[3]), "r"(db), "n"(OFF));
}
template <int I> using IC = std::integral_constant<int, I>;
template <int I, int N, class F> __device__ __forceinline__ void sfor(F&& f) {
  if constexpr (I < N) { f(std::integral_constant<int, I>{}); sfor<I + 1, N>(f); }
}
__device__ __forceinline__ void keep(float (&d)[16]) {
  asm volatile("" : "+f"(d[0]), "+f"(d[1]), "+f"(d[2]), "+f"(d[3]), "+f"(d[4]), "+f"(d[5]), "+f"(d[6]), "+f"(d[7]),
      "+f"(d[8]), "+f"(d[9]), "+f"(d[10]), "+f"(d[11]), "+f"(d[12]), "+f"(d[13]), "+f"(d[14]), "+f"(d[15]) :: "memory");
}

template <int N, int S2 = 1024> __device__ __forceinline__ void ldx(uint32_t (&v)[N][4], const uint8_t* p) {
#pragma unroll
  for (int k = 0; k < 2 * N; k++) {
    const int i = k;
    asm volatile("ld.relaxed.gpu.global.v2.b32 {%0,%1}, [%2];" : "=r"(v[i >> 1][2 * (i & 1)]), "=r"(v[i >> 1][2 * (i & 1) + 1]) : "l"(p + (i & 3) * 256 + (i >> 2) * S2) : "memory");
  }
}
__device__ __forceinline__ uint32_t dif2(uint32_t a, uint32_t b, uint32_t tag) { uint32_t r; asm("lop3.b32 %0, %1, %2, %3, 0x7e;" : "=r"(r) : "r"(a), "r"(b), "r"(tag)); return r; }
__device__ __forceinline__ uint32_t dif2v(uint32_t a, uint32_t b, uint32_t tag) { uint32_t r; asm volatile("lop3.b32 %0, %1, %2, %3, 0x7e;" : "=r"(r) : "r"(a), "r"(b), "r"(tag)); return r; }
__device__ __forceinline__ uint32_t or3(uint32_t a, uint32_t b, uint32_t c) { uint32_t r; asm("lop3.b32 %0, %1, %2, %3, 0xfe;" : "=r"(r) : "r"(a), "r"(b), "r"(c)); return r; }
__device__ __forceinline__ uint32_t after(uint32_t x, float f, uint32_t z) { uint32_t r; asm("lop3.b32 %0, %1, %2, %3, 0xea;" : "=r"(r) : "r"(__float_as_uint(f)), "r"(z), "r"(x)); return r; }
__device__ __forceinline__ bool any_bit(uint32_t a, uint32_t b, uint32_t m) {
  uint32_t r; asm("lop3.b32 %0, %1, %2, %3, 0xa8;" : "=r"(r) : "r"(a), "r"(b), "r"(m)); return __any_sync(0xffffffffu, r); }
template <int W, int N> __device__ __forceinline__ bool stale(const uint32_t (&v)[N][4], uint32_t tag) {
  uint32_t x = dif2(v[0][0], v[0][2], tag);
  if (N == 4) x = or3(x, dif2(v[1][0], v[1][2], tag), dif2(v[2 % N][0], v[2 % N][2], tag));
  return any_bit(x, dif2(v[N - 1][0], v[N - 1][2], tag), 1);
}
template <int W, int N, int S2 = 1024> __device__ __forceinline__ void retry(uint32_t (&v)[N][4], const uint8_t* p, uint32_t tag, int& it) {
#pragma unroll 1
  do { ldx<N, S2>(v, p); it += INC_A; } while (stale<W>(v, tag) && it < SPIN_LIMIT);
}
__device__ __forceinline__ void mma_h(float (&d)[4], const uint32_t (&a)[4], const uint32_t (&b)[4], int hf) { mma16816(d, a[0], a[1], a[2], a[3], b[2 * hf], b[2 * hf + 1]); }
__device__ __forceinline__ void sts128(uint32_t a, const uint32_t (&r)[4]) { sts128(a, r[0], r[1], r[2], r[3]); }
__device__ __forceinline__ void sts128f(uint32_t a, const float* r) { sts128(a, __float_as_uint(r[0]), __float_as_uint(r[1]), __float_as_uint(r[2]), __float_as_uint(r[3])); }
__device__ __forceinline__ void mbar_spin(uint32_t bar, uint32_t par, int& it) {
  asm volatile("{.reg .pred p; .reg .b32 par; mov.b32 par, %2;\nLOOP: mbarrier.try_wait.parity.shared::cta.b64 p, [%1], par; @p bra.uni DONE;\n"
               "add.s32 %0, %0, 1; setp.le.s32 p, %0, %3; @p bra.uni LOOP;\nDONE: }" : "+r"(it) : "r"(bar), "r"(par), "n"(SPIN_LIMIT) : "memory"); }
__device__ __forceinline__ void warp_arrive(uint32_t bar) {
  __syncwarp(); asm volatile("{.reg .pred p; elect.sync _|p, 0xffffffff; @p mbarrier.arrive.shared::cta.b64 _, [%0];}" :: "r"(bar) : "memory"); }
__device__ __forceinline__ void delay_until(unsigned t) {
  asm volatile("{.reg .pred p; .reg .b64 c; .reg .b32 lo, hi;\nLOOP: mov.u64 c, %%clock64; mov.b64 {lo, hi}, c; sub.s32 lo, lo, %0; setp.lt.s32 p, lo, 0; @p bra.uni LOOP;}" :: "r"(t) : "memory"); }
__device__ __forceinline__ void cut(int it) { asm volatile("{.reg .pred p; setp.lt.s32 p, %0, 0;\nL: @p st.volatile.shared.u32 [%0], %0; @p bra.uni L;}" :: "r"(it) : "memory"); }
__device__ __forceinline__ void zero(float (&c)[4][4]) {
#pragma unroll
  for (int i = 0; i < 4; i++) c[i][0] = c[i][1] = c[i][2] = c[i][3] = 0.f;
}

__device__ __forceinline__ void sched() { asm volatile("griddepcontrol.launch_dependents;" ::: "memory"); }
__device__ __forceinline__ const uint8_t* pinp(const uint8_t* p) { return reinterpret_cast<const uint8_t*>(__shfl_xor_sync(0xffffffffu, reinterpret_cast<unsigned long long>(p), 0)); }
__device__ __forceinline__ uint32_t bar_or(int id, uint32_t x) {
  uint32_t r; asm volatile("{.reg .pred p, q; setp.ne.u32 p, %2, 0; bar.red.or.pred q, %1, 256, p; selp.u32 %0, 1, 0, q;}" : "=r"(r) : "r"(id), "r"(x) : "memory"); return r; }
__device__ __forceinline__ void bar_sync_unless(int id, uint32_t x) { asm volatile("{.reg .pred p; setp.eq.u32 p, %1, 0; @p bar.sync %0, 256;}" :: "r"(id), "r"((uint32_t)x) : "memory"); }
__device__ __forceinline__ void bar_arrive_unless(int id, uint32_t x) { asm volatile("{.reg .pred p; setp.eq.u32 p, %1, 0; @p bar.arrive %0, 256;}" :: "r"(id), "r"((uint32_t)x) : "memory"); }
__device__ __forceinline__ void stsm2t(uint32_t a, uint32_t r0, uint32_t r1, uint32_t x) {
  asm volatile("{.reg .pred p; setp.eq.u32 p, %3, 0; @p stmatrix.sync.aligned.m8n8.x2.trans.shared.b16 [%0], {%1,%2};}" :: "r"(a), "r"(r0), "r"(r1), "r"((uint32_t)x) : "memory"); }
__device__ __forceinline__ uint32_t or_and(uint32_t a, uint32_t b, uint32_t m) { uint32_t r; asm("lop3.b32 %0, %1, %2, %3, 0xa8;" : "=r"(r) : "r"(a), "r"(b), "r"(m)); return r; }
#define rare(x) __builtin_expect(!!(x), 0)
__device__ __forceinline__ uint32_t gtime() { unsigned long long g; asm volatile("mov.u64 %0, %%globaltimer;" : "=l"(g) :: "memory"); return (uint32_t)g; }
__device__ __forceinline__ void wait_time(uint32_t t) {
  asm volatile("{.reg .pred p; .reg .b32 g; .reg .b64 c;\nLOOP: mov.u64 c, %%globaltimer; cvt.u32.u64 g, c; sub.s32 g, %0, g; setp.lt.u32 p, g, 16384; @p bra.uni LOOP;}" :: "r"(t - 1) : "memory"); }
__device__ __forceinline__ uint32_t ldx32(const void* p) { uint32_t v; asm volatile("ld.relaxed.gpu.global.b32 %0, [%1];" : "=r"(v) : "l"(p) : "memory"); return v; }
__device__ __forceinline__ void stx32(const void* p, uint32_t v) { asm volatile("st.relaxed.gpu.global.b32 [%0], %1;" :: "l"(p), "r"(v) : "memory"); }

__global__ void __launch_bounds__(256, 1)
rec_kernel(const __grid_constant__ RecMaps maps, const bf16* __restrict__ xin, const bf16* __restrict__ mem0, Xchg* const gx,
           const bf16* __restrict__ fx, const bf16* __restrict__ wr, const bf16* __restrict__ wi) {
  extern __shared__ __align__(1024) uint8_t smem_raw[];
  const uint32_t sb = smem_u32(smem_raw);
  int role = blockIdx.x;
  {
    uint32_t smid, nsm; asm volatile("mov.u32 %0, %%smid;" : "=r"(smid)); asm volatile("mov.u32 %0, %%nsmid;" : "=r"(nsm));
    const int p = smid >> 1, u = p - 32;
    if (nsm == gridDim.x)
      role = (smid & 1) + (p < 32 ? 4 * ((p & 7) + 8 * (p >> 4)) + 2 * ((p >> 3) & 1) : p < 60 ? 4 * (16 + u % 7 + 7 * (u / 14)) + 2 * ((u / 7) & 1)
                         : p < 62 ? 2 * p + 8 : 2 * p - 4);
    role = uni(role);
  }
  if (role >= 128) {
    fft_cols(sb, role - 128, 4, [&]() { grid_wait(&gx->ctr[33], 128); });
    __threadfence(); __syncwarp();
    if ((threadIdx.x & 31) == 0) atomicAdd(&gx->ctr[32], 1u);
    __syncwarp();
    fft_rows_inv(&maps.fo, sb, role - 128, 4, [&]() { grid_wait(&gx->ctr[32], 32); });
    return;
  }
  const int tid = threadIdx.x, warp = uni(tid >> 5), lane = tid & 31, wg = warp >> 2, w4 = warp & 3, g = lane >> 2, t = lane & 3;
  const int h = role >> 2, j = role & 3, jh = j & 1;
  uint32_t w[48][4];
  float aq[16], av[16];
  int it = 0;

#define PT(k)
  auto pf_wo = [&]() {
    for (int i = 0; i < 4; i++)
      asm volatile("cp.async.bulk.prefetch.tensor.2d.L2.global [%0, {%1, %2}];" :: "l"(&maps.wo), "r"(256 * j + 64 * i), "r"(h * DH) : "memory");
  };
  fft_rows_fwd(fx, wr, wi, sb + R_MEM + 49152, role, [&]() {
    if (tid == 224) {
      mbar_init(sb + B_KV, 1); mbar_init(sb + B_W, 1); mbar_init(sb + B_X, 1); mbar_init(sb + B_X + 8, 1); mbar_init(sb + B_X + 16, 1); mbar_init(sb + B_X + 24, 1); mbar_init(sb + B_C, 4); mbar_init(sb + B_PK, 4); mbar_init(sb + B_B, 1);
      asm volatile("fence.mbarrier_init.release.cluster;" ::: "memory");
      mbar_expect_tx(sb + B_W, 3 * 65536);
      for (int i = 0; i < 4; i++) {
        tma2d(sb + R_X + i * 16384, &maps.wq, h * DH + 32 * j, i * 256, sb + B_W);
        if (i < 3) tma2d(sb + R_MEM + i * 16384, &maps.wk, h * DH + 32 * j, i * 256, sb + B_W);
        else asm volatile("cp.async.bulk.prefetch.tensor.2d.L2.global [%0, {%1, %2}];" :: "l"(&maps.wk), "r"(h * DH + 32 * j), "r"(768) : "memory");
      }
      for (int i = 0; i < 2; i++) tma2d(sb + R_WO + i * 32768, &maps.wv, h * DH + 64 * (j >> 1), jh * 512 + i * 256, sb + B_W);
      if (PFD) asm volatile("cp.async.bulk.prefetch.L2.global [%0], 2048;" :: "l"(xin + role * DM) : "memory");
      else for (int i = 0; i < 4; i++) asm volatile("cp.async.bulk.prefetch.L2.global [%0], 8192;" :: "l"(xin + role * 16384 + i * 4096) : "memory");
      if (WOP == 0) pf_wo();
      for (int i = 0; i < 5; i++) asm volatile("prefetch.tensormap [%0];" :: "l"(&maps.wo + i) : "memory");
    }
    __syncwarp();
  });
  if (tid < 16) sts32(sb + R_T + tid * 4, ~0u);
  fence_async();
  PT(0);
  grid_arrive(&gx->ctr[33]);
  PT(1);
  if (tid == 224) { tma2d(sb + R_MEM + 49152, &maps.wk, h * DH + 32 * j, 768, sb + B_W); if (WOP == 1) pf_wo(); }
  __syncwarp();
  uint8_t* const xb = reinterpret_cast<uint8_t*>(gx);
  auto probe_at = [&](int n) { return xb + (n ? offsetof(Xchg, C) + w4 * 8192 + role * 32 : offsetof(Xchg, B) + role * 8192 + warp * 128); };
  if (lane < 8) stx128(probe_at(lane >> 2) + (lane & 2) * 2048 + (lane & 1) * 16, 0, 0, 0, 0);
  uint32_t m0[4][4];
#pragma unroll
  for (int i = 0; i < 16; i++) m0[i >> 2][i & 3] = ldnc32(mem0 + g * DM + 128 * warp + 8 * i + 2 * t);
  mbar_spin(sb + B_W, 0, it);
  PT(2);
  const int lrow = (lane & 7) + ((lane >> 4) << 3), lhi = (lane >> 3) & 1;
  const int kq = wg ? 3 - 3 * jh : 3 * jh;
  const uint32_t LW = lrow * 128 + ((lhi ^ (lane & 7)) << 4);
  {
    const int chunk = w4 < 2 ? w4 + 2 * lhi : 2 * (w4 & 1) + lhi;
    uint32_t a = sb + (w4 < 2 ? R_X : R_MEM) + kq * 16384 + lrow * 64 + ((chunk ^ ((lrow >> 1) & 3)) << 4);
#pragma unroll
    for (int i = 0; i < 16; i++) ldsm4t(w[i], a + i * 1024);
    const uint32_t st = wg ? 1024 : 2048, av0 = sb + R_WO + (LW ^ (w4 << 5));
    const uint32_t a1 = wg ? a + (2 * jh - 1) * 16384 : av0 + jh * 32768, a2 = wg ? a + (2 * jh - 1) * 32768 : av0 + (1 - jh) * 32768;
#pragma unroll
    for (int i = 0; i < 16; i++) { ldsm4t(w[16 + i], a1 + i * st); ldsm4t(w[32 + i], a2 + i * st); }
  }
  uint32_t L16 = pin(lane * 16);
  const uint32_t uW = uni(sb + w4 * 512), uWo = uni(sb + R_WO + w4 * 16384), uMem = uni(sb + R_MEM + kq * 4096);
  const uint32_t dX = uni(((sb + R_X + kq * 16384) >> 4) | 0x10000u);
  auto load_wo = [&](uint32_t (&d)[32][4], int i0, int i1) {
#pragma unroll
    for (int i = i0; i < i1; i++) lds128(d[i], uWo + L16 + (i & 1) * 512 + (i >> 4) * 1024 + (i & 14) * 1024);
  };
  auto issue_x = [&](int n, int k) {
    const uint32_t bar = sb + B_X + 8 * k, q = k ^ (3 - 3 * jh);
    mbar_expect_tx(bar, 16384); tma3d(sb + R_X + q * 16384, &maps.x, n * SEG, 4 * q, bar);
  };
  auto store_stage = [&](int n) {
    asm volatile("cp.async.bulk.global.shared::cta.bulk_group [%0], [%1], 8192; cp.async.bulk.commit_group;"
                 :: "l"(g_kqv[n & 3][role]), "r"(sb + R_STAGE) : "memory");
  };
  auto issue_kqv = [&](int n) {
    const int p = (n & 3) * 128 + 4 * h;
    mbar_expect_tx(sb + B_KV, 26624);
    tma3d(sb + R_K, &maps.k, 0, p, sb + B_KV); tma3d(sb + R_Q, &maps.q, 8 + 2 * j, p, sb + B_KV); tma3d(sb + R_V, &maps.v, 16, p, sb + B_KV);
  };
  auto fetch4k = [&](uint32_t dst, uint32_t off, uint32_t bar, uint32_t t) {
    asm volatile("{.reg .pred p, q; .reg .b32 g; .reg .b64 c; elect.sync _|q, 0xffffffff; @q mbarrier.arrive.expect_tx.shared::cta.b64 _, [%2], 4096;\n"
                 "LOOP: mov.u64 c, %%globaltimer; cvt.u32.u64 g, c; sub.s32 g, %3, g; setp.lt.u32 p, g, 16384; @p bra.uni LOOP;\n"
                 "@q cp.async.bulk.shared::cluster.global.mbarrier::complete_tx::bytes [%0], [%1], 4096, [%2];}" :: "r"(dst), "l"(xb + off), "r"(bar), "r"(t - 1) : "memory");
  };
  uint32_t uS;
  auto my_b = [&]() { return offsetof(Xchg, B) + role * 8192 + ((uS + ((uint32_t)it >> 31)) & 1) * 4096; };
  auto issue_c = [&](uint32_t t) { fetch4k(sb + R_MEM + w4 * 4096, offsetof(Xchg, C) + w4 * 8192 + ((uS + ((uint32_t)it >> 31)) & 4096), sb + B_C, t); };
  auto wait_x = [&](int n, int i) { if (!(EXP & 1) || n < 2) mbar_spin(sb + B_X + 8 * i, n & 1, it); };
#define PACED(d0) uint32_t dz = d0; const uint32_t z = (uint32_t)it >> 31; auto pace = [&]() { for (int k = 0; k < PACE; k++) { if (k & 1) asm("add.u32 %0, %0, %1;" : "+r"(dz) : "r"(z)); else asm("xor.b32 %0, %0, %1;" : "+r"(dz) : "r"(z)); } };
  auto project_v = [&](auto I0, auto I1, auto&& mid) {
    PACED(decltype(I0)::value < 16 ? dX : dX ^ 1024);
    wg_fence();
    sfor<decltype(I0)::value, decltype(I1)::value>([&](auto I) {
      constexpr int i = decltype(I)::value;
      mid(i);
      if (i == 16 && decltype(I0)::value < 16) dz ^= 1024;
      wg_rs32<((i >> 2) & 3) * 256 + (i & 3) * 2, (i > 0)>(av, w[16 + i], dz);
      pace();
    });
    wg_commit();
  };
  auto project_qk = [&](auto I0, auto I1, auto first, auto&& mid) {
    PACED((dX ^ (decltype(I0)::value >> 4 << 10)) + ((uint32_t)it >> 31));
    wg_fence();
    sfor<decltype(I0)::value, decltype(I1)::value>([&](auto I) {
      constexpr int i = decltype(I)::value;
      mid(i);
      wg_rs32<((i >> 2) & 3) * 256 + (i & 3) * 2, !decltype(first)::value || i != decltype(I0)::value>(aq, w[i], dz);
      pace();
    });
    wg_commit();
  };
  const uint32_t uP = uni(sb + R_X + 3 * jh * 16384 + w4 * 512);
  auto park = [&]() {
    bar_sync(1, 128);
#pragma unroll
    for (int i = 0; i < 4; i++) sts128f(uP + L16 + i * 2048, aq + 4 * i);
    warp_arrive(sb + B_PK);
  };
  auto unpark = [&]() {
#pragma unroll
    for (int i = 0; i < 4; i++) {
      const float4 p = lds128f(uP + L16 + i * 2048);
      av[4 * i] = p.x; av[4 * i + 1] = p.y; av[4 * i + 2] = p.z; av[4 * i + 3] = p.w;
    }
  };
  auto fin_qk = [&]() {
#pragma unroll
    for (int i = 0; i < 16; i++) aq[i] += av[i];
    const uint32_t a = sb + R_STAGE + (w4 < 2 ? 2048 + w4 * 128 : (w4 & 1) * 256) + (L16 & 112) + (L16 >> 7) * 512;
    stsm4t(a, pack2(aq[0], aq[1]), pack2(aq[4], aq[5]), pack2(aq[8], aq[9]), pack2(aq[12], aq[13]));
    stsm4t(a + (w4 < 2 ? 256 : 128), pack2(aq[2], aq[3]), pack2(aq[6], aq[7]), pack2(aq[10], aq[11]), pack2(aq[14], aq[15]));
  };
  auto fin_v = [&]() {
#pragma unroll
    for (int a = 0; a < 2; a++)
      sts128(sb + R_STAGE + 4096 + w4 * 1024 + a * 512 + L16, pack2(av[8 * a], av[8 * a + 1]), pack2(av[8 * a + 2], av[8 * a + 3]),
             pack2(av[8 * a + 4], av[8 * a + 5]), pack2(av[8 * a + 6], av[8 * a + 7]));
  };
  __syncthreads();
  if (tid == 224) {
#pragma unroll 1
    for (int i = 0; i < 4; i++) issue_x(0, i);
    mbar_expect_tx(sb + B_W, 65536);
    for (int i = 0; i < 4; i++) tma2d(sb + R_WO + i * 16384, &maps.wo, 256 * j + 64 * i, h * DH, sb + B_W);
  }
  __syncwarp();
  if (wg) {
#pragma unroll
    for (int i = 0; i < NSW; i++) sts128(uW + R_WC + L16 + i * 2048, w[i]);
  }
#pragma unroll
  for (int i = 0; i < 4; i++) sts128(sb + R_MEM + warp * 2048 + i * 512 + (g >> 1) * 128 + t * 32 + (g & 1) * 16, m0[i]);
  auto probe = [&](int n, int cnt) {
    if (lane == 0) {
#pragma unroll 1
      for (int i = role >> 7; i < cnt; i++) {
        const int k = (i ^ wg) & 1;
        const unsigned t0 = clk();
        uint32_t v; asm volatile("atom.relaxed.gpu.global.exch.b32 %0, [%1], 0;" : "=r"(v) : "l"(probe_at(n) + k * 4096) : "memory");
        if (v == 0) asm volatile("red.shared.min.u32 [%0], %1;" :: "r"(sb + R_T + (n ? w4 * 8 : 32) + k * 4), "r"(clk() - t0) : "memory");
      }
    }
    __syncwarp();
  };
#pragma unroll 1
  for (int n = 0; n < 2; n++) {
    probe(0, n ? NPB : NPB0);
    asm volatile("{.reg .pred p; cp.async.bulk.wait_group 0; setp.eq.u32 p, %1, 97; @p red.relaxed.gpu.global.add.u32 [%0], 1;}" :: "l"(&gx->ctr[h]), "r"(tid ^ n ^ (1 - n) << 9) : "memory");
    PT(3 + 3 * n);
    wait_x(n, 2);
    PT(4 + 3 * n);
    if (wg == 0) {
      wait_x(n, 3);
      project_qk(IC<0>{}, IC<16>{}, IC<1>{}, [](int) {});
      project_v(IC<0>{}, IC<32>{}, [](int) {});
      wg_wait<0>(); keep(aq); keep(av);
      park();
      fin_v();
      fence_async();
    } else {
      wait_x(n, 0); wait_x(n, 1);
      project_qk(IC<32>{}, IC<48>{}, IC<1>{}, [](int) {});
      project_qk(IC<16>{}, IC<32>{}, IC<0>{}, [](int) {});
      project_qk(IC<0>{}, IC<16>{}, IC<0>{}, [](int) {});
      mbar_spin(sb + B_PK, n, it);
      unpark();
      wg_wait<0>(); keep(aq);
      fin_qk();
      fence_async();
    }
    __syncthreads();
    if (tid == 0 && n) stx32(&gx->S[role], 1 + (HOME & 2 && lds32(sb + R_T + 36) < lds32(sb + R_T + 32)));
    PT(5 + 3 * n);
    if (tid == 96 && n == 0) store_stage(0);
    if (tid == 128 && n == 0) {
#pragma unroll 1
      for (int i = 0; i < 4; i++) issue_x(1, i);
    }
    if (warp == 5 && n == 1) {
#pragma unroll 1
      while (__any_sync(0xffffffffu, ldx32(&gx->ctr[h]) < 4) && ++it < SPIN_LIMIT) {}
      if (elect()) issue_kqv(0);
    }
    __syncwarp();
  }
  mbar_spin(sb + B_W, 1, it);
  PT(9);
#pragma unroll
  for (int i = 0; i < 4; i++) {
    uint32_t f[4][4];
    const uint32_t a = sb + R_WO + warp * 8192 + i * 2048;
#pragma unroll
    for (int q = 0; q < 4; q++) ldsm4t(f[q], a + (LW ^ (q << 5)));
    __syncwarp();
#pragma unroll
    for (int q = 0; q < 4; q++) sts128(a + q * 512 + L16, f[q]);
  }
  if (NPC) probe(1, NPC);
  {
    const int o = 32 * w4 + 16 * wg + 4 * t + j;
    uint32_t v;
#pragma unroll 1
    while (__any_sync(0xffffffffu, (v = ldx32(&gx->S[o])) == 0) && ++it < SPIN_LIMIT) {}
    asm volatile("st.shared.u64 [%0], %1;" :: "r"(sb + R_DST + wg * 1024 + w4 * 256 + lane * 8), "l"(xb + offsetof(Xchg, B) + o * 8192 + (v >> 1) * 4096 + h * 128 + ((g ^ h) & 7) * 16) : "memory");
  }
  if (wg == 0) {
    const uint64_t cd = reinterpret_cast<uint64_t>(xb + (offsetof(Xchg, C) + j * 8192 + h * 128 + w4 * 32 + (L16 & 16) * 256 + (L16 & 64) / 4 + (L16 >> 7) * 4));
    sts128(uW + R_RD + L16, (uint32_t)cd, (uint32_t)(cd >> 32), sb + R_MEM + (L16 & 112) * 8 + (L16 >> 8) * 1024 + ((w4 * 32 + ((L16 >> 3) & 16)) ^ (L16 & 112)),
           (L16 >> 6) == (h & 3) * 2 + ((h >> 2) & 1) ? 0xFFFE0000u : 0xFFFFFFFFu);
  }
  if (tid == 0) sts32(sb + B_DUE + 8, gtime() & ~31u);
  PT(10);
  mbar_spin(sb + B_KV, 0, it);
  PT(11);
  if (tid < 4) sts32(sb + B_ONE + tid * 4, 0x3F803F80u);
  if (warp == 1) { const uint32_t e = g >> 1 == t ? 0x3F80u << (16 * (g & 1)) : 0u; sts128(sb + R_ID + L16, e, 0, 0, e); }
  __syncthreads();
  {
    const uint32_t kb = lds32(sb + R_T + 36) < lds32(sb + R_T + 32);
    uS = uni((HOME & 4 ? (__popc(((offsetof(Xchg, B) / 4096 + 2 * role) ^ (offsetof(Xchg, C) / 4096 + 2 * w4)) & 0xb3) ^ kb) & 1 : lds32(sb + R_T + w4 * 8 + 4) < lds32(sb + R_T + w4 * 8)) * 4096 + kb);
  }

  const float sc = 0.08838834764831845f * 1.4426950408889634f;
  uint8_t* const xa = xb + uni(h * 16384);
  const uint32_t uA = uni(wg ? (w4 >> 1) * 2048 + j * 512 + (w4 & 1) * 256 : 8192 + (4 * (j >> 1) + w4) * 512 + jh * 256);
  const uint32_t uP2 = uni(sb + R_P + w4 * 256);
  uint32_t nc = 1;
  uint32_t ma;
  const uint8_t* adst;
  auto pin_mem = [&]() { adst = pinp(xa + uA + L16 / 2); ma = pin(uMem + (L16 & 384) + (L16 & 48) * 2 + (L16 & 64) / 4); };
  pin_mem();

#pragma unroll 1
  for (int s = 0;; nc++) {
    const uint32_t tag = (s + 1) & 1;
    auto fresh = [&]() { L16 += (uint32_t)it >> 31; };
    auto get_due = [&]() { return lds32(sb + B_DUE + 4 + tag * 4); };
    float c[4][4], r4[4];
    auto fold = [&]() {
#pragma unroll
      for (int i = 0; i < 4; i++) r4[i] = ((c[0][i] + c[1][i]) + c[2][i]) + c[3][i];
    };
    auto mma4 = [&](int n, const uint32_t (&b0)[4], const uint32_t (&b1)[4]) {
      mma_h(c[0], w[n + 2], b1, 0); mma_h(c[1], w[n + 3], b1, 1); mma_h(c[2], w[n], b0, 0); mma_h(c[3], w[n + 1], b0, 1);
    };
    auto xpos = [&](int pos, int wp) {
      if ((pos == X0 || pos == X1 || pos == X2 || pos == X3) && warp == wp && s + 1 < NSEG && elect()) {
        const int z = (uint32_t)it >> 31;
        if (pos == X2) issue_x(s + 2, 2 + z);
        if (pos == X3) issue_x(s + 2, 3 + z);
        if (pos == X1) issue_x(s + 2, 1 + z);
        if (pos == X0) issue_x(s + 2, z);
      }
      __syncwarp();
    };
    if (wg == 0) {
      mbar_spin(sb + B_C, nc & 1, it);
      TS(13);
      uint32_t b[16][4], tg[4];
#pragma unroll
      for (int i = 0; i < PD0; i++) { lds128(b[i], ma + i * 512); __syncwarp(); }
      sched();
      zero(c);
#pragma unroll
      for (int i = 0; i < 8; i++) {
        const int k = i ^ 1;
        mma_h(c[0], w[2 * k], b[k], 0); mma_h(c[1], w[2 * k + 1], b[k], 1);
        if (i < 2 * NV0) { mma_h(c[2], w[16 + 2 * k], b[k], 0); mma_h(c[3], w[17 + 2 * k], b[k], 1); }
        sched();
        if ((i & 1) && i + PD0 < 9) { lds128(b[i + PD0 - 1], ma + (i + PD0 - 1) * 512); __syncwarp(); lds128(b[i + PD0], ma + (i + PD0) * 512); sched(); }
        if (i == TGP) {
          fresh();
#pragma unroll
          for (int k = 0; k < 4; k++) tg[k] = lds32((uW * 4 + L16) * 2 + (L16 >> 6) * 4 + (R_MEM + k * 1024 - 7 * sb));
          sched();
        }
      }
#pragma unroll
      for (int i = 0; i < 4; i++) { r4[i] = c[0][i] + c[1][i]; c[0][i] = c[1][i] = 0.f; }
      sts128f(uW + R_RED + L16, r4);
      TS(1);
      const uint32_t old = bar_or(4, (dif2(tg[0], tg[1], s) | dif2(tg[2], tg[3], s)) & (s > 0));
      TS(0);
#pragma unroll
      for (int i = 0; i < 2 * NV0; i++) { lds128(b[8 + i], (ma ^ 4096) + i * 512); __syncwarp(); }
      sched();
#pragma unroll
      for (int i = NV0; i < 8; i++) {
        if (VB && i == VB) bar_sync(7, 256);
        mma4(16 + 4 * i, b[2 * i], b[2 * i + 1]);
        if (i < 7) sched();
        if (i < 4) { lds128(b[8 + 2 * i], (ma ^ 4096) + i * 1024); __syncwarp(); lds128(b[9 + 2 * i], (ma ^ 4096) + i * 1024 + 512); sched(); }
      }
      fold();
      asm volatile("{.reg .pred p; setp.eq.u32 p, %3, 0; @p st.relaxed.gpu.global.v2.b32 [%0], {%1,%2};}" :: "l"(adst), "r"((pack2(r4[0], r4[1]) & ~1u) | tag), "r"(pack2(r4[2], r4[3])), "r"(old) : "memory");
      sched();
      const unsigned tpub = clk();
      if (__any_sync(0xffffffffu, old) && nc < NC_MAX) {
        bar_sync(3, 256);
        issue_c(gtime());
        continue;
      }
      TS(3);
      xpos(0, 0);
      const uint32_t due = get_due();
      uint32_t vf[4][4], vm[2][4], p[4], pm, o[4];
      const uint32_t va = sb + R_V + (w4 >> 1) * 8192 + (w4 & 1) * 2048 + L16;
#pragma unroll
      for (int i = 0; i < 4; i++) {
        uint32_t q[4]; lds128(vf[i], va + i * 512); lds128(q, va + 4096 + i * 512);
#pragma unroll
        for (int e = 0; e < 4; e++) vf[i][e] = hadd2(vf[i][e], q[e]);
      }
      const uint32_t pa = pin(sb + R_P + (L16 >> 1));
      const uint8_t* vsrc = pinp(xa + 8192 + w4 * 1024 + L16 / 2);
      uint32_t one[4];
      lds128(one, sb + B_ONE);
      auto pv_x = [&]() {
        zero(c);
        mma_a(c[2], one, p[0], p[1]);
        mma_a(c[0], vf[0], p[0], p[1]); mma_a(c[1], vf[2], p[0], p[1]);
        sched();
        mma_a(c[2], one, p[2], p[3]);
        mma_a(c[0], vf[1], p[2], p[3]); mma_a(c[1], vf[3], p[2], p[3]);
        sched();
      };
      auto pv_m = [&]() {
        mma1688(c[2], one[0], one[1], pm);
        mma_a(c[0], vm[0], pm, pm);
        sched();
        mma_a(c[1], vm[1], pm, pm);
      };
      auto norm = [&]() {
        const float n0 = rcp(c[2][0]), n1 = rcp(c[2][1]);
#pragma unroll
        for (int i = 0; i < 4; i++) o[i] = pack2(c[i >> 1][2 * (i & 1)] * n0, c[i >> 1][2 * (i & 1) + 1] * n1);
        return ((__float_as_uint(c[2][0]) - 0x1F800000u) | (__float_as_uint(c[2][1]) - 0x1F800000u)) >> 30;
      };
      auto load_m = [&](int x) { const float2 e0 = lds64f(pa + 512 + x * 1024), e1 = lds64f(pa + 768 + x * 1024); pm = pack2(e0.x * e1.x, e0.y * e1.y); };
      auto attend_max = [&](int x) {
        float2 sv[6];
#pragma unroll
        for (int i = 0; i < 6; i++) sv[i] = lds64f(pa - 3072 + x * 1536 + i * 256);
        sv[4].x += sv[5].x; sv[4].y += sv[5].y;
        const int dq = (int)(L16 >> 6) - (int)((L16 >> 3) & 6) + 8 * j;
        float m = fmaxf(sv[4].x, sv[4].y);
#pragma unroll
        for (int i = 0; i < 4; i++) {
          if (x && 8 * i > dq) sv[i].x = -INFINITY;
          if (x && 8 * i + 1 > dq) sv[i].y = -INFINITY;
          m = fmaxf(m, fmaxf(sv[i].x, sv[i].y));
        }
        m = fmaxf(m, __shfl_xor_sync(0xffffffffu, m, 1));
        m = fmaxf(m, __shfl_xor_sync(0xffffffffu, m, 2));
#pragma unroll
        for (int i = 0; i < 5; i++) (i < 4 ? p[i] : pm) = pack2(ex2(sv[i].x - m), ex2(sv[i].y - m));
        pv_x(); pv_m(); norm();
      };
      uint32_t tq[4];
      auto get_t = [&]() {
        tq[0] = tq[1] = tq[2] = tq[3] = 0;
        asm volatile("{.reg .pred p; setp.eq.u32 p, %5, 0; @p ld.relaxed.gpu.global.v4.b32 {%0,%1,%2,%3}, [%4];}"
                     : "+r"(tq[0]), "+r"(tq[1]), "+r"(tq[2]), "+r"(tq[3]) : "l"(xb + offsetof(Xchg, T) + L16 * 8), "r"(warp) : "memory");
      };
      delay_until(tpub + DLY_V);
      wait_time(due + NS_V);
      TS(4);
      ldx(vm, vsrc);
      sched();
      xpos(2, 2);
      auto store_kqv = [&]() {
        fence_async();
        if (!(EXP & 4))
          asm volatile("{.reg .pred p; elect.sync _|p, 0xffffffff; @p cp.async.bulk.global.shared::cta.bulk_group [%0], [%1], 2048; cp.async.bulk.commit_group;}"
                       :: "l"(g_kqv[(s + 1) & 3][role] + w4 * 128), "r"(sb + R_STAGE + w4 * 2048) : "memory");
      };
      if (SPOS == 2) store_kqv();
      sched();
      bar_sync(5, 256);
      ldsm4(p, sb + R_P + L16);
      load_m(0);
      pv_x();
      ldsm4(p, sb + R_P + 1024 + L16);
      pv_m();
      const uint32_t r = norm(), tl = after(tag, c[2][0], (uint32_t)it >> 31);
      const bool redo = __any_sync(0xffffffffu, r | ((dif2(vm[0][0], vm[0][2], tl) | dif2(vm[1][0], vm[1][2], tl)) & 1));
      TS(6);
      stsm4t(uW + R_O + L16, o[0], o[1], o[2], o[3]);
      bar_arrive_unless(6, redo);
      sched();
      if (TQL == 7) get_t();
      TS(7);
      pv_x();
      if (rare(redo)) retry<2>(vm, vsrc, tag, it);
      bar_sync(8, 256);
      load_m(1);
      pv_m();
      if (rare(__any_sync(0xffffffffu, norm()) || redo)) {
        fresh();
#pragma unroll 1
        for (int x = !redo; x < 2; x++) {
          attend_max(x);
          if (x == 0) { stsm4t(uW + R_O + L16, o[0], o[1], o[2], o[3]); bar_arrive(6, 256); }
        }
      }
      TS(8);
      if (TQL == 8) get_t();
      const bool xok = mbar_test(sb + B_X + 16, s & 1) & mbar_test(sb + B_X + 24, s & 1);
      xpos(4, 2);
      fresh();
      const uint32_t ob = uni(sb + R_MEM + 4096 + w4 * 1024);
      stsm4t(ob + (L16 & 112) * 4 + (((L16 >> 3) ^ (L16 >> 1)) & 48), o[0], o[1], o[2], o[3]);
      __syncwarp();
      uint32_t rd[4];
      lds128(rd, uW + R_RD + L16);
      lds128(o, ob + (L16 ^ ((L16 >> 3) & 48)));
      auto put_o = [&]() {
        *reinterpret_cast<uint4*>(reinterpret_cast<uint8_t*>(g_ox) + (((s * SEG + 8 * j) * HD + h * DH + 32 * w4) * 2 + (L16 >> 6) * (HD * 2) + (L16 & 48))) = make_uint4(o[0], o[1], o[2], o[3]);
      };
      if (s + 1 == NSEG) { put_o(); asm volatile("cp.async.bulk.wait_group 0;" ::: "memory"); break; }
      asm volatile("cp.async.bulk.wait_group 0;" ::: "memory");
      if (elect()) stx32(xa + 4096 + j * 16 + w4 * 4, s + 1);
      __syncwarp();
      if (rare(!xok)) { wait_x(s + 2, 3); wait_x(s + 2, 2); }
      TS(9);
      fresh();
      const uint32_t e = due | ((s + 1) & 31);
      project_qk(IC<0>{}, IC<NQ>{}, IC<1>{}, [&](int n) {
        if (n == OXPOS) { __syncwarp(); put_o(); __syncwarp(); }
        if (n == TQP) { __syncwarp(); tq[0] = dif2v(tq[0], tq[1], e) | dif2v(tq[2], tq[3], e); __syncwarp(); }
      });
      if (NPA) project_v(IC<0>{}, IC<NPA>{}, [](int) {});
      TS(2);
      if (warp == 0) {
        uint32_t last = due, nx = NS_P;
        if (rare(__any_sync(0xffffffffu, tq[0]))) {
          const uint32_t ref = gtime();
#pragma unroll 1
          do ldx128(o, xb + offsetof(Xchg, T) + L16 * 8); while (any_bit(or3(o[0] - s - 1, o[1] - s - 1, o[2] - s - 1), o[3] - s - 1, 30) && ++it < SPIN_LIMIT);
          const int d = max(max((int)(o[0] - ref), (int)(o[1] - ref)), max((int)(o[2] - ref), (int)(o[3] - ref)));
          last = (ref + __reduce_max_sync(0xffffffffu, d)) & ~31u;
          if (last != due) nx += NS_X;
        }
        const uint32_t bdue = last + NS_B;
        if (s < 4) { last += (MG_Y >> 8 * s & 255) * 32; nx += (MG_Z >> 8 * s & 255) * 32; }
        sts32(sb + B_DUE, last);
        sts32(sb + B_DUE + 8 - tag * 4, last + nx);
        fetch4k(sb + R_MEM, my_b(), sb + B_B, bdue);
        LOG(13, tl - last);
        LOG(9, last);
      }
      if (NQ < 16) project_qk(IC<NQ>{}, IC<16>{}, IC<0>{}, [](int) {});
      project_v(IC<NPA>{}, IC<NPRE>{}, [](int) {});
      const uint32_t ba = rd[2], msk = rd[3];
      const uint8_t* cdst = reinterpret_cast<const uint8_t*>(rd[0] | (uint64_t)rd[1] << 32);
      TS(14);
      mbar_spin(sb + B_B, s & 1, it);
      TS(10);
      uint32_t bq[2][4];
      auto sum_b = [&]() {
        ldsm4t(bq[0], ba); ldsm4t(bq[1], ba + 2048);
        sched();
#pragma unroll
        for (int i = 0; i < 8; i++) c[i >> 2][i & 3] = 0.f;
        mma_a(c[0], bq[0], 0x3F803F80u, 0x3F803F80u); mma_a(c[1], bq[1], 0x3F803F80u, 0x3F803F80u);
        const uint32_t t2 = tag * 0x10001u;
        const bool old = any_bit(or3(dif2(bq[0][0], bq[0][1], t2), dif2(bq[0][2], bq[0][3], t2), dif2(bq[1][0], bq[1][1], t2)), dif2(bq[1][2], bq[1][3], t2), L16 < 64 ? 0x10001u : 0u);
        const uint32_t T = (tag << 16) & ~msk, u = ((__float_as_uint(c[0][0] + c[1][0]) + ((0x10000u & ~msk) - T)) & msk) | T;
        asm volatile("{.reg .pred p; setp.eq.u32 p, %2, 0; @p st.relaxed.gpu.global.b32 [%0], %1;}"
                     :: "l"(cdst), "r"(pack2(__uint_as_float(u), c[0][2] + c[1][2])), "r"((uint32_t)(old || (L16 & 32))) : "memory");
        return old;
      };
      if (rare(sum_b())) {
#pragma unroll 1
        do {
          const uint8_t* p = xb + (my_b() + (ba - sb - R_MEM));
          ldx128(bq[0], p); ldx128(bq[1], p + 2048);
          sts128(ba, bq[0]); sts128(ba + 2048, bq[1]);
          __syncwarp();
          it += INC_B;
        } while (sum_b() && it < SPIN_LIMIT);
      }
      sched();
      TS(11);
      bar_arrive(0, 256);
      const unsigned tc = clk();
      const uint32_t cdue = lds32(sb + B_DUE) + NS_C;
      if (warp == 3) LOG(11, gtime() - cdue);
      fresh();
      wg_wait<0>(); keep(aq); keep(av);
      park();
      if (NPRE < 32) project_v(IC<NPRE>{}, IC<32>{}, [](int) {}); else fin_v();
      TS(12);
      delay_until(tc + DLY_C);
      issue_c(cdue);
      TS(5);
      LOG(warp, it);
      pin_mem();
      if (NPRE < 32) { wg_wait<0>(); keep(av); fin_v(); }
      if (!(EXP & 2)) mbar_spin(sb + B_KV, tag, it);
      TS(15);
    } else {
      uint32_t kf[8][4];
      auto load_k = [&]() {
        const uint32_t ka = sb + R_K + w4 * 1024 + (L16 & 112) + (L16 & 128) * 4 + (L16 & 256);
#pragma unroll
        for (int i = 0; i < 8; i++) ldsm4(kf[i], ka + (i >> 1) * 2048 + (i & 1) * 128);
      };
      auto put_p = [&](int x, uint32_t old, uint32_t again) {
        float e[4];
        const int dq = (int)((L16 >> 3) & 6) + 8 * j - (int)(L16 >> 6) - 16 * w4;
#pragma unroll
        for (int i = 0; i < 4; i++) { r4[i] = fmaf(c[3][i], sc, fmaf(c[2][i], sc, fmaf(c[0][i] + c[1][i], sc, __uint_as_float(i == 3 ? 0u - old : 0u)))); e[i] = x && dq + (i & 1) < 8 * (i >> 1) ? 0.f : ex2(r4[i]); }
        stsm2t(uP2 + x * 1024 + L16, pack2(e[0], e[1]), pack2(e[2], e[3]), again);
      };
      auto put_s = [&](int x) {
#pragma unroll
        for (int i = 0; i < 4; i++) sts32f(uW + R_S + x * 1536 + (L16 & 48) * 4 + (L16 >> 6) * 4 + (i & 1) * 32 + (i >> 1) * 256, r4[i]);
      };
      auto load_q = [&](uint32_t (&q)[4], uint32_t off) { ldsm4(q, sb + R_Q + (L16 & 112) + (L16 & 128) * 2 + (L16 >> 8) * 128 + off); };
      mbar_spin(sb + B_C, nc & 1, it);
      TS(13);
      float4 o4;
      uint32_t id[4], old;
      {
        uint32_t b[24][4];
#pragma unroll
        for (int i = 0; i < 2 * PD1; i++) { lds128(b[i], ma + i * 512); __syncwarp(); }
        sched();
        zero(c);
#pragma unroll
        for (int i = 0; i < 12; i++) {
          mma4(4 * i, b[2 * i], b[2 * i + 1]);
          if (i < 11) sched();
          if (i + PD1 < 12) { const int k = i + PD1; const uint32_t a = (ma ^ (k >> 2 << 12)) + (k & 3) * 1024; lds128(b[2 * k], a); __syncwarp(); lds128(b[2 * k + 1], a + 512); sched(); }
          if (i == RJ) { lds128(id, sb + R_ID + L16); sched(); }
          if (i == RI) { old = bar_or(4, 0); o4 = lds128f(uW + R_RED + L16); sched(); }
        }
      }
      TS(0);
      {
        float e[4] = {o4.x, o4.y, o4.z, o4.w};
#pragma unroll
        for (int i = 0; i < 4; i++) { r4[i] = (((e[i] + c[0][i]) + c[1][i]) + c[2][i]) + c[3][i]; e[i] = 0.f; }
        mma_a(e, id, pack2(r4[0], r4[1]), pack2(r4[2], r4[3]));
        sched();
        if (VB) bar_arrive(7, 256);
        sched();
        asm volatile("{.reg .pred p; setp.eq.u32 p, %3, 0; @p st.relaxed.gpu.global.v2.b32 [%0], {%1,%2};}" :: "l"(adst),
                     "r"((__byte_perm(__float_as_uint(e[0]), __float_as_uint(e[1]), 0x7632) & ~1u) | tag), "r"(__byte_perm(__float_as_uint(e[2]), __float_as_uint(e[3]), 0x7632)), "r"(old) : "memory");
        sched();
      }
      const unsigned tpub = clk(), now = gtime(), due = get_due();
      if (__any_sync(0xffffffffu, old) && nc < NC_MAX) { bar_sync(3, 256); continue; }
      TS(2);
      const uint8_t* asrc = pinp(adst + ((warp == 7) * 1024 - (int)uA));
      fresh();
      uint32_t wo[32][4];
      bool xok;
      auto reload = [&]() {
        sched();
#pragma unroll
        for (int i = RE0 + RE1; i < NSW; i++) lds128(w[i], uW + R_WC + L16 + i * 2048);
        sched();
      };
      auto out_proj = [&]() {
        uint32_t b[4][4];
        float d[4][4];
        uint8_t* dst[2];
        const uint32_t da = pin(uP2 + (R_DST - R_P) + L16 / 2);
        sched();
        TS(7);
        bar_sync(6, 256);
#pragma unroll
        for (int i = 0; i < 4; i++) { ldsm4(b[i], sb + R_O + i * 512 + L16); __syncwarp(); }
        sched();
        auto put_b = [&](uint8_t* a, const float (&e)[4][4]) {
          stx128(a, (pack2(e[0][0] + e[2][0], e[0][1] + e[2][1]) & ~1u) | tag, pack2(e[0][2] + e[2][2], e[0][3] + e[2][3]),
                 pack2(e[1][0] + e[3][0], e[1][1] + e[3][1]), pack2(e[1][2] + e[3][2], e[1][3] + e[3][3]));
        };
        zero(c); zero(d);
#pragma unroll
        for (int i = 0; i < 32; i++) {
          mma_h(i < 16 ? c[i & 3] : d[i & 3], wo[i], b[(i >> 2) & 3], (i >> 1) & 1);
          if (i >= LW0 && NB1 + i - LW0 < 32) { load_wo(wo, (NB1 + i - LW0) ^ 1, ((NB1 + i - LW0) ^ 1) + 1); __syncwarp(); }
          if (i == DL0 || i == DL1) asm volatile("ld.shared.u64 %0, [%1];" : "=l"(dst[i > DL0]) : "r"(da + (i > DL0) * 1024) : "memory");
          if (i >= 16 && i < 16 + RE0) { lds128(w[i - 16], uW + R_WC + L16 + (i - 16) * 2048); __syncwarp(); }
          if (i >= RP1 && i < RP1 + RE1) { lds128(w[i - RP1 + RE0], uW + R_WC + L16 + (i - RP1 + RE0) * 2048); __syncwarp(); }
          if (i == 22) put_b(dst[0], c);
          if ((i & 1) && (i < 20 || i > 22)) sched();
        }
        put_b(dst[1], d);
        sched();
        TS(6);
      };
      if (warp < 6) {
        delay_until(tpub + DLY_A);
        const int it0 = it;
        bool redo;
#pragma unroll 1
        do {
          uint32_t q[4][4], y[4];
          float d[4][4];
          wait_time(due);
          TS(4);
          ldx(q, asrc);
          sched();
          load_k();
          uint32_t qx[4][4];
#pragma unroll
          for (int i = 0; i < 4; i++) load_q(qx[i], i * 512);
          sched();
          load_wo(wo, 0, NE4);
          sched();
          zero(c);
#pragma unroll
          for (int i = 0; i < 8; i++) mma_h(c[i & 3], kf[i], qx[i >> 1], i & 1);
          put_p(1, 0, 0); put_s(1);
          sched();
          load_wo(wo, NE4, NA4);
          sched();
          zero(c); zero(d);
#pragma unroll
          for (int i = 0; i < 8; i++) {
            if (i == 0) { y[0] = dif2v(q[0][0], q[0][2], q[1][0]); sched(); }
            if (i == 3) { y[1] = dif2v(q[1][2], q[2][0], q[2][2]); sched(); }
            if (i == 6) { y[2] = dif2v(q[3][0], q[3][2], tag); sched(); }
            mma_h(i % 6 < 2 ? c[2 + i % 6] : d[i - 2], kf[i], q[i >> 1], i & 1);
            if (i == 2 || i == 5 || i == 7) sched();
          }
          y[0] = or_and(or3(y[0], y[1], dif2v(q[0][0], q[2][0], tag)), y[2], it < SPIN_LIMIT);
#pragma unroll
          for (int i = 0; i < 4; i++) { c[0][i] = d[0][i] + d[1][i]; c[1][i] = d[2][i] + d[3][i]; }
          put_p(0, y[0], it - it0);
          TS(5);
          bar_sync_unless(5, it - it0);
          redo = __any_sync(0xffffffffu, y[0]);
          it += INC_A;
        } while (redo);
        it -= INC_A;
        put_s(0);
        bar_arrive(8, 256);
        load_wo(wo, NA4, NB1);
        out_proj();
        if (warp == 4) LOG(12, tb);
      } else {
        uint32_t qx[2][4], q[4][4];
        if (warp == 6) {
          const uint32_t t1 = (now & ~31u) + NS_M;
          LOG(10, now - due);
          if (elect()) stx32(&gx->T[h][j], ((int)(t1 - due) > 0 ? t1 + NS_PEN : due) | ((s + 1) & 31));
          __syncwarp();
        }
        auto score = [&](const uint32_t (&a0)[4], const uint32_t (&a1)[4]) {
          zero(c);
#pragma unroll
          for (int i = 0; i < 4; i++) mma_h(c[i], i < 2 ? a0 : a1, q[2 + (i >> 1)], i & 1);
        };
        auto put_m = [&](uint32_t a, uint32_t old, uint32_t again) {
#pragma unroll
          for (int i = 0; i < 2; i++) { r4[i] = fmaf(c[3][2 + i], sc, fmaf((c[0][i] + c[1][2 + i]) + c[2][i], sc, __uint_as_float(i ? 0u - old : 0u))); r4[2 + i] = fmaf(r4[i] * 0x1p122f, 0.f, ex2(r4[i])); }
          asm volatile("{.reg .pred p; setp.eq.u32 p, %3, 0; @p st.shared.v2.f32 [%0], {%1,%2};}" :: "r"(a), "f"(r4[2]), "f"(r4[3]), "r"(again) : "memory");
        };
        delay_until(tpub + DLY_A);
        const uint32_t sa = sb + R_S + 512 + w4 * 256 + (L16 >> 1);
        const int it0 = it;
        bool redo;
#pragma unroll 1
        do {
          wait_time(due);
          TS(4);
          ldx<4, 2048>(q, asrc);
          sched();
          load_q(qx[0], (w4 & 1) * 1024); load_q(qx[1], (w4 & 1) * 1024 + 512);
          load_wo(wo, 0, NA6);
          sched();
          score(q[0], q[1]);
          sched();
          const uint32_t y = or_and(or3(dif2v(q[0][0], q[0][2], tag), dif2v(q[1][0], q[1][2], tag), dif2v(q[2][0], q[2][2], tag)), dif2v(q[3][0], q[3][2], tag), it < SPIN_LIMIT);
          put_m(sa + 2560, y, it - it0);
          TS(5);
          bar_arrive_unless(5, it - it0);
          redo = __any_sync(0xffffffffu, y);
          it += INC_A;
        } while (redo);
        it -= INC_A;
        sts64f(sa, r4[0], r4[1]);
        score(qx[0], qx[1]);
        put_m(sa + 3584, 0, 0);
        sts64f(sa + 1536, r4[0], r4[1]);
        bar_arrive(8, 256);
        load_wo(wo, NA6, NB1);
        out_proj();
      }
      TS(8);
      if (s + 1 == NSEG) break;
      wait_x(s + 2, 2);
      TS(9);
      fresh();
      if (N1) project_qk(IC<32>{}, IC<32 + N1>{}, IC<1>{}, [](int) {});
      TS(10);
      xpos(6, 6);
      uint32_t fl = s + 1;
      if (warp == 5) { wait_time(due + NS_F); fl = ldx32(xa + 4096 + ((L16 >> 2) & 60)); }
      reload();
      TS(14);
      pin_mem();
      wait_x(s + 2, 1); wait_x(s + 2, 0);
      if (warp == 5) {
#pragma unroll 1
        while (__any_sync(0xffffffffu, fl != s + 1) && !(EXP & 4) && ++it < SPIN_LIMIT) fl = ldx32(xa + 4096 + ((L16 >> 2) & 60));
        wait_time(due + (NS_B + NS_K));
        if (!(EXP & 2) && elect()) issue_kqv(s + 1);
        __syncwarp();
      }
      if (PFD && warp == 6 && s + PFD < NSEG && elect())
        asm volatile("cp.async.bulk.prefetch.L2.global [%0], 2048;" :: "l"(xin + ((s + PFD) * SEG + ((role + 4 * (role >> 5)) & 31)) * DM) : "memory");
      __syncwarp();
      TS(11);
      LOG(warp, it);
      if (warp == 4) LOG(8, nc);
      bar_sync(0, 256);
      if (N1 < 16) project_qk(IC<32 + N1>{}, IC<48>{}, IC<!N1>{}, [](int) {});
      project_qk(IC<16>{}, IC<32>{}, IC<0>{}, [&](int n) { if ((n & 15) == XWPOS) { __syncwarp(); xok = mbar_test(sb + B_PK, s & 1); __syncwarp(); } });
      if (rare(!xok)) mbar_spin(sb + B_PK, s & 1, it);
      unpark();
      project_qk(IC<0>{}, IC<16>{}, IC<0>{}, [](int) {});
      TS(12);
      wg_wait<0>(); keep(aq);
      TS(1);
      fin_qk();
      TS(15);
    }
    s++;
  }
  if (it >= SPIN_LIMIT || nc >= NC_MAX) g_err = 2;
}

typedef CUresult (*EncodeFn)(CUtensorMap*, CUtensorMapDataType, cuuint32_t, void*, const cuuint64_t*, const cuuint64_t*, const cuuint32_t*,
                             const cuuint32_t*, CUtensorMapInterleave, CUtensorMapSwizzle, CUtensorMapL2promotion, CUtensorMapFloatOOBfill);
static void make_map(EncodeFn fn, CUtensorMap* m, const void* p, uint64_t cols, uint64_t rows, uint64_t pitch, uint32_t bc, uint32_t br, CUtensorMapSwizzle sw) {
  cuuint64_t dims[2] = {cols, rows}, strides[1] = {pitch * 2};
  cuuint32_t box[2] = {bc, br}, es[2] = {1, 1};
  fn(m, CU_TENSOR_MAP_DATA_TYPE_BFLOAT16, 2, const_cast<void*>(p), dims, strides, box, es, CU_TENSOR_MAP_INTERLEAVE_NONE, sw,
     CU_TENSOR_MAP_L2_PROMOTION_L2_256B, CU_TENSOR_MAP_FLOAT_OOB_FILL_NONE);
}

extern "C" void kernel_launch(void* const* d_in, const int* in_sizes, int n_in, void* d_out, int out_size) {
  const bf16* Ax = (const bf16*)d_in[0]; const bf16* mem0 = (const bf16*)d_in[1];
  const bf16* Wq = (const bf16*)d_in[2]; const bf16* Wk = (const bf16*)d_in[3]; const bf16* Wv = (const bf16*)d_in[4];
  const bf16* Wo = (const bf16*)d_in[5];
  const bf16* Bx = (const bf16*)d_in[7]; const bf16* wr = (const bf16*)d_in[8]; const bf16* wi = (const bf16*)d_in[9];
  bf16* out = (bf16*)d_out;

  void* fp = nullptr; cudaDriverEntryPointQueryResult qr;
  cudaGetDriverEntryPoint("cuTensorMapEncodeTiled", &fp, cudaEnableDefault, &qr);
  EncodeFn fn = (EncodeFn)fp;
  void *kqv, *ox, *xr;
  cudaGetSymbolAddress(&xr, g_xraw);
  cudaGetSymbolAddress(&kqv, g_kqv); cudaGetSymbolAddress(&ox, g_ox);
  const CUtensorMapSwizzle S128 = CU_TENSOR_MAP_SWIZZLE_128B, S64 = CU_TENSOR_MAP_SWIZZLE_64B;

  GemmMaps m3; RecMaps mr;
  make_map(fn, &m3.a, ox, HD, S_LEN, HD, 64, 128, S128);
  make_map(fn, &m3.b[0], Wo, DM, HD, DM, 64, 64, S128);
  m3.b[1] = m3.b[0]; m3.b[2] = m3.b[0];
  make_map(fn, &m3.c, out, DM, S_LEN, 2 * DM, 64, 64, S128);
  make_map(fn, &mr.wq, Wq, HD, DM, HD, 32, 256, S64);
  make_map(fn, &mr.wk, Wk, HD, DM, HD, 32, 256, S64);
  make_map(fn, &mr.wv, Wv, HD, DM, HD, 64, 256, S128);
  make_map(fn, &mr.wo, Wo, DM, HD, DM, 64, 128, S128);
  {
    cuuint64_t dims[3] = {64, S_LEN, 16}, strides[2] = {DM * 2, 128};
    cuuint32_t box[3] = {64, 32, 4}, es[3] = {1, 1, 1};
    fn(&mr.x, CU_TENSOR_MAP_DATA_TYPE_BFLOAT16, 3, const_cast<bf16*>(Ax), dims, strides, box, es, CU_TENSOR_MAP_INTERLEAVE_NONE, S128,
       CU_TENSOR_MAP_L2_PROMOTION_L2_256B, CU_TENSOR_MAP_FLOAT_OOB_FILL_NONE);
  }
  for (int i = 0; i < 3; i++) {
    cuuint64_t dims[3] = {128, 32, 512}, strides[2] = {256, 8192};
    cuuint32_t box[3] = {128, i == 0 ? 8u : i == 1 ? 2u : 16u, 4}, es[3] = {1, 1, 1};
    fn(i == 0 ? &mr.k : i == 1 ? &mr.q : &mr.v, CU_TENSOR_MAP_DATA_TYPE_BFLOAT16, 3, kqv, dims, strides, box, es, CU_TENSOR_MAP_INTERLEAVE_NONE,
       CU_TENSOR_MAP_SWIZZLE_NONE, CU_TENSOR_MAP_L2_PROMOTION_L2_256B, CU_TENSOR_MAP_FLOAT_OOB_FILL_NONE);
  }
  {
    cuuint64_t dims[3] = {64, 16, S_LEN}, strides[2] = {128, 2 * DM * 2};
    cuuint32_t box[3] = {64, 16, 2}, es[3] = {1, 1, 1};
    fn(&mr.fo, CU_TENSOR_MAP_DATA_TYPE_BFLOAT16, 3, out + DM, dims, strides, box, es, CU_TENSOR_MAP_INTERLEAVE_NONE, S128,
       CU_TENSOR_MAP_L2_PROMOTION_NONE, CU_TENSOR_MAP_FLOAT_OOB_FILL_NONE);
  }
  constexpr int SM3 = 6 * 32768 + 32768 + 256 + 1024;
  cudaFuncSetAttribute(gemm_kernel<128, 6>, cudaFuncAttributeMaxDynamicSharedMemorySize, SM3);
  cudaFuncSetAttribute(rec_kernel, cudaFuncAttributeMaxDynamicSharedMemorySize, R_TOTAL);

  cudaStream_t st = cudaStreamPerThread;
  Xchg* gx = reinterpret_cast<Xchg*>((reinterpret_cast<uintptr_t>(xr) + 0x1FFFFF) & ~(uintptr_t)0x1FFFFF);
  rec_kernel<<<132, 256, R_TOTAL, st>>>(mr, Ax, mem0, gx, Bx, wr, wi);
  cudaLaunchConfig_t cfg = {};
  cudaLaunchAttribute at[1];
  at[0].id = cudaLaunchAttributeProgrammaticStreamSerialization; at[0].val.programmaticStreamSerializationAllowed = PDL & 1;
  cfg.gridDim = dim3(128); cfg.blockDim = dim3(384); cfg.dynamicSmemBytes = SM3; cfg.stream = st; cfg.attrs = at; cfg.numAttrs = 1;
  cudaLaunchKernelEx(&cfg, gemm_kernel<128, 6>, m3, 16, 8, 64, 8, reinterpret_cast<uint4*>(gx));
}
```

```cpp
#include <cuda_runtime.h>
#include <cuda_bf16.h>
#include <cuda.h>
#include <stdint.h>
#include <stddef.h>
#include <type_traits>

typedef __nv_bfloat16 bf16;

constexpr int S_LEN = 2048, DM = 1024, NH = 32, DH = 128, MEM = 8, SEG = 32, NSEG = 64;
constexpr int HD = NH * DH;
#define SPIN 20
constexpr int SPIN_LIMIT = 1 << SPIN, INC_A = 1, INC_B = 1;

constexpr unsigned NC_MAX = 4096;
__device__ __align__(1024) uint4 g_kqv[4][128][512];
__device__ __align__(1024) bf16 g_ox[(size_t)S_LEN * HD];
struct Xchg {
  uint4 A[32][4][256];
  uint4 C[4][2][256];
  uint4 B[128][2][256];
  uint32_t T[32][32];
  uint32_t S[128];
  unsigned ctr[64];
};
__device__ __align__(1024) uint4 g_xraw[(sizeof(Xchg) + (1 << 21)) / 16];
__device__ __align__(1024) uint4 g_y[1024 * 256];
__device__ __align__(1024) uint4 g_wt[513 * 512];
__device__ int g_err;

__device__ __forceinline__ unsigned clk() { unsigned long long c; asm volatile("mov.u64 %0, %%clock64;" : "=l"(c)); return (unsigned)c; }
__device__ __forceinline__ uint32_t smem_u32(const void* p) { return (uint32_t)__cvta_generic_to_shared(p); }
__device__ __forceinline__ void mbar_init(uint32_t bar, int cnt) { asm volatile("mbarrier.init.shared::cta.b64 [%0], %1;" :: "r"(bar), "r"(cnt) : "memory"); }
__device__ __forceinline__ void mbar_expect_tx(uint32_t bar, int bytes) { asm volatile("mbarrier.arrive.expect_tx.shared::cta.b64 _, [%0], %1;" :: "r"(bar), "r"(bytes) : "memory"); }
__device__ __forceinline__ void mbar_arrive(uint32_t bar) { asm volatile("mbarrier.arrive.shared::cta.b64 _, [%0];" :: "r"(bar) : "memory"); }
__device__ __forceinline__ void mbar_arrive_cluster(uint32_t bar, int cta) {
  asm volatile("{.reg .b32 r; mapa.shared::cluster.u32 r, %0, %1; mbarrier.arrive.shared::cluster.b64 _, [r];}" :: "r"(bar), "r"(cta) : "memory"); }
__device__ __forceinline__ bool mbar_try(uint32_t bar, int par) {
  uint32_t ok; asm volatile("{.reg .pred p; mbarrier.try_wait.parity.shared::cta.b64 p, [%1], %2; selp.u32 %0, 1, 0, p;}" : "=r"(ok) : "r"(bar), "r"(par) : "memory"); return ok; }
__device__ __forceinline__ bool mbar_test(uint32_t bar, int par) {
  uint32_t ok; asm volatile("{.reg .pred p; mbarrier.test_wait.parity.shared::cta.b64 p, [%1], %2; selp.u32 %0, 1, 0, p;}" : "=r"(ok) : "r"(bar), "r"(par) : "memory"); return ok; }
__device__ __forceinline__ void mbar_wait(uint32_t bar, int par) {
  int it = 0;
  while (!mbar_try(bar, par)) { if (++it > SPIN_LIMIT) { g_err = 1; break; } }
}
__device__ __forceinline__ void tma2d(uint32_t dst, const CUtensorMap* m, int c0, int c1, uint32_t bar) {
  asm volatile("cp.async.bulk.tensor.2d.shared::cluster.global.mbarrier::complete_tx::bytes [%0], [%1, {%3, %4}], [%2];"
    :: "r"(dst), "l"(m), "r"(bar), "r"(c0), "r"(c1) : "memory"); }
__device__ __forceinline__ void tma2d_mc(uint32_t dst, const CUtensorMap* m, int c0, int c1, uint32_t bar, uint16_t mask) {
  asm volatile("cp.async.bulk.tensor.2d.shared::cluster.global.mbarrier::complete_tx::bytes.multicast::cluster [%0], [%1, {%3, %4}], [%2], %5;"
    :: "r"(dst), "l"(m), "r"(bar), "r"(c0), "r"(c1), "h"(mask) : "memory"); }
__device__ __forceinline__ void tma2d_store(const CUtensorMap* m, uint32_t src, int c0, int c1) {
  asm volatile("cp.async.bulk.tensor.2d.global.shared::cta.bulk_group [%0, {%2, %3}], [%1];" :: "l"(m), "r"(src), "r"(c0), "r"(c1) : "memory"); }
__device__ __forceinline__ void fence_async() { asm volatile("fence.proxy.async.shared::cta;" ::: "memory"); }
__device__ __forceinline__ void bar_sync(int id, int n) { asm volatile("bar.sync %0, %1;" :: "r"(id), "r"(n) : "memory"); }
__device__ __forceinline__ void bar_arrive(int id, int n) { asm volatile("bar.arrive %0, %1;" :: "r"(id), "r"(n) : "memory"); }
__device__ __forceinline__ uint32_t pack2(float lo, float hi) { uint32_t r; asm("cvt.rn.bf16x2.f32 %0, %1, %2;" : "=r"(r) : "f"(hi), "f"(lo)); return r; }
__device__ __forceinline__ uint32_t pack2_tag(float lo, float hi, uint32_t T) {
  uint32_t u = ((__float_as_uint(lo) - T + 0x10000u) & 0xFFFE0000u) + T;
  return __byte_perm(u, pack2(0.f, hi), 0x7632); }
__device__ __forceinline__ void ldsm4(uint32_t (&r)[4], uint32_t a) {
  asm volatile("ldmatrix.sync.aligned.m8n8.x4.shared.b16 {%0,%1,%2,%3}, [%4];" : "=r"(r[0]), "=r"(r[1]), "=r"(r[2]), "=r"(r[3]) : "r"(a) : "memory"); }
__device__ __forceinline__ void ldsm4t(uint32_t (&r)[4], uint32_t a) {
  asm volatile("ldmatrix.sync.aligned.m8n8.x4.trans.shared.b16 {%0,%1,%2,%3}, [%4];" : "=r"(r[0]), "=r"(r[1]), "=r"(r[2]), "=r"(r[3]) : "r"(a) : "memory"); }
__device__ __forceinline__ void stsm4(uint32_t a, uint32_t r0, uint32_t r1, uint32_t r2, uint32_t r3) {
  asm volatile("stmatrix.sync.aligned.m8n8.x4.shared.b16 [%0], {%1,%2,%3,%4};" :: "r"(a), "r"(r0), "r"(r1), "r"(r2), "r"(r3) : "memory"); }
__device__ __forceinline__ void stsm4t(uint32_t a, uint32_t r0, uint32_t r1, uint32_t r2, uint32_t r3) {
  asm volatile("stmatrix.sync.aligned.m8n8.x4.trans.shared.b16 [%0], {%1,%2,%3,%4};" :: "r"(a), "r"(r0), "r"(r1), "r"(r2), "r"(r3) : "memory"); }
__device__ __forceinline__ void lds128(uint32_t (&r)[4], uint32_t a) {
  asm volatile("ld.shared.v4.u32 {%0,%1,%2,%3}, [%4];" : "=r"(r[0]), "=r"(r[1]), "=r"(r[2]), "=r"(r[3]) : "r"(a) : "memory"); }
__device__ __forceinline__ float4 lds128f(uint32_t a) { float4 r;
  asm volatile("ld.shared.v4.f32 {%0,%1,%2,%3}, [%4];" : "=f"(r.x), "=f"(r.y), "=f"(r.z), "=f"(r.w) : "r"(a) : "memory"); return r; }
__device__ __forceinline__ float2 lds64f(uint32_t a) { float2 r;
  asm volatile("ld.shared.v2.f32 {%0,%1}, [%2];" : "=f"(r.x), "=f"(r.y) : "r"(a) : "memory"); return r; }
__device__ __forceinline__ void sts128(uint32_t a, uint32_t r0, uint32_t r1, uint32_t r2, uint32_t r3) {
  asm volatile("st.shared.v4.u32 [%0], {%1,%2,%3,%4};" :: "r"(a), "r"(r0), "r"(r1), "r"(r2), "r"(r3) : "memory"); }
__device__ __forceinline__ void sts64f(uint32_t a, float x, float y) { asm volatile("st.shared.v2.f32 [%0], {%1,%2};" :: "r"(a), "f"(x), "f"(y) : "memory"); }
__device__ __forceinline__ void sts32f(uint32_t a, float x) { asm volatile("st.shared.f32 [%0], %1;" :: "r"(a), "f"(x) : "memory"); }
__device__ __forceinline__ void mma16816(float (&d)[4], uint32_t a0, uint32_t a1, uint32_t a2, uint32_t a3, uint32_t b0, uint32_t b1) {
  asm volatile("mma.sync.aligned.m16n8k16.row.col.f32.bf16.bf16.f32 {%0,%1,%2,%3}, {%4,%5,%6,%7}, {%8,%9}, {%0,%1,%2,%3};"
    : "+f"(d[0]), "+f"(d[1]), "+f"(d[2]), "+f"(d[3]) : "r"(a0), "r"(a1), "r"(a2), "r"(a3), "r"(b0), "r"(b1)); }
__device__ __forceinline__ void mma1688(float (&d)[4], uint32_t a0, uint32_t a1, uint32_t b0) {
  asm volatile("mma.sync.aligned.m16n8k8.row.col.f32.bf16.bf16.f32 {%0,%1,%2,%3}, {%4,%5}, {%6}, {%0,%1,%2,%3};"
    : "+f"(d[0]), "+f"(d[1]), "+f"(d[2]), "+f"(d[3]) : "r"(a0), "r"(a1), "r"(b0)); }
__device__ __forceinline__ void ldx128(uint32_t (&r)[4], const void* p) {
  asm volatile("{.reg .b128 t; .reg .b64 a, b; ld.relaxed.gpu.global.b128 t, [%4]; mov.b128 {a, b}, t; mov.b64 {%0,%1}, a; mov.b64 {%2,%3}, b;}"
    : "=r"(r[0]), "=r"(r[1]), "=r"(r[2]), "=r"(r[3]) : "l"(p) : "memory"); }
__device__ __forceinline__ void ldx2x64(uint32_t (&r)[4], const void* p) {
  asm volatile("{.reg .b64 a, b; ld.relaxed.gpu.global.v2.b64 {a, b}, [%4]; mov.b64 {%0,%1}, a; mov.b64 {%2,%3}, b;}"
    : "=r"(r[0]), "=r"(r[1]), "=r"(r[2]), "=r"(r[3]) : "l"(p) : "memory"); }
__device__ __forceinline__ void stx128(void* p, uint32_t r0, uint32_t r1, uint32_t r2, uint32_t r3) {
  asm volatile("{.reg .b128 t; .reg .b64 a, b; mov.b64 a, {%1,%2}; mov.b64 b, {%3,%4}; mov.b128 t, {a, b}; st.relaxed.gpu.global.b128 [%0], t;}"
    :: "l"(p), "r"(r0), "r"(r1), "r"(r2), "r"(r3) : "memory"); }
__device__ __forceinline__ void stx64(void* p, uint32_t r0, uint32_t r1) {
  asm volatile("{.reg .b64 a; mov.b64 a, {%1,%2}; st.relaxed.gpu.global.b64 [%0], a;}" :: "l"(p), "r"(r0), "r"(r1) : "memory"); }
__device__ __forceinline__ uint32_t uni(uint32_t x) { return __shfl_sync(0xffffffffu, x, 0); }
__device__ __forceinline__ uint32_t pin(uint32_t x) { return __shfl_xor_sync(0xffffffffu, x, 0); }
__device__ __forceinline__ float ex2(float x) { float r; asm("ex2.approx.ftz.f32 %0, %1;" : "=f"(r) : "f"(x)); return r; }
__device__ __forceinline__ void wg_fence() { asm volatile("wgmma.fence.sync.aligned;" ::: "memory"); }
__device__ __forceinline__ void wg_commit() { asm volatile("wgmma.commit_group.sync.aligned;" ::: "memory"); }
template <int N> __device__ __forceinline__ void wg_wait() { asm volatile("wgmma.wait_group.sync.aligned %0;" :: "n"(N) : "memory"); }

__device__ __forceinline__ void wgmma_ss_n256_tb1(float (&d)[128], uint64_t da, uint64_t db, int sc) {
  asm volatile("{.reg .pred p; setp.ne.b32 p, %130, 0;\n"
    "wgmma.mma_async.sync.aligned.m64n256k16.f32.bf16.bf16 {%0,%1,%2,%3,%4,%5,%6,%7,%8,%9,%10,%11,%12,%13,%14,%15,%16,%17,%18,%19,%20,%21,%22,%23,%24,%25,%26,%27,%28,%29,%30,%31,%32,%33,%34,%35,%36,%37,%38,%39,%40,%41,%42,%43,%44,%45,%46,%47,%48,%49,%50,%51,%52,%53,%54,%55,%56,%57,%58,%59,%60,%61,%62,%63,%64,%65,%66,%67,%68,%69,%70,%71,%72,%73,%74,%75,%76,%77,%78,%79,%80,%81,%82,%83,%84,%85,%86,%87,%88,%89,%90,%91,%92,%93,%94,%95,%96,%97,%98,%99,%100,%101,%102,%103,%104,%105,%106,%107,%108,%109,%110,%111,%112,%113,%114,%115,%116,%117,%118,%119,%120,%121,%122,%123,%124,%125,%126,%127}, %128, %129, p, 1, 1, 0, 1;}\n"
    : "+f"(d[0]),"+f"(d[1]),"+f"(d[2]),"+f"(d[3]),"+f"(d[4]),"+f"(d[5]),"+f"(d[6]),"+f"(d[7]),"+f"(d[8]),"+f"(d[9]),"+f"(d[10]),"+f"(d[11]),"+f"(d[12]),"+f"(d[13]),"+f"(d[14]),"+f"(d[15]),"+f"(d[16]),"+f"(d[17]),"+f"(d[18]),"+f"(d[19]),"+f"(d[20]),"+f"(d[21]),"+f"(d[22]),"+f"(d[23]),"+f"(d[24]),"+f"(d[25]),"+f"(d[26]),"+f"(d[27]),"+f"(d[28]),"+f"(d[29]),"+f"(d[30]),"+f"(d[31]),"+f"(d[32]),"+f"(d[33]),"+f"(d[34]),"+f"(d[35]),"+f"(d[36]),"+f"(d[37]),"+f"(d[38]),"+f"(d[39]),"+f"(d[40]),"+f"(d[41]),"+f"(d[42]),"+f"(d[43]),"+f"(d[44]),"+f"(d[45]),"+f"(d[46]),"+f"(d[47]),"+f"(d[48]),"+f"(d[49]),"+f"(d[50]),"+f"(d[51]),"+f"(d[52]),"+f"(d[53]),"+f"(d[54]),"+f"(d[55]),"+f"(d[56]),"+f"(d[57]),"+f"(d[58]),"+f"(d[59]),"+f"(d[60]),"+f"(d[61]),"+f"(d[62]),"+f"(d[63]),"+f"(d[64]),"+f"(d[65]),"+f"(d[66]),"+f"(d[67]),"+f"(d[68]),"+f"(d[69]),"+f"(d[70]),"+f"(d[71]),"+f"(d[72]),"+f"(d[73]),"+f"(d[74]),"+f"(d[75]),"+f"(d[76]),"+f"(d[77]),"+f"(d[78]),"+f"(d[79]),"+f"(d[80]),"+f"(d[81]),"+f"(d[82]),"+f"(d[83]),"+f"(d[84]),"+f"(d[85]),"+f"(d[86]),"+f"(d[87]),"+f"(d[88]),"+f"(d[89]),"+f"(d[90]),"+f"(d[91]),"+f"(d[92]),"+f"(d[93]),"+f"(d[94]),"+f"(d[95]),"+f"(d[96]),"+f"(d[97]),"+f"(d[98]),"+f"(d[99]),"+f"(d[100]),"+f"(d[101]),"+f"(d[102]),"+f"(d[103]),"+f"(d[104]),"+f"(d[105]),"+f"(d[106]),"+f"(d[107]),"+f"(d[108]),"+f"(d[109]),"+f"(d[110]),"+f"(d[111]),"+f"(d[112]),"+f"(d[113]),"+f"(d[114]),"+f"(d[115]),"+f"(d[116]),"+f"(d[117]),"+f"(d[118]),"+f"(d[119]),"+f"(d[120]),"+f"(d[121]),"+f"(d[122]),"+f"(d[123]),"+f"(d[124]),"+f"(d[125]),"+f"(d[126]),"+f"(d[127])
    : "l"(da), "l"(db), "r"(sc));
}

__device__ __forceinline__ void wgmma_ss_n128_tb1(float (&d)[64], uint64_t da, uint64_t db, int sc) {
  asm volatile("{.reg .pred p; setp.ne.b32 p, %66, 0;\n"
    "wgmma.mma_async.sync.aligned.m64n128k16.f32.bf16.bf16 {%0,%1,%2,%3,%4,%5,%6,%7,%8,%9,%10,%11,%12,%13,%14,%15,%16,%17,%18,%19,%20,%21,%22,%23,%24,%25,%26,%27,%28,%29,%30,%31,%32,%33,%34,%35,%36,%37,%38,%39,%40,%41,%42,%43,%44,%45,%46,%47,%48,%49,%50,%51,%52,%53,%54,%55,%56,%57,%58,%59,%60,%61,%62,%63}, %64, %65, p, 1, 1, 0, 1;}\n"
    : "+f"(d[0]),"+f"(d[1]),"+f"(d[2]),"+f"(d[3]),"+f"(d[4]),"+f"(d[5]),"+f"(d[6]),"+f"(d[7]),"+f"(d[8]),"+f"(d[9]),"+f"(d[10]),"+f"(d[11]),"+f"(d[12]),"+f"(d[13]),"+f"(d[14]),"+f"(d[15]),"+f"(d[16]),"+f"(d[17]),"+f"(d[18]),"+f"(d[19]),"+f"(d[20]),"+f"(d[21]),"+f"(d[22]),"+f"(d[23]),"+f"(d[24]),"+f"(d[25]),"+f"(d[26]),"+f"(d[27]),"+f"(d[28]),"+f"(d[29]),"+f"(d[30]),"+f"(d[31]),"+f"(d[32]),"+f"(d[33]),"+f"(d[34]),"+f"(d[35]),"+f"(d[36]),"+f"(d[37]),"+f"(d[38]),"+f"(d[39]),"+f"(d[40]),"+f"(d[41]),"+f"(d[42]),"+f"(d[43]),"+f"(d[44]),"+f"(d[45]),"+f"(d[46]),"+f"(d[47]),"+f"(d[48]),"+f"(d[49]),"+f"(d[50]),"+f"(d[51]),"+f"(d[52]),"+f"(d[53]),"+f"(d[54]),"+f"(d[55]),"+f"(d[56]),"+f"(d[57]),"+f"(d[58]),"+f"(d[59]),"+f"(d[60]),"+f"(d[61]),"+f"(d[62]),"+f"(d[63])
    : "l"(da), "l"(db), "r"(sc));
}

template <int BN> struct WG;
template <> struct WG<256> { static __device__ __forceinline__ void mma(float (&d)[128], uint64_t a, uint64_t b, int sc) { wgmma_ss_n256_tb1(d, a, b, sc); } };
template <> struct WG<128> { static __device__ __forceinline__ void mma(float (&d)[64], uint64_t a, uint64_t b, int sc) { wgmma_ss_n128_tb1(d, a, b, sc); } };

struct GemmMaps { CUtensorMap a, b[3], c; };
template <int BN, int STAGES>
__global__ void __cluster_dims__(2, 1, 1) __launch_bounds__(384, 1)
gemm_kernel(const __grid_constant__ GemmMaps maps, int tilesM, int tilesN, int kblocks, int nPerB, uint4* __restrict__ clearX) {
  extern __shared__ __align__(1024) uint8_t smem_raw[];
  constexpr int STAGE_BYTES = 16384 + BN * 128;
  constexpr int NBOX = BN / 64;
  const uint32_t sbase = (smem_u32(smem_raw) + 1023) & ~1023u;
  const uint32_t sEpi = sbase + STAGES * STAGE_BYTES;
  const uint32_t sBar = sEpi + 32768;
  const int warp = threadIdx.x >> 5, lane = threadIdx.x & 31, wg = warp >> 2;
  uint32_t crank; asm("mov.u32 %0, %%cluster_ctarank;" : "=r"(crank));
#define GT(k)
  const int npairs = (tilesM >> 1) * tilesN, pair0 = blockIdx.x >> 1, pstep = gridDim.x >> 1;
  if (threadIdx.x == 256) {
    asm volatile("prefetch.tensormap [%0];" :: "l"(&maps.b[0]) : "memory");
    for (int i = 0; i < STAGES; i++) { mbar_init(sBar + 8 * i, 1); mbar_init(sBar + 8 * (STAGES + i), 4); }
    asm volatile("fence.mbarrier_init.release.cluster;" ::: "memory");
    asm volatile("barrier.cluster.arrive.relaxed;" ::: "memory");
    for (int i = 0; i < STAGES; i++) {
      mbar_expect_tx(sBar + 8 * i, STAGE_BYTES);
      tma2d(sbase + i * STAGE_BYTES, &maps.a, i * 64, ((pair0 % (tilesM >> 1)) * 2 + crank) * 128, sBar + 8 * i);
    }
    asm volatile("prefetch.tensormap [%0];" :: "l"(&maps.c) : "memory");
  } else asm volatile("barrier.cluster.arrive.relaxed;" ::: "memory");
  asm volatile("barrier.cluster.wait.acquire;" ::: "memory");
  __syncwarp();
  if (wg == 2) {
    asm volatile("setmaxnreg.dec.sync.aligned.u32 40;");
    if (warp > 8) {
      __nanosleep(4000);
      for (int i = blockIdx.x * 96 + threadIdx.x - 288; i < (int)(sizeof(Xchg) / 16); i += gridDim.x * 96) clearX[i] = make_uint4(0, 0, 0, 0);
    }
    if (warp == 8 && lane == 0) {
      int st = 0, ph = 1;
      for (int p = pair0; p < npairs; p += pstep) {
        const int tm = (p % (tilesM >> 1)) * 2 + crank, tn = p / (tilesM >> 1);
        const CUtensorMap* mb = &maps.b[tn / nPerB];
        const int n0 = (tn % nPerB) * BN;
        for (int kb = 0; kb < kblocks; kb++) {
          const uint32_t a = sbase + st * STAGE_BYTES, full = sBar + 8 * st;
          if (p > pair0 || kb >= STAGES) {
            mbar_wait(sBar + 8 * (STAGES + st), ph);
            mbar_expect_tx(full, STAGE_BYTES);
            tma2d(a, &maps.a, kb * 64, tm * 128, full);
          }
#pragma unroll
          for (int i = 0; i < NBOX / 2; i++) {
            const int bx = crank * (NBOX / 2) + i;
            tma2d_mc(a + 16384 + bx * 8192, mb, n0 + bx * 64, kb * 64, full, (uint16_t)3);
          }
          if (++st == STAGES) { st = 0; ph ^= 1; }
        }
      }
      for (int i = 0; i < STAGES; i++) { mbar_wait(sBar + 8 * (STAGES + st), ph); if (++st == STAGES) { st = 0; ph ^= 1; } }
    }
  } else {
    asm volatile("setmaxnreg.inc.sync.aligned.u32 232;");
    int st = 0, ph = 0;
    float acc[BN / 2];
    const uint64_t descA0 = (uint64_t)(((sbase + wg * 8192) & 0x3FFFF) >> 4) | (1ull << 16) | (64ull << 32) | (1ull << 62);
    const uint64_t descB0 = (uint64_t)(((sbase + 16384) & 0x3FFFF) >> 4) | (512ull << 16) | (64ull << 32) | (1ull << 62);
    const uint32_t epi = sEpi + wg * 16384;
    for (int p = pair0; p < npairs; p += pstep) {
      const int tm = (p % (tilesM >> 1)) * 2 + crank, tn = p / (tilesM >> 1);
      int prev = -1;
      for (int kb = 0; kb < kblocks; kb++) {
        mbar_wait(sBar + 8 * st, ph);
        if ((kb & 15) == 0) { GT(kb >> 4); }
        wg_fence();
        const uint64_t so = (uint64_t)(st * (STAGE_BYTES >> 4));
#pragma unroll
        for (int k = 0; k < 4; k++) WG<BN>::mma(acc, descA0 + so + k * 2, descB0 + so + k * 128, kb | k);
        wg_commit();
        if (prev >= 0) {
          wg_wait<1>();
          if ((threadIdx.x & 127) < 2) mbar_arrive_cluster(sBar + 8 * (STAGES + prev), threadIdx.x & 1);
        }
        prev = st;
        if (++st == STAGES) { st = 0; ph ^= 1; }
      }
      wg_wait<0>();
      if ((threadIdx.x & 127) < 2) mbar_arrive_cluster(sBar + 8 * (STAGES + prev), threadIdx.x & 1);
      GT(4);
#pragma unroll
      for (int r = 0; r < BN / 128; r++) {
        if (r || p > pair0) {
          if ((threadIdx.x & 127) == 0) asm volatile("cp.async.bulk.wait_group.read 0;" ::: "memory");
          bar_sync(1 + wg, 128);
        }
        const int row = (warp & 3) * 16 + (lane & 15);
#pragma unroll
        for (int i = 0; i < 8; i++) {
          const int c = 2 * (i & 3) + (lane >> 4);
          const float* q = &acc[r * 64 + i * 8];
          stsm4(epi + (i >> 2) * 8192 + row * 128 + ((c ^ (row & 7)) << 4), pack2(q[0], q[1]), pack2(q[2], q[3]), pack2(q[4], q[5]), pack2(q[6], q[7]));
        }
        fence_async();
        bar_sync(1 + wg, 128);
        if ((threadIdx.x & 127) == 0) {
          tma2d_store(&maps.c, epi, tn * BN + r * 128, tm * 128 + wg * 64);
          tma2d_store(&maps.c, epi + 8192, tn * BN + r * 128 + 64, tm * 128 + wg * 64);
          asm volatile("cp.async.bulk.commit_group;" ::: "memory");
        }
      }
    }
    GT(5);
    if ((threadIdx.x & 127) == 0) asm volatile("cp.async.bulk.wait_group.read 0;" ::: "memory");
    GT(6);
  }
}

struct Dft { uint32_t m[2][2][2][4]; };
template <bool P4> __device__ __forceinline__ int fidx(int tile, int x) { return P4 ? 4 * (x >> 1) + 2 * (tile & 1) + (x & 1) + 16 * (tile >> 1) : x + 8 * tile; }
__device__ __forceinline__ float2 cis(int k, int n) {
  k &= n - 1; if (2 * k > n) k -= n;
  const float a = (float)k * (6.283185307179586f / (float)n);
  return make_float2(__cosf(a), __sinf(a));
}
template <bool OUT4> __device__ __forceinline__ void make_dft(Dft& D, int g, int t) {
#pragma unroll
  for (int q = 0; q < 16; q++) {
    const int b = q >> 3, u = (q >> 2) & 1, r = (q >> 1) & 1, v = q & 1;
    const float2 w = cis(fidx<OUT4>(v, g) * fidx<false>(2 * u + r, 2 * t + b), 32);
    D.m[b][u][0][q & 3] = pack2(w.x, w.y); D.m[b][u][1][q & 3] = pack2(-w.y, w.x);
  }
}
__device__ __forceinline__ void mma_dc(float (&d)[4], uint32_t a0, uint32_t a1, uint32_t a2, uint32_t a3, uint32_t b0, uint32_t b1, const float (&c)[4]) {
  asm("mma.sync.aligned.m16n8k16.row.col.f32.bf16.bf16.f32 {%0,%1,%2,%3}, {%4,%5,%6,%7}, {%8,%9}, {%10,%11,%12,%13};"
    : "=f"(d[0]), "=f"(d[1]), "=f"(d[2]), "=f"(d[3]) : "r"(a0), "r"(a1), "r"(a2), "r"(a3), "r"(b0), "r"(b1), "f"(c[0]), "f"(c[1]), "f"(c[2]), "f"(c[3])); }
__device__ __forceinline__ void dft_b(const Dft& D, const uint32_t (&x)[2][4], float (&o)[2][8]) {
#pragma unroll
  for (int ri = 0; ri < 2; ri++) {
    float z[4] = {0.f, 0.f, 0.f, 0.f}, e[4], p[4];
    mma_dc(e, D.m[0][0][ri][0], D.m[0][0][ri][1], D.m[0][0][ri][2], D.m[0][0][ri][3], x[0][0], x[0][1], z);
    mma_dc(e, D.m[0][1][ri][0], D.m[0][1][ri][1], D.m[0][1][ri][2], D.m[0][1][ri][3], x[0][2], x[0][3], e);
    mma_dc(p, D.m[1][0][ri][0], D.m[1][0][ri][1], D.m[1][0][ri][2], D.m[1][0][ri][3], x[1][0], x[1][1], e);
    mma_dc(p, D.m[1][1][ri][0], D.m[1][1][ri][1], D.m[1][1][ri][2], D.m[1][1][ri][3], x[1][2], x[1][3], p);
#pragma unroll
    for (int q = 0; q < 4; q++) { o[ri][q] = p[q]; o[ri][4 + q] = fmaf(2.f, e[q], -p[q]); }
  }
}
__device__ __forceinline__ void dft_a(const uint32_t (&m)[2][2][4], const uint32_t (&x0)[2][4], const uint32_t (&x1)[2][4], float (&o)[2][8]) {
#pragma unroll
  for (int ri = 0; ri < 2; ri++) {
    float z[4] = {0.f, 0.f, 0.f, 0.f}, e[4], p[4];
    mma_dc(e, x0[0][0], x1[0][0], x0[0][1], x1[0][1], m[0][ri][0], m[0][ri][1], z);
    mma_dc(e, x0[0][2], x1[0][2], x0[0][3], x1[0][3], m[0][ri][2], m[0][ri][3], e);
    mma_dc(p, x0[1][0], x1[1][0], x0[1][1], x1[1][1], m[1][ri][0], m[1][ri][1], e);
    mma_dc(p, x0[1][2], x1[1][2], x0[1][3], x1[1][3], m[1][ri][2], m[1][ri][3], p);
#pragma unroll
    for (int q = 0; q < 4; q++) { o[ri][q] = p[q]; o[ri][4 + q] = fmaf(2.f, e[q], -p[q]); }
  }
}
__device__ __forceinline__ uint32_t twid(float re, float im, float c, float s) { return pack2(fmaf(re, c, im * s), fmaf(im, c, -re * s)); }
__device__ __forceinline__ void cpa16(uint32_t d, const void* s) { asm volatile("cp.async.cg.shared.global [%0], [%1], 16;" :: "r"(d), "l"(s) : "memory"); }
__device__ __forceinline__ void sts32(uint32_t a, uint32_t x) { asm volatile("st.shared.u32 [%0], %1;" :: "r"(a), "r"(x) : "memory"); }
__device__ __forceinline__ void cpa_commit() { asm volatile("cp.async.commit_group;" ::: "memory"); }
template <int N> __device__ __forceinline__ void cpa_wait() { asm volatile("cp.async.wait_group %0;" :: "n"(N) : "memory"); }
__device__ __forceinline__ uint32_t lds32(uint32_t a) { uint32_t r; asm volatile("ld.shared.u32 %0, [%1];" : "=r"(r) : "r"(a) : "memory"); return r; }
#define FMID 0
constexpr int F_TP = 4112, F_TSZ = 8 * F_TP;

__device__ __forceinline__ uint32_t ldnc32(const void* p) { uint32_t v; asm volatile("ld.global.nc.b32 %0, [%1];" : "=r"(v) : "l"(p) : "memory"); return v; }
template <class F>
__device__ __forceinline__ void fft_wprep(const bf16* __restrict__ wr, const bf16* __restrict__ wi, int cta, F&& mid) {
  const int tid = threadIdx.x, g = (cta >> 1) & 7, c = (cta >> 4) & 3, t = 2 * (cta & 1) + (tid & 1);
  const int k0 = g + 8 * (cta >> 6) + 32 * (8 * c + 2 * t), l0 = (tid & ~1) + (g & 1);
  uint32_t a[4][4], b[4][4];
#pragma unroll
  for (int q = 0; q < 16; q++) {
    const int o = (k0 + 16 * (q >> 3) + 32 * ((q >> 1) & 1) + 1024 * (q & 1)) * 513 + l0 + 256 * ((q >> 2) & 1);
    a[q >> 2][q & 3] = ldnc32(wr + o);
    b[q >> 2][q & 3] = ldnc32(wi + o);
  }
  const int e = cta * 32 + (tid & 31), lh = (e >> 11) * 512, k = e & 2047, k2 = (k >> 5) & 31;
  uint32_t hz[4];
#pragma unroll
  for (int q = 0; q < 4; q++) asm volatile("ld.global.nc.u16 %0, [%1];" : "=r"(hz[q]) : "l"((q < 2 ? wr : wi) + (q & 1 ? (2048 - k) & 2047 : k) * 513 + lh) : "memory");
  mid();
  uint4* dst = g_wt + l0 * 512 + cta * 2 + (tid & 1);
#pragma unroll
  for (int q = 0; q < 8; q++) {
    const int hf = q >> 1, l = l0 + 256 * (hf & 1) + (q & 1);
    const uint32_t sel = (q & 1) ? 0x7632 : 0x5410;
    if (l & 511) dst[(256 * (hf & 1) + (q & 1)) * 512 + 256 * (q >> 2)] = make_uint4(__byte_perm(a[hf][0], b[hf][0], sel), __byte_perm(a[hf][1], b[hf][1], sel),
                                                                                   __byte_perm(a[hf][2], b[hf][2], sel), __byte_perm(a[hf][3], b[hf][3], sel));
  }
  if (tid < 32) reinterpret_cast<uint32_t*>(g_wt)[(64 * ((k >> 3) & 3) + 16 * (k2 >> 3) + 2 * (k & 7) + ((k2 >> 2) & 1)) * 8 + lh * 2048 + 2 * (k2 & 3) + (k >> 10)] =
      pack2(0.5f * (__uint_as_float(hz[0] << 16) + __uint_as_float(hz[1] << 16)), 0.5f * (__uint_as_float(hz[2] << 16) - __uint_as_float(hz[3] << 16)));
}

template <class F>
__device__ __forceinline__ void fft_rows_fwd(const bf16* __restrict__ x, const bf16* __restrict__ wr, const bf16* __restrict__ wi, uint32_t tb, int it, F&& mid) {
  const int warp = threadIdx.x >> 5, lane = threadIdx.x & 31, g = lane >> 2, t = lane & 3;
  const uint32_t in = tb + warp * 4096;
  const uint32_t f0 = in + (lane >> 3) * 256 + (((lane & 7) ^ (2 * (lane >> 3))) << 4);
  const bf16* src = x + ((256 * (warp & 3) + 64 * (warp >> 2) + 128 * (it & 1) + 32 * ((it >> 4) & 1) + 8 * (it >> 5) + ((it >> 1) & 7)) * 2048 + lane * 8);
#pragma unroll
  for (int q = 0; q < 8; q++) cpa16((f0 ^ ((q >> 2) * 144)) + (q & 3) * 1024, src + q * 256);
  cpa_commit();
  Dft D;
  float2 tw[4][8];
  fft_wprep(wr, wi, it, [&]() {
    if (FMID == 0) mid();
    make_dft<true>(D, g, t);
#pragma unroll
    for (int q = 0; q < 32; q++) {
      tw[q >> 3][q & 7] = cis(fidx<true>((q >> 1) & 3, g) * fidx<false>(q >> 3, 2 * t + (q & 1)), 1024);
      if (FMID) asm volatile("" : "+f"(tw[q >> 3][q & 7].x), "+f"(tw[q >> 3][q & 7].y) :: "memory");
    }
    if (FMID == 1) mid();
  });
  if (FMID == 2) mid();
  cpa_wait<0>(); __syncwarp();
  uint32_t a[4][2][4], y[4][2][4];
#pragma unroll
  for (int q = 0; q < 8; q++) ldsm4t(a[q & 3][q >> 2], (in + lane * 128 + ((lane & 7) << 4)) ^ (q << 4));
  float o[2][8];
#pragma unroll
  for (int i = 0; i < 4; i++) {
    dft_b(D, a[i], o);
#pragma unroll
    for (int q = 0; q < 8; q++) y[q >> 1][q & 1][i] = twid(o[0][q], o[1][q], tw[i][q].x, tw[i][q].y);
  }
  __syncthreads();
  const uint32_t w0 = tb + warp * F_TP + fidx<true>(0, g) * 128 + t * 16 + ((g & 1) << 6), wz = (g & 1) ? -64 : 64;
#pragma unroll
  for (int z = 0; z < 2; z++) {
    float o2[2][8];
    dft_b(D, y[2 * z], o); dft_b(D, y[2 * z + 1], o2);
#pragma unroll
    for (int i = 0; i < 4; i++) {
      const float sg = i < 2 ? 1.f : -1.f;
      sts128(w0 + z * wz + fidx<true>(i, 0) * 128, pack2(o[0][2 * i], sg * o[1][2 * i]), pack2(o[0][2 * i + 1], sg * o[1][2 * i + 1]),
             pack2(o2[0][2 * i], sg * o2[1][2 * i]), pack2(o2[0][2 * i + 1], sg * o2[1][2 * i + 1]));
    }
  }
  __syncthreads();
  const uint32_t ra = tb + (lane & 1) * 4 * F_TP + ((lane >> 1) + 16 * (warp ^ ((warp >> 1) & 1))) * 4;
  uint4* dst = g_y + (threadIdx.x >> 1) * 256 + (lane & 1) + it * 2;
#pragma unroll
  for (int q = 0; q < 8; q++) { const uint32_t r = ra + q * 512; dst[q * 32768] = make_uint4(lds32(r), lds32(r + F_TP), lds32(r + 2 * F_TP), lds32(r + 3 * F_TP)); }
}

template <class F>
__device__ __forceinline__ void fft_cols(uint32_t sb, int cta, int ncta, F&& ready) {
  const int warp = threadIdx.x >> 5, lane = threadIdx.x & 31, g = lane >> 2, t = lane & 3;
  const uint32_t in = sb + warp * 16384 + lane * 16, tab = sb + 131072 + lane * 16;
  auto fetch_y = [&](int l) {
#pragma unroll
    for (int q = 0; q < 16; q++) cpa16(in + q * 512, g_y + (q < 8 ? l : (1024 - l) & 1023) * 256 + (q & 7) * 32 + lane);
  };
  auto fetch_w = [&](int l) {
#pragma unroll
    for (int q = 0; q < 16; q++) cpa16(in + 8192 + q * 512, g_wt + l * 512 + q * 32 + lane);
  };
  const int l0 = cta * 8 + warp, dl = ncta * 8;
  Dft D; make_dft<false>(D, g, t);
#pragma unroll
  for (int q = 2 * warp; q < 2 * warp + 2; q++) {
    const int r = fidx<false>(q & 3, g), c = fidx<false>(q >> 2, 2 * t);
    const float2 w0 = cis(r * c, 1024), w1 = cis(r * c + r, 1024), p0 = cis(r + 32 * c, 2048), p1 = cis(r + 32 * c + 32, 2048);
    sts128(tab + q * 512, __float_as_uint(w0.x), __float_as_uint(w0.y), __float_as_uint(w1.x), __float_as_uint(w1.y));
    sts128(tab + 8192 + q * 512, __float_as_uint(p0.x), __float_as_uint(p0.y), __float_as_uint(p1.x), __float_as_uint(p1.y));
  }
  if (warp == 0) {
#pragma unroll
    for (int q = 0; q < 8; q++) {
      const int v = q >> 2, b = (q >> 1) & 1, ri = q & 1;
      sts128(tab + 16384 + q * 512, D.m[b][0][ri][v], D.m[b][0][ri][v + 2], D.m[b][1][ri][v], D.m[b][1][ri][v + 2]);
    }
  }
  ready();
  fetch_y(l0); cpa_commit();
  fetch_w(l0); cpa_commit();
#pragma unroll 1
  for (int l = l0; l <= 512; l += dl) {
    uint32_t a[2][4][2][4], y[2][4][2][4];
    float o[2][2][8];
    cpa_wait<1>();
#pragma unroll
    for (int q = 0; q < 16; q++) lds128(a[q >> 3][(q >> 1) & 3][q & 1], in + q * 512);
    if (!(l & 511)) {
      const uint32_t m0 = l ? 0x80000000u : 0u;
#pragma unroll
      for (int q = 0; q < 32; q++) { a[0][q >> 3][(q >> 2) & 1][q & 3] ^= m0; a[1][q >> 3][(q >> 2) & 1][q & 3] ^= m0 ^ 0x80000000u; }
    }
    auto first = [&]() {
#pragma unroll
      for (int i = 0; i < 4; i++) {
        dft_b(D, a[0][i], o[0]); dft_b(D, a[1][i], o[1]);
#pragma unroll
        for (int r = 0; r < 4; r++) {
          const float4 w = lds128f(tab + (4 * i + r) * 512);
#pragma unroll
          for (int s = 0; s < 2; s++) {
            y[s][r][0][i] = twid(o[s][0][2 * r], o[s][1][2 * r], w.x, w.y);
            y[s][r][1][i] = twid(o[s][0][2 * r + 1], o[s][1][2 * r + 1], w.z, w.w);
          }
        }
      }
    };
    first();
    if (l + dl <= 512) fetch_y(l + dl);
    cpa_commit();
    cpa_wait<1>();
#pragma unroll
    for (int zv = 0; zv < 4; zv++) {
      const int z = zv >> 1, v = zv & 1;
      uint32_t m[2][2][4];
#pragma unroll
      for (int q = 0; q < 4; q++) lds128(m[q >> 1][q & 1], tab + 16384 + (4 * v + q) * 512);
      dft_a(m, y[0][2 * z], y[0][2 * z + 1], o[0]); dft_a(m, y[1][2 * z], y[1][2 * z + 1], o[1]);
#pragma unroll
      for (int q = 0; q < 4; q++) {
        const int i = 2 * z + (q & 1), c = v + (q & 2);
        uint32_t w[4]; lds128(w, in + 8192 + (4 * i + c) * 512);
        const float4 ph = lds128f(tab + 8192 + (4 * c + i) * 512);
#pragma unroll
        for (int b = 0; b < 2; b++) {
          const float cs = b ? ph.z : ph.x, sn = b ? ph.w : ph.y;
          const float r1 = __uint_as_float(w[2 * b] << 16), i1 = __uint_as_float(w[2 * b] & 0xFFFF0000u);
          const float r2 = __uint_as_float(w[2 * b + 1] << 16), i2 = __uint_as_float(w[2 * b + 1] & 0xFFFF0000u);
          const float Sr = r1 + r2, Si = i1 + i2, Dr = r1 - r2, Di = i1 - i2;
          const float ar = fmaf(-Dr, sn, Sr), ai = fmaf(-Di, sn, Si), dr = fmaf(Dr, sn, Sr), di = fmaf(Di, sn, Si), br = -Di * cs, bi = Dr * cs;
          const float Ar = o[0][0][2 * q + b], Ai = o[0][1][2 * q + b], Br = o[1][0][2 * q + b], Bi = o[1][1][2 * q + b];
          a[0][i][b][c] = pack2(fmaf(ar, Ai, fmaf(ai, Ar, fmaf(br, Bi, bi * Br))), fmaf(ar, Ar, fmaf(-ai, Ai, fmaf(br, Br, -bi * Bi))));
          a[1][i][b][c] = pack2(fmaf(dr, Bi, fmaf(di, Br, fmaf(-br, Ai, -bi * Ar))), fmaf(dr, Br, fmaf(-di, Bi, fmaf(-br, Ar, bi * Ai))));
        }
      }
    }
    if (l + dl <= 512) fetch_w(l + dl);
    cpa_commit();
    first();
#pragma unroll
    for (int s = 0; s < 2; s++) {
      uint4* dst = g_y + (s ? (1024 - l) & 1023 : l) * 256 + lane;
      const float sg = s ? -1.f : 1.f;
#pragma unroll
      for (int i = 0; i < 4; i++) {
        dft_b(D, y[s][i], o[0]);
#pragma unroll
        for (int b = 0; b < 2; b++)
          dst[(2 * i + b) * 32] = make_uint4(pack2(sg * o[0][0][b], o[0][1][b]), pack2(sg * o[0][0][2 + b], o[0][1][2 + b]),
                                             pack2(sg * o[0][0][4 + b], o[0][1][4 + b]), pack2(sg * o[0][0][6 + b], o[0][1][6 + b]));
      }
    }
  }
}

template <class F>
__device__ __forceinline__ void fft_rows_inv(const CUtensorMap* om, uint32_t sb, int cta, int ncta, F&& ready) {
  const int warp = threadIdx.x >> 5, lane = threadIdx.x & 31, g = lane >> 2, t = lane & 3, wg = warp >> 2, w4 = warp & 3;
  const uint32_t tb = sb + 32768 + wg * 2 * F_TSZ;
  const uint4* src = g_y + pin((256 * ((lane >> 1) & 3) + 64 * (lane >> 3) + 8 * w4) * 256 + (lane & 1));
  const uint32_t wa = pin(tb + (lane & 1) * 4 * F_TP + w4 * 1024 + (lane >> 1) * 4);
  uint4 pf[8];
  auto fetch = [&](int it, int hf) {
#pragma unroll
    for (int q = 0; q < 8; q++) pf[q] = __ldcg(src + (it * 2 + hf * 8192) + q * 256);
  };
  auto put = [&](uint32_t off) {
#pragma unroll
    for (int q = 0; q < 8; q++) {
      sts32(wa + off + q * 64, pf[q].x); sts32(wa + off + q * 64 + F_TP, pf[q].y);
      sts32(wa + off + q * 64 + 2 * F_TP, pf[q].z); sts32(wa + off + q * 64 + 3 * F_TP, pf[q].w);
    }
  };
  const int it0 = 2 * cta + wg;
  Dft D; make_dft<false>(D, g, t);
  float2 tw[4][8];
#pragma unroll
  for (int q = 0; q < 32; q++) {
    tw[q >> 3][q & 7] = cis(fidx<false>((q >> 1) & 3, g) * fidx<false>(q >> 3, 2 * t + (q & 1)), 1024);
    tw[q >> 3][q & 7].x *= 1.f / 2097152.f; tw[q >> 3][q & 7].y *= 1.f / 2097152.f;
    asm volatile("" : "+f"(tw[q >> 3][q & 7].x), "+f"(tw[q >> 3][q & 7].y) :: "memory");
  }
  ready();
  fetch(it0, 0); put(0); fetch(it0, 1); put(512);
  const uint32_t la = pin(tb + w4 * F_TP + lane * 16), ob = uni(sb + warp * 4096);
  const uint32_t oa = pin(ob + (lane >> 1) * 128 + (((4 * (lane & 1)) ^ ((lane >> 1) & 7)) << 4));
#pragma unroll 1
  for (int n = 0;; n++) {
    const int it = it0 + (n >> 1) * 2 * ncta, hf = n & 1, buf = (n >> 1) & 1;
    if (it >= 128) break;
    if (!hf) bar_sync(1 + wg, 128);
    uint32_t a[4][2][4], y[4][2][4];
#pragma unroll
    for (int q = 0; q < 8; q++) lds128(a[q >> 1][q & 1], la + buf * F_TSZ + hf * 4 * F_TP + q * 512);
    fetch(min(it + 2 * ncta, 127), hf);
    float o[2][8];
#pragma unroll
    for (int i = 0; i < 4; i++) {
      dft_b(D, a[i], o);
#pragma unroll
      for (int q = 0; q < 8; q++) y[q >> 1][q & 1][i] = twid(o[0][q], o[1][q], tw[i][q].x, tw[i][q].y);
    }
    if (lane == 0) asm volatile("cp.async.bulk.wait_group.read 0;" ::: "memory");
    __syncwarp();
#pragma unroll
    for (int c = 0; c < 4; c++) {
      dft_b(D, y[c], o);
#pragma unroll
      for (int ri = 0; ri < 2; ri++)
        stsm4((oa ^ (c << 4)) + (1 - ri) * 2048, pack2(o[ri][0], o[ri][1]), pack2(o[ri][2], o[ri][3]), pack2(o[ri][4], o[ri][5]), pack2(o[ri][6], o[ri][7]));
    }
    fence_async();
    __syncwarp();
    if (lane == 0) {
      const int m = 256 * w4 + 32 * ((it >> 1) & 7) + 8 * (it >> 5) + 4 * (it & 1) + 2 * hf + ((it >> 4) & 1);
      asm volatile("cp.async.bulk.tensor.3d.global.shared::cta.bulk_group [%0, {0, 0, %2}], [%1];" :: "l"(om), "r"(ob), "r"(2 * m) : "memory");
      asm volatile("cp.async.bulk.commit_group;" ::: "memory");
    }
    put((buf ^ 1) * F_TSZ + hf * 512);
  }
  if (lane == 0) asm volatile("cp.async.bulk.wait_group 0;" ::: "memory");
}
__device__ __forceinline__ void grid_arrive(unsigned* ctr) {
  __syncthreads();
  if (threadIdx.x == 0) { __threadfence(); atomicAdd(ctr, 1u); }
}
__device__ __forceinline__ void grid_wait(unsigned* ctr, unsigned n) {
  if (threadIdx.x == 224) {
    int it = 0;
    while (*reinterpret_cast<volatile unsigned*>(ctr) < n) { __nanosleep(100); if (++it > SPIN_LIMIT) { g_err = 3; break; } }
    __threadfence();
  }
  __syncthreads();
}

struct RecMaps { CUtensorMap wq, wk, wv, wo, x, k, q, v, fo; };
#define NSW 16
#define EXP 0
#define NPB 3
#define NPB0 3
#define NPC 0
#define WOP 2
#define HOME 7
#define DL0 14
#define PD1 4
#define NE4 6
#define NE6 0
#define NA4 14
#define NA6 18
#define NB1 24
#define TQL 7
#define NQ 16
#define TQP (NQ - 1)
#define OXPOS 4
#define KVPOS 2
#define NK0 0
#define FLPOS 1
#define XWPOS 10
#define FSPOS 28
#define RL0 4
#define RLS 6
#define RLB 4
#define VL0 3
#define RI 9
#define RJ 8
#define NPRE 22
#define PFD 4
#define PD0 4
#define VB NV0
#define NPA 0
#define N1 16
#define DL1 16
#define PACE 0
#define RE0 0
#define RE1 0
#define RP1 23
#define UNP 1
#define X2 2
#define X3 2
#define SPOS 2
#ifndef NV0
#define NV0 4
#endif
#define TGP 3
#define FENP 0
#define LW0 8
#define X1 4
#define X0 4
constexpr int R_WO = 0, R_X = 65536, R_MEM = 131072, R_WC = 147456, R_RED = R_WC + NSW * 2048, R_O = R_RED, R_S = R_O + 2048, R_P = R_S + 3072, R_STAGE = R_P + 2048,
              R_K = R_STAGE + 8192, R_Q = R_K + 8192, R_V = R_Q + 2048, R_ID = R_V + 16384, R_T = R_ID + 512, R_DST = R_T + 512, R_RD = R_DST + 2048, R_BAR = R_RD + 2048, R_TS = R_BAR + 128,
              R_TOTAL = R_TS;
#define TS(i)
#define LOG(i, v)
constexpr int B_KV = R_BAR, B_W = R_BAR + 8, B_X = R_BAR + 80, B_PK = R_BAR + 24, B_C = R_BAR + 32, B_B = R_BAR + 40, B_DUE = R_BAR + 48, B_ONE = R_BAR + 64;
#define DLY_A 150
#define DLY_V 150
#define DLY_C 200
#define DLY_L 90
#define NS_B 1120
#define NS_C 1728
#define NS_P 2624
#define NS_V 128
#define NS_F 896
#define NS_K 128
#define NS_M 32
#define NS_X 128
#define MG_Z 0x00010206
#define MG_Y 0x00010512
#define NS_PEN 1024
__device__ __forceinline__ float rcp(float x) { float r; asm("rcp.approx.ftz.f32 %0, %1;" : "=f"(r) : "f"(x)); return r; }
__device__ __forceinline__ uint32_t movm(uint32_t a) { uint32_t d; asm volatile("movmatrix.sync.aligned.m8n8.trans.b16 %0, %1;" : "=r"(d) : "r"(a)); return d; }
__device__ __forceinline__ uint32_t hadd2(uint32_t a, uint32_t b) { uint32_t d; asm("add.rn.bf16x2 %0, %1, %2;" : "=r"(d) : "r"(a), "r"(b)); return d; }
__device__ __forceinline__ void mma_a(float (&d)[4], const uint32_t (&a)[4], uint32_t b0, uint32_t b1) { mma16816(d, a[0], a[1], a[2], a[3], b0, b1); }
__device__ __forceinline__ bool elect() {
  uint32_t p; asm volatile("{.reg .pred p; elect.sync _|p, 0xffffffff; selp.u32 %0, 1, 0, p;}" : "=r"(p)); return p; }
__device__ __forceinline__ void tma3d(uint32_t dst, const CUtensorMap* m, int c1, int c2, uint32_t bar) {
  asm volatile("cp.async.bulk.tensor.3d.shared::cluster.global.mbarrier::complete_tx::bytes [%0], [%1, {0, %3, %4}], [%2];"
    :: "r"(dst), "l"(m), "r"(bar), "r"(c1), "r"(c2) : "memory"); }
__device__ __forceinline__ void tma4d(uint32_t dst, const CUtensorMap* m, int c1, int c2, uint32_t bar) {
  asm volatile("cp.async.bulk.tensor.4d.shared::cluster.global.mbarrier::complete_tx::bytes [%0], [%1, {0, %3, %4, 0}], [%2];"
    :: "r"(dst), "l"(m), "r"(bar), "r"(c1), "r"(c2) : "memory"); }
template <int OFF, int ACC>
__device__ __forceinline__ void wg_rs32(float (&d)[16], const uint32_t (&a)[4], uint32_t db) {
  if (ACC)
    asm volatile("{.reg .b64 db; .reg .b32 lo; add.u32 lo, %20, %21; mov.b64 db, {lo, 0x40000040};\n"
      "wgmma.mma_async.sync.aligned.m64n32k16.f32.bf16.bf16 {%0,%1,%2,%3,%4,%5,%6,%7,%8,%9,%10,%11,%12,%13,%14,%15}, {%16,%17,%18,%19}, db, 1, 1, 1, 0;}"
      : "+f"(d[0]), "+f"(d[1]), "+f"(d[2]), "+f"(d[3]), "+f"(d[4]), "+f"(d[5]), "+f"(d[6]), "+f"(d[7]), "+f"(d[8]), "+f"(d[9]), "+f"(d[10]), "+f"(d[11]), "+f"(d[12]), "+f"(d[13]), "+f"(d[14]), "+f"(d[15])
      : "r"(a[0]), "r"(a[1]), "r"(a[2]), "r"(a[3]), "r"(db), "n"(OFF));
  else
    asm volatile("{.reg .b64 db; .reg .b32 lo; add.u32 lo, %20, %21; mov.b64 db, {lo, 0x40000040};\n"
      "wgmma.mma_async.sync.aligned.m64n32k16.f32.bf16.bf16 {%0,%1,%2,%3,%4,%5,%6,%7,%8,%9,%10,%11,%12,%13,%14,%15}, {%16,%17,%18,%19}, db, 0, 1, 1, 0;}"
      : "=f"(d[0]), "=f"(d[1]), "=f"(d[2]), "=f"(d[3]), "=f"(d[4]), "=f"(d[5]), "=f"(d[6]), "=f"(d[7]), "=f"(d[8]), "=f"(d[9]), "=f"(d[10]), "=f"(d[11]), "=f"(d[12]), "=f"(d[13]), "=f"(d[14]), "=f"(d[15])
      : "r"(a[0]), "r"(a[1]), "r"(a[2]), "r"(a[3]), "r"(db), "n"(OFF));
}
template <int I> using IC = std::integral_constant<int, I>;
template <int I, int N, class F> __device__ __forceinline__ void sfor(F&& f) {
  if constexpr (I < N) { f(std::integral_constant<int, I>{}); sfor<I + 1, N>(f); }
}
__device__ __forceinline__ void keep(float (&d)[16]) {
  asm volatile("" : "+f"(d[0]), "+f"(d[1]), "+f"(d[2]), "+f"(d[3]), "+f"(d[4]), "+f"(d[5]), "+f"(d[6]), "+f"(d[7]),
      "+f"(d[8]), "+f"(d[9]), "+f"(d[10]), "+f"(d[11]), "+f"(d[12]), "+f"(d[13]), "+f"(d[14]), "+f"(d[15]) :: "memory");
}

template <int N, int S2 = 1024> __device__ __forceinline__ void ldx(uint32_t (&v)[N][4], const uint8_t* p) {
#pragma unroll
  for (int k = 0; k < 2 * N; k++) {
    const int i = k;
    asm volatile("ld.relaxed.gpu.global.v2.b32 {%0,%1}, [%2];" : "=r"(v[i >> 1][2 * (i & 1)]), "=r"(v[i >> 1][2 * (i & 1) + 1]) : "l"(p + (i & 3) * 256 + (i >> 2) * S2) : "memory");
  }
}
__device__ __forceinline__ uint32_t dif2(uint32_t a, uint32_t b, uint32_t tag) { uint32_t r; asm("lop3.b32 %0, %1, %2, %3, 0x7e;" : "=r"(r) : "r"(a), "r"(b), "r"(tag)); return r; }
__device__ __forceinline__ uint32_t dif2v(uint32_t a, uint32_t b, uint32_t tag) { uint32_t r; asm volatile("lop3.b32 %0, %1, %2, %3, 0x7e;" : "=r"(r) : "r"(a), "r"(b), "r"(tag)); return r; }
__device__ __forceinline__ uint32_t or3(uint32_t a, uint32_t b, uint32_t c) { uint32_t r; asm("lop3.b32 %0, %1, %2, %3, 0xfe;" : "=r"(r) : "r"(a), "r"(b), "r"(c)); return r; }
__device__ __forceinline__ uint32_t after(uint32_t x, float f, uint32_t z) { uint32_t r; asm("lop3.b32 %0, %1, %2, %3, 0xea;" : "=r"(r) : "r"(__float_as_uint(f)), "r"(z), "r"(x)); return r; }
__device__ __forceinline__ bool any_bit(uint32_t a, uint32_t b, uint32_t m) {
  uint32_t r; asm("lop3.b32 %0, %1, %2, %3, 0xa8;" : "=r"(r) : "r"(a), "r"(b), "r"(m)); return __any_sync(0xffffffffu, r); }
template <int W, int N> __device__ __forceinline__ bool stale(const uint32_t (&v)[N][4], uint32_t tag) {
  uint32_t x = dif2(v[0][0], v[0][2], tag);
  if (N == 4) x = or3(x, dif2(v[1][0], v[1][2], tag), dif2(v[2 % N][0], v[2 % N][2], tag));
  return any_bit(x, dif2(v[N - 1][0], v[N - 1][2], tag), 1);
}
template <int W, int N, int S2 = 1024> __device__ __forceinline__ void retry(uint32_t (&v)[N][4], const uint8_t* p, uint32_t tag, int& it) {
#pragma unroll 1
  do { ldx<N, S2>(v, p); it += INC_A; } while (stale<W>(v, tag) && it < SPIN_LIMIT);
}
__device__ __forceinline__ void mma_h(float (&d)[4], const uint32_t (&a)[4], const uint32_t (&b)[4], int hf) { mma16816(d, a[0], a[1], a[2], a[3], b[2 * hf], b[2 * hf + 1]); }
__device__ __forceinline__ void sts128(uint32_t a, const uint32_t (&r)[4]) { sts128(a, r[0], r[1], r[2], r[3]); }
__device__ __forceinline__ void sts128f(uint32_t a, const float* r) { sts128(a, __float_as_uint(r[0]), __float_as_uint(r[1]), __float_as_uint(r[2]), __float_as_uint(r[3])); }
__device__ __forceinline__ void mbar_spin(uint32_t bar, uint32_t par, int& it) {
  asm volatile("{.reg .pred p; .reg .b32 par; mov.b32 par, %2;\nLOOP: mbarrier.try_wait.parity.shared::cta.b64 p, [%1], par; @p bra.uni DONE;\n"
               "add.s32 %0, %0, 1; setp.le.s32 p, %0, %3; @p bra.uni LOOP;\nDONE: }" : "+r"(it) : "r"(bar), "r"(par), "n"(SPIN_LIMIT) : "memory"); }
__device__ __forceinline__ void warp_arrive(uint32_t bar) {
  __syncwarp(); asm volatile("{.reg .pred p; elect.sync _|p, 0xffffffff; @p mbarrier.arrive.shared::cta.b64 _, [%0];}" :: "r"(bar) : "memory"); }
__device__ __forceinline__ void delay_until(unsigned t) {
  asm volatile("{.reg .pred p; .reg .b64 c; .reg .b32 lo, hi;\nLOOP: mov.u64 c, %%clock64; mov.b64 {lo, hi}, c; sub.s32 lo, lo, %0; setp.lt.s32 p, lo, 0; @p bra.uni LOOP;}" :: "r"(t) : "memory"); }
__device__ __forceinline__ void cut(int it) { asm volatile("{.reg .pred p; setp.lt.s32 p, %0, 0;\nL: @p st.volatile.shared.u32 [%0], %0; @p bra.uni L;}" :: "r"(it) : "memory"); }
__device__ __forceinline__ void zero(float (&c)[4][4]) {
#pragma unroll
  for (int i = 0; i < 4; i++) c[i][0] = c[i][1] = c[i][2] = c[i][3] = 0.f;
}

__device__ __forceinline__ void sched() { asm volatile("griddepcontrol.launch_dependents;" ::: "memory"); }
__device__ __forceinline__ const uint8_t* pinp(const uint8_t* p) { return reinterpret_cast<const uint8_t*>(__shfl_xor_sync(0xffffffffu, reinterpret_cast<unsigned long long>(p), 0)); }
__device__ __forceinline__ uint32_t bar_or(int id, uint32_t x) {
  uint32_t r; asm volatile("{.reg .pred p, q; setp.ne.u32 p, %2, 0; bar.red.or.pred q, %1, 256, p; selp.u32 %0, 1, 0, q;}" : "=r"(r) : "r"(id), "r"(x) : "memory"); return r; }
__device__ __forceinline__ void bar_sync_unless(int id, uint32_t x) { asm volatile("{.reg .pred p; setp.eq.u32 p, %1, 0; @p bar.sync %0, 256;}" :: "r"(id), "r"((uint32_t)x) : "memory"); }
__device__ __forceinline__ void bar_arrive_unless(int id, uint32_t x) { asm volatile("{.reg .pred p; setp.eq.u32 p, %1, 0; @p bar.arrive %0, 256;}" :: "r"(id), "r"((uint32_t)x) : "memory"); }
__device__ __forceinline__ void stsm2t(uint32_t a, uint32_t r0, uint32_t r1, uint32_t x) {
  asm volatile("{.reg .pred p; setp.eq.u32 p, %3, 0; @p stmatrix.sync.aligned.m8n8.x2.trans.shared.b16 [%0], {%1,%2};}" :: "r"(a), "r"(r0), "r"(r1), "r"((uint32_t)x) : "memory"); }
__device__ __forceinline__ uint32_t or_and(uint32_t a, uint32_t b, uint32_t m) { uint32_t r; asm("lop3.b32 %0, %1, %2, %3, 0xa8;" : "=r"(r) : "r"(a), "r"(b), "r"(m)); return r; }
#define rare(x) __builtin_expect(!!(x), 0)
__device__ __forceinline__ uint32_t gtime() { unsigned long long g; asm volatile("mov.u64 %0, %%globaltimer;" : "=l"(g) :: "memory"); return (uint32_t)g; }
__device__ __forceinline__ void wait_time(uint32_t t) {
  asm volatile("{.reg .pred p; .reg .b32 g; .reg .b64 c;\nLOOP: mov.u64 c, %%globaltimer; cvt.u32.u64 g, c; sub.s32 g, %0, g; setp.lt.u32 p, g, 16384; @p bra.uni LOOP;}" :: "r"(t - 1) : "memory"); }
__device__ __forceinline__ uint32_t ldx32(const void* p) { uint32_t v; asm volatile("ld.relaxed.gpu.global.b32 %0, [%1];" : "=r"(v) : "l"(p) : "memory"); return v; }
__device__ __forceinline__ void stx32(const void* p, uint32_t v) { asm volatile("st.relaxed.gpu.global.b32 [%0], %1;" :: "l"(p), "r"(v) : "memory"); }

__global__ void __launch_bounds__(256, 1)
rec_kernel(const __grid_constant__ RecMaps maps, const bf16* __restrict__ xin, const bf16* __restrict__ mem0, Xchg* const gx,
           const bf16* __restrict__ fx, const bf16* __restrict__ wr, const bf16* __restrict__ wi) {
  extern __shared__ __align__(1024) uint8_t smem_raw[];
  const uint32_t sb = smem_u32(smem_raw);
  int role = blockIdx.x;
  {
    uint32_t smid, nsm; asm volatile("mov.u32 %0, %%smid;" : "=r"(smid)); asm volatile("mov.u32 %0, %%nsmid;" : "=r"(nsm));
    const int p = smid >> 1, u = p - 32;
    if (nsm == gridDim.x)
      role = (smid & 1) + (p < 32 ? 4 * ((p & 7) + 8 * (p >> 4)) + 2 * ((p >> 3) & 1) : p < 60 ? 4 * (16 + u % 7 + 7 * (u / 14)) + 2 * ((u / 7) & 1)
                         : p < 62 ? 2 * p + 8 : 2 * p - 4);
    role = uni(role);
  }
  if (role >= 128) {
    fft_cols(sb, role - 128, 4, [&]() { grid_wait(&gx->ctr[33], 128); });
    __threadfence(); __syncwarp();
    if ((threadIdx.x & 31) == 0) atomicAdd(&gx->ctr[32], 1u);
    __syncwarp();
    fft_rows_inv(&maps.fo, sb, role - 128, 4, [&]() { grid_wait(&gx->ctr[32], 32); });
    return;
  }
  const int tid = threadIdx.x, warp = uni(tid >> 5), lane = tid & 31, wg = warp >> 2, w4 = warp & 3, g = lane >> 2, t = lane & 3;
  const int h = role >> 2, j = role & 3, jh = j & 1;
  uint32_t w[48][4];
  float aq[16], av[16];
  int it = 0;

#define PT(k)
  auto pf_wo = [&]() {
    for (int i = 0; i < 4; i++)
      asm volatile("cp.async.bulk.prefetch.tensor.2d.L2.global [%0, {%1, %2}];" :: "l"(&maps.wo), "r"(256 * j + 64 * i), "r"(h * DH) : "memory");
  };
  fft_rows_fwd(fx, wr, wi, sb + R_MEM + 49152, role, [&]() {
    if (tid == 224) {
      mbar_init(sb + B_KV, 1); mbar_init(sb + B_W, 1); mbar_init(sb + B_X, 1); mbar_init(sb + B_X + 8, 1); mbar_init(sb + B_X + 16, 1); mbar_init(sb + B_X + 24, 1); mbar_init(sb + B_C, 4); mbar_init(sb + B_PK, 4); mbar_init(sb + B_B, 1);
      asm volatile("fence.mbarrier_init.release.cluster;" ::: "memory");
      mbar_expect_tx(sb + B_W, 3 * 65536);
      for (int i = 0; i < 4; i++) {
        tma2d(sb + R_X + i * 16384, &maps.wq, h * DH + 32 * j, i * 256, sb + B_W);
        if (i < 3) tma2d(sb + R_MEM + i * 16384, &maps.wk, h * DH + 32 * j, i * 256, sb + B_W);
        else asm volatile("cp.async.bulk.prefetch.tensor.2d.L2.global [%0, {%1, %2}];" :: "l"(&maps.wk), "r"(h * DH + 32 * j), "r"(768) : "memory");
      }
      for (int i = 0; i < 2; i++) tma2d(sb + R_WO + i * 32768, &maps.wv, h * DH + 64 * (j >> 1), jh * 512 + i * 256, sb + B_W);
      if (PFD) asm volatile("cp.async.bulk.prefetch.L2.global [%0], 2048;" :: "l"(xin + role * DM) : "memory");
      else for (int i = 0; i < 4; i++) asm volatile("cp.async.bulk.prefetch.L2.global [%0], 8192;" :: "l"(xin + role * 16384 + i * 4096) : "memory");
      if (WOP == 0) pf_wo();
      for (int i = 0; i < 5; i++) asm volatile("prefetch.tensormap [%0];" :: "l"(&maps.wo + i) : "memory");
    }
    __syncwarp();
  });
  if (tid < 16) sts32(sb + R_T + tid * 4, ~0u);
  fence_async();
  PT(0);
  grid_arrive(&gx->ctr[33]);
  PT(1);
  if (tid == 224) { tma2d(sb + R_MEM + 49152, &maps.wk, h * DH + 32 * j, 768, sb + B_W); if (WOP == 1) pf_wo(); }
  __syncwarp();
  uint8_t* const xb = reinterpret_cast<uint8_t*>(gx);
  auto probe_at = [&](int n) { return xb + (n ? offsetof(Xchg, C) + w4 * 8192 + role * 32 : offsetof(Xchg, B) + role * 8192 + warp * 128); };
  if (lane < 8) stx128(probe_at(lane >> 2) + (lane & 2) * 2048 + (lane & 1) * 16, 0, 0, 0, 0);
  uint32_t m0[4][4];
#pragma unroll
  for (int i = 0; i < 16; i++) m0[i >> 2][i & 3] = ldnc32(mem0 + g * DM + 128 * warp + 8 * i + 2 * t);
  mbar_spin(sb + B_W, 0, it);
  PT(2);
  const int lrow = (lane & 7) + ((lane >> 4) << 3), lhi = (lane >> 3) & 1;
  const int kq = wg ? 3 - 3 * jh : 3 * jh;
  const uint32_t LW = lrow * 128 + ((lhi ^ (lane & 7)) << 4);
  {
    const int chunk = w4 < 2 ? w4 + 2 * lhi : 2 * (w4 & 1) + lhi;
    uint32_t a = sb + (w4 < 2 ? R_X : R_MEM) + kq * 16384 + lrow * 64 + ((chunk ^ ((lrow >> 1) & 3)) << 4);
#pragma unroll
    for (int i = 0; i < 16; i++) ldsm4t(w[i], a + i * 1024);
    const uint32_t st = wg ? 1024 : 2048, av0 = sb + R_WO + (LW ^ (w4 << 5));
    const uint32_t a1 = wg ? a + (2 * jh - 1) * 16384 : av0 + jh * 32768, a2 = wg ? a + (2 * jh - 1) * 32768 : av0 + (1 - jh) * 32768;
#pragma unroll
    for (int i = 0; i < 16; i++) { ldsm4t(w[16 + i], a1 + i * st); ldsm4t(w[32 + i], a2 + i * st); }
  }
  uint32_t L16 = pin(lane * 16);
  const uint32_t uW = uni(sb + w4 * 512), uWo = uni(sb + R_WO + w4 * 16384), uMem = uni(sb + R_MEM + kq * 4096);
  const uint32_t dX = uni(((sb + R_X + kq * 16384) >> 4) | 0x10000u);
  auto load_wo = [&](uint32_t (&d)[32][4], int i0, int i1) {
#pragma unroll
    for (int i = i0; i < i1; i++) lds128(d[i], uWo + L16 + (i & 1) * 512 + (i >> 4) * 1024 + (i & 14) * 1024);
  };
  auto issue_x = [&](int n, int k) {
    const uint32_t bar = sb + B_X + 8 * k, q = k ^ (3 - 3 * jh);
    mbar_expect_tx(bar, 16384); tma3d(sb + R_X + q * 16384, &maps.x, min(n, NSEG - 1) * SEG, 4 * q, bar);
  };
  auto store_stage = [&](int n) {
    asm volatile("cp.async.bulk.global.shared::cta.bulk_group [%0], [%1], 8192; cp.async.bulk.commit_group;"
                 :: "l"(g_kqv[n & 3][role]), "r"(sb + R_STAGE) : "memory");
  };
  auto issue_kqv = [&](int n) {
    const int p = (n & 3) * 128 + 4 * h;
    mbar_expect_tx(sb + B_KV, 26624);
    tma3d(sb + R_K, &maps.k, 0, p, sb + B_KV); tma3d(sb + R_Q, &maps.q, 8 + 2 * j, p, sb + B_KV); tma3d(sb + R_V, &maps.v, 16, p, sb + B_KV);
  };
  auto fetch4k = [&](uint32_t dst, uint32_t off, uint32_t bar, uint32_t t) {
    asm volatile("{.reg .pred p, q; .reg .b32 g; .reg .b64 c; elect.sync _|q, 0xffffffff; @q mbarrier.arrive.expect_tx.shared::cta.b64 _, [%2], 4096;\n"
                 "LOOP: mov.u64 c, %%globaltimer; cvt.u32.u64 g, c; sub.s32 g, %3, g; setp.lt.u32 p, g, 16384; @p bra.uni LOOP;\n"
                 "@q cp.async.bulk.shared::cluster.global.mbarrier::complete_tx::bytes [%0], [%1], 4096, [%2];}" :: "r"(dst), "l"(xb + off), "r"(bar), "r"(t - 1) : "memory");
  };
  uint32_t uS;
  auto my_b = [&]() { return offsetof(Xchg, B) + role * 8192 + ((uS + ((uint32_t)it >> 31)) & 1) * 4096; };
  auto issue_c = [&](uint32_t t) { fetch4k(sb + R_MEM + w4 * 4096, offsetof(Xchg, C) + w4 * 8192 + ((uS + ((uint32_t)it >> 31)) & 4096), sb + B_C, t); };
  auto wait_x = [&](int n, int i) { if (!(EXP & 1) || n < 2) mbar_spin(sb + B_X + 8 * i, n & 1, it); };
#define PACED(d0) uint32_t dz = d0; const uint32_t z = (uint32_t)it >> 31; auto pace = [&]() { for (int k = 0; k < PACE; k++) { if (k & 1) asm("add.u32 %0, %0, %1;" : "+r"(dz) : "r"(z)); else asm("xor.b32 %0, %0, %1;" : "+r"(dz) : "r"(z)); } };
  auto project_v = [&](auto I0, auto I1, auto&& mid) {
    PACED(decltype(I0)::value < 16 ? dX : dX ^ 1024);
    wg_fence();
    sfor<decltype(I0)::value, decltype(I1)::value>([&](auto I) {
      constexpr int i = decltype(I)::value;
      mid(i);
      if (i == 16 && decltype(I0)::value < 16) dz ^= 1024;
      wg_rs32<((i >> 2) & 3) * 256 + (i & 3) * 2, (i > 0)>(av, w[16 + i], dz);
      pace();
    });
    wg_commit();
  };
  auto project_qk = [&](auto I0, auto I1, auto first, auto&& mid) {
    PACED((dX ^ (decltype(I0)::value >> 4 << 10)) + ((uint32_t)it >> 31));
    wg_fence();
    sfor<decltype(I0)::value, decltype(I1)::value>([&](auto I) {
      constexpr int i = decltype(I)::value;
      mid(i);
      wg_rs32<((i >> 2) & 3) * 256 + (i & 3) * 2, !decltype(first)::value || i != decltype(I0)::value>(aq, w[i], dz);
      pace();
    });
    wg_commit();
  };
  const uint32_t uP = uni(sb + R_X + 3 * jh * 16384 + w4 * 512);
  auto park = [&]() {
    bar_sync(1, 128);
#pragma unroll
    for (int i = 0; i < 4; i++) sts128f(uP + L16 + i * 2048, aq + 4 * i);
    warp_arrive(sb + B_PK);
  };
  auto unpark = [&]() {
#pragma unroll
    for (int i = 0; i < 4; i++) {
      const float4 p = lds128f(uP + L16 + i * 2048);
      av[4 * i] = p.x; av[4 * i + 1] = p.y; av[4 * i + 2] = p.z; av[4 * i + 3] = p.w;
    }
  };
  auto fin_qk = [&]() {
#pragma unroll
    for (int i = 0; i < 16; i++) aq[i] += av[i];
    const uint32_t a = sb + R_STAGE + (w4 < 2 ? 2048 + w4 * 128 : (w4 & 1) * 256) + (L16 & 112) + (L16 >> 7) * 512;
    stsm4t(a, pack2(aq[0], aq[1]), pack2(aq[4], aq[5]), pack2(aq[8], aq[9]), pack2(aq[12], aq[13]));
    stsm4t(a + (w4 < 2 ? 256 : 128), pack2(aq[2], aq[3]), pack2(aq[6], aq[7]), pack2(aq[10], aq[11]), pack2(aq[14], aq[15]));
  };
  auto fin_v = [&]() {
#pragma unroll
    for (int a = 0; a < 2; a++)
      sts128(sb + R_STAGE + 4096 + w4 * 1024 + a * 512 + L16, pack2(av[8 * a], av[8 * a + 1]), pack2(av[8 * a + 2], av[8 * a + 3]),
             pack2(av[8 * a + 4], av[8 * a + 5]), pack2(av[8 * a + 6], av[8 * a + 7]));
  };
  __syncthreads();
  if (tid == 224) {
#pragma unroll 1
    for (int i = 0; i < 4; i++) issue_x(0, i);
    mbar_expect_tx(sb + B_W, 65536);
    for (int i = 0; i < 4; i++) tma2d(sb + R_WO + i * 16384, &maps.wo, 256 * j + 64 * i, h * DH, sb + B_W);
  }
  __syncwarp();
  if (wg) {
#pragma unroll
    for (int i = 0; i < NSW; i++) sts128(uW + R_WC + L16 + i * 2048, w[i]);
  }
#pragma unroll
  for (int i = 0; i < 4; i++) sts128(sb + R_MEM + warp * 2048 + i * 512 + (g >> 1) * 128 + t * 32 + (g & 1) * 16, m0[i]);
  auto probe = [&](int n, int cnt) {
    if (lane == 0) {
#pragma unroll 1
      for (int i = role >> 7; i < cnt; i++) {
        const int k = (i ^ wg) & 1;
        const unsigned t0 = clk();
        uint32_t v; asm volatile("atom.relaxed.gpu.global.exch.b32 %0, [%1], 0;" : "=r"(v) : "l"(probe_at(n) + k * 4096) : "memory");
        if (v == 0) asm volatile("red.shared.min.u32 [%0], %1;" :: "r"(sb + R_T + (n ? w4 * 8 : 32) + k * 4), "r"(clk() - t0) : "memory");
      }
    }
    __syncwarp();
  };
#pragma unroll 1
  for (int n = 0; n < 2; n++) {
    probe(0, n ? NPB : NPB0);
    asm volatile("{.reg .pred p; cp.async.bulk.wait_group 0; setp.eq.u32 p, %1, 97; @p red.relaxed.gpu.global.add.u32 [%0], 1;}" :: "l"(&gx->ctr[h]), "r"(tid ^ n ^ (1 - n) << 9) : "memory");
    PT(3 + 3 * n);
    wait_x(n, 2);
    PT(4 + 3 * n);
    if (wg == 0) {
      wait_x(n, 3);
      project_qk(IC<0>{}, IC<16>{}, IC<1>{}, [](int) {});
      project_v(IC<0>{}, IC<32>{}, [](int) {});
      wg_wait<0>(); keep(aq); keep(av);
      park();
      fin_v();
      fence_async();
    } else {
      wait_x(n, 0); wait_x(n, 1);
      project_qk(IC<32>{}, IC<48>{}, IC<1>{}, [](int) {});
      project_qk(IC<16>{}, IC<32>{}, IC<0>{}, [](int) {});
      project_qk(IC<0>{}, IC<16>{}, IC<0>{}, [](int) {});
      mbar_spin(sb + B_PK, n, it);
      unpark();
      wg_wait<0>(); keep(aq);
      fin_qk();
      fence_async();
    }
    __syncthreads();
    if (tid == 0 && n) stx32(&gx->S[role], 1 + (HOME & 2 && lds32(sb + R_T + 36) < lds32(sb + R_T + 32)));
    PT(5 + 3 * n);
    if (tid == 96 && n == 0) store_stage(0);
    if (tid == 128 && n == 0) {
#pragma unroll 1
      for (int i = 0; i < 4; i++) issue_x(1, i);
    }
    if (warp == 5 && n == 1) {
#pragma unroll 1
      while (__any_sync(0xffffffffu, ldx32(&gx->ctr[h]) < 4) && ++it < SPIN_LIMIT) {}
      if (elect()) issue_kqv(0);
    }
    __syncwarp();
  }
  mbar_spin(sb + B_W, 1, it);
  PT(9);
#pragma unroll
  for (int i = 0; i < 4; i++) {
    uint32_t f[4][4];
    const uint32_t a = sb + R_WO + warp * 8192 + i * 2048;
#pragma unroll
    for (int q = 0; q < 4; q++) ldsm4t(f[q], a + (LW ^ (q << 5)));
    __syncwarp();
#pragma unroll
    for (int q = 0; q < 4; q++) sts128(a + q * 512 + L16, f[q]);
  }
  if (NPC) probe(1, NPC);
  {
    const int o = 32 * w4 + 16 * wg + 4 * t + j;
    uint32_t v;
#pragma unroll 1
    while (__any_sync(0xffffffffu, (v = ldx32(&gx->S[o])) == 0) && ++it < SPIN_LIMIT) {}
    asm volatile("st.shared.u64 [%0], %1;" :: "r"(sb + R_DST + wg * 1024 + w4 * 256 + lane * 8), "l"(xb + offsetof(Xchg, B) + o * 8192 + (v >> 1) * 4096 + h * 128 + ((g ^ h) & 7) * 16) : "memory");
  }
  if (wg == 0) {
    const uint64_t cd = reinterpret_cast<uint64_t>(xb + (offsetof(Xchg, C) + j * 8192 + h * 128 + w4 * 32 + (L16 & 16) * 256 + (L16 & 64) / 4 + (L16 >> 7) * 4));
    sts128(uW + R_RD + L16, (uint32_t)cd, (uint32_t)(cd >> 32), sb + R_MEM + (L16 & 112) * 8 + (L16 >> 8) * 1024 + ((w4 * 32 + ((L16 >> 3) & 16)) ^ (L16 & 112)),
           (L16 >> 6) == (h & 3) * 2 + ((h >> 2) & 1) ? 0xFFFE0000u : 0xFFFFFFFFu);
  }
  if (tid == 0) sts32(sb + B_DUE + 8, gtime() & ~31u);
  PT(10);
  mbar_spin(sb + B_KV, 0, it);
  PT(11);
  if (tid < 4) sts32(sb + B_ONE + tid * 4, 0x3F803F80u);
  if (warp == 1) { const uint32_t e = g >> 1 == t ? 0x3F80u << (16 * (g & 1)) : 0u; sts128(sb + R_ID + L16, e, 0, 0, e); }
  __syncthreads();
  {
    const uint32_t kb = lds32(sb + R_T + 36) < lds32(sb + R_T + 32);
    uS = uni((HOME & 4 ? (__popc(((offsetof(Xchg, B) / 4096 + 2 * role) ^ (offsetof(Xchg, C) / 4096 + 2 * w4)) & 0xb3) ^ kb) & 1 : lds32(sb + R_T + w4 * 8 + 4) < lds32(sb + R_T + w4 * 8)) * 4096 + kb);
  }

  const float sc = 0.08838834764831845f * 1.4426950408889634f;
  uint8_t* const xa = xb + uni(h * 16384);
  const uint32_t uA = uni(wg ? (w4 >> 1) * 2048 + j * 512 + (w4 & 1) * 256 : 8192 + (4 * (j >> 1) + w4) * 512 + jh * 256);
  const uint32_t uP2 = uni(sb + R_P + w4 * 256);
  uint32_t nc = 1;
  uint32_t ma;
  const uint8_t* adst;
  auto pin_mem = [&]() { adst = pinp(xa + uA + L16 / 2); ma = pin(uMem + (L16 & 384) + (L16 & 48) * 2 + (L16 & 64) / 4); };
  pin_mem();

#pragma unroll 1
  for (int s = 0;; nc++) {
    const uint32_t tag = (s + 1) & 1;
    auto fresh = [&]() { L16 += (uint32_t)it >> 31; };
    auto get_due = [&]() { return lds32(sb + B_DUE + 4 + tag * 4); };
    float c[4][4], r4[4];
    auto fold = [&]() {
#pragma unroll
      for (int i = 0; i < 4; i++) r4[i] = ((c[0][i] + c[1][i]) + c[2][i]) + c[3][i];
    };
    auto mma4 = [&](int n, const uint32_t (&b0)[4], const uint32_t (&b1)[4]) {
      mma_h(c[0], w[n + 2], b1, 0); mma_h(c[1], w[n + 3], b1, 1); mma_h(c[2], w[n], b0, 0); mma_h(c[3], w[n + 1], b0, 1);
    };
    auto xpos = [&](int pos, int wp) {
      if ((pos == X0 || pos == X1 || pos == X2 || pos == X3) && warp == wp && s + 1 < NSEG && elect()) {
        const int z = (uint32_t)it >> 31;
        if (pos == X2) issue_x(s + 2, 2 + z);
        if (pos == X3) issue_x(s + 2, 3 + z);
        if (pos == X1) issue_x(s + 2, 1 + z);
        if (pos == X0) issue_x(s + 2, z);
      }
      __syncwarp();
    };
    if (wg == 0) {
      mbar_spin(sb + B_C, nc & 1, it);
      TS(13);
      uint32_t b[16][4], tg[4];
#pragma unroll
      for (int i = 0; i < PD0; i++) { lds128(b[i], ma + i * 512); __syncwarp(); }
      sched();
      zero(c);
#pragma unroll
      for (int i = 0; i < 8; i++) {
        const int k = i ^ 1;
        mma_h(c[0], w[2 * k], b[k], 0); mma_h(c[1], w[2 * k + 1], b[k], 1);
        if (i < 2 * NV0) { mma_h(c[2], w[16 + 2 * k], b[k], 0); mma_h(c[3], w[17 + 2 * k], b[k], 1); }
        sched();
        if ((i & 1) && i + PD0 < 9) { lds128(b[i + PD0 - 1], ma + (i + PD0 - 1) * 512); __syncwarp(); lds128(b[i + PD0], ma + (i + PD0) * 512); sched(); }
        if (i == TGP) {
          fresh();
#pragma unroll
          for (int k = 0; k < 4; k++) tg[k] = lds32((uW * 4 + L16) * 2 + (L16 >> 6) * 4 + (R_MEM + k * 1024 - 7 * sb));
          sched();
        }
      }
#pragma unroll
      for (int i = 0; i < 4; i++) { r4[i] = c[0][i] + c[1][i]; c[0][i] = c[1][i] = 0.f; }
      sts128f(uW + R_RED + L16, r4);
      TS(1);
      const uint32_t old = bar_or(4, (dif2(tg[0], tg[1], s) | dif2(tg[2], tg[3], s)) & (s > 0));
      TS(0);
#pragma unroll
      for (int i = 0; i < 2 * NV0; i++) { lds128(b[8 + i], (ma ^ 4096) + i * 512); __syncwarp(); }
      sched();
#pragma unroll
      for (int i = NV0; i < 8; i++) {
        if (VB && i == VB) bar_sync(7, 256);
        mma4(16 + 4 * i, b[2 * i], b[2 * i + 1]);
        if (i < 7) sched();
        if (i < 4) { lds128(b[8 + 2 * i], (ma ^ 4096) + i * 1024); __syncwarp(); lds128(b[9 + 2 * i], (ma ^ 4096) + i * 1024 + 512); sched(); }
      }
      fold();
      asm volatile("{.reg .pred p; setp.eq.u32 p, %3, 0; @p st.relaxed.gpu.global.v2.b32 [%0], {%1,%2};}" :: "l"(adst), "r"((pack2(r4[0], r4[1]) & ~1u) | tag), "r"(pack2(r4[2], r4[3])), "r"(old) : "memory");
      sched();
      const unsigned tpub = clk();
      if (__any_sync(0xffffffffu, old) && nc < NC_MAX) {
        bar_sync(3, 256);
        issue_c(gtime());
        continue;
      }
      TS(3);
      xpos(0, 0);
      const uint32_t due = get_due();
      uint32_t vf[4][4], vm[2][4], p[4], pm, o[4];
      const uint32_t va = sb + R_V + (w4 >> 1) * 8192 + (w4 & 1) * 2048 + L16;
#pragma unroll
      for (int i = 0; i < 4; i++) {
        uint32_t q[4]; lds128(vf[i], va + i * 512); lds128(q, va + 4096 + i * 512);
#pragma unroll
        for (int e = 0; e < 4; e++) vf[i][e] = hadd2(vf[i][e], q[e]);
      }
      const uint32_t pa = pin(sb + R_P + (L16 >> 1));
      const uint8_t* vsrc = pinp(xa + 8192 + w4 * 1024 + L16 / 2);
      uint32_t one[4];
      lds128(one, sb + B_ONE);
      auto pv_x = [&]() {
        zero(c);
        mma_a(c[2], one, p[0], p[1]);
        mma_a(c[0], vf[0], p[0], p[1]); mma_a(c[1], vf[2], p[0], p[1]);
        sched();
        mma_a(c[2], one, p[2], p[3]);
        mma_a(c[0], vf[1], p[2], p[3]); mma_a(c[1], vf[3], p[2], p[3]);
        sched();
      };
      auto pv_m = [&]() {
        mma1688(c[2], one[0], one[1], pm);
        mma_a(c[0], vm[0], pm, pm);
        sched();
        mma_a(c[1], vm[1], pm, pm);
      };
      auto norm = [&]() {
        const float n0 = rcp(c[2][0]), n1 = rcp(c[2][1]);
#pragma unroll
        for (int i = 0; i < 4; i++) o[i] = pack2(c[i >> 1][2 * (i & 1)] * n0, c[i >> 1][2 * (i & 1) + 1] * n1);
        return ((__float_as_uint(c[2][0]) - 0x1F800000u) | (__float_as_uint(c[2][1]) - 0x1F800000u)) >> 30;
      };
      auto load_m = [&](int x) { const float2 e0 = lds64f(pa + 512 + x * 1024), e1 = lds64f(pa + 768 + x * 1024); pm = pack2(e0.x * e1.x, e0.y * e1.y); };
      auto attend_max = [&](int x) {
        float2 sv[6];
#pragma unroll
        for (int i = 0; i < 6; i++) sv[i] = lds64f(pa - 3072 + x * 1536 + i * 256);
        sv[4].x += sv[5].x; sv[4].y += sv[5].y;
        const int dq = (int)(L16 >> 6) - (int)((L16 >> 3) & 6) + 8 * j;
        float m = fmaxf(sv[4].x, sv[4].y);
#pragma unroll
        for (int i = 0; i < 4; i++) {
          if (x && 8 * i > dq) sv[i].x = -INFINITY;
          if (x && 8 * i + 1 > dq) sv[i].y = -INFINITY;
          m = fmaxf(m, fmaxf(sv[i].x, sv[i].y));
        }
        m = fmaxf(m, __shfl_xor_sync(0xffffffffu, m, 1));
        m = fmaxf(m, __shfl_xor_sync(0xffffffffu, m, 2));
#pragma unroll
        for (int i = 0; i < 5; i++) (i < 4 ? p[i] : pm) = pack2(ex2(sv[i].x - m), ex2(sv[i].y - m));
        pv_x(); pv_m(); norm();
      };
      uint32_t tq[4];
      auto get_t = [&]() {
        tq[0] = tq[1] = tq[2] = tq[3] = 0;
        asm volatile("{.reg .pred p; setp.eq.u32 p, %5, 0; @p ld.relaxed.gpu.global.v4.b32 {%0,%1,%2,%3}, [%4];}"
                     : "+r"(tq[0]), "+r"(tq[1]), "+r"(tq[2]), "+r"(tq[3]) : "l"(xb + offsetof(Xchg, T) + L16 * 8), "r"(warp) : "memory");
      };
      delay_until(tpub + DLY_V);
      wait_time(due + NS_V);
      TS(4);
      ldx(vm, vsrc);
      sched();
      xpos(2, 2);
      auto store_kqv = [&]() {
        fence_async();
        if (!(EXP & 4))
          asm volatile("{.reg .pred p; elect.sync _|p, 0xffffffff; @p cp.async.bulk.global.shared::cta.bulk_group [%0], [%1], 2048; cp.async.bulk.commit_group;}"
                       :: "l"(g_kqv[(s + 1) & 3][role] + w4 * 128), "r"(sb + R_STAGE + w4 * 2048) : "memory");
      };
      if (SPOS == 2) store_kqv();
      sched();
      bar_sync(5, 256);
      ldsm4(p, sb + R_P + L16);
      load_m(0);
      pv_x();
      ldsm4(p, sb + R_P + 1024 + L16);
      pv_m();
      const uint32_t r = norm(), tl = after(tag, c[2][0], (uint32_t)it >> 31);
      const bool redo = __any_sync(0xffffffffu, r | ((dif2(vm[0][0], vm[0][2], tl) | dif2(vm[1][0], vm[1][2], tl)) & 1));
      TS(6);
      stsm4t(uW + R_O + L16, o[0], o[1], o[2], o[3]);
      bar_arrive_unless(6, redo);
      sched();
      if (TQL == 7) get_t();
      TS(7);
      pv_x();
      if (rare(redo)) retry<2>(vm, vsrc, tag, it);
      bar_sync(8, 256);
      load_m(1);
      pv_m();
      if (rare(__any_sync(0xffffffffu, norm()) || redo)) {
        fresh();
#pragma unroll 1
        for (int x = !redo; x < 2; x++) {
          attend_max(x);
          if (x == 0) { stsm4t(uW + R_O + L16, o[0], o[1], o[2], o[3]); bar_arrive(6, 256); }
        }
      }
      TS(8);
      if (TQL == 8) get_t();
      const bool xok = mbar_test(sb + B_X + 16, s & 1) & mbar_test(sb + B_X + 24, s & 1);
      xpos(4, 2);
      fresh();
      const uint32_t ob = uni(sb + R_MEM + 4096 + w4 * 1024);
      stsm4t(ob + (L16 & 112) * 4 + (((L16 >> 3) ^ (L16 >> 1)) & 48), o[0], o[1], o[2], o[3]);
      __syncwarp();
      uint32_t rd[4];
      lds128(rd, uW + R_RD + L16);
      lds128(o, ob + (L16 ^ ((L16 >> 3) & 48)));
      auto put_o = [&]() {
        *reinterpret_cast<uint4*>(reinterpret_cast<uint8_t*>(g_ox) + (((s * SEG + 8 * j) * HD + h * DH + 32 * w4) * 2 + (L16 >> 6) * (HD * 2) + (L16 & 48))) = make_uint4(o[0], o[1], o[2], o[3]);
      };
      if (s + 1 == NSEG) { put_o(); asm volatile("cp.async.bulk.wait_group 0;" ::: "memory"); break; }
      asm volatile("cp.async.bulk.wait_group 0;" ::: "memory");
      if (elect()) stx32(xa + 4096 + j * 16 + w4 * 4, s + 1);
      __syncwarp();
      if (rare(!xok)) { wait_x(s + 2, 3); wait_x(s + 2, 2); }
      TS(9);
      fresh();
      const uint32_t e = due | ((s + 1) & 31);
      project_qk(IC<0>{}, IC<NQ>{}, IC<1>{}, [&](int n) {
        if (n == OXPOS) { __syncwarp(); put_o(); __syncwarp(); }
        if (n == TQP) { __syncwarp(); tq[0] = dif2v(tq[0], tq[1], e) | dif2v(tq[2], tq[3], e); __syncwarp(); }
      });
      if (NPA) project_v(IC<0>{}, IC<NPA>{}, [](int) {});
      TS(2);
      if (warp == 0) {
        uint32_t last = due, nx = NS_P;
        if (rare(__any_sync(0xffffffffu, tq[0]))) {
          const uint32_t ref = gtime();
#pragma unroll 1
          do ldx128(o, xb + offsetof(Xchg, T) + L16 * 8); while (any_bit(or3(o[0] - s - 1, o[1] - s - 1, o[2] - s - 1), o[3] - s - 1, 30) && ++it < SPIN_LIMIT);
          const int d = max(max((int)(o[0] - ref), (int)(o[1] - ref)), max((int)(o[2] - ref), (int)(o[3] - ref)));
          last = (ref + __reduce_max_sync(0xffffffffu, d)) & ~31u;
          if (last != due) nx += NS_X;
        }
        const uint32_t bdue = last + NS_B;
        if (s < 4) { last += (MG_Y >> 8 * s & 255) * 32; nx += (MG_Z >> 8 * s & 255) * 32; }
        sts32(sb + B_DUE, last);
        sts32(sb + B_DUE + 8 - tag * 4, last + nx);
        fetch4k(sb + R_MEM, my_b(), sb + B_B, bdue);
        LOG(13, tl - last);
        LOG(9, last);
      }
      if (NQ < 16) project_qk(IC<NQ>{}, IC<16>{}, IC<0>{}, [](int) {});
      project_v(IC<NPA>{}, IC<NPRE>{}, [](int) {});
      const uint32_t ba = rd[2], msk = rd[3];
      const uint8_t* cdst = reinterpret_cast<const uint8_t*>(rd[0] | (uint64_t)rd[1] << 32);
      TS(14);
      mbar_spin(sb + B_B, s & 1, it);
      TS(10);
      uint32_t bq[2][4];
      auto sum_b = [&]() {
        ldsm4t(bq[0], ba); ldsm4t(bq[1], ba + 2048);
        sched();
#pragma unroll
        for (int i = 0; i < 8; i++) c[i >> 2][i & 3] = 0.f;
        mma_a(c[0], bq[0], 0x3F803F80u, 0x3F803F80u); mma_a(c[1], bq[1], 0x3F803F80u, 0x3F803F80u);
        const uint32_t t2 = tag * 0x10001u;
        const bool old = any_bit(or3(dif2(bq[0][0], bq[0][1], t2), dif2(bq[0][2], bq[0][3], t2), dif2(bq[1][0], bq[1][1], t2)), dif2(bq[1][2], bq[1][3], t2), L16 < 64 ? 0x10001u : 0u);
        const uint32_t T = (tag << 16) & ~msk, u = ((__float_as_uint(c[0][0] + c[1][0]) + ((0x10000u & ~msk) - T)) & msk) | T;
        asm volatile("{.reg .pred p; setp.eq.u32 p, %2, 0; @p st.relaxed.gpu.global.b32 [%0], %1;}"
                     :: "l"(cdst), "r"(pack2(__uint_as_float(u), c[0][2] + c[1][2])), "r"((uint32_t)(old || (L16 & 32))) : "memory");
        return old;
      };
      if (rare(sum_b())) {
#pragma unroll 1
        do {
          const uint8_t* p = xb + (my_b() + (ba - sb - R_MEM));
          ldx128(bq[0], p); ldx128(bq[1], p + 2048);
          sts128(ba, bq[0]); sts128(ba + 2048, bq[1]);
          __syncwarp();
          it += INC_B;
        } while (sum_b() && it < SPIN_LIMIT);
      }
      sched();
      TS(11);
      bar_arrive(0, 256);
      const unsigned tc = clk();
      const uint32_t cdue = lds32(sb + B_DUE) + NS_C;
      if (warp == 3) LOG(11, gtime() - cdue);
      fresh();
      wg_wait<0>(); keep(aq); keep(av);
      park();
      if (NPRE < 32) project_v(IC<NPRE>{}, IC<32>{}, [](int) {}); else fin_v();
      TS(12);
      delay_until(tc + DLY_C);
      issue_c(cdue);
      TS(5);
      LOG(warp, it);
      pin_mem();
      if (NPRE < 32) { wg_wait<0>(); keep(av); fin_v(); }
      if (!(EXP & 2)) mbar_spin(sb + B_KV, tag, it);
      TS(15);
    } else {
      uint32_t kf[8][4];
      auto load_k = [&]() {
        const uint32_t ka = sb + R_K + w4 * 1024 + (L16 & 112) + (L16 & 128) * 4 + (L16 & 256);
#pragma unroll
        for (int i = 0; i < 8; i++) ldsm4(kf[i], ka + (i >> 1) * 2048 + (i & 1) * 128);
      };
      auto put_p = [&](int x, uint32_t old, uint32_t again) {
        float e[4];
        const int dq = (int)((L16 >> 3) & 6) + 8 * j - (int)(L16 >> 6) - 16 * w4;
#pragma unroll
        for (int i = 0; i < 4; i++) { r4[i] = fmaf(c[3][i], sc, fmaf(c[2][i], sc, fmaf(c[0][i] + c[1][i], sc, __uint_as_float(i == 3 ? 0u - old : 0u)))); e[i] = x && dq + (i & 1) < 8 * (i >> 1) ? 0.f : ex2(r4[i]); }
        stsm2t(uP2 + x * 1024 + L16, pack2(e[0], e[1]), pack2(e[2], e[3]), again);
      };
      auto put_s = [&](int x) {
#pragma unroll
        for (int i = 0; i < 4; i++) sts32f(uW + R_S + x * 1536 + (L16 & 48) * 4 + (L16 >> 6) * 4 + (i & 1) * 32 + (i >> 1) * 256, r4[i]);
      };
      auto load_q = [&](uint32_t (&q)[4], uint32_t off) { ldsm4(q, sb + R_Q + (L16 & 112) + (L16 & 128) * 2 + (L16 >> 8) * 128 + off); };
      mbar_spin(sb + B_C, nc & 1, it);
      TS(13);
      float4 o4;
      uint32_t id[4], old;
      {
        uint32_t b[24][4];
#pragma unroll
        for (int i = 0; i < 2 * PD1; i++) { lds128(b[i], ma + i * 512); __syncwarp(); }
        sched();
        zero(c);
#pragma unroll
        for (int i = 0; i < 12; i++) {
          mma4(4 * i, b[2 * i], b[2 * i + 1]);
          if (i < 11) sched();
          if (i + PD1 < 12) { const int k = i + PD1; const uint32_t a = (ma ^ (k >> 2 << 12)) + (k & 3) * 1024; lds128(b[2 * k], a); __syncwarp(); lds128(b[2 * k + 1], a + 512); sched(); }
          if (i == RJ) { lds128(id, sb + R_ID + L16); sched(); }
          if (i == RI) { old = bar_or(4, 0); o4 = lds128f(uW + R_RED + L16); sched(); }
        }
      }
      TS(0);
      {
        float e[4] = {o4.x, o4.y, o4.z, o4.w};
#pragma unroll
        for (int i = 0; i < 4; i++) { r4[i] = (((e[i] + c[0][i]) + c[1][i]) + c[2][i]) + c[3][i]; e[i] = 0.f; }
        mma_a(e, id, pack2(r4[0], r4[1]), pack2(r4[2], r4[3]));
        sched();
        if (VB) bar_arrive(7, 256);
        sched();
        asm volatile("{.reg .pred p; setp.eq.u32 p, %3, 0; @p st.relaxed.gpu.global.v2.b32 [%0], {%1,%2};}" :: "l"(adst),
                     "r"((__byte_perm(__float_as_uint(e[0]), __float_as_uint(e[1]), 0x7632) & ~1u) | tag), "r"(__byte_perm(__float_as_uint(e[2]), __float_as_uint(e[3]), 0x7632)), "r"(old) : "memory");
        sched();
      }
      const unsigned tpub = clk(), now = gtime(), due = get_due();
      if (__any_sync(0xffffffffu, old) && nc < NC_MAX) { bar_sync(3, 256); continue; }
      TS(2);
      const uint8_t* asrc = pinp(adst + ((warp == 7) * 1024 - (int)uA));
      fresh();
      uint32_t wo[32][4];
      bool xok;
      auto reload = [&]() {
        sched();
#pragma unroll
        for (int i = RE0 + RE1; i < NSW; i++) lds128(w[i], uW + R_WC + L16 + i * 2048);
        sched();
      };
      auto out_proj = [&]() {
        uint32_t b[4][4];
        float d[4][4];
        uint8_t* dst[2];
        const uint32_t da = pin(uP2 + (R_DST - R_P) + L16 / 2);
        sched();
        TS(7);
        bar_sync(6, 256);
#pragma unroll
        for (int i = 0; i < 4; i++) { ldsm4(b[i], sb + R_O + i * 512 + L16); __syncwarp(); }
        sched();
        auto put_b = [&](uint8_t* a, const float (&e)[4][4]) {
          stx128(a, (pack2(e[0][0] + e[2][0], e[0][1] + e[2][1]) & ~1u) | tag, pack2(e[0][2] + e[2][2], e[0][3] + e[2][3]),
                 pack2(e[1][0] + e[3][0], e[1][1] + e[3][1]), pack2(e[1][2] + e[3][2], e[1][3] + e[3][3]));
        };
        zero(c); zero(d);
#pragma unroll
        for (int i = 0; i < 32; i++) {
          mma_h(i < 16 ? c[i & 3] : d[i & 3], wo[i], b[(i >> 2) & 3], (i >> 1) & 1);
          if (i >= LW0 && NB1 + i - LW0 < 32) { load_wo(wo, (NB1 + i - LW0) ^ 1, ((NB1 + i - LW0) ^ 1) + 1); __syncwarp(); }
          if (i == DL0 || i == DL1) asm volatile("ld.shared.u64 %0, [%1];" : "=l"(dst[i > DL0]) : "r"(da + (i > DL0) * 1024) : "memory");
          if (i >= 16 && i < 16 + RE0) { lds128(w[i - 16], uW + R_WC + L16 + (i - 16) * 2048); __syncwarp(); }
          if (i >= RP1 && i < RP1 + RE1) { lds128(w[i - RP1 + RE0], uW + R_WC + L16 + (i - RP1 + RE0) * 2048); __syncwarp(); }
          if (i == 22) put_b(dst[0], c);
          if ((i & 1) && (i < 20 || i > 22)) sched();
        }
        put_b(dst[1], d);
        sched();
        TS(6);
      };
      if (warp < 6) {
        delay_until(tpub + DLY_A);
        const int it0 = it;
        bool redo;
#pragma unroll 1
        do {
          uint32_t q[4][4], y[4];
          float d[4][4];
          wait_time(due);
          TS(4);
          ldx(q, asrc);
          sched();
          load_k();
          uint32_t qx[4][4];
#pragma unroll
          for (int i = 0; i < 4; i++) load_q(qx[i], i * 512);
          sched();
          load_wo(wo, 0, NE4);
          sched();
          zero(c);
#pragma unroll
          for (int i = 0; i < 8; i++) mma_h(c[i & 3], kf[i], qx[i >> 1], i & 1);
          put_p(1, 0, 0); put_s(1);
          sched();
          load_wo(wo, NE4, NA4);
          sched();
          zero(c); zero(d);
#pragma unroll
          for (int i = 0; i < 8; i++) {
            if (i == 0) { y[0] = dif2v(q[0][0], q[0][2], q[1][0]); sched(); }
            if (i == 3) { y[1] = dif2v(q[1][2], q[2][0], q[2][2]); sched(); }
            if (i == 6) { y[2] = dif2v(q[3][0], q[3][2], tag); sched(); }
            mma_h(i % 6 < 2 ? c[2 + i % 6] : d[i - 2], kf[i], q[i >> 1], i & 1);
            if (i == 2 || i == 5 || i == 7) sched();
          }
          y[0] = or_and(or3(y[0], y[1], dif2v(q[0][0], q[2][0], tag)), y[2], it < SPIN_LIMIT);
#pragma unroll
          for (int i = 0; i < 4; i++) { c[0][i] = d[0][i] + d[1][i]; c[1][i] = d[2][i] + d[3][i]; }
          put_p(0, y[0], it - it0);
          TS(5);
          bar_sync_unless(5, it - it0);
          redo = __any_sync(0xffffffffu, y[0]);
          it += INC_A;
        } while (redo);
        it -= INC_A;
        put_s(0);
        bar_arrive(8, 256);
        load_wo(wo, NA4, NB1);
        out_proj();
        if (warp == 4) LOG(12, tb);
      } else {
        uint32_t qx[2][4], q[4][4];
        if (warp == 6) {
          const uint32_t t1 = (now & ~31u) + NS_M;
          LOG(10, now - due);
          if (elect()) stx32(&gx->T[h][j], ((int)(t1 - due) > 0 ? t1 + NS_PEN : due) | ((s + 1) & 31));
          __syncwarp();
        }
        auto score = [&](const uint32_t (&a0)[4], const uint32_t (&a1)[4]) {
          zero(c);
#pragma unroll
          for (int i = 0; i < 4; i++) mma_h(c[i], i < 2 ? a0 : a1, q[2 + (i >> 1)], i & 1);
        };
        auto put_m = [&](uint32_t a, uint32_t old, uint32_t again) {
#pragma unroll
          for (int i = 0; i < 2; i++) { r4[i] = fmaf(c[3][2 + i], sc, fmaf((c[0][i] + c[1][2 + i]) + c[2][i], sc, __uint_as_float(i ? 0u - old : 0u))); r4[2 + i] = fmaf(r4[i] * 0x1p122f, 0.f, ex2(r4[i])); }
          asm volatile("{.reg .pred p; setp.eq.u32 p, %3, 0; @p st.shared.v2.f32 [%0], {%1,%2};}" :: "r"(a), "f"(r4[2]), "f"(r4[3]), "r"(again) : "memory");
        };
        delay_until(tpub + DLY_A);
        const uint32_t sa = sb + R_S + 512 + w4 * 256 + (L16 >> 1);
        const int it0 = it;
        bool redo;
#pragma unroll 1
        do {
          wait_time(due);
          TS(4);
          ldx<4, 2048>(q, asrc);
          sched();
          load_q(qx[0], (w4 & 1) * 1024); load_q(qx[1], (w4 & 1) * 1024 + 512);
          load_wo(wo, 0, NA6);
          sched();
          score(q[0], q[1]);
          sched();
          const uint32_t y = or_and(or3(dif2v(q[0][0], q[0][2], tag), dif2v(q[1][0], q[1][2], tag), dif2v(q[2][0], q[2][2], tag)), dif2v(q[3][0], q[3][2], tag), it < SPIN_LIMIT);
          put_m(sa + 2560, y, it - it0);
          TS(5);
          bar_arrive_unless(5, it - it0);
          redo = __any_sync(0xffffffffu, y);
          it += INC_A;
        } while (redo);
        it -= INC_A;
        sts64f(sa, r4[0], r4[1]);
        score(qx[0], qx[1]);
        put_m(sa + 3584, 0, 0);
        sts64f(sa + 1536, r4[0], r4[1]);
        bar_arrive(8, 256);
        load_wo(wo, NA6, NB1);
        out_proj();
      }
      TS(8);
      if (s + 1 == NSEG) break;
      wait_x(s + 2, 2);
      TS(9);
      fresh();
      if (N1) project_qk(IC<32>{}, IC<32 + N1>{}, IC<1>{}, [](int) {});
      TS(10);
      xpos(6, 6);
      uint32_t fl = s + 1;
      if (warp == 5) { wait_time(due + NS_F); fl = ldx32(xa + 4096 + ((L16 >> 2) & 60)); }
      reload();
      TS(14);
      pin_mem();
      wait_x(s + 2, 1); wait_x(s + 2, 0);
      if (warp == 5) {
#pragma unroll 1
        while (__any_sync(0xffffffffu, fl != s + 1) && !(EXP & 4) && ++it < SPIN_LIMIT) fl = ldx32(xa + 4096 + ((L16 >> 2) & 60));
        wait_time(due + (NS_B + NS_K));
        if (!(EXP & 2) && elect()) issue_kqv(s + 1);
        __syncwarp();
      }
      if (PFD && warp == 6 && s + PFD < NSEG && elect())
        asm volatile("cp.async.bulk.prefetch.L2.global [%0], 2048;" :: "l"(xin + ((s + PFD) * SEG + ((role + 4 * (role >> 5)) & 31)) * DM) : "memory");
      __syncwarp();
      TS(11);
      LOG(warp, it);
      if (warp == 4) LOG(8, nc);
      bar_sync(0, 256);
      if (N1 < 16) project_qk(IC<32 + N1>{}, IC<48>{}, IC<!N1>{}, [](int) {});
      project_qk(IC<16>{}, IC<32>{}, IC<0>{}, [&](int n) { if ((n & 15) == XWPOS) { __syncwarp(); xok = mbar_test(sb + B_PK, s & 1); __syncwarp(); } });
      if (rare(!xok)) mbar_spin(sb + B_PK, s & 1, it);
      unpark();
      project_qk(IC<0>{}, IC<16>{}, IC<0>{}, [](int) {});
      TS(12);
      wg_wait<0>(); keep(aq);
      TS(1);
      fin_qk();
      TS(15);
    }
    s++;
  }
  if (it >= SPIN_LIMIT || nc >= NC_MAX) g_err = 2;
}

typedef CUresult (*EncodeFn)(CUtensorMap*, CUtensorMapDataType, cuuint32_t, void*, const cuuint64_t*, const cuuint64_t*, const cuuint32_t*,
                             const cuuint32_t*, CUtensorMapInterleave, CUtensorMapSwizzle, CUtensorMapL2promotion, CUtensorMapFloatOOBfill);
static void make_map(EncodeFn fn, CUtensorMap* m, const void* p, uint64_t cols, uint64_t rows, uint64_t pitch, uint32_t bc, uint32_t br, CUtensorMapSwizzle sw) {
  cuuint64_t dims[2] = {cols, rows}, strides[1] = {pitch * 2};
  cuuint32_t box[2] = {bc, br}, es[2] = {1, 1};
  fn(m, CU_TENSOR_MAP_DATA_TYPE_BFLOAT16, 2, const_cast<void*>(p), dims, strides, box, es, CU_TENSOR_MAP_INTERLEAVE_NONE, sw,
     CU_TENSOR_MAP_L2_PROMOTION_L2_256B, CU_TENSOR_MAP_FLOAT_OOB_FILL_NONE);
}

extern "C" void kernel_launch(void* const* d_in, const int* in_sizes, int n_in, void* d_out, int out_size) {
  const bf16* Ax = (const bf16*)d_in[0]; const bf16* mem0 = (const bf16*)d_in[1];
  const bf16* Wq = (const bf16*)d_in[2]; const bf16* Wk = (const bf16*)d_in[3]; const bf16* Wv = (const bf16*)d_in[4];
  const bf16* Wo = (const bf16*)d_in[5];
  const bf16* Bx = (const bf16*)d_in[7]; const bf16* wr = (const bf16*)d_in[8]; const bf16* wi = (const bf16*)d_in[9];
  bf16* out = (bf16*)d_out;

  void* fp = nullptr; cudaDriverEntryPointQueryResult qr;
  cudaGetDriverEntryPoint("cuTensorMapEncodeTiled", &fp, cudaEnableDefault, &qr);
  EncodeFn fn = (EncodeFn)fp;
  void *kqv, *ox, *xr;
  cudaGetSymbolAddress(&xr, g_xraw);
  cudaGetSymbolAddress(&kqv, g_kqv); cudaGetSymbolAddress(&ox, g_ox);
  const CUtensorMapSwizzle S128 = CU_TENSOR_MAP_SWIZZLE_128B, S64 = CU_TENSOR_MAP_SWIZZLE_64B;

  GemmMaps m3; RecMaps mr;
  make_map(fn, &m3.a, ox, HD, S_LEN, HD, 64, 128, S128);
  make_map(fn, &m3.b[0], Wo, DM, HD, DM, 64, 64, S128);
  m3.b[1] = m3.b[0]; m3.b[2] = m3.b[0];
  make_map(fn, &m3.c, out, DM, S_LEN, 2 * DM, 64, 64, S128);
  make_map(fn, &mr.wq, Wq, HD, DM, HD, 32, 256, S64);
  make_map(fn, &mr.wk, Wk, HD, DM, HD, 32, 256, S64);
  make_map(fn, &mr.wv, Wv, HD, DM, HD, 64, 256, S128);
  make_map(fn, &mr.wo, Wo, DM, HD, DM, 64, 128, S128);
  {
    cuuint64_t dims[3] = {64, S_LEN, 16}, strides[2] = {DM * 2, 128};
    cuuint32_t box[3] = {64, 32, 4}, es[3] = {1, 1, 1};
    fn(&mr.x, CU_TENSOR_MAP_DATA_TYPE_BFLOAT16, 3, const_cast<bf16*>(Ax), dims, strides, box, es, CU_TENSOR_MAP_INTERLEAVE_NONE, S128,
       CU_TENSOR_MAP_L2_PROMOTION_L2_256B, CU_TENSOR_MAP_FLOAT_OOB_FILL_NONE);
  }
  for (int i = 0; i < 3; i++) {
    cuuint64_t dims[3] = {128, 32, 512}, strides[2] = {256, 8192};
    cuuint32_t box[3] = {128, i == 0 ? 8u : i == 1 ? 2u : 16u, 4}, es[3] = {1, 1, 1};
    fn(i == 0 ? &mr.k : i == 1 ? &mr.q : &mr.v, CU_TENSOR_MAP_DATA_TYPE_BFLOAT16, 3, kqv, dims, strides, box, es, CU_TENSOR_MAP_INTERLEAVE_NONE,
       CU_TENSOR_MAP_SWIZZLE_NONE, CU_TENSOR_MAP_L2_PROMOTION_L2_256B, CU_TENSOR_MAP_FLOAT_OOB_FILL_NONE);
  }
  {
    cuuint64_t dims[3] = {64, 16, S_LEN}, strides[2] = {128, 2 * DM * 2};
    cuuint32_t box[3] = {64, 16, 2}, es[3] = {1, 1, 1};
    fn(&mr.fo, CU_TENSOR_MAP_DATA_TYPE_BFLOAT16, 3, out + DM, dims, strides, box, es, CU_TENSOR_MAP_INTERLEAVE_NONE, S128,
       CU_TENSOR_MAP_L2_PROMOTION_NONE, CU_TENSOR_MAP_FLOAT_OOB_FILL_NONE);
  }
  constexpr int SM3 = 6 * 32768 + 32768 + 256 + 1024;
  cudaFuncSetAttribute(gemm_kernel<128, 6>, cudaFuncAttributeMaxDynamicSharedMemorySize, SM3);
  cudaFuncSetAttribute(rec_kernel, cudaFuncAttributeMaxDynamicSharedMemorySize, R_TOTAL);

  cudaStream_t st = cudaStreamPerThread;
  Xchg* gx = reinterpret_cast<Xchg*>((reinterpret_cast<uintptr_t>(xr) + 0x1FFFFF) & ~(uintptr_t)0x1FFFFF);
  rec_kernel<<<132, 256, R_TOTAL, st>>>(mr, Ax, mem0, gx, Bx, wr, wi);
  gemm_kernel<128, 6><<<128, 384, SM3, st>>>(m3, 16, 8, 64, 8, reinterpret_cast<uint4*>(gx));
}
```

```cpp
#include <cuda_runtime.h>
#include <cuda_bf16.h>
#include <cuda.h>
#include <stdint.h>
#include <stddef.h>
#include <type_traits>

typedef __nv_bfloat16 bf16;

constexpr int S_LEN = 2048, DM = 1024, NH = 32, DH = 128, MEM = 8, SEG = 32, NSEG = 64;
constexpr int HD = NH * DH;
#define SPIN 20
constexpr int SPIN_LIMIT = 1 << SPIN, INC_A = 1, INC_B = 1;

constexpr unsigned NC_MAX = 4096;
__device__ __align__(1024) uint4 g_kqv[4][128][512];
__device__ __align__(1024) bf16 g_ox[(size_t)S_LEN * HD];
struct Xchg {
  uint4 A[32][4][256];
  uint4 C[4][2][256];
  uint4 B[128][2][256];
  uint32_t T[32][32];
  uint32_t S[128];
  unsigned ctr[64];
};
__device__ __align__(1024) uint4 g_xraw[(sizeof(Xchg) + (1 << 21)) / 16];
__device__ __align__(1024) uint4 g_y[1024 * 256];
__device__ __align__(1024) uint4 g_wt[513 * 512];
__device__ int g_err;

__device__ __forceinline__ unsigned clk() { unsigned long long c; asm volatile("mov.u64 %0, %%clock64;" : "=l"(c)); return (unsigned)c; }
__device__ __forceinline__ uint32_t smem_u32(const void* p) { return (uint32_t)__cvta_generic_to_shared(p); }
__device__ __forceinline__ void mbar_init(uint32_t bar, int cnt) { asm volatile("mbarrier.init.shared::cta.b64 [%0], %1;" :: "r"(bar), "r"(cnt) : "memory"); }
__device__ __forceinline__ void mbar_expect_tx(uint32_t bar, int bytes) { asm volatile("mbarrier.arrive.expect_tx.shared::cta.b64 _, [%0], %1;" :: "r"(bar), "r"(bytes) : "memory"); }
__device__ __forceinline__ void mbar_arrive(uint32_t bar) { asm volatile("mbarrier.arrive.shared::cta.b64 _, [%0];" :: "r"(bar) : "memory"); }
__device__ __forceinline__ void mbar_arrive_cluster(uint32_t bar, int cta) {
  asm volatile("{.reg .b32 r; mapa.shared::cluster.u32 r, %0, %1; mbarrier.arrive.shared::cluster.b64 _, [r];}" :: "r"(bar), "r"(cta) : "memory"); }
__device__ __forceinline__ bool mbar_try(uint32_t bar, int par) {
  uint32_t ok; asm volatile("{.reg .pred p; mbarrier.try_wait.parity.shared::cta.b64 p, [%1], %2; selp.u32 %0, 1, 0, p;}" : "=r"(ok) : "r"(bar), "r"(par) : "memory"); return ok; }
__device__ __forceinline__ bool mbar_test(uint32_t bar, int par) {
  uint32_t ok; asm volatile("{.reg .pred p; mbarrier.test_wait.parity.shared::cta.b64 p, [%1], %2; selp.u32 %0, 1, 0, p;}" : "=r"(ok) : "r"(bar), "r"(par) : "memory"); return ok; }
__device__ __forceinline__ void mbar_wait(uint32_t bar, int par) {
  int it = 0;
  while (!mbar_try(bar, par)) { if (++it > SPIN_LIMIT) { g_err = 1; break; } }
}
__device__ __forceinline__ void tma2d(uint32_t dst, const CUtensorMap* m, int c0, int c1, uint32_t bar) {
  asm volatile("cp.async.bulk.tensor.2d.shared::cluster.global.mbarrier::complete_tx::bytes [%0], [%1, {%3, %4}], [%2];"
    :: "r"(dst), "l"(m), "r"(bar), "r"(c0), "r"(c1) : "memory"); }
__device__ __forceinline__ void tma2d_mc(uint32_t dst, const CUtensorMap* m, int c0, int c1, uint32_t bar, uint16_t mask) {
  asm volatile("cp.async.bulk.tensor.2d.shared::cluster.global.mbarrier::complete_tx::bytes.multicast::cluster [%0], [%1, {%3, %4}], [%2], %5;"
    :: "r"(dst), "l"(m), "r"(bar), "r"(c0), "r"(c1), "h"(mask) : "memory"); }
__device__ __forceinline__ void tma2d_store(const CUtensorMap* m, uint32_t src, int c0, int c1) {
  asm volatile("cp.async.bulk.tensor.2d.global.shared::cta.bulk_group [%0, {%2, %3}], [%1];" :: "l"(m), "r"(src), "r"(c0), "r"(c1) : "memory"); }
__device__ __forceinline__ void fence_async() { asm volatile("fence.proxy.async.shared::cta;" ::: "memory"); }
__device__ __forceinline__ void bar_sync(int id, int n) { asm volatile("bar.sync %0, %1;" :: "r"(id), "r"(n) : "memory"); }
__device__ __forceinline__ void bar_arrive(int id, int n) { asm volatile("bar.arrive %0, %1;" :: "r"(id), "r"(n) : "memory"); }
__device__ __forceinline__ uint32_t pack2(float lo, float hi) { uint32_t r; asm("cvt.rn.bf16x2.f32 %0, %1, %2;" : "=r"(r) : "f"(hi), "f"(lo)); return r; }
__device__ __forceinline__ uint32_t pack2_tag(float lo, float hi, uint32_t T) {
  uint32_t u = ((__float_as_uint(lo) - T + 0x10000u) & 0xFFFE0000u) + T;
  return __byte_perm(u, pack2(0.f, hi), 0x7632); }
__device__ __forceinline__ void ldsm4(uint32_t (&r)[4], uint32_t a) {
  asm volatile("ldmatrix.sync.aligned.m8n8.x4.shared.b16 {%0,%1,%2,%3}, [%4];" : "=r"(r[0]), "=r"(r[1]), "=r"(r[2]), "=r"(r[3]) : "r"(a) : "memory"); }
__device__ __forceinline__ void ldsm4t(uint32_t (&r)[4], uint32_t a) {
  asm volatile("ldmatrix.sync.aligned.m8n8.x4.trans.shared.b16 {%0,%1,%2,%3}, [%4];" : "=r"(r[0]), "=r"(r[1]), "=r"(r[2]), "=r"(r[3]) : "r"(a) : "memory"); }
__device__ __forceinline__ void stsm4(uint32_t a, uint32_t r0, uint32_t r1, uint32_t r2, uint32_t r3) {
  asm volatile("stmatrix.sync.aligned.m8n8.x4.shared.b16 [%0], {%1,%2,%3,%4};" :: "r"(a), "r"(r0), "r"(r1), "r"(r2), "r"(r3) : "memory"); }
__device__ __forceinline__ void stsm4t(uint32_t a, uint32_t r0, uint32_t r1, uint32_t r2, uint32_t r3) {
  asm volatile("stmatrix.sync.aligned.m8n8.x4.trans.shared.b16 [%0], {%1,%2,%3,%4};" :: "r"(a), "r"(r0), "r"(r1), "r"(r2), "r"(r3) : "memory"); }
__device__ __forceinline__ void lds128(uint32_t (&r)[4], uint32_t a) {
  asm volatile("ld.shared.v4.u32 {%0,%1,%2,%3}, [%4];" : "=r"(r[0]), "=r"(r[1]), "=r"(r[2]), "=r"(r[3]) : "r"(a) : "memory"); }
__device__ __forceinline__ float4 lds128f(uint32_t a) { float4 r;
  asm volatile("ld.shared.v4.f32 {%0,%1,%2,%3}, [%4];" : "=f"(r.x), "=f"(r.y), "=f"(r.z), "=f"(r.w) : "r"(a) : "memory"); return r; }
__device__ __forceinline__ float2 lds64f(uint32_t a) { float2 r;
  asm volatile("ld.shared.v2.f32 {%0,%1}, [%2];" : "=f"(r.x), "=f"(r.y) : "r"(a) : "memory"); return r; }
__device__ __forceinline__ void sts128(uint32_t a, uint32_t r0, uint32_t r1, uint32_t r2, uint32_t r3) {
  asm volatile("st.shared.v4.u32 [%0], {%1,%2,%3,%4};" :: "r"(a), "r"(r0), "r"(r1), "r"(r2), "r"(r3) : "memory"); }
__device__ __forceinline__ void sts64f(uint32_t a, float x, float y) { asm volatile("st.shared.v2.f32 [%0], {%1,%2};" :: "r"(a), "f"(x), "f"(y) : "memory"); }
__device__ __forceinline__ void sts32f(uint32_t a, float x) { asm volatile("st.shared.f32 [%0], %1;" :: "r"(a), "f"(x) : "memory"); }
__device__ __forceinline__ void mma16816(float (&d)[4], uint32_t a0, uint32_t a1, uint32_t a2, uint32_t a3, uint32_t b0, uint32_t b1) {
  asm volatile("mma.sync.aligned.m16n8k16.row.col.f32.bf16.bf16.f32 {%0,%1,%2,%3}, {%4,%5,%6,%7}, {%8,%9}, {%0,%1,%2,%3};"
    : "+f"(d[0]), "+f"(d[1]), "+f"(d[2]), "+f"(d[3]) : "r"(a0), "r"(a1), "r"(a2), "r"(a3), "r"(b0), "r"(b1)); }
__device__ __forceinline__ void mma1688(float (&d)[4], uint32_t a0, uint32_t a1, uint32_t b0) {
  asm volatile("mma.sync.aligned.m16n8k8.row.col.f32.bf16.bf16.f32 {%0,%1,%2,%3}, {%4,%5}, {%6}, {%0,%1,%2,%3};"
    : "+f"(d[0]), "+f"(d[1]), "+f"(d[2]), "+f"(d[3]) : "r"(a0), "r"(a1), "r"(b0)); }
__device__ __forceinline__ void ldx128(uint32_t (&r)[4], const void* p) {
  asm volatile("{.reg .b128 t; .reg .b64 a, b; ld.relaxed.gpu.global.b128 t, [%4]; mov.b128 {a, b}, t; mov.b64 {%0,%1}, a; mov.b64 {%2,%3}, b;}"
    : "=r"(r[0]), "=r"(r[1]), "=r"(r[2]), "=r"(r[3]) : "l"(p) : "memory"); }
__device__ __forceinline__ void ldx2x64(uint32_t (&r)[4], const void* p) {
  asm volatile("{.reg .b64 a, b; ld.relaxed.gpu.global.v2.b64 {a, b}, [%4]; mov.b64 {%0,%1}, a; mov.b64 {%2,%3}, b;}"
    : "=r"(r[0]), "=r"(r[1]), "=r"(r[2]), "=r"(r[3]) : "l"(p) : "memory"); }
__device__ __forceinline__ void stx128(void* p, uint32_t r0, uint32_t r1, uint32_t r2, uint32_t r3) {
  asm volatile("{.reg .b128 t; .reg .b64 a, b; mov.b64 a, {%1,%2}; mov.b64 b, {%3,%4}; mov.b128 t, {a, b}; st.relaxed.gpu.global.b128 [%0], t;}"
    :: "l"(p), "r"(r0), "r"(r1), "r"(r2), "r"(r3) : "memory"); }
__device__ __forceinline__ void stx64(void* p, uint32_t r0, uint32_t r1) {
  asm volatile("{.reg .b64 a; mov.b64 a, {%1,%2}; st.relaxed.gpu.global.b64 [%0], a;}" :: "l"(p), "r"(r0), "r"(r1) : "memory"); }
__device__ __forceinline__ uint32_t uni(uint32_t x) { return __shfl_sync(0xffffffffu, x, 0); }
__device__ __forceinline__ uint32_t pin(uint32_t x) { return __shfl_xor_sync(0xffffffffu, x, 0); }
__device__ __forceinline__ float ex2(float x) { float r; asm("ex2.approx.ftz.f32 %0, %1;" : "=f"(r) : "f"(x)); return r; }
__device__ __forceinline__ void wg_fence() { asm volatile("wgmma.fence.sync.aligned;" ::: "memory"); }
__device__ __forceinline__ void wg_commit() { asm volatile("wgmma.commit_group.sync.aligned;" ::: "memory"); }
template <int N> __device__ __forceinline__ void wg_wait() { asm volatile("wgmma.wait_group.sync.aligned %0;" :: "n"(N) : "memory"); }

__device__ __forceinline__ void wgmma_ss_n256_tb1(float (&d)[128], uint64_t da, uint64_t db, int sc) {
  asm volatile("{.reg .pred p; setp.ne.b32 p, %130, 0;\n"
    "wgmma.mma_async.sync.aligned.m64n256k16.f32.bf16.bf16 {%0,%1,%2,%3,%4,%5,%6,%7,%8,%9,%10,%11,%12,%13,%14,%15,%16,%17,%18,%19,%20,%21,%22,%23,%24,%25,%26,%27,%28,%29,%30,%31,%32,%33,%34,%35,%36,%37,%38,%39,%40,%41,%42,%43,%44,%45,%46,%47,%48,%49,%50,%51,%52,%53,%54,%55,%56,%57,%58,%59,%60,%61,%62,%63,%64,%65,%66,%67,%68,%69,%70,%71,%72,%73,%74,%75,%76,%77,%78,%79,%80,%81,%82,%83,%84,%85,%86,%87,%88,%89,%90,%91,%92,%93,%94,%95,%96,%97,%98,%99,%100,%101,%102,%103,%104,%105,%106,%107,%108,%109,%110,%111,%112,%113,%114,%115,%116,%117,%118,%119,%120,%121,%122,%123,%124,%125,%126,%127}, %128, %129, p, 1, 1, 0, 1;}\n"
    : "+f"(d[0]),"+f"(d[1]),"+f"(d[2]),"+f"(d[3]),"+f"(d[4]),"+f"(d[5]),"+f"(d[6]),"+f"(d[7]),"+f"(d[8]),"+f"(d[9]),"+f"(d[10]),"+f"(d[11]),"+f"(d[12]),"+f"(d[13]),"+f"(d[14]),"+f"(d[15]),"+f"(d[16]),"+f"(d[17]),"+f"(d[18]),"+f"(d[19]),"+f"(d[20]),"+f"(d[21]),"+f"(d[22]),"+f"(d[23]),"+f"(d[24]),"+f"(d[25]),"+f"(d[26]),"+f"(d[27]),"+f"(d[28]),"+f"(d[29]),"+f"(d[30]),"+f"(d[31]),"+f"(d[32]),"+f"(d[33]),"+f"(d[34]),"+f"(d[35]),"+f"(d[36]),"+f"(d[37]),"+f"(d[38]),"+f"(d[39]),"+f"(d[40]),"+f"(d[41]),"+f"(d[42]),"+f"(d[43]),"+f"(d[44]),"+f"(d[45]),"+f"(d[46]),"+f"(d[47]),"+f"(d[48]),"+f"(d[49]),"+f"(d[50]),"+f"(d[51]),"+f"(d[52]),"+f"(d[53]),"+f"(d[54]),"+f"(d[55]),"+f"(d[56]),"+f"(d[57]),"+f"(d[58]),"+f"(d[59]),"+f"(d[60]),"+f"(d[61]),"+f"(d[62]),"+f"(d[63]),"+f"(d[64]),"+f"(d[65]),"+f"(d[66]),"+f"(d[67]),"+f"(d[68]),"+f"(d[69]),"+f"(d[70]),"+f"(d[71]),"+f"(d[72]),"+f"(d[73]),"+f"(d[74]),"+f"(d[75]),"+f"(d[76]),"+f"(d[77]),"+f"(d[78]),"+f"(d[79]),"+f"(d[80]),"+f"(d[81]),"+f"(d[82]),"+f"(d[83]),"+f"(d[84]),"+f"(d[85]),"+f"(d[86]),"+f"(d[87]),"+f"(d[88]),"+f"(d[89]),"+f"(d[90]),"+f"(d[91]),"+f"(d[92]),"+f"(d[93]),"+f"(d[94]),"+f"(d[95]),"+f"(d[96]),"+f"(d[97]),"+f"(d[98]),"+f"(d[99]),"+f"(d[100]),"+f"(d[101]),"+f"(d[102]),"+f"(d[103]),"+f"(d[104]),"+f"(d[105]),"+f"(d[106]),"+f"(d[107]),"+f"(d[108]),"+f"(d[109]),"+f"(d[110]),"+f"(d[111]),"+f"(d[112]),"+f"(d[113]),"+f"(d[114]),"+f"(d[115]),"+f"(d[116]),"+f"(d[117]),"+f"(d[118]),"+f"(d[119]),"+f"(d[120]),"+f"(d[121]),"+f"(d[122]),"+f"(d[123]),"+f"(d[124]),"+f"(d[125]),"+f"(d[126]),"+f"(d[127])
    : "l"(da), "l"(db), "r"(sc));
}

__device__ __forceinline__ void wgmma_ss_n128_tb1(float (&d)[64], uint64_t da, uint64_t db, int sc) {
  asm volatile("{.reg .pred p; setp.ne.b32 p, %66, 0;\n"
    "wgmma.mma_async.sync.aligned.m64n128k16.f32.bf16.bf16 {%0,%1,%2,%3,%4,%5,%6,%7,%8,%9,%10,%11,%12,%13,%14,%15,%16,%17,%18,%19,%20,%21,%22,%23,%24,%25,%26,%27,%28,%29,%30,%31,%32,%33,%34,%35,%36,%37,%38,%39,%40,%41,%42,%43,%44,%45,%46,%47,%48,%49,%50,%51,%52,%53,%54,%55,%56,%57,%58,%59,%60,%61,%62,%63}, %64, %65, p, 1, 1, 0, 1;}\n"
    : "+f"(d[0]),"+f"(d[1]),"+f"(d[2]),"+f"(d[3]),"+f"(d[4]),"+f"(d[5]),"+f"(d[6]),"+f"(d[7]),"+f"(d[8]),"+f"(d[9]),"+f"(d[10]),"+f"(d[11]),"+f"(d[12]),"+f"(d[13]),"+f"(d[14]),"+f"(d[15]),"+f"(d[16]),"+f"(d[17]),"+f"(d[18]),"+f"(d[19]),"+f"(d[20]),"+f"(d[21]),"+f"(d[22]),"+f"(d[23]),"+f"(d[24]),"+f"(d[25]),"+f"(d[26]),"+f"(d[27]),"+f"(d[28]),"+f"(d[29]),"+f"(d[30]),"+f"(d[31]),"+f"(d[32]),"+f"(d[33]),"+f"(d[34]),"+f"(d[35]),"+f"(d[36]),"+f"(d[37]),"+f"(d[38]),"+f"(d[39]),"+f"(d[40]),"+f"(d[41]),"+f"(d[42]),"+f"(d[43]),"+f"(d[44]),"+f"(d[45]),"+f"(d[46]),"+f"(d[47]),"+f"(d[48]),"+f"(d[49]),"+f"(d[50]),"+f"(d[51]),"+f"(d[52]),"+f"(d[53]),"+f"(d[54]),"+f"(d[55]),"+f"(d[56]),"+f"(d[57]),"+f"(d[58]),"+f"(d[59]),"+f"(d[60]),"+f"(d[61]),"+f"(d[62]),"+f"(d[63])
    : "l"(da), "l"(db), "r"(sc));
}

template <int BN> struct WG;
template <> struct WG<256> { static __device__ __forceinline__ void mma(float (&d)[128], uint64_t a, uint64_t b, int sc) { wgmma_ss_n256_tb1(d, a, b, sc); } };
template <> struct WG<128> { static __device__ __forceinline__ void mma(float (&d)[64], uint64_t a, uint64_t b, int sc) { wgmma_ss_n128_tb1(d, a, b, sc); } };

struct GemmMaps { CUtensorMap a, b[3], c; };
template <int BN, int STAGES>
__global__ void __cluster_dims__(2, 1, 1) __launch_bounds__(384, 1)
gemm_kernel(const __grid_constant__ GemmMaps maps, int tilesM, int tilesN, int kblocks, int nPerB, uint4* __restrict__ clearX) {
  extern __shared__ __align__(1024) uint8_t smem_raw[];
  constexpr int STAGE_BYTES = 16384 + BN * 128;
  constexpr int NBOX = BN / 64;
  const uint32_t sbase = (smem_u32(smem_raw) + 1023) & ~1023u;
  const uint32_t sEpi = sbase + STAGES * STAGE_BYTES;
  const uint32_t sBar = sEpi + 32768;
  const int warp = threadIdx.x >> 5, lane = threadIdx.x & 31, wg = warp >> 2;
  uint32_t crank; asm("mov.u32 %0, %%cluster_ctarank;" : "=r"(crank));
#define GT(k)
  const int npairs = (tilesM >> 1) * tilesN, pair0 = blockIdx.x >> 1, pstep = gridDim.x >> 1;
  if (threadIdx.x == 256) {
    asm volatile("prefetch.tensormap [%0];" :: "l"(&maps.b[0]) : "memory");
    for (int i = 0; i < STAGES; i++) { mbar_init(sBar + 8 * i, 1); mbar_init(sBar + 8 * (STAGES + i), 4); }
    asm volatile("fence.mbarrier_init.release.cluster;" ::: "memory");
    asm volatile("barrier.cluster.arrive.relaxed;" ::: "memory");
    for (int i = 0; i < STAGES; i++) {
      mbar_expect_tx(sBar + 8 * i, STAGE_BYTES);
      tma2d(sbase + i * STAGE_BYTES, &maps.a, i * 64, ((pair0 % (tilesM >> 1)) * 2 + crank) * 128, sBar + 8 * i);
    }
    asm volatile("prefetch.tensormap [%0];" :: "l"(&maps.c) : "memory");
  } else asm volatile("barrier.cluster.arrive.relaxed;" ::: "memory");
  asm volatile("barrier.cluster.wait.acquire;" ::: "memory");
  __syncwarp();
  if (wg == 2) {
    asm volatile("setmaxnreg.dec.sync.aligned.u32 40;");
    if (warp > 8) {
      __nanosleep(4000);
      for (int i = blockIdx.x * 96 + threadIdx.x - 288; i < (int)(sizeof(Xchg) / 16); i += gridDim.x * 96) clearX[i] = make_uint4(0, 0, 0, 0);
    }
    if (warp == 8 && lane == 0) {
      int st = 0, ph = 1;
      for (int p = pair0; p < npairs; p += pstep) {
        const int tm = (p % (tilesM >> 1)) * 2 + crank, tn = p / (tilesM >> 1);
        const CUtensorMap* mb = &maps.b[tn / nPerB];
        const int n0 = (tn % nPerB) * BN;
        for (int kb = 0; kb < kblocks; kb++) {
          const uint32_t a = sbase + st * STAGE_BYTES, full = sBar + 8 * st;
          if (p > pair0 || kb >= STAGES) {
            mbar_wait(sBar + 8 * (STAGES + st), ph);
            mbar_expect_tx(full, STAGE_BYTES);
            tma2d(a, &maps.a, kb * 64, tm * 128, full);
          }
#pragma unroll
          for (int i = 0; i < NBOX / 2; i++) {
            const int bx = crank * (NBOX / 2) + i;
            tma2d_mc(a + 16384 + bx * 8192, mb, n0 + bx * 64, kb * 64, full, (uint16_t)3);
          }
          if (++st == STAGES) { st = 0; ph ^= 1; }
        }
      }
      for (int i = 0; i < STAGES; i++) { mbar_wait(sBar + 8 * (STAGES + st), ph); if (++st == STAGES) { st = 0; ph ^= 1; } }
    }
  } else {
    asm volatile("setmaxnreg.inc.sync.aligned.u32 232;");
    int st = 0, ph = 0;
    float acc[BN / 2];
    const uint64_t descA0 = (uint64_t)(((sbase + wg * 8192) & 0x3FFFF) >> 4) | (1ull << 16) | (64ull << 32) | (1ull << 62);
    const uint64_t descB0 = (uint64_t)(((sbase + 16384) & 0x3FFFF) >> 4) | (512ull << 16) | (64ull << 32) | (1ull << 62);
    const uint32_t epi = sEpi + wg * 16384;
    for (int p = pair0; p < npairs; p += pstep) {
      const int tm = (p % (tilesM >> 1)) * 2 + crank, tn = p / (tilesM >> 1);
      int prev = -1;
      for (int kb = 0; kb < kblocks; kb++) {
        mbar_wait(sBar + 8 * st, ph);
        if ((kb & 15) == 0) { GT(kb >> 4); }
        wg_fence();
        const uint64_t so = (uint64_t)(st * (STAGE_BYTES >> 4));
#pragma unroll
        for (int k = 0; k < 4; k++) WG<BN>::mma(acc, descA0 + so + k * 2, descB0 + so + k * 128, kb | k);
        wg_commit();
        if (prev >= 0) {
          wg_wait<1>();
          if ((threadIdx.x & 127) < 2) mbar_arrive_cluster(sBar + 8 * (STAGES + prev), threadIdx.x & 1);
        }
        prev = st;
        if (++st == STAGES) { st = 0; ph ^= 1; }
      }
      wg_wait<0>();
      if ((threadIdx.x & 127) < 2) mbar_arrive_cluster(sBar + 8 * (STAGES + prev), threadIdx.x & 1);
      GT(4);
#pragma unroll
      for (int r = 0; r < BN / 128; r++) {
        if (r || p > pair0) {
          if ((threadIdx.x & 127) == 0) asm volatile("cp.async.bulk.wait_group.read 0;" ::: "memory");
          bar_sync(1 + wg, 128);
        }
        const int row = (warp & 3) * 16 + (lane & 15);
#pragma unroll
        for (int i = 0; i < 8; i++) {
          const int c = 2 * (i & 3) + (lane >> 4);
          const float* q = &acc[r * 64 + i * 8];
          stsm4(epi + (i >> 2) * 8192 + row * 128 + ((c ^ (row & 7)) << 4), pack2(q[0], q[1]), pack2(q[2], q[3]), pack2(q[4], q[5]), pack2(q[6], q[7]));
        }
        fence_async();
        bar_sync(1 + wg, 128);
        if ((threadIdx.x & 127) == 0) {
          tma2d_store(&maps.c, epi, tn * BN + r * 128, tm * 128 + wg * 64);
          tma2d_store(&maps.c, epi + 8192, tn * BN + r * 128 + 64, tm * 128 + wg * 64);
          asm volatile("cp.async.bulk.commit_group;" ::: "memory");
        }
      }
    }
    GT(5);
    if ((threadIdx.x & 127) == 0) asm volatile("cp.async.bulk.wait_group.read 0;" ::: "memory");
    GT(6);
  }
}

struct Dft { uint32_t m[2][2][2][4]; };
template <bool P4> __device__ __forceinline__ int fidx(int tile, int x) { return P4 ? 4 * (x >> 1) + 2 * (tile & 1) + (x & 1) + 16 * (tile >> 1) : x + 8 * tile; }
__device__ __forceinline__ float2 cis(int k, int n) {
  k &= n - 1; if (2 * k > n) k -= n;
  const float a = (float)k * (6.283185307179586f / (float)n);
  return make_float2(__cosf(a), __sinf(a));
}
template <bool OUT4> __device__ __forceinline__ void make_dft(Dft& D, int g, int t) {
#pragma unroll
  for (int q = 0; q < 16; q++) {
    const int b = q >> 3, u = (q >> 2) & 1, r = (q >> 1) & 1, v = q & 1;
    const float2 w = cis(fidx<OUT4>(v, g) * fidx<false>(2 * u + r, 2 * t + b), 32);
    D.m[b][u][0][q & 3] = pack2(w.x, w.y); D.m[b][u][1][q & 3] = pack2(-w.y, w.x);
  }
}
__device__ __forceinline__ void mma_dc(float (&d)[4], uint32_t a0, uint32_t a1, uint32_t a2, uint32_t a3, uint32_t b0, uint32_t b1, const float (&c)[4]) {
  asm("mma.sync.aligned.m16n8k16.row.col.f32.bf16.bf16.f32 {%0,%1,%2,%3}, {%4,%5,%6,%7}, {%8,%9}, {%10,%11,%12,%13};"
    : "=f"(d[0]), "=f"(d[1]), "=f"(d[2]), "=f"(d[3]) : "r"(a0), "r"(a1), "r"(a2), "r"(a3), "r"(b0), "r"(b1), "f"(c[0]), "f"(c[1]), "f"(c[2]), "f"(c[3])); }
__device__ __forceinline__ void dft_b(const Dft& D, const uint32_t (&x)[2][4], float (&o)[2][8]) {
#pragma unroll
  for (int ri = 0; ri < 2; ri++) {
    float z[4] = {0.f, 0.f, 0.f, 0.f}, e[4], p[4];
    mma_dc(e, D.m[0][0][ri][0], D.m[0][0][ri][1], D.m[0][0][ri][2], D.m[0][0][ri][3], x[0][0], x[0][1], z);
    mma_dc(e, D.m[0][1][ri][0], D.m[0][1][ri][1], D.m[0][1][ri][2], D.m[0][1][ri][3], x[0][2], x[0][3], e);
    mma_dc(p, D.m[1][0][ri][0], D.m[1][0][ri][1], D.m[1][0][ri][2], D.m[1][0][ri][3], x[1][0], x[1][1], e);
    mma_dc(p, D.m[1][1][ri][0], D.m[1][1][ri][1], D.m[1][1][ri][2], D.m[1][1][ri][3], x[1][2], x[1][3], p);
#pragma unroll
    for (int q = 0; q < 4; q++) { o[ri][q] = p[q]; o[ri][4 + q] = fmaf(2.f, e[q], -p[q]); }
  }
}
__device__ __forceinline__ void dft_a(const uint32_t (&m)[2][2][4], const uint32_t (&x0)[2][4], const uint32_t (&x1)[2][4], float (&o)[2][8]) {
#pragma unroll
  for (int ri = 0; ri < 2; ri++) {
    float z[4] = {0.f, 0.f, 0.f, 0.f}, e[4], p[4];
    mma_dc(e, x0[0][0], x1[0][0], x0[0][1], x1[0][1], m[0][ri][0], m[0][ri][1], z);
    mma_dc(e, x0[0][2], x1[0][2], x0[0][3], x1[0][3], m[0][ri][2], m[0][ri][3], e);
    mma_dc(p, x0[1][0], x1[1][0], x0[1][1], x1[1][1], m[1][ri][0], m[1][ri][1], e);
    mma_dc(p, x0[1][2], x1[1][2], x0[1][3], x1[1][3], m[1][ri][2], m[1][ri][3], p);
#pragma unroll
    for (int q = 0; q < 4; q++) { o[ri][q] = p[q]; o[ri][4 + q] = fmaf(2.f, e[q], -p[q]); }
  }
}
__device__ __forceinline__ uint32_t twid(float re, float im, float c, float s) { return pack2(fmaf(re, c, im * s), fmaf(im, c, -re * s)); }
__device__ __forceinline__ void cpa16(uint32_t d, const void* s) { asm volatile("cp.async.cg.shared.global [%0], [%1], 16;" :: "r"(d), "l"(s) : "memory"); }
__device__ __forceinline__ void sts32(uint32_t a, uint32_t x) { asm volatile("st.shared.u32 [%0], %1;" :: "r"(a), "r"(x) : "memory"); }
__device__ __forceinline__ void cpa_commit() { asm volatile("cp.async.commit_group;" ::: "memory"); }
template <int N> __device__ __forceinline__ void cpa_wait() { asm volatile("cp.async.wait_group %0;" :: "n"(N) : "memory"); }
__device__ __forceinline__ uint32_t lds32(uint32_t a) { uint32_t r; asm volatile("ld.shared.u32 %0, [%1];" : "=r"(r) : "r"(a) : "memory"); return r; }
#define FMID 0
constexpr int F_TP = 4112, F_TSZ = 8 * F_TP;

__device__ __forceinline__ uint32_t ldnc32(const void* p) { uint32_t v; asm volatile("ld.global.nc.b32 %0, [%1];" : "=r"(v) : "l"(p) : "memory"); return v; }
template <class F>
__device__ __forceinline__ void fft_wprep(const bf16* __restrict__ wr, const bf16* __restrict__ wi, int cta, F&& mid) {
  const int tid = threadIdx.x, g = (cta >> 1) & 7, c = (cta >> 4) & 3, t = 2 * (cta & 1) + (tid & 1);
  const int k0 = g + 8 * (cta >> 6) + 32 * (8 * c + 2 * t), l0 = (tid & ~1) + (g & 1);
  uint32_t a[4][4], b[4][4];
#pragma unroll
  for (int q = 0; q < 16; q++) {
    const int o = (k0 + 16 * (q >> 3) + 32 * ((q >> 1) & 1) + 1024 * (q & 1)) * 513 + l0 + 256 * ((q >> 2) & 1);
    a[q >> 2][q & 3] = ldnc32(wr + o);
    b[q >> 2][q & 3] = ldnc32(wi + o);
  }
  const int e = cta * 32 + (tid & 31), lh = (e >> 11) * 512, k = e & 2047, k2 = (k >> 5) & 31;
  uint32_t hz[4];
#pragma unroll
  for (int q = 0; q < 4; q++) asm volatile("ld.global.nc.u16 %0, [%1];" : "=r"(hz[q]) : "l"((q < 2 ? wr : wi) + (q & 1 ? (2048 - k) & 2047 : k) * 513 + lh) : "memory");
  mid();
  uint4* dst = g_wt + l0 * 512 + cta * 2 + (tid & 1);
#pragma unroll
  for (int q = 0; q < 8; q++) {
    const int hf = q >> 1, l = l0 + 256 * (hf & 1) + (q & 1);
    const uint32_t sel = (q & 1) ? 0x7632 : 0x5410;
    if (l & 511) dst[(256 * (hf & 1) + (q & 1)) * 512 + 256 * (q >> 2)] = make_uint4(__byte_perm(a[hf][0], b[hf][0], sel), __byte_perm(a[hf][1], b[hf][1], sel),
                                                                                   __byte_perm(a[hf][2], b[hf][2], sel), __byte_perm(a[hf][3], b[hf][3], sel));
  }
  if (tid < 32) reinterpret_cast<uint32_t*>(g_wt)[(64 * ((k >> 3) & 3) + 16 * (k2 >> 3) + 2 * (k & 7) + ((k2 >> 2) & 1)) * 8 + lh * 2048 + 2 * (k2 & 3) + (k >> 10)] =
      pack2(0.5f * (__uint_as_float(hz[0] << 16) + __uint_as_float(hz[1] << 16)), 0.5f * (__uint_as_float(hz[2] << 16) - __uint_as_float(hz[3] << 16)));
}

template <class F>
__device__ __forceinline__ void fft_rows_fwd(const bf16* __restrict__ x, const bf16* __restrict__ wr, const bf16* __restrict__ wi, uint32_t tb, int it, F&& mid) {
  const int warp = threadIdx.x >> 5, lane = threadIdx.x & 31, g = lane >> 2, t = lane & 3;
  const uint32_t in = tb + warp * 4096;
  const uint32_t f0 = in + (lane >> 3) * 256 + (((lane & 7) ^ (2 * (lane >> 3))) << 4);
  const bf16* src = x + ((256 * (warp & 3) + 64 * (warp >> 2) + 128 * (it & 1) + 32 * ((it >> 4) & 1) + 8 * (it >> 5) + ((it >> 1) & 7)) * 2048 + lane * 8);
#pragma unroll
  for (int q = 0; q < 8; q++) cpa16((f0 ^ ((q >> 2) * 144)) + (q & 3) * 1024, src + q * 256);
  cpa_commit();
  Dft D;
  float2 tw[4][8];
  fft_wprep(wr, wi, it, [&]() {
    if (FMID == 0) mid();
    make_dft<true>(D, g, t);
#pragma unroll
    for (int q = 0; q < 32; q++) {
      tw[q >> 3][q & 7] = cis(fidx<true>((q >> 1) & 3, g) * fidx<false>(q >> 3, 2 * t + (q & 1)), 1024);
      if (FMID) asm volatile("" : "+f"(tw[q >> 3][q & 7].x), "+f"(tw[q >> 3][q & 7].y) :: "memory");
    }
    if (FMID == 1) mid();
  });
  if (FMID == 2) mid();
  cpa_wait<0>(); __syncwarp();
  uint32_t a[4][2][4], y[4][2][4];
#pragma unroll
  for (int q = 0; q < 8; q++) ldsm4t(a[q & 3][q >> 2], (in + lane * 128 + ((lane & 7) << 4)) ^ (q << 4));
  float o[2][8];
#pragma unroll
  for (int i = 0; i < 4; i++) {
    dft_b(D, a[i], o);
#pragma unroll
    for (int q = 0; q < 8; q++) y[q >> 1][q & 1][i] = twid(o[0][q], o[1][q], tw[i][q].x, tw[i][q].y);
  }
  __syncthreads();
  const uint32_t w0 = tb + warp * F_TP + fidx<true>(0, g) * 128 + t * 16 + ((g & 1) << 6), wz = (g & 1) ? -64 : 64;
#pragma unroll
  for (int z = 0; z < 2; z++) {
    float o2[2][8];
    dft_b(D, y[2 * z], o); dft_b(D, y[2 * z + 1], o2);
#pragma unroll
    for (int i = 0; i < 4; i++) {
      const float sg = i < 2 ? 1.f : -1.f;
      sts128(w0 + z * wz + fidx<true>(i, 0) * 128, pack2(o[0][2 * i], sg * o[1][2 * i]), pack2(o[0][2 * i + 1], sg * o[1][2 * i + 1]),
             pack2(o2[0][2 * i], sg * o2[1][2 * i]), pack2(o2[0][2 * i + 1], sg * o2[1][2 * i + 1]));
    }
  }
  __syncthreads();
  const uint32_t ra = tb + (lane & 1) * 4 * F_TP + ((lane >> 1) + 16 * (warp ^ ((warp >> 1) & 1))) * 4;
  uint4* dst = g_y + (threadIdx.x >> 1) * 256 + (lane & 1) + it * 2;
#pragma unroll
  for (int q = 0; q < 8; q++) { const uint32_t r = ra + q * 512; dst[q * 32768] = make_uint4(lds32(r), lds32(r + F_TP), lds32(r + 2 * F_TP), lds32(r + 3 * F_TP)); }
}

template <class F>
__device__ __forceinline__ void fft_cols(uint32_t sb, int cta, int ncta, F&& ready) {
  const int warp = threadIdx.x >> 5, lane = threadIdx.x & 31, g = lane >> 2, t = lane & 3;
  const uint32_t in = sb + warp * 16384 + lane * 16, tab = sb + 131072 + lane * 16;
  auto fetch_y = [&](int l) {
#pragma unroll
    for (int q = 0; q < 16; q++) cpa16(in + q * 512, g_y + (q < 8 ? l : (1024 - l) & 1023) * 256 + (q & 7) * 32 + lane);
  };
  auto fetch_w = [&](int l) {
#pragma unroll
    for (int q = 0; q < 16; q++) cpa16(in + 8192 + q * 512, g_wt + l * 512 + q * 32 + lane);
  };
  const int l0 = cta * 8 + warp, dl = ncta * 8;
  Dft D; make_dft<false>(D, g, t);
#pragma unroll
  for (int q = 2 * warp; q < 2 * warp + 2; q++) {
    const int r = fidx<false>(q & 3, g), c = fidx<false>(q >> 2, 2 * t);
    const float2 w0 = cis(r * c, 1024), w1 = cis(r * c + r, 1024), p0 = cis(r + 32 * c, 2048), p1 = cis(r + 32 * c + 32, 2048);
    sts128(tab + q * 512, __float_as_uint(w0.x), __float_as_uint(w0.y), __float_as_uint(w1.x), __float_as_uint(w1.y));
    sts128(tab + 8192 + q * 512, __float_as_uint(p0.x), __float_as_uint(p0.y), __float_as_uint(p1.x), __float_as_uint(p1.y));
  }
  if (warp == 0) {
#pragma unroll
    for (int q = 0; q < 8; q++) {
      const int v = q >> 2, b = (q >> 1) & 1, ri = q & 1;
      sts128(tab + 16384 + q * 512, D.m[b][0][ri][v], D.m[b][0][ri][v + 2], D.m[b][1][ri][v], D.m[b][1][ri][v + 2]);
    }
  }
  ready();
  fetch_y(l0); cpa_commit();
  fetch_w(l0); cpa_commit();
#pragma unroll 1
  for (int l = l0; l <= 512; l += dl) {
    uint32_t a[2][4][2][4], y[2][4][2][4];
    float o[2][2][8];
    cpa_wait<1>();
#pragma unroll
    for (int q = 0; q < 16; q++) lds128(a[q >> 3][(q >> 1) & 3][q & 1], in + q * 512);
    if (!(l & 511)) {
      const uint32_t m0 = l ? 0x80000000u : 0u;
#pragma unroll
      for (int q = 0; q < 32; q++) { a[0][q >> 3][(q >> 2) & 1][q & 3] ^= m0; a[1][q >> 3][(q >> 2) & 1][q & 3] ^= m0 ^ 0x80000000u; }
    }
    auto first = [&]() {
#pragma unroll
      for (int i = 0; i < 4; i++) {
        dft_b(D, a[0][i], o[0]); dft_b(D, a[1][i], o[1]);
#pragma unroll
        for (int r = 0; r < 4; r++) {
          const float4 w = lds128f(tab + (4 * i + r) * 512);
#pragma unroll
          for (int s = 0; s < 2; s++) {
            y[s][r][0][i] = twid(o[s][0][2 * r], o[s][1][2 * r], w.x, w.y);
            y[s][r][1][i] = twid(o[s][0][2 * r + 1], o[s][1][2 * r + 1], w.z, w.w);
          }
        }
      }
    };
    first();
    if (l + dl <= 512) fetch_y(l + dl);
    cpa_commit();
    cpa_wait<1>();
#pragma unroll
    for (int zv = 0; zv < 4; zv++) {
      const int z = zv >> 1, v = zv & 1;
      uint32_t m[2][2][4];
#pragma unroll
      for (int q = 0; q < 4; q++) lds128(m[q >> 1][q & 1], tab + 16384 + (4 * v + q) * 512);
      dft_a(m, y[0][2 * z], y[0][2 * z + 1], o[0]); dft_a(m, y[1][2 * z], y[1][2 * z + 1], o[1]);
#pragma unroll
      for (int q = 0; q < 4; q++) {
        const int i = 2 * z + (q & 1), c = v + (q & 2);
        uint32_t w[4]; lds128(w, in + 8192 + (4 * i + c) * 512);
        const float4 ph = lds128f(tab + 8192 + (4 * c + i) * 512);
#pragma unroll
        for (int b = 0; b < 2; b++) {
          const float cs = b ? ph.z : ph.x, sn = b ? ph.w : ph.y;
          const float r1 = __uint_as_float(w[2 * b] << 16), i1 = __uint_as_float(w[2 * b] & 0xFFFF0000u);
          const float r2 = __uint_as_float(w[2 * b + 1] << 16), i2 = __uint_as_float(w[2 * b + 1] & 0xFFFF0000u);
          const float Sr = r1 + r2, Si = i1 + i2, Dr = r1 - r2, Di = i1 - i2;
          const float ar = fmaf(-Dr, sn, Sr), ai = fmaf(-Di, sn, Si), dr = fmaf(Dr, sn, Sr), di = fmaf(Di, sn, Si), br = -Di * cs, bi = Dr * cs;
          const float Ar = o[0][0][2 * q + b], Ai = o[0][1][2 * q + b], Br = o[1][0][2 * q + b], Bi = o[1][1][2 * q + b];
          a[0][i][b][c] = pack2(fmaf(ar, Ai, fmaf(ai, Ar, fmaf(br, Bi, bi * Br))), fmaf(ar, Ar, fmaf(-ai, Ai, fmaf(br, Br, -bi * Bi))));
          a[1][i][b][c] = pack2(fmaf(dr, Bi, fmaf(di, Br, fmaf(-br, Ai, -bi * Ar))), fmaf(dr, Br, fmaf(-di, Bi, fmaf(-br, Ar, bi * Ai))));
        }
      }
    }
    if (l + dl <= 512) fetch_w(l + dl);
    cpa_commit();
    first();
#pragma unroll
    for (int s = 0; s < 2; s++) {
      uint4* dst = g_y + (s ? (1024 - l) & 1023 : l) * 256 + lane;
      const float sg = s ? -1.f : 1.f;
#pragma unroll
      for (int i = 0; i < 4; i++) {
        dft_b(D, y[s][i], o[0]);
#pragma unroll
        for (int b = 0; b < 2; b++)
          dst[(2 * i + b) * 32] = make_uint4(pack2(sg * o[0][0][b], o[0][1][b]), pack2(sg * o[0][0][2 + b], o[0][1][2 + b]),
                                             pack2(sg * o[0][0][4 + b], o[0][1][4 + b]), pack2(sg * o[0][0][6 + b], o[0][1][6 + b]));
      }
    }
  }
}

template <class F>
__device__ __forceinline__ void fft_rows_inv(const CUtensorMap* om, uint32_t sb, int cta, int ncta, F&& ready) {
  const int warp = threadIdx.x >> 5, lane = threadIdx.x & 31, g = lane >> 2, t = lane & 3, wg = warp >> 2, w4 = warp & 3;
  const uint32_t tb = sb + 32768 + wg * 2 * F_TSZ;
  const uint4* src = g_y + pin((256 * ((lane >> 1) & 3) + 64 * (lane >> 3) + 8 * w4) * 256 + (lane & 1));
  const uint32_t wa = pin(tb + (lane & 1) * 4 * F_TP + w4 * 1024 + (lane >> 1) * 4);
  uint4 pf[8];
  auto fetch = [&](int it, int hf) {
#pragma unroll
    for (int q = 0; q < 8; q++) pf[q] = __ldcg(src + (it * 2 + hf * 8192) + q * 256);
  };
  auto put = [&](uint32_t off) {
#pragma unroll
    for (int q = 0; q < 8; q++) {
      sts32(wa + off + q * 64, pf[q].x); sts32(wa + off + q * 64 + F_TP, pf[q].y);
      sts32(wa + off + q * 64 + 2 * F_TP, pf[q].z); sts32(wa + off + q * 64 + 3 * F_TP, pf[q].w);
    }
  };
  const int it0 = 2 * cta + wg;
  Dft D; make_dft<false>(D, g, t);
  float2 tw[4][8];
#pragma unroll
  for (int q = 0; q < 32; q++) {
    tw[q >> 3][q & 7] = cis(fidx<false>((q >> 1) & 3, g) * fidx<false>(q >> 3, 2 * t + (q & 1)), 1024);
    tw[q >> 3][q & 7].x *= 1.f / 2097152.f; tw[q >> 3][q & 7].y *= 1.f / 2097152.f;
    asm volatile("" : "+f"(tw[q >> 3][q & 7].x), "+f"(tw[q >> 3][q & 7].y) :: "memory");
  }
  ready();
  fetch(it0, 0); put(0); fetch(it0, 1); put(512);
  const uint32_t la = pin(tb + w4 * F_TP + lane * 16), ob = uni(sb + warp * 4096);
  const uint32_t oa = pin(ob + (lane >> 1) * 128 + (((4 * (lane & 1)) ^ ((lane >> 1) & 7)) << 4));
#pragma unroll 1
  for (int n = 0;; n++) {
    const int it = it0 + (n >> 1) * 2 * ncta, hf = n & 1, buf = (n >> 1) & 1;
    if (it >= 128) break;
    if (!hf) bar_sync(1 + wg, 128);
    uint32_t a[4][2][4], y[4][2][4];
#pragma unroll
    for (int q = 0; q < 8; q++) lds128(a[q >> 1][q & 1], la + buf * F_TSZ + hf * 4 * F_TP + q * 512);
    fetch(min(it + 2 * ncta, 127), hf);
    float o[2][8];
#pragma unroll
    for (int i = 0; i < 4; i++) {
      dft_b(D, a[i], o);
#pragma unroll
      for (int q = 0; q < 8; q++) y[q >> 1][q & 1][i] = twid(o[0][q], o[1][q], tw[i][q].x, tw[i][q].y);
    }
    if (lane == 0) asm volatile("cp.async.bulk.wait_group.read 0;" ::: "memory");
    __syncwarp();
#pragma unroll
    for (int c = 0; c < 4; c++) {
      dft_b(D, y[c], o);
#pragma unroll
      for (int ri = 0; ri < 2; ri++)
        stsm4((oa ^ (c << 4)) + (1 - ri) * 2048, pack2(o[ri][0], o[ri][1]), pack2(o[ri][2], o[ri][3]), pack2(o[ri][4], o[ri][5]), pack2(o[ri][6], o[ri][7]));
    }
    fence_async();
    __syncwarp();
    if (lane == 0) {
      const int m = 256 * w4 + 32 * ((it >> 1) & 7) + 8 * (it >> 5) + 4 * (it & 1) + 2 * hf + ((it >> 4) & 1);
      asm volatile("cp.async.bulk.tensor.3d.global.shared::cta.bulk_group [%0, {0, 0, %2}], [%1];" :: "l"(om), "r"(ob), "r"(2 * m) : "memory");
      asm volatile("cp.async.bulk.commit_group;" ::: "memory");
    }
    put((buf ^ 1) * F_TSZ + hf * 512);
  }
  if (lane == 0) asm volatile("cp.async.bulk.wait_group 0;" ::: "memory");
}
__device__ __forceinline__ void grid_arrive(unsigned* ctr) {
  __syncthreads();
  if (threadIdx.x == 0) { __threadfence(); atomicAdd(ctr, 1u); }
}
__device__ __forceinline__ void grid_wait(unsigned* ctr, unsigned n) {
  if (threadIdx.x == 224) {
    int it = 0;
    while (*reinterpret_cast<volatile unsigned*>(ctr) < n) { __nanosleep(100); if (++it > SPIN_LIMIT) { g_err = 3; break; } }
    __threadfence();
  }
  __syncthreads();
}

struct RecMaps { CUtensorMap wq, wk, wv, wo, x, k, q, v, fo; };
#define NSW 16
#define EXP 0
#define NPB 3
#define NPB0 3
#define NPC 0
#define WOP 2
#define HOME 7
#define DL0 14
#define PD1 4
#define NE4 6
#define NA4 14
#define NA6 18
#define NB1 24
#define TQL 7
#define NQ 16
#define TQP (NQ - 1)
#define OXPOS 4
#define XWPOS 10
#define RI 9
#define RJ 8
#define NPRE 22
#define PFD 4
#define PD0 4
#define VB NV0
#define NPA 0
#define N1 16
#define DL1 16
#define PACE 0
#define RE0 0
#define RE1 0
#define RP1 23
#define X2 2
#define X3 2
#define SPOS 2
#ifndef NV0
#define NV0 4
#endif
#define TGP 3
#define LW0 8
#define X1 4
#define X0 4
constexpr int R_WO = 0, R_X = 65536, R_MEM = 131072, R_WC = 147456, R_RED = R_WC + NSW * 2048, R_O = R_RED, R_S = R_O + 2048, R_P = R_S + 3072, R_STAGE = R_P + 2048,
              R_K = R_STAGE + 8192, R_Q = R_K + 8192, R_V = R_Q + 2048, R_ID = R_V + 16384, R_T = R_ID + 512, R_DST = R_T + 512, R_RD = R_DST + 2048, R_BAR = R_RD + 2048, R_TS = R_BAR + 128,
              R_TOTAL = R_TS;
#define TS(i)
#define LOG(i, v)
constexpr int B_KV = R_BAR, B_W = R_BAR + 8, B_X = R_BAR + 80, B_PK = R_BAR + 24, B_C = R_BAR + 32, B_B = R_BAR + 40, B_DUE = R_BAR + 48, B_ONE = R_BAR + 64;
#define DLY_A 150
#define DLY_V 150
#define DLY_C 200
#define NS_B 1120
#define NS_C 1728
#define NS_P 2624
#define NS_V 128
#define NS_F 896
#define NS_K 128
#define NS_M 32
#define NS_X 128
#define MG_Z 0x00010206
#define MG_Y 0x0001051a
#define NS_PEN 1024
__device__ __forceinline__ float rcp(float x) { float r; asm("rcp.approx.ftz.f32 %0, %1;" : "=f"(r) : "f"(x)); return r; }
__device__ __forceinline__ uint32_t movm(uint32_t a) { uint32_t d; asm volatile("movmatrix.sync.aligned.m8n8.trans.b16 %0, %1;" : "=r"(d) : "r"(a)); return d; }
__device__ __forceinline__ uint32_t hadd2(uint32_t a, uint32_t b) { uint32_t d; asm("add.rn.bf16x2 %0, %1, %2;" : "=r"(d) : "r"(a), "r"(b)); return d; }
__device__ __forceinline__ void mma_a(float (&d)[4], const uint32_t (&a)[4], uint32_t b0, uint32_t b1) { mma16816(d, a[0], a[1], a[2], a[3], b0, b1); }
__device__ __forceinline__ bool elect() {
  uint32_t p; asm volatile("{.reg .pred p; elect.sync _|p, 0xffffffff; selp.u32 %0, 1, 0, p;}" : "=r"(p)); return p; }
__device__ __forceinline__ void tma3d(uint32_t dst, const CUtensorMap* m, int c1, int c2, uint32_t bar) {
  asm volatile("cp.async.bulk.tensor.3d.shared::cluster.global.mbarrier::complete_tx::bytes [%0], [%1, {0, %3, %4}], [%2];"
    :: "r"(dst), "l"(m), "r"(bar), "r"(c1), "r"(c2) : "memory"); }
__device__ __forceinline__ void tma4d(uint32_t dst, const CUtensorMap* m, int c1, int c2, uint32_t bar) {
  asm volatile("cp.async.bulk.tensor.4d.shared::cluster.global.mbarrier::complete_tx::bytes [%0], [%1, {0, %3, %4, 0}], [%2];"
    :: "r"(dst), "l"(m), "r"(bar), "r"(c1), "r"(c2) : "memory"); }
template <int OFF, int ACC>
__device__ __forceinline__ void wg_rs32(float (&d)[16], const uint32_t (&a)[4], uint32_t db) {
  if (ACC)
    asm volatile("{.reg .b64 db; .reg .b32 lo; add.u32 lo, %20, %21; mov.b64 db, {lo, 0x40000040};\n"
      "wgmma.mma_async.sync.aligned.m64n32k16.f32.bf16.bf16 {%0,%1,%2,%3,%4,%5,%6,%7,%8,%9,%10,%11,%12,%13,%14,%15}, {%16,%17,%18,%19}, db, 1, 1, 1, 0;}"
      : "+f"(d[0]), "+f"(d[1]), "+f"(d[2]), "+f"(d[3]), "+f"(d[4]), "+f"(d[5]), "+f"(d[6]), "+f"(d[7]), "+f"(d[8]), "+f"(d[9]), "+f"(d[10]), "+f"(d[11]), "+f"(d[12]), "+f"(d[13]), "+f"(d[14]), "+f"(d[15])
      : "r"(a[0]), "r"(a[1]), "r"(a[2]), "r"(a[3]), "r"(db), "n"(OFF));
  else
    asm volatile("{.reg .b64 db; .reg .b32 lo; add.u32 lo, %20, %21; mov.b64 db, {lo, 0x40000040};\n"
      "wgmma.mma_async.sync.aligned.m64n32k16.f32.bf16.bf16 {%0,%1,%2,%3,%4,%5,%6,%7,%8,%9,%10,%11,%12,%13,%14,%15}, {%16,%17,%18,%19}, db, 0, 1, 1, 0;}"
      : "=f"(d[0]), "=f"(d[1]), "=f"(d[2]), "=f"(d[3]), "=f"(d[4]), "=f"(d[5]), "=f"(d[6]), "=f"(d[7]), "=f"(d[8]), "=f"(d[9]), "=f"(d[10]), "=f"(d[11]), "=f"(d[12]), "=f"(d[13]), "=f"(d[14]), "=f"(d[15])
      : "r"(a[0]), "r"(a[1]), "r"(a[2]), "r"(a[3]), "r"(db), "n"(OFF));
}
template <int I> using IC = std::integral_constant<int, I>;
template <int I, int N, class F> __device__ __forceinline__ void sfor(F&& f) {
  if constexpr (I < N) { f(std::integral_constant<int, I>{}); sfor<I + 1, N>(f); }
}
__device__ __forceinline__ void keep(float (&d)[16]) {
  asm volatile("" : "+f"(d[0]), "+f"(d[1]), "+f"(d[2]), "+f"(d[3]), "+f"(d[4]), "+f"(d[5]), "+f"(d[6]), "+f"(d[7]),
      "+f"(d[8]), "+f"(d[9]), "+f"(d[10]), "+f"(d[11]), "+f"(d[12]), "+f"(d[13]), "+f"(d[14]), "+f"(d[15]) :: "memory");
}

template <int N, int S2 = 1024> __device__ __forceinline__ void ldx(uint32_t (&v)[N][4], const uint8_t* p) {
#pragma unroll
  for (int k = 0; k < 2 * N; k++) {
    const int i = k;
    asm volatile("ld.relaxed.gpu.global.v2.b32 {%0,%1}, [%2];" : "=r"(v[i >> 1][2 * (i & 1)]), "=r"(v[i >> 1][2 * (i & 1) + 1]) : "l"(p + (i & 3) * 256 + (i >> 2) * S2) : "memory");
  }
}
__device__ __forceinline__ uint32_t dif2(uint32_t a, uint32_t b, uint32_t tag) { uint32_t r; asm("lop3.b32 %0, %1, %2, %3, 0x7e;" : "=r"(r) : "r"(a), "r"(b), "r"(tag)); return r; }
__device__ __forceinline__ uint32_t dif2v(uint32_t a, uint32_t b, uint32_t tag) { uint32_t r; asm volatile("lop3.b32 %0, %1, %2, %3, 0x7e;" : "=r"(r) : "r"(a), "r"(b), "r"(tag)); return r; }
__device__ __forceinline__ uint32_t or3(uint32_t a, uint32_t b, uint32_t c) { uint32_t r; asm("lop3.b32 %0, %1, %2, %3, 0xfe;" : "=r"(r) : "r"(a), "r"(b), "r"(c)); return r; }
__device__ __forceinline__ uint32_t after(uint32_t x, float f, uint32_t z) { uint32_t r; asm("lop3.b32 %0, %1, %2, %3, 0xea;" : "=r"(r) : "r"(__float_as_uint(f)), "r"(z), "r"(x)); return r; }
__device__ __forceinline__ bool any_bit(uint32_t a, uint32_t b, uint32_t m) {
  uint32_t r; asm("lop3.b32 %0, %1, %2, %3, 0xa8;" : "=r"(r) : "r"(a), "r"(b), "r"(m)); return __any_sync(0xffffffffu, r); }
template <int W, int N> __device__ __forceinline__ bool stale(const uint32_t (&v)[N][4], uint32_t tag) {
  uint32_t x = dif2(v[0][0], v[0][2], tag);
  if (N == 4) x = or3(x, dif2(v[1][0], v[1][2], tag), dif2(v[2 % N][0], v[2 % N][2], tag));
  return any_bit(x, dif2(v[N - 1][0], v[N - 1][2], tag), 1);
}
template <int W, int N, int S2 = 1024> __device__ __forceinline__ void retry(uint32_t (&v)[N][4], const uint8_t* p, uint32_t tag, int& it) {
#pragma unroll 1
  do { ldx<N, S2>(v, p); it += INC_A; } while (stale<W>(v, tag) && it < SPIN_LIMIT);
}
__device__ __forceinline__ void mma_h(float (&d)[4], const uint32_t (&a)[4], const uint32_t (&b)[4], int hf) { mma16816(d, a[0], a[1], a[2], a[3], b[2 * hf], b[2 * hf + 1]); }
__device__ __forceinline__ void sts128(uint32_t a, const uint32_t (&r)[4]) { sts128(a, r[0], r[1], r[2], r[3]); }
__device__ __forceinline__ void sts128f(uint32_t a, const float* r) { sts128(a, __float_as_uint(r[0]), __float_as_uint(r[1]), __float_as_uint(r[2]), __float_as_uint(r[3])); }
__device__ __forceinline__ void mbar_spin(uint32_t bar, uint32_t par, int& it) {
  asm volatile("{.reg .pred p; .reg .b32 par; mov.b32 par, %2;\nLOOP: mbarrier.try_wait.parity.shared::cta.b64 p, [%1], par; @p bra.uni DONE;\n"
               "add.s32 %0, %0, 1; setp.le.s32 p, %0, %3; @p bra.uni LOOP;\nDONE: }" : "+r"(it) : "r"(bar), "r"(par), "n"(SPIN_LIMIT) : "memory"); }
__device__ __forceinline__ void warp_arrive(uint32_t bar) {
  __syncwarp(); asm volatile("{.reg .pred p; elect.sync _|p, 0xffffffff; @p mbarrier.arrive.shared::cta.b64 _, [%0];}" :: "r"(bar) : "memory"); }
__device__ __forceinline__ void delay_until(unsigned t) {
  asm volatile("{.reg .pred p; .reg .b64 c; .reg .b32 lo, hi;\nLOOP: mov.u64 c, %%clock64; mov.b64 {lo, hi}, c; sub.s32 lo, lo, %0; setp.lt.s32 p, lo, 0; @p bra.uni LOOP;}" :: "r"(t) : "memory"); }
__device__ __forceinline__ void cut(int it) { asm volatile("{.reg .pred p; setp.lt.s32 p, %0, 0;\nL: @p st.volatile.shared.u32 [%0], %0; @p bra.uni L;}" :: "r"(it) : "memory"); }
__device__ __forceinline__ void zero(float (&c)[4][4]) {
#pragma unroll
  for (int i = 0; i < 4; i++) c[i][0] = c[i][1] = c[i][2] = c[i][3] = 0.f;
}

__device__ __forceinline__ void sched() { asm volatile("griddepcontrol.launch_dependents;" ::: "memory"); }
__device__ __forceinline__ const uint8_t* pinp(const uint8_t* p) { return reinterpret_cast<const uint8_t*>(__shfl_xor_sync(0xffffffffu, reinterpret_cast<unsigned long long>(p), 0)); }
__device__ __forceinline__ uint32_t bar_or(int id, uint32_t x) {
  uint32_t r; asm volatile("{.reg .pred p, q; setp.ne.u32 p, %2, 0; bar.red.or.pred q, %1, 256, p; selp.u32 %0, 1, 0, q;}" : "=r"(r) : "r"(id), "r"(x) : "memory"); return r; }
__device__ __forceinline__ void bar_sync_unless(int id, uint32_t x) { asm volatile("{.reg .pred p; setp.eq.u32 p, %1, 0; @p bar.sync %0, 256;}" :: "r"(id), "r"((uint32_t)x) : "memory"); }
__device__ __forceinline__ void bar_arrive_unless(int id, uint32_t x) { asm volatile("{.reg .pred p; setp.eq.u32 p, %1, 0; @p bar.arrive %0, 256;}" :: "r"(id), "r"((uint32_t)x) : "memory"); }
__device__ __forceinline__ void stsm2t(uint32_t a, uint32_t r0, uint32_t r1, uint32_t x) {
  asm volatile("{.reg .pred p; setp.eq.u32 p, %3, 0; @p stmatrix.sync.aligned.m8n8.x2.trans.shared.b16 [%0], {%1,%2};}" :: "r"(a), "r"(r0), "r"(r1), "r"((uint32_t)x) : "memory"); }
__device__ __forceinline__ uint32_t or_and(uint32_t a, uint32_t b, uint32_t m) { uint32_t r; asm("lop3.b32 %0, %1, %2, %3, 0xa8;" : "=r"(r) : "r"(a), "r"(b), "r"(m)); return r; }
#define rare(x) __builtin_expect(!!(x), 0)
__device__ __forceinline__ uint32_t gtime() { unsigned long long g; asm volatile("mov.u64 %0, %%globaltimer;" : "=l"(g) :: "memory"); return (uint32_t)g; }
__device__ __forceinline__ void wait_time(uint32_t t) {
  asm volatile("{.reg .pred p; .reg .b32 g; .reg .b64 c;\nLOOP: mov.u64 c, %%globaltimer; cvt.u32.u64 g, c; sub.s32 g, %0, g; setp.lt.u32 p, g, 16384; @p bra.uni LOOP;}" :: "r"(t - 1) : "memory"); }
__device__ __forceinline__ uint32_t ldx32(const void* p) { uint32_t v; asm volatile("ld.relaxed.gpu.global.b32 %0, [%1];" : "=r"(v) : "l"(p) : "memory"); return v; }
__device__ __forceinline__ void stx32(const void* p, uint32_t v) { asm volatile("st.relaxed.gpu.global.b32 [%0], %1;" :: "l"(p), "r"(v) : "memory"); }

__global__ void __launch_bounds__(256, 1)
rec_kernel(const __grid_constant__ RecMaps maps, const bf16* __restrict__ xin, const bf16* __restrict__ mem0, Xchg* const gx,
           const bf16* __restrict__ fx, const bf16* __restrict__ wr, const bf16* __restrict__ wi) {
  extern __shared__ __align__(1024) uint8_t smem_raw[];
  const uint32_t sb = smem_u32(smem_raw);
  int role = blockIdx.x;
  {
    uint32_t smid, nsm; asm volatile("mov.u32 %0, %%smid;" : "=r"(smid)); asm volatile("mov.u32 %0, %%nsmid;" : "=r"(nsm));
    const int p = smid >> 1, u = p - 32;
    if (nsm == gridDim.x)
      role = (smid & 1) + (p < 32 ? 4 * ((p & 7) + 8 * (p >> 4)) + 2 * ((p >> 3) & 1) : p < 60 ? 4 * (16 + u % 7 + 7 * (u / 14)) + 2 * ((u / 7) & 1)
                         : p < 62 ? 2 * p + 8 : 2 * p - 4);
    role = uni(role);
  }
  if (role >= 128) {
    fft_cols(sb, role - 128, 4, [&]() { grid_wait(&gx->ctr[33], 128); });
    __threadfence(); __syncwarp();
    if ((threadIdx.x & 31) == 0) atomicAdd(&gx->ctr[32], 1u);
    __syncwarp();
    fft_rows_inv(&maps.fo, sb, role - 128, 4, [&]() { grid_wait(&gx->ctr[32], 32); });
    return;
  }
  const int tid = threadIdx.x, warp = uni(tid >> 5), lane = tid & 31, wg = warp >> 2, w4 = warp & 3, g = lane >> 2, t = lane & 3;
  const int h = role >> 2, j = role & 3, jh = j & 1;
  uint32_t w[48][4];
  float aq[16], av[16];
  int it = 0;

#define PT(k)
  auto pf_wo = [&]() {
    for (int i = 0; i < 4; i++)
      asm volatile("cp.async.bulk.prefetch.tensor.2d.L2.global [%0, {%1, %2}];" :: "l"(&maps.wo), "r"(256 * j + 64 * i), "r"(h * DH) : "memory");
  };
  fft_rows_fwd(fx, wr, wi, sb + R_MEM + 49152, role, [&]() {
    if (tid == 224) {
      mbar_init(sb + B_KV, 1); mbar_init(sb + B_W, 1); mbar_init(sb + B_X, 1); mbar_init(sb + B_X + 8, 1); mbar_init(sb + B_X + 16, 1); mbar_init(sb + B_X + 24, 1); mbar_init(sb + B_C, 4); mbar_init(sb + B_PK, 4); mbar_init(sb + B_B, 1);
      asm volatile("fence.mbarrier_init.release.cluster;" ::: "memory");
      mbar_expect_tx(sb + B_W, 3 * 65536);
      for (int i = 0; i < 4; i++) {
        tma2d(sb + R_X + i * 16384, &maps.wq, h * DH + 32 * j, i * 256, sb + B_W);
        if (i < 3) tma2d(sb + R_MEM + i * 16384, &maps.wk, h * DH + 32 * j, i * 256, sb + B_W);
        else asm volatile("cp.async.bulk.prefetch.tensor.2d.L2.global [%0, {%1, %2}];" :: "l"(&maps.wk), "r"(h * DH + 32 * j), "r"(768) : "memory");
      }
      for (int i = 0; i < 2; i++) tma2d(sb + R_WO + i * 32768, &maps.wv, h * DH + 64 * (j >> 1), jh * 512 + i * 256, sb + B_W);
      if (PFD) asm volatile("cp.async.bulk.prefetch.L2.global [%0], 2048;" :: "l"(xin + role * DM) : "memory");
      else for (int i = 0; i < 4; i++) asm volatile("cp.async.bulk.prefetch.L2.global [%0], 8192;" :: "l"(xin + role * 16384 + i * 4096) : "memory");
      if (WOP == 0) pf_wo();
      for (int i = 0; i < 5; i++) asm volatile("prefetch.tensormap [%0];" :: "l"(&maps.wo + i) : "memory");
    }
    __syncwarp();
  });
  if (tid < 16) sts32(sb + R_T + tid * 4, ~0u);
  fence_async();
  PT(0);
  grid_arrive(&gx->ctr[33]);
  PT(1);
  if (tid == 224) { tma2d(sb + R_MEM + 49152, &maps.wk, h * DH + 32 * j, 768, sb + B_W); if (WOP == 1) pf_wo(); }
  __syncwarp();
  uint8_t* const xb = reinterpret_cast<uint8_t*>(gx);
  auto probe_at = [&](int n) { return xb + (n ? offsetof(Xchg, C) + w4 * 8192 + role * 32 : offsetof(Xchg, B) + role * 8192 + warp * 128); };
  if (lane < 8) stx128(probe_at(lane >> 2) + (lane & 2) * 2048 + (lane & 1) * 16, 0, 0, 0, 0);
  uint32_t m0[4][4];
#pragma unroll
  for (int i = 0; i < 16; i++) m0[i >> 2][i & 3] = ldnc32(mem0 + g * DM + 128 * warp + 8 * i + 2 * t);
  mbar_spin(sb + B_W, 0, it);
  PT(2);
  const int lrow = (lane & 7) + ((lane >> 4) << 3), lhi = (lane >> 3) & 1;
  const int kq = wg ? 3 - 3 * jh : 3 * jh;
  const uint32_t LW = lrow * 128 + ((lhi ^ (lane & 7)) << 4);
  {
    const int chunk = w4 < 2 ? w4 + 2 * lhi : 2 * (w4 & 1) + lhi;
    uint32_t a = sb + (w4 < 2 ? R_X : R_MEM) + kq * 16384 + lrow * 64 + ((chunk ^ ((lrow >> 1) & 3)) << 4);
#pragma unroll
    for (int i = 0; i < 16; i++) ldsm4t(w[i], a + i * 1024);
    const uint32_t st = wg ? 1024 : 2048, av0 = sb + R_WO + (LW ^ (w4 << 5));
    const uint32_t a1 = wg ? a + (2 * jh - 1) * 16384 : av0 + jh * 32768, a2 = wg ? a + (2 * jh - 1) * 32768 : av0 + (1 - jh) * 32768;
#pragma unroll
    for (int i = 0; i < 16; i++) { ldsm4t(w[16 + i], a1 + i * st); ldsm4t(w[32 + i], a2 + i * st); }
  }
  uint32_t L16 = pin(lane * 16);
  const uint32_t uW = uni(sb + w4 * 512), uWo = uni(sb + R_WO + w4 * 16384), uMem = uni(sb + R_MEM + kq * 4096);
  const uint32_t dX = uni(((sb + R_X + kq * 16384) >> 4) | 0x10000u);
  auto load_wo = [&](uint32_t (&d)[32][4], int i0, int i1) {
#pragma unroll
    for (int i = i0; i < i1; i++) lds128(d[i], uWo + L16 + (i & 1) * 512 + (i >> 4) * 1024 + (i & 14) * 1024);
  };
  auto issue_x = [&](int n, int k) {
    const uint32_t bar = sb + B_X + 8 * k, q = k ^ (3 - 3 * jh);
    mbar_expect_tx(bar, 16384); tma3d(sb + R_X + q * 16384, &maps.x, min(n, NSEG - 1) * SEG, 4 * q, bar);
  };
  auto store_stage = [&](int n) {
    asm volatile("cp.async.bulk.global.shared::cta.bulk_group [%0], [%1], 8192; cp.async.bulk.commit_group;"
                 :: "l"(g_kqv[n & 3][role]), "r"(sb + R_STAGE) : "memory");
  };
  auto issue_kqv = [&](int n) {
    const int p = (n & 3) * 128 + 4 * h;
    mbar_expect_tx(sb + B_KV, 26624);
    tma3d(sb + R_K, &maps.k, 0, p, sb + B_KV); tma3d(sb + R_Q, &maps.q, 8 + 2 * j, p, sb + B_KV); tma3d(sb + R_V, &maps.v, 16, p, sb + B_KV);
  };
  auto fetch4k = [&](uint32_t dst, uint32_t off, uint32_t bar, uint32_t t) {
    asm volatile("{.reg .pred p, q; .reg .b32 g; .reg .b64 c; elect.sync _|q, 0xffffffff; @q mbarrier.arrive.expect_tx.shared::cta.b64 _, [%2], 4096;\n"
                 "LOOP: mov.u64 c, %%globaltimer; cvt.u32.u64 g, c; sub.s32 g, %3, g; setp.lt.u32 p, g, 16384; @p bra.uni LOOP;\n"
                 "@q cp.async.bulk.shared::cluster.global.mbarrier::complete_tx::bytes [%0], [%1], 4096, [%2];}" :: "r"(dst), "l"(xb + off), "r"(bar), "r"(t - 1) : "memory");
  };
  uint32_t uS;
  auto my_b = [&]() { return offsetof(Xchg, B) + role * 8192 + ((uS + ((uint32_t)it >> 31)) & 1) * 4096; };
  auto issue_c = [&](uint32_t t) { fetch4k(sb + R_MEM + w4 * 4096, offsetof(Xchg, C) + w4 * 8192 + ((uS + ((uint32_t)it >> 31)) & 4096), sb + B_C, t); };
  auto wait_x = [&](int n, int i) { if (!(EXP & 1) || n < 2) mbar_spin(sb + B_X + 8 * i, n & 1, it); };
#define PACED(d0) uint32_t dz = d0; const uint32_t z = (uint32_t)it >> 31; auto pace = [&]() { for (int k = 0; k < PACE; k++) { if (k & 1) asm("add.u32 %0, %0, %1;" : "+r"(dz) : "r"(z)); else asm("xor.b32 %0, %0, %1;" : "+r"(dz) : "r"(z)); } };
  auto project_v = [&](auto I0, auto I1, auto&& mid) {
    PACED(decltype(I0)::value < 16 ? dX : dX ^ 1024);
    wg_fence();
    sfor<decltype(I0)::value, decltype(I1)::value>([&](auto I) {
      constexpr int i = decltype(I)::value;
      mid(i);
      if (i == 16 && decltype(I0)::value < 16) dz ^= 1024;
      wg_rs32<((i >> 2) & 3) * 256 + (i & 3) * 2, (i > 0)>(av, w[16 + i], dz);
      pace();
    });
    wg_commit();
  };
  auto project_qk = [&](auto I0, auto I1, auto first, auto&& mid) {
    PACED((dX ^ (decltype(I0)::value >> 4 << 10)) + ((uint32_t)it >> 31));
    wg_fence();
    sfor<decltype(I0)::value, decltype(I1)::value>([&](auto I) {
      constexpr int i = decltype(I)::value;
      mid(i);
      wg_rs32<((i >> 2) & 3) * 256 + (i & 3) * 2, !decltype(first)::value || i != decltype(I0)::value>(aq, w[i], dz);
      pace();
    });
    wg_commit();
  };
  const uint32_t uP = uni(sb + R_X + 3 * jh * 16384 + w4 * 512);
  auto park = [&]() {
    bar_sync(1, 128);
#pragma unroll
    for (int i = 0; i < 4; i++) sts128f(uP + L16 + i * 2048, aq + 4 * i);
    warp_arrive(sb + B_PK);
  };
  auto unpark = [&]() {
#pragma unroll
    for (int i = 0; i < 4; i++) {
      const float4 p = lds128f(uP + L16 + i * 2048);
      av[4 * i] = p.x; av[4 * i + 1] = p.y; av[4 * i + 2] = p.z; av[4 * i + 3] = p.w;
    }
  };
  auto fin_qk = [&]() {
#pragma unroll
    for (int i = 0; i < 16; i++) aq[i] += av[i];
    const uint32_t a = sb + R_STAGE + (w4 < 2 ? 2048 + w4 * 128 : (w4 & 1) * 256) + (L16 & 112) + (L16 >> 7) * 512;
    stsm4t(a, pack2(aq[0], aq[1]), pack2(aq[4], aq[5]), pack2(aq[8], aq[9]), pack2(aq[12], aq[13]));
    stsm4t(a + (w4 < 2 ? 256 : 128), pack2(aq[2], aq[3]), pack2(aq[6], aq[7]), pack2(aq[10], aq[11]), pack2(aq[14], aq[15]));
  };
  auto fin_v = [&]() {
#pragma unroll
    for (int a = 0; a < 2; a++)
      sts128(sb + R_STAGE + 4096 + w4 * 1024 + a * 512 + L16, pack2(av[8 * a], av[8 * a + 1]), pack2(av[8 * a + 2], av[8 * a + 3]),
             pack2(av[8 * a + 4], av[8 * a + 5]), pack2(av[8 * a + 6], av[8 * a + 7]));
  };
  __syncthreads();
  if (tid == 224) {
#pragma unroll 1
    for (int i = 0; i < 4; i++) issue_x(0, i);
    mbar_expect_tx(sb + B_W, 65536);
    for (int i = 0; i < 4; i++) tma2d(sb + R_WO + i * 16384, &maps.wo, 256 * j + 64 * i, h * DH, sb + B_W);
  }
  __syncwarp();
  if (wg) {
#pragma unroll
    for (int i = 0; i < NSW; i++) sts128(uW + R_WC + L16 + i * 2048, w[i]);
  }
#pragma unroll
  for (int i = 0; i < 4; i++) sts128(sb + R_MEM + warp * 2048 + i * 512 + (g >> 1) * 128 + t * 32 + (g & 1) * 16, m0[i]);
  auto probe = [&](int n, int cnt) {
    if (lane == 0) {
#pragma unroll 1
      for (int i = role >> 7; i < cnt; i++) {
        const int k = (i ^ wg) & 1;
        const unsigned t0 = clk();
        uint32_t v; asm volatile("atom.relaxed.gpu.global.exch.b32 %0, [%1], 0;" : "=r"(v) : "l"(probe_at(n) + k * 4096) : "memory");
        if (v == 0) asm volatile("red.shared.min.u32 [%0], %1;" :: "r"(sb + R_T + (n ? w4 * 8 : 32) + k * 4), "r"(clk() - t0) : "memory");
      }
    }
    __syncwarp();
  };
#pragma unroll 1
  for (int n = 0; n < 2; n++) {
    probe(0, n ? NPB : NPB0);
    asm volatile("{.reg .pred p; cp.async.bulk.wait_group 0; setp.eq.u32 p, %1, 97; @p red.relaxed.gpu.global.add.u32 [%0], 1;}" :: "l"(&gx->ctr[h]), "r"(tid ^ n ^ (1 - n) << 9) : "memory");
    PT(3 + 3 * n);
    wait_x(n, 2);
    PT(4 + 3 * n);
    if (wg == 0) {
      wait_x(n, 3);
      project_qk(IC<0>{}, IC<16>{}, IC<1>{}, [](int) {});
      project_v(IC<0>{}, IC<32>{}, [](int) {});
      wg_wait<0>(); keep(aq); keep(av);
      park();
      fin_v();
      fence_async();
    } else {
      wait_x(n, 0); wait_x(n, 1);
      project_qk(IC<32>{}, IC<48>{}, IC<1>{}, [](int) {});
      project_qk(IC<16>{}, IC<32>{}, IC<0>{}, [](int) {});
      project_qk(IC<0>{}, IC<16>{}, IC<0>{}, [](int) {});
      mbar_spin(sb + B_PK, n, it);
      unpark();
      wg_wait<0>(); keep(aq);
      fin_qk();
      fence_async();
    }
    __syncthreads();
    if (tid == 0 && n) stx32(&gx->S[role], 1 + (HOME & 2 && lds32(sb + R_T + 36) < lds32(sb + R_T + 32)));
    PT(5 + 3 * n);
    if (tid == 96 && n == 0) store_stage(0);
    if (tid == 128 && n == 0) {
#pragma unroll 1
      for (int i = 0; i < 4; i++) issue_x(1, i);
    }
    if (warp == 5 && n == 1) {
#pragma unroll 1
      while (__any_sync(0xffffffffu, ldx32(&gx->ctr[h]) < 4) && ++it < SPIN_LIMIT) {}
      if (elect()) issue_kqv(0);
    }
    __syncwarp();
  }
  mbar_spin(sb + B_W, 1, it);
  PT(9);
#pragma unroll
  for (int i = 0; i < 4; i++) {
    uint32_t f[4][4];
    const uint32_t a = sb + R_WO + warp * 8192 + i * 2048;
#pragma unroll
    for (int q = 0; q < 4; q++) ldsm4t(f[q], a + (LW ^ (q << 5)));
    __syncwarp();
#pragma unroll
    for (int q = 0; q < 4; q++) sts128(a + q * 512 + L16, f[q]);
  }
  if (NPC) probe(1, NPC);
  {
    const int o = 32 * w4 + 16 * wg + 4 * t + j;
    uint32_t v;
#pragma unroll 1
    while (__any_sync(0xffffffffu, (v = ldx32(&gx->S[o])) == 0) && ++it < SPIN_LIMIT) {}
    asm volatile("st.shared.u64 [%0], %1;" :: "r"(sb + R_DST + wg * 1024 + w4 * 256 + lane * 8), "l"(xb + offsetof(Xchg, B) + o * 8192 + (v >> 1) * 4096 + h * 128 + ((g ^ h) & 7) * 16) : "memory");
  }
  if (wg == 0) {
    const uint64_t cd = reinterpret_cast<uint64_t>(xb + (offsetof(Xchg, C) + j * 8192 + h * 128 + w4 * 32 + (L16 & 16) * 256 + (L16 & 64) / 4 + (L16 >> 7) * 4));
    sts128(uW + R_RD + L16, (uint32_t)cd, (uint32_t)(cd >> 32), sb + R_MEM + (L16 & 112) * 8 + (L16 >> 8) * 1024 + ((w4 * 32 + ((L16 >> 3) & 16)) ^ (L16 & 112)),
           (L16 >> 6) == (h & 3) * 2 + ((h >> 2) & 1) ? 0xFFFE0000u : 0xFFFFFFFFu);
  }
  if (tid == 0) sts32(sb + B_DUE + 8, gtime() & ~31u);
  PT(10);
  mbar_spin(sb + B_KV, 0, it);
  PT(11);
  if (tid < 4) sts32(sb + B_ONE + tid * 4, 0x3F803F80u);
  if (warp == 1) { const uint32_t e = g >> 1 == t ? 0x3F80u << (16 * (g & 1)) : 0u; sts128(sb + R_ID + L16, e, 0, 0, e); }
  __syncthreads();
  {
    const uint32_t kb = lds32(sb + R_T + 36) < lds32(sb + R_T + 32);
    uS = uni((HOME & 4 ? (__popc(((offsetof(Xchg, B) / 4096 + 2 * role) ^ (offsetof(Xchg, C) / 4096 + 2 * w4)) & 0xb3) ^ kb) & 1 : lds32(sb + R_T + w4 * 8 + 4) < lds32(sb + R_T + w4 * 8)) * 4096 + kb);
  }

  const float sc = 0.08838834764831845f * 1.4426950408889634f;
  uint8_t* const xa = xb + uni(h * 16384);
  const uint32_t uA = uni(wg ? (w4 >> 1) * 2048 + j * 512 + (w4 & 1) * 256 : 8192 + (4 * (j >> 1) + w4) * 512 + jh * 256);
  const uint32_t uP2 = uni(sb + R_P + w4 * 256);
  uint32_t nc = 1;
  uint32_t ma;
  const uint8_t* adst;
  auto pin_mem = [&]() { adst = pinp(xa + uA + L16 / 2); ma = pin(uMem + (L16 & 384) + (L16 & 48) * 2 + (L16 & 64) / 4); };
  pin_mem();

#pragma unroll 1
  for (int s = 0;; nc++) {
    const uint32_t tag = (s + 1) & 1;
    auto fresh = [&]() { L16 += (uint32_t)it >> 31; };
    auto get_due = [&]() { return lds32(sb + B_DUE + 4 + tag * 4); };
    float c[4][4], r4[4];
    auto fold = [&]() {
#pragma unroll
      for (int i = 0; i < 4; i++) r4[i] = ((c[0][i] + c[1][i]) + c[2][i]) + c[3][i];
    };
    auto mma4 = [&](int n, const uint32_t (&b0)[4], const uint32_t (&b1)[4]) {
      mma_h(c[0], w[n + 2], b1, 0); mma_h(c[1], w[n + 3], b1, 1); mma_h(c[2], w[n], b0, 0); mma_h(c[3], w[n + 1], b0, 1);
    };
    auto xpos = [&](int pos, int wp) {
      if ((pos == X0 || pos == X1 || pos == X2 || pos == X3) && warp == wp && s + 1 < NSEG && elect()) {
        const int z = (uint32_t)it >> 31;
        if (pos == X2) issue_x(s + 2, 2 + z);
        if (pos == X3) issue_x(s + 2, 3 + z);
        if (pos == X1) issue_x(s + 2, 1 + z);
        if (pos == X0) issue_x(s + 2, z);
      }
      __syncwarp();
    };
    if (wg == 0) {
      mbar_spin(sb + B_C, nc & 1, it);
      TS(13);
      uint32_t b[16][4], tg[4];
#pragma unroll
      for (int i = 0; i < PD0; i++) { lds128(b[i], ma + i * 512); __syncwarp(); }
      sched();
      zero(c);
#pragma unroll
      for (int i = 0; i < 8; i++) {
        const int k = i ^ 1;
        mma_h(c[0], w[2 * k], b[k], 0); mma_h(c[1], w[2 * k + 1], b[k], 1);
        if (i < 2 * NV0) { mma_h(c[2], w[16 + 2 * k], b[k], 0); mma_h(c[3], w[17 + 2 * k], b[k], 1); }
        sched();
        if ((i & 1) && i + PD0 < 9) { lds128(b[i + PD0 - 1], ma + (i + PD0 - 1) * 512); __syncwarp(); lds128(b[i + PD0], ma + (i + PD0) * 512); sched(); }
        if (i == TGP) {
          fresh();
#pragma unroll
          for (int k = 0; k < 4; k++) tg[k] = lds32((uW * 4 + L16) * 2 + (L16 >> 6) * 4 + (R_MEM + k * 1024 - 7 * sb));
          sched();
        }
      }
#pragma unroll
      for (int i = 0; i < 4; i++) { r4[i] = c[0][i] + c[1][i]; c[0][i] = c[1][i] = 0.f; }
      sts128f(uW + R_RED + L16, r4);
      TS(1);
      const uint32_t old = bar_or(4, (dif2(tg[0], tg[1], s) | dif2(tg[2], tg[3], s)) & (s > 0));
      TS(0);
#pragma unroll
      for (int i = 0; i < 2 * NV0; i++) { lds128(b[8 + i], (ma ^ 4096) + i * 512); __syncwarp(); }
      sched();
#pragma unroll
      for (int i = NV0; i < 8; i++) {
        if (VB && i == VB) bar_sync(7, 256);
        mma4(16 + 4 * i, b[2 * i], b[2 * i + 1]);
        if (i < 7) sched();
        if (i < 4) { lds128(b[8 + 2 * i], (ma ^ 4096) + i * 1024); __syncwarp(); lds128(b[9 + 2 * i], (ma ^ 4096) + i * 1024 + 512); sched(); }
      }
      fold();
      asm volatile("{.reg .pred p; setp.eq.u32 p, %3, 0; @p st.relaxed.gpu.global.v2.b32 [%0], {%1,%2};}" :: "l"(adst), "r"((pack2(r4[0], r4[1]) & ~1u) | tag), "r"(pack2(r4[2], r4[3])), "r"(old) : "memory");
      sched();
      const unsigned tpub = clk();
      if (__any_sync(0xffffffffu, old) && nc < NC_MAX) {
        bar_sync(3, 256);
        issue_c(gtime());
        continue;
      }
      TS(3);
      xpos(0, 0);
      const uint32_t due = get_due();
      uint32_t vf[4][4], vm[2][4], p[4], pm, o[4];
      const uint32_t va = sb + R_V + (w4 >> 1) * 8192 + (w4 & 1) * 2048 + L16;
#pragma unroll
      for (int i = 0; i < 4; i++) {
        uint32_t q[4]; lds128(vf[i], va + i * 512); lds128(q, va + 4096 + i * 512);
#pragma unroll
        for (int e = 0; e < 4; e++) vf[i][e] = hadd2(vf[i][e], q[e]);
      }
      const uint32_t pa = pin(sb + R_P + (L16 >> 1));
      const uint8_t* vsrc = pinp(xa + 8192 + w4 * 1024 + L16 / 2);
      uint32_t one[4];
      lds128(one, sb + B_ONE);
      auto pv_x = [&]() {
        zero(c);
        mma_a(c[2], one, p[0], p[1]);
        mma_a(c[0], vf[0], p[0], p[1]); mma_a(c[1], vf[2], p[0], p[1]);
        sched();
        mma_a(c[2], one, p[2], p[3]);
        mma_a(c[0], vf[1], p[2], p[3]); mma_a(c[1], vf[3], p[2], p[3]);
        sched();
      };
      auto pv_m = [&]() {
        mma1688(c[2], one[0], one[1], pm);
        mma_a(c[0], vm[0], pm, pm);
        sched();
        mma_a(c[1], vm[1], pm, pm);
      };
      auto norm = [&]() {
        const float n0 = rcp(c[2][0]), n1 = rcp(c[2][1]);
#pragma unroll
        for (int i = 0; i < 4; i++) o[i] = pack2(c[i >> 1][2 * (i & 1)] * n0, c[i >> 1][2 * (i & 1) + 1] * n1);
        return ((__float_as_uint(c[2][0]) - 0x1F800000u) | (__float_as_uint(c[2][1]) - 0x1F800000u)) >> 30;
      };
      auto load_m = [&](int x) { const float2 e0 = lds64f(pa + 512 + x * 1024), e1 = lds64f(pa + 768 + x * 1024); pm = pack2(e0.x * e1.x, e0.y * e1.y); };
      auto attend_max = [&](int x) {
        float2 sv[6];
#pragma unroll
        for (int i = 0; i < 6; i++) sv[i] = lds64f(pa - 3072 + x * 1536 + i * 256);
        sv[4].x += sv[5].x; sv[4].y += sv[5].y;
        const int dq = (int)(L16 >> 6) - (int)((L16 >> 3) & 6) + 8 * j;
        float m = fmaxf(sv[4].x, sv[4].y);
#pragma unroll
        for (int i = 0; i < 4; i++) {
          if (x && 8 * i > dq) sv[i].x = -INFINITY;
          if (x && 8 * i + 1 > dq) sv[i].y = -INFINITY;
          m = fmaxf(m, fmaxf(sv[i].x, sv[i].y));
        }
        m = fmaxf(m, __shfl_xor_sync(0xffffffffu, m, 1));
        m = fmaxf(m, __shfl_xor_sync(0xffffffffu, m, 2));
#pragma unroll
        for (int i = 0; i < 5; i++) (i < 4 ? p[i] : pm) = pack2(ex2(sv[i].x - m), ex2(sv[i].y - m));
        pv_x(); pv_m(); norm();
      };
      uint32_t tq[4];
      auto get_t = [&]() {
        tq[0] = tq[1] = tq[2] = tq[3] = 0;
        asm volatile("{.reg .pred p; setp.eq.u32 p, %5, 0; @p ld.relaxed.gpu.global.v4.b32 {%0,%1,%2,%3}, [%4];}"
                     : "+r"(tq[0]), "+r"(tq[1]), "+r"(tq[2]), "+r"(tq[3]) : "l"(xb + offsetof(Xchg, T) + L16 * 8), "r"(warp) : "memory");
      };
      delay_until(tpub + DLY_V);
      wait_time(due + NS_V);
      TS(4);
      ldx(vm, vsrc);
      sched();
      xpos(2, 2);
      auto store_kqv = [&]() {
        fence_async();
        if (!(EXP & 4))
          asm volatile("{.reg .pred p; elect.sync _|p, 0xffffffff; @p cp.async.bulk.global.shared::cta.bulk_group [%0], [%1], 2048; cp.async.bulk.commit_group;}"
                       :: "l"(g_kqv[(s + 1) & 3][role] + w4 * 128), "r"(sb + R_STAGE + w4 * 2048) : "memory");
      };
      if (SPOS == 2) store_kqv();
      sched();
      bar_sync(5, 256);
      ldsm4(p, sb + R_P + L16);
      load_m(0);
      pv_x();
      ldsm4(p, sb + R_P + 1024 + L16);
      pv_m();
      const uint32_t r = norm(), tl = after(tag, c[2][0], (uint32_t)it >> 31);
      const bool redo = __any_sync(0xffffffffu, r | ((dif2(vm[0][0], vm[0][2], tl) | dif2(vm[1][0], vm[1][2], tl)) & 1));
      TS(6);
      stsm4t(uW + R_O + L16, o[0], o[1], o[2], o[3]);
      bar_arrive_unless(6, redo);
      sched();
      if (TQL == 7) get_t();
      TS(7);
      pv_x();
      if (rare(redo)) retry<2>(vm, vsrc, tag, it);
      bar_sync(8, 256);
      load_m(1);
      pv_m();
      if (rare(__any_sync(0xffffffffu, norm()) || redo)) {
        fresh();
#pragma unroll 1
        for (int x = !redo; x < 2; x++) {
          attend_max(x);
          if (x == 0) { stsm4t(uW + R_O + L16, o[0], o[1], o[2], o[3]); bar_arrive(6, 256); }
        }
      }
      TS(8);
      if (TQL == 8) get_t();
      const bool xok = mbar_test(sb + B_X + 16, s & 1) & mbar_test(sb + B_X + 24, s & 1);
      xpos(4, 2);
      fresh();
      const uint32_t ob = uni(sb + R_MEM + 4096 + w4 * 1024);
      stsm4t(ob + (L16 & 112) * 4 + (((L16 >> 3) ^ (L16 >> 1)) & 48), o[0], o[1], o[2], o[3]);
      __syncwarp();
      uint32_t rd[4];
      lds128(rd, uW + R_RD + L16);
      lds128(o, ob + (L16 ^ ((L16 >> 3) & 48)));
      auto put_o = [&]() {
        *reinterpret_cast<uint4*>(reinterpret_cast<uint8_t*>(g_ox) + (((s * SEG + 8 * j) * HD + h * DH + 32 * w4) * 2 + (L16 >> 6) * (HD * 2) + (L16 & 48))) = make_uint4(o[0], o[1], o[2], o[3]);
      };
      if (s + 1 == NSEG) { put_o(); asm volatile("cp.async.bulk.wait_group 0;" ::: "memory"); break; }
      asm volatile("cp.async.bulk.wait_group 0;" ::: "memory");
      if (elect()) stx32(xa + 4096 + j * 16 + w4 * 4, s + 1);
      __syncwarp();
      if (rare(!xok)) { wait_x(s + 2, 3); wait_x(s + 2, 2); }
      TS(9);
      fresh();
      const uint32_t e = due | ((s + 1) & 31);
      project_qk(IC<0>{}, IC<NQ>{}, IC<1>{}, [&](int n) {
        if (n == OXPOS) { __syncwarp(); put_o(); __syncwarp(); }
        if (n == TQP) { __syncwarp(); tq[0] = dif2v(tq[0], tq[1], e) | dif2v(tq[2], tq[3], e); __syncwarp(); }
      });
      if (NPA) project_v(IC<0>{}, IC<NPA>{}, [](int) {});
      TS(2);
      if (warp == 0) {
        uint32_t last = due, nx = NS_P;
        if (rare(__any_sync(0xffffffffu, tq[0]))) {
          const uint32_t ref = gtime();
#pragma unroll 1
          do ldx128(o, xb + offsetof(Xchg, T) + L16 * 8); while (any_bit(or3(o[0] - s - 1, o[1] - s - 1, o[2] - s - 1), o[3] - s - 1, 30) && ++it < SPIN_LIMIT);
          const int d = max(max((int)(o[0] - ref), (int)(o[1] - ref)), max((int)(o[2] - ref), (int)(o[3] - ref)));
          last = (ref + __reduce_max_sync(0xffffffffu, d)) & ~31u;
          if (last != due) nx += NS_X;
        }
        const uint32_t bdue = last + NS_B;
        if (s < 4) { last += (MG_Y >> 8 * s & 255) * 32; nx += (MG_Z >> 8 * s & 255) * 32; }
        sts32(sb + B_DUE, last);
        sts32(sb + B_DUE + 8 - tag * 4, last + nx);
        fetch4k(sb + R_MEM, my_b(), sb + B_B, bdue);
        LOG(13, tl - last);
        LOG(9, last);
      }
      if (NQ < 16) project_qk(IC<NQ>{}, IC<16>{}, IC<0>{}, [](int) {});
      project_v(IC<NPA>{}, IC<NPRE>{}, [](int) {});
      const uint32_t ba = rd[2], msk = rd[3];
      const uint8_t* cdst = reinterpret_cast<const uint8_t*>(rd[0] | (uint64_t)rd[1] << 32);
      TS(14);
      mbar_spin(sb + B_B, s & 1, it);
      TS(10);
      uint32_t bq[2][4];
      auto sum_b = [&]() {
        ldsm4t(bq[0], ba); ldsm4t(bq[1], ba + 2048);
        sched();
#pragma unroll
        for (int i = 0; i < 8; i++) c[i >> 2][i & 3] = 0.f;
        mma_a(c[0], bq[0], 0x3F803F80u, 0x3F803F80u); mma_a(c[1], bq[1], 0x3F803F80u, 0x3F803F80u);
        const uint32_t t2 = tag * 0x10001u;
        const bool old = any_bit(or3(dif2(bq[0][0], bq[0][1], t2), dif2(bq[0][2], bq[0][3], t2), dif2(bq[1][0], bq[1][1], t2)), dif2(bq[1][2], bq[1][3], t2), L16 < 64 ? 0x10001u : 0u);
        const uint32_t T = (tag << 16) & ~msk, u = ((__float_as_uint(c[0][0] + c[1][0]) + ((0x10000u & ~msk) - T)) & msk) | T;
        asm volatile("{.reg .pred p; setp.eq.u32 p, %2, 0; @p st.relaxed.gpu.global.b32 [%0], %1;}"
                     :: "l"(cdst), "r"(pack2(__uint_as_float(u), c[0][2] + c[1][2])), "r"((uint32_t)(old || (L16 & 32))) : "memory");
        return old;
      };
      if (rare(sum_b())) {
#pragma unroll 1
        do {
          const uint8_t* p = xb + (my_b() + (ba - sb - R_MEM));
          ldx128(bq[0], p); ldx128(bq[1], p + 2048);
          sts128(ba, bq[0]); sts128(ba + 2048, bq[1]);
          __syncwarp();
          it += INC_B;
        } while (sum_b() && it < SPIN_LIMIT);
      }
      sched();
      TS(11);
      bar_arrive(0, 256);
      const unsigned tc = clk();
      const uint32_t cdue = lds32(sb + B_DUE) + NS_C;
      if (warp == 3) LOG(11, gtime() - cdue);
      fresh();
      wg_wait<0>(); keep(aq); keep(av);
      park();
      if (NPRE < 32) project_v(IC<NPRE>{}, IC<32>{}, [](int) {}); else fin_v();
      TS(12);
      delay_until(tc + DLY_C);
      issue_c(cdue);
      TS(5);
      LOG(warp, it);
      pin_mem();
      if (NPRE < 32) { wg_wait<0>(); keep(av); fin_v(); }
      if (!(EXP & 2)) mbar_spin(sb + B_KV, tag, it);
      TS(15);
    } else {
      uint32_t kf[8][4];
      auto load_k = [&]() {
        const uint32_t ka = sb + R_K + w4 * 1024 + (L16 & 112) + (L16 & 128) * 4 + (L16 & 256);
#pragma unroll
        for (int i = 0; i < 8; i++) ldsm4(kf[i], ka + (i >> 1) * 2048 + (i & 1) * 128);
      };
      auto put_p = [&](int x, uint32_t old, uint32_t again) {
        float e[4];
        const int dq = (int)((L16 >> 3) & 6) + 8 * j - (int)(L16 >> 6) - 16 * w4;
#pragma unroll
        for (int i = 0; i < 4; i++) { r4[i] = fmaf(c[3][i], sc, fmaf(c[2][i], sc, fmaf(c[0][i] + c[1][i], sc, __uint_as_float(i == 3 ? 0u - old : 0u)))); e[i] = x && dq + (i & 1) < 8 * (i >> 1) ? 0.f : ex2(r4[i]); }
        stsm2t(uP2 + x * 1024 + L16, pack2(e[0], e[1]), pack2(e[2], e[3]), again);
      };
      auto put_s = [&](int x) {
#pragma unroll
        for (int i = 0; i < 4; i++) sts32f(uW + R_S + x * 1536 + (L16 & 48) * 4 + (L16 >> 6) * 4 + (i & 1) * 32 + (i >> 1) * 256, r4[i]);
      };
      auto load_q = [&](uint32_t (&q)[4], uint32_t off) { ldsm4(q, sb + R_Q + (L16 & 112) + (L16 & 128) * 2 + (L16 >> 8) * 128 + off); };
      mbar_spin(sb + B_C, nc & 1, it);
      TS(13);
      float4 o4;
      uint32_t id[4], old;
      {
        uint32_t b[24][4];
#pragma unroll
        for (int i = 0; i < 2 * PD1; i++) { lds128(b[i], ma + i * 512); __syncwarp(); }
        sched();
        zero(c);
#pragma unroll
        for (int i = 0; i < 12; i++) {
          mma4(4 * i, b[2 * i], b[2 * i + 1]);
          if (i < 11) sched();
          if (i + PD1 < 12) { const int k = i + PD1; const uint32_t a = (ma ^ (k >> 2 << 12)) + (k & 3) * 1024; lds128(b[2 * k], a); __syncwarp(); lds128(b[2 * k + 1], a + 512); sched(); }
          if (i == RJ) { lds128(id, sb + R_ID + L16); sched(); }
          if (i == RI) { old = bar_or(4, 0); o4 = lds128f(uW + R_RED + L16); sched(); }
        }
      }
      TS(0);
      {
        float e[4] = {o4.x, o4.y, o4.z, o4.w};
#pragma unroll
        for (int i = 0; i < 4; i++) { r4[i] = (((e[i] + c[0][i]) + c[1][i]) + c[2][i]) + c[3][i]; e[i] = 0.f; }
        mma_a(e, id, pack2(r4[0], r4[1]), pack2(r4[2], r4[3]));
        sched();
        if (VB) bar_arrive(7, 256);
        sched();
        asm volatile("{.reg .pred p; setp.eq.u32 p, %3, 0; @p st.relaxed.gpu.global.v2.b32 [%0], {%1,%2};}" :: "l"(adst),
                     "r"((__byte_perm(__float_as_uint(e[0]), __float_as_uint(e[1]), 0x7632) & ~1u) | tag), "r"(__byte_perm(__float_as_uint(e[2]), __float_as_uint(e[3]), 0x7632)), "r"(old) : "memory");
        sched();
      }
      const unsigned tpub = clk(), now = gtime(), due = get_due();
      if (__any_sync(0xffffffffu, old) && nc < NC_MAX) { bar_sync(3, 256); continue; }
      TS(2);
      const uint8_t* asrc = pinp(adst + ((warp == 7) * 1024 - (int)uA));
      fresh();
      uint32_t wo[32][4];
      bool xok;
      auto reload = [&]() {
        sched();
#pragma unroll
        for (int i = RE0 + RE1; i < NSW; i++) lds128(w[i], uW + R_WC + L16 + i * 2048);
        sched();
      };
      auto out_proj = [&]() {
        uint32_t b[4][4];
        float d[4][4];
        uint8_t* dst[2];
        const uint32_t da = pin(uP2 + (R_DST - R_P) + L16 / 2);
        sched();
        TS(7);
        bar_sync(6, 256);
#pragma unroll
        for (int i = 0; i < 4; i++) { ldsm4(b[i], sb + R_O + i * 512 + L16); __syncwarp(); }
        sched();
        auto put_b = [&](uint8_t* a, const float (&e)[4][4]) {
          stx128(a, (pack2(e[0][0] + e[2][0], e[0][1] + e[2][1]) & ~1u) | tag, pack2(e[0][2] + e[2][2], e[0][3] + e[2][3]),
                 pack2(e[1][0] + e[3][0], e[1][1] + e[3][1]), pack2(e[1][2] + e[3][2], e[1][3] + e[3][3]));
        };
        zero(c); zero(d);
#pragma unroll
        for (int i = 0; i < 32; i++) {
          mma_h(i < 16 ? c[i & 3] : d[i & 3], wo[i], b[(i >> 2) & 3], (i >> 1) & 1);
          if (i >= LW0 && NB1 + i - LW0 < 32) { load_wo(wo, (NB1 + i - LW0) ^ 1, ((NB1 + i - LW0) ^ 1) + 1); __syncwarp(); }
          if (i == DL0 || i == DL1) asm volatile("ld.shared.u64 %0, [%1];" : "=l"(dst[i > DL0]) : "r"(da + (i > DL0) * 1024) : "memory");
          if (i >= 16 && i < 16 + RE0) { lds128(w[i - 16], uW + R_WC + L16 + (i - 16) * 2048); __syncwarp(); }
          if (i >= RP1 && i < RP1 + RE1) { lds128(w[i - RP1 + RE0], uW + R_WC + L16 + (i - RP1 + RE0) * 2048); __syncwarp(); }
          if (i == 22) put_b(dst[0], c);
          if ((i & 1) && (i < 20 || i > 22)) sched();
        }
        put_b(dst[1], d);
        sched();
        TS(6);
      };
      if (warp < 6) {
        delay_until(tpub + DLY_A);
        const int it0 = it;
        bool redo;
#pragma unroll 1
        do {
          uint32_t q[4][4], y[4];
          float d[4][4];
          wait_time(due);
          TS(4);
          ldx(q, asrc);
          sched();
          load_k();
          uint32_t qx[4][4];
#pragma unroll
          for (int i = 0; i < 4; i++) load_q(qx[i], i * 512);
          sched();
          load_wo(wo, 0, NE4);
          sched();
          zero(c);
#pragma unroll
          for (int i = 0; i < 8; i++) mma_h(c[i & 3], kf[i], qx[i >> 1], i & 1);
          put_p(1, 0, 0); put_s(1);
          sched();
          load_wo(wo, NE4, NA4);
          sched();
          zero(c); zero(d);
#pragma unroll
          for (int i = 0; i < 8; i++) {
            if (i == 0) { y[0] = dif2v(q[0][0], q[0][2], q[1][0]); sched(); }
            if (i == 3) { y[1] = dif2v(q[1][2], q[2][0], q[2][2]); sched(); }
            if (i == 6) { y[2] = dif2v(q[3][0], q[3][2], tag); sched(); }
            mma_h(i % 6 < 2 ? c[2 + i % 6] : d[i - 2], kf[i], q[i >> 1], i & 1);
            if (i == 2 || i == 5 || i == 7) sched();
          }
          y[0] = or_and(or3(y[0], y[1], dif2v(q[0][0], q[2][0], tag)), y[2], it < SPIN_LIMIT);
#pragma unroll
          for (int i = 0; i < 4; i++) { c[0][i] = d[0][i] + d[1][i]; c[1][i] = d[2][i] + d[3][i]; }
          put_p(0, y[0], it - it0);
          TS(5);
          bar_sync_unless(5, it - it0);
          redo = __any_sync(0xffffffffu, y[0]);
          it += INC_A;
        } while (redo);
        it -= INC_A;
        put_s(0);
        bar_arrive(8, 256);
        load_wo(wo, NA4, NB1);
        out_proj();
        if (warp == 4) LOG(12, tb);
      } else {
        uint32_t qx[2][4], q[4][4];
        if (warp == 6) {
          const uint32_t t1 = (now & ~31u) + NS_M;
          LOG(10, now - due);
          if (elect()) stx32(&gx->T[h][j], ((int)(t1 - due) > 0 ? t1 + NS_PEN : due) | ((s + 1) & 31));
          __syncwarp();
        }
        auto score = [&](const uint32_t (&a0)[4], const uint32_t (&a1)[4]) {
          zero(c);
#pragma unroll
          for (int i = 0; i < 4; i++) mma_h(c[i], i < 2 ? a0 : a1, q[2 + (i >> 1)], i & 1);
        };
        auto put_m = [&](uint32_t a, uint32_t old, uint32_t again) {
#pragma unroll
          for (int i = 0; i < 2; i++) { r4[i] = fmaf(c[3][2 + i], sc, fmaf((c[0][i] + c[1][2 + i]) + c[2][i], sc, __uint_as_float(i ? 0u - old : 0u))); r4[2 + i] = fmaf(r4[i] * 0x1p122f, 0.f, ex2(r4[i])); }
          asm volatile("{.reg .pred p; setp.eq.u32 p, %3, 0; @p st.shared.v2.f32 [%0], {%1,%2};}" :: "r"(a), "f"(r4[2]), "f"(r4[3]), "r"(again) : "memory");
        };
        delay_until(tpub + DLY_A);
        const uint32_t sa = sb + R_S + 512 + w4 * 256 + (L16 >> 1);
        const int it0 = it;
        bool redo;
#pragma unroll 1
        do {
          wait_time(due);
          TS(4);
          ldx<4, 2048>(q, asrc);
          sched();
          load_q(qx[0], (w4 & 1) * 1024); load_q(qx[1], (w4 & 1) * 1024 + 512);
          load_wo(wo, 0, NA6);
          sched();
          score(q[0], q[1]);
          sched();
          const uint32_t y = or_and(or3(dif2v(q[0][0], q[0][2], tag), dif2v(q[1][0], q[1][2], tag), dif2v(q[2][0], q[2][2], tag)), dif2v(q[3][0], q[3][2], tag), it < SPIN_LIMIT);
          put_m(sa + 2560, y, it - it0);
          TS(5);
          bar_arrive_unless(5, it - it0);
          redo = __any_sync(0xffffffffu, y);
          it += INC_A;
        } while (redo);
        it -= INC_A;
        sts64f(sa, r4[0], r4[1]);
        score(qx[0], qx[1]);
        put_m(sa + 3584, 0, 0);
        sts64f(sa + 1536, r4[0], r4[1]);
        bar_arrive(8, 256);
        load_wo(wo, NA6, NB1);
        out_proj();
      }
      TS(8);
      if (s + 1 == NSEG) break;
      wait_x(s + 2, 2);
      TS(9);
      fresh();
      if (N1) project_qk(IC<32>{}, IC<32 + N1>{}, IC<1>{}, [](int) {});
      TS(10);
      xpos(6, 6);
      uint32_t fl = s + 1;
      if (warp == 5) { wait_time(due + NS_F); fl = ldx32(xa + 4096 + ((L16 >> 2) & 60)); }
      reload();
      TS(14);
      pin_mem();
      wait_x(s + 2, 1); wait_x(s + 2, 0);
      if (warp == 5) {
#pragma unroll 1
        while (__any_sync(0xffffffffu, fl != s + 1) && !(EXP & 4) && ++it < SPIN_LIMIT) fl = ldx32(xa + 4096 + ((L16 >> 2) & 60));
        wait_time(due + (NS_B + NS_K));
        if (!(EXP & 2) && elect()) issue_kqv(s + 1);
        __syncwarp();
      }
      if (PFD && warp == 6 && s + PFD < NSEG && elect())
        asm volatile("cp.async.bulk.prefetch.L2.global [%0], 2048;" :: "l"(xin + ((s + PFD) * SEG + ((role + 4 * (role >> 5)) & 31)) * DM) : "memory");
      __syncwarp();
      TS(11);
      LOG(warp, it);
      if (warp == 4) LOG(8, nc);
      bar_sync(0, 256);
      if (N1 < 16) project_qk(IC<32 + N1>{}, IC<48>{}, IC<!N1>{}, [](int) {});
      project_qk(IC<16>{}, IC<32>{}, IC<0>{}, [&](int n) { if ((n & 15) == XWPOS) { __syncwarp(); xok = mbar_test(sb + B_PK, s & 1); __syncwarp(); } });
      if (rare(!xok)) mbar_spin(sb + B_PK, s & 1, it);
      unpark();
      project_qk(IC<0>{}, IC<16>{}, IC<0>{}, [](int) {});
      TS(12);
      wg_wait<0>(); keep(aq);
      TS(1);
      fin_qk();
      TS(15);
    }
    s++;
  }
  if (it >= SPIN_LIMIT || nc >= NC_MAX) g_err = 2;
}

typedef CUresult (*EncodeFn)(CUtensorMap*, CUtensorMapDataType, cuuint32_t, void*, const cuuint64_t*, const cuuint64_t*, const cuuint32_t*,
                             const cuuint32_t*, CUtensorMapInterleave, CUtensorMapSwizzle, CUtensorMapL2promotion, CUtensorMapFloatOOBfill);
static void make_map(EncodeFn fn, CUtensorMap* m, const void* p, uint64_t cols, uint64_t rows, uint64_t pitch, uint32_t bc, uint32_t br, CUtensorMapSwizzle sw) {
  cuuint64_t dims[2] = {cols, rows}, strides[1] = {pitch * 2};
  cuuint32_t box[2] = {bc, br}, es[2] = {1, 1};
  fn(m, CU_TENSOR_MAP_DATA_TYPE_BFLOAT16, 2, const_cast<void*>(p), dims, strides, box, es, CU_TENSOR_MAP_INTERLEAVE_NONE, sw,
     CU_TENSOR_MAP_L2_PROMOTION_L2_256B, CU_TENSOR_MAP_FLOAT_OOB_FILL_NONE);
}

extern "C" void kernel_launch(void* const* d_in, const int* in_sizes, int n_in, void* d_out, int out_size) {
  const bf16* Ax = (const bf16*)d_in[0]; const bf16* mem0 = (const bf16*)d_in[1];
  const bf16* Wq = (const bf16*)d_in[2]; const bf16* Wk = (const bf16*)d_in[3]; const bf16* Wv = (const bf16*)d_in[4];
  const bf16* Wo = (const bf16*)d_in[5];
  const bf16* Bx = (const bf16*)d_in[7]; const bf16* wr = (const bf16*)d_in[8]; const bf16* wi = (const bf16*)d_in[9];
  bf16* out = (bf16*)d_out;

  void* fp = nullptr; cudaDriverEntryPointQueryResult qr;
  cudaGetDriverEntryPoint("cuTensorMapEncodeTiled", &fp, cudaEnableDefault, &qr);
  EncodeFn fn = (EncodeFn)fp;
  void *kqv, *ox, *xr;
  cudaGetSymbolAddress(&xr, g_xraw);
  cudaGetSymbolAddress(&kqv, g_kqv); cudaGetSymbolAddress(&ox, g_ox);
  const CUtensorMapSwizzle S128 = CU_TENSOR_MAP_SWIZZLE_128B, S64 = CU_TENSOR_MAP_SWIZZLE_64B;

  GemmMaps m3; RecMaps mr;
  make_map(fn, &m3.a, ox, HD, S_LEN, HD, 64, 128, S128);
  make_map(fn, &m3.b[0], Wo, DM, HD, DM, 64, 64, S128);
  m3.b[1] = m3.b[0]; m3.b[2] = m3.b[0];
  make_map(fn, &m3.c, out, DM, S_LEN, 2 * DM, 64, 64, S128);
  make_map(fn, &mr.wq, Wq, HD, DM, HD, 32, 256, S64);
  make_map(fn, &mr.wk, Wk, HD, DM, HD, 32, 256, S64);
  make_map(fn, &mr.wv, Wv, HD, DM, HD, 64, 256, S128);
  make_map(fn, &mr.wo, Wo, DM, HD, DM, 64, 128, S128);
  {
    cuuint64_t dims[3] = {64, S_LEN, 16}, strides[2] = {DM * 2, 128};
    cuuint32_t box[3] = {64, 32, 4}, es[3] = {1, 1, 1};
    fn(&mr.x, CU_TENSOR_MAP_DATA_TYPE_BFLOAT16, 3, const_cast<bf16*>(Ax), dims, strides, box, es, CU_TENSOR_MAP_INTERLEAVE_NONE, S128,
       CU_TENSOR_MAP_L2_PROMOTION_L2_256B, CU_TENSOR_MAP_FLOAT_OOB_FILL_NONE);
  }
  for (int i = 0; i < 3; i++) {
    cuuint64_t dims[3] = {128, 32, 512}, strides[2] = {256, 8192};
    cuuint32_t box[3] = {128, i == 0 ? 8u : i == 1 ? 2u : 16u, 4}, es[3] = {1, 1, 1};
    fn(i == 0 ? &mr.k : i == 1 ? &mr.q : &mr.v, CU_TENSOR_MAP_DATA_TYPE_BFLOAT16, 3, kqv, dims, strides, box, es, CU_TENSOR_MAP_INTERLEAVE_NONE,
       CU_TENSOR_MAP_SWIZZLE_NONE, CU_TENSOR_MAP_L2_PROMOTION_L2_256B, CU_TENSOR_MAP_FLOAT_OOB_FILL_NONE);
  }
  {
    cuuint64_t dims[3] = {64, 16, S_LEN}, strides[2] = {128, 2 * DM * 2};
    cuuint32_t box[3] = {64, 16, 2}, es[3] = {1, 1, 1};
    fn(&mr.fo, CU_TENSOR_MAP_DATA_TYPE_BFLOAT16, 3, out + DM, dims, strides, box, es, CU_TENSOR_MAP_INTERLEAVE_NONE, S128,
       CU_TENSOR_MAP_L2_PROMOTION_NONE, CU_TENSOR_MAP_FLOAT_OOB_FILL_NONE);
  }
  constexpr int SM3 = 6 * 32768 + 32768 + 256 + 1024;
  cudaFuncSetAttribute(gemm_kernel<128, 6>, cudaFuncAttributeMaxDynamicSharedMemorySize, SM3);
  cudaFuncSetAttribute(rec_kernel, cudaFuncAttributeMaxDynamicSharedMemorySize, R_TOTAL);

  cudaStream_t st = cudaStreamPerThread;
  Xchg* gx = reinterpret_cast<Xchg*>((reinterpret_cast<uintptr_t>(xr) + 0x1FFFFF) & ~(uintptr_t)0x1FFFFF);
  rec_kernel<<<132, 256, R_TOTAL, st>>>(mr, Ax, mem0, gx, Bx, wr, wi);
  gemm_kernel<128, 6><<<128, 384, SM3, st>>>(m3, 16, 8, 64, 8, reinterpret_cast<uint4*>(gx));
}
```

```cpp
#include <cuda_runtime.h>
#include <cuda_bf16.h>
#include <cuda.h>
#include <stdint.h>
#include <stddef.h>
#include <type_traits>

typedef __nv_bfloat16 bf16;

constexpr int S_LEN = 2048, DM = 1024, NH = 32, DH = 128, MEM = 8, SEG = 32, NSEG = 64;
constexpr int HD = NH * DH;
#define SPIN 20
constexpr int SPIN_LIMIT = 1 << SPIN, INC_A = 1, INC_B = 1;

constexpr unsigned NC_MAX = 4096;
__device__ __align__(1024) uint4 g_kqv[4][128][512];
__device__ __align__(1024) bf16 g_ox[(size_t)S_LEN * HD];
struct Xchg {
  uint4 A[32][4][256];
  uint4 C[4][2][256];
  uint4 B[128][2][256];
  uint32_t T[32][32];
  uint32_t S[128];
  unsigned ctr[64];
};
__device__ __align__(1024) uint4 g_xraw[(sizeof(Xchg) + (1 << 21)) / 16];
__device__ __align__(1024) uint4 g_y[1024 * 256];
__device__ __align__(1024) uint4 g_wt[513 * 512];
__device__ int g_err;

__device__ __forceinline__ unsigned clk() { unsigned long long c; asm volatile("mov.u64 %0, %%clock64;" : "=l"(c)); return (unsigned)c; }
__device__ __forceinline__ uint32_t smem_u32(const void* p) { return (uint32_t)__cvta_generic_to_shared(p); }
__device__ __forceinline__ void mbar_init(uint32_t bar, int cnt) { asm volatile("mbarrier.init.shared::cta.b64 [%0], %1;" :: "r"(bar), "r"(cnt) : "memory"); }
__device__ __forceinline__ void mbar_expect_tx(uint32_t bar, int bytes) { asm volatile("mbarrier.arrive.expect_tx.shared::cta.b64 _, [%0], %1;" :: "r"(bar), "r"(bytes) : "memory"); }
__device__ __forceinline__ void mbar_arrive_cluster(uint32_t bar, int cta) {
  asm volatile("{.reg .b32 r; mapa.shared::cluster.u32 r, %0, %1; mbarrier.arrive.shared::cluster.b64 _, [r];}" :: "r"(bar), "r"(cta) : "memory"); }
__device__ __forceinline__ bool mbar_try(uint32_t bar, int par) {
  uint32_t ok; asm volatile("{.reg .pred p; mbarrier.try_wait.parity.shared::cta.b64 p, [%1], %2; selp.u32 %0, 1, 0, p;}" : "=r"(ok) : "r"(bar), "r"(par) : "memory"); return ok; }
__device__ __forceinline__ bool mbar_test(uint32_t bar, int par) {
  uint32_t ok; asm volatile("{.reg .pred p; mbarrier.test_wait.parity.shared::cta.b64 p, [%1], %2; selp.u32 %0, 1, 0, p;}" : "=r"(ok) : "r"(bar), "r"(par) : "memory"); return ok; }
__device__ __forceinline__ void mbar_wait(uint32_t bar, int par) {
  int it = 0;
  while (!mbar_try(bar, par)) { if (++it > SPIN_LIMIT) { g_err = 1; break; } }
}
__device__ __forceinline__ void tma2d(uint32_t dst, const CUtensorMap* m, int c0, int c1, uint32_t bar) {
  asm volatile("cp.async.bulk.tensor.2d.shared::cluster.global.mbarrier::complete_tx::bytes [%0], [%1, {%3, %4}], [%2];"
    :: "r"(dst), "l"(m), "r"(bar), "r"(c0), "r"(c1) : "memory"); }
__device__ __forceinline__ void tma2d_mc(uint32_t dst, const CUtensorMap* m, int c0, int c1, uint32_t bar, uint16_t mask) {
  asm volatile("cp.async.bulk.tensor.2d.shared::cluster.global.mbarrier::complete_tx::bytes.multicast::cluster [%0], [%1, {%3, %4}], [%2], %5;"
    :: "r"(dst), "l"(m), "r"(bar), "r"(c0), "r"(c1), "h"(mask) : "memory"); }
__device__ __forceinline__ void tma2d_store(const CUtensorMap* m, uint32_t src, int c0, int c1) {
  asm volatile("cp.async.bulk.tensor.2d.global.shared::cta.bulk_group [%0, {%2, %3}], [%1];" :: "l"(m), "r"(src), "r"(c0), "r"(c1) : "memory"); }
__device__ __forceinline__ void fence_async() { asm volatile("fence.proxy.async.shared::cta;" ::: "memory"); }
__device__ __forceinline__ void bar_sync(int id, int n) { asm volatile("bar.sync %0, %1;" :: "r"(id), "r"(n) : "memory"); }
__device__ __forceinline__ void bar_arrive(int id, int n) { asm volatile("bar.arrive %0, %1;" :: "r"(id), "r"(n) : "memory"); }
__device__ __forceinline__ uint32_t pack2(float lo, float hi) { uint32_t r; asm("cvt.rn.bf16x2.f32 %0, %1, %2;" : "=r"(r) : "f"(hi), "f"(lo)); return r; }
__device__ __forceinline__ void ldsm4(uint32_t (&r)[4], uint32_t a) {
  asm volatile("ldmatrix.sync.aligned.m8n8.x4.shared.b16 {%0,%1,%2,%3}, [%4];" : "=r"(r[0]), "=r"(r[1]), "=r"(r[2]), "=r"(r[3]) : "r"(a) : "memory"); }
__device__ __forceinline__ void ldsm4t(uint32_t (&r)[4], uint32_t a) {
  asm volatile("ldmatrix.sync.aligned.m8n8.x4.trans.shared.b16 {%0,%1,%2,%3}, [%4];" : "=r"(r[0]), "=r"(r[1]), "=r"(r[2]), "=r"(r[3]) : "r"(a) : "memory"); }
__device__ __forceinline__ void stsm4(uint32_t a, uint32_t r0, uint32_t r1, uint32_t r2, uint32_t r3) {
  asm volatile("stmatrix.sync.aligned.m8n8.x4.shared.b16 [%0], {%1,%2,%3,%4};" :: "r"(a), "r"(r0), "r"(r1), "r"(r2), "r"(r3) : "memory"); }
__device__ __forceinline__ void stsm4t(uint32_t a, uint32_t r0, uint32_t r1, uint32_t r2, uint32_t r3) {
  asm volatile("stmatrix.sync.aligned.m8n8.x4.trans.shared.b16 [%0], {%1,%2,%3,%4};" :: "r"(a), "r"(r0), "r"(r1), "r"(r2), "r"(r3) : "memory"); }
__device__ __forceinline__ void lds128(uint32_t (&r)[4], uint32_t a) {
  asm volatile("ld.shared.v4.u32 {%0,%1,%2,%3}, [%4];" : "=r"(r[0]), "=r"(r[1]), "=r"(r[2]), "=r"(r[3]) : "r"(a) : "memory"); }
__device__ __forceinline__ float4 lds128f(uint32_t a) { float4 r;
  asm volatile("ld.shared.v4.f32 {%0,%1,%2,%3}, [%4];" : "=f"(r.x), "=f"(r.y), "=f"(r.z), "=f"(r.w) : "r"(a) : "memory"); return r; }
__device__ __forceinline__ float2 lds64f(uint32_t a) { float2 r;
  asm volatile("ld.shared.v2.f32 {%0,%1}, [%2];" : "=f"(r.x), "=f"(r.y) : "r"(a) : "memory"); return r; }
__device__ __forceinline__ void sts128(uint32_t a, uint32_t r0, uint32_t r1, uint32_t r2, uint32_t r3) {
  asm volatile("st.shared.v4.u32 [%0], {%1,%2,%3,%4};" :: "r"(a), "r"(r0), "r"(r1), "r"(r2), "r"(r3) : "memory"); }
__device__ __forceinline__ void sts64f(uint32_t a, float x, float y) { asm volatile("st.shared.v2.f32 [%0], {%1,%2};" :: "r"(a), "f"(x), "f"(y) : "memory"); }
__device__ __forceinline__ void sts32f(uint32_t a, float x) { asm volatile("st.shared.f32 [%0], %1;" :: "r"(a), "f"(x) : "memory"); }
__device__ __forceinline__ void mma16816(float (&d)[4], uint32_t a0, uint32_t a1, uint32_t a2, uint32_t a3, uint32_t b0, uint32_t b1) {
  asm volatile("mma.sync.aligned.m16n8k16.row.col.f32.bf16.bf16.f32 {%0,%1,%2,%3}, {%4,%5,%6,%7}, {%8,%9}, {%0,%1,%2,%3};"
    : "+f"(d[0]), "+f"(d[1]), "+f"(d[2]), "+f"(d[3]) : "r"(a0), "r"(a1), "r"(a2), "r"(a3), "r"(b0), "r"(b1)); }
__device__ __forceinline__ void mma1688(float (&d)[4], uint32_t a0, uint32_t a1, uint32_t b0) {
  asm volatile("mma.sync.aligned.m16n8k8.row.col.f32.bf16.bf16.f32 {%0,%1,%2,%3}, {%4,%5}, {%6}, {%0,%1,%2,%3};"
    : "+f"(d[0]), "+f"(d[1]), "+f"(d[2]), "+f"(d[3]) : "r"(a0), "r"(a1), "r"(b0)); }
__device__ __forceinline__ void ldx128(uint32_t (&r)[4], const void* p) {
  asm volatile("{.reg .b128 t; .reg .b64 a, b; ld.relaxed.gpu.global.b128 t, [%4]; mov.b128 {a, b}, t; mov.b64 {%0,%1}, a; mov.b64 {%2,%3}, b;}"
    : "=r"(r[0]), "=r"(r[1]), "=r"(r[2]), "=r"(r[3]) : "l"(p) : "memory"); }
__device__ __forceinline__ void stx128(void* p, uint32_t r0, uint32_t r1, uint32_t r2, uint32_t r3) {
  asm volatile("{.reg .b128 t; .reg .b64 a, b; mov.b64 a, {%1,%2}; mov.b64 b, {%3,%4}; mov.b128 t, {a, b}; st.relaxed.gpu.global.b128 [%0], t;}"
    :: "l"(p), "r"(r0), "r"(r1), "r"(r2), "r"(r3) : "memory"); }
__device__ __forceinline__ uint32_t uni(uint32_t x) { return __shfl_sync(0xffffffffu, x, 0); }
__device__ __forceinline__ uint32_t pin(uint32_t x) { return __shfl_xor_sync(0xffffffffu, x, 0); }
__device__ __forceinline__ float ex2(float x) { float r; asm("ex2.approx.ftz.f32 %0, %1;" : "=f"(r) : "f"(x)); return r; }
__device__ __forceinline__ void wg_fence() { asm volatile("wgmma.fence.sync.aligned;" ::: "memory"); }
__device__ __forceinline__ void wg_commit() { asm volatile("wgmma.commit_group.sync.aligned;" ::: "memory"); }
template <int N> __device__ __forceinline__ void wg_wait() { asm volatile("wgmma.wait_group.sync.aligned %0;" :: "n"(N) : "memory"); }

__device__ __forceinline__ void wgmma_ss_n256_tb1(float (&d)[128], uint64_t da, uint64_t db, int sc) {
  asm volatile("{.reg .pred p; setp.ne.b32 p, %130, 0;\n"
    "wgmma.mma_async.sync.aligned.m64n256k16.f32.bf16.bf16 {%0,%1,%2,%3,%4,%5,%6,%7,%8,%9,%10,%11,%12,%13,%14,%15,%16,%17,%18,%19,%20,%21,%22,%23,%24,%25,%26,%27,%28,%29,%30,%31,%32,%33,%34,%35,%36,%37,%38,%39,%40,%41,%42,%43,%44,%45,%46,%47,%48,%49,%50,%51,%52,%53,%54,%55,%56,%57,%58,%59,%60,%61,%62,%63,%64,%65,%66,%67,%68,%69,%70,%71,%72,%73,%74,%75,%76,%77,%78,%79,%80,%81,%82,%83,%84,%85,%86,%87,%88,%89,%90,%91,%92,%93,%94,%95,%96,%97,%98,%99,%100,%101,%102,%103,%104,%105,%106,%107,%108,%109,%110,%111,%112,%113,%114,%115,%116,%117,%118,%119,%120,%121,%122,%123,%124,%125,%126,%127}, %128, %129, p, 1, 1, 0, 1;}\n"
    : "+f"(d[0]),"+f"(d[1]),"+f"(d[2]),"+f"(d[3]),"+f"(d[4]),"+f"(d[5]),"+f"(d[6]),"+f"(d[7]),"+f"(d[8]),"+f"(d[9]),"+f"(d[10]),"+f"(d[11]),"+f"(d[12]),"+f"(d[13]),"+f"(d[14]),"+f"(d[15]),"+f"(d[16]),"+f"(d[17]),"+f"(d[18]),"+f"(d[19]),"+f"(d[20]),"+f"(d[21]),"+f"(d[22]),"+f"(d[23]),"+f"(d[24]),"+f"(d[25]),"+f"(d[26]),"+f"(d[27]),"+f"(d[28]),"+f"(d[29]),"+f"(d[30]),"+f"(d[31]),"+f"(d[32]),"+f"(d[33]),"+f"(d[34]),"+f"(d[35]),"+f"(d[36]),"+f"(d[37]),"+f"(d[38]),"+f"(d[39]),"+f"(d[40]),"+f"(d[41]),"+f"(d[42]),"+f"(d[43]),"+f"(d[44]),"+f"(d[45]),"+f"(d[46]),"+f"(d[47]),"+f"(d[48]),"+f"(d[49]),"+f"(d[50]),"+f"(d[51]),"+f"(d[52]),"+f"(d[53]),"+f"(d[54]),"+f"(d[55]),"+f"(d[56]),"+f"(d[57]),"+f"(d[58]),"+f"(d[59]),"+f"(d[60]),"+f"(d[61]),"+f"(d[62]),"+f"(d[63]),"+f"(d[64]),"+f"(d[65]),"+f"(d[66]),"+f"(d[67]),"+f"(d[68]),"+f"(d[69]),"+f"(d[70]),"+f"(d[71]),"+f"(d[72]),"+f"(d[73]),"+f"(d[74]),"+f"(d[75]),"+f"(d[76]),"+f"(d[77]),"+f"(d[78]),"+f"(d[79]),"+f"(d[80]),"+f"(d[81]),"+f"(d[82]),"+f"(d[83]),"+f"(d[84]),"+f"(d[85]),"+f"(d[86]),"+f"(d[87]),"+f"(d[88]),"+f"(d[89]),"+f"(d[90]),"+f"(d[91]),"+f"(d[92]),"+f"(d[93]),"+f"(d[94]),"+f"(d[95]),"+f"(d[96]),"+f"(d[97]),"+f"(d[98]),"+f"(d[99]),"+f"(d[100]),"+f"(d[101]),"+f"(d[102]),"+f"(d[103]),"+f"(d[104]),"+f"(d[105]),"+f"(d[106]),"+f"(d[107]),"+f"(d[108]),"+f"(d[109]),"+f"(d[110]),"+f"(d[111]),"+f"(d[112]),"+f"(d[113]),"+f"(d[114]),"+f"(d[115]),"+f"(d[116]),"+f"(d[117]),"+f"(d[118]),"+f"(d[119]),"+f"(d[120]),"+f"(d[121]),"+f"(d[122]),"+f"(d[123]),"+f"(d[124]),"+f"(d[125]),"+f"(d[126]),"+f"(d[127])
    : "l"(da), "l"(db), "r"(sc));
}

__device__ __forceinline__ void wgmma_ss_n128_tb1(float (&d)[64], uint64_t da, uint64_t db, int sc) {
  asm volatile("{.reg .pred p; setp.ne.b32 p, %66, 0;\n"
    "wgmma.mma_async.sync.aligned.m64n128k16.f32.bf16.bf16 {%0,%1,%2,%3,%4,%5,%6,%7,%8,%9,%10,%11,%12,%13,%14,%15,%16,%17,%18,%19,%20,%21,%22,%23,%24,%25,%26,%27,%28,%29,%30,%31,%32,%33,%34,%35,%36,%37,%38,%39,%40,%41,%42,%43,%44,%45,%46,%47,%48,%49,%50,%51,%52,%53,%54,%55,%56,%57,%58,%59,%60,%61,%62,%63}, %64, %65, p, 1, 1, 0, 1;}\n"
    : "+f"(d[0]),"+f"(d[1]),"+f"(d[2]),"+f"(d[3]),"+f"(d[4]),"+f"(d[5]),"+f"(d[6]),"+f"(d[7]),"+f"(d[8]),"+f"(d[9]),"+f"(d[10]),"+f"(d[11]),"+f"(d[12]),"+f"(d[13]),"+f"(d[14]),"+f"(d[15]),"+f"(d[16]),"+f"(d[17]),"+f"(d[18]),"+f"(d[19]),"+f"(d[20]),"+f"(d[21]),"+f"(d[22]),"+f"(d[23]),"+f"(d[24]),"+f"(d[25]),"+f"(d[26]),"+f"(d[27]),"+f"(d[28]),"+f"(d[29]),"+f"(d[30]),"+f"(d[31]),"+f"(d[32]),"+f"(d[33]),"+f"(d[34]),"+f"(d[35]),"+f"(d[36]),"+f"(d[37]),"+f"(d[38]),"+f"(d[39]),"+f"(d[40]),"+f"(d[41]),"+f"(d[42]),"+f"(d[43]),"+f"(d[44]),"+f"(d[45]),"+f"(d[46]),"+f"(d[47]),"+f"(d[48]),"+f"(d[49]),"+f"(d[50]),"+f"(d[51]),"+f"(d[52]),"+f"(d[53]),"+f"(d[54]),"+f"(d[55]),"+f"(d[56]),"+f"(d[57]),"+f"(d[58]),"+f"(d[59]),"+f"(d[60]),"+f"(d[61]),"+f"(d[62]),"+f"(d[63])
    : "l"(da), "l"(db), "r"(sc));
}

template <int BN> struct WG;
template <> struct WG<256> { static __device__ __forceinline__ void mma(float (&d)[128], uint64_t a, uint64_t b, int sc) { wgmma_ss_n256_tb1(d, a, b, sc); } };
template <> struct WG<128> { static __device__ __forceinline__ void mma(float (&d)[64], uint64_t a, uint64_t b, int sc) { wgmma_ss_n128_tb1(d, a, b, sc); } };

struct GemmMaps { CUtensorMap a, b[3], c; };
template <int BN, int STAGES>
__global__ void __cluster_dims__(2, 1, 1) __launch_bounds__(384, 1)
gemm_kernel(const __grid_constant__ GemmMaps maps, int tilesM, int tilesN, int kblocks, int nPerB, uint4* __restrict__ clearX) {
  extern __shared__ __align__(1024) uint8_t smem_raw[];
  constexpr int STAGE_BYTES = 16384 + BN * 128;
  constexpr int NBOX = BN / 64;
  const uint32_t sbase = (smem_u32(smem_raw) + 1023) & ~1023u;
  const uint32_t sEpi = sbase + STAGES * STAGE_BYTES;
  const uint32_t sBar = sEpi + 32768;
  const int warp = threadIdx.x >> 5, lane = threadIdx.x & 31, wg = warp >> 2;
  uint32_t crank; asm("mov.u32 %0, %%cluster_ctarank;" : "=r"(crank));
#define GT(k)
  const int npairs = (tilesM >> 1) * tilesN, pair0 = blockIdx.x >> 1, pstep = gridDim.x >> 1;
  if (threadIdx.x == 256) {
    asm volatile("prefetch.tensormap [%0];" :: "l"(&maps.b[0]) : "memory");
    for (int i = 0; i < STAGES; i++) { mbar_init(sBar + 8 * i, 1); mbar_init(sBar + 8 * (STAGES + i), 4); }
    asm volatile("fence.mbarrier_init.release.cluster;" ::: "memory");
    asm volatile("barrier.cluster.arrive.relaxed;" ::: "memory");
    for (int i = 0; i < STAGES; i++) {
      mbar_expect_tx(sBar + 8 * i, STAGE_BYTES);
      tma2d(sbase + i * STAGE_BYTES, &maps.a, i * 64, ((pair0 % (tilesM >> 1)) * 2 + crank) * 128, sBar + 8 * i);
    }
    asm volatile("prefetch.tensormap [%0];" :: "l"(&maps.c) : "memory");
  } else asm volatile("barrier.cluster.arrive.relaxed;" ::: "memory");
  asm volatile("barrier.cluster.wait.acquire;" ::: "memory");
  __syncwarp();
  if (wg == 2) {
    asm volatile("setmaxnreg.dec.sync.aligned.u32 40;");
    if (warp > 8) {
      __nanosleep(4000);
      for (int i = blockIdx.x * 96 + threadIdx.x - 288; i < (int)(sizeof(Xchg) / 16); i += gridDim.x * 96) clearX[i] = make_uint4(0, 0, 0, 0);
    }
    if (warp == 8 && lane == 0) {
      int st = 0, ph = 1;
      for (int p = pair0; p < npairs; p += pstep) {
        const int tm = (p % (tilesM >> 1)) * 2 + crank, tn = p / (tilesM >> 1);
        const CUtensorMap* mb = &maps.b[tn / nPerB];
        const int n0 = (tn % nPerB) * BN;
        for (int kb = 0; kb < kblocks; kb++) {
          const uint32_t a = sbase + st * STAGE_BYTES, full = sBar + 8 * st;
          if (p > pair0 || kb >= STAGES) {
            mbar_wait(sBar + 8 * (STAGES + st), ph);
            mbar_expect_tx(full, STAGE_BYTES);
            tma2d(a, &maps.a, kb * 64, tm * 128, full);
          }
#pragma unroll
          for (int i = 0; i < NBOX / 2; i++) {
            const int bx = crank * (NBOX / 2) + i;
            tma2d_mc(a + 16384 + bx * 8192, mb, n0 + bx * 64, kb * 64, full, (uint16_t)3);
          }
          if (++st == STAGES) { st = 0; ph ^= 1; }
        }
      }
      for (int i = 0; i < STAGES; i++) { mbar_wait(sBar + 8 * (STAGES + st), ph); if (++st == STAGES) { st = 0; ph ^= 1; } }
    }
  } else {
    asm volatile("setmaxnreg.inc.sync.aligned.u32 232;");
    int st = 0, ph = 0;
    float acc[BN / 2];
    const uint64_t descA0 = (uint64_t)(((sbase + wg * 8192) & 0x3FFFF) >> 4) | (1ull << 16) | (64ull << 32) | (1ull << 62);
    const uint64_t descB0 = (uint64_t)(((sbase + 16384) & 0x3FFFF) >> 4) | (512ull << 16) | (64ull << 32) | (1ull << 62);
    const uint32_t epi = sEpi + wg * 16384;
    for (int p = pair0; p < npairs; p += pstep) {
      const int tm = (p % (tilesM >> 1)) * 2 + crank, tn = p / (tilesM >> 1);
      int prev = -1;
      for (int kb = 0; kb < kblocks; kb++) {
        mbar_wait(sBar + 8 * st, ph);
        if ((kb & 15) == 0) { GT(kb >> 4); }
        wg_fence();
        const uint64_t so = (uint64_t)(st * (STAGE_BYTES >> 4));
#pragma unroll
        for (int k = 0; k < 4; k++) WG<BN>::mma(acc, descA0 + so + k * 2, descB0 + so + k * 128, kb | k);
        wg_commit();
        if (prev >= 0) {
          wg_wait<1>();
          if ((threadIdx.x & 127) < 2) mbar_arrive_cluster(sBar + 8 * (STAGES + prev), threadIdx.x & 1);
        }
        prev = st;
        if (++st == STAGES) { st = 0; ph ^= 1; }
      }
      wg_wait<0>();
      if ((threadIdx.x & 127) < 2) mbar_arrive_cluster(sBar + 8 * (STAGES + prev), threadIdx.x & 1);
      GT(4);
#pragma unroll
      for (int r = 0; r < BN / 128; r++) {
        if (r || p > pair0) {
          if ((threadIdx.x & 127) == 0) asm volatile("cp.async.bulk.wait_group.read 0;" ::: "memory");
          bar_sync(1 + wg, 128);
        }
        const int row = (warp & 3) * 16 + (lane & 15);
#pragma unroll
        for (int i = 0; i < 8; i++) {
          const int c = 2 * (i & 3) + (lane >> 4);
          const float* q = &acc[r * 64 + i * 8];
          stsm4(epi + (i >> 2) * 8192 + row * 128 + ((c ^ (row & 7)) << 4), pack2(q[0], q[1]), pack2(q[2], q[3]), pack2(q[4], q[5]), pack2(q[6], q[7]));
        }
        fence_async();
        bar_sync(1 + wg, 128);
        if ((threadIdx.x & 127) == 0) {
          tma2d_store(&maps.c, epi, tn * BN + r * 128, tm * 128 + wg * 64);
          tma2d_store(&maps.c, epi + 8192, tn * BN + r * 128 + 64, tm * 128 + wg * 64);
          asm volatile("cp.async.bulk.commit_group;" ::: "memory");
        }
      }
    }
    GT(5);
    if ((threadIdx.x & 127) == 0) asm volatile("cp.async.bulk.wait_group.read 0;" ::: "memory");
    GT(6);
  }
}

struct Dft { uint32_t m[2][2][2][4]; };
template <bool P4> __device__ __forceinline__ int fidx(int tile, int x) { return P4 ? 4 * (x >> 1) + 2 * (tile & 1) + (x & 1) + 16 * (tile >> 1) : x + 8 * tile; }
__device__ __forceinline__ float2 cis(int k, int n) {
  k &= n - 1; if (2 * k > n) k -= n;
  const float a = (float)k * (6.283185307179586f / (float)n);
  return make_float2(__cosf(a), __sinf(a));
}
template <bool OUT4> __device__ __forceinline__ void make_dft(Dft& D, int g, int t) {
#pragma unroll
  for (int q = 0; q < 16; q++) {
    const int b = q >> 3, u = (q >> 2) & 1, r = (q >> 1) & 1, v = q & 1;
    const float2 w = cis(fidx<OUT4>(v, g) * fidx<false>(2 * u + r, 2 * t + b), 32);
    D.m[b][u][0][q & 3] = pack2(w.x, w.y); D.m[b][u][1][q & 3] = pack2(-w.y, w.x);
  }
}
__device__ __forceinline__ void mma_dc(float (&d)[4], uint32_t a0, uint32_t a1, uint32_t a2, uint32_t a3, uint32_t b0, uint32_t b1, const float (&c)[4]) {
  asm("mma.sync.aligned.m16n8k16.row.col.f32.bf16.bf16.f32 {%0,%1,%2,%3}, {%4,%5,%6,%7}, {%8,%9}, {%10,%11,%12,%13};"
    : "=f"(d[0]), "=f"(d[1]), "=f"(d[2]), "=f"(d[3]) : "r"(a0), "r"(a1), "r"(a2), "r"(a3), "r"(b0), "r"(b1), "f"(c[0]), "f"(c[1]), "f"(c[2]), "f"(c[3])); }
__device__ __forceinline__ void dft_b(const Dft& D, const uint32_t (&x)[2][4], float (&o)[2][8]) {
#pragma unroll
  for (int ri = 0; ri < 2; ri++) {
    float z[4] = {0.f, 0.f, 0.f, 0.f}, e[4], p[4];
    mma_dc(e, D.m[0][0][ri][0], D.m[0][0][ri][1], D.m[0][0][ri][2], D.m[0][0][ri][3], x[0][0], x[0][1], z);
    mma_dc(e, D.m[0][1][ri][0], D.m[0][1][ri][1], D.m[0][1][ri][2], D.m[0][1][ri][3], x[0][2], x[0][3], e);
    mma_dc(p, D.m[1][0][ri][0], D.m[1][0][ri][1], D.m[1][0][ri][2], D.m[1][0][ri][3], x[1][0], x[1][1], e);
    mma_dc(p, D.m[1][1][ri][0], D.m[1][1][ri][1], D.m[1][1][ri][2], D.m[1][1][ri][3], x[1][2], x[1][3], p);
#pragma unroll
    for (int q = 0; q < 4; q++) { o[ri][q] = p[q]; o[ri][4 + q] = fmaf(2.f, e[q], -p[q]); }
  }
}
__device__ __forceinline__ void dft_a(const uint32_t (&m)[2][2][4], const uint32_t (&x0)[2][4], const uint32_t (&x1)[2][4], float (&o)[2][8]) {
#pragma unroll
  for (int ri = 0; ri < 2; ri++) {
    float z[4] = {0.f, 0.f, 0.f, 0.f}, e[4], p[4];
    mma_dc(e, x0[0][0], x1[0][0], x0[0][1], x1[0][1], m[0][ri][0], m[0][ri][1], z);
    mma_dc(e, x0[0][2], x1[0][2], x0[0][3], x1[0][3], m[0][ri][2], m[0][ri][3], e);
    mma_dc(p, x0[1][0], x1[1][0], x0[1][1], x1[1][1], m[1][ri][0], m[1][ri][1], e);
    mma_dc(p, x0[1][2], x1[1][2], x0[1][3], x1[1][3], m[1][ri][2], m[1][ri][3], p);
#pragma unroll
    for (int q = 0; q < 4; q++) { o[ri][q] = p[q]; o[ri][4 + q] = fmaf(2.f, e[q], -p[q]); }
  }
}
__device__ __forceinline__ uint32_t twid(float re, float im, float c, float s) { return pack2(fmaf(re, c, im * s), fmaf(im, c, -re * s)); }
__device__ __forceinline__ void cpa16(uint32_t d, const void* s) { asm volatile("cp.async.cg.shared.global [%0], [%1], 16;" :: "r"(d), "l"(s) : "memory"); }
__device__ __forceinline__ void sts32(uint32_t a, uint32_t x) { asm volatile("st.shared.u32 [%0], %1;" :: "r"(a), "r"(x) : "memory"); }
__device__ __forceinline__ void cpa_commit() { asm volatile("cp.async.commit_group;" ::: "memory"); }
template <int N> __device__ __forceinline__ void cpa_wait() { asm volatile("cp.async.wait_group %0;" :: "n"(N) : "memory"); }
__device__ __forceinline__ uint32_t lds32(uint32_t a) { uint32_t r; asm volatile("ld.shared.u32 %0, [%1];" : "=r"(r) : "r"(a) : "memory"); return r; }
#define FMID 0
constexpr int F_TP = 4112, F_TSZ = 8 * F_TP;

__device__ __forceinline__ uint32_t ldnc32(const void* p) { uint32_t v; asm volatile("ld.global.nc.b32 %0, [%1];" : "=r"(v) : "l"(p) : "memory"); return v; }
template <class F>
__device__ __forceinline__ void fft_wprep(const bf16* __restrict__ wr, const bf16* __restrict__ wi, int cta, F&& mid) {
  const int tid = threadIdx.x, g = (cta >> 1) & 7, c = (cta >> 4) & 3, t = 2 * (cta & 1) + (tid & 1);
  const int k0 = g + 8 * (cta >> 6) + 32 * (8 * c + 2 * t), l0 = (tid & ~1) + (g & 1);
  uint32_t a[4][4], b[4][4];
#pragma unroll
  for (int q = 0; q < 16; q++) {
    const int o = (k0 + 16 * (q >> 3) + 32 * ((q >> 1) & 1) + 1024 * (q & 1)) * 513 + l0 + 256 * ((q >> 2) & 1);
    a[q >> 2][q & 3] = ldnc32(wr + o);
    b[q >> 2][q & 3] = ldnc32(wi + o);
  }
  const int e = cta * 32 + (tid & 31), lh = (e >> 11) * 512, k = e & 2047, k2 = (k >> 5) & 31;
  uint32_t hz[4];
#pragma unroll
  for (int q = 0; q < 4; q++) asm volatile("ld.global.nc.u16 %0, [%1];" : "=r"(hz[q]) : "l"((q < 2 ? wr : wi) + (q & 1 ? (2048 - k) & 2047 : k) * 513 + lh) : "memory");
  mid();
  uint4* dst = g_wt + l0 * 512 + cta * 2 + (tid & 1);
#pragma unroll
  for (int q = 0; q < 8; q++) {
    const int hf = q >> 1, l = l0 + 256 * (hf & 1) + (q & 1);
    const uint32_t sel = (q & 1) ? 0x7632 : 0x5410;
    if (l & 511) dst[(256 * (hf & 1) + (q & 1)) * 512 + 256 * (q >> 2)] = make_uint4(__byte_perm(a[hf][0], b[hf][0], sel), __byte_perm(a[hf][1], b[hf][1], sel),
                                                                                   __byte_perm(a[hf][2], b[hf][2], sel), __byte_perm(a[hf][3], b[hf][3], sel));
  }
  if (tid < 32) reinterpret_cast<uint32_t*>(g_wt)[(64 * ((k >> 3) & 3) + 16 * (k2 >> 3) + 2 * (k & 7) + ((k2 >> 2) & 1)) * 8 + lh * 2048 + 2 * (k2 & 3) + (k >> 10)] =
      pack2(0.5f * (__uint_as_float(hz[0] << 16) + __uint_as_float(hz[1] << 16)), 0.5f * (__uint_as_float(hz[2] << 16) - __uint_as_float(hz[3] << 16)));
}

template <class F>
__device__ __forceinline__ void fft_rows_fwd(const bf16* __restrict__ x, const bf16* __restrict__ wr, const bf16* __restrict__ wi, uint32_t tb, int it, F&& mid) {
  const int warp = threadIdx.x >> 5, lane = threadIdx.x & 31, g = lane >> 2, t = lane & 3;
  const uint32_t in = tb + warp * 4096;
  const uint32_t f0 = in + (lane >> 3) * 256 + (((lane & 7) ^ (2 * (lane >> 3))) << 4);
  const bf16* src = x + ((256 * (warp & 3) + 64 * (warp >> 2) + 128 * (it & 1) + 32 * ((it >> 4) & 1) + 8 * (it >> 5) + ((it >> 1) & 7)) * 2048 + lane * 8);
#pragma unroll
  for (int q = 0; q < 8; q++) cpa16((f0 ^ ((q >> 2) * 144)) + (q & 3) * 1024, src + q * 256);
  cpa_commit();
  Dft D;
  float2 tw[4][8];
  fft_wprep(wr, wi, it, [&]() {
    if (FMID == 0) mid();
    make_dft<true>(D, g, t);
#pragma unroll
    for (int q = 0; q < 32; q++) {
      tw[q >> 3][q & 7] = cis(fidx<true>((q >> 1) & 3, g) * fidx<false>(q >> 3, 2 * t + (q & 1)), 1024);
      if (FMID) asm volatile("" : "+f"(tw[q >> 3][q & 7].x), "+f"(tw[q >> 3][q & 7].y) :: "memory");
    }
    if (FMID == 1) mid();
  });
  if (FMID == 2) mid();
  cpa_wait<0>(); __syncwarp();
  uint32_t a[4][2][4], y[4][2][4];
#pragma unroll
  for (int q = 0; q < 8; q++) ldsm4t(a[q & 3][q >> 2], (in + lane * 128 + ((lane & 7) << 4)) ^ (q << 4));
  float o[2][8];
#pragma unroll
  for (int i = 0; i < 4; i++) {
    dft_b(D, a[i], o);
#pragma unroll
    for (int q = 0; q < 8; q++) y[q >> 1][q & 1][i] = twid(o[0][q], o[1][q], tw[i][q].x, tw[i][q].y);
  }
  __syncthreads();
  const uint32_t w0 = tb + warp * F_TP + fidx<true>(0, g) * 128 + t * 16 + ((g & 1) << 6), wz = (g & 1) ? -64 : 64;
#pragma unroll
  for (int z = 0; z < 2; z++) {
    float o2[2][8];
    dft_b(D, y[2 * z], o); dft_b(D, y[2 * z + 1], o2);
#pragma unroll
    for (int i = 0; i < 4; i++) {
      const float sg = i < 2 ? 1.f : -1.f;
      sts128(w0 + z * wz + fidx<true>(i, 0) * 128, pack2(o[0][2 * i], sg * o[1][2 * i]), pack2(o[0][2 * i + 1], sg * o[1][2 * i + 1]),
             pack2(o2[0][2 * i], sg * o2[1][2 * i]), pack2(o2[0][2 * i + 1], sg * o2[1][2 * i + 1]));
    }
  }
  __syncthreads();
  const uint32_t ra = tb + (lane & 1) * 4 * F_TP + ((lane >> 1) + 16 * (warp ^ ((warp >> 1) & 1))) * 4;
  uint4* dst = g_y + (threadIdx.x >> 1) * 256 + (lane & 1) + it * 2;
#pragma unroll
  for (int q = 0; q < 8; q++) { const uint32_t r = ra + q * 512; dst[q * 32768] = make_uint4(lds32(r), lds32(r + F_TP), lds32(r + 2 * F_TP), lds32(r + 3 * F_TP)); }
}

template <class F>
__device__ __forceinline__ void fft_cols(uint32_t sb, int cta, int ncta, F&& ready) {
  const int warp = threadIdx.x >> 5, lane = threadIdx.x & 31, g = lane >> 2, t = lane & 3;
  const uint32_t in = sb + warp * 16384 + lane * 16, tab = sb + 131072 + lane * 16;
  auto fetch_y = [&](int l) {
#pragma unroll
    for (int q = 0; q < 16; q++) cpa16(in + q * 512, g_y + (q < 8 ? l : (1024 - l) & 1023) * 256 + (q & 7) * 32 + lane);
  };
  auto fetch_w = [&](int l) {
#pragma unroll
    for (int q = 0; q < 16; q++) cpa16(in + 8192 + q * 512, g_wt + l * 512 + q * 32 + lane);
  };
  const int l0 = cta * 8 + warp, dl = ncta * 8;
  Dft D; make_dft<false>(D, g, t);
#pragma unroll
  for (int q = 2 * warp; q < 2 * warp + 2; q++) {
    const int r = fidx<false>(q & 3, g), c = fidx<false>(q >> 2, 2 * t);
    const float2 w0 = cis(r * c, 1024), w1 = cis(r * c + r, 1024), p0 = cis(r + 32 * c, 2048), p1 = cis(r + 32 * c + 32, 2048);
    sts128(tab + q * 512, __float_as_uint(w0.x), __float_as_uint(w0.y), __float_as_uint(w1.x), __float_as_uint(w1.y));
    sts128(tab + 8192 + q * 512, __float_as_uint(p0.x), __float_as_uint(p0.y), __float_as_uint(p1.x), __float_as_uint(p1.y));
  }
  if (warp == 0) {
#pragma unroll
    for (int q = 0; q < 8; q++) {
      const int v = q >> 2, b = (q >> 1) & 1, ri = q & 1;
      sts128(tab + 16384 + q * 512, D.m[b][0][ri][v], D.m[b][0][ri][v + 2], D.m[b][1][ri][v], D.m[b][1][ri][v + 2]);
    }
  }
  ready();
  fetch_y(l0); cpa_commit();
  fetch_w(l0); cpa_commit();
#pragma unroll 1
  for (int l = l0; l <= 512; l += dl) {
    uint32_t a[2][4][2][4], y[2][4][2][4];
    float o[2][2][8];
    cpa_wait<1>();
#pragma unroll
    for (int q = 0; q < 16; q++) lds128(a[q >> 3][(q >> 1) & 3][q & 1], in + q * 512);
    if (!(l & 511)) {
      const uint32_t m0 = l ? 0x80000000u : 0u;
#pragma unroll
      for (int q = 0; q < 32; q++) { a[0][q >> 3][(q >> 2) & 1][q & 3] ^= m0; a[1][q >> 3][(q >> 2) & 1][q & 3] ^= m0 ^ 0x80000000u; }
    }
    auto first = [&]() {
#pragma unroll
      for (int i = 0; i < 4; i++) {
        dft_b(D, a[0][i], o[0]); dft_b(D, a[1][i], o[1]);
#pragma unroll
        for (int r = 0; r < 4; r++) {
          const float4 w = lds128f(tab + (4 * i + r) * 512);
#pragma unroll
          for (int s = 0; s < 2; s++) {
            y[s][r][0][i] = twid(o[s][0][2 * r], o[s][1][2 * r], w.x, w.y);
            y[s][r][1][i] = twid(o[s][0][2 * r + 1], o[s][1][2 * r + 1], w.z, w.w);
          }
        }
      }
    };
    first();
    if (l + dl <= 512) fetch_y(l + dl);
    cpa_commit();
    cpa_wait<1>();
#pragma unroll
    for (int zv = 0; zv < 4; zv++) {
      const int z = zv >> 1, v = zv & 1;
      uint32_t m[2][2][4];
#pragma unroll
      for (int q = 0; q < 4; q++) lds128(m[q >> 1][q & 1], tab + 16384 + (4 * v + q) * 512);
      dft_a(m, y[0][2 * z], y[0][2 * z + 1], o[0]); dft_a(m, y[1][2 * z], y[1][2 * z + 1], o[1]);
#pragma unroll
      for (int q = 0; q < 4; q++) {
        const int i = 2 * z + (q & 1), c = v + (q & 2);
        uint32_t w[4]; lds128(w, in + 8192 + (4 * i + c) * 512);
        const float4 ph = lds128f(tab + 8192 + (4 * c + i) * 512);
#pragma unroll
        for (int b = 0; b < 2; b++) {
          const float cs = b ? ph.z : ph.x, sn = b ? ph.w : ph.y;
          const float r1 = __uint_as_float(w[2 * b] << 16), i1 = __uint_as_float(w[2 * b] & 0xFFFF0000u);
          const float r2 = __uint_as_float(w[2 * b + 1] << 16), i2 = __uint_as_float(w[2 * b + 1] & 0xFFFF0000u);
          const float Sr = r1 + r2, Si = i1 + i2, Dr = r1 - r2, Di = i1 - i2;
          const float ar = fmaf(-Dr, sn, Sr), ai = fmaf(-Di, sn, Si), dr = fmaf(Dr, sn, Sr), di = fmaf(Di, sn, Si), br = -Di * cs, bi = Dr * cs;
          const float Ar = o[0][0][2 * q + b], Ai = o[0][1][2 * q + b], Br = o[1][0][2 * q + b], Bi = o[1][1][2 * q + b];
          a[0][i][b][c] = pack2(fmaf(ar, Ai, fmaf(ai, Ar, fmaf(br, Bi, bi * Br))), fmaf(ar, Ar, fmaf(-ai, Ai, fmaf(br, Br, -bi * Bi))));
          a[1][i][b][c] = pack2(fmaf(dr, Bi, fmaf(di, Br, fmaf(-br, Ai, -bi * Ar))), fmaf(dr, Br, fmaf(-di, Bi, fmaf(-br, Ar, bi * Ai))));
        }
      }
    }
    if (l + dl <= 512) fetch_w(l + dl);
    cpa_commit();
    first();
#pragma unroll
    for (int s = 0; s < 2; s++) {
      uint4* dst = g_y + (s ? (1024 - l) & 1023 : l) * 256 + lane;
      const float sg = s ? -1.f : 1.f;
#pragma unroll
      for (int i = 0; i < 4; i++) {
        dft_b(D, y[s][i], o[0]);
#pragma unroll
        for (int b = 0; b < 2; b++)
          dst[(2 * i + b) * 32] = make_uint4(pack2(sg * o[0][0][b], o[0][1][b]), pack2(sg * o[0][0][2 + b], o[0][1][2 + b]),
                                             pack2(sg * o[0][0][4 + b], o[0][1][4 + b]), pack2(sg * o[0][0][6 + b], o[0][1][6 + b]));
      }
    }
  }
}

template <class F>
__device__ __forceinline__ void fft_rows_inv(const CUtensorMap* om, uint32_t sb, int cta, int ncta, F&& ready) {
  const int warp = threadIdx.x >> 5, lane = threadIdx.x & 31, g = lane >> 2, t = lane & 3, wg = warp >> 2, w4 = warp & 3;
  const uint32_t tb = sb + 32768 + wg * 2 * F_TSZ;
  const uint4* src = g_y + pin((256 * ((lane >> 1) & 3) + 64 * (lane >> 3) + 8 * w4) * 256 + (lane & 1));
  const uint32_t wa = pin(tb + (lane & 1) * 4 * F_TP + w4 * 1024 + (lane >> 1) * 4);
  uint4 pf[8];
  auto fetch = [&](int it, int hf) {
#pragma unroll
    for (int q = 0; q < 8; q++) pf[q] = __ldcg(src + (it * 2 + hf * 8192) + q * 256);
  };
  auto put = [&](uint32_t off) {
#pragma unroll
    for (int q = 0; q < 8; q++) {
      sts32(wa + off + q * 64, pf[q].x); sts32(wa + off + q * 64 + F_TP, pf[q].y);
      sts32(wa + off + q * 64 + 2 * F_TP, pf[q].z); sts32(wa + off + q * 64 + 3 * F_TP, pf[q].w);
    }
  };
  const int it0 = 2 * cta + wg;
  Dft D; make_dft<false>(D, g, t);
  float2 tw[4][8];
#pragma unroll
  for (int q = 0; q < 32; q++) {
    tw[q >> 3][q & 7] = cis(fidx<false>((q >> 1) & 3, g) * fidx<false>(q >> 3, 2 * t + (q & 1)), 1024);
    tw[q >> 3][q & 7].x *= 1.f / 2097152.f; tw[q >> 3][q & 7].y *= 1.f / 2097152.f;
    asm volatile("" : "+f"(tw[q >> 3][q & 7].x), "+f"(tw[q >> 3][q & 7].y) :: "memory");
  }
  ready();
  fetch(it0, 0); put(0); fetch(it0, 1); put(512);
  const uint32_t la = pin(tb + w4 * F_TP + lane * 16), ob = uni(sb + warp * 4096);
  const uint32_t oa = pin(ob + (lane >> 1) * 128 + (((4 * (lane & 1)) ^ ((lane >> 1) & 7)) << 4));
#pragma unroll 1
  for (int n = 0;; n++) {
    const int it = it0 + (n >> 1) * 2 * ncta, hf = n & 1, buf = (n >> 1) & 1;
    if (it >= 128) break;
    if (!hf) bar_sync(1 + wg, 128);
    uint32_t a[4][2][4], y[4][2][4];
#pragma unroll
    for (int q = 0; q < 8; q++) lds128(a[q >> 1][q & 1], la + buf * F_TSZ + hf * 4 * F_TP + q * 512);
    fetch(min(it + 2 * ncta, 127), hf);
    float o[2][8];
#pragma unroll
    for (int i = 0; i < 4; i++) {
      dft_b(D, a[i], o);
#pragma unroll
      for (int q = 0; q < 8; q++) y[q >> 1][q & 1][i] = twid(o[0][q], o[1][q], tw[i][q].x, tw[i][q].y);
    }
    if (lane == 0) asm volatile("cp.async.bulk.wait_group.read 0;" ::: "memory");
    __syncwarp();
#pragma unroll
    for (int c = 0; c < 4; c++) {
      dft_b(D, y[c], o);
#pragma unroll
      for (int ri = 0; ri < 2; ri++)
        stsm4((oa ^ (c << 4)) + (1 - ri) * 2048, pack2(o[ri][0], o[ri][1]), pack2(o[ri][2], o[ri][3]), pack2(o[ri][4], o[ri][5]), pack2(o[ri][6], o[ri][7]));
    }
    fence_async();
    __syncwarp();
    if (lane == 0) {
      const int m = 256 * w4 + 32 * ((it >> 1) & 7) + 8 * (it >> 5) + 4 * (it & 1) + 2 * hf + ((it >> 4) & 1);
      asm volatile("cp.async.bulk.tensor.3d.global.shared::cta.bulk_group [%0, {0, 0, %2}], [%1];" :: "l"(om), "r"(ob), "r"(2 * m) : "memory");
      asm volatile("cp.async.bulk.commit_group;" ::: "memory");
    }
    put((buf ^ 1) * F_TSZ + hf * 512);
  }
  if (lane == 0) asm volatile("cp.async.bulk.wait_group 0;" ::: "memory");
}
__device__ __forceinline__ void grid_arrive(unsigned* ctr) {
  __syncthreads();
  if (threadIdx.x == 0) { __threadfence(); atomicAdd(ctr, 1u); }
}
__device__ __forceinline__ void grid_wait(unsigned* ctr, unsigned n) {
  if (threadIdx.x == 224) {
    int it = 0;
    while (*reinterpret_cast<volatile unsigned*>(ctr) < n) { __nanosleep(100); if (++it > SPIN_LIMIT) { g_err = 3; break; } }
    __threadfence();
  }
  __syncthreads();
}

struct RecMaps { CUtensorMap wq, wk, wv, wo, x, k, q, v, fo; };
#define NSW 16
#define EXP 0
#define NPB 3
#define NPB0 3
#define NPC 0
#define WOP 2
#define HOME 7
#define DL0 14
#define PD1 4
#define NE4 6
#define NA4 14
#define NA6 18
#define NB1 24
#define TQL 7
#define NQ 16
#define TQP (NQ - 1)
#define OXPOS 4
#define XWPOS 10
#define RI 9
#define RJ 8
#define NPRE 22
#define PFD 4
#define PD0 4
#define VB NV0
#define NPA 0
#define N1 16
#define DL1 16
#define PACE 0
#define RE0 0
#define RE1 0
#define RP1 23
#define X2 2
#define X3 2
#define SPOS 2
#ifndef NV0
#define NV0 4
#endif
#define TGP 3
#define LW0 8
#define X1 4
#define X0 4
constexpr int R_WO = 0, R_X = 65536, R_MEM = 131072, R_WC = 147456, R_RED = R_WC + NSW * 2048, R_O = R_RED, R_S = R_O + 2048, R_P = R_S + 3072, R_STAGE = R_P + 2048,
              R_K = R_STAGE + 8192, R_Q = R_K + 8192, R_V = R_Q + 2048, R_ID = R_V + 16384, R_T = R_ID + 512, R_DST = R_T + 512, R_RD = R_DST + 2048, R_BAR = R_RD + 2048, R_TS = R_BAR + 128,
              R_TOTAL = R_TS;
#define TS(i)
#define LOG(i, v)
constexpr int B_KV = R_BAR, B_W = R_BAR + 8, B_X = R_BAR + 80, B_PK = R_BAR + 24, B_C = R_BAR + 32, B_B = R_BAR + 40, B_DUE = R_BAR + 48, B_ONE = R_BAR + 64;
#define DLY_A 150
#define DLY_V 150
#define DLY_C 200
#define NS_B 1120
#define NS_C 1728
#define NS_P 2624
#define NS_V 128
#define NS_F 896
#define NS_K 128
#define NS_M 32
#define NS_X 128
#define MG_Z 0x00010206
#define MG_Y 0x0001051a
#define NS_PEN 1024
__device__ __forceinline__ float rcp(float x) { float r; asm("rcp.approx.ftz.f32 %0, %1;" : "=f"(r) : "f"(x)); return r; }
__device__ __forceinline__ uint32_t hadd2(uint32_t a, uint32_t b) { uint32_t d; asm("add.rn.bf16x2 %0, %1, %2;" : "=r"(d) : "r"(a), "r"(b)); return d; }
__device__ __forceinline__ void mma_a(float (&d)[4], const uint32_t (&a)[4], uint32_t b0, uint32_t b1) { mma16816(d, a[0], a[1], a[2], a[3], b0, b1); }
__device__ __forceinline__ bool elect() {
  uint32_t p; asm volatile("{.reg .pred p; elect.sync _|p, 0xffffffff; selp.u32 %0, 1, 0, p;}" : "=r"(p)); return p; }
__device__ __forceinline__ void tma3d(uint32_t dst, const CUtensorMap* m, int c1, int c2, uint32_t bar) {
  asm volatile("cp.async.bulk.tensor.3d.shared::cluster.global.mbarrier::complete_tx::bytes [%0], [%1, {0, %3, %4}], [%2];"
    :: "r"(dst), "l"(m), "r"(bar), "r"(c1), "r"(c2) : "memory"); }
template <int OFF, int ACC>
__device__ __forceinline__ void wg_rs32(float (&d)[16], const uint32_t (&a)[4], uint32_t db) {
  if (ACC)
    asm volatile("{.reg .b64 db; .reg .b32 lo; add.u32 lo, %20, %21; mov.b64 db, {lo, 0x40000040};\n"
      "wgmma.mma_async.sync.aligned.m64n32k16.f32.bf16.bf16 {%0,%1,%2,%3,%4,%5,%6,%7,%8,%9,%10,%11,%12,%13,%14,%15}, {%16,%17,%18,%19}, db, 1, 1, 1, 0;}"
      : "+f"(d[0]), "+f"(d[1]), "+f"(d[2]), "+f"(d[3]), "+f"(d[4]), "+f"(d[5]), "+f"(d[6]), "+f"(d[7]), "+f"(d[8]), "+f"(d[9]), "+f"(d[10]), "+f"(d[11]), "+f"(d[12]), "+f"(d[13]), "+f"(d[14]), "+f"(d[15])
      : "r"(a[0]), "r"(a[1]), "r"(a[2]), "r"(a[3]), "r"(db), "n"(OFF));
  else
    asm volatile("{.reg .b64 db; .reg .b32 lo; add.u32 lo, %20, %21; mov.b64 db, {lo, 0x40000040};\n"
      "wgmma.mma_async.sync.aligned.m64n32k16.f32.bf16.bf16 {%0,%1,%2,%3,%4,%5,%6,%7,%8,%9,%10,%11,%12,%13,%14,%15}, {%16,%17,%18,%19}, db, 0, 1, 1, 0;}"
      : "=f"(d[0]), "=f"(d[1]), "=f"(d[2]), "=f"(d[3]), "=f"(d[4]), "=f"(d[5]), "=f"(d[6]), "=f"(d[7]), "=f"(d[8]), "=f"(d[9]), "=f"(d[10]), "=f"(d[11]), "=f"(d[12]), "=f"(d[13]), "=f"(d[14]), "=f"(d[15])
      : "r"(a[0]), "r"(a[1]), "r"(a[2]), "r"(a[3]), "r"(db), "n"(OFF));
}
template <int I> using IC = std::integral_constant<int, I>;
template <int I, int N, class F> __device__ __forceinline__ void sfor(F&& f) {
  if constexpr (I < N) { f(std::integral_constant<int, I>{}); sfor<I + 1, N>(f); }
}
__device__ __forceinline__ void keep(float (&d)[16]) {
  asm volatile("" : "+f"(d[0]), "+f"(d[1]), "+f"(d[2]), "+f"(d[3]), "+f"(d[4]), "+f"(d[5]), "+f"(d[6]), "+f"(d[7]),
      "+f"(d[8]), "+f"(d[9]), "+f"(d[10]), "+f"(d[11]), "+f"(d[12]), "+f"(d[13]), "+f"(d[14]), "+f"(d[15]) :: "memory");
}

template <int N, int S2 = 1024> __device__ __forceinline__ void ldx(uint32_t (&v)[N][4], const uint8_t* p) {
#pragma unroll
  for (int k = 0; k < 2 * N; k++) {
    const int i = k;
    asm volatile("ld.relaxed.gpu.global.v2.b32 {%0,%1}, [%2];" : "=r"(v[i >> 1][2 * (i & 1)]), "=r"(v[i >> 1][2 * (i & 1) + 1]) : "l"(p + (i & 3) * 256 + (i >> 2) * S2) : "memory");
  }
}
__device__ __forceinline__ uint32_t dif2(uint32_t a, uint32_t b, uint32_t tag) { uint32_t r; asm("lop3.b32 %0, %1, %2, %3, 0x7e;" : "=r"(r) : "r"(a), "r"(b), "r"(tag)); return r; }
__device__ __forceinline__ uint32_t dif2v(uint32_t a, uint32_t b, uint32_t tag) { uint32_t r; asm volatile("lop3.b32 %0, %1, %2, %3, 0x7e;" : "=r"(r) : "r"(a), "r"(b), "r"(tag)); return r; }
__device__ __forceinline__ uint32_t or3(uint32_t a, uint32_t b, uint32_t c) { uint32_t r; asm("lop3.b32 %0, %1, %2, %3, 0xfe;" : "=r"(r) : "r"(a), "r"(b), "r"(c)); return r; }
__device__ __forceinline__ uint32_t after(uint32_t x, float f, uint32_t z) { uint32_t r; asm("lop3.b32 %0, %1, %2, %3, 0xea;" : "=r"(r) : "r"(__float_as_uint(f)), "r"(z), "r"(x)); return r; }
__device__ __forceinline__ bool any_bit(uint32_t a, uint32_t b, uint32_t m) {
  uint32_t r; asm("lop3.b32 %0, %1, %2, %3, 0xa8;" : "=r"(r) : "r"(a), "r"(b), "r"(m)); return __any_sync(0xffffffffu, r); }
template <int W, int N> __device__ __forceinline__ bool stale(const uint32_t (&v)[N][4], uint32_t tag) {
  uint32_t x = dif2(v[0][0], v[0][2], tag);
  if (N == 4) x = or3(x, dif2(v[1][0], v[1][2], tag), dif2(v[2 % N][0], v[2 % N][2], tag));
  return any_bit(x, dif2(v[N - 1][0], v[N - 1][2], tag), 1);
}
template <int W, int N, int S2 = 1024> __device__ __forceinline__ void retry(uint32_t (&v)[N][4], const uint8_t* p, uint32_t tag, int& it) {
#pragma unroll 1
  do { ldx<N, S2>(v, p); it += INC_A; } while (stale<W>(v, tag) && it < SPIN_LIMIT);
}
__device__ __forceinline__ void mma_h(float (&d)[4], const uint32_t (&a)[4], const uint32_t (&b)[4], int hf) { mma16816(d, a[0], a[1], a[2], a[3], b[2 * hf], b[2 * hf + 1]); }
__device__ __forceinline__ void sts128(uint32_t a, const uint32_t (&r)[4]) { sts128(a, r[0], r[1], r[2], r[3]); }
__device__ __forceinline__ void sts128f(uint32_t a, const float* r) { sts128(a, __float_as_uint(r[0]), __float_as_uint(r[1]), __float_as_uint(r[2]), __float_as_uint(r[3])); }
__device__ __forceinline__ void mbar_spin(uint32_t bar, uint32_t par, int& it) {
  asm volatile("{.reg .pred p; .reg .b32 par; mov.b32 par, %2;\nLOOP: mbarrier.try_wait.parity.shared::cta.b64 p, [%1], par; @p bra.uni DONE;\n"
               "add.s32 %0, %0, 1; setp.le.s32 p, %0, %3; @p bra.uni LOOP;\nDONE: }" : "+r"(it) : "r"(bar), "r"(par), "n"(SPIN_LIMIT) : "memory"); }
__device__ __forceinline__ void warp_arrive(uint32_t bar) {
  __syncwarp(); asm volatile("{.reg .pred p; elect.sync _|p, 0xffffffff; @p mbarrier.arrive.shared::cta.b64 _, [%0];}" :: "r"(bar) : "memory"); }
__device__ __forceinline__ void delay_until(unsigned t) {
  asm volatile("{.reg .pred p; .reg .b64 c; .reg .b32 lo, hi;\nLOOP: mov.u64 c, %%clock64; mov.b64 {lo, hi}, c; sub.s32 lo, lo, %0; setp.lt.s32 p, lo, 0; @p bra.uni LOOP;}" :: "r"(t) : "memory"); }
__device__ __forceinline__ void zero(float (&c)[4][4]) {
#pragma unroll
  for (int i = 0; i < 4; i++) c[i][0] = c[i][1] = c[i][2] = c[i][3] = 0.f;
}

__device__ __forceinline__ void sched() { asm volatile("griddepcontrol.launch_dependents;" ::: "memory"); }
__device__ __forceinline__ const uint8_t* pinp(const uint8_t* p) { return reinterpret_cast<const uint8_t*>(__shfl_xor_sync(0xffffffffu, reinterpret_cast<unsigned long long>(p), 0)); }
__device__ __forceinline__ uint32_t bar_or(int id, uint32_t x) {
  uint32_t r; asm volatile("{.reg .pred p, q; setp.ne.u32 p, %2, 0; bar.red.or.pred q, %1, 256, p; selp.u32 %0, 1, 0, q;}" : "=r"(r) : "r"(id), "r"(x) : "memory"); return r; }
__device__ __forceinline__ void bar_sync_unless(int id, uint32_t x) { asm volatile("{.reg .pred p; setp.eq.u32 p, %1, 0; @p bar.sync %0, 256;}" :: "r"(id), "r"((uint32_t)x) : "memory"); }
__device__ __forceinline__ void bar_arrive_unless(int id, uint32_t x) { asm volatile("{.reg .pred p; setp.eq.u32 p, %1, 0; @p bar.arrive %0, 256;}" :: "r"(id), "r"((uint32_t)x) : "memory"); }
__device__ __forceinline__ void stsm2t(uint32_t a, uint32_t r0, uint32_t r1, uint32_t x) {
  asm volatile("{.reg .pred p; setp.eq.u32 p, %3, 0; @p stmatrix.sync.aligned.m8n8.x2.trans.shared.b16 [%0], {%1,%2};}" :: "r"(a), "r"(r0), "r"(r1), "r"((uint32_t)x) : "memory"); }
__device__ __forceinline__ uint32_t or_and(uint32_t a, uint32_t b, uint32_t m) { uint32_t r; asm("lop3.b32 %0, %1, %2, %3, 0xa8;" : "=r"(r) : "r"(a), "r"(b), "r"(m)); return r; }
#define rare(x) __builtin_expect(!!(x), 0)
__device__ __forceinline__ uint32_t gtime() { unsigned long long g; asm volatile("mov.u64 %0, %%globaltimer;" : "=l"(g) :: "memory"); return (uint32_t)g; }
__device__ __forceinline__ void wait_time(uint32_t t) {
  asm volatile("{.reg .pred p; .reg .b32 g; .reg .b64 c;\nLOOP: mov.u64 c, %%globaltimer; cvt.u32.u64 g, c; sub.s32 g, %0, g; setp.lt.u32 p, g, 16384; @p bra.uni LOOP;}" :: "r"(t - 1) : "memory"); }
__device__ __forceinline__ uint32_t ldx32(const void* p) { uint32_t v; asm volatile("ld.relaxed.gpu.global.b32 %0, [%1];" : "=r"(v) : "l"(p) : "memory"); return v; }
__device__ __forceinline__ void stx32(const void* p, uint32_t v) { asm volatile("st.relaxed.gpu.global.b32 [%0], %1;" :: "l"(p), "r"(v) : "memory"); }

__global__ void __launch_bounds__(256, 1)
rec_kernel(const __grid_constant__ RecMaps maps, const bf16* __restrict__ xin, const bf16* __restrict__ mem0, Xchg* const gx,
           const bf16* __restrict__ fx, const bf16* __restrict__ wr, const bf16* __restrict__ wi) {
  extern __shared__ __align__(1024) uint8_t smem_raw[];
  const uint32_t sb = smem_u32(smem_raw);
  int role = blockIdx.x;
  {
    uint32_t smid, nsm; asm volatile("mov.u32 %0, %%smid;" : "=r"(smid)); asm volatile("mov.u32 %0, %%nsmid;" : "=r"(nsm));
    const int p = smid >> 1, u = p - 32;
    if (nsm == gridDim.x)
      role = (smid & 1) + (p < 32 ? 4 * ((p & 7) + 8 * (p >> 4)) + 2 * ((p >> 3) & 1) : p < 60 ? 4 * (16 + u % 7 + 7 * (u / 14)) + 2 * ((u / 7) & 1)
                         : p < 62 ? 2 * p + 8 : 2 * p - 4);
    role = uni(role);
  }
  if (role >= 128) {
    fft_cols(sb, role - 128, 4, [&]() { grid_wait(&gx->ctr[33], 128); });
    __threadfence(); __syncwarp();
    if ((threadIdx.x & 31) == 0) atomicAdd(&gx->ctr[32], 1u);
    __syncwarp();
    fft_rows_inv(&maps.fo, sb, role - 128, 4, [&]() { grid_wait(&gx->ctr[32], 32); });
    return;
  }
  const int tid = threadIdx.x, warp = uni(tid >> 5), lane = tid & 31, wg = warp >> 2, w4 = warp & 3, g = lane >> 2, t = lane & 3;
  const int h = role >> 2, j = role & 3, jh = j & 1;
  uint32_t w[48][4];
  float aq[16], av[16];
  int it = 0;

#define PT(k)
  auto pf_wo = [&]() {
    for (int i = 0; i < 4; i++)
      asm volatile("cp.async.bulk.prefetch.tensor.2d.L2.global [%0, {%1, %2}];" :: "l"(&maps.wo), "r"(256 * j + 64 * i), "r"(h * DH) : "memory");
  };
  fft_rows_fwd(fx, wr, wi, sb + R_MEM + 49152, role, [&]() {
    if (tid == 224) {
      mbar_init(sb + B_KV, 1); mbar_init(sb + B_W, 1); mbar_init(sb + B_X, 1); mbar_init(sb + B_X + 8, 1); mbar_init(sb + B_X + 16, 1); mbar_init(sb + B_X + 24, 1); mbar_init(sb + B_C, 4); mbar_init(sb + B_PK, 4); mbar_init(sb + B_B, 1);
      asm volatile("fence.mbarrier_init.release.cluster;" ::: "memory");
      mbar_expect_tx(sb + B_W, 3 * 65536);
      for (int i = 0; i < 4; i++) {
        tma2d(sb + R_X + i * 16384, &maps.wq, h * DH + 32 * j, i * 256, sb + B_W);
        if (i < 3) tma2d(sb + R_MEM + i * 16384, &maps.wk, h * DH + 32 * j, i * 256, sb + B_W);
        else asm volatile("cp.async.bulk.prefetch.tensor.2d.L2.global [%0, {%1, %2}];" :: "l"(&maps.wk), "r"(h * DH + 32 * j), "r"(768) : "memory");
      }
      for (int i = 0; i < 2; i++) tma2d(sb + R_WO + i * 32768, &maps.wv, h * DH + 64 * (j >> 1), jh * 512 + i * 256, sb + B_W);
      if (PFD) asm volatile("cp.async.bulk.prefetch.L2.global [%0], 2048;" :: "l"(xin + role * DM) : "memory");
      else for (int i = 0; i < 4; i++) asm volatile("cp.async.bulk.prefetch.L2.global [%0], 8192;" :: "l"(xin + role * 16384 + i * 4096) : "memory");
      if (WOP == 0) pf_wo();
      for (int i = 0; i < 5; i++) asm volatile("prefetch.tensormap [%0];" :: "l"(&maps.wo + i) : "memory");
    }
    __syncwarp();
  });
  if (tid < 16) sts32(sb + R_T + tid * 4, ~0u);
  fence_async();
  PT(0);
  grid_arrive(&gx->ctr[33]);
  PT(1);
  if (tid == 224) { tma2d(sb + R_MEM + 49152, &maps.wk, h * DH + 32 * j, 768, sb + B_W); if (WOP == 1) pf_wo(); }
  __syncwarp();
  uint8_t* const xb = reinterpret_cast<uint8_t*>(gx);
  auto probe_at = [&](int n) { return xb + (n ? offsetof(Xchg, C) + w4 * 8192 + role * 32 : offsetof(Xchg, B) + role * 8192 + warp * 128); };
  if (lane < 8) stx128(probe_at(lane >> 2) + (lane & 2) * 2048 + (lane & 1) * 16, 0, 0, 0, 0);
  uint32_t m0[4][4];
#pragma unroll
  for (int i = 0; i < 16; i++) m0[i >> 2][i & 3] = ldnc32(mem0 + g * DM + 128 * warp + 8 * i + 2 * t);
  mbar_spin(sb + B_W, 0, it);
  PT(2);
  const int lrow = (lane & 7) + ((lane >> 4) << 3), lhi = (lane >> 3) & 1;
  const int kq = wg ? 3 - 3 * jh : 3 * jh;
  const uint32_t LW = lrow * 128 + ((lhi ^ (lane & 7)) << 4);
  {
    const int chunk = w4 < 2 ? w4 + 2 * lhi : 2 * (w4 & 1) + lhi;
    uint32_t a = sb + (w4 < 2 ? R_X : R_MEM) + kq * 16384 + lrow * 64 + ((chunk ^ ((lrow >> 1) & 3)) << 4);
#pragma unroll
    for (int i = 0; i < 16; i++) ldsm4t(w[i], a + i * 1024);
    const uint32_t st = wg ? 1024 : 2048, av0 = sb + R_WO + (LW ^ (w4 << 5));
    const uint32_t a1 = wg ? a + (2 * jh - 1) * 16384 : av0 + jh * 32768, a2 = wg ? a + (2 * jh - 1) * 32768 : av0 + (1 - jh) * 32768;
#pragma unroll
    for (int i = 0; i < 16; i++) { ldsm4t(w[16 + i], a1 + i * st); ldsm4t(w[32 + i], a2 + i * st); }
  }
  uint32_t L16 = pin(lane * 16);
  const uint32_t uW = uni(sb + w4 * 512), uWo = uni(sb + R_WO + w4 * 16384), uMem = uni(sb + R_MEM + kq * 4096);
  const uint32_t dX = uni(((sb + R_X + kq * 16384) >> 4) | 0x10000u);
  auto load_wo = [&](uint32_t (&d)[32][4], int i0, int i1) {
#pragma unroll
    for (int i = i0; i < i1; i++) lds128(d[i], uWo + L16 + (i & 1) * 512 + (i >> 4) * 1024 + (i & 14) * 1024);
  };
  auto issue_x = [&](int n, int k) {
    const uint32_t bar = sb + B_X + 8 * k, q = k ^ (3 - 3 * jh);
    mbar_expect_tx(bar, 16384); tma3d(sb + R_X + q * 16384, &maps.x, min(n, NSEG - 1) * SEG, 4 * q, bar);
  };
  auto store_stage = [&](int n) {
    asm volatile("cp.async.bulk.global.shared::cta.bulk_group [%0], [%1], 8192; cp.async.bulk.commit_group;"
                 :: "l"(g_kqv[n & 3][role]), "r"(sb + R_STAGE) : "memory");
  };
  auto issue_kqv = [&](int n) {
    const int p = (n & 3) * 128 + 4 * h;
    mbar_expect_tx(sb + B_KV, 26624);
    tma3d(sb + R_K, &maps.k, 0, p, sb + B_KV); tma3d(sb + R_Q, &maps.q, 8 + 2 * j, p, sb + B_KV); tma3d(sb + R_V, &maps.v, 16, p, sb + B_KV);
  };
  auto fetch4k = [&](uint32_t dst, uint32_t off, uint32_t bar, uint32_t t) {
    asm volatile("{.reg .pred p, q; .reg .b32 g; .reg .b64 c; elect.sync _|q, 0xffffffff; @q mbarrier.arrive.expect_tx.shared::cta.b64 _, [%2], 4096;\n"
                 "LOOP: mov.u64 c, %%globaltimer; cvt.u32.u64 g, c; sub.s32 g, %3, g; setp.lt.u32 p, g, 16384; @p bra.uni LOOP;\n"
                 "@q cp.async.bulk.shared::cluster.global.mbarrier::complete_tx::bytes [%0], [%1], 4096, [%2];}" :: "r"(dst), "l"(xb + off), "r"(bar), "r"(t - 1) : "memory");
  };
  uint32_t uS;
  auto my_b = [&]() { return offsetof(Xchg, B) + role * 8192 + ((uS + ((uint32_t)it >> 31)) & 1) * 4096; };
  auto issue_c = [&](uint32_t t) { fetch4k(sb + R_MEM + w4 * 4096, offsetof(Xchg, C) + w4 * 8192 + ((uS + ((uint32_t)it >> 31)) & 4096), sb + B_C, t); };
  auto wait_x = [&](int n, int i) { if (!(EXP & 1) || n < 2) mbar_spin(sb + B_X + 8 * i, n & 1, it); };
#define PACED(d0) uint32_t dz = d0; const uint32_t z = (uint32_t)it >> 31; auto pace = [&]() { for (int k = 0; k < PACE; k++) { if (k & 1) asm("add.u32 %0, %0, %1;" : "+r"(dz) : "r"(z)); else asm("xor.b32 %0, %0, %1;" : "+r"(dz) : "r"(z)); } };
  auto project_v = [&](auto I0, auto I1, auto&& mid) {
    PACED(decltype(I0)::value < 16 ? dX : dX ^ 1024);
    wg_fence();
    sfor<decltype(I0)::value, decltype(I1)::value>([&](auto I) {
      constexpr int i = decltype(I)::value;
      mid(i);
      if (i == 16 && decltype(I0)::value < 16) dz ^= 1024;
      wg_rs32<((i >> 2) & 3) * 256 + (i & 3) * 2, (i > 0)>(av, w[16 + i], dz);
      pace();
    });
    wg_commit();
  };
  auto project_qk = [&](auto I0, auto I1, auto first, auto&& mid) {
    PACED((dX ^ (decltype(I0)::value >> 4 << 10)) + ((uint32_t)it >> 31));
    wg_fence();
    sfor<decltype(I0)::value, decltype(I1)::value>([&](auto I) {
      constexpr int i = decltype(I)::value;
      mid(i);
      wg_rs32<((i >> 2) & 3) * 256 + (i & 3) * 2, !decltype(first)::value || i != decltype(I0)::value>(aq, w[i], dz);
      pace();
    });
    wg_commit();
  };
  const uint32_t uP = uni(sb + R_X + 3 * jh * 16384 + w4 * 512);
  auto park = [&]() {
    bar_sync(1, 128);
#pragma unroll
    for (int i = 0; i < 4; i++) sts128f(uP + L16 + i * 2048, aq + 4 * i);
    warp_arrive(sb + B_PK);
  };
  auto unpark = [&]() {
#pragma unroll
    for (int i = 0; i < 4; i++) {
      const float4 p = lds128f(uP + L16 + i * 2048);
      av[4 * i] = p.x; av[4 * i + 1] = p.y; av[4 * i + 2] = p.z; av[4 * i + 3] = p.w;
    }
  };
  auto fin_qk = [&]() {
#pragma unroll
    for (int i = 0; i < 16; i++) aq[i] += av[i];
    const uint32_t a = sb + R_STAGE + (w4 < 2 ? 2048 + w4 * 128 : (w4 & 1) * 256) + (L16 & 112) + (L16 >> 7) * 512;
    stsm4t(a, pack2(aq[0], aq[1]), pack2(aq[4], aq[5]), pack2(aq[8], aq[9]), pack2(aq[12], aq[13]));
    stsm4t(a + (w4 < 2 ? 256 : 128), pack2(aq[2], aq[3]), pack2(aq[6], aq[7]), pack2(aq[10], aq[11]), pack2(aq[14], aq[15]));
  };
  auto fin_v = [&]() {
#pragma unroll
    for (int a = 0; a < 2; a++)
      sts128(sb + R_STAGE + 4096 + w4 * 1024 + a * 512 + L16, pack2(av[8 * a], av[8 * a + 1]), pack2(av[8 * a + 2], av[8 * a + 3]),
             pack2(av[8 * a + 4], av[8 * a + 5]), pack2(av[8 * a + 6], av[8 * a + 7]));
  };
  __syncthreads();
  if (tid == 224) {
#pragma unroll 1
    for (int i = 0; i < 4; i++) issue_x(0, i);
    mbar_expect_tx(sb + B_W, 65536);
    for (int i = 0; i < 4; i++) tma2d(sb + R_WO + i * 16384, &maps.wo, 256 * j + 64 * i, h * DH, sb + B_W);
  }
  __syncwarp();
  if (wg) {
#pragma unroll
    for (int i = 0; i < NSW; i++) sts128(uW + R_WC + L16 + i * 2048, w[i]);
  }
#pragma unroll
  for (int i = 0; i < 4; i++) sts128(sb + R_MEM + warp * 2048 + i * 512 + (g >> 1) * 128 + t * 32 + (g & 1) * 16, m0[i]);
  auto probe = [&](int n, int cnt) {
    if (lane == 0) {
#pragma unroll 1
      for (int i = role >> 7; i < cnt; i++) {
        const int k = (i ^ wg) & 1;
        const unsigned t0 = clk();
        uint32_t v; asm volatile("atom.relaxed.gpu.global.exch.b32 %0, [%1], 0;" : "=r"(v) : "l"(probe_at(n) + k * 4096) : "memory");
        if (v == 0) asm volatile("red.shared.min.u32 [%0], %1;" :: "r"(sb + R_T + (n ? w4 * 8 : 32) + k * 4), "r"(clk() - t0) : "memory");
      }
    }
    __syncwarp();
  };
#pragma unroll 1
  for (int n = 0; n < 2; n++) {
    probe(0, n ? NPB : NPB0);
    asm volatile("{.reg .pred p; cp.async.bulk.wait_group 0; setp.eq.u32 p, %1, 97; @p red.relaxed.gpu.global.add.u32 [%0], 1;}" :: "l"(&gx->ctr[h]), "r"(tid ^ n ^ (1 - n) << 9) : "memory");
    PT(3 + 3 * n);
    wait_x(n, 2);
    PT(4 + 3 * n);
    if (wg == 0) {
      wait_x(n, 3);
      project_qk(IC<0>{}, IC<16>{}, IC<1>{}, [](int) {});
      project_v(IC<0>{}, IC<32>{}, [](int) {});
      wg_wait<0>(); keep(aq); keep(av);
      park();
      fin_v();
      fence_async();
    } else {
      wait_x(n, 0); wait_x(n, 1);
      project_qk(IC<32>{}, IC<48>{}, IC<1>{}, [](int) {});
      project_qk(IC<16>{}, IC<32>{}, IC<0>{}, [](int) {});
      project_qk(IC<0>{}, IC<16>{}, IC<0>{}, [](int) {});
      mbar_spin(sb + B_PK, n, it);
      unpark();
      wg_wait<0>(); keep(aq);
      fin_qk();
      fence_async();
    }
    __syncthreads();
    if (tid == 0 && n) stx32(&gx->S[role], 1 + (HOME & 2 && lds32(sb + R_T + 36) < lds32(sb + R_T + 32)));
    PT(5 + 3 * n);
    if (tid == 96 && n == 0) store_stage(0);
    if (tid == 128 && n == 0) {
#pragma unroll 1
      for (int i = 0; i < 4; i++) issue_x(1, i);
    }
    if (warp == 5 && n == 1) {
#pragma unroll 1
      while (__any_sync(0xffffffffu, ldx32(&gx->ctr[h]) < 4) && ++it < SPIN_LIMIT) {}
      if (elect()) issue_kqv(0);
    }
    __syncwarp();
  }
  mbar_spin(sb + B_W, 1, it);
  PT(9);
#pragma unroll
  for (int i = 0; i < 4; i++) {
    uint32_t f[4][4];
    const uint32_t a = sb + R_WO + warp * 8192 + i * 2048;
#pragma unroll
    for (int q = 0; q < 4; q++) ldsm4t(f[q], a + (LW ^ (q << 5)));
    __syncwarp();
#pragma unroll
    for (int q = 0; q < 4; q++) sts128(a + q * 512 + L16, f[q]);
  }
  if (NPC) probe(1, NPC);
  {
    const int o = 32 * w4 + 16 * wg + 4 * t + j;
    uint32_t v;
#pragma unroll 1
    while (__any_sync(0xffffffffu, (v = ldx32(&gx->S[o])) == 0) && ++it < SPIN_LIMIT) {}
    asm volatile("st.shared.u64 [%0], %1;" :: "r"(sb + R_DST + wg * 1024 + w4 * 256 + lane * 8), "l"(xb + offsetof(Xchg, B) + o * 8192 + (v >> 1) * 4096 + h * 128 + ((g ^ h) & 7) * 16) : "memory");
  }
  if (wg == 0) {
    const uint64_t cd = reinterpret_cast<uint64_t>(xb + (offsetof(Xchg, C) + j * 8192 + h * 128 + w4 * 32 + (L16 & 16) * 256 + (L16 & 64) / 4 + (L16 >> 7) * 4));
    sts128(uW + R_RD + L16, (uint32_t)cd, (uint32_t)(cd >> 32), sb + R_MEM + (L16 & 112) * 8 + (L16 >> 8) * 1024 + ((w4 * 32 + ((L16 >> 3) & 16)) ^ (L16 & 112)),
           (L16 >> 6) == (h & 3) * 2 + ((h >> 2) & 1) ? 0xFFFE0000u : 0xFFFFFFFFu);
  }
  if (tid == 0) sts32(sb + B_DUE + 8, gtime() & ~31u);
  PT(10);
  mbar_spin(sb + B_KV, 0, it);
  PT(11);
  if (tid < 4) sts32(sb + B_ONE + tid * 4, 0x3F803F80u);
  if (warp == 1) { const uint32_t e = g >> 1 == t ? 0x3F80u << (16 * (g & 1)) : 0u; sts128(sb + R_ID + L16, e, 0, 0, e); }
  __syncthreads();
  {
    const uint32_t kb = lds32(sb + R_T + 36) < lds32(sb + R_T + 32);
    uS = uni((HOME & 4 ? (__popc(((offsetof(Xchg, B) / 4096 + 2 * role) ^ (offsetof(Xchg, C) / 4096 + 2 * w4)) & 0xb3) ^ kb) & 1 : lds32(sb + R_T + w4 * 8 + 4) < lds32(sb + R_T + w4 * 8)) * 4096 + kb);
  }

  const float sc = 0.08838834764831845f * 1.4426950408889634f;
  uint8_t* const xa = xb + uni(h * 16384);
  const uint32_t uA = uni(wg ? (w4 >> 1) * 2048 + j * 512 + (w4 & 1) * 256 : 8192 + (4 * (j >> 1) + w4) * 512 + jh * 256);
  const uint32_t uP2 = uni(sb + R_P + w4 * 256);
  uint32_t nc = 1;
  uint32_t ma;
  const uint8_t* adst;
  auto pin_mem = [&]() { adst = pinp(xa + uA + L16 / 2); ma = pin(uMem + (L16 & 384) + (L16 & 48) * 2 + (L16 & 64) / 4); };
  pin_mem();

#pragma unroll 1
  for (int s = 0;; nc++) {
    const uint32_t tag = (s + 1) & 1;
    auto fresh = [&]() { L16 += (uint32_t)it >> 31; };
    auto get_due = [&]() { return lds32(sb + B_DUE + 4 + tag * 4); };
    float c[4][4], r4[4];
    auto fold = [&]() {
#pragma unroll
      for (int i = 0; i < 4; i++) r4[i] = ((c[0][i] + c[1][i]) + c[2][i]) + c[3][i];
    };
    auto mma4 = [&](int n, const uint32_t (&b0)[4], const uint32_t (&b1)[4]) {
      mma_h(c[0], w[n + 2], b1, 0); mma_h(c[1], w[n + 3], b1, 1); mma_h(c[2], w[n], b0, 0); mma_h(c[3], w[n + 1], b0, 1);
    };
    auto xpos = [&](int pos, int wp) {
      if ((pos == X0 || pos == X1 || pos == X2 || pos == X3) && warp == wp && s + 1 < NSEG && elect()) {
        const int z = (uint32_t)it >> 31;
        if (pos == X2) issue_x(s + 2, 2 + z);
        if (pos == X3) issue_x(s + 2, 3 + z);
        if (pos == X1) issue_x(s + 2, 1 + z);
        if (pos == X0) issue_x(s + 2, z);
      }
      __syncwarp();
    };
    if (wg == 0) {
      mbar_spin(sb + B_C, nc & 1, it);
      TS(13);
      uint32_t b[16][4], tg[4];
#pragma unroll
      for (int i = 0; i < PD0; i++) { lds128(b[i], ma + i * 512); __syncwarp(); }
      sched();
      zero(c);
#pragma unroll
      for (int i = 0; i < 8; i++) {
        const int k = i ^ 1;
        mma_h(c[0], w[2 * k], b[k], 0); mma_h(c[1], w[2 * k + 1], b[k], 1);
        if (i < 2 * NV0) { mma_h(c[2], w[16 + 2 * k], b[k], 0); mma_h(c[3], w[17 + 2 * k], b[k], 1); }
        sched();
        if ((i & 1) && i + PD0 < 9) { lds128(b[i + PD0 - 1], ma + (i + PD0 - 1) * 512); __syncwarp(); lds128(b[i + PD0], ma + (i + PD0) * 512); sched(); }
        if (i == TGP) {
          fresh();
#pragma unroll
          for (int k = 0; k < 4; k++) tg[k] = lds32((uW * 4 + L16) * 2 + (L16 >> 6) * 4 + (R_MEM + k * 1024 - 7 * sb));
          sched();
        }
      }
#pragma unroll
      for (int i = 0; i < 4; i++) { r4[i] = c[0][i] + c[1][i]; c[0][i] = c[1][i] = 0.f; }
      sts128f(uW + R_RED + L16, r4);
      TS(1);
      const uint32_t old = bar_or(4, (dif2(tg[0], tg[1], s) | dif2(tg[2], tg[3], s)) & (s > 0));
      TS(0);
#pragma unroll
      for (int i = 0; i < 2 * NV0; i++) { lds128(b[8 + i], (ma ^ 4096) + i * 512); __syncwarp(); }
      sched();
#pragma unroll
      for (int i = NV0; i < 8; i++) {
        if (VB && i == VB) bar_sync(7, 256);
        mma4(16 + 4 * i, b[2 * i], b[2 * i + 1]);
        if (i < 7) sched();
        if (i < 4) { lds128(b[8 + 2 * i], (ma ^ 4096) + i * 1024); __syncwarp(); lds128(b[9 + 2 * i], (ma ^ 4096) + i * 1024 + 512); sched(); }
      }
      fold();
      asm volatile("{.reg .pred p; setp.eq.u32 p, %3, 0; @p st.relaxed.gpu.global.v2.b32 [%0], {%1,%2};}" :: "l"(adst), "r"((pack2(r4[0], r4[1]) & ~1u) | tag), "r"(pack2(r4[2], r4[3])), "r"(old) : "memory");
      sched();
      const unsigned tpub = clk();
      if (__any_sync(0xffffffffu, old) && nc < NC_MAX) {
        bar_sync(3, 256);
        issue_c(gtime());
        continue;
      }
      TS(3);
      xpos(0, 0);
      const uint32_t due = get_due();
      uint32_t vf[4][4], vm[2][4], p[4], pm, o[4];
      const uint32_t va = sb + R_V + (w4 >> 1) * 8192 + (w4 & 1) * 2048 + L16;
#pragma unroll
      for (int i = 0; i < 4; i++) {
        uint32_t q[4]; lds128(vf[i], va + i * 512); lds128(q, va + 4096 + i * 512);
#pragma unroll
        for (int e = 0; e < 4; e++) vf[i][e] = hadd2(vf[i][e], q[e]);
      }
      const uint32_t pa = pin(sb + R_P + (L16 >> 1));
      const uint8_t* vsrc = pinp(xa + 8192 + w4 * 1024 + L16 / 2);
      uint32_t one[4];
      lds128(one, sb + B_ONE);
      auto pv_x = [&]() {
        zero(c);
        mma_a(c[2], one, p[0], p[1]);
        mma_a(c[0], vf[0], p[0], p[1]); mma_a(c[1], vf[2], p[0], p[1]);
        sched();
        mma_a(c[2], one, p[2], p[3]);
        mma_a(c[0], vf[1], p[2], p[3]); mma_a(c[1], vf[3], p[2], p[3]);
        sched();
      };
      auto pv_m = [&]() {
        mma1688(c[2], one[0], one[1], pm);
        mma_a(c[0], vm[0], pm, pm);
        sched();
        mma_a(c[1], vm[1], pm, pm);
      };
      auto norm = [&]() {
        const float n0 = rcp(c[2][0]), n1 = rcp(c[2][1]);
#pragma unroll
        for (int i = 0; i < 4; i++) o[i] = pack2(c[i >> 1][2 * (i & 1)] * n0, c[i >> 1][2 * (i & 1) + 1] * n1);
        return ((__float_as_uint(c[2][0]) - 0x1F800000u) | (__float_as_uint(c[2][1]) - 0x1F800000u)) >> 30;
      };
      auto load_m = [&](int x) { const float2 e0 = lds64f(pa + 512 + x * 1024), e1 = lds64f(pa + 768 + x * 1024); pm = pack2(e0.x * e1.x, e0.y * e1.y); };
      auto attend_max = [&](int x) {
        float2 sv[6];
#pragma unroll
        for (int i = 0; i < 6; i++) sv[i] = lds64f(pa - 3072 + x * 1536 + i * 256);
        sv[4].x += sv[5].x; sv[4].y += sv[5].y;
        const int dq = (int)(L16 >> 6) - (int)((L16 >> 3) & 6) + 8 * j;
        float m = fmaxf(sv[4].x, sv[4].y);
#pragma unroll
        for (int i = 0; i < 4; i++) {
          if (x && 8 * i > dq) sv[i].x = -INFINITY;
          if (x && 8 * i + 1 > dq) sv[i].y = -INFINITY;
          m = fmaxf(m, fmaxf(sv[i].x, sv[i].y));
        }
        m = fmaxf(m, __shfl_xor_sync(0xffffffffu, m, 1));
        m = fmaxf(m, __shfl_xor_sync(0xffffffffu, m, 2));
#pragma unroll
        for (int i = 0; i < 5; i++) (i < 4 ? p[i] : pm) = pack2(ex2(sv[i].x - m), ex2(sv[i].y - m));
        pv_x(); pv_m(); norm();
      };
      uint32_t tq[4];
      auto get_t = [&]() {
        tq[0] = tq[1] = tq[2] = tq[3] = 0;
        asm volatile("{.reg .pred p; setp.eq.u32 p, %5, 0; @p ld.relaxed.gpu.global.v4.b32 {%0,%1,%2,%3}, [%4];}"
                     : "+r"(tq[0]), "+r"(tq[1]), "+r"(tq[2]), "+r"(tq[3]) : "l"(xb + offsetof(Xchg, T) + L16 * 8), "r"(warp) : "memory");
      };
      delay_until(tpub + DLY_V);
      wait_time(due + NS_V);
      TS(4);
      ldx(vm, vsrc);
      sched();
      xpos(2, 2);
      auto store_kqv = [&]() {
        fence_async();
        if (!(EXP & 4))
          asm volatile("{.reg .pred p; elect.sync _|p, 0xffffffff; @p cp.async.bulk.global.shared::cta.bulk_group [%0], [%1], 2048; cp.async.bulk.commit_group;}"
                       :: "l"(g_kqv[(s + 1) & 3][role] + w4 * 128), "r"(sb + R_STAGE + w4 * 2048) : "memory");
      };
      if (SPOS == 2) store_kqv();
      sched();
      bar_sync(5, 256);
      ldsm4(p, sb + R_P + L16);
      load_m(0);
      pv_x();
      ldsm4(p, sb + R_P + 1024 + L16);
      pv_m();
      const uint32_t r = norm(), tl = after(tag, c[2][0], (uint32_t)it >> 31);
      const bool redo = __any_sync(0xffffffffu, r | ((dif2(vm[0][0], vm[0][2], tl) | dif2(vm[1][0], vm[1][2], tl)) & 1));
      TS(6);
      stsm4t(uW + R_O + L16, o[0], o[1], o[2], o[3]);
      bar_arrive_unless(6, redo);
      sched();
      if (TQL == 7) get_t();
      TS(7);
      pv_x();
      if (rare(redo)) retry<2>(vm, vsrc, tag, it);
      bar_sync(8, 256);
      load_m(1);
      pv_m();
      if (rare(__any_sync(0xffffffffu, norm()) || redo)) {
        fresh();
#pragma unroll 1
        for (int x = !redo; x < 2; x++) {
          attend_max(x);
          if (x == 0) { stsm4t(uW + R_O + L16, o[0], o[1], o[2], o[3]); bar_arrive(6, 256); }
        }
      }
      TS(8);
      if (TQL == 8) get_t();
      const bool xok = mbar_test(sb + B_X + 16, s & 1) & mbar_test(sb + B_X + 24, s & 1);
      xpos(4, 2);
      fresh();
      const uint32_t ob = uni(sb + R_MEM + 4096 + w4 * 1024);
      stsm4t(ob + (L16 & 112) * 4 + (((L16 >> 3) ^ (L16 >> 1)) & 48), o[0], o[1], o[2], o[3]);
      __syncwarp();
      uint32_t rd[4];
      lds128(rd, uW + R_RD + L16);
      lds128(o, ob + (L16 ^ ((L16 >> 3) & 48)));
      auto put_o = [&]() {
        *reinterpret_cast<uint4*>(reinterpret_cast<uint8_t*>(g_ox) + (((s * SEG + 8 * j) * HD + h * DH + 32 * w4) * 2 + (L16 >> 6) * (HD * 2) + (L16 & 48))) = make_uint4(o[0], o[1], o[2], o[3]);
      };
      if (s + 1 == NSEG) { put_o(); asm volatile("cp.async.bulk.wait_group 0;" ::: "memory"); break; }
      asm volatile("cp.async.bulk.wait_group 0;" ::: "memory");
      if (elect()) stx32(xa + 4096 + j * 16 + w4 * 4, s + 1);
      __syncwarp();
      if (rare(!xok)) { wait_x(s + 2, 3); wait_x(s + 2, 2); }
      TS(9);
      fresh();
      const uint32_t e = due | ((s + 1) & 31);
      project_qk(IC<0>{}, IC<NQ>{}, IC<1>{}, [&](int n) {
        if (n == OXPOS) { __syncwarp(); put_o(); __syncwarp(); }
        if (n == TQP) { __syncwarp(); tq[0] = dif2v(tq[0], tq[1], e) | dif2v(tq[2], tq[3], e); __syncwarp(); }
      });
      if (NPA) project_v(IC<0>{}, IC<NPA>{}, [](int) {});
      TS(2);
      if (warp == 0) {
        uint32_t last = due, nx = NS_P;
        if (rare(__any_sync(0xffffffffu, tq[0]))) {
          const uint32_t ref = gtime();
#pragma unroll 1
          do ldx128(o, xb + offsetof(Xchg, T) + L16 * 8); while (any_bit(or3(o[0] - s - 1, o[1] - s - 1, o[2] - s - 1), o[3] - s - 1, 30) && ++it < SPIN_LIMIT);
          const int d = max(max((int)(o[0] - ref), (int)(o[1] - ref)), max((int)(o[2] - ref), (int)(o[3] - ref)));
          last = (ref + __reduce_max_sync(0xffffffffu, d)) & ~31u;
          if (last != due) nx += NS_X;
        }
        const uint32_t bdue = last + NS_B;
        if (s < 4) { last += (MG_Y >> 8 * s & 255) * 32; nx += (MG_Z >> 8 * s & 255) * 32; }
        sts32(sb + B_DUE, last);
        sts32(sb + B_DUE + 8 - tag * 4, last + nx);
        fetch4k(sb + R_MEM, my_b(), sb + B_B, bdue);
        LOG(13, tl - last);
        LOG(9, last);
      }
      if (NQ < 16) project_qk(IC<NQ>{}, IC<16>{}, IC<0>{}, [](int) {});
      project_v(IC<NPA>{}, IC<NPRE>{}, [](int) {});
      const uint32_t ba = rd[2], msk = rd[3];
      const uint8_t* cdst = reinterpret_cast<const uint8_t*>(rd[0] | (uint64_t)rd[1] << 32);
      TS(14);
      mbar_spin(sb + B_B, s & 1, it);
      TS(10);
      uint32_t bq[2][4];
      auto sum_b = [&]() {
        ldsm4t(bq[0], ba); ldsm4t(bq[1], ba + 2048);
        sched();
#pragma unroll
        for (int i = 0; i < 8; i++) c[i >> 2][i & 3] = 0.f;
        mma_a(c[0], bq[0], 0x3F803F80u, 0x3F803F80u); mma_a(c[1], bq[1], 0x3F803F80u, 0x3F803F80u);
        const uint32_t t2 = tag * 0x10001u;
        const bool old = any_bit(or3(dif2(bq[0][0], bq[0][1], t2), dif2(bq[0][2], bq[0][3], t2), dif2(bq[1][0], bq[1][1], t2)), dif2(bq[1][2], bq[1][3], t2), L16 < 64 ? 0x10001u : 0u);
        const uint32_t T = (tag << 16) & ~msk, u = ((__float_as_uint(c[0][0] + c[1][0]) + ((0x10000u & ~msk) - T)) & msk) | T;
        asm volatile("{.reg .pred p; setp.eq.u32 p, %2, 0; @p st.relaxed.gpu.global.b32 [%0], %1;}"
                     :: "l"(cdst), "r"(pack2(__uint_as_float(u), c[0][2] + c[1][2])), "r"((uint32_t)(old || (L16 & 32))) : "memory");
        return old;
      };
      if (rare(sum_b())) {
#pragma unroll 1
        do {
          const uint8_t* p = xb + (my_b() + (ba - sb - R_MEM));
          ldx128(bq[0], p); ldx128(bq[1], p + 2048);
          sts128(ba, bq[0]); sts128(ba + 2048, bq[1]);
          __syncwarp();
          it += INC_B;
        } while (sum_b() && it < SPIN_LIMIT);
      }
      sched();
      TS(11);
      bar_arrive(0, 256);
      const unsigned tc = clk();
      const uint32_t cdue = lds32(sb + B_DUE) + NS_C;
      if (warp == 3) LOG(11, gtime() - cdue);
      fresh();
      wg_wait<0>(); keep(aq); keep(av);
      park();
      if (NPRE < 32) project_v(IC<NPRE>{}, IC<32>{}, [](int) {}); else fin_v();
      TS(12);
      delay_until(tc + DLY_C);
      issue_c(cdue);
      TS(5);
      LOG(warp, it);
      pin_mem();
      if (NPRE < 32) { wg_wait<0>(); keep(av); fin_v(); }
      if (!(EXP & 2)) mbar_spin(sb + B_KV, tag, it);
      TS(15);
    } else {
      uint32_t kf[8][4];
      auto load_k = [&]() {
        const uint32_t ka = sb + R_K + w4 * 1024 + (L16 & 112) + (L16 & 128) * 4 + (L16 & 256);
#pragma unroll
        for (int i = 0; i < 8; i++) ldsm4(kf[i], ka + (i >> 1) * 2048 + (i & 1) * 128);
      };
      auto put_p = [&](int x, uint32_t old, uint32_t again) {
        float e[4];
        const int dq = (int)((L16 >> 3) & 6) + 8 * j - (int)(L16 >> 6) - 16 * w4;
#pragma unroll
        for (int i = 0; i < 4; i++) { r4[i] = fmaf(c[3][i], sc, fmaf(c[2][i], sc, fmaf(c[0][i] + c[1][i], sc, __uint_as_float(i == 3 ? 0u - old : 0u)))); e[i] = x && dq + (i & 1) < 8 * (i >> 1) ? 0.f : ex2(r4[i]); }
        stsm2t(uP2 + x * 1024 + L16, pack2(e[0], e[1]), pack2(e[2], e[3]), again);
      };
      auto put_s = [&](int x) {
#pragma unroll
        for (int i = 0; i < 4; i++) sts32f(uW + R_S + x * 1536 + (L16 & 48) * 4 + (L16 >> 6) * 4 + (i & 1) * 32 + (i >> 1) * 256, r4[i]);
      };
      auto load_q = [&](uint32_t (&q)[4], uint32_t off) { ldsm4(q, sb + R_Q + (L16 & 112) + (L16 & 128) * 2 + (L16 >> 8) * 128 + off); };
      mbar_spin(sb + B_C, nc & 1, it);
      TS(13);
      float4 o4;
      uint32_t id[4], old;
      {
        uint32_t b[24][4];
#pragma unroll
        for (int i = 0; i < 2 * PD1; i++) { lds128(b[i], ma + i * 512); __syncwarp(); }
        sched();
        zero(c);
#pragma unroll
        for (int i = 0; i < 12; i++) {
          mma4(4 * i, b[2 * i], b[2 * i + 1]);
          if (i < 11) sched();
          if (i + PD1 < 12) { const int k = i + PD1; const uint32_t a = (ma ^ (k >> 2 << 12)) + (k & 3) * 1024; lds128(b[2 * k], a); __syncwarp(); lds128(b[2 * k + 1], a + 512); sched(); }
          if (i == RJ) { lds128(id, sb + R_ID + L16); sched(); }
          if (i == RI) { old = bar_or(4, 0); o4 = lds128f(uW + R_RED + L16); sched(); }
        }
      }
      TS(0);
      {
        float e[4] = {o4.x, o4.y, o4.z, o4.w};
#pragma unroll
        for (int i = 0; i < 4; i++) { r4[i] = (((e[i] + c[0][i]) + c[1][i]) + c[2][i]) + c[3][i]; e[i] = 0.f; }
        mma_a(e, id, pack2(r4[0], r4[1]), pack2(r4[2], r4[3]));
        sched();
        if (VB) bar_arrive(7, 256);
        sched();
        asm volatile("{.reg .pred p; setp.eq.u32 p, %3, 0; @p st.relaxed.gpu.global.v2.b32 [%0], {%1,%2};}" :: "l"(adst),
                     "r"((__byte_perm(__float_as_uint(e[0]), __float_as_uint(e[1]), 0x7632) & ~1u) | tag), "r"(__byte_perm(__float_as_uint(e[2]), __float_as_uint(e[3]), 0x7632)), "r"(old) : "memory");
        sched();
      }
      const unsigned tpub = clk(), now = gtime(), due = get_due();
      if (__any_sync(0xffffffffu, old) && nc < NC_MAX) { bar_sync(3, 256); continue; }
      TS(2);
      const uint8_t* asrc = pinp(adst + ((warp == 7) * 1024 - (int)uA));
      fresh();
      uint32_t wo[32][4];
      bool xok;
      auto reload = [&]() {
        sched();
#pragma unroll
        for (int i = RE0 + RE1; i < NSW; i++) lds128(w[i], uW + R_WC + L16 + i * 2048);
        sched();
      };
      auto out_proj = [&]() {
        uint32_t b[4][4];
        float d[4][4];
        uint8_t* dst[2];
        const uint32_t da = pin(uP2 + (R_DST - R_P) + L16 / 2);
        sched();
        TS(7);
        bar_sync(6, 256);
#pragma unroll
        for (int i = 0; i < 4; i++) { ldsm4(b[i], sb + R_O + i * 512 + L16); __syncwarp(); }
        sched();
        auto put_b = [&](uint8_t* a, const float (&e)[4][4]) {
          stx128(a, (pack2(e[0][0] + e[2][0], e[0][1] + e[2][1]) & ~1u) | tag, pack2(e[0][2] + e[2][2], e[0][3] + e[2][3]),
                 pack2(e[1][0] + e[3][0], e[1][1] + e[3][1]), pack2(e[1][2] + e[3][2], e[1][3] + e[3][3]));
        };
        zero(c); zero(d);
#pragma unroll
        for (int i = 0; i < 32; i++) {
          mma_h(i < 16 ? c[i & 3] : d[i & 3], wo[i], b[(i >> 2) & 3], (i >> 1) & 1);
          if (i >= LW0 && NB1 + i - LW0 < 32) { load_wo(wo, (NB1 + i - LW0) ^ 1, ((NB1 + i - LW0) ^ 1) + 1); __syncwarp(); }
          if (i == DL0 || i == DL1) asm volatile("ld.shared.u64 %0, [%1];" : "=l"(dst[i > DL0]) : "r"(da + (i > DL0) * 1024) : "memory");
          if (i >= 16 && i < 16 + RE0) { lds128(w[i - 16], uW + R_WC + L16 + (i - 16) * 2048); __syncwarp(); }
          if (i >= RP1 && i < RP1 + RE1) { lds128(w[i - RP1 + RE0], uW + R_WC + L16 + (i - RP1 + RE0) * 2048); __syncwarp(); }
          if (i == 22) put_b(dst[0], c);
          if ((i & 1) && (i < 20 || i > 22)) sched();
        }
        put_b(dst[1], d);
        sched();
        TS(6);
      };
      if (warp < 6) {
        delay_until(tpub + DLY_A);
        const int it0 = it;
        bool redo;
#pragma unroll 1
        do {
          uint32_t q[4][4], y[4];
          float d[4][4];
          wait_time(due);
          TS(4);
          ldx(q, asrc);
          sched();
          load_k();
          uint32_t qx[4][4];
#pragma unroll
          for (int i = 0; i < 4; i++) load_q(qx[i], i * 512);
          sched();
          load_wo(wo, 0, NE4);
          sched();
          zero(c);
#pragma unroll
          for (int i = 0; i < 8; i++) mma_h(c[i & 3], kf[i], qx[i >> 1], i & 1);
          put_p(1, 0, 0); put_s(1);
          sched();
          load_wo(wo, NE4, NA4);
          sched();
          zero(c); zero(d);
#pragma unroll
          for (int i = 0; i < 8; i++) {
            if (i == 0) { y[0] = dif2v(q[0][0], q[0][2], q[1][0]); sched(); }
            if (i == 3) { y[1] = dif2v(q[1][2], q[2][0], q[2][2]); sched(); }
            if (i == 6) { y[2] = dif2v(q[3][0], q[3][2], tag); sched(); }
            mma_h(i % 6 < 2 ? c[2 + i % 6] : d[i - 2], kf[i], q[i >> 1], i & 1);
            if (i == 2 || i == 5 || i == 7) sched();
          }
          y[0] = or_and(or3(y[0], y[1], dif2v(q[0][0], q[2][0], tag)), y[2], it < SPIN_LIMIT);
#pragma unroll
          for (int i = 0; i < 4; i++) { c[0][i] = d[0][i] + d[1][i]; c[1][i] = d[2][i] + d[3][i]; }
          put_p(0, y[0], it - it0);
          TS(5);
          bar_sync_unless(5, it - it0);
          redo = __any_sync(0xffffffffu, y[0]);
          it += INC_A;
        } while (redo);
        it -= INC_A;
        put_s(0);
        bar_arrive(8, 256);
        load_wo(wo, NA4, NB1);
        out_proj();
        if (warp == 4) LOG(12, tb);
      } else {
        uint32_t qx[2][4], q[4][4];
        if (warp == 6) {
          const uint32_t t1 = (now & ~31u) + NS_M;
          LOG(10, now - due);
          if (elect()) stx32(&gx->T[h][j], ((int)(t1 - due) > 0 ? t1 + NS_PEN : due) | ((s + 1) & 31));
          __syncwarp();
        }
        auto score = [&](const uint32_t (&a0)[4], const uint32_t (&a1)[4]) {
          zero(c);
#pragma unroll
          for (int i = 0; i < 4; i++) mma_h(c[i], i < 2 ? a0 : a1, q[2 + (i >> 1)], i & 1);
        };
        auto put_m = [&](uint32_t a, uint32_t old, uint32_t again) {
#pragma unroll
          for (int i = 0; i < 2; i++) { r4[i] = fmaf(c[3][2 + i], sc, fmaf((c[0][i] + c[1][2 + i]) + c[2][i], sc, __uint_as_float(i ? 0u - old : 0u))); r4[2 + i] = fmaf(r4[i] * 0x1p122f, 0.f, ex2(r4[i])); }
          asm volatile("{.reg .pred p; setp.eq.u32 p, %3, 0; @p st.shared.v2.f32 [%0], {%1,%2};}" :: "r"(a), "f"(r4[2]), "f"(r4[3]), "r"(again) : "memory");
        };
        delay_until(tpub + DLY_A);
        const uint32_t sa = sb + R_S + 512 + w4 * 256 + (L16 >> 1);
        const int it0 = it;
        bool redo;
#pragma unroll 1
        do {
          wait_time(due);
          TS(4);
          ldx<4, 2048>(q, asrc);
          sched();
          load_q(qx[0], (w4 & 1) * 1024); load_q(qx[1], (w4 & 1) * 1024 + 512);
          load_wo(wo, 0, NA6);
          sched();
          score(q[0], q[1]);
          sched();
          const uint32_t y = or_and(or3(dif2v(q[0][0], q[0][2], tag), dif2v(q[1][0], q[1][2], tag), dif2v(q[2][0], q[2][2], tag)), dif2v(q[3][0], q[3][2], tag), it < SPIN_LIMIT);
          put_m(sa + 2560, y, it - it0);
          TS(5);
          bar_arrive_unless(5, it - it0);
          redo = __any_sync(0xffffffffu, y);
          it += INC_A;
        } while (redo);
        it -= INC_A;
        sts64f(sa, r4[0], r4[1]);
        score(qx[0], qx[1]);
        put_m(sa + 3584, 0, 0);
        sts64f(sa + 1536, r4[0], r4[1]);
        bar_arrive(8, 256);
        load_wo(wo, NA6, NB1);
        out_proj();
      }
      TS(8);
      if (s + 1 == NSEG) break;
      wait_x(s + 2, 2);
      TS(9);
      fresh();
      if (N1) project_qk(IC<32>{}, IC<32 + N1>{}, IC<1>{}, [](int) {});
      TS(10);
      xpos(6, 6);
      uint32_t fl = s + 1;
      if (warp == 5) { wait_time(due + NS_F); fl = ldx32(xa + 4096 + ((L16 >> 2) & 60)); }
      reload();
      TS(14);
      pin_mem();
      wait_x(s + 2, 1); wait_x(s + 2, 0);
      if (warp == 5) {
#pragma unroll 1
        while (__any_sync(0xffffffffu, fl != s + 1) && !(EXP & 4) && ++it < SPIN_LIMIT) fl = ldx32(xa + 4096 + ((L16 >> 2) & 60));
        wait_time(due + (NS_B + NS_K));
        if (!(EXP & 2) && elect()) issue_kqv(s + 1);
        __syncwarp();
      }
      if (PFD && warp == 6 && s + PFD < NSEG && elect())
        asm volatile("cp.async.bulk.prefetch.L2.global [%0], 2048;" :: "l"(xin + ((s + PFD) * SEG + ((role + 4 * (role >> 5)) & 31)) * DM) : "memory");
      __syncwarp();
      TS(11);
      LOG(warp, it);
      if (warp == 4) LOG(8, nc);
      bar_sync(0, 256);
      if (N1 < 16) project_qk(IC<32 + N1>{}, IC<48>{}, IC<!N1>{}, [](int) {});
      project_qk(IC<16>{}, IC<32>{}, IC<0>{}, [&](int n) { if ((n & 15) == XWPOS) { __syncwarp(); xok = mbar_test(sb + B_PK, s & 1); __syncwarp(); } });
      if (rare(!xok)) mbar_spin(sb + B_PK, s & 1, it);
      unpark();
      project_qk(IC<0>{}, IC<16>{}, IC<0>{}, [](int) {});
      TS(12);
      wg_wait<0>(); keep(aq);
      TS(1);
      fin_qk();
      TS(15);
    }
    s++;
  }
  if (it >= SPIN_LIMIT || nc >= NC_MAX) g_err = 2;
}

typedef CUresult (*EncodeFn)(CUtensorMap*, CUtensorMapDataType, cuuint32_t, void*, const cuuint64_t*, const cuuint64_t*, const cuuint32_t*,
                             const cuuint32_t*, CUtensorMapInterleave, CUtensorMapSwizzle, CUtensorMapL2promotion, CUtensorMapFloatOOBfill);
static void make_map(EncodeFn fn, CUtensorMap* m, const void* p, uint64_t cols, uint64_t rows, uint64_t pitch, uint32_t bc, uint32_t br, CUtensorMapSwizzle sw) {
  cuuint64_t dims[2] = {cols, rows}, strides[1] = {pitch * 2};
  cuuint32_t box[2] = {bc, br}, es[2] = {1, 1};
  fn(m, CU_TENSOR_MAP_DATA_TYPE_BFLOAT16, 2, const_cast<void*>(p), dims, strides, box, es, CU_TENSOR_MAP_INTERLEAVE_NONE, sw,
     CU_TENSOR_MAP_L2_PROMOTION_L2_256B, CU_TENSOR_MAP_FLOAT_OOB_FILL_NONE);
}

extern "C" void kernel_launch(void* const* d_in, const int* in_sizes, int n_in, void* d_out, int out_size) {
  const bf16* Ax = (const bf16*)d_in[0]; const bf16* mem0 = (const bf16*)d_in[1];
  const bf16* Wq = (const bf16*)d_in[2]; const bf16* Wk = (const bf16*)d_in[3]; const bf16* Wv = (const bf16*)d_in[4];
  const bf16* Wo = (const bf16*)d_in[5];
  const bf16* Bx = (const bf16*)d_in[7]; const bf16* wr = (const bf16*)d_in[8]; const bf16* wi = (const bf16*)d_in[9];
  bf16* out = (bf16*)d_out;

  void* fp = nullptr; cudaDriverEntryPointQueryResult qr;
  cudaGetDriverEntryPoint("cuTensorMapEncodeTiled", &fp, cudaEnableDefault, &qr);
  EncodeFn fn = (EncodeFn)fp;
  void *kqv, *ox, *xr;
  cudaGetSymbolAddress(&xr, g_xraw);
  cudaGetSymbolAddress(&kqv, g_kqv); cudaGetSymbolAddress(&ox, g_ox);
  const CUtensorMapSwizzle S128 = CU_TENSOR_MAP_SWIZZLE_128B, S64 = CU_TENSOR_MAP_SWIZZLE_64B;

  GemmMaps m3; RecMaps mr;
  make_map(fn, &m3.a, ox, HD, S_LEN, HD, 64, 128, S128);
  make_map(fn, &m3.b[0], Wo, DM, HD, DM, 64, 64, S128);
  m3.b[1] = m3.b[0]; m3.b[2] = m3.b[0];
  make_map(fn, &m3.c, out, DM, S_LEN, 2 * DM, 64, 64, S128);
  make_map(fn, &mr.wq, Wq, HD, DM, HD, 32, 256, S64);
  make_map(fn, &mr.wk, Wk, HD, DM, HD, 32, 256, S64);
  make_map(fn, &mr.wv, Wv, HD, DM, HD, 64, 256, S128);
  make_map(fn, &mr.wo, Wo, DM, HD, DM, 64, 128, S128);
  {
    cuuint64_t dims[3] = {64, S_LEN, 16}, strides[2] = {DM * 2, 128};
    cuuint32_t box[3] = {64, 32, 4}, es[3] = {1, 1, 1};
    fn(&mr.x, CU_TENSOR_MAP_DATA_TYPE_BFLOAT16, 3, const_cast<bf16*>(Ax), dims, strides, box, es, CU_TENSOR_MAP_INTERLEAVE_NONE, S128,
       CU_TENSOR_MAP_L2_PROMOTION_L2_256B, CU_TENSOR_MAP_FLOAT_OOB_FILL_NONE);
  }
  for (int i = 0; i < 3; i++) {
    cuuint64_t dims[3] = {128, 32, 512}, strides[2] = {256, 8192};
    cuuint32_t box[3] = {128, i == 0 ? 8u : i == 1 ? 2u : 16u, 4}, es[3] = {1, 1, 1};
    fn(i == 0 ? &mr.k : i == 1 ? &mr.q : &mr.v, CU_TENSOR_MAP_DATA_TYPE_BFLOAT16, 3, kqv, dims, strides, box, es, CU_TENSOR_MAP_INTERLEAVE_NONE,
       CU_TENSOR_MAP_SWIZZLE_NONE, CU_TENSOR_MAP_L2_PROMOTION_L2_256B, CU_TENSOR_MAP_FLOAT_OOB_FILL_NONE);
  }
  {
    cuuint64_t dims[3] = {64, 16, S_LEN}, strides[2] = {128, 2 * DM * 2};
    cuuint32_t box[3] = {64, 16, 2}, es[3] = {1, 1, 1};
    fn(&mr.fo, CU_TENSOR_MAP_DATA_TYPE_BFLOAT16, 3, out + DM, dims, strides, box, es, CU_TENSOR_MAP_INTERLEAVE_NONE, S128,
       CU_TENSOR_MAP_L2_PROMOTION_NONE, CU_TENSOR_MAP_FLOAT_OOB_FILL_NONE);
  }
  constexpr int SM3 = 6 * 32768 + 32768 + 256 + 1024;
  cudaFuncSetAttribute(gemm_kernel<128, 6>, cudaFuncAttributeMaxDynamicSharedMemorySize, SM3);
  cudaFuncSetAttribute(rec_kernel, cudaFuncAttributeMaxDynamicSharedMemorySize, R_TOTAL);

  cudaStream_t st = cudaStreamPerThread;
  Xchg* gx = reinterpret_cast<Xchg*>((reinterpret_cast<uintptr_t>(xr) + 0x1FFFFF) & ~(uintptr_t)0x1FFFFF);
  rec_kernel<<<132, 256, R_TOTAL, st>>>(mr, Ax, mem0, gx, Bx, wr, wi);
  gemm_kernel<128, 6><<<128, 384, SM3, st>>>(m3, 16, 8, 64, 8, reinterpret_cast<uint4*>(gx));
}
```

```cpp
#include <cuda_runtime.h>
#include <cuda_bf16.h>
#include <cuda.h>
#include <stdint.h>
#include <stddef.h>
#include <type_traits>

typedef __nv_bfloat16 bf16;

constexpr int S_LEN = 2048, DM = 1024, NH = 32, DH = 128, MEM = 8, SEG = 32, NSEG = 64;
constexpr int HD = NH * DH;
#define SPIN 20
constexpr int SPIN_LIMIT = 1 << SPIN, INC_A = 1, INC_B = 1;

constexpr unsigned NC_MAX = 4096;
__device__ __align__(1024) uint4 g_kqv[4][128][512];
__device__ __align__(1024) bf16 g_ox[(size_t)S_LEN * HD];
struct Xchg {
  uint4 A[32][4][256];
  uint4 C[4][2][256];
  uint4 B[128][2][256];
  uint32_t T[32][32];
  uint32_t S[128];
  unsigned ctr[64];
};
__device__ __align__(1024) uint4 g_xraw[(sizeof(Xchg) + (1 << 21)) / 16];
__device__ __align__(1024) uint4 g_y[1024 * 256];
__device__ __align__(1024) uint4 g_wt[513 * 512];
__device__ int g_err;

__device__ __forceinline__ unsigned clk() { unsigned long long c; asm volatile("mov.u64 %0, %%clock64;" : "=l"(c)); return (unsigned)c; }
__device__ __forceinline__ uint32_t smem_u32(const void* p) { return (uint32_t)__cvta_generic_to_shared(p); }
__device__ __forceinline__ void mbar_init(uint32_t bar, int cnt) { asm volatile("mbarrier.init.shared::cta.b64 [%0], %1;" :: "r"(bar), "r"(cnt) : "memory"); }
__device__ __forceinline__ void mbar_expect_tx(uint32_t bar, int bytes) { asm volatile("mbarrier.arrive.expect_tx.shared::cta.b64 _, [%0], %1;" :: "r"(bar), "r"(bytes) : "memory"); }
__device__ __forceinline__ void mbar_arrive_cluster(uint32_t bar, int cta) {
  asm volatile("{.reg .b32 r; mapa.shared::cluster.u32 r, %0, %1; mbarrier.arrive.shared::cluster.b64 _, [r];}" :: "r"(bar), "r"(cta) : "memory"); }
__device__ __forceinline__ bool mbar_try(uint32_t bar, int par) {
  uint32_t ok; asm volatile("{.reg .pred p; mbarrier.try_wait.parity.shared::cta.b64 p, [%1], %2; selp.u32 %0, 1, 0, p;}" : "=r"(ok) : "r"(bar), "r"(par) : "memory"); return ok; }
__device__ __forceinline__ bool mbar_test(uint32_t bar, int par) {
  uint32_t ok; asm volatile("{.reg .pred p; mbarrier.test_wait.parity.shared::cta.b64 p, [%1], %2; selp.u32 %0, 1, 0, p;}" : "=r"(ok) : "r"(bar), "r"(par) : "memory"); return ok; }
__device__ __forceinline__ void mbar_wait(uint32_t bar, int par) {
  int it = 0;
  while (!mbar_try(bar, par)) { if (++it > SPIN_LIMIT) { g_err = 1; break; } }
}
__device__ __forceinline__ void tma2d(uint32_t dst, const CUtensorMap* m, int c0, int c1, uint32_t bar) {
  asm volatile("cp.async.bulk.tensor.2d.shared::cluster.global.mbarrier::complete_tx::bytes [%0], [%1, {%3, %4}], [%2];"
    :: "r"(dst), "l"(m), "r"(bar), "r"(c0), "r"(c1) : "memory"); }
__device__ __forceinline__ void tma2d_mc(uint32_t dst, const CUtensorMap* m, int c0, int c1, uint32_t bar, uint16_t mask) {
  asm volatile("cp.async.bulk.tensor.2d.shared::cluster.global.mbarrier::complete_tx::bytes.multicast::cluster [%0], [%1, {%3, %4}], [%2], %5;"
    :: "r"(dst), "l"(m), "r"(bar), "r"(c0), "r"(c1), "h"(mask) : "memory"); }
__device__ __forceinline__ void tma2d_store(const CUtensorMap* m, uint32_t src, int c0, int c1) {
  asm volatile("cp.async.bulk.tensor.2d.global.shared::cta.bulk_group [%0, {%2, %3}], [%1];" :: "l"(m), "r"(src), "r"(c0), "r"(c1) : "memory"); }
__device__ __forceinline__ void fence_async() { asm volatile("fence.proxy.async.shared::cta;" ::: "memory"); }
__device__ __forceinline__ void bar_sync(int id, int n) { asm volatile("bar.sync %0, %1;" :: "r"(id), "r"(n) : "memory"); }
__device__ __forceinline__ void bar_arrive(int id, int n) { asm volatile("bar.arrive %0, %1;" :: "r"(id), "r"(n) : "memory"); }
__device__ __forceinline__ uint32_t pack2(float lo, float hi) { uint32_t r; asm("cvt.rn.bf16x2.f32 %0, %1, %2;" : "=r"(r) : "f"(hi), "f"(lo)); return r; }
__device__ __forceinline__ void ldsm4(uint32_t (&r)[4], uint32_t a) {
  asm volatile("ldmatrix.sync.aligned.m8n8.x4.shared.b16 {%0,%1,%2,%3}, [%4];" : "=r"(r[0]), "=r"(r[1]), "=r"(r[2]), "=r"(r[3]) : "r"(a) : "memory"); }
__device__ __forceinline__ void ldsm4t(uint32_t (&r)[4], uint32_t a) {
  asm volatile("ldmatrix.sync.aligned.m8n8.x4.trans.shared.b16 {%0,%1,%2,%3}, [%4];" : "=r"(r[0]), "=r"(r[1]), "=r"(r[2]), "=r"(r[3]) : "r"(a) : "memory"); }
__device__ __forceinline__ void stsm4(uint32_t a, uint32_t r0, uint32_t r1, uint32_t r2, uint32_t r3) {
  asm volatile("stmatrix.sync.aligned.m8n8.x4.shared.b16 [%0], {%1,%2,%3,%4};" :: "r"(a), "r"(r0), "r"(r1), "r"(r2), "r"(r3) : "memory"); }
__device__ __forceinline__ void stsm4t(uint32_t a, uint32_t r0, uint32_t r1, uint32_t r2, uint32_t r3) {
  asm volatile("stmatrix.sync.aligned.m8n8.x4.trans.shared.b16 [%0], {%1,%2,%3,%4};" :: "r"(a), "r"(r0), "r"(r1), "r"(r2), "r"(r3) : "memory"); }
__device__ __forceinline__ void lds128(uint32_t (&r)[4], uint32_t a) {
  asm volatile("ld.shared.v4.u32 {%0,%1,%2,%3}, [%4];" : "=r"(r[0]), "=r"(r[1]), "=r"(r[2]), "=r"(r[3]) : "r"(a) : "memory"); }
__device__ __forceinline__ float4 lds128f(uint32_t a) { float4 r;
  asm volatile("ld.shared.v4.f32 {%0,%1,%2,%3}, [%4];" : "=f"(r.x), "=f"(r.y), "=f"(r.z), "=f"(r.w) : "r"(a) : "memory"); return r; }
__device__ __forceinline__ float2 lds64f(uint32_t a) { float2 r;
  asm volatile("ld.shared.v2.f32 {%0,%1}, [%2];" : "=f"(r.x), "=f"(r.y) : "r"(a) : "memory"); return r; }
__device__ __forceinline__ void sts128(uint32_t a, uint32_t r0, uint32_t r1, uint32_t r2, uint32_t r3) {
  asm volatile("st.shared.v4.u32 [%0], {%1,%2,%3,%4};" :: "r"(a), "r"(r0), "r"(r1), "r"(r2), "r"(r3) : "memory"); }
__device__ __forceinline__ void sts64f(uint32_t a, float x, float y) { asm volatile("st.shared.v2.f32 [%0], {%1,%2};" :: "r"(a), "f"(x), "f"(y) : "memory"); }
__device__ __forceinline__ void sts32f(uint32_t a, float x) { asm volatile("st.shared.f32 [%0], %1;" :: "r"(a), "f"(x) : "memory"); }
__device__ __forceinline__ void mma16816(float (&d)[4], uint32_t a0, uint32_t a1, uint32_t a2, uint32_t a3, uint32_t b0, uint32_t b1) {
  asm volatile("mma.sync.aligned.m16n8k16.row.col.f32.bf16.bf16.f32 {%0,%1,%2,%3}, {%4,%5,%6,%7}, {%8,%9}, {%0,%1,%2,%3};"
    : "+f"(d[0]), "+f"(d[1]), "+f"(d[2]), "+f"(d[3]) : "r"(a0), "r"(a1), "r"(a2), "r"(a3), "r"(b0), "r"(b1)); }
__device__ __forceinline__ void mma1688(float (&d)[4], uint32_t a0, uint32_t a1, uint32_t b0) {
  asm volatile("mma.sync.aligned.m16n8k8.row.col.f32.bf16.bf16.f32 {%0,%1,%2,%3}, {%4,%5}, {%6}, {%0,%1,%2,%3};"
    : "+f"(d[0]), "+f"(d[1]), "+f"(d[2]), "+f"(d[3]) : "r"(a0), "r"(a1), "r"(b0)); }
__device__ __forceinline__ void ldx128(uint32_t (&r)[4], const void* p) {
  asm volatile("{.reg .b128 t; .reg .b64 a, b; ld.relaxed.gpu.global.b128 t, [%4]; mov.b128 {a, b}, t; mov.b64 {%0,%1}, a; mov.b64 {%2,%3}, b;}"
    : "=r"(r[0]), "=r"(r[1]), "=r"(r[2]), "=r"(r[3]) : "l"(p) : "memory"); }
__device__ __forceinline__ void stx128(void* p, uint32_t r0, uint32_t r1, uint32_t r2, uint32_t r3) {
  asm volatile("{.reg .b128 t; .reg .b64 a, b; mov.b64 a, {%1,%2}; mov.b64 b, {%3,%4}; mov.b128 t, {a, b}; st.relaxed.gpu.global.b128 [%0], t;}"
    :: "l"(p), "r"(r0), "r"(r1), "r"(r2), "r"(r3) : "memory"); }
__device__ __forceinline__ uint32_t uni(uint32_t x) { return __shfl_sync(0xffffffffu, x, 0); }
__device__ __forceinline__ uint32_t pin(uint32_t x) { return __shfl_xor_sync(0xffffffffu, x, 0); }
__device__ __forceinline__ float ex2(float x) { float r; asm("ex2.approx.ftz.f32 %0, %1;" : "=f"(r) : "f"(x)); return r; }
__device__ __forceinline__ void wg_fence() { asm volatile("wgmma.fence.sync.aligned;" ::: "memory"); }
__device__ __forceinline__ void wg_commit() { asm volatile("wgmma.commit_group.sync.aligned;" ::: "memory"); }
template <int N> __device__ __forceinline__ void wg_wait() { asm volatile("wgmma.wait_group.sync.aligned %0;" :: "n"(N) : "memory"); }

__device__ __forceinline__ void wgmma_ss_n256_tb1(float (&d)[128], uint64_t da, uint64_t db, int sc) {
  asm volatile("{.reg .pred p; setp.ne.b32 p, %130, 0;\n"
    "wgmma.mma_async.sync.aligned.m64n256k16.f32.bf16.bf16 {%0,%1,%2,%3,%4,%5,%6,%7,%8,%9,%10,%11,%12,%13,%14,%15,%16,%17,%18,%19,%20,%21,%22,%23,%24,%25,%26,%27,%28,%29,%30,%31,%32,%33,%34,%35,%36,%37,%38,%39,%40,%41,%42,%43,%44,%45,%46,%47,%48,%49,%50,%51,%52,%53,%54,%55,%56,%57,%58,%59,%60,%61,%62,%63,%64,%65,%66,%67,%68,%69,%70,%71,%72,%73,%74,%75,%76,%77,%78,%79,%80,%81,%82,%83,%84,%85,%86,%87,%88,%89,%90,%91,%92,%93,%94,%95,%96,%97,%98,%99,%100,%101,%102,%103,%104,%105,%106,%107,%108,%109,%110,%111,%112,%113,%114,%115,%116,%117,%118,%119,%120,%121,%122,%123,%124,%125,%126,%127}, %128, %129, p, 1, 1, 0, 1;}\n"
    : "+f"(d[0]),"+f"(d[1]),"+f"(d[2]),"+f"(d[3]),"+f"(d[4]),"+f"(d[5]),"+f"(d[6]),"+f"(d[7]),"+f"(d[8]),"+f"(d[9]),"+f"(d[10]),"+f"(d[11]),"+f"(d[12]),"+f"(d[13]),"+f"(d[14]),"+f"(d[15]),"+f"(d[16]),"+f"(d[17]),"+f"(d[18]),"+f"(d[19]),"+f"(d[20]),"+f"(d[21]),"+f"(d[22]),"+f"(d[23]),"+f"(d[24]),"+f"(d[25]),"+f"(d[26]),"+f"(d[27]),"+f"(d[28]),"+f"(d[29]),"+f"(d[30]),"+f"(d[31]),"+f"(d[32]),"+f"(d[33]),"+f"(d[34]),"+f"(d[35]),"+f"(d[36]),"+f"(d[37]),"+f"(d[38]),"+f"(d[39]),"+f"(d[40]),"+f"(d[41]),"+f"(d[42]),"+f"(d[43]),"+f"(d[44]),"+f"(d[45]),"+f"(d[46]),"+f"(d[47]),"+f"(d[48]),"+f"(d[49]),"+f"(d[50]),"+f"(d[51]),"+f"(d[52]),"+f"(d[53]),"+f"(d[54]),"+f"(d[55]),"+f"(d[56]),"+f"(d[57]),"+f"(d[58]),"+f"(d[59]),"+f"(d[60]),"+f"(d[61]),"+f"(d[62]),"+f"(d[63]),"+f"(d[64]),"+f"(d[65]),"+f"(d[66]),"+f"(d[67]),"+f"(d[68]),"+f"(d[69]),"+f"(d[70]),"+f"(d[71]),"+f"(d[72]),"+f"(d[73]),"+f"(d[74]),"+f"(d[75]),"+f"(d[76]),"+f"(d[77]),"+f"(d[78]),"+f"(d[79]),"+f"(d[80]),"+f"(d[81]),"+f"(d[82]),"+f"(d[83]),"+f"(d[84]),"+f"(d[85]),"+f"(d[86]),"+f"(d[87]),"+f"(d[88]),"+f"(d[89]),"+f"(d[90]),"+f"(d[91]),"+f"(d[92]),"+f"(d[93]),"+f"(d[94]),"+f"(d[95]),"+f"(d[96]),"+f"(d[97]),"+f"(d[98]),"+f"(d[99]),"+f"(d[100]),"+f"(d[101]),"+f"(d[102]),"+f"(d[103]),"+f"(d[104]),"+f"(d[105]),"+f"(d[106]),"+f"(d[107]),"+f"(d[108]),"+f"(d[109]),"+f"(d[110]),"+f"(d[111]),"+f"(d[112]),"+f"(d[113]),"+f"(d[114]),"+f"(d[115]),"+f"(d[116]),"+f"(d[117]),"+f"(d[118]),"+f"(d[119]),"+f"(d[120]),"+f"(d[121]),"+f"(d[122]),"+f"(d[123]),"+f"(d[124]),"+f"(d[125]),"+f"(d[126]),"+f"(d[127])
    : "l"(da), "l"(db), "r"(sc));
}

__device__ __forceinline__ void wgmma_ss_n128_tb1(float (&d)[64], uint64_t da, uint64_t db, int sc) {
  asm volatile("{.reg .pred p; setp.ne.b32 p, %66, 0;\n"
    "wgmma.mma_async.sync.aligned.m64n128k16.f32.bf16.bf16 {%0,%1,%2,%3,%4,%5,%6,%7,%8,%9,%10,%11,%12,%13,%14,%15,%16,%17,%18,%19,%20,%21,%22,%23,%24,%25,%26,%27,%28,%29,%30,%31,%32,%33,%34,%35,%36,%37,%38,%39,%40,%41,%42,%43,%44,%45,%46,%47,%48,%49,%50,%51,%52,%53,%54,%55,%56,%57,%58,%59,%60,%61,%62,%63}, %64, %65, p, 1, 1, 0, 1;}\n"
    : "+f"(d[0]),"+f"(d[1]),"+f"(d[2]),"+f"(d[3]),"+f"(d[4]),"+f"(d[5]),"+f"(d[6]),"+f"(d[7]),"+f"(d[8]),"+f"(d[9]),"+f"(d[10]),"+f"(d[11]),"+f"(d[12]),"+f"(d[13]),"+f"(d[14]),"+f"(d[15]),"+f"(d[16]),"+f"(d[17]),"+f"(d[18]),"+f"(d[19]),"+f"(d[20]),"+f"(d[21]),"+f"(d[22]),"+f"(d[23]),"+f"(d[24]),"+f"(d[25]),"+f"(d[26]),"+f"(d[27]),"+f"(d[28]),"+f"(d[29]),"+f"(d[30]),"+f"(d[31]),"+f"(d[32]),"+f"(d[33]),"+f"(d[34]),"+f"(d[35]),"+f"(d[36]),"+f"(d[37]),"+f"(d[38]),"+f"(d[39]),"+f"(d[40]),"+f"(d[41]),"+f"(d[42]),"+f"(d[43]),"+f"(d[44]),"+f"(d[45]),"+f"(d[46]),"+f"(d[47]),"+f"(d[48]),"+f"(d[49]),"+f"(d[50]),"+f"(d[51]),"+f"(d[52]),"+f"(d[53]),"+f"(d[54]),"+f"(d[55]),"+f"(d[56]),"+f"(d[57]),"+f"(d[58]),"+f"(d[59]),"+f"(d[60]),"+f"(d[61]),"+f"(d[62]),"+f"(d[63])
    : "l"(da), "l"(db), "r"(sc));
}

template <int BN> struct WG;
template <> struct WG<256> { static __device__ __forceinline__ void mma(float (&d)[128], uint64_t a, uint64_t b, int sc) { wgmma_ss_n256_tb1(d, a, b, sc); } };
template <> struct WG<128> { static __device__ __forceinline__ void mma(float (&d)[64], uint64_t a, uint64_t b, int sc) { wgmma_ss_n128_tb1(d, a, b, sc); } };

#define GST 7
#define GA0 3
struct GemmMaps { CUtensorMap a, b[3], c; };
template <int BN, int STAGES>
__global__ void __cluster_dims__(2, 1, 1) __launch_bounds__(384, 1)
gemm_kernel(const __grid_constant__ GemmMaps maps, int tilesM, int tilesN, int kblocks, int nPerB, uint4* __restrict__ clearX) {
  extern __shared__ __align__(1024) uint8_t smem_raw[];
  constexpr int STAGE_BYTES = 16384 + BN * 128;
  constexpr int NBOX = BN / 64;
  const uint32_t sbase = (smem_u32(smem_raw) + 1023) & ~1023u;
  const uint32_t sBar = sbase + STAGES * STAGE_BYTES;
  const int warp = threadIdx.x >> 5, lane = threadIdx.x & 31, wg = warp >> 2;
  uint32_t crank; asm("mov.u32 %0, %%cluster_ctarank;" : "=r"(crank));
#define GT(k)
  const int npairs = (tilesM >> 1) * tilesN, pair0 = blockIdx.x >> 1, pstep = gridDim.x >> 1;
  if (threadIdx.x == 256) {
    asm volatile("prefetch.tensormap [%0];" :: "l"(&maps.b[0]) : "memory");
    for (int i = 0; i < STAGES; i++) { mbar_init(sBar + 8 * i, 1); mbar_init(sBar + 8 * (STAGES + i), 4); }
    asm volatile("fence.mbarrier_init.release.cluster;" ::: "memory");
    asm volatile("barrier.cluster.arrive.relaxed;" ::: "memory");
    for (int i = 0; i < GA0; i++) {
      mbar_expect_tx(sBar + 8 * i, STAGE_BYTES);
      tma2d(sbase + i * STAGE_BYTES, &maps.a, i * 64, ((pair0 % (tilesM >> 1)) * 2 + crank) * 128, sBar + 8 * i);
    }
    asm volatile("prefetch.tensormap [%0];" :: "l"(&maps.c) : "memory");
  } else asm volatile("barrier.cluster.arrive.relaxed;" ::: "memory");
  asm volatile("barrier.cluster.wait.acquire;" ::: "memory");
  __syncwarp();
  if (wg == 2) {
    asm volatile("setmaxnreg.dec.sync.aligned.u32 40;");
    if (warp > 8) {
      __nanosleep(4000);
      for (int i = blockIdx.x * 96 + threadIdx.x - 288; i < (int)(sizeof(Xchg) / 16); i += gridDim.x * 96) clearX[i] = make_uint4(0, 0, 0, 0);
    }
    if (warp == 8 && lane == 0) {
      int st = 0, ph = 1;
      for (int p = pair0; p < npairs; p += pstep) {
        const int tm = (p % (tilesM >> 1)) * 2 + crank, tn = p / (tilesM >> 1);
        const CUtensorMap* mb = &maps.b[tn / nPerB];
        const int n0 = (tn % nPerB) * BN;
        for (int kb = 0; kb < kblocks; kb++) {
          const uint32_t a = sbase + st * STAGE_BYTES, full = sBar + 8 * st;
          if (p > pair0 || kb >= GA0) {
            mbar_wait(sBar + 8 * (STAGES + st), ph);
            mbar_expect_tx(full, STAGE_BYTES);
            tma2d(a, &maps.a, kb * 64, tm * 128, full);
          }
#pragma unroll
          for (int i = 0; i < NBOX / 2; i++) {
            const int bx = crank * (NBOX / 2) + i;
            tma2d_mc(a + 16384 + bx * 8192, mb, n0 + bx * 64, kb * 64, full, (uint16_t)3);
          }
          if (++st == STAGES) { st = 0; ph ^= 1; }
        }
      }
      for (int i = 0; i < STAGES; i++) { mbar_wait(sBar + 8 * (STAGES + st), ph); if (++st == STAGES) { st = 0; ph ^= 1; } }
    }
  } else {
    asm volatile("setmaxnreg.inc.sync.aligned.u32 232;");
    int st = 0, ph = 0;
    float acc[BN / 2];
    const uint64_t descA0 = (uint64_t)(((sbase + wg * 8192) & 0x3FFFF) >> 4) | (1ull << 16) | (64ull << 32) | (1ull << 62);
    const uint64_t descB0 = (uint64_t)(((sbase + 16384) & 0x3FFFF) >> 4) | (512ull << 16) | (64ull << 32) | (1ull << 62);
    const uint32_t epi = sbase + wg * 8192;
    for (int p = pair0; p < npairs; p += pstep) {
      const int tm = (p % (tilesM >> 1)) * 2 + crank, tn = p / (tilesM >> 1);
      int prev = -1;
      for (int kb = 0; kb < kblocks; kb++) {
        mbar_wait(sBar + 8 * st, ph);
        if ((kb & 15) == 0) { GT(kb >> 4); }
        wg_fence();
        const uint64_t so = (uint64_t)(st * (STAGE_BYTES >> 4));
#pragma unroll
        for (int k = 0; k < 4; k++) WG<BN>::mma(acc, descA0 + so + k * 2, descB0 + so + k * 128, kb | k);
        wg_commit();
        if (prev >= 0) {
          wg_wait<1>();
          if ((threadIdx.x & 127) < 2) mbar_arrive_cluster(sBar + 8 * (STAGES + prev), threadIdx.x & 1);
        }
        prev = st;
        if (++st == STAGES) { st = 0; ph ^= 1; }
      }
      wg_wait<0>();
      if ((threadIdx.x & 127) < 2) mbar_arrive_cluster(sBar + 8 * (STAGES + prev), threadIdx.x & 1);
      GT(4);
#pragma unroll
      for (int r = 0; r < BN / 128; r++) {
        const int row = (warp & 3) * 16 + (lane & 15);
#pragma unroll
        for (int i = 0; i < 8; i++) {
          const int c = 2 * (i & 3) + (lane >> 4);
          const float* q = &acc[r * 64 + i * 8];
          stsm4(epi + (2 * r + (i >> 2)) * STAGE_BYTES + row * 128 + ((c ^ (row & 7)) << 4), pack2(q[0], q[1]), pack2(q[2], q[3]), pack2(q[4], q[5]), pack2(q[6], q[7]));
        }
        fence_async();
        bar_sync(1 + wg, 128);
        if ((threadIdx.x & 127) == 0) {
          tma2d_store(&maps.c, epi + 2 * r * STAGE_BYTES, tn * BN + r * 128, tm * 128 + wg * 64);
          tma2d_store(&maps.c, epi + (2 * r + 1) * STAGE_BYTES, tn * BN + r * 128 + 64, tm * 128 + wg * 64);
          asm volatile("cp.async.bulk.commit_group;" ::: "memory");
        }
      }
    }
    GT(5);
    if ((threadIdx.x & 127) == 0) asm volatile("cp.async.bulk.wait_group.read 0;" ::: "memory");
    GT(6);
  }
}

struct Dft { uint32_t m[2][2][2][4]; };
template <bool P4> __device__ __forceinline__ int fidx(int tile, int x) { return P4 ? 4 * (x >> 1) + 2 * (tile & 1) + (x & 1) + 16 * (tile >> 1) : x + 8 * tile; }
__device__ __forceinline__ float2 cis(int k, int n) {
  k &= n - 1; if (2 * k > n) k -= n;
  const float a = (float)k * (6.283185307179586f / (float)n);
  return make_float2(__cosf(a), __sinf(a));
}
template <bool OUT4> __device__ __forceinline__ void make_dft(Dft& D, int g, int t) {
#pragma unroll
  for (int q = 0; q < 16; q++) {
    const int b = q >> 3, u = (q >> 2) & 1, r = (q >> 1) & 1, v = q & 1;
    const float2 w = cis(fidx<OUT4>(v, g) * fidx<false>(2 * u + r, 2 * t + b), 32);
    D.m[b][u][0][q & 3] = pack2(w.x, w.y); D.m[b][u][1][q & 3] = pack2(-w.y, w.x);
  }
}
__device__ __forceinline__ void mma_dc(float (&d)[4], uint32_t a0, uint32_t a1, uint32_t a2, uint32_t a3, uint32_t b0, uint32_t b1, const float (&c)[4]) {
  asm("mma.sync.aligned.m16n8k16.row.col.f32.bf16.bf16.f32 {%0,%1,%2,%3}, {%4,%5,%6,%7}, {%8,%9}, {%10,%11,%12,%13};"
    : "=f"(d[0]), "=f"(d[1]), "=f"(d[2]), "=f"(d[3]) : "r"(a0), "r"(a1), "r"(a2), "r"(a3), "r"(b0), "r"(b1), "f"(c[0]), "f"(c[1]), "f"(c[2]), "f"(c[3])); }
__device__ __forceinline__ void dft_b(const Dft& D, const uint32_t (&x)[2][4], float (&o)[2][8]) {
#pragma unroll
  for (int ri = 0; ri < 2; ri++) {
    float z[4] = {0.f, 0.f, 0.f, 0.f}, e[4], p[4];
    mma_dc(e, D.m[0][0][ri][0], D.m[0][0][ri][1], D.m[0][0][ri][2], D.m[0][0][ri][3], x[0][0], x[0][1], z);
    mma_dc(e, D.m[0][1][ri][0], D.m[0][1][ri][1], D.m[0][1][ri][2], D.m[0][1][ri][3], x[0][2], x[0][3], e);
    mma_dc(p, D.m[1][0][ri][0], D.m[1][0][ri][1], D.m[1][0][ri][2], D.m[1][0][ri][3], x[1][0], x[1][1], e);
    mma_dc(p, D.m[1][1][ri][0], D.m[1][1][ri][1], D.m[1][1][ri][2], D.m[1][1][ri][3], x[1][2], x[1][3], p);
#pragma unroll
    for (int q = 0; q < 4; q++) { o[ri][q] = p[q]; o[ri][4 + q] = fmaf(2.f, e[q], -p[q]); }
  }
}
__device__ __forceinline__ void dft_a(const uint32_t (&m)[2][2][4], const uint32_t (&x0)[2][4], const uint32_t (&x1)[2][4], float (&o)[2][8]) {
#pragma unroll
  for (int ri = 0; ri < 2; ri++) {
    float z[4] = {0.f, 0.f, 0.f, 0.f}, e[4], p[4];
    mma_dc(e, x0[0][0], x1[0][0], x0[0][1], x1[0][1], m[0][ri][0], m[0][ri][1], z);
    mma_dc(e, x0[0][2], x1[0][2], x0[0][3], x1[0][3], m[0][ri][2], m[0][ri][3], e);
    mma_dc(p, x0[1][0], x1[1][0], x0[1][1], x1[1][1], m[1][ri][0], m[1][ri][1], e);
    mma_dc(p, x0[1][2], x1[1][2], x0[1][3], x1[1][3], m[1][ri][2], m[1][ri][3], p);
#pragma unroll
    for (int q = 0; q < 4; q++) { o[ri][q] = p[q]; o[ri][4 + q] = fmaf(2.f, e[q], -p[q]); }
  }
}
__device__ __forceinline__ uint32_t twid(float re, float im, float c, float s) { return pack2(fmaf(re, c, im * s), fmaf(im, c, -re * s)); }
__device__ __forceinline__ void cpa16(uint32_t d, const void* s) { asm volatile("cp.async.cg.shared.global [%0], [%1], 16;" :: "r"(d), "l"(s) : "memory"); }
__device__ __forceinline__ void sts32(uint32_t a, uint32_t x) { asm volatile("st.shared.u32 [%0], %1;" :: "r"(a), "r"(x) : "memory"); }
__device__ __forceinline__ void cpa_commit() { asm volatile("cp.async.commit_group;" ::: "memory"); }
template <int N> __device__ __forceinline__ void cpa_wait() { asm volatile("cp.async.wait_group %0;" :: "n"(N) : "memory"); }
__device__ __forceinline__ uint32_t lds32(uint32_t a) { uint32_t r; asm volatile("ld.shared.u32 %0, [%1];" : "=r"(r) : "r"(a) : "memory"); return r; }
#define FMID 0
constexpr int F_TP = 4112, F_TSZ = 8 * F_TP;

__device__ __forceinline__ uint32_t ldnc32(const void* p) { uint32_t v; asm volatile("ld.global.nc.b32 %0, [%1];" : "=r"(v) : "l"(p) : "memory"); return v; }
template <class F>
__device__ __forceinline__ void fft_wprep(const bf16* __restrict__ wr, const bf16* __restrict__ wi, int cta, F&& mid) {
  const int tid = threadIdx.x, g = (cta >> 1) & 7, c = (cta >> 4) & 3, t = 2 * (cta & 1) + (tid & 1);
  const int k0 = g + 8 * (cta >> 6) + 32 * (8 * c + 2 * t), l0 = (tid & ~1) + (g & 1);
  uint32_t a[4][4], b[4][4];
#pragma unroll
  for (int q = 0; q < 16; q++) {
    const int o = (k0 + 16 * (q >> 3) + 32 * ((q >> 1) & 1) + 1024 * (q & 1)) * 513 + l0 + 256 * ((q >> 2) & 1);
    a[q >> 2][q & 3] = ldnc32(wr + o);
    b[q >> 2][q & 3] = ldnc32(wi + o);
  }
  const int e = cta * 32 + (tid & 31), lh = (e >> 11) * 512, k = e & 2047, k2 = (k >> 5) & 31;
  uint32_t hz[4];
#pragma unroll
  for (int q = 0; q < 4; q++) asm volatile("ld.global.nc.u16 %0, [%1];" : "=r"(hz[q]) : "l"((q < 2 ? wr : wi) + (q & 1 ? (2048 - k) & 2047 : k) * 513 + lh) : "memory");
  mid();
  uint4* dst = g_wt + l0 * 512 + cta * 2 + (tid & 1);
#pragma unroll
  for (int q = 0; q < 8; q++) {
    const int hf = q >> 1, l = l0 + 256 * (hf & 1) + (q & 1);
    const uint32_t sel = (q & 1) ? 0x7632 : 0x5410;
    if (l & 511) dst[(256 * (hf & 1) + (q & 1)) * 512 + 256 * (q >> 2)] = make_uint4(__byte_perm(a[hf][0], b[hf][0], sel), __byte_perm(a[hf][1], b[hf][1], sel),
                                                                                   __byte_perm(a[hf][2], b[hf][2], sel), __byte_perm(a[hf][3], b[hf][3], sel));
  }
  if (tid < 32) reinterpret_cast<uint32_t*>(g_wt)[(64 * ((k >> 3) & 3) + 16 * (k2 >> 3) + 2 * (k & 7) + ((k2 >> 2) & 1)) * 8 + lh * 2048 + 2 * (k2 & 3) + (k >> 10)] =
      pack2(0.5f * (__uint_as_float(hz[0] << 16) + __uint_as_float(hz[1] << 16)), 0.5f * (__uint_as_float(hz[2] << 16) - __uint_as_float(hz[3] << 16)));
}

template <class F>
__device__ __forceinline__ void fft_rows_fwd(const bf16* __restrict__ x, const bf16* __restrict__ wr, const bf16* __restrict__ wi, uint32_t tb, int it, F&& mid) {
  const int warp = threadIdx.x >> 5, lane = threadIdx.x & 31, g = lane >> 2, t = lane & 3;
  const uint32_t in = tb + warp * 4096;
  const uint32_t f0 = in + (lane >> 3) * 256 + (((lane & 7) ^ (2 * (lane >> 3))) << 4);
  const bf16* src = x + ((256 * (warp & 3) + 64 * (warp >> 2) + 128 * (it & 1) + 32 * ((it >> 4) & 1) + 8 * (it >> 5) + ((it >> 1) & 7)) * 2048 + lane * 8);
#pragma unroll
  for (int q = 0; q < 8; q++) cpa16((f0 ^ ((q >> 2) * 144)) + (q & 3) * 1024, src + q * 256);
  cpa_commit();
  Dft D;
  float2 tw[4][8];
  fft_wprep(wr, wi, it, [&]() {
    if (FMID == 0) mid();
    make_dft<true>(D, g, t);
#pragma unroll
    for (int q = 0; q < 32; q++) {
      tw[q >> 3][q & 7] = cis(fidx<true>((q >> 1) & 3, g) * fidx<false>(q >> 3, 2 * t + (q & 1)), 1024);
      if (FMID) asm volatile("" : "+f"(tw[q >> 3][q & 7].x), "+f"(tw[q >> 3][q & 7].y) :: "memory");
    }
    if (FMID == 1) mid();
  });
  if (FMID == 2) mid();
  cpa_wait<0>(); __syncwarp();
  uint32_t a[4][2][4], y[4][2][4];
#pragma unroll
  for (int q = 0; q < 8; q++) ldsm4t(a[q & 3][q >> 2], (in + lane * 128 + ((lane & 7) << 4)) ^ (q << 4));
  float o[2][8];
#pragma unroll
  for (int i = 0; i < 4; i++) {
    dft_b(D, a[i], o);
#pragma unroll
    for (int q = 0; q < 8; q++) y[q >> 1][q & 1][i] = twid(o[0][q], o[1][q], tw[i][q].x, tw[i][q].y);
  }
  __syncthreads();
  const uint32_t w0 = tb + warp * F_TP + fidx<true>(0, g) * 128 + t * 16 + ((g & 1) << 6), wz = (g & 1) ? -64 : 64;
#pragma unroll
  for (int z = 0; z < 2; z++) {
    float o2[2][8];
    dft_b(D, y[2 * z], o); dft_b(D, y[2 * z + 1], o2);
#pragma unroll
    for (int i = 0; i < 4; i++) {
      const float sg = i < 2 ? 1.f : -1.f;
      sts128(w0 + z * wz + fidx<true>(i, 0) * 128, pack2(o[0][2 * i], sg * o[1][2 * i]), pack2(o[0][2 * i + 1], sg * o[1][2 * i + 1]),
             pack2(o2[0][2 * i], sg * o2[1][2 * i]), pack2(o2[0][2 * i + 1], sg * o2[1][2 * i + 1]));
    }
  }
  __syncthreads();
  const uint32_t ra = tb + (lane & 1) * 4 * F_TP + ((lane >> 1) + 16 * (warp ^ ((warp >> 1) & 1))) * 4;
  uint4* dst = g_y + (threadIdx.x >> 1) * 256 + (lane & 1) + it * 2;
#pragma unroll
  for (int q = 0; q < 8; q++) { const uint32_t r = ra + q * 512; dst[q * 32768] = make_uint4(lds32(r), lds32(r + F_TP), lds32(r + 2 * F_TP), lds32(r + 3 * F_TP)); }
}

template <class F>
__device__ __forceinline__ void fft_cols(uint32_t sb, int cta, int ncta, F&& ready) {
  const int warp = threadIdx.x >> 5, lane = threadIdx.x & 31, g = lane >> 2, t = lane & 3;
  const uint32_t in = sb + warp * 16384 + lane * 16, tab = sb + 131072 + lane * 16;
  auto fetch_y = [&](int l) {
#pragma unroll
    for (int q = 0; q < 16; q++) cpa16(in + q * 512, g_y + (q < 8 ? l : (1024 - l) & 1023) * 256 + (q & 7) * 32 + lane);
  };
  auto fetch_w = [&](int l) {
#pragma unroll
    for (int q = 0; q < 16; q++) cpa16(in + 8192 + q * 512, g_wt + l * 512 + q * 32 + lane);
  };
  const int l0 = cta * 8 + warp, dl = ncta * 8;
  Dft D; make_dft<false>(D, g, t);
#pragma unroll
  for (int q = 2 * warp; q < 2 * warp + 2; q++) {
    const int r = fidx<false>(q & 3, g), c = fidx<false>(q >> 2, 2 * t);
    const float2 w0 = cis(r * c, 1024), w1 = cis(r * c + r, 1024), p0 = cis(r + 32 * c, 2048), p1 = cis(r + 32 * c + 32, 2048);
    sts128(tab + q * 512, __float_as_uint(w0.x), __float_as_uint(w0.y), __float_as_uint(w1.x), __float_as_uint(w1.y));
    sts128(tab + 8192 + q * 512, __float_as_uint(p0.x), __float_as_uint(p0.y), __float_as_uint(p1.x), __float_as_uint(p1.y));
  }
  if (warp == 0) {
#pragma unroll
    for (int q = 0; q < 8; q++) {
      const int v = q >> 2, b = (q >> 1) & 1, ri = q & 1;
      sts128(tab + 16384 + q * 512, D.m[b][0][ri][v], D.m[b][0][ri][v + 2], D.m[b][1][ri][v], D.m[b][1][ri][v + 2]);
    }
  }
  ready();
  fetch_y(l0); cpa_commit();
  fetch_w(l0); cpa_commit();
#pragma unroll 1
  for (int l = l0; l <= 512; l += dl) {
    uint32_t a[2][4][2][4], y[2][4][2][4];
    float o[2][2][8];
    cpa_wait<1>();
#pragma unroll
    for (int q = 0; q < 16; q++) lds128(a[q >> 3][(q >> 1) & 3][q & 1], in + q * 512);
    if (!(l & 511)) {
      const uint32_t m0 = l ? 0x80000000u : 0u;
#pragma unroll
      for (int q = 0; q < 32; q++) { a[0][q >> 3][(q >> 2) & 1][q & 3] ^= m0; a[1][q >> 3][(q >> 2) & 1][q & 3] ^= m0 ^ 0x80000000u; }
    }
    auto first = [&]() {
#pragma unroll
      for (int i = 0; i < 4; i++) {
        dft_b(D, a[0][i], o[0]); dft_b(D, a[1][i], o[1]);
#pragma unroll
        for (int r = 0; r < 4; r++) {
          const float4 w = lds128f(tab + (4 * i + r) * 512);
#pragma unroll
          for (int s = 0; s < 2; s++) {
            y[s][r][0][i] = twid(o[s][0][2 * r], o[s][1][2 * r], w.x, w.y);
            y[s][r][1][i] = twid(o[s][0][2 * r + 1], o[s][1][2 * r + 1], w.z, w.w);
          }
        }
      }
    };
    first();
    if (l + dl <= 512) fetch_y(l + dl);
    cpa_commit();
    cpa_wait<1>();
#pragma unroll
    for (int zv = 0; zv < 4; zv++) {
      const int z = zv >> 1, v = zv & 1;
      uint32_t m[2][2][4];
#pragma unroll
      for (int q = 0; q < 4; q++) lds128(m[q >> 1][q & 1], tab + 16384 + (4 * v + q) * 512);
      dft_a(m, y[0][2 * z], y[0][2 * z + 1], o[0]); dft_a(m, y[1][2 * z], y[1][2 * z + 1], o[1]);
#pragma unroll
      for (int q = 0; q < 4; q++) {
        const int i = 2 * z + (q & 1), c = v + (q & 2);
        uint32_t w[4]; lds128(w, in + 8192 + (4 * i + c) * 512);
        const float4 ph = lds128f(tab + 8192 + (4 * c + i) * 512);
#pragma unroll
        for (int b = 0; b < 2; b++) {
          const float cs = b ? ph.z : ph.x, sn = b ? ph.w : ph.y;
          const float r1 = __uint_as_float(w[2 * b] << 16), i1 = __uint_as_float(w[2 * b] & 0xFFFF0000u);
          const float r2 = __uint_as_float(w[2 * b + 1] << 16), i2 = __uint_as_float(w[2 * b + 1] & 0xFFFF0000u);
          const float Sr = r1 + r2, Si = i1 + i2, Dr = r1 - r2, Di = i1 - i2;
          const float ar = fmaf(-Dr, sn, Sr), ai = fmaf(-Di, sn, Si), dr = fmaf(Dr, sn, Sr), di = fmaf(Di, sn, Si), br = -Di * cs, bi = Dr * cs;
          const float Ar = o[0][0][2 * q + b], Ai = o[0][1][2 * q + b], Br = o[1][0][2 * q + b], Bi = o[1][1][2 * q + b];
          a[0][i][b][c] = pack2(fmaf(ar, Ai, fmaf(ai, Ar, fmaf(br, Bi, bi * Br))), fmaf(ar, Ar, fmaf(-ai, Ai, fmaf(br, Br, -bi * Bi))));
          a[1][i][b][c] = pack2(fmaf(dr, Bi, fmaf(di, Br, fmaf(-br, Ai, -bi * Ar))), fmaf(dr, Br, fmaf(-di, Bi, fmaf(-br, Ar, bi * Ai))));
        }
      }
    }
    if (l + dl <= 512) fetch_w(l + dl);
    cpa_commit();
    first();
#pragma unroll
    for (int s = 0; s < 2; s++) {
      uint4* dst = g_y + (s ? (1024 - l) & 1023 : l) * 256 + lane;
      const float sg = s ? -1.f : 1.f;
#pragma unroll
      for (int i = 0; i < 4; i++) {
        dft_b(D, y[s][i], o[0]);
#pragma unroll
        for (int b = 0; b < 2; b++)
          dst[(2 * i + b) * 32] = make_uint4(pack2(sg * o[0][0][b], o[0][1][b]), pack2(sg * o[0][0][2 + b], o[0][1][2 + b]),
                                             pack2(sg * o[0][0][4 + b], o[0][1][4 + b]), pack2(sg * o[0][0][6 + b], o[0][1][6 + b]));
      }
    }
  }
}

template <class F>
__device__ __forceinline__ void fft_rows_inv(const CUtensorMap* om, uint32_t sb, int cta, int ncta, F&& ready) {
  const int warp = threadIdx.x >> 5, lane = threadIdx.x & 31, g = lane >> 2, t = lane & 3, wg = warp >> 2, w4 = warp & 3;
  const uint32_t tb = sb + 32768 + wg * 2 * F_TSZ;
  const uint4* src = g_y + pin((256 * ((lane >> 1) & 3) + 64 * (lane >> 3) + 8 * w4) * 256 + (lane & 1));
  const uint32_t wa = pin(tb + (lane & 1) * 4 * F_TP + w4 * 1024 + (lane >> 1) * 4);
  uint4 pf[8];
  auto fetch = [&](int it, int hf) {
#pragma unroll
    for (int q = 0; q < 8; q++) pf[q] = __ldcg(src + (it * 2 + hf * 8192) + q * 256);
  };
  auto put = [&](uint32_t off) {
#pragma unroll
    for (int q = 0; q < 8; q++) {
      sts32(wa + off + q * 64, pf[q].x); sts32(wa + off + q * 64 + F_TP, pf[q].y);
      sts32(wa + off + q * 64 + 2 * F_TP, pf[q].z); sts32(wa + off + q * 64 + 3 * F_TP, pf[q].w);
    }
  };
  const int it0 = 2 * cta + wg;
  Dft D; make_dft<false>(D, g, t);
  float2 tw[4][8];
#pragma unroll
  for (int q = 0; q < 32; q++) {
    tw[q >> 3][q & 7] = cis(fidx<false>((q >> 1) & 3, g) * fidx<false>(q >> 3, 2 * t + (q & 1)), 1024);
    tw[q >> 3][q & 7].x *= 1.f / 2097152.f; tw[q >> 3][q & 7].y *= 1.f / 2097152.f;
    asm volatile("" : "+f"(tw[q >> 3][q & 7].x), "+f"(tw[q >> 3][q & 7].y) :: "memory");
  }
  ready();
  fetch(it0, 0); put(0); fetch(it0, 1); put(512);
  const uint32_t la = pin(tb + w4 * F_TP + lane * 16), ob = uni(sb + warp * 4096);
  const uint32_t oa = pin(ob + (lane >> 1) * 128 + (((4 * (lane & 1)) ^ ((lane >> 1) & 7)) << 4));
#pragma unroll 1
  for (int n = 0;; n++) {
    const int it = it0 + (n >> 1) * 2 * ncta, hf = n & 1, buf = (n >> 1) & 1;
    if (it >= 128) break;
    if (!hf) bar_sync(1 + wg, 128);
    uint32_t a[4][2][4], y[4][2][4];
#pragma unroll
    for (int q = 0; q < 8; q++) lds128(a[q >> 1][q & 1], la + buf * F_TSZ + hf * 4 * F_TP + q * 512);
    fetch(min(it + 2 * ncta, 127), hf);
    float o[2][8];
#pragma unroll
    for (int i = 0; i < 4; i++) {
      dft_b(D, a[i], o);
#pragma unroll
      for (int q = 0; q < 8; q++) y[q >> 1][q & 1][i] = twid(o[0][q], o[1][q], tw[i][q].x, tw[i][q].y);
    }
    if (lane == 0) asm volatile("cp.async.bulk.wait_group.read 0;" ::: "memory");
    __syncwarp();
#pragma unroll
    for (int c = 0; c < 4; c++) {
      dft_b(D, y[c], o);
#pragma unroll
      for (int ri = 0; ri < 2; ri++)
        stsm4((oa ^ (c << 4)) + (1 - ri) * 2048, pack2(o[ri][0], o[ri][1]), pack2(o[ri][2], o[ri][3]), pack2(o[ri][4], o[ri][5]), pack2(o[ri][6], o[ri][7]));
    }
    fence_async();
    __syncwarp();
    if (lane == 0) {
      const int m = 256 * w4 + 32 * ((it >> 1) & 7) + 8 * (it >> 5) + 4 * (it & 1) + 2 * hf + ((it >> 4) & 1);
      asm volatile("cp.async.bulk.tensor.3d.global.shared::cta.bulk_group [%0, {0, 0, %2}], [%1];" :: "l"(om), "r"(ob), "r"(2 * m) : "memory");
      asm volatile("cp.async.bulk.commit_group;" ::: "memory");
    }
    put((buf ^ 1) * F_TSZ + hf * 512);
  }
  if (lane == 0) asm volatile("cp.async.bulk.wait_group 0;" ::: "memory");
}
__device__ __forceinline__ void grid_arrive(unsigned* ctr) {
  __syncthreads();
  if (threadIdx.x == 0) { __threadfence(); atomicAdd(ctr, 1u); }
}
__device__ __forceinline__ void grid_wait(unsigned* ctr, unsigned n) {
  if (threadIdx.x == 224) {
    int it = 0;
    while (*reinterpret_cast<volatile unsigned*>(ctr) < n) { __nanosleep(100); if (++it > SPIN_LIMIT) { g_err = 3; break; } }
    __threadfence();
  }
  __syncthreads();
}

struct RecMaps { CUtensorMap wq, wk, wv, wo, x, k, q, v, fo; };
#define NSW 16
#define EXP 0
#define NPB 3
#define NPB0 3
#define NPC 0
#define WOP 2
#define HOME 7
#define DL0 14
#define PD1 4
#define NE4 6
#define NA4 14
#define NA6 18
#define NB1 24
#define TQL 7
#define NQ 16
#define TQP (NQ - 1)
#define OXPOS 4
#define XWPOS 10
#define RI 9
#define RJ 8
#define NPRE 22
#define PFD 4
#define PD0 4
#define VB NV0
#define NPA 0
#define N1 16
#define DL1 16
#define PACE 0
#define RE0 0
#define RE1 0
#define RP1 23
#define X2 2
#define X3 2
#define SPOS 2
#ifndef NV0
#define NV0 4
#endif
#define TGP 3
#define LW0 8
#define X1 4
#define X0 4
constexpr int R_WO = 0, R_X = 65536, R_MEM = 131072, R_WC = 147456, R_RED = R_WC + NSW * 2048, R_O = R_RED, R_S = R_O + 2048, R_P = R_S + 3072, R_STAGE = R_P + 2048,
              R_K = R_STAGE + 8192, R_Q = R_K + 8192, R_V = R_Q + 2048, R_ID = R_V + 16384, R_T = R_ID + 512, R_DST = R_T + 512, R_RD = R_DST + 2048, R_BAR = R_RD + 2048, R_TS = R_BAR + 128,
              R_TOTAL = R_TS;
#define TS(i)
#define LOG(i, v)
constexpr int B_KV = R_BAR, B_W = R_BAR + 8, B_X = R_BAR + 80, B_PK = R_BAR + 24, B_C = R_BAR + 32, B_B = R_BAR + 40, B_DUE = R_BAR + 48, B_ONE = R_BAR + 64;
#define DLY_A 150
#define DLY_V 150
#define DLY_C 200
#define NS_B 1120
#define NS_C 1728
#define NS_P 2624
#define NS_V 128
#define NS_F 896
#define NS_K 128
#define NS_M 32
#define NS_X 128
#define MG_Z 0x00010206
#define MG_Y 0x0001051a
#define NS_PEN 1024
__device__ __forceinline__ float rcp(float x) { float r; asm("rcp.approx.ftz.f32 %0, %1;" : "=f"(r) : "f"(x)); return r; }
__device__ __forceinline__ uint32_t hadd2(uint32_t a, uint32_t b) { uint32_t d; asm("add.rn.bf16x2 %0, %1, %2;" : "=r"(d) : "r"(a), "r"(b)); return d; }
__device__ __forceinline__ void mma_a(float (&d)[4], const uint32_t (&a)[4], uint32_t b0, uint32_t b1) { mma16816(d, a[0], a[1], a[2], a[3], b0, b1); }
__device__ __forceinline__ bool elect() {
  uint32_t p; asm volatile("{.reg .pred p; elect.sync _|p, 0xffffffff; selp.u32 %0, 1, 0, p;}" : "=r"(p)); return p; }
__device__ __forceinline__ void tma3d(uint32_t dst, const CUtensorMap* m, int c1, int c2, uint32_t bar) {
  asm volatile("cp.async.bulk.tensor.3d.shared::cluster.global.mbarrier::complete_tx::bytes [%0], [%1, {0, %3, %4}], [%2];"
    :: "r"(dst), "l"(m), "r"(bar), "r"(c1), "r"(c2) : "memory"); }
template <int OFF, int ACC>
__device__ __forceinline__ void wg_rs32(float (&d)[16], const uint32_t (&a)[4], uint32_t db) {
  if (ACC)
    asm volatile("{.reg .b64 db; .reg .b32 lo; add.u32 lo, %20, %21; mov.b64 db, {lo, 0x40000040};\n"
      "wgmma.mma_async.sync.aligned.m64n32k16.f32.bf16.bf16 {%0,%1,%2,%3,%4,%5,%6,%7,%8,%9,%10,%11,%12,%13,%14,%15}, {%16,%17,%18,%19}, db, 1, 1, 1, 0;}"
      : "+f"(d[0]), "+f"(d[1]), "+f"(d[2]), "+f"(d[3]), "+f"(d[4]), "+f"(d[5]), "+f"(d[6]), "+f"(d[7]), "+f"(d[8]), "+f"(d[9]), "+f"(d[10]), "+f"(d[11]), "+f"(d[12]), "+f"(d[13]), "+f"(d[14]), "+f"(d[15])
      : "r"(a[0]), "r"(a[1]), "r"(a[2]), "r"(a[3]), "r"(db), "n"(OFF));
  else
    asm volatile("{.reg .b64 db; .reg .b32 lo; add.u32 lo, %20, %21; mov.b64 db, {lo, 0x40000040};\n"
      "wgmma.mma_async.sync.aligned.m64n32k16.f32.bf16.bf16 {%0,%1,%2,%3,%4,%5,%6,%7,%8,%9,%10,%11,%12,%13,%14,%15}, {%16,%17,%18,%19}, db, 0, 1, 1, 0;}"
      : "=f"(d[0]), "=f"(d[1]), "=f"(d[2]), "=f"(d[3]), "=f"(d[4]), "=f"(d[5]), "=f"(d[6]), "=f"(d[7]), "=f"(d[8]), "=f"(d[9]), "=f"(d[10]), "=f"(d[11]), "=f"(d[12]), "=f"(d[13]), "=f"(d[14]), "=f"(d[15])
      : "r"(a[0]), "r"(a[1]), "r"(a[2]), "r"(a[3]), "r"(db), "n"(OFF));
}
template <int I> using IC = std::integral_constant<int, I>;
template <int I, int N, class F> __device__ __forceinline__ void sfor(F&& f) {
  if constexpr (I < N) { f(std::integral_constant<int, I>{}); sfor<I + 1, N>(f); }
}
__device__ __forceinline__ void keep(float (&d)[16]) {
  asm volatile("" : "+f"(d[0]), "+f"(d[1]), "+f"(d[2]), "+f"(d[3]), "+f"(d[4]), "+f"(d[5]), "+f"(d[6]), "+f"(d[7]),
      "+f"(d[8]), "+f"(d[9]), "+f"(d[10]), "+f"(d[11]), "+f"(d[12]), "+f"(d[13]), "+f"(d[14]), "+f"(d[15]) :: "memory");
}

template <int N, int S2 = 1024> __device__ __forceinline__ void ldx(uint32_t (&v)[N][4], const uint8_t* p) {
#pragma unroll
  for (int k = 0; k < 2 * N; k++) {
    const int i = k;
    asm volatile("ld.relaxed.gpu.global.v2.b32 {%0,%1}, [%2];" : "=r"(v[i >> 1][2 * (i & 1)]), "=r"(v[i >> 1][2 * (i & 1) + 1]) : "l"(p + (i & 3) * 256 + (i >> 2) * S2) : "memory");
  }
}
__device__ __forceinline__ uint32_t dif2(uint32_t a, uint32_t b, uint32_t tag) { uint32_t r; asm("lop3.b32 %0, %1, %2, %3, 0x7e;" : "=r"(r) : "r"(a), "r"(b), "r"(tag)); return r; }
__device__ __forceinline__ uint32_t dif2v(uint32_t a, uint32_t b, uint32_t tag) { uint32_t r; asm volatile("lop3.b32 %0, %1, %2, %3, 0x7e;" : "=r"(r) : "r"(a), "r"(b), "r"(tag)); return r; }
__device__ __forceinline__ uint32_t or3(uint32_t a, uint32_t b, uint32_t c) { uint32_t r; asm("lop3.b32 %0, %1, %2, %3, 0xfe;" : "=r"(r) : "r"(a), "r"(b), "r"(c)); return r; }
__device__ __forceinline__ uint32_t after(uint32_t x, float f, uint32_t z) { uint32_t r; asm("lop3.b32 %0, %1, %2, %3, 0xea;" : "=r"(r) : "r"(__float_as_uint(f)), "r"(z), "r"(x)); return r; }
__device__ __forceinline__ bool any_bit(uint32_t a, uint32_t b, uint32_t m) {
  uint32_t r; asm("lop3.b32 %0, %1, %2, %3, 0xa8;" : "=r"(r) : "r"(a), "r"(b), "r"(m)); return __any_sync(0xffffffffu, r); }
template <int W, int N> __device__ __forceinline__ bool stale(const uint32_t (&v)[N][4], uint32_t tag) {
  uint32_t x = dif2(v[0][0], v[0][2], tag);
  if (N == 4) x = or3(x, dif2(v[1][0], v[1][2], tag), dif2(v[2 % N][0], v[2 % N][2], tag));
  return any_bit(x, dif2(v[N - 1][0], v[N - 1][2], tag), 1);
}
template <int W, int N, int S2 = 1024> __device__ __forceinline__ void retry(uint32_t (&v)[N][4], const uint8_t* p, uint32_t tag, int& it) {
#pragma unroll 1
  do { ldx<N, S2>(v, p); it += INC_A; } while (stale<W>(v, tag) && it < SPIN_LIMIT);
}
__device__ __forceinline__ void mma_h(float (&d)[4], const uint32_t (&a)[4], const uint32_t (&b)[4], int hf) { mma16816(d, a[0], a[1], a[2], a[3], b[2 * hf], b[2 * hf + 1]); }
__device__ __forceinline__ void sts128(uint32_t a, const uint32_t (&r)[4]) { sts128(a, r[0], r[1], r[2], r[3]); }
__device__ __forceinline__ void sts128f(uint32_t a, const float* r) { sts128(a, __float_as_uint(r[0]), __float_as_uint(r[1]), __float_as_uint(r[2]), __float_as_uint(r[3])); }
__device__ __forceinline__ void mbar_spin(uint32_t bar, uint32_t par, int& it) {
  asm volatile("{.reg .pred p; .reg .b32 par; mov.b32 par, %2;\nLOOP: mbarrier.try_wait.parity.shared::cta.b64 p, [%1], par; @p bra.uni DONE;\n"
               "add.s32 %0, %0, 1; setp.le.s32 p, %0, %3; @p bra.uni LOOP;\nDONE: }" : "+r"(it) : "r"(bar), "r"(par), "n"(SPIN_LIMIT) : "memory"); }
__device__ __forceinline__ void warp_arrive(uint32_t bar) {
  __syncwarp(); asm volatile("{.reg .pred p; elect.sync _|p, 0xffffffff; @p mbarrier.arrive.shared::cta.b64 _, [%0];}" :: "r"(bar) : "memory"); }
__device__ __forceinline__ void delay_until(unsigned t) {
  asm volatile("{.reg .pred p; .reg .b64 c; .reg .b32 lo, hi;\nLOOP: mov.u64 c, %%clock64; mov.b64 {lo, hi}, c; sub.s32 lo, lo, %0; setp.lt.s32 p, lo, 0; @p bra.uni LOOP;}" :: "r"(t) : "memory"); }
__device__ __forceinline__ void zero(float (&c)[4][4]) {
#pragma unroll
  for (int i = 0; i < 4; i++) c[i][0] = c[i][1] = c[i][2] = c[i][3] = 0.f;
}

__device__ __forceinline__ void sched() { asm volatile("griddepcontrol.launch_dependents;" ::: "memory"); }
__device__ __forceinline__ const uint8_t* pinp(const uint8_t* p) { return reinterpret_cast<const uint8_t*>(__shfl_xor_sync(0xffffffffu, reinterpret_cast<unsigned long long>(p), 0)); }
__device__ __forceinline__ uint32_t bar_or(int id, uint32_t x) {
  uint32_t r; asm volatile("{.reg .pred p, q; setp.ne.u32 p, %2, 0; bar.red.or.pred q, %1, 256, p; selp.u32 %0, 1, 0, q;}" : "=r"(r) : "r"(id), "r"(x) : "memory"); return r; }
__device__ __forceinline__ void bar_sync_unless(int id, uint32_t x) { asm volatile("{.reg .pred p; setp.eq.u32 p, %1, 0; @p bar.sync %0, 256;}" :: "r"(id), "r"((uint32_t)x) : "memory"); }
__device__ __forceinline__ void bar_arrive_unless(int id, uint32_t x) { asm volatile("{.reg .pred p; setp.eq.u32 p, %1, 0; @p bar.arrive %0, 256;}" :: "r"(id), "r"((uint32_t)x) : "memory"); }
__device__ __forceinline__ void stsm2t(uint32_t a, uint32_t r0, uint32_t r1, uint32_t x) {
  asm volatile("{.reg .pred p; setp.eq.u32 p, %3, 0; @p stmatrix.sync.aligned.m8n8.x2.trans.shared.b16 [%0], {%1,%2};}" :: "r"(a), "r"(r0), "r"(r1), "r"((uint32_t)x) : "memory"); }
__device__ __forceinline__ uint32_t or_and(uint32_t a, uint32_t b, uint32_t m) { uint32_t r; asm("lop3.b32 %0, %1, %2, %3, 0xa8;" : "=r"(r) : "r"(a), "r"(b), "r"(m)); return r; }
#define rare(x) __builtin_expect(!!(x), 0)
__device__ __forceinline__ uint32_t gtime() { unsigned long long g; asm volatile("mov.u64 %0, %%globaltimer;" : "=l"(g) :: "memory"); return (uint32_t)g; }
__device__ __forceinline__ void wait_time(uint32_t t) {
  asm volatile("{.reg .pred p; .reg .b32 g; .reg .b64 c;\nLOOP: mov.u64 c, %%globaltimer; cvt.u32.u64 g, c; sub.s32 g, %0, g; setp.lt.u32 p, g, 16384; @p bra.uni LOOP;}" :: "r"(t - 1) : "memory"); }
__device__ __forceinline__ uint32_t ldx32(const void* p) { uint32_t v; asm volatile("ld.relaxed.gpu.global.b32 %0, [%1];" : "=r"(v) : "l"(p) : "memory"); return v; }
__device__ __forceinline__ void stx32(const void* p, uint32_t v) { asm volatile("st.relaxed.gpu.global.b32 [%0], %1;" :: "l"(p), "r"(v) : "memory"); }

__global__ void __launch_bounds__(256, 1)
rec_kernel(const __grid_constant__ RecMaps maps, const bf16* __restrict__ xin, const bf16* __restrict__ mem0, Xchg* const gx,
           const bf16* __restrict__ fx, const bf16* __restrict__ wr, const bf16* __restrict__ wi) {
  extern __shared__ __align__(1024) uint8_t smem_raw[];
  const uint32_t sb = smem_u32(smem_raw);
  int role = blockIdx.x;
  {
    uint32_t smid, nsm; asm volatile("mov.u32 %0, %%smid;" : "=r"(smid)); asm volatile("mov.u32 %0, %%nsmid;" : "=r"(nsm));
    const int p = smid >> 1, u = p - 32;
    if (nsm == gridDim.x)
      role = (smid & 1) + (p < 32 ? 4 * ((p & 7) + 8 * (p >> 4)) + 2 * ((p >> 3) & 1) : p < 60 ? 4 * (16 + u % 7 + 7 * (u / 14)) + 2 * ((u / 7) & 1)
                         : p < 62 ? 2 * p + 8 : 2 * p - 4);
    role = uni(role);
  }
  if (role >= 128) {
    fft_cols(sb, role - 128, 4, [&]() { grid_wait(&gx->ctr[33], 128); });
    __threadfence(); __syncwarp();
    if ((threadIdx.x & 31) == 0) atomicAdd(&gx->ctr[32], 1u);
    __syncwarp();
    fft_rows_inv(&maps.fo, sb, role - 128, 4, [&]() { grid_wait(&gx->ctr[32], 32); });
    return;
  }
  const int tid = threadIdx.x, warp = uni(tid >> 5), lane = tid & 31, wg = warp >> 2, w4 = warp & 3, g = lane >> 2, t = lane & 3;
  const int h = role >> 2, j = role & 3, jh = j & 1;
  uint32_t w[48][4];
  float aq[16], av[16];
  int it = 0;

#define PT(k)
  auto pf_wo = [&]() {
    for (int i = 0; i < 4; i++)
      asm volatile("cp.async.bulk.prefetch.tensor.2d.L2.global [%0, {%1, %2}];" :: "l"(&maps.wo), "r"(256 * j + 64 * i), "r"(h * DH) : "memory");
  };
  fft_rows_fwd(fx, wr, wi, sb + R_MEM + 49152, role, [&]() {
    if (tid == 224) {
      mbar_init(sb + B_KV, 1); mbar_init(sb + B_W, 1); mbar_init(sb + B_X, 1); mbar_init(sb + B_X + 8, 1); mbar_init(sb + B_X + 16, 1); mbar_init(sb + B_X + 24, 1); mbar_init(sb + B_C, 4); mbar_init(sb + B_PK, 4); mbar_init(sb + B_B, 1);
      asm volatile("fence.mbarrier_init.release.cluster;" ::: "memory");
      mbar_expect_tx(sb + B_W, 3 * 65536);
      for (int i = 0; i < 4; i++) {
        tma2d(sb + R_X + i * 16384, &maps.wq, h * DH + 32 * j, i * 256, sb + B_W);
        if (i < 3) tma2d(sb + R_MEM + i * 16384, &maps.wk, h * DH + 32 * j, i * 256, sb + B_W);
        else asm volatile("cp.async.bulk.prefetch.tensor.2d.L2.global [%0, {%1, %2}];" :: "l"(&maps.wk), "r"(h * DH + 32 * j), "r"(768) : "memory");
      }
      for (int i = 0; i < 2; i++) tma2d(sb + R_WO + i * 32768, &maps.wv, h * DH + 64 * (j >> 1), jh * 512 + i * 256, sb + B_W);
      if (PFD) asm volatile("cp.async.bulk.prefetch.L2.global [%0], 2048;" :: "l"(xin + role * DM) : "memory");
      else for (int i = 0; i < 4; i++) asm volatile("cp.async.bulk.prefetch.L2.global [%0], 8192;" :: "l"(xin + role * 16384 + i * 4096) : "memory");
      if (WOP == 0) pf_wo();
      for (int i = 0; i < 5; i++) asm volatile("prefetch.tensormap [%0];" :: "l"(&maps.wo + i) : "memory");
    }
    __syncwarp();
  });
  if (tid < 16) sts32(sb + R_T + tid * 4, ~0u);
  fence_async();
  PT(0);
  grid_arrive(&gx->ctr[33]);
  PT(1);
  if (tid == 224) { tma2d(sb + R_MEM + 49152, &maps.wk, h * DH + 32 * j, 768, sb + B_W); if (WOP == 1) pf_wo(); }
  __syncwarp();
  uint8_t* const xb = reinterpret_cast<uint8_t*>(gx);
  auto probe_at = [&](int n) { return xb + (n ? offsetof(Xchg, C) + w4 * 8192 + role * 32 : offsetof(Xchg, B) + role * 8192 + warp * 128); };
  if (lane < 8) stx128(probe_at(lane >> 2) + (lane & 2) * 2048 + (lane & 1) * 16, 0, 0, 0, 0);
  uint32_t m0[4][4];
#pragma unroll
  for (int i = 0; i < 16; i++) m0[i >> 2][i & 3] = ldnc32(mem0 + g * DM + 128 * warp + 8 * i + 2 * t);
  mbar_spin(sb + B_W, 0, it);
  PT(2);
  const int lrow = (lane & 7) + ((lane >> 4) << 3), lhi = (lane >> 3) & 1;
  const int kq = wg ? 3 - 3 * jh : 3 * jh;
  const uint32_t LW = lrow * 128 + ((lhi ^ (lane & 7)) << 4);
  {
    const int chunk = w4 < 2 ? w4 + 2 * lhi : 2 * (w4 & 1) + lhi;
    uint32_t a = sb + (w4 < 2 ? R_X : R_MEM) + kq * 16384 + lrow * 64 + ((chunk ^ ((lrow >> 1) & 3)) << 4);
#pragma unroll
    for (int i = 0; i < 16; i++) ldsm4t(w[i], a + i * 1024);
    const uint32_t st = wg ? 1024 : 2048, av0 = sb + R_WO + (LW ^ (w4 << 5));
    const uint32_t a1 = wg ? a + (2 * jh - 1) * 16384 : av0 + jh * 32768, a2 = wg ? a + (2 * jh - 1) * 32768 : av0 + (1 - jh) * 32768;
#pragma unroll
    for (int i = 0; i < 16; i++) { ldsm4t(w[16 + i], a1 + i * st); ldsm4t(w[32 + i], a2 + i * st); }
  }
  uint32_t L16 = pin(lane * 16);
  const uint32_t uW = uni(sb + w4 * 512), uWo = uni(sb + R_WO + w4 * 16384), uMem = uni(sb + R_MEM + kq * 4096);
  const uint32_t dX = uni(((sb + R_X + kq * 16384) >> 4) | 0x10000u);
  auto load_wo = [&](uint32_t (&d)[32][4], int i0, int i1) {
#pragma unroll
    for (int i = i0; i < i1; i++) lds128(d[i], uWo + L16 + (i & 1) * 512 + (i >> 4) * 1024 + (i & 14) * 1024);
  };
  auto issue_x = [&](int n, int k) {
    const uint32_t bar = sb + B_X + 8 * k, q = k ^ (3 - 3 * jh);
    mbar_expect_tx(bar, 16384); tma3d(sb + R_X + q * 16384, &maps.x, min(n, NSEG - 1) * SEG, 4 * q, bar);
  };
  auto store_stage = [&](int n) {
    asm volatile("cp.async.bulk.global.shared::cta.bulk_group [%0], [%1], 8192; cp.async.bulk.commit_group;"
                 :: "l"(g_kqv[n & 3][role]), "r"(sb + R_STAGE) : "memory");
  };
  auto issue_kqv = [&](int n) {
    const int p = (n & 3) * 128 + 4 * h;
    mbar_expect_tx(sb + B_KV, 26624);
    tma3d(sb + R_K, &maps.k, 0, p, sb + B_KV); tma3d(sb + R_Q, &maps.q, 8 + 2 * j, p, sb + B_KV); tma3d(sb + R_V, &maps.v, 16, p, sb + B_KV);
  };
  auto fetch4k = [&](uint32_t dst, uint32_t off, uint32_t bar, uint32_t t) {
    asm volatile("{.reg .pred p, q; .reg .b32 g; .reg .b64 c; elect.sync _|q, 0xffffffff; @q mbarrier.arrive.expect_tx.shared::cta.b64 _, [%2], 4096;\n"
                 "LOOP: mov.u64 c, %%globaltimer; cvt.u32.u64 g, c; sub.s32 g, %3, g; setp.lt.u32 p, g, 16384; @p bra.uni LOOP;\n"
                 "@q cp.async.bulk.shared::cluster.global.mbarrier::complete_tx::bytes [%0], [%1], 4096, [%2];}" :: "r"(dst), "l"(xb + off), "r"(bar), "r"(t - 1) : "memory");
  };
  uint32_t uS;
  auto my_b = [&]() { return offsetof(Xchg, B) + role * 8192 + ((uS + ((uint32_t)it >> 31)) & 1) * 4096; };
  auto issue_c = [&](uint32_t t) { fetch4k(sb + R_MEM + w4 * 4096, offsetof(Xchg, C) + w4 * 8192 + ((uS + ((uint32_t)it >> 31)) & 4096), sb + B_C, t); };
  auto wait_x = [&](int n, int i) { if (!(EXP & 1) || n < 2) mbar_spin(sb + B_X + 8 * i, n & 1, it); };
#define PACED(d0) uint32_t dz = d0; const uint32_t z = (uint32_t)it >> 31; auto pace = [&]() { for (int k = 0; k < PACE; k++) { if (k & 1) asm("add.u32 %0, %0, %1;" : "+r"(dz) : "r"(z)); else asm("xor.b32 %0, %0, %1;" : "+r"(dz) : "r"(z)); } };
  auto project_v = [&](auto I0, auto I1, auto&& mid) {
    PACED(decltype(I0)::value < 16 ? dX : dX ^ 1024);
    wg_fence();
    sfor<decltype(I0)::value, decltype(I1)::value>([&](auto I) {
      constexpr int i = decltype(I)::value;
      mid(i);
      if (i == 16 && decltype(I0)::value < 16) dz ^= 1024;
      wg_rs32<((i >> 2) & 3) * 256 + (i & 3) * 2, (i > 0)>(av, w[16 + i], dz);
      pace();
    });
    wg_commit();
  };
  auto project_qk = [&](auto I0, auto I1, auto first, auto&& mid) {
    PACED((dX ^ (decltype(I0)::value >> 4 << 10)) + ((uint32_t)it >> 31));
    wg_fence();
    sfor<decltype(I0)::value, decltype(I1)::value>([&](auto I) {
      constexpr int i = decltype(I)::value;
      mid(i);
      wg_rs32<((i >> 2) & 3) * 256 + (i & 3) * 2, !decltype(first)::value || i != decltype(I0)::value>(aq, w[i], dz);
      pace();
    });
    wg_commit();
  };
  const uint32_t uP = uni(sb + R_X + 3 * jh * 16384 + w4 * 512);
  auto park = [&]() {
    bar_sync(1, 128);
#pragma unroll
    for (int i = 0; i < 4; i++) sts128f(uP + L16 + i * 2048, aq + 4 * i);
    warp_arrive(sb + B_PK);
  };
  auto unpark = [&]() {
#pragma unroll
    for (int i = 0; i < 4; i++) {
      const float4 p = lds128f(uP + L16 + i * 2048);
      av[4 * i] = p.x; av[4 * i + 1] = p.y; av[4 * i + 2] = p.z; av[4 * i + 3] = p.w;
    }
  };
  auto fin_qk = [&]() {
#pragma unroll
    for (int i = 0; i < 16; i++) aq[i] += av[i];
    const uint32_t a = sb + R_STAGE + (w4 < 2 ? 2048 + w4 * 128 : (w4 & 1) * 256) + (L16 & 112) + (L16 >> 7) * 512;
    stsm4t(a, pack2(aq[0], aq[1]), pack2(aq[4], aq[5]), pack2(aq[8], aq[9]), pack2(aq[12], aq[13]));
    stsm4t(a + (w4 < 2 ? 256 : 128), pack2(aq[2], aq[3]), pack2(aq[6], aq[7]), pack2(aq[10], aq[11]), pack2(aq[14], aq[15]));
  };
  auto fin_v = [&]() {
#pragma unroll
    for (int a = 0; a < 2; a++)
      sts128(sb + R_STAGE + 4096 + w4 * 1024 + a * 512 + L16, pack2(av[8 * a], av[8 * a + 1]), pack2(av[8 * a + 2], av[8 * a + 3]),
             pack2(av[8 * a + 4], av[8 * a + 5]), pack2(av[8 * a + 6], av[8 * a + 7]));
  };
  __syncthreads();
  if (tid == 224) {
#pragma unroll 1
    for (int i = 0; i < 4; i++) issue_x(0, i);
    mbar_expect_tx(sb + B_W, 65536);
    for (int i = 0; i < 4; i++) tma2d(sb + R_WO + i * 16384, &maps.wo, 256 * j + 64 * i, h * DH, sb + B_W);
  }
  __syncwarp();
  if (wg) {
#pragma unroll
    for (int i = 0; i < NSW; i++) sts128(uW + R_WC + L16 + i * 2048, w[i]);
  }
#pragma unroll
  for (int i = 0; i < 4; i++) sts128(sb + R_MEM + warp * 2048 + i * 512 + (g >> 1) * 128 + t * 32 + (g & 1) * 16, m0[i]);
  auto probe = [&](int n, int cnt) {
    if (lane == 0) {
#pragma unroll 1
      for (int i = role >> 7; i < cnt; i++) {
        const int k = (i ^ wg) & 1;
        const unsigned t0 = clk();
        uint32_t v; asm volatile("atom.relaxed.gpu.global.exch.b32 %0, [%1], 0;" : "=r"(v) : "l"(probe_at(n) + k * 4096) : "memory");
        if (v == 0) asm volatile("red.shared.min.u32 [%0], %1;" :: "r"(sb + R_T + (n ? w4 * 8 : 32) + k * 4), "r"(clk() - t0) : "memory");
      }
    }
    __syncwarp();
  };
#pragma unroll 1
  for (int n = 0; n < 2; n++) {
    probe(0, n ? NPB : NPB0);
    asm volatile("{.reg .pred p; cp.async.bulk.wait_group 0; setp.eq.u32 p, %1, 97; @p red.relaxed.gpu.global.add.u32 [%0], 1;}" :: "l"(&gx->ctr[h]), "r"(tid ^ n ^ (1 - n) << 9) : "memory");
    PT(3 + 3 * n);
    wait_x(n, 2);
    PT(4 + 3 * n);
    if (wg == 0) {
      wait_x(n, 3);
      project_qk(IC<0>{}, IC<16>{}, IC<1>{}, [](int) {});
      project_v(IC<0>{}, IC<32>{}, [](int) {});
      wg_wait<0>(); keep(aq); keep(av);
      park();
      fin_v();
      fence_async();
    } else {
      wait_x(n, 0); wait_x(n, 1);
      project_qk(IC<32>{}, IC<48>{}, IC<1>{}, [](int) {});
      project_qk(IC<16>{}, IC<32>{}, IC<0>{}, [](int) {});
      project_qk(IC<0>{}, IC<16>{}, IC<0>{}, [](int) {});
      mbar_spin(sb + B_PK, n, it);
      unpark();
      wg_wait<0>(); keep(aq);
      fin_qk();
      fence_async();
    }
    __syncthreads();
    if (tid == 0 && n) stx32(&gx->S[role], 1 + (HOME & 2 && lds32(sb + R_T + 36) < lds32(sb + R_T + 32)));
    PT(5 + 3 * n);
    if (tid == 96 && n == 0) store_stage(0);
    if (tid == 128 && n == 0) {
#pragma unroll 1
      for (int i = 0; i < 4; i++) issue_x(1, i);
    }
    if (warp == 5 && n == 1) {
#pragma unroll 1
      while (__any_sync(0xffffffffu, ldx32(&gx->ctr[h]) < 4) && ++it < SPIN_LIMIT) {}
      if (elect()) issue_kqv(0);
    }
    __syncwarp();
  }
  mbar_spin(sb + B_W, 1, it);
  PT(9);
#pragma unroll
  for (int i = 0; i < 4; i++) {
    uint32_t f[4][4];
    const uint32_t a = sb + R_WO + warp * 8192 + i * 2048;
#pragma unroll
    for (int q = 0; q < 4; q++) ldsm4t(f[q], a + (LW ^ (q << 5)));
    __syncwarp();
#pragma unroll
    for (int q = 0; q < 4; q++) sts128(a + q * 512 + L16, f[q]);
  }
  if (NPC) probe(1, NPC);
  {
    const int o = 32 * w4 + 16 * wg + 4 * t + j;
    uint32_t v;
#pragma unroll 1
    while (__any_sync(0xffffffffu, (v = ldx32(&gx->S[o])) == 0) && ++it < SPIN_LIMIT) {}
    asm volatile("st.shared.u64 [%0], %1;" :: "r"(sb + R_DST + wg * 1024 + w4 * 256 + lane * 8), "l"(xb + offsetof(Xchg, B) + o * 8192 + (v >> 1) * 4096 + h * 128 + ((g ^ h) & 7) * 16) : "memory");
  }
  if (wg == 0) {
    const uint64_t cd = reinterpret_cast<uint64_t>(xb + (offsetof(Xchg, C) + j * 8192 + h * 128 + w4 * 32 + (L16 & 16) * 256 + (L16 & 64) / 4 + (L16 >> 7) * 4));
    sts128(uW + R_RD + L16, (uint32_t)cd, (uint32_t)(cd >> 32), sb + R_MEM + (L16 & 112) * 8 + (L16 >> 8) * 1024 + ((w4 * 32 + ((L16 >> 3) & 16)) ^ (L16 & 112)),
           (L16 >> 6) == (h & 3) * 2 + ((h >> 2) & 1) ? 0xFFFE0000u : 0xFFFFFFFFu);
  }
  if (tid == 0) sts32(sb + B_DUE + 8, gtime() & ~31u);
  PT(10);
  mbar_spin(sb + B_KV, 0, it);
  PT(11);
  if (tid < 4) sts32(sb + B_ONE + tid * 4, 0x3F803F80u);
  if (warp == 1) { const uint32_t e = g >> 1 == t ? 0x3F80u << (16 * (g & 1)) : 0u; sts128(sb + R_ID + L16, e, 0, 0, e); }
  __syncthreads();
  {
    const uint32_t kb = lds32(sb + R_T + 36) < lds32(sb + R_T + 32);
    uS = uni((HOME & 4 ? (__popc(((offsetof(Xchg, B) / 4096 + 2 * role) ^ (offsetof(Xchg, C) / 4096 + 2 * w4)) & 0xb3) ^ kb) & 1 : lds32(sb + R_T + w4 * 8 + 4) < lds32(sb + R_T + w4 * 8)) * 4096 + kb);
  }

  const float sc = 0.08838834764831845f * 1.4426950408889634f;
  uint8_t* const xa = xb + uni(h * 16384);
  const uint32_t uA = uni(wg ? (w4 >> 1) * 2048 + j * 512 + (w4 & 1) * 256 : 8192 + (4 * (j >> 1) + w4) * 512 + jh * 256);
  const uint32_t uP2 = uni(sb + R_P + w4 * 256);
  uint32_t nc = 1;
  uint32_t ma;
  const uint8_t* adst;
  auto pin_mem = [&]() { adst = pinp(xa + uA + L16 / 2); ma = pin(uMem + (L16 & 384) + (L16 & 48) * 2 + (L16 & 64) / 4); };
  pin_mem();

#pragma unroll 1
  for (int s = 0;; nc++) {
    const uint32_t tag = (s + 1) & 1;
    auto fresh = [&]() { L16 += (uint32_t)it >> 31; };
    auto get_due = [&]() { return lds32(sb + B_DUE + 4 + tag * 4); };
    float c[4][4], r4[4];
    auto fold = [&]() {
#pragma unroll
      for (int i = 0; i < 4; i++) r4[i] = ((c[0][i] + c[1][i]) + c[2][i]) + c[3][i];
    };
    auto mma4 = [&](int n, const uint32_t (&b0)[4], const uint32_t (&b1)[4]) {
      mma_h(c[0], w[n + 2], b1, 0); mma_h(c[1], w[n + 3], b1, 1); mma_h(c[2], w[n], b0, 0); mma_h(c[3], w[n + 1], b0, 1);
    };
    auto xpos = [&](int pos, int wp) {
      if ((pos == X0 || pos == X1 || pos == X2 || pos == X3) && warp == wp && s + 1 < NSEG && elect()) {
        const int z = (uint32_t)it >> 31;
        if (pos == X2) issue_x(s + 2, 2 + z);
        if (pos == X3) issue_x(s + 2, 3 + z);
        if (pos == X1) issue_x(s + 2, 1 + z);
        if (pos == X0) issue_x(s + 2, z);
      }
      __syncwarp();
    };
    if (wg == 0) {
      mbar_spin(sb + B_C, nc & 1, it);
      TS(13);
      uint32_t b[16][4], tg[4];
#pragma unroll
      for (int i = 0; i < PD0; i++) { lds128(b[i], ma + i * 512); __syncwarp(); }
      sched();
      zero(c);
#pragma unroll
      for (int i = 0; i < 8; i++) {
        const int k = i ^ 1;
        mma_h(c[0], w[2 * k], b[k], 0); mma_h(c[1], w[2 * k + 1], b[k], 1);
        if (i < 2 * NV0) { mma_h(c[2], w[16 + 2 * k], b[k], 0); mma_h(c[3], w[17 + 2 * k], b[k], 1); }
        sched();
        if ((i & 1) && i + PD0 < 9) { lds128(b[i + PD0 - 1], ma + (i + PD0 - 1) * 512); __syncwarp(); lds128(b[i + PD0], ma + (i + PD0) * 512); sched(); }
        if (i == TGP) {
          fresh();
#pragma unroll
          for (int k = 0; k < 4; k++) tg[k] = lds32((uW * 4 + L16) * 2 + (L16 >> 6) * 4 + (R_MEM + k * 1024 - 7 * sb));
          sched();
        }
      }
#pragma unroll
      for (int i = 0; i < 4; i++) { r4[i] = c[0][i] + c[1][i]; c[0][i] = c[1][i] = 0.f; }
      sts128f(uW + R_RED + L16, r4);
      TS(1);
      const uint32_t old = bar_or(4, (dif2(tg[0], tg[1], s) | dif2(tg[2], tg[3], s)) & (s > 0));
      TS(0);
#pragma unroll
      for (int i = 0; i < 2 * NV0; i++) { lds128(b[8 + i], (ma ^ 4096) + i * 512); __syncwarp(); }
      sched();
#pragma unroll
      for (int i = NV0; i < 8; i++) {
        if (VB && i == VB) bar_sync(7, 256);
        mma4(16 + 4 * i, b[2 * i], b[2 * i + 1]);
        if (i < 7) sched();
        if (i < 4) { lds128(b[8 + 2 * i], (ma ^ 4096) + i * 1024); __syncwarp(); lds128(b[9 + 2 * i], (ma ^ 4096) + i * 1024 + 512); sched(); }
      }
      fold();
      asm volatile("{.reg .pred p; setp.eq.u32 p, %3, 0; @p st.relaxed.gpu.global.v2.b32 [%0], {%1,%2};}" :: "l"(adst), "r"((pack2(r4[0], r4[1]) & ~1u) | tag), "r"(pack2(r4[2], r4[3])), "r"(old) : "memory");
      sched();
      const unsigned tpub = clk();
      if (__any_sync(0xffffffffu, old) && nc < NC_MAX) {
        bar_sync(3, 256);
        issue_c(gtime());
        continue;
      }
      TS(3);
      xpos(0, 0);
      const uint32_t due = get_due();
      uint32_t vf[4][4], vm[2][4], p[4], pm, o[4];
      const uint32_t va = sb + R_V + (w4 >> 1) * 8192 + (w4 & 1) * 2048 + L16;
#pragma unroll
      for (int i = 0; i < 4; i++) {
        uint32_t q[4]; lds128(vf[i], va + i * 512); lds128(q, va + 4096 + i * 512);
#pragma unroll
        for (int e = 0; e < 4; e++) vf[i][e] = hadd2(vf[i][e], q[e]);
      }
      const uint32_t pa = pin(sb + R_P + (L16 >> 1));
      const uint8_t* vsrc = pinp(xa + 8192 + w4 * 1024 + L16 / 2);
      uint32_t one[4];
      lds128(one, sb + B_ONE);
      auto pv_x = [&]() {
        zero(c);
        mma_a(c[2], one, p[0], p[1]);
        mma_a(c[0], vf[0], p[0], p[1]); mma_a(c[1], vf[2], p[0], p[1]);
        sched();
        mma_a(c[2], one, p[2], p[3]);
        mma_a(c[0], vf[1], p[2], p[3]); mma_a(c[1], vf[3], p[2], p[3]);
        sched();
      };
      auto pv_m = [&]() {
        mma1688(c[2], one[0], one[1], pm);
        mma_a(c[0], vm[0], pm, pm);
        sched();
        mma_a(c[1], vm[1], pm, pm);
      };
      auto norm = [&]() {
        const float n0 = rcp(c[2][0]), n1 = rcp(c[2][1]);
#pragma unroll
        for (int i = 0; i < 4; i++) o[i] = pack2(c[i >> 1][2 * (i & 1)] * n0, c[i >> 1][2 * (i & 1) + 1] * n1);
        return ((__float_as_uint(c[2][0]) - 0x1F800000u) | (__float_as_uint(c[2][1]) - 0x1F800000u)) >> 30;
      };
      auto load_m = [&](int x) { const float2 e0 = lds64f(pa + 512 + x * 1024), e1 = lds64f(pa + 768 + x * 1024); pm = pack2(e0.x * e1.x, e0.y * e1.y); };
      auto attend_max = [&](int x) {
        float2 sv[6];
#pragma unroll
        for (int i = 0; i < 6; i++) sv[i] = lds64f(pa - 3072 + x * 1536 + i * 256);
        sv[4].x += sv[5].x; sv[4].y += sv[5].y;
        const int dq = (int)(L16 >> 6) - (int)((L16 >> 3) & 6) + 8 * j;
        float m = fmaxf(sv[4].x, sv[4].y);
#pragma unroll
        for (int i = 0; i < 4; i++) {
          if (x && 8 * i > dq) sv[i].x = -INFINITY;
          if (x && 8 * i + 1 > dq) sv[i].y = -INFINITY;
          m = fmaxf(m, fmaxf(sv[i].x, sv[i].y));
        }
        m = fmaxf(m, __shfl_xor_sync(0xffffffffu, m, 1));
        m = fmaxf(m, __shfl_xor_sync(0xffffffffu, m, 2));
#pragma unroll
        for (int i = 0; i < 5; i++) (i < 4 ? p[i] : pm) = pack2(ex2(sv[i].x - m), ex2(sv[i].y - m));
        pv_x(); pv_m(); norm();
      };
      uint32_t tq[4];
      auto get_t = [&]() {
        tq[0] = tq[1] = tq[2] = tq[3] = 0;
        asm volatile("{.reg .pred p; setp.eq.u32 p, %5, 0; @p ld.relaxed.gpu.global.v4.b32 {%0,%1,%2,%3}, [%4];}"
                     : "+r"(tq[0]), "+r"(tq[1]), "+r"(tq[2]), "+r"(tq[3]) : "l"(xb + offsetof(Xchg, T) + L16 * 8), "r"(warp) : "memory");
      };
      delay_until(tpub + DLY_V);
      wait_time(due + NS_V);
      TS(4);
      ldx(vm, vsrc);
      sched();
      xpos(2, 2);
      auto store_kqv = [&]() {
        fence_async();
        if (!(EXP & 4))
          asm volatile("{.reg .pred p; elect.sync _|p, 0xffffffff; @p cp.async.bulk.global.shared::cta.bulk_group [%0], [%1], 2048; cp.async.bulk.commit_group;}"
                       :: "l"(g_kqv[(s + 1) & 3][role] + w4 * 128), "r"(sb + R_STAGE + w4 * 2048) : "memory");
      };
      if (SPOS == 2) store_kqv();
      sched();
      bar_sync(5, 256);
      ldsm4(p, sb + R_P + L16);
      load_m(0);
      pv_x();
      ldsm4(p, sb + R_P + 1024 + L16);
      pv_m();
      const uint32_t r = norm(), tl = after(tag, c[2][0], (uint32_t)it >> 31);
      const bool redo = __any_sync(0xffffffffu, r | ((dif2(vm[0][0], vm[0][2], tl) | dif2(vm[1][0], vm[1][2], tl)) & 1));
      TS(6);
      stsm4t(uW + R_O + L16, o[0], o[1], o[2], o[3]);
      bar_arrive_unless(6, redo);
      sched();
      if (TQL == 7) get_t();
      TS(7);
      pv_x();
      if (rare(redo)) retry<2>(vm, vsrc, tag, it);
      bar_sync(8, 256);
      load_m(1);
      pv_m();
      if (rare(__any_sync(0xffffffffu, norm()) || redo)) {
        fresh();
#pragma unroll 1
        for (int x = !redo; x < 2; x++) {
          attend_max(x);
          if (x == 0) { stsm4t(uW + R_O + L16, o[0], o[1], o[2], o[3]); bar_arrive(6, 256); }
        }
      }
      TS(8);
      if (TQL == 8) get_t();
      const bool xok = mbar_test(sb + B_X + 16, s & 1) & mbar_test(sb + B_X + 24, s & 1);
      xpos(4, 2);
      fresh();
      const uint32_t ob = uni(sb + R_MEM + 4096 + w4 * 1024);
      stsm4t(ob + (L16 & 112) * 4 + (((L16 >> 3) ^ (L16 >> 1)) & 48), o[0], o[1], o[2], o[3]);
      __syncwarp();
      uint32_t rd[4];
      lds128(rd, uW + R_RD + L16);
      lds128(o, ob + (L16 ^ ((L16 >> 3) & 48)));
      auto put_o = [&]() {
        *reinterpret_cast<uint4*>(reinterpret_cast<uint8_t*>(g_ox) + (((s * SEG + 8 * j) * HD + h * DH + 32 * w4) * 2 + (L16 >> 6) * (HD * 2) + (L16 & 48))) = make_uint4(o[0], o[1], o[2], o[3]);
      };
      if (s + 1 == NSEG) { put_o(); asm volatile("cp.async.bulk.wait_group 0;" ::: "memory"); break; }
      asm volatile("cp.async.bulk.wait_group 0;" ::: "memory");
      if (elect()) stx32(xa + 4096 + j * 16 + w4 * 4, s + 1);
      __syncwarp();
      if (rare(!xok)) { wait_x(s + 2, 3); wait_x(s + 2, 2); }
      TS(9);
      fresh();
      const uint32_t e = due | ((s + 1) & 31);
      project_qk(IC<0>{}, IC<NQ>{}, IC<1>{}, [&](int n) {
        if (n == OXPOS) { __syncwarp(); put_o(); __syncwarp(); }
        if (n == TQP) { __syncwarp(); tq[0] = dif2v(tq[0], tq[1], e) | dif2v(tq[2], tq[3], e); __syncwarp(); }
      });
      if (NPA) project_v(IC<0>{}, IC<NPA>{}, [](int) {});
      TS(2);
      if (warp == 0) {
        uint32_t last = due, nx = NS_P;
        if (rare(__any_sync(0xffffffffu, tq[0]))) {
          const uint32_t ref = gtime();
#pragma unroll 1
          do ldx128(o, xb + offsetof(Xchg, T) + L16 * 8); while (any_bit(or3(o[0] - s - 1, o[1] - s - 1, o[2] - s - 1), o[3] - s - 1, 30) && ++it < SPIN_LIMIT);
          const int d = max(max((int)(o[0] - ref), (int)(o[1] - ref)), max((int)(o[2] - ref), (int)(o[3] - ref)));
          last = (ref + __reduce_max_sync(0xffffffffu, d)) & ~31u;
          if (last != due) nx += NS_X;
        }
        const uint32_t bdue = last + NS_B;
        if (s < 4) { last += (MG_Y >> 8 * s & 255) * 32; nx += (MG_Z >> 8 * s & 255) * 32; }
        sts32(sb + B_DUE, last);
        sts32(sb + B_DUE + 8 - tag * 4, last + nx);
        fetch4k(sb + R_MEM, my_b(), sb + B_B, bdue);
        LOG(13, tl - last);
        LOG(9, last);
      }
      if (NQ < 16) project_qk(IC<NQ>{}, IC<16>{}, IC<0>{}, [](int) {});
      project_v(IC<NPA>{}, IC<NPRE>{}, [](int) {});
      const uint32_t ba = rd[2], msk = rd[3];
      const uint8_t* cdst = reinterpret_cast<const uint8_t*>(rd[0] | (uint64_t)rd[1] << 32);
      TS(14);
      mbar_spin(sb + B_B, s & 1, it);
      TS(10);
      uint32_t bq[2][4];
      auto sum_b = [&]() {
        ldsm4t(bq[0], ba); ldsm4t(bq[1], ba + 2048);
        sched();
#pragma unroll
        for (int i = 0; i < 8; i++) c[i >> 2][i & 3] = 0.f;
        mma_a(c[0], bq[0], 0x3F803F80u, 0x3F803F80u); mma_a(c[1], bq[1], 0x3F803F80u, 0x3F803F80u);
        const uint32_t t2 = tag * 0x10001u;
        const bool old = any_bit(or3(dif2(bq[0][0], bq[0][1], t2), dif2(bq[0][2], bq[0][3], t2), dif2(bq[1][0], bq[1][1], t2)), dif2(bq[1][2], bq[1][3], t2), L16 < 64 ? 0x10001u : 0u);
        const uint32_t T = (tag << 16) & ~msk, u = ((__float_as_uint(c[0][0] + c[1][0]) + ((0x10000u & ~msk) - T)) & msk) | T;
        asm volatile("{.reg .pred p; setp.eq.u32 p, %2, 0; @p st.relaxed.gpu.global.b32 [%0], %1;}"
                     :: "l"(cdst), "r"(pack2(__uint_as_float(u), c[0][2] + c[1][2])), "r"((uint32_t)(old || (L16 & 32))) : "memory");
        return old;
      };
      if (rare(sum_b())) {
#pragma unroll 1
        do {
          const uint8_t* p = xb + (my_b() + (ba - sb - R_MEM));
          ldx128(bq[0], p); ldx128(bq[1], p + 2048);
          sts128(ba, bq[0]); sts128(ba + 2048, bq[1]);
          __syncwarp();
          it += INC_B;
        } while (sum_b() && it < SPIN_LIMIT);
      }
      sched();
      TS(11);
      bar_arrive(0, 256);
      const unsigned tc = clk();
      const uint32_t cdue = lds32(sb + B_DUE) + NS_C;
      if (warp == 3) LOG(11, gtime() - cdue);
      fresh();
      wg_wait<0>(); keep(aq); keep(av);
      park();
      if (NPRE < 32) project_v(IC<NPRE>{}, IC<32>{}, [](int) {}); else fin_v();
      TS(12);
      delay_until(tc + DLY_C);
      issue_c(cdue);
      TS(5);
      LOG(warp, it);
      pin_mem();
      if (NPRE < 32) { wg_wait<0>(); keep(av); fin_v(); }
      if (!(EXP & 2)) mbar_spin(sb + B_KV, tag, it);
      TS(15);
    } else {
      uint32_t kf[8][4];
      auto load_k = [&]() {
        const uint32_t ka = sb + R_K + w4 * 1024 + (L16 & 112) + (L16 & 128) * 4 + (L16 & 256);
#pragma unroll
        for (int i = 0; i < 8; i++) ldsm4(kf[i], ka + (i >> 1) * 2048 + (i & 1) * 128);
      };
      auto put_p = [&](int x, uint32_t old, uint32_t again) {
        float e[4];
        const int dq = (int)((L16 >> 3) & 6) + 8 * j - (int)(L16 >> 6) - 16 * w4;
#pragma unroll
        for (int i = 0; i < 4; i++) { r4[i] = fmaf(c[3][i], sc, fmaf(c[2][i], sc, fmaf(c[0][i] + c[1][i], sc, __uint_as_float(i == 3 ? 0u - old : 0u)))); e[i] = x && dq + (i & 1) < 8 * (i >> 1) ? 0.f : ex2(r4[i]); }
        stsm2t(uP2 + x * 1024 + L16, pack2(e[0], e[1]), pack2(e[2], e[3]), again);
      };
      auto put_s = [&](int x) {
#pragma unroll
        for (int i = 0; i < 4; i++) sts32f(uW + R_S + x * 1536 + (L16 & 48) * 4 + (L16 >> 6) * 4 + (i & 1) * 32 + (i >> 1) * 256, r4[i]);
      };
      auto load_q = [&](uint32_t (&q)[4], uint32_t off) { ldsm4(q, sb + R_Q + (L16 & 112) + (L16 & 128) * 2 + (L16 >> 8) * 128 + off); };
      mbar_spin(sb + B_C, nc & 1, it);
      TS(13);
      float4 o4;
      uint32_t id[4], old;
      {
        uint32_t b[24][4];
#pragma unroll
        for (int i = 0; i < 2 * PD1; i++) { lds128(b[i], ma + i * 512); __syncwarp(); }
        sched();
        zero(c);
#pragma unroll
        for (int i = 0; i < 12; i++) {
          mma4(4 * i, b[2 * i], b[2 * i + 1]);
          if (i < 11) sched();
          if (i + PD1 < 12) { const int k = i + PD1; const uint32_t a = (ma ^ (k >> 2 << 12)) + (k & 3) * 1024; lds128(b[2 * k], a); __syncwarp(); lds128(b[2 * k + 1], a + 512); sched(); }
          if (i == RJ) { lds128(id, sb + R_ID + L16); sched(); }
          if (i == RI) { old = bar_or(4, 0); o4 = lds128f(uW + R_RED + L16); sched(); }
        }
      }
      TS(0);
      {
        float e[4] = {o4.x, o4.y, o4.z, o4.w};
#pragma unroll
        for (int i = 0; i < 4; i++) { r4[i] = (((e[i] + c[0][i]) + c[1][i]) + c[2][i]) + c[3][i]; e[i] = 0.f; }
        mma_a(e, id, pack2(r4[0], r4[1]), pack2(r4[2], r4[3]));
        sched();
        if (VB) bar_arrive(7, 256);
        sched();
        asm volatile("{.reg .pred p; setp.eq.u32 p, %3, 0; @p st.relaxed.gpu.global.v2.b32 [%0], {%1,%2};}" :: "l"(adst),
                     "r"((__byte_perm(__float_as_uint(e[0]), __float_as_uint(e[1]), 0x7632) & ~1u) | tag), "r"(__byte_perm(__float_as_uint(e[2]), __float_as_uint(e[3]), 0x7632)), "r"(old) : "memory");
        sched();
      }
      const unsigned tpub = clk(), now = gtime(), due = get_due();
      if (__any_sync(0xffffffffu, old) && nc < NC_MAX) { bar_sync(3, 256); continue; }
      TS(2);
      const uint8_t* asrc = pinp(adst + ((warp == 7) * 1024 - (int)uA));
      fresh();
      uint32_t wo[32][4];
      bool xok;
      auto reload = [&]() {
        sched();
#pragma unroll
        for (int i = RE0 + RE1; i < NSW; i++) lds128(w[i], uW + R_WC + L16 + i * 2048);
        sched();
      };
      auto out_proj = [&]() {
        uint32_t b[4][4];
        float d[4][4];
        uint8_t* dst[2];
        const uint32_t da = pin(uP2 + (R_DST - R_P) + L16 / 2);
        sched();
        TS(7);
        bar_sync(6, 256);
#pragma unroll
        for (int i = 0; i < 4; i++) { ldsm4(b[i], sb + R_O + i * 512 + L16); __syncwarp(); }
        sched();
        auto put_b = [&](uint8_t* a, const float (&e)[4][4]) {
          stx128(a, (pack2(e[0][0] + e[2][0], e[0][1] + e[2][1]) & ~1u) | tag, pack2(e[0][2] + e[2][2], e[0][3] + e[2][3]),
                 pack2(e[1][0] + e[3][0], e[1][1] + e[3][1]), pack2(e[1][2] + e[3][2], e[1][3] + e[3][3]));
        };
        zero(c); zero(d);
#pragma unroll
        for (int i = 0; i < 32; i++) {
          mma_h(i < 16 ? c[i & 3] : d[i & 3], wo[i], b[(i >> 2) & 3], (i >> 1) & 1);
          if (i >= LW0 && NB1 + i - LW0 < 32) { load_wo(wo, (NB1 + i - LW0) ^ 1, ((NB1 + i - LW0) ^ 1) + 1); __syncwarp(); }
          if (i == DL0 || i == DL1) asm volatile("ld.shared.u64 %0, [%1];" : "=l"(dst[i > DL0]) : "r"(da + (i > DL0) * 1024) : "memory");
          if (i >= 16 && i < 16 + RE0) { lds128(w[i - 16], uW + R_WC + L16 + (i - 16) * 2048); __syncwarp(); }
          if (i >= RP1 && i < RP1 + RE1) { lds128(w[i - RP1 + RE0], uW + R_WC + L16 + (i - RP1 + RE0) * 2048); __syncwarp(); }
          if (i == 22) put_b(dst[0], c);
          if ((i & 1) && (i < 20 || i > 22)) sched();
        }
        put_b(dst[1], d);
        sched();
        TS(6);
      };
      if (warp < 6) {
        delay_until(tpub + DLY_A);
        const int it0 = it;
        bool redo;
#pragma unroll 1
        do {
          uint32_t q[4][4], y[4];
          float d[4][4];
          wait_time(due);
          TS(4);
          ldx(q, asrc);
          sched();
          load_k();
          uint32_t qx[4][4];
#pragma unroll
          for (int i = 0; i < 4; i++) load_q(qx[i], i * 512);
          sched();
          load_wo(wo, 0, NE4);
          sched();
          zero(c);
#pragma unroll
          for (int i = 0; i < 8; i++) mma_h(c[i & 3], kf[i], qx[i >> 1], i & 1);
          put_p(1, 0, 0); put_s(1);
          sched();
          load_wo(wo, NE4, NA4);
          sched();
          zero(c); zero(d);
#pragma unroll
          for (int i = 0; i < 8; i++) {
            if (i == 0) { y[0] = dif2v(q[0][0], q[0][2], q[1][0]); sched(); }
            if (i == 3) { y[1] = dif2v(q[1][2], q[2][0], q[2][2]); sched(); }
            if (i == 6) { y[2] = dif2v(q[3][0], q[3][2], tag); sched(); }
            mma_h(i % 6 < 2 ? c[2 + i % 6] : d[i - 2], kf[i], q[i >> 1], i & 1);
            if (i == 2 || i == 5 || i == 7) sched();
          }
          y[0] = or_and(or3(y[0], y[1], dif2v(q[0][0], q[2][0], tag)), y[2], it < SPIN_LIMIT);
#pragma unroll
          for (int i = 0; i < 4; i++) { c[0][i] = d[0][i] + d[1][i]; c[1][i] = d[2][i] + d[3][i]; }
          put_p(0, y[0], it - it0);
          TS(5);
          bar_sync_unless(5, it - it0);
          redo = __any_sync(0xffffffffu, y[0]);
          it += INC_A;
        } while (redo);
        it -= INC_A;
        put_s(0);
        bar_arrive(8, 256);
        load_wo(wo, NA4, NB1);
        out_proj();
        if (warp == 4) LOG(12, tb);
      } else {
        uint32_t qx[2][4], q[4][4];
        if (warp == 6) {
          const uint32_t t1 = (now & ~31u) + NS_M;
          LOG(10, now - due);
          if (elect()) stx32(&gx->T[h][j], ((int)(t1 - due) > 0 ? t1 + NS_PEN : due) | ((s + 1) & 31));
          __syncwarp();
        }
        auto score = [&](const uint32_t (&a0)[4], const uint32_t (&a1)[4]) {
          zero(c);
#pragma unroll
          for (int i = 0; i < 4; i++) mma_h(c[i], i < 2 ? a0 : a1, q[2 + (i >> 1)], i & 1);
        };
        auto put_m = [&](uint32_t a, uint32_t old, uint32_t again) {
#pragma unroll
          for (int i = 0; i < 2; i++) { r4[i] = fmaf(c[3][2 + i], sc, fmaf((c[0][i] + c[1][2 + i]) + c[2][i], sc, __uint_as_float(i ? 0u - old : 0u))); r4[2 + i] = fmaf(r4[i] * 0x1p122f, 0.f, ex2(r4[i])); }
          asm volatile("{.reg .pred p; setp.eq.u32 p, %3, 0; @p st.shared.v2.f32 [%0], {%1,%2};}" :: "r"(a), "f"(r4[2]), "f"(r4[3]), "r"(again) : "memory");
        };
        delay_until(tpub + DLY_A);
        const uint32_t sa = sb + R_S + 512 + w4 * 256 + (L16 >> 1);
        const int it0 = it;
        bool redo;
#pragma unroll 1
        do {
          wait_time(due);
          TS(4);
          ldx<4, 2048>(q, asrc);
          sched();
          load_q(qx[0], (w4 & 1) * 1024); load_q(qx[1], (w4 & 1) * 1024 + 512);
          load_wo(wo, 0, NA6);
          sched();
          score(q[0], q[1]);
          sched();
          const uint32_t y = or_and(or3(dif2v(q[0][0], q[0][2], tag), dif2v(q[1][0], q[1][2], tag), dif2v(q[2][0], q[2][2], tag)), dif2v(q[3][0], q[3][2], tag), it < SPIN_LIMIT);
          put_m(sa + 2560, y, it - it0);
          TS(5);
          bar_arrive_unless(5, it - it0);
          redo = __any_sync(0xffffffffu, y);
          it += INC_A;
        } while (redo);
        it -= INC_A;
        sts64f(sa, r4[0], r4[1]);
        score(qx[0], qx[1]);
        put_m(sa + 3584, 0, 0);
        sts64f(sa + 1536, r4[0], r4[1]);
        bar_arrive(8, 256);
        load_wo(wo, NA6, NB1);
        out_proj();
      }
      TS(8);
      if (s + 1 == NSEG) break;
      wait_x(s + 2, 2);
      TS(9);
      fresh();
      if (N1) project_qk(IC<32>{}, IC<32 + N1>{}, IC<1>{}, [](int) {});
      TS(10);
      xpos(6, 6);
      uint32_t fl = s + 1;
      if (warp == 5) { wait_time(due + NS_F); fl = ldx32(xa + 4096 + ((L16 >> 2) & 60)); }
      reload();
      TS(14);
      pin_mem();
      wait_x(s + 2, 1); wait_x(s + 2, 0);
      if (warp == 5) {
#pragma unroll 1
        while (__any_sync(0xffffffffu, fl != s + 1) && !(EXP & 4) && ++it < SPIN_LIMIT) fl = ldx32(xa + 4096 + ((L16 >> 2) & 60));
        wait_time(due + (NS_B + NS_K));
        if (!(EXP & 2) && elect()) issue_kqv(s + 1);
        __syncwarp();
      }
      if (PFD && warp == 6 && s + PFD < NSEG && elect())
        asm volatile("cp.async.bulk.prefetch.L2.global [%0], 2048;" :: "l"(xin + ((s + PFD) * SEG + ((role + 4 * (role >> 5)) & 31)) * DM) : "memory");
      __syncwarp();
      TS(11);
      LOG(warp, it);
      if (warp == 4) LOG(8, nc);
      bar_sync(0, 256);
      if (N1 < 16) project_qk(IC<32 + N1>{}, IC<48>{}, IC<!N1>{}, [](int) {});
      project_qk(IC<16>{}, IC<32>{}, IC<0>{}, [&](int n) { if ((n & 15) == XWPOS) { __syncwarp(); xok = mbar_test(sb + B_PK, s & 1); __syncwarp(); } });
      if (rare(!xok)) mbar_spin(sb + B_PK, s & 1, it);
      unpark();
      project_qk(IC<0>{}, IC<16>{}, IC<0>{}, [](int) {});
      TS(12);
      wg_wait<0>(); keep(aq);
      TS(1);
      fin_qk();
      TS(15);
    }
    s++;
  }
  if (it >= SPIN_LIMIT || nc >= NC_MAX) g_err = 2;
}

typedef CUresult (*EncodeFn)(CUtensorMap*, CUtensorMapDataType, cuuint32_t, void*, const cuuint64_t*, const cuuint64_t*, const cuuint32_t*,
                             const cuuint32_t*, CUtensorMapInterleave, CUtensorMapSwizzle, CUtensorMapL2promotion, CUtensorMapFloatOOBfill);
static void make_map(EncodeFn fn, CUtensorMap* m, const void* p, uint64_t cols, uint64_t rows, uint64_t pitch, uint32_t bc, uint32_t br, CUtensorMapSwizzle sw) {
  cuuint64_t dims[2] = {cols, rows}, strides[1] = {pitch * 2};
  cuuint32_t box[2] = {bc, br}, es[2] = {1, 1};
  fn(m, CU_TENSOR_MAP_DATA_TYPE_BFLOAT16, 2, const_cast<void*>(p), dims, strides, box, es, CU_TENSOR_MAP_INTERLEAVE_NONE, sw,
     CU_TENSOR_MAP_L2_PROMOTION_L2_256B, CU_TENSOR_MAP_FLOAT_OOB_FILL_NONE);
}

extern "C" void kernel_launch(void* const* d_in, const int* in_sizes, int n_in, void* d_out, int out_size) {
  const bf16* Ax = (const bf16*)d_in[0]; const bf16* mem0 = (const bf16*)d_in[1];
  const bf16* Wq = (const bf16*)d_in[2]; const bf16* Wk = (const bf16*)d_in[3]; const bf16* Wv = (const bf16*)d_in[4];
  const bf16* Wo = (const bf16*)d_in[5];
  const bf16* Bx = (const bf16*)d_in[7]; const bf16* wr = (const bf16*)d_in[8]; const bf16* wi = (const bf16*)d_in[9];
  bf16* out = (bf16*)d_out;

  void* fp = nullptr; cudaDriverEntryPointQueryResult qr;
  cudaGetDriverEntryPoint("cuTensorMapEncodeTiled", &fp, cudaEnableDefault, &qr);
  EncodeFn fn = (EncodeFn)fp;
  void *kqv, *ox, *xr;
  cudaGetSymbolAddress(&xr, g_xraw);
  cudaGetSymbolAddress(&kqv, g_kqv); cudaGetSymbolAddress(&ox, g_ox);
  const CUtensorMapSwizzle S128 = CU_TENSOR_MAP_SWIZZLE_128B, S64 = CU_TENSOR_MAP_SWIZZLE_64B;

  GemmMaps m3; RecMaps mr;
  make_map(fn, &m3.a, ox, HD, S_LEN, HD, 64, 128, S128);
  make_map(fn, &m3.b[0], Wo, DM, HD, DM, 64, 64, S128);
  m3.b[1] = m3.b[0]; m3.b[2] = m3.b[0];
  make_map(fn, &m3.c, out, DM, S_LEN, 2 * DM, 64, 64, S128);
  make_map(fn, &mr.wq, Wq, HD, DM, HD, 32, 256, S64);
  make_map(fn, &mr.wk, Wk, HD, DM, HD, 32, 256, S64);
  make_map(fn, &mr.wv, Wv, HD, DM, HD, 64, 256, S128);
  make_map(fn, &mr.wo, Wo, DM, HD, DM, 64, 128, S128);
  {
    cuuint64_t dims[3] = {64, S_LEN, 16}, strides[2] = {DM * 2, 128};
    cuuint32_t box[3] = {64, 32, 4}, es[3] = {1, 1, 1};
    fn(&mr.x, CU_TENSOR_MAP_DATA_TYPE_BFLOAT16, 3, const_cast<bf16*>(Ax), dims, strides, box, es, CU_TENSOR_MAP_INTERLEAVE_NONE, S128,
       CU_TENSOR_MAP_L2_PROMOTION_L2_256B, CU_TENSOR_MAP_FLOAT_OOB_FILL_NONE);
  }
  for (int i = 0; i < 3; i++) {
    cuuint64_t dims[3] = {128, 32, 512}, strides[2] = {256, 8192};
    cuuint32_t box[3] = {128, i == 0 ? 8u : i == 1 ? 2u : 16u, 4}, es[3] = {1, 1, 1};
    fn(i == 0 ? &mr.k : i == 1 ? &mr.q : &mr.v, CU_TENSOR_MAP_DATA_TYPE_BFLOAT16, 3, kqv, dims, strides, box, es, CU_TENSOR_MAP_INTERLEAVE_NONE,
       CU_TENSOR_MAP_SWIZZLE_NONE, CU_TENSOR_MAP_L2_PROMOTION_L2_256B, CU_TENSOR_MAP_FLOAT_OOB_FILL_NONE);
  }
  {
    cuuint64_t dims[3] = {64, 16, S_LEN}, strides[2] = {128, 2 * DM * 2};
    cuuint32_t box[3] = {64, 16, 2}, es[3] = {1, 1, 1};
    fn(&mr.fo, CU_TENSOR_MAP_DATA_TYPE_BFLOAT16, 3, out + DM, dims, strides, box, es, CU_TENSOR_MAP_INTERLEAVE_NONE, S128,
       CU_TENSOR_MAP_L2_PROMOTION_NONE, CU_TENSOR_MAP_FLOAT_OOB_FILL_NONE);
  }
  constexpr int SM3 = GST * 32768 + 256 + 1024;
  cudaFuncSetAttribute(gemm_kernel<128, GST>, cudaFuncAttributeMaxDynamicSharedMemorySize, SM3);
  cudaFuncSetAttribute(rec_kernel, cudaFuncAttributeMaxDynamicSharedMemorySize, R_TOTAL);

  cudaStream_t st = cudaStreamPerThread;
  Xchg* gx = reinterpret_cast<Xchg*>((reinterpret_cast<uintptr_t>(xr) + 0x1FFFFF) & ~(uintptr_t)0x1FFFFF);
  rec_kernel<<<132, 256, R_TOTAL, st>>>(mr, Ax, mem0, gx, Bx, wr, wi);
  gemm_kernel<128, GST><<<128, 384, SM3, st>>>(m3, 16, 8, 64, 8, reinterpret_cast<uint4*>(gx));
}
```

```cpp
#include <cuda_runtime.h>
#include <cuda_bf16.h>
#include <cuda.h>
#include <stdint.h>
#include <stddef.h>
#include <type_traits>

typedef __nv_bfloat16 bf16;

constexpr int S_LEN = 2048, DM = 1024, NH = 32, DH = 128, MEM = 8, SEG = 32, NSEG = 64;
constexpr int HD = NH * DH;
#define SPIN 20
constexpr int SPIN_LIMIT = 1 << SPIN, INC_A = 1, INC_B = 1;

constexpr unsigned NC_MAX = 4096;
__device__ __align__(1024) uint4 g_kqv[4][128][512];
__device__ __align__(1024) bf16 g_ox[(size_t)S_LEN * HD];
struct Xchg {
  uint4 A[32][4][256];
  uint4 C[4][2][256];
  uint4 B[128][2][256];
  uint32_t T[32][32];
  uint32_t S[128];
  unsigned ctr[64];
};
__device__ __align__(1024) uint4 g_xraw[(sizeof(Xchg) + (1 << 21)) / 16];
__device__ __align__(1024) uint4 g_y[1024 * 256];
__device__ __align__(1024) uint4 g_wt[513 * 512];
__device__ int g_err;

__device__ __forceinline__ unsigned clk() { unsigned long long c; asm volatile("mov.u64 %0, %%clock64;" : "=l"(c)); return (unsigned)c; }
__device__ __forceinline__ uint32_t smem_u32(const void* p) { return (uint32_t)__cvta_generic_to_shared(p); }
__device__ __forceinline__ void mbar_init(uint32_t bar, int cnt) { asm volatile("mbarrier.init.shared::cta.b64 [%0], %1;" :: "r"(bar), "r"(cnt) : "memory"); }
__device__ __forceinline__ void mbar_expect_tx(uint32_t bar, int bytes) { asm volatile("mbarrier.arrive.expect_tx.shared::cta.b64 _, [%0], %1;" :: "r"(bar), "r"(bytes) : "memory"); }
__device__ __forceinline__ void mbar_arrive_cluster(uint32_t bar, int cta) {
  asm volatile("{.reg .b32 r; mapa.shared::cluster.u32 r, %0, %1; mbarrier.arrive.shared::cluster.b64 _, [r];}" :: "r"(bar), "r"(cta) : "memory"); }
__device__ __forceinline__ bool mbar_try(uint32_t bar, int par) {
  uint32_t ok; asm volatile("{.reg .pred p; mbarrier.try_wait.parity.shared::cta.b64 p, [%1], %2; selp.u32 %0, 1, 0, p;}" : "=r"(ok) : "r"(bar), "r"(par) : "memory"); return ok; }
__device__ __forceinline__ bool mbar_test(uint32_t bar, int par) {
  uint32_t ok; asm volatile("{.reg .pred p; mbarrier.test_wait.parity.shared::cta.b64 p, [%1], %2; selp.u32 %0, 1, 0, p;}" : "=r"(ok) : "r"(bar), "r"(par) : "memory"); return ok; }
__device__ __forceinline__ void mbar_wait(uint32_t bar, int par) {
  int it = 0;
  while (!mbar_try(bar, par)) { if (++it > SPIN_LIMIT) { g_err = 1; break; } }
}
__device__ __forceinline__ void tma2d(uint32_t dst, const CUtensorMap* m, int c0, int c1, uint32_t bar) {
  asm volatile("cp.async.bulk.tensor.2d.shared::cluster.global.mbarrier::complete_tx::bytes [%0], [%1, {%3, %4}], [%2];"
    :: "r"(dst), "l"(m), "r"(bar), "r"(c0), "r"(c1) : "memory"); }
__device__ __forceinline__ void tma2d_mc(uint32_t dst, const CUtensorMap* m, int c0, int c1, uint32_t bar, uint16_t mask) {
  asm volatile("cp.async.bulk.tensor.2d.shared::cluster.global.mbarrier::complete_tx::bytes.multicast::cluster [%0], [%1, {%3, %4}], [%2], %5;"
    :: "r"(dst), "l"(m), "r"(bar), "r"(c0), "r"(c1), "h"(mask) : "memory"); }
__device__ __forceinline__ void tma2d_store(const CUtensorMap* m, uint32_t src, int c0, int c1) {
  asm volatile("cp.async.bulk.tensor.2d.global.shared::cta.bulk_group [%0, {%2, %3}], [%1];" :: "l"(m), "r"(src), "r"(c0), "r"(c1) : "memory"); }
__device__ __forceinline__ void fence_async() { asm volatile("fence.proxy.async.shared::cta;" ::: "memory"); }
__device__ __forceinline__ void bar_sync(int id, int n) { asm volatile("bar.sync %0, %1;" :: "r"(id), "r"(n) : "memory"); }
__device__ __forceinline__ void bar_arrive(int id, int n) { asm volatile("bar.arrive %0, %1;" :: "r"(id), "r"(n) : "memory"); }
__device__ __forceinline__ uint32_t pack2(float lo, float hi) { uint32_t r; asm("cvt.rn.bf16x2.f32 %0, %1, %2;" : "=r"(r) : "f"(hi), "f"(lo)); return r; }
__device__ __forceinline__ void ldsm4(uint32_t (&r)[4], uint32_t a) {
  asm volatile("ldmatrix.sync.aligned.m8n8.x4.shared.b16 {%0,%1,%2,%3}, [%4];" : "=r"(r[0]), "=r"(r[1]), "=r"(r[2]), "=r"(r[3]) : "r"(a) : "memory"); }
__device__ __forceinline__ void ldsm4t(uint32_t (&r)[4], uint32_t a) {
  asm volatile("ldmatrix.sync.aligned.m8n8.x4.trans.shared.b16 {%0,%1,%2,%3}, [%4];" : "=r"(r[0]), "=r"(r[1]), "=r"(r[2]), "=r"(r[3]) : "r"(a) : "memory"); }
__device__ __forceinline__ void stsm4(uint32_t a, uint32_t r0, uint32_t r1, uint32_t r2, uint32_t r3) {
  asm volatile("stmatrix.sync.aligned.m8n8.x4.shared.b16 [%0], {%1,%2,%3,%4};" :: "r"(a), "r"(r0), "r"(r1), "r"(r2), "r"(r3) : "memory"); }
__device__ __forceinline__ void stsm4t(uint32_t a, uint32_t r0, uint32_t r1, uint32_t r2, uint32_t r3) {
  asm volatile("stmatrix.sync.aligned.m8n8.x4.trans.shared.b16 [%0], {%1,%2,%3,%4};" :: "r"(a), "r"(r0), "r"(r1), "r"(r2), "r"(r3) : "memory"); }
__device__ __forceinline__ void lds128(uint32_t (&r)[4], uint32_t a) {
  asm volatile("ld.shared.v4.u32 {%0,%1,%2,%3}, [%4];" : "=r"(r[0]), "=r"(r[1]), "=r"(r[2]), "=r"(r[3]) : "r"(a) : "memory"); }
__device__ __forceinline__ float4 lds128f(uint32_t a) { float4 r;
  asm volatile("ld.shared.v4.f32 {%0,%1,%2,%3}, [%4];" : "=f"(r.x), "=f"(r.y), "=f"(r.z), "=f"(r.w) : "r"(a) : "memory"); return r; }
__device__ __forceinline__ float2 lds64f(uint32_t a) { float2 r;
  asm volatile("ld.shared.v2.f32 {%0,%1}, [%2];" : "=f"(r.x), "=f"(r.y) : "r"(a) : "memory"); return r; }
__device__ __forceinline__ void sts128(uint32_t a, uint32_t r0, uint32_t r1, uint32_t r2, uint32_t r3) {
  asm volatile("st.shared.v4.u32 [%0], {%1,%2,%3,%4};" :: "r"(a), "r"(r0), "r"(r1), "r"(r2), "r"(r3) : "memory"); }
__device__ __forceinline__ void sts64f(uint32_t a, float x, float y) { asm volatile("st.shared.v2.f32 [%0], {%1,%2};" :: "r"(a), "f"(x), "f"(y) : "memory"); }
__device__ __forceinline__ void sts32f(uint32_t a, float x) { asm volatile("st.shared.f32 [%0], %1;" :: "r"(a), "f"(x) : "memory"); }
__device__ __forceinline__ void mma16816(float (&d)[4], uint32_t a0, uint32_t a1, uint32_t a2, uint32_t a3, uint32_t b0, uint32_t b1) {
  asm volatile("mma.sync.aligned.m16n8k16.row.col.f32.bf16.bf16.f32 {%0,%1,%2,%3}, {%4,%5,%6,%7}, {%8,%9}, {%0,%1,%2,%3};"
    : "+f"(d[0]), "+f"(d[1]), "+f"(d[2]), "+f"(d[3]) : "r"(a0), "r"(a1), "r"(a2), "r"(a3), "r"(b0), "r"(b1)); }
__device__ __forceinline__ void mma1688(float (&d)[4], uint32_t a0, uint32_t a1, uint32_t b0) {
  asm volatile("mma.sync.aligned.m16n8k8.row.col.f32.bf16.bf16.f32 {%0,%1,%2,%3}, {%4,%5}, {%6}, {%0,%1,%2,%3};"
    : "+f"(d[0]), "+f"(d[1]), "+f"(d[2]), "+f"(d[3]) : "r"(a0), "r"(a1), "r"(b0)); }
__device__ __forceinline__ void ldx128(uint32_t (&r)[4], const void* p) {
  asm volatile("{.reg .b128 t; .reg .b64 a, b; ld.relaxed.gpu.global.b128 t, [%4]; mov.b128 {a, b}, t; mov.b64 {%0,%1}, a; mov.b64 {%2,%3}, b;}"
    : "=r"(r[0]), "=r"(r[1]), "=r"(r[2]), "=r"(r[3]) : "l"(p) : "memory"); }
__device__ __forceinline__ void stx128(void* p, uint32_t r0, uint32_t r1, uint32_t r2, uint32_t r3) {
  asm volatile("{.reg .b128 t; .reg .b64 a, b; mov.b64 a, {%1,%2}; mov.b64 b, {%3,%4}; mov.b128 t, {a, b}; st.relaxed.gpu.global.b128 [%0], t;}"
    :: "l"(p), "r"(r0), "r"(r1), "r"(r2), "r"(r3) : "memory"); }
__device__ __forceinline__ uint32_t uni(uint32_t x) { return __shfl_sync(0xffffffffu, x, 0); }
__device__ __forceinline__ uint32_t pin(uint32_t x) { return __shfl_xor_sync(0xffffffffu, x, 0); }
__device__ __forceinline__ float ex2(float x) { float r; asm("ex2.approx.ftz.f32 %0, %1;" : "=f"(r) : "f"(x)); return r; }
__device__ __forceinline__ void wg_fence() { asm volatile("wgmma.fence.sync.aligned;" ::: "memory"); }
__device__ __forceinline__ void wg_commit() { asm volatile("wgmma.commit_group.sync.aligned;" ::: "memory"); }
template <int N> __device__ __forceinline__ void wg_wait() { asm volatile("wgmma.wait_group.sync.aligned %0;" :: "n"(N) : "memory"); }

__device__ __forceinline__ void wgmma_ss_n256_tb1(float (&d)[128], uint64_t da, uint64_t db, int sc) {
  asm volatile("{.reg .pred p; setp.ne.b32 p, %130, 0;\n"
    "wgmma.mma_async.sync.aligned.m64n256k16.f32.bf16.bf16 {%0,%1,%2,%3,%4,%5,%6,%7,%8,%9,%10,%11,%12,%13,%14,%15,%16,%17,%18,%19,%20,%21,%22,%23,%24,%25,%26,%27,%28,%29,%30,%31,%32,%33,%34,%35,%36,%37,%38,%39,%40,%41,%42,%43,%44,%45,%46,%47,%48,%49,%50,%51,%52,%53,%54,%55,%56,%57,%58,%59,%60,%61,%62,%63,%64,%65,%66,%67,%68,%69,%70,%71,%72,%73,%74,%75,%76,%77,%78,%79,%80,%81,%82,%83,%84,%85,%86,%87,%88,%89,%90,%91,%92,%93,%94,%95,%96,%97,%98,%99,%100,%101,%102,%103,%104,%105,%106,%107,%108,%109,%110,%111,%112,%113,%114,%115,%116,%117,%118,%119,%120,%121,%122,%123,%124,%125,%126,%127}, %128, %129, p, 1, 1, 0, 1;}\n"
    : "+f"(d[0]),"+f"(d[1]),"+f"(d[2]),"+f"(d[3]),"+f"(d[4]),"+f"(d[5]),"+f"(d[6]),"+f"(d[7]),"+f"(d[8]),"+f"(d[9]),"+f"(d[10]),"+f"(d[11]),"+f"(d[12]),"+f"(d[13]),"+f"(d[14]),"+f"(d[15]),"+f"(d[16]),"+f"(d[17]),"+f"(d[18]),"+f"(d[19]),"+f"(d[20]),"+f"(d[21]),"+f"(d[22]),"+f"(d[23]),"+f"(d[24]),"+f"(d[25]),"+f"(d[26]),"+f"(d[27]),"+f"(d[28]),"+f"(d[29]),"+f"(d[30]),"+f"(d[31]),"+f"(d[32]),"+f"(d[33]),"+f"(d[34]),"+f"(d[35]),"+f"(d[36]),"+f"(d[37]),"+f"(d[38]),"+f"(d[39]),"+f"(d[40]),"+f"(d[41]),"+f"(d[42]),"+f"(d[43]),"+f"(d[44]),"+f"(d[45]),"+f"(d[46]),"+f"(d[47]),"+f"(d[48]),"+f"(d[49]),"+f"(d[50]),"+f"(d[51]),"+f"(d[52]),"+f"(d[53]),"+f"(d[54]),"+f"(d[55]),"+f"(d[56]),"+f"(d[57]),"+f"(d[58]),"+f"(d[59]),"+f"(d[60]),"+f"(d[61]),"+f"(d[62]),"+f"(d[63]),"+f"(d[64]),"+f"(d[65]),"+f"(d[66]),"+f"(d[67]),"+f"(d[68]),"+f"(d[69]),"+f"(d[70]),"+f"(d[71]),"+f"(d[72]),"+f"(d[73]),"+f"(d[74]),"+f"(d[75]),"+f"(d[76]),"+f"(d[77]),"+f"(d[78]),"+f"(d[79]),"+f"(d[80]),"+f"(d[81]),"+f"(d[82]),"+f"(d[83]),"+f"(d[84]),"+f"(d[85]),"+f"(d[86]),"+f"(d[87]),"+f"(d[88]),"+f"(d[89]),"+f"(d[90]),"+f"(d[91]),"+f"(d[92]),"+f"(d[93]),"+f"(d[94]),"+f"(d[95]),"+f"(d[96]),"+f"(d[97]),"+f"(d[98]),"+f"(d[99]),"+f"(d[100]),"+f"(d[101]),"+f"(d[102]),"+f"(d[103]),"+f"(d[104]),"+f"(d[105]),"+f"(d[106]),"+f"(d[107]),"+f"(d[108]),"+f"(d[109]),"+f"(d[110]),"+f"(d[111]),"+f"(d[112]),"+f"(d[113]),"+f"(d[114]),"+f"(d[115]),"+f"(d[116]),"+f"(d[117]),"+f"(d[118]),"+f"(d[119]),"+f"(d[120]),"+f"(d[121]),"+f"(d[122]),"+f"(d[123]),"+f"(d[124]),"+f"(d[125]),"+f"(d[126]),"+f"(d[127])
    : "l"(da), "l"(db), "r"(sc));
}

__device__ __forceinline__ void wgmma_ss_n128_tb1(float (&d)[64], uint64_t da, uint64_t db, int sc) {
  asm volatile("{.reg .pred p; setp.ne.b32 p, %66, 0;\n"
    "wgmma.mma_async.sync.aligned.m64n128k16.f32.bf16.bf16 {%0,%1,%2,%3,%4,%5,%6,%7,%8,%9,%10,%11,%12,%13,%14,%15,%16,%17,%18,%19,%20,%21,%22,%23,%24,%25,%26,%27,%28,%29,%30,%31,%32,%33,%34,%35,%36,%37,%38,%39,%40,%41,%42,%43,%44,%45,%46,%47,%48,%49,%50,%51,%52,%53,%54,%55,%56,%57,%58,%59,%60,%61,%62,%63}, %64, %65, p, 1, 1, 0, 1;}\n"
    : "+f"(d[0]),"+f"(d[1]),"+f"(d[2]),"+f"(d[3]),"+f"(d[4]),"+f"(d[5]),"+f"(d[6]),"+f"(d[7]),"+f"(d[8]),"+f"(d[9]),"+f"(d[10]),"+f"(d[11]),"+f"(d[12]),"+f"(d[13]),"+f"(d[14]),"+f"(d[15]),"+f"(d[16]),"+f"(d[17]),"+f"(d[18]),"+f"(d[19]),"+f"(d[20]),"+f"(d[21]),"+f"(d[22]),"+f"(d[23]),"+f"(d[24]),"+f"(d[25]),"+f"(d[26]),"+f"(d[27]),"+f"(d[28]),"+f"(d[29]),"+f"(d[30]),"+f"(d[31]),"+f"(d[32]),"+f"(d[33]),"+f"(d[34]),"+f"(d[35]),"+f"(d[36]),"+f"(d[37]),"+f"(d[38]),"+f"(d[39]),"+f"(d[40]),"+f"(d[41]),"+f"(d[42]),"+f"(d[43]),"+f"(d[44]),"+f"(d[45]),"+f"(d[46]),"+f"(d[47]),"+f"(d[48]),"+f"(d[49]),"+f"(d[50]),"+f"(d[51]),"+f"(d[52]),"+f"(d[53]),"+f"(d[54]),"+f"(d[55]),"+f"(d[56]),"+f"(d[57]),"+f"(d[58]),"+f"(d[59]),"+f"(d[60]),"+f"(d[61]),"+f"(d[62]),"+f"(d[63])
    : "l"(da), "l"(db), "r"(sc));
}

template <int BN> struct WG;
template <> struct WG<256> { static __device__ __forceinline__ void mma(float (&d)[128], uint64_t a, uint64_t b, int sc) { wgmma_ss_n256_tb1(d, a, b, sc); } };
template <> struct WG<128> { static __device__ __forceinline__ void mma(float (&d)[64], uint64_t a, uint64_t b, int sc) { wgmma_ss_n128_tb1(d, a, b, sc); } };

#define GST 7
#define GA0 2
#define GMAP 7
struct GemmMaps { CUtensorMap a, b[3], c; };
template <int BN, int STAGES>
__global__ void __cluster_dims__(2, 1, 1) __launch_bounds__(384, 1)
gemm_kernel(const __grid_constant__ GemmMaps maps, int tilesM, int tilesN, int kblocks, int nPerB, uint4* __restrict__ clearX) {
  extern __shared__ __align__(1024) uint8_t smem_raw[];
  constexpr int STAGE_BYTES = 16384 + BN * 128;
  constexpr int NBOX = BN / 64;
  const uint32_t sbase = (smem_u32(smem_raw) + 1023) & ~1023u;
  const uint32_t sBar = sbase + STAGES * STAGE_BYTES;
  const int warp = threadIdx.x >> 5, lane = threadIdx.x & 31, wg = warp >> 2;
  uint32_t crank; asm("mov.u32 %0, %%cluster_ctarank;" : "=r"(crank));
#define GT(k)
  const int cl = ((blockIdx.x >> 1) - (GMAP & 4)) & 63, cu = cl - 32;
  const int npairs = (tilesM >> 1) * tilesN, pair0 = !GMAP || cl < 32 ? cl : cl < 60 ? cu % 7 + (GMAP & 1) + 8 * (4 + cu / 7) : 7 * (~GMAP & 1) + 8 * (cl - 56), pstep = gridDim.x >> 1;
  if (threadIdx.x == 256) {
    asm volatile("prefetch.tensormap [%0];" :: "l"(&maps.b[0]) : "memory");
    for (int i = 0; i < STAGES; i++) { mbar_init(sBar + 8 * i, 1); mbar_init(sBar + 8 * (STAGES + i), 4); }
    asm volatile("fence.mbarrier_init.release.cluster;" ::: "memory");
    asm volatile("barrier.cluster.arrive.relaxed;" ::: "memory");
    for (int i = 0; i < GA0; i++) {
      mbar_expect_tx(sBar + 8 * i, STAGE_BYTES);
      tma2d(sbase + i * STAGE_BYTES, &maps.a, i * 64, ((pair0 % (tilesM >> 1)) * 2 + crank) * 128, sBar + 8 * i);
    }
    asm volatile("prefetch.tensormap [%0];" :: "l"(&maps.c) : "memory");
  } else asm volatile("barrier.cluster.arrive.relaxed;" ::: "memory");
  asm volatile("barrier.cluster.wait.acquire;" ::: "memory");
  __syncwarp();
  if (wg == 2) {
    asm volatile("setmaxnreg.dec.sync.aligned.u32 40;");
    if (warp > 8) {
      __nanosleep(4000);
      for (int i = blockIdx.x * 96 + threadIdx.x - 288; i < (int)(sizeof(Xchg) / 16); i += gridDim.x * 96) clearX[i] = make_uint4(0, 0, 0, 0);
    }
    if (warp == 8 && lane == 0) {
      int st = 0, ph = 1;
      for (int p = pair0; p < npairs; p += pstep) {
        const int tm = (p % (tilesM >> 1)) * 2 + crank, tn = p / (tilesM >> 1);
        const CUtensorMap* mb = &maps.b[tn / nPerB];
        const int n0 = (tn % nPerB) * BN;
        for (int kb = 0; kb < kblocks; kb++) {
          const uint32_t a = sbase + st * STAGE_BYTES, full = sBar + 8 * st;
          if (p > pair0 || kb >= GA0) {
            mbar_wait(sBar + 8 * (STAGES + st), ph);
            mbar_expect_tx(full, STAGE_BYTES);
            tma2d(a, &maps.a, kb * 64, tm * 128, full);
          }
#pragma unroll
          for (int i = 0; i < NBOX / 2; i++) {
            const int bx = crank * (NBOX / 2) + i;
            tma2d_mc(a + 16384 + bx * 8192, mb, n0 + bx * 64, kb * 64, full, (uint16_t)3);
          }
          if (++st == STAGES) { st = 0; ph ^= 1; }
        }
      }
      for (int i = 0; i < STAGES; i++) { mbar_wait(sBar + 8 * (STAGES + st), ph); if (++st == STAGES) { st = 0; ph ^= 1; } }
    }
  } else {
    asm volatile("setmaxnreg.inc.sync.aligned.u32 232;");
    int st = 0, ph = 0;
    float acc[BN / 2];
    const uint64_t descA0 = (uint64_t)(((sbase + wg * 8192) & 0x3FFFF) >> 4) | (1ull << 16) | (64ull << 32) | (1ull << 62);
    const uint64_t descB0 = (uint64_t)(((sbase + 16384) & 0x3FFFF) >> 4) | (512ull << 16) | (64ull << 32) | (1ull << 62);
    const uint32_t epi = sbase + wg * 8192;
    for (int p = pair0; p < npairs; p += pstep) {
      const int tm = (p % (tilesM >> 1)) * 2 + crank, tn = p / (tilesM >> 1);
      int prev = -1;
      for (int kb = 0; kb < kblocks; kb++) {
        mbar_wait(sBar + 8 * st, ph);
        if ((kb & 15) == 0) { GT(kb >> 4); }
        wg_fence();
        const uint64_t so = (uint64_t)(st * (STAGE_BYTES >> 4));
#pragma unroll
        for (int k = 0; k < 4; k++) WG<BN>::mma(acc, descA0 + so + k * 2, descB0 + so + k * 128, kb | k);
        wg_commit();
        if (prev >= 0) {
          wg_wait<1>();
          if ((threadIdx.x & 127) < 2) mbar_arrive_cluster(sBar + 8 * (STAGES + prev), threadIdx.x & 1);
        }
        prev = st;
        if (++st == STAGES) { st = 0; ph ^= 1; }
      }
      wg_wait<0>();
      if ((threadIdx.x & 127) < 2) mbar_arrive_cluster(sBar + 8 * (STAGES + prev), threadIdx.x & 1);
      GT(4);
#pragma unroll
      for (int r = 0; r < BN / 128; r++) {
        const int row = (warp & 3) * 16 + (lane & 15);
#pragma unroll
        for (int i = 0; i < 8; i++) {
          const int c = 2 * (i & 3) + (lane >> 4);
          const float* q = &acc[r * 64 + i * 8];
          stsm4(epi + (2 * r + (i >> 2)) * STAGE_BYTES + row * 128 + ((c ^ (row & 7)) << 4), pack2(q[0], q[1]), pack2(q[2], q[3]), pack2(q[4], q[5]), pack2(q[6], q[7]));
        }
        fence_async();
        bar_sync(1 + wg, 128);
        if ((threadIdx.x & 127) == 0) {
          tma2d_store(&maps.c, epi + 2 * r * STAGE_BYTES, tn * BN + r * 128, tm * 128 + wg * 64);
          tma2d_store(&maps.c, epi + (2 * r + 1) * STAGE_BYTES, tn * BN + r * 128 + 64, tm * 128 + wg * 64);
          asm volatile("cp.async.bulk.commit_group;" ::: "memory");
        }
      }
    }
    GT(5);
    if ((threadIdx.x & 127) == 0) asm volatile("cp.async.bulk.wait_group.read 0;" ::: "memory");
    GT(6);
  }
}

struct Dft { uint32_t m[2][2][2][4]; };
template <bool P4> __device__ __forceinline__ int fidx(int tile, int x) { return P4 ? 4 * (x >> 1) + 2 * (tile & 1) + (x & 1) + 16 * (tile >> 1) : x + 8 * tile; }
__device__ __forceinline__ float2 cis(int k, int n) {
  k &= n - 1; if (2 * k > n) k -= n;
  const float a = (float)k * (6.283185307179586f / (float)n);
  return make_float2(__cosf(a), __sinf(a));
}
template <bool OUT4> __device__ __forceinline__ void make_dft(Dft& D, int g, int t) {
#pragma unroll
  for (int q = 0; q < 16; q++) {
    const int b = q >> 3, u = (q >> 2) & 1, r = (q >> 1) & 1, v = q & 1;
    const float2 w = cis(fidx<OUT4>(v, g) * fidx<false>(2 * u + r, 2 * t + b), 32);
    D.m[b][u][0][q & 3] = pack2(w.x, w.y); D.m[b][u][1][q & 3] = pack2(-w.y, w.x);
  }
}
__device__ __forceinline__ void mma_dc(float (&d)[4], uint32_t a0, uint32_t a1, uint32_t a2, uint32_t a3, uint32_t b0, uint32_t b1, const float (&c)[4]) {
  asm("mma.sync.aligned.m16n8k16.row.col.f32.bf16.bf16.f32 {%0,%1,%2,%3}, {%4,%5,%6,%7}, {%8,%9}, {%10,%11,%12,%13};"
    : "=f"(d[0]), "=f"(d[1]), "=f"(d[2]), "=f"(d[3]) : "r"(a0), "r"(a1), "r"(a2), "r"(a3), "r"(b0), "r"(b1), "f"(c[0]), "f"(c[1]), "f"(c[2]), "f"(c[3])); }
__device__ __forceinline__ void dft_b(const Dft& D, const uint32_t (&x)[2][4], float (&o)[2][8]) {
#pragma unroll
  for (int ri = 0; ri < 2; ri++) {
    float z[4] = {0.f, 0.f, 0.f, 0.f}, e[4], p[4];
    mma_dc(e, D.m[0][0][ri][0], D.m[0][0][ri][1], D.m[0][0][ri][2], D.m[0][0][ri][3], x[0][0], x[0][1], z);
    mma_dc(e, D.m[0][1][ri][0], D.m[0][1][ri][1], D.m[0][1][ri][2], D.m[0][1][ri][3], x[0][2], x[0][3], e);
    mma_dc(p, D.m[1][0][ri][0], D.m[1][0][ri][1], D.m[1][0][ri][2], D.m[1][0][ri][3], x[1][0], x[1][1], e);
    mma_dc(p, D.m[1][1][ri][0], D.m[1][1][ri][1], D.m[1][1][ri][2], D.m[1][1][ri][3], x[1][2], x[1][3], p);
#pragma unroll
    for (int q = 0; q < 4; q++) { o[ri][q] = p[q]; o[ri][4 + q] = fmaf(2.f, e[q], -p[q]); }
  }
}
__device__ __forceinline__ void dft_a(const uint32_t (&m)[2][2][4], const uint32_t (&x0)[2][4], const uint32_t (&x1)[2][4], float (&o)[2][8]) {
#pragma unroll
  for (int ri = 0; ri < 2; ri++) {
    float z[4] = {0.f, 0.f, 0.f, 0.f}, e[4], p[4];
    mma_dc(e, x0[0][0], x1[0][0], x0[0][1], x1[0][1], m[0][ri][0], m[0][ri][1], z);
    mma_dc(e, x0[0][2], x1[0][2], x0[0][3], x1[0][3], m[0][ri][2], m[0][ri][3], e);
    mma_dc(p, x0[1][0], x1[1][0], x0[1][1], x1[1][1], m[1][ri][0], m[1][ri][1], e);
    mma_dc(p, x0[1][2], x1[1][2], x0[1][3], x1[1][3], m[1][ri][2], m[1][ri][3], p);
#pragma unroll
    for (int q = 0; q < 4; q++) { o[ri][q] = p[q]; o[ri][4 + q] = fmaf(2.f, e[q], -p[q]); }
  }
}
__device__ __forceinline__ uint32_t twid(float re, float im, float c, float s) { return pack2(fmaf(re, c, im * s), fmaf(im, c, -re * s)); }
__device__ __forceinline__ void cpa16(uint32_t d, const void* s) { asm volatile("cp.async.cg.shared.global [%0], [%1], 16;" :: "r"(d), "l"(s) : "memory"); }
__device__ __forceinline__ void sts32(uint32_t a, uint32_t x) { asm volatile("st.shared.u32 [%0], %1;" :: "r"(a), "r"(x) : "memory"); }
__device__ __forceinline__ void cpa_commit() { asm volatile("cp.async.commit_group;" ::: "memory"); }
template <int N> __device__ __forceinline__ void cpa_wait() { asm volatile("cp.async.wait_group %0;" :: "n"(N) : "memory"); }
__device__ __forceinline__ uint32_t lds32(uint32_t a) { uint32_t r; asm volatile("ld.shared.u32 %0, [%1];" : "=r"(r) : "r"(a) : "memory"); return r; }
#define FMID 0
constexpr int F_TP = 4112, F_TSZ = 8 * F_TP;

__device__ __forceinline__ uint32_t ldnc32(const void* p) { uint32_t v; asm volatile("ld.global.nc.b32 %0, [%1];" : "=r"(v) : "l"(p) : "memory"); return v; }
template <class F>
__device__ __forceinline__ void fft_wprep(const bf16* __restrict__ wr, const bf16* __restrict__ wi, int cta, F&& mid) {
  const int tid = threadIdx.x, g = (cta >> 1) & 7, c = (cta >> 4) & 3, t = 2 * (cta & 1) + (tid & 1);
  const int k0 = g + 8 * (cta >> 6) + 32 * (8 * c + 2 * t), l0 = (tid & ~1) + (g & 1);
  uint32_t a[4][4], b[4][4];
#pragma unroll
  for (int q = 0; q < 16; q++) {
    const int o = (k0 + 16 * (q >> 3) + 32 * ((q >> 1) & 1) + 1024 * (q & 1)) * 513 + l0 + 256 * ((q >> 2) & 1);
    a[q >> 2][q & 3] = ldnc32(wr + o);
    b[q >> 2][q & 3] = ldnc32(wi + o);
  }
  const int e = cta * 32 + (tid & 31), lh = (e >> 11) * 512, k = e & 2047, k2 = (k >> 5) & 31;
  uint32_t hz[4];
#pragma unroll
  for (int q = 0; q < 4; q++) asm volatile("ld.global.nc.u16 %0, [%1];" : "=r"(hz[q]) : "l"((q < 2 ? wr : wi) + (q & 1 ? (2048 - k) & 2047 : k) * 513 + lh) : "memory");
  mid();
  uint4* dst = g_wt + l0 * 512 + cta * 2 + (tid & 1);
#pragma unroll
  for (int q = 0; q < 8; q++) {
    const int hf = q >> 1, l = l0 + 256 * (hf & 1) + (q & 1);
    const uint32_t sel = (q & 1) ? 0x7632 : 0x5410;
    if (l & 511) dst[(256 * (hf & 1) + (q & 1)) * 512 + 256 * (q >> 2)] = make_uint4(__byte_perm(a[hf][0], b[hf][0], sel), __byte_perm(a[hf][1], b[hf][1], sel),
                                                                                   __byte_perm(a[hf][2], b[hf][2], sel), __byte_perm(a[hf][3], b[hf][3], sel));
  }
  if (tid < 32) reinterpret_cast<uint32_t*>(g_wt)[(64 * ((k >> 3) & 3) + 16 * (k2 >> 3) + 2 * (k & 7) + ((k2 >> 2) & 1)) * 8 + lh * 2048 + 2 * (k2 & 3) + (k >> 10)] =
      pack2(0.5f * (__uint_as_float(hz[0] << 16) + __uint_as_float(hz[1] << 16)), 0.5f * (__uint_as_float(hz[2] << 16) - __uint_as_float(hz[3] << 16)));
}

template <class F>
__device__ __forceinline__ void fft_rows_fwd(const bf16* __restrict__ x, const bf16* __restrict__ wr, const bf16* __restrict__ wi, uint32_t tb, int it, F&& mid) {
  const int warp = threadIdx.x >> 5, lane = threadIdx.x & 31, g = lane >> 2, t = lane & 3;
  const uint32_t in = tb + warp * 4096;
  const uint32_t f0 = in + (lane >> 3) * 256 + (((lane & 7) ^ (2 * (lane >> 3))) << 4);
  const bf16* src = x + ((256 * (warp & 3) + 64 * (warp >> 2) + 128 * (it & 1) + 32 * ((it >> 4) & 1) + 8 * (it >> 5) + ((it >> 1) & 7)) * 2048 + lane * 8);
#pragma unroll
  for (int q = 0; q < 8; q++) cpa16((f0 ^ ((q >> 2) * 144)) + (q & 3) * 1024, src + q * 256);
  cpa_commit();
  Dft D;
  float2 tw[4][8];
  fft_wprep(wr, wi, it, [&]() {
    if (FMID == 0) mid();
    make_dft<true>(D, g, t);
#pragma unroll
    for (int q = 0; q < 32; q++) {
      tw[q >> 3][q & 7] = cis(fidx<true>((q >> 1) & 3, g) * fidx<false>(q >> 3, 2 * t + (q & 1)), 1024);
      if (FMID) asm volatile("" : "+f"(tw[q >> 3][q & 7].x), "+f"(tw[q >> 3][q & 7].y) :: "memory");
    }
    if (FMID == 1) mid();
  });
  if (FMID == 2) mid();
  cpa_wait<0>(); __syncwarp();
  uint32_t a[4][2][4], y[4][2][4];
#pragma unroll
  for (int q = 0; q < 8; q++) ldsm4t(a[q & 3][q >> 2], (in + lane * 128 + ((lane & 7) << 4)) ^ (q << 4));
  float o[2][8];
#pragma unroll
  for (int i = 0; i < 4; i++) {
    dft_b(D, a[i], o);
#pragma unroll
    for (int q = 0; q < 8; q++) y[q >> 1][q & 1][i] = twid(o[0][q], o[1][q], tw[i][q].x, tw[i][q].y);
  }
  __syncthreads();
  const uint32_t w0 = tb + warp * F_TP + fidx<true>(0, g) * 128 + t * 16 + ((g & 1) << 6), wz = (g & 1) ? -64 : 64;
#pragma unroll
  for (int z = 0; z < 2; z++) {
    float o2[2][8];
    dft_b(D, y[2 * z], o); dft_b(D, y[2 * z + 1], o2);
#pragma unroll
    for (int i = 0; i < 4; i++) {
      const float sg = i < 2 ? 1.f : -1.f;
      sts128(w0 + z * wz + fidx<true>(i, 0) * 128, pack2(o[0][2 * i], sg * o[1][2 * i]), pack2(o[0][2 * i + 1], sg * o[1][2 * i + 1]),
             pack2(o2[0][2 * i], sg * o2[1][2 * i]), pack2(o2[0][2 * i + 1], sg * o2[1][2 * i + 1]));
    }
  }
  __syncthreads();
  const uint32_t ra = tb + (lane & 1) * 4 * F_TP + ((lane >> 1) + 16 * (warp ^ ((warp >> 1) & 1))) * 4;
  uint4* dst = g_y + (threadIdx.x >> 1) * 256 + (lane & 1) + it * 2;
#pragma unroll
  for (int q = 0; q < 8; q++) { const uint32_t r = ra + q * 512; dst[q * 32768] = make_uint4(lds32(r), lds32(r + F_TP), lds32(r + 2 * F_TP), lds32(r + 3 * F_TP)); }
}

template <class F>
__device__ __forceinline__ void fft_cols(uint32_t sb, int cta, int ncta, F&& ready) {
  const int warp = threadIdx.x >> 5, lane = threadIdx.x & 31, g = lane >> 2, t = lane & 3;
  const uint32_t in = sb + warp * 16384 + lane * 16, tab = sb + 131072 + lane * 16;
  auto fetch_y = [&](int l) {
#pragma unroll
    for (int q = 0; q < 16; q++) cpa16(in + q * 512, g_y + (q < 8 ? l : (1024 - l) & 1023) * 256 + (q & 7) * 32 + lane);
  };
  auto fetch_w = [&](int l) {
#pragma unroll
    for (int q = 0; q < 16; q++) cpa16(in + 8192 + q * 512, g_wt + l * 512 + q * 32 + lane);
  };
  const int l0 = cta * 8 + warp, dl = ncta * 8;
  Dft D; make_dft<false>(D, g, t);
#pragma unroll
  for (int q = 2 * warp; q < 2 * warp + 2; q++) {
    const int r = fidx<false>(q & 3, g), c = fidx<false>(q >> 2, 2 * t);
    const float2 w0 = cis(r * c, 1024), w1 = cis(r * c + r, 1024), p0 = cis(r + 32 * c, 2048), p1 = cis(r + 32 * c + 32, 2048);
    sts128(tab + q * 512, __float_as_uint(w0.x), __float_as_uint(w0.y), __float_as_uint(w1.x), __float_as_uint(w1.y));
    sts128(tab + 8192 + q * 512, __float_as_uint(p0.x), __float_as_uint(p0.y), __float_as_uint(p1.x), __float_as_uint(p1.y));
  }
  if (warp == 0) {
#pragma unroll
    for (int q = 0; q < 8; q++) {
      const int v = q >> 2, b = (q >> 1) & 1, ri = q & 1;
      sts128(tab + 16384 + q * 512, D.m[b][0][ri][v], D.m[b][0][ri][v + 2], D.m[b][1][ri][v], D.m[b][1][ri][v + 2]);
    }
  }
  ready();
  fetch_y(l0); cpa_commit();
  fetch_w(l0); cpa_commit();
#pragma unroll 1
  for (int l = l0; l <= 512; l += dl) {
    uint32_t a[2][4][2][4], y[2][4][2][4];
    float o[2][2][8];
    cpa_wait<1>();
#pragma unroll
    for (int q = 0; q < 16; q++) lds128(a[q >> 3][(q >> 1) & 3][q & 1], in + q * 512);
    if (!(l & 511)) {
      const uint32_t m0 = l ? 0x80000000u : 0u;
#pragma unroll
      for (int q = 0; q < 32; q++) { a[0][q >> 3][(q >> 2) & 1][q & 3] ^= m0; a[1][q >> 3][(q >> 2) & 1][q & 3] ^= m0 ^ 0x80000000u; }
    }
    auto first = [&]() {
#pragma unroll
      for (int i = 0; i < 4; i++) {
        dft_b(D, a[0][i], o[0]); dft_b(D, a[1][i], o[1]);
#pragma unroll
        for (int r = 0; r < 4; r++) {
          const float4 w = lds128f(tab + (4 * i + r) * 512);
#pragma unroll
          for (int s = 0; s < 2; s++) {
            y[s][r][0][i] = twid(o[s][0][2 * r], o[s][1][2 * r], w.x, w.y);
            y[s][r][1][i] = twid(o[s][0][2 * r + 1], o[s][1][2 * r + 1], w.z, w.w);
          }
        }
      }
    };
    first();
    if (l + dl <= 512) fetch_y(l + dl);
    cpa_commit();
    cpa_wait<1>();
#pragma unroll
    for (int zv = 0; zv < 4; zv++) {
      const int z = zv >> 1, v = zv & 1;
      uint32_t m[2][2][4];
#pragma unroll
      for (int q = 0; q < 4; q++) lds128(m[q >> 1][q & 1], tab + 16384 + (4 * v + q) * 512);
      dft_a(m, y[0][2 * z], y[0][2 * z + 1], o[0]); dft_a(m, y[1][2 * z], y[1][2 * z + 1], o[1]);
#pragma unroll
      for (int q = 0; q < 4; q++) {
        const int i = 2 * z + (q & 1), c = v + (q & 2);
        uint32_t w[4]; lds128(w, in + 8192 + (4 * i + c) * 512);
        const float4 ph = lds128f(tab + 8192 + (4 * c + i) * 512);
#pragma unroll
        for (int b = 0; b < 2; b++) {
          const float cs = b ? ph.z : ph.x, sn = b ? ph.w : ph.y;
          const float r1 = __uint_as_float(w[2 * b] << 16), i1 = __uint_as_float(w[2 * b] & 0xFFFF0000u);
          const float r2 = __uint_as_float(w[2 * b + 1] << 16), i2 = __uint_as_float(w[2 * b + 1] & 0xFFFF0000u);
          const float Sr = r1 + r2, Si = i1 + i2, Dr = r1 - r2, Di = i1 - i2;
          const float ar = fmaf(-Dr, sn, Sr), ai = fmaf(-Di, sn, Si), dr = fmaf(Dr, sn, Sr), di = fmaf(Di, sn, Si), br = -Di * cs, bi = Dr * cs;
          const float Ar = o[0][0][2 * q + b], Ai = o[0][1][2 * q + b], Br = o[1][0][2 * q + b], Bi = o[1][1][2 * q + b];
          a[0][i][b][c] = pack2(fmaf(ar, Ai, fmaf(ai, Ar, fmaf(br, Bi, bi * Br))), fmaf(ar, Ar, fmaf(-ai, Ai, fmaf(br, Br, -bi * Bi))));
          a[1][i][b][c] = pack2(fmaf(dr, Bi, fmaf(di, Br, fmaf(-br, Ai, -bi * Ar))), fmaf(dr, Br, fmaf(-di, Bi, fmaf(-br, Ar, bi * Ai))));
        }
      }
    }
    if (l + dl <= 512) fetch_w(l + dl);
    cpa_commit();
    first();
#pragma unroll
    for (int s = 0; s < 2; s++) {
      uint4* dst = g_y + (s ? (1024 - l) & 1023 : l) * 256 + lane;
      const float sg = s ? -1.f : 1.f;
#pragma unroll
      for (int i = 0; i < 4; i++) {
        dft_b(D, y[s][i], o[0]);
#pragma unroll
        for (int b = 0; b < 2; b++)
          dst[(2 * i + b) * 32] = make_uint4(pack2(sg * o[0][0][b], o[0][1][b]), pack2(sg * o[0][0][2 + b], o[0][1][2 + b]),
                                             pack2(sg * o[0][0][4 + b], o[0][1][4 + b]), pack2(sg * o[0][0][6 + b], o[0][1][6 + b]));
      }
    }
  }
}

template <class F>
__device__ __forceinline__ void fft_rows_inv(const CUtensorMap* om, uint32_t sb, int cta, int ncta, F&& ready) {
  const int warp = threadIdx.x >> 5, lane = threadIdx.x & 31, g = lane >> 2, t = lane & 3, wg = warp >> 2, w4 = warp & 3;
  const uint32_t tb = sb + 32768 + wg * 2 * F_TSZ;
  const uint4* src = g_y + pin((256 * ((lane >> 1) & 3) + 64 * (lane >> 3) + 8 * w4) * 256 + (lane & 1));
  const uint32_t wa = pin(tb + (lane & 1) * 4 * F_TP + w4 * 1024 + (lane >> 1) * 4);
  uint4 pf[8];
  auto fetch = [&](int it, int hf) {
#pragma unroll
    for (int q = 0; q < 8; q++) pf[q] = __ldcg(src + (it * 2 + hf * 8192) + q * 256);
  };
  auto put = [&](uint32_t off) {
#pragma unroll
    for (int q = 0; q < 8; q++) {
      sts32(wa + off + q * 64, pf[q].x); sts32(wa + off + q * 64 + F_TP, pf[q].y);
      sts32(wa + off + q * 64 + 2 * F_TP, pf[q].z); sts32(wa + off + q * 64 + 3 * F_TP, pf[q].w);
    }
  };
  const int it0 = 2 * cta + wg;
  Dft D; make_dft<false>(D, g, t);
  float2 tw[4][8];
#pragma unroll
  for (int q = 0; q < 32; q++) {
    tw[q >> 3][q & 7] = cis(fidx<false>((q >> 1) & 3, g) * fidx<false>(q >> 3, 2 * t + (q & 1)), 1024);
    tw[q >> 3][q & 7].x *= 1.f / 2097152.f; tw[q >> 3][q & 7].y *= 1.f / 2097152.f;
    asm volatile("" : "+f"(tw[q >> 3][q & 7].x), "+f"(tw[q >> 3][q & 7].y) :: "memory");
  }
  ready();
  fetch(it0, 0); put(0); fetch(it0, 1); put(512);
  const uint32_t la = pin(tb + w4 * F_TP + lane * 16), ob = uni(sb + warp * 4096);
  const uint32_t oa = pin(ob + (lane >> 1) * 128 + (((4 * (lane & 1)) ^ ((lane >> 1) & 7)) << 4));
#pragma unroll 1
  for (int n = 0;; n++) {
    const int it = it0 + (n >> 1) * 2 * ncta, hf = n & 1, buf = (n >> 1) & 1;
    if (it >= 128) break;
    if (!hf) bar_sync(1 + wg, 128);
    uint32_t a[4][2][4], y[4][2][4];
#pragma unroll
    for (int q = 0; q < 8; q++) lds128(a[q >> 1][q & 1], la + buf * F_TSZ + hf * 4 * F_TP + q * 512);
    fetch(min(it + 2 * ncta, 127), hf);
    float o[2][8];
#pragma unroll
    for (int i = 0; i < 4; i++) {
      dft_b(D, a[i], o);
#pragma unroll
      for (int q = 0; q < 8; q++) y[q >> 1][q & 1][i] = twid(o[0][q], o[1][q], tw[i][q].x, tw[i][q].y);
    }
    if (lane == 0) asm volatile("cp.async.bulk.wait_group.read 0;" ::: "memory");
    __syncwarp();
#pragma unroll
    for (int c = 0; c < 4; c++) {
      dft_b(D, y[c], o);
#pragma unroll
      for (int ri = 0; ri < 2; ri++)
        stsm4((oa ^ (c << 4)) + (1 - ri) * 2048, pack2(o[ri][0], o[ri][1]), pack2(o[ri][2], o[ri][3]), pack2(o[ri][4], o[ri][5]), pack2(o[ri][6], o[ri][7]));
    }
    fence_async();
    __syncwarp();
    if (lane == 0) {
      const int m = 256 * w4 + 32 * ((it >> 1) & 7) + 8 * (it >> 5) + 4 * (it & 1) + 2 * hf + ((it >> 4) & 1);
      asm volatile("cp.async.bulk.tensor.3d.global.shared::cta.bulk_group [%0, {0, 0, %2}], [%1];" :: "l"(om), "r"(ob), "r"(2 * m) : "memory");
      asm volatile("cp.async.bulk.commit_group;" ::: "memory");
    }
    put((buf ^ 1) * F_TSZ + hf * 512);
  }
  if (lane == 0) asm volatile("cp.async.bulk.wait_group 0;" ::: "memory");
}
__device__ __forceinline__ void grid_arrive(unsigned* ctr) {
  __syncthreads();
  if (threadIdx.x == 0) { __threadfence(); atomicAdd(ctr, 1u); }
}
__device__ __forceinline__ void grid_wait(unsigned* ctr, unsigned n) {
  if (threadIdx.x == 224) {
    int it = 0;
    while (*reinterpret_cast<volatile unsigned*>(ctr) < n) { __nanosleep(100); if (++it > SPIN_LIMIT) { g_err = 3; break; } }
    __threadfence();
  }
  __syncthreads();
}

struct RecMaps { CUtensorMap wq, wk, wv, wo, x, k, q, v, fo; };
#define NSW 16
#define EXP 0
#define NPB 3
#define NPB0 3
#define NPC 0
#define WOP 2
#define HOME 7
#define DL0 14
#define PD1 4
#define NE4 6
#define NA4 14
#define NA6 18
#define NB1 24
#define TQL 7
#define NQ 16
#define TQP (NQ - 1)
#define OXPOS 4
#define XWPOS 10
#define RI 9
#define RJ 8
#define NPRE 22
#define PFD 4
#define PD0 4
#define VB NV0
#define NPA 0
#define N1 16
#define DL1 16
#define PACE 0
#define RE0 0
#define RE1 0
#define RP1 23
#define X2 2
#define X3 2
#define SPOS 2
#ifndef NV0
#define NV0 4
#endif
#define TGP 3
#define LW0 8
#define X1 4
#define X0 4
constexpr int R_WO = 0, R_X = 65536, R_MEM = 131072, R_WC = 147456, R_RED = R_WC + NSW * 2048, R_O = R_RED, R_S = R_O + 2048, R_P = R_S + 3072, R_STAGE = R_P + 2048,
              R_K = R_STAGE + 8192, R_Q = R_K + 8192, R_V = R_Q + 2048, R_ID = R_V + 16384, R_T = R_ID + 512, R_DST = R_T + 512, R_RD = R_DST + 2048, R_BAR = R_RD + 2048, R_TS = R_BAR + 128,
              R_TOTAL = R_TS;
#define TS(i)
#define LOG(i, v)
constexpr int B_KV = R_BAR, B_W = R_BAR + 8, B_X = R_BAR + 80, B_PK = R_BAR + 24, B_C = R_BAR + 32, B_B = R_BAR + 40, B_DUE = R_BAR + 48, B_ONE = R_BAR + 64;
#define DLY_A 150
#define DLY_V 150
#define DLY_C 200
#define NS_B 1120
#define NS_C 1728
#define NS_P 2624
#define NS_V 128
#define NS_F 896
#define NS_K 128
#define NS_M 32
#define NS_X 128
#define MG_Z 0x00010206
#define MG_Y 0x0001051a
#define ALT 32
#define NS_PEN 1024
__device__ __forceinline__ float rcp(float x) { float r; asm("rcp.approx.ftz.f32 %0, %1;" : "=f"(r) : "f"(x)); return r; }
__device__ __forceinline__ uint32_t hadd2(uint32_t a, uint32_t b) { uint32_t d; asm("add.rn.bf16x2 %0, %1, %2;" : "=r"(d) : "r"(a), "r"(b)); return d; }
__device__ __forceinline__ void mma_a(float (&d)[4], const uint32_t (&a)[4], uint32_t b0, uint32_t b1) { mma16816(d, a[0], a[1], a[2], a[3], b0, b1); }
__device__ __forceinline__ bool elect() {
  uint32_t p; asm volatile("{.reg .pred p; elect.sync _|p, 0xffffffff; selp.u32 %0, 1, 0, p;}" : "=r"(p)); return p; }
__device__ __forceinline__ void tma3d(uint32_t dst, const CUtensorMap* m, int c1, int c2, uint32_t bar) {
  asm volatile("cp.async.bulk.tensor.3d.shared::cluster.global.mbarrier::complete_tx::bytes [%0], [%1, {0, %3, %4}], [%2];"
    :: "r"(dst), "l"(m), "r"(bar), "r"(c1), "r"(c2) : "memory"); }
template <int OFF, int ACC>
__device__ __forceinline__ void wg_rs32(float (&d)[16], const uint32_t (&a)[4], uint32_t db) {
  if (ACC)
    asm volatile("{.reg .b64 db; .reg .b32 lo; add.u32 lo, %20, %21; mov.b64 db, {lo, 0x40000040};\n"
      "wgmma.mma_async.sync.aligned.m64n32k16.f32.bf16.bf16 {%0,%1,%2,%3,%4,%5,%6,%7,%8,%9,%10,%11,%12,%13,%14,%15}, {%16,%17,%18,%19}, db, 1, 1, 1, 0;}"
      : "+f"(d[0]), "+f"(d[1]), "+f"(d[2]), "+f"(d[3]), "+f"(d[4]), "+f"(d[5]), "+f"(d[6]), "+f"(d[7]), "+f"(d[8]), "+f"(d[9]), "+f"(d[10]), "+f"(d[11]), "+f"(d[12]), "+f"(d[13]), "+f"(d[14]), "+f"(d[15])
      : "r"(a[0]), "r"(a[1]), "r"(a[2]), "r"(a[3]), "r"(db), "n"(OFF));
  else
    asm volatile("{.reg .b64 db; .reg .b32 lo; add.u32 lo, %20, %21; mov.b64 db, {lo, 0x40000040};\n"
      "wgmma.mma_async.sync.aligned.m64n32k16.f32.bf16.bf16 {%0,%1,%2,%3,%4,%5,%6,%7,%8,%9,%10,%11,%12,%13,%14,%15}, {%16,%17,%18,%19}, db, 0, 1, 1, 0;}"
      : "=f"(d[0]), "=f"(d[1]), "=f"(d[2]), "=f"(d[3]), "=f"(d[4]), "=f"(d[5]), "=f"(d[6]), "=f"(d[7]), "=f"(d[8]), "=f"(d[9]), "=f"(d[10]), "=f"(d[11]), "=f"(d[12]), "=f"(d[13]), "=f"(d[14]), "=f"(d[15])
      : "r"(a[0]), "r"(a[1]), "r"(a[2]), "r"(a[3]), "r"(db), "n"(OFF));
}
template <int I> using IC = std::integral_constant<int, I>;
template <int I, int N, class F> __device__ __forceinline__ void sfor(F&& f) {
  if constexpr (I < N) { f(std::integral_constant<int, I>{}); sfor<I + 1, N>(f); }
}
__device__ __forceinline__ void keep(float (&d)[16]) {
  asm volatile("" : "+f"(d[0]), "+f"(d[1]), "+f"(d[2]), "+f"(d[3]), "+f"(d[4]), "+f"(d[5]), "+f"(d[6]), "+f"(d[7]),
      "+f"(d[8]), "+f"(d[9]), "+f"(d[10]), "+f"(d[11]), "+f"(d[12]), "+f"(d[13]), "+f"(d[14]), "+f"(d[15]) :: "memory");
}

template <int N, int S2 = 1024> __device__ __forceinline__ void ldx(uint32_t (&v)[N][4], const uint8_t* p) {
#pragma unroll
  for (int k = 0; k < 2 * N; k++) {
    const int i = k;
    asm volatile("ld.relaxed.gpu.global.v2.b32 {%0,%1}, [%2];" : "=r"(v[i >> 1][2 * (i & 1)]), "=r"(v[i >> 1][2 * (i & 1) + 1]) : "l"(p + (i & 3) * 256 + (i >> 2) * S2) : "memory");
  }
}
__device__ __forceinline__ uint32_t dif2(uint32_t a, uint32_t b, uint32_t tag) { uint32_t r; asm("lop3.b32 %0, %1, %2, %3, 0x7e;" : "=r"(r) : "r"(a), "r"(b), "r"(tag)); return r; }
__device__ __forceinline__ uint32_t dif2v(uint32_t a, uint32_t b, uint32_t tag) { uint32_t r; asm volatile("lop3.b32 %0, %1, %2, %3, 0x7e;" : "=r"(r) : "r"(a), "r"(b), "r"(tag)); return r; }
__device__ __forceinline__ uint32_t or3(uint32_t a, uint32_t b, uint32_t c) { uint32_t r; asm("lop3.b32 %0, %1, %2, %3, 0xfe;" : "=r"(r) : "r"(a), "r"(b), "r"(c)); return r; }
__device__ __forceinline__ uint32_t after(uint32_t x, float f, uint32_t z) { uint32_t r; asm("lop3.b32 %0, %1, %2, %3, 0xea;" : "=r"(r) : "r"(__float_as_uint(f)), "r"(z), "r"(x)); return r; }
__device__ __forceinline__ bool any_bit(uint32_t a, uint32_t b, uint32_t m) {
  uint32_t r; asm("lop3.b32 %0, %1, %2, %3, 0xa8;" : "=r"(r) : "r"(a), "r"(b), "r"(m)); return __any_sync(0xffffffffu, r); }
template <int W, int N> __device__ __forceinline__ bool stale(const uint32_t (&v)[N][4], uint32_t tag) {
  uint32_t x = dif2(v[0][0], v[0][2], tag);
  if (N == 4) x = or3(x, dif2(v[1][0], v[1][2], tag), dif2(v[2 % N][0], v[2 % N][2], tag));
  return any_bit(x, dif2(v[N - 1][0], v[N - 1][2], tag), 1);
}
template <int W, int N, int S2 = 1024> __device__ __forceinline__ void retry(uint32_t (&v)[N][4], const uint8_t* p, uint32_t tag, int& it) {
#pragma unroll 1
  do { ldx<N, S2>(v, p); it += INC_A; } while (stale<W>(v, tag) && it < SPIN_LIMIT);
}
__device__ __forceinline__ void mma_h(float (&d)[4], const uint32_t (&a)[4], const uint32_t (&b)[4], int hf) { mma16816(d, a[0], a[1], a[2], a[3], b[2 * hf], b[2 * hf + 1]); }
__device__ __forceinline__ void sts128(uint32_t a, const uint32_t (&r)[4]) { sts128(a, r[0], r[1], r[2], r[3]); }
__device__ __forceinline__ void sts128f(uint32_t a, const float* r) { sts128(a, __float_as_uint(r[0]), __float_as_uint(r[1]), __float_as_uint(r[2]), __float_as_uint(r[3])); }
__device__ __forceinline__ void mbar_spin(uint32_t bar, uint32_t par, int& it) {
  asm volatile("{.reg .pred p; .reg .b32 par; mov.b32 par, %2;\nLOOP: mbarrier.try_wait.parity.shared::cta.b64 p, [%1], par; @p bra.uni DONE;\n"
               "add.s32 %0, %0, 1; setp.le.s32 p, %0, %3; @p bra.uni LOOP;\nDONE: }" : "+r"(it) : "r"(bar), "r"(par), "n"(SPIN_LIMIT) : "memory"); }
__device__ __forceinline__ void warp_arrive(uint32_t bar) {
  __syncwarp(); asm volatile("{.reg .pred p; elect.sync _|p, 0xffffffff; @p mbarrier.arrive.shared::cta.b64 _, [%0];}" :: "r"(bar) : "memory"); }
__device__ __forceinline__ void delay_until(unsigned t) {
  asm volatile("{.reg .pred p; .reg .b64 c; .reg .b32 lo, hi;\nLOOP: mov.u64 c, %%clock64; mov.b64 {lo, hi}, c; sub.s32 lo, lo, %0; setp.lt.s32 p, lo, 0; @p bra.uni LOOP;}" :: "r"(t) : "memory"); }
__device__ __forceinline__ void zero(float (&c)[4][4]) {
#pragma unroll
  for (int i = 0; i < 4; i++) c[i][0] = c[i][1] = c[i][2] = c[i][3] = 0.f;
}

__device__ __forceinline__ void sched() { asm volatile("griddepcontrol.launch_dependents;" ::: "memory"); }
__device__ __forceinline__ const uint8_t* pinp(const uint8_t* p) { return reinterpret_cast<const uint8_t*>(__shfl_xor_sync(0xffffffffu, reinterpret_cast<unsigned long long>(p), 0)); }
__device__ __forceinline__ uint32_t bar_or(int id, uint32_t x) {
  uint32_t r; asm volatile("{.reg .pred p, q; setp.ne.u32 p, %2, 0; bar.red.or.pred q, %1, 256, p; selp.u32 %0, 1, 0, q;}" : "=r"(r) : "r"(id), "r"(x) : "memory"); return r; }
__device__ __forceinline__ void bar_sync_unless(int id, uint32_t x) { asm volatile("{.reg .pred p; setp.eq.u32 p, %1, 0; @p bar.sync %0, 256;}" :: "r"(id), "r"((uint32_t)x) : "memory"); }
__device__ __forceinline__ void bar_arrive_unless(int id, uint32_t x) { asm volatile("{.reg .pred p; setp.eq.u32 p, %1, 0; @p bar.arrive %0, 256;}" :: "r"(id), "r"((uint32_t)x) : "memory"); }
__device__ __forceinline__ void stsm2t(uint32_t a, uint32_t r0, uint32_t r1, uint32_t x) {
  asm volatile("{.reg .pred p; setp.eq.u32 p, %3, 0; @p stmatrix.sync.aligned.m8n8.x2.trans.shared.b16 [%0], {%1,%2};}" :: "r"(a), "r"(r0), "r"(r1), "r"((uint32_t)x) : "memory"); }
__device__ __forceinline__ uint32_t or_and(uint32_t a, uint32_t b, uint32_t m) { uint32_t r; asm("lop3.b32 %0, %1, %2, %3, 0xa8;" : "=r"(r) : "r"(a), "r"(b), "r"(m)); return r; }
#define rare(x) __builtin_expect(!!(x), 0)
__device__ __forceinline__ uint32_t gtime() { unsigned long long g; asm volatile("mov.u64 %0, %%globaltimer;" : "=l"(g) :: "memory"); return (uint32_t)g; }
__device__ __forceinline__ void wait_time(uint32_t t) {
  asm volatile("{.reg .pred p; .reg .b32 g; .reg .b64 c;\nLOOP: mov.u64 c, %%globaltimer; cvt.u32.u64 g, c; sub.s32 g, %0, g; setp.lt.u32 p, g, 16384; @p bra.uni LOOP;}" :: "r"(t - 1) : "memory"); }
__device__ __forceinline__ uint32_t ldx32(const void* p) { uint32_t v; asm volatile("ld.relaxed.gpu.global.b32 %0, [%1];" : "=r"(v) : "l"(p) : "memory"); return v; }
__device__ __forceinline__ void stx32(const void* p, uint32_t v) { asm volatile("st.relaxed.gpu.global.b32 [%0], %1;" :: "l"(p), "r"(v) : "memory"); }

__global__ void __launch_bounds__(256, 1)
rec_kernel(const __grid_constant__ RecMaps maps, const bf16* __restrict__ xin, const bf16* __restrict__ mem0, Xchg* const gx,
           const bf16* __restrict__ fx, const bf16* __restrict__ wr, const bf16* __restrict__ wi) {
  extern __shared__ __align__(1024) uint8_t smem_raw[];
  const uint32_t sb = smem_u32(smem_raw);
  int role = blockIdx.x;
  {
    uint32_t smid, nsm; asm volatile("mov.u32 %0, %%smid;" : "=r"(smid)); asm volatile("mov.u32 %0, %%nsmid;" : "=r"(nsm));
    const int p = smid >> 1, u = p - 32;
    if (nsm == gridDim.x)
      role = (smid & 1) + (p < 32 ? 4 * ((p & 7) + 8 * (p >> 4)) + 2 * ((p >> 3) & 1) : p < 60 ? 4 * (16 + u % 7 + 7 * (u / 14)) + 2 * ((u / 7) & 1)
                         : p < 62 ? 2 * p + 8 : 2 * p - 4);
    role = uni(role);
  }
  if (role >= 128) {
    fft_cols(sb, role - 128, 4, [&]() { grid_wait(&gx->ctr[33], 128); });
    __threadfence(); __syncwarp();
    if ((threadIdx.x & 31) == 0) atomicAdd(&gx->ctr[32], 1u);
    __syncwarp();
    fft_rows_inv(&maps.fo, sb, role - 128, 4, [&]() { grid_wait(&gx->ctr[32], 32); });
    return;
  }
  const int tid = threadIdx.x, warp = uni(tid >> 5), lane = tid & 31, wg = warp >> 2, w4 = warp & 3, g = lane >> 2, t = lane & 3;
  const int h = role >> 2, j = role & 3, jh = j & 1;
  uint32_t w[48][4];
  float aq[16], av[16];
  int it = 0;

#define PT(k)
  auto pf_wo = [&]() {
    for (int i = 0; i < 4; i++)
      asm volatile("cp.async.bulk.prefetch.tensor.2d.L2.global [%0, {%1, %2}];" :: "l"(&maps.wo), "r"(256 * j + 64 * i), "r"(h * DH) : "memory");
  };
  fft_rows_fwd(fx, wr, wi, sb + R_MEM + 49152, role, [&]() {
    if (tid == 224) {
      mbar_init(sb + B_KV, 1); mbar_init(sb + B_W, 1); mbar_init(sb + B_X, 1); mbar_init(sb + B_X + 8, 1); mbar_init(sb + B_X + 16, 1); mbar_init(sb + B_X + 24, 1); mbar_init(sb + B_C, 4); mbar_init(sb + B_PK, 4); mbar_init(sb + B_B, 1);
      asm volatile("fence.mbarrier_init.release.cluster;" ::: "memory");
      mbar_expect_tx(sb + B_W, 3 * 65536);
      for (int i = 0; i < 4; i++) {
        tma2d(sb + R_X + i * 16384, &maps.wq, h * DH + 32 * j, i * 256, sb + B_W);
        if (i < 3) tma2d(sb + R_MEM + i * 16384, &maps.wk, h * DH + 32 * j, i * 256, sb + B_W);
        else asm volatile("cp.async.bulk.prefetch.tensor.2d.L2.global [%0, {%1, %2}];" :: "l"(&maps.wk), "r"(h * DH + 32 * j), "r"(768) : "memory");
      }
      for (int i = 0; i < 2; i++) tma2d(sb + R_WO + i * 32768, &maps.wv, h * DH + 64 * (j >> 1), jh * 512 + i * 256, sb + B_W);
      if (PFD) asm volatile("cp.async.bulk.prefetch.L2.global [%0], 2048;" :: "l"(xin + role * DM) : "memory");
      else for (int i = 0; i < 4; i++) asm volatile("cp.async.bulk.prefetch.L2.global [%0], 8192;" :: "l"(xin + role * 16384 + i * 4096) : "memory");
      if (WOP == 0) pf_wo();
      for (int i = 0; i < 5; i++) asm volatile("prefetch.tensormap [%0];" :: "l"(&maps.wo + i) : "memory");
    }
    __syncwarp();
  });
  if (tid < 16) sts32(sb + R_T + tid * 4, ~0u);
  fence_async();
  PT(0);
  grid_arrive(&gx->ctr[33]);
  PT(1);
  if (tid == 224) { tma2d(sb + R_MEM + 49152, &maps.wk, h * DH + 32 * j, 768, sb + B_W); if (WOP == 1) pf_wo(); }
  __syncwarp();
  uint8_t* const xb = reinterpret_cast<uint8_t*>(gx);
  auto probe_at = [&](int n) { return xb + (n ? offsetof(Xchg, C) + w4 * 8192 + role * 32 : offsetof(Xchg, B) + role * 8192 + warp * 128); };
  if (lane < 8) stx128(probe_at(lane >> 2) + (lane & 2) * 2048 + (lane & 1) * 16, 0, 0, 0, 0);
  uint32_t m0[4][4];
#pragma unroll
  for (int i = 0; i < 16; i++) m0[i >> 2][i & 3] = ldnc32(mem0 + g * DM + 128 * warp + 8 * i + 2 * t);
  mbar_spin(sb + B_W, 0, it);
  PT(2);
  const int lrow = (lane & 7) + ((lane >> 4) << 3), lhi = (lane >> 3) & 1;
  const int kq = wg ? 3 - 3 * jh : 3 * jh;
  const uint32_t LW = lrow * 128 + ((lhi ^ (lane & 7)) << 4);
  {
    const int chunk = w4 < 2 ? w4 + 2 * lhi : 2 * (w4 & 1) + lhi;
    uint32_t a = sb + (w4 < 2 ? R_X : R_MEM) + kq * 16384 + lrow * 64 + ((chunk ^ ((lrow >> 1) & 3)) << 4);
#pragma unroll
    for (int i = 0; i < 16; i++) ldsm4t(w[i], a + i * 1024);
    const uint32_t st = wg ? 1024 : 2048, av0 = sb + R_WO + (LW ^ (w4 << 5));
    const uint32_t a1 = wg ? a + (2 * jh - 1) * 16384 : av0 + jh * 32768, a2 = wg ? a + (2 * jh - 1) * 32768 : av0 + (1 - jh) * 32768;
#pragma unroll
    for (int i = 0; i < 16; i++) { ldsm4t(w[16 + i], a1 + i * st); ldsm4t(w[32 + i], a2 + i * st); }
  }
  uint32_t L16 = pin(lane * 16);
  const uint32_t uW = uni(sb + w4 * 512), uWo = uni(sb + R_WO + w4 * 16384), uMem = uni(sb + R_MEM + kq * 4096);
  const uint32_t dX = uni(((sb + R_X + kq * 16384) >> 4) | 0x10000u);
  auto load_wo = [&](uint32_t (&d)[32][4], int i0, int i1) {
#pragma unroll
    for (int i = i0; i < i1; i++) lds128(d[i], uWo + L16 + (i & 1) * 512 + (i >> 4) * 1024 + (i & 14) * 1024);
  };
  auto issue_x = [&](int n, int k) {
    const uint32_t bar = sb + B_X + 8 * k, q = k ^ (3 - 3 * jh);
    mbar_expect_tx(bar, 16384); tma3d(sb + R_X + q * 16384, &maps.x, min(n, NSEG - 1) * SEG, 4 * q, bar);
  };
  auto store_stage = [&](int n) {
    asm volatile("cp.async.bulk.global.shared::cta.bulk_group [%0], [%1], 8192; cp.async.bulk.commit_group;"
                 :: "l"(g_kqv[n & 3][role]), "r"(sb + R_STAGE) : "memory");
  };
  auto issue_kqv = [&](int n) {
    const int p = (n & 3) * 128 + 4 * h;
    mbar_expect_tx(sb + B_KV, 26624);
    tma3d(sb + R_K, &maps.k, 0, p, sb + B_KV); tma3d(sb + R_Q, &maps.q, 8 + 2 * j, p, sb + B_KV); tma3d(sb + R_V, &maps.v, 16, p, sb + B_KV);
  };
  auto fetch4k = [&](uint32_t dst, uint32_t off, uint32_t bar, uint32_t t) {
    asm volatile("{.reg .pred p, q; .reg .b32 g; .reg .b64 c; elect.sync _|q, 0xffffffff; @q mbarrier.arrive.expect_tx.shared::cta.b64 _, [%2], 4096;\n"
                 "LOOP: mov.u64 c, %%globaltimer; cvt.u32.u64 g, c; sub.s32 g, %3, g; setp.lt.u32 p, g, 16384; @p bra.uni LOOP;\n"
                 "@q cp.async.bulk.shared::cluster.global.mbarrier::complete_tx::bytes [%0], [%1], 4096, [%2];}" :: "r"(dst), "l"(xb + off), "r"(bar), "r"(t - 1) : "memory");
  };
  uint32_t uS;
  auto my_b = [&]() { return offsetof(Xchg, B) + role * 8192 + ((uS + ((uint32_t)it >> 31)) & 1) * 4096; };
  auto issue_c = [&](uint32_t t) { fetch4k(sb + R_MEM + w4 * 4096, offsetof(Xchg, C) + w4 * 8192 + ((uS + ((uint32_t)it >> 31)) & 4096), sb + B_C, t); };
  auto wait_x = [&](int n, int i) { if (!(EXP & 1) || n < 2) mbar_spin(sb + B_X + 8 * i, n & 1, it); };
#define PACED(d0) uint32_t dz = d0; const uint32_t z = (uint32_t)it >> 31; auto pace = [&]() { for (int k = 0; k < PACE; k++) { if (k & 1) asm("add.u32 %0, %0, %1;" : "+r"(dz) : "r"(z)); else asm("xor.b32 %0, %0, %1;" : "+r"(dz) : "r"(z)); } };
  auto project_v = [&](auto I0, auto I1, auto&& mid) {
    PACED(decltype(I0)::value < 16 ? dX : dX ^ 1024);
    wg_fence();
    sfor<decltype(I0)::value, decltype(I1)::value>([&](auto I) {
      constexpr int i = decltype(I)::value;
      mid(i);
      if (i == 16 && decltype(I0)::value < 16) dz ^= 1024;
      wg_rs32<((i >> 2) & 3) * 256 + (i & 3) * 2, (i > 0)>(av, w[16 + i], dz);
      pace();
    });
    wg_commit();
  };
  auto project_qk = [&](auto I0, auto I1, auto first, auto&& mid) {
    PACED((dX ^ (decltype(I0)::value >> 4 << 10)) + ((uint32_t)it >> 31));
    wg_fence();
    sfor<decltype(I0)::value, decltype(I1)::value>([&](auto I) {
      constexpr int i = decltype(I)::value;
      mid(i);
      wg_rs32<((i >> 2) & 3) * 256 + (i & 3) * 2, !decltype(first)::value || i != decltype(I0)::value>(aq, w[i], dz);
      pace();
    });
    wg_commit();
  };
  const uint32_t uP = uni(sb + R_X + 3 * jh * 16384 + w4 * 512);
  auto park = [&]() {
    bar_sync(1, 128);
#pragma unroll
    for (int i = 0; i < 4; i++) sts128f(uP + L16 + i * 2048, aq + 4 * i);
    warp_arrive(sb + B_PK);
  };
  auto unpark = [&]() {
#pragma unroll
    for (int i = 0; i < 4; i++) {
      const float4 p = lds128f(uP + L16 + i * 2048);
      av[4 * i] = p.x; av[4 * i + 1] = p.y; av[4 * i + 2] = p.z; av[4 * i + 3] = p.w;
    }
  };
  auto fin_qk = [&]() {
#pragma unroll
    for (int i = 0; i < 16; i++) aq[i] += av[i];
    const uint32_t a = sb + R_STAGE + (w4 < 2 ? 2048 + w4 * 128 : (w4 & 1) * 256) + (L16 & 112) + (L16 >> 7) * 512;
    stsm4t(a, pack2(aq[0], aq[1]), pack2(aq[4], aq[5]), pack2(aq[8], aq[9]), pack2(aq[12], aq[13]));
    stsm4t(a + (w4 < 2 ? 256 : 128), pack2(aq[2], aq[3]), pack2(aq[6], aq[7]), pack2(aq[10], aq[11]), pack2(aq[14], aq[15]));
  };
  auto fin_v = [&]() {
#pragma unroll
    for (int a = 0; a < 2; a++)
      sts128(sb + R_STAGE + 4096 + w4 * 1024 + a * 512 + L16, pack2(av[8 * a], av[8 * a + 1]), pack2(av[8 * a + 2], av[8 * a + 3]),
             pack2(av[8 * a + 4], av[8 * a + 5]), pack2(av[8 * a + 6], av[8 * a + 7]));
  };
  __syncthreads();
  if (tid == 224) {
#pragma unroll 1
    for (int i = 0; i < 4; i++) issue_x(0, i);
    mbar_expect_tx(sb + B_W, 65536);
    for (int i = 0; i < 4; i++) tma2d(sb + R_WO + i * 16384, &maps.wo, 256 * j + 64 * i, h * DH, sb + B_W);
  }
  __syncwarp();
  if (wg) {
#pragma unroll
    for (int i = 0; i < NSW; i++) sts128(uW + R_WC + L16 + i * 2048, w[i]);
  }
#pragma unroll
  for (int i = 0; i < 4; i++) sts128(sb + R_MEM + warp * 2048 + i * 512 + (g >> 1) * 128 + t * 32 + (g & 1) * 16, m0[i]);
  auto probe = [&](int n, int cnt) {
    if (lane == 0) {
#pragma unroll 1
      for (int i = role >> 7; i < cnt; i++) {
        const int k = (i ^ wg) & 1;
        const unsigned t0 = clk();
        uint32_t v; asm volatile("atom.relaxed.gpu.global.exch.b32 %0, [%1], 0;" : "=r"(v) : "l"(probe_at(n) + k * 4096) : "memory");
        if (v == 0) asm volatile("red.shared.min.u32 [%0], %1;" :: "r"(sb + R_T + (n ? w4 * 8 : 32) + k * 4), "r"(clk() - t0) : "memory");
      }
    }
    __syncwarp();
  };
#pragma unroll 1
  for (int n = 0; n < 2; n++) {
    probe(0, n ? NPB : NPB0);
    asm volatile("{.reg .pred p; cp.async.bulk.wait_group 0; setp.eq.u32 p, %1, 97; @p red.relaxed.gpu.global.add.u32 [%0], 1;}" :: "l"(&gx->ctr[h]), "r"(tid ^ n ^ (1 - n) << 9) : "memory");
    PT(3 + 3 * n);
    wait_x(n, 2);
    PT(4 + 3 * n);
    if (wg == 0) {
      wait_x(n, 3);
      project_qk(IC<0>{}, IC<16>{}, IC<1>{}, [](int) {});
      project_v(IC<0>{}, IC<32>{}, [](int) {});
      wg_wait<0>(); keep(aq); keep(av);
      park();
      fin_v();
      fence_async();
    } else {
      wait_x(n, 0); wait_x(n, 1);
      project_qk(IC<32>{}, IC<48>{}, IC<1>{}, [](int) {});
      project_qk(IC<16>{}, IC<32>{}, IC<0>{}, [](int) {});
      project_qk(IC<0>{}, IC<16>{}, IC<0>{}, [](int) {});
      mbar_spin(sb + B_PK, n, it);
      unpark();
      wg_wait<0>(); keep(aq);
      fin_qk();
      fence_async();
    }
    __syncthreads();
    if (tid == 0 && n) stx32(&gx->S[role], 1 + (HOME & 2 && lds32(sb + R_T + 36) < lds32(sb + R_T + 32)));
    PT(5 + 3 * n);
    if (tid == 96 && n == 0) store_stage(0);
    if (tid == 128 && n == 0) {
#pragma unroll 1
      for (int i = 0; i < 4; i++) issue_x(1, i);
    }
    if (warp == 5 && n == 1) {
#pragma unroll 1
      while (__any_sync(0xffffffffu, ldx32(&gx->ctr[h]) < 4) && ++it < SPIN_LIMIT) {}
      if (elect()) issue_kqv(0);
    }
    __syncwarp();
  }
  mbar_spin(sb + B_W, 1, it);
  PT(9);
#pragma unroll
  for (int i = 0; i < 4; i++) {
    uint32_t f[4][4];
    const uint32_t a = sb + R_WO + warp * 8192 + i * 2048;
#pragma unroll
    for (int q = 0; q < 4; q++) ldsm4t(f[q], a + (LW ^ (q << 5)));
    __syncwarp();
#pragma unroll
    for (int q = 0; q < 4; q++) sts128(a + q * 512 + L16, f[q]);
  }
  if (NPC) probe(1, NPC);
  {
    const int o = 32 * w4 + 16 * wg + 4 * t + j;
    uint32_t v;
#pragma unroll 1
    while (__any_sync(0xffffffffu, (v = ldx32(&gx->S[o])) == 0) && ++it < SPIN_LIMIT) {}
    asm volatile("st.shared.u64 [%0], %1;" :: "r"(sb + R_DST + wg * 1024 + w4 * 256 + lane * 8), "l"(xb + offsetof(Xchg, B) + o * 8192 + (v >> 1) * 4096 + h * 128 + ((g ^ h) & 7) * 16) : "memory");
  }
  if (wg == 0) {
    const uint64_t cd = reinterpret_cast<uint64_t>(xb + (offsetof(Xchg, C) + j * 8192 + h * 128 + w4 * 32 + (L16 & 16) * 256 + (L16 & 64) / 4 + (L16 >> 7) * 4));
    sts128(uW + R_RD + L16, (uint32_t)cd, (uint32_t)(cd >> 32), sb + R_MEM + (L16 & 112) * 8 + (L16 >> 8) * 1024 + ((w4 * 32 + ((L16 >> 3) & 16)) ^ (L16 & 112)),
           (L16 >> 6) == (h & 3) * 2 + ((h >> 2) & 1) ? 0xFFFE0000u : 0xFFFFFFFFu);
  }
  if (tid == 0) sts32(sb + B_DUE + 8, gtime() & ~31u);
  PT(10);
  mbar_spin(sb + B_KV, 0, it);
  PT(11);
  if (tid < 4) sts32(sb + B_ONE + tid * 4, 0x3F803F80u);
  if (warp == 1) { const uint32_t e = g >> 1 == t ? 0x3F80u << (16 * (g & 1)) : 0u; sts128(sb + R_ID + L16, e, 0, 0, e); }
  __syncthreads();
  {
    const uint32_t kb = lds32(sb + R_T + 36) < lds32(sb + R_T + 32);
    uS = uni((HOME & 4 ? (__popc(((offsetof(Xchg, B) / 4096 + 2 * role) ^ (offsetof(Xchg, C) / 4096 + 2 * w4)) & 0xb3) ^ kb) & 1 : lds32(sb + R_T + w4 * 8 + 4) < lds32(sb + R_T + w4 * 8)) * 4096 + kb);
  }

  const float sc = 0.08838834764831845f * 1.4426950408889634f;
  uint8_t* const xa = xb + uni(h * 16384);
  const uint32_t uA = uni(wg ? (w4 >> 1) * 2048 + j * 512 + (w4 & 1) * 256 : 8192 + (4 * (j >> 1) + w4) * 512 + jh * 256);
  const uint32_t uP2 = uni(sb + R_P + w4 * 256);
  uint32_t nc = 1;
  uint32_t ma;
  const uint8_t* adst;
  auto pin_mem = [&]() { adst = pinp(xa + uA + L16 / 2); ma = pin(uMem + (L16 & 384) + (L16 & 48) * 2 + (L16 & 64) / 4); };
  pin_mem();

#pragma unroll 1
  for (int s = 0;; nc++) {
    const uint32_t tag = (s + 1) & 1;
    auto fresh = [&]() { L16 += (uint32_t)it >> 31; };
    auto get_due = [&]() { return lds32(sb + B_DUE + 4 + tag * 4); };
    float c[4][4], r4[4];
    auto fold = [&]() {
#pragma unroll
      for (int i = 0; i < 4; i++) r4[i] = ((c[0][i] + c[1][i]) + c[2][i]) + c[3][i];
    };
    auto mma4 = [&](int n, const uint32_t (&b0)[4], const uint32_t (&b1)[4]) {
      mma_h(c[0], w[n + 2], b1, 0); mma_h(c[1], w[n + 3], b1, 1); mma_h(c[2], w[n], b0, 0); mma_h(c[3], w[n + 1], b0, 1);
    };
    auto xpos = [&](int pos, int wp) {
      if ((pos == X0 || pos == X1 || pos == X2 || pos == X3) && warp == wp && s + 1 < NSEG && elect()) {
        const int z = (uint32_t)it >> 31;
        if (pos == X2) issue_x(s + 2, 2 + z);
        if (pos == X3) issue_x(s + 2, 3 + z);
        if (pos == X1) issue_x(s + 2, 1 + z);
        if (pos == X0) issue_x(s + 2, z);
      }
      __syncwarp();
    };
    if (wg == 0) {
      mbar_spin(sb + B_C, nc & 1, it);
      TS(13);
      uint32_t b[16][4], tg[4];
#pragma unroll
      for (int i = 0; i < PD0; i++) { lds128(b[i], ma + i * 512); __syncwarp(); }
      sched();
      zero(c);
#pragma unroll
      for (int i = 0; i < 8; i++) {
        const int k = i ^ 1;
        mma_h(c[0], w[2 * k], b[k], 0); mma_h(c[1], w[2 * k + 1], b[k], 1);
        if (i < 2 * NV0) { mma_h(c[2], w[16 + 2 * k], b[k], 0); mma_h(c[3], w[17 + 2 * k], b[k], 1); }
        sched();
        if ((i & 1) && i + PD0 < 9) { lds128(b[i + PD0 - 1], ma + (i + PD0 - 1) * 512); __syncwarp(); lds128(b[i + PD0], ma + (i + PD0) * 512); sched(); }
        if (i == TGP) {
          fresh();
#pragma unroll
          for (int k = 0; k < 4; k++) tg[k] = lds32((uW * 4 + L16) * 2 + (L16 >> 6) * 4 + (R_MEM + k * 1024 - 7 * sb));
          sched();
        }
      }
#pragma unroll
      for (int i = 0; i < 4; i++) { r4[i] = c[0][i] + c[1][i]; c[0][i] = c[1][i] = 0.f; }
      sts128f(uW + R_RED + L16, r4);
      TS(1);
      const uint32_t old = bar_or(4, (dif2(tg[0], tg[1], s) | dif2(tg[2], tg[3], s)) & (s > 0));
      TS(0);
#pragma unroll
      for (int i = 0; i < 2 * NV0; i++) { lds128(b[8 + i], (ma ^ 4096) + i * 512); __syncwarp(); }
      sched();
#pragma unroll
      for (int i = NV0; i < 8; i++) {
        if (VB && i == VB) bar_sync(7, 256);
        mma4(16 + 4 * i, b[2 * i], b[2 * i + 1]);
        if (i < 7) sched();
        if (i < 4) { lds128(b[8 + 2 * i], (ma ^ 4096) + i * 1024); __syncwarp(); lds128(b[9 + 2 * i], (ma ^ 4096) + i * 1024 + 512); sched(); }
      }
      fold();
      asm volatile("{.reg .pred p; setp.eq.u32 p, %3, 0; @p st.relaxed.gpu.global.v2.b32 [%0], {%1,%2};}" :: "l"(adst), "r"((pack2(r4[0], r4[1]) & ~1u) | tag), "r"(pack2(r4[2], r4[3])), "r"(old) : "memory");
      sched();
      const unsigned tpub = clk();
      if (__any_sync(0xffffffffu, old) && nc < NC_MAX) {
        bar_sync(3, 256);
        issue_c(gtime());
        continue;
      }
      TS(3);
      xpos(0, 0);
      const uint32_t due = get_due();
      uint32_t vf[4][4], vm[2][4], p[4], pm, o[4];
      const uint32_t va = sb + R_V + (w4 >> 1) * 8192 + (w4 & 1) * 2048 + L16;
#pragma unroll
      for (int i = 0; i < 4; i++) {
        uint32_t q[4]; lds128(vf[i], va + i * 512); lds128(q, va + 4096 + i * 512);
#pragma unroll
        for (int e = 0; e < 4; e++) vf[i][e] = hadd2(vf[i][e], q[e]);
      }
      const uint32_t pa = pin(sb + R_P + (L16 >> 1));
      const uint8_t* vsrc = pinp(xa + 8192 + w4 * 1024 + L16 / 2);
      uint32_t one[4];
      lds128(one, sb + B_ONE);
      auto pv_x = [&]() {
        zero(c);
        mma_a(c[2], one, p[0], p[1]);
        mma_a(c[0], vf[0], p[0], p[1]); mma_a(c[1], vf[2], p[0], p[1]);
        sched();
        mma_a(c[2], one, p[2], p[3]);
        mma_a(c[0], vf[1], p[2], p[3]); mma_a(c[1], vf[3], p[2], p[3]);
        sched();
      };
      auto pv_m = [&]() {
        mma1688(c[2], one[0], one[1], pm);
        mma_a(c[0], vm[0], pm, pm);
        sched();
        mma_a(c[1], vm[1], pm, pm);
      };
      auto norm = [&]() {
        const float n0 = rcp(c[2][0]), n1 = rcp(c[2][1]);
#pragma unroll
        for (int i = 0; i < 4; i++) o[i] = pack2(c[i >> 1][2 * (i & 1)] * n0, c[i >> 1][2 * (i & 1) + 1] * n1);
        return ((__float_as_uint(c[2][0]) - 0x1F800000u) | (__float_as_uint(c[2][1]) - 0x1F800000u)) >> 30;
      };
      auto load_m = [&](int x) { const float2 e0 = lds64f(pa + 512 + x * 1024), e1 = lds64f(pa + 768 + x * 1024); pm = pack2(e0.x * e1.x, e0.y * e1.y); };
      auto attend_max = [&](int x) {
        float2 sv[6];
#pragma unroll
        for (int i = 0; i < 6; i++) sv[i] = lds64f(pa - 3072 + x * 1536 + i * 256);
        sv[4].x += sv[5].x; sv[4].y += sv[5].y;
        const int dq = (int)(L16 >> 6) - (int)((L16 >> 3) & 6) + 8 * j;
        float m = fmaxf(sv[4].x, sv[4].y);
#pragma unroll
        for (int i = 0; i < 4; i++) {
          if (x && 8 * i > dq) sv[i].x = -INFINITY;
          if (x && 8 * i + 1 > dq) sv[i].y = -INFINITY;
          m = fmaxf(m, fmaxf(sv[i].x, sv[i].y));
        }
        m = fmaxf(m, __shfl_xor_sync(0xffffffffu, m, 1));
        m = fmaxf(m, __shfl_xor_sync(0xffffffffu, m, 2));
#pragma unroll
        for (int i = 0; i < 5; i++) (i < 4 ? p[i] : pm) = pack2(ex2(sv[i].x - m), ex2(sv[i].y - m));
        pv_x(); pv_m(); norm();
      };
      uint32_t tq[4];
      auto get_t = [&]() {
        tq[0] = tq[1] = tq[2] = tq[3] = 0;
        asm volatile("{.reg .pred p; setp.eq.u32 p, %5, 0; @p ld.relaxed.gpu.global.v4.b32 {%0,%1,%2,%3}, [%4];}"
                     : "+r"(tq[0]), "+r"(tq[1]), "+r"(tq[2]), "+r"(tq[3]) : "l"(xb + offsetof(Xchg, T) + L16 * 8), "r"(warp) : "memory");
      };
      delay_until(tpub + DLY_V);
      wait_time(due + NS_V);
      TS(4);
      ldx(vm, vsrc);
      sched();
      xpos(2, 2);
      auto store_kqv = [&]() {
        fence_async();
        if (!(EXP & 4))
          asm volatile("{.reg .pred p; elect.sync _|p, 0xffffffff; @p cp.async.bulk.global.shared::cta.bulk_group [%0], [%1], 2048; cp.async.bulk.commit_group;}"
                       :: "l"(g_kqv[(s + 1) & 3][role] + w4 * 128), "r"(sb + R_STAGE + w4 * 2048) : "memory");
      };
      if (SPOS == 2) store_kqv();
      sched();
      bar_sync(5, 256);
      ldsm4(p, sb + R_P + L16);
      load_m(0);
      pv_x();
      ldsm4(p, sb + R_P + 1024 + L16);
      pv_m();
      const uint32_t r = norm(), tl = after(tag, c[2][0], (uint32_t)it >> 31);
      const bool redo = __any_sync(0xffffffffu, r | ((dif2(vm[0][0], vm[0][2], tl) | dif2(vm[1][0], vm[1][2], tl)) & 1));
      TS(6);
      stsm4t(uW + R_O + L16, o[0], o[1], o[2], o[3]);
      bar_arrive_unless(6, redo);
      sched();
      if (TQL == 7) get_t();
      TS(7);
      pv_x();
      if (rare(redo)) retry<2>(vm, vsrc, tag, it);
      bar_sync(8, 256);
      load_m(1);
      pv_m();
      if (rare(__any_sync(0xffffffffu, norm()) || redo)) {
        fresh();
#pragma unroll 1
        for (int x = !redo; x < 2; x++) {
          attend_max(x);
          if (x == 0) { stsm4t(uW + R_O + L16, o[0], o[1], o[2], o[3]); bar_arrive(6, 256); }
        }
      }
      TS(8);
      if (TQL == 8) get_t();
      const bool xok = mbar_test(sb + B_X + 16, s & 1) & mbar_test(sb + B_X + 24, s & 1);
      xpos(4, 2);
      fresh();
      const uint32_t ob = uni(sb + R_MEM + 4096 + w4 * 1024);
      stsm4t(ob + (L16 & 112) * 4 + (((L16 >> 3) ^ (L16 >> 1)) & 48), o[0], o[1], o[2], o[3]);
      __syncwarp();
      uint32_t rd[4];
      lds128(rd, uW + R_RD + L16);
      lds128(o, ob + (L16 ^ ((L16 >> 3) & 48)));
      auto put_o = [&]() {
        *reinterpret_cast<uint4*>(reinterpret_cast<uint8_t*>(g_ox) + (((s * SEG + 8 * j) * HD + h * DH + 32 * w4) * 2 + (L16 >> 6) * (HD * 2) + (L16 & 48))) = make_uint4(o[0], o[1], o[2], o[3]);
      };
      if (s + 1 == NSEG) { put_o(); asm volatile("cp.async.bulk.wait_group 0;" ::: "memory"); break; }
      asm volatile("cp.async.bulk.wait_group 0;" ::: "memory");
      if (elect()) stx32(xa + 4096 + j * 16 + w4 * 4, s + 1);
      __syncwarp();
      if (rare(!xok)) { wait_x(s + 2, 3); wait_x(s + 2, 2); }
      TS(9);
      fresh();
      const uint32_t e = due | ((s + 1) & 31);
      project_qk(IC<0>{}, IC<NQ>{}, IC<1>{}, [&](int n) {
        if (n == OXPOS) { __syncwarp(); put_o(); __syncwarp(); }
        if (n == TQP) { __syncwarp(); tq[0] = dif2v(tq[0], tq[1], e) | dif2v(tq[2], tq[3], e); __syncwarp(); }
      });
      if (NPA) project_v(IC<0>{}, IC<NPA>{}, [](int) {});
      TS(2);
      if (warp == 0) {
        uint32_t last = due, nx = NS_P + ALT * tag;
        if (rare(__any_sync(0xffffffffu, tq[0]))) {
          const uint32_t ref = gtime();
#pragma unroll 1
          do ldx128(o, xb + offsetof(Xchg, T) + L16 * 8); while (any_bit(or3(o[0] - s - 1, o[1] - s - 1, o[2] - s - 1), o[3] - s - 1, 30) && ++it < SPIN_LIMIT);
          const int d = max(max((int)(o[0] - ref), (int)(o[1] - ref)), max((int)(o[2] - ref), (int)(o[3] - ref)));
          last = (ref + __reduce_max_sync(0xffffffffu, d)) & ~31u;
          if (last != due) nx += NS_X;
        }
        const uint32_t bdue = last + NS_B;
        if (s < 4) { last += (MG_Y >> 8 * s & 255) * 32; nx += (MG_Z >> 8 * s & 255) * 32; }
        sts32(sb + B_DUE, last);
        sts32(sb + B_DUE + 8 - tag * 4, last + nx);
        fetch4k(sb + R_MEM, my_b(), sb + B_B, bdue);
        LOG(13, tl - last);
        LOG(9, last);
      }
      if (NQ < 16) project_qk(IC<NQ>{}, IC<16>{}, IC<0>{}, [](int) {});
      project_v(IC<NPA>{}, IC<NPRE>{}, [](int) {});
      const uint32_t ba = rd[2], msk = rd[3];
      const uint8_t* cdst = reinterpret_cast<const uint8_t*>(rd[0] | (uint64_t)rd[1] << 32);
      TS(14);
      mbar_spin(sb + B_B, s & 1, it);
      TS(10);
      uint32_t bq[2][4];
      auto sum_b = [&]() {
        ldsm4t(bq[0], ba); ldsm4t(bq[1], ba + 2048);
        sched();
#pragma unroll
        for (int i = 0; i < 8; i++) c[i >> 2][i & 3] = 0.f;
        mma_a(c[0], bq[0], 0x3F803F80u, 0x3F803F80u); mma_a(c[1], bq[1], 0x3F803F80u, 0x3F803F80u);
        const uint32_t t2 = tag * 0x10001u;
        const bool old = any_bit(or3(dif2(bq[0][0], bq[0][1], t2), dif2(bq[0][2], bq[0][3], t2), dif2(bq[1][0], bq[1][1], t2)), dif2(bq[1][2], bq[1][3], t2), L16 < 64 ? 0x10001u : 0u);
        const uint32_t T = (tag << 16) & ~msk, u = ((__float_as_uint(c[0][0] + c[1][0]) + ((0x10000u & ~msk) - T)) & msk) | T;
        asm volatile("{.reg .pred p; setp.eq.u32 p, %2, 0; @p st.relaxed.gpu.global.b32 [%0], %1;}"
                     :: "l"(cdst), "r"(pack2(__uint_as_float(u), c[0][2] + c[1][2])), "r"((uint32_t)(old || (L16 & 32))) : "memory");
        return old;
      };
      if (rare(sum_b())) {
#pragma unroll 1
        do {
          const uint8_t* p = xb + (my_b() + (ba - sb - R_MEM));
          ldx128(bq[0], p); ldx128(bq[1], p + 2048);
          sts128(ba, bq[0]); sts128(ba + 2048, bq[1]);
          __syncwarp();
          it += INC_B;
        } while (sum_b() && it < SPIN_LIMIT);
      }
      sched();
      TS(11);
      bar_arrive(0, 256);
      const unsigned tc = clk();
      const uint32_t cdue = lds32(sb + B_DUE) + NS_C;
      if (warp == 3) LOG(11, gtime() - cdue);
      fresh();
      wg_wait<0>(); keep(aq); keep(av);
      park();
      if (NPRE < 32) project_v(IC<NPRE>{}, IC<32>{}, [](int) {}); else fin_v();
      TS(12);
      delay_until(tc + DLY_C);
      issue_c(cdue);
      TS(5);
      LOG(warp, it);
      pin_mem();
      if (NPRE < 32) { wg_wait<0>(); keep(av); fin_v(); }
      if (!(EXP & 2)) mbar_spin(sb + B_KV, tag, it);
      TS(15);
    } else {
      uint32_t kf[8][4];
      auto load_k = [&]() {
        const uint32_t ka = sb + R_K + w4 * 1024 + (L16 & 112) + (L16 & 128) * 4 + (L16 & 256);
#pragma unroll
        for (int i = 0; i < 8; i++) ldsm4(kf[i], ka + (i >> 1) * 2048 + (i & 1) * 128);
      };
      auto put_p = [&](int x, uint32_t old, uint32_t again) {
        float e[4];
        const int dq = (int)((L16 >> 3) & 6) + 8 * j - (int)(L16 >> 6) - 16 * w4;
#pragma unroll
        for (int i = 0; i < 4; i++) { r4[i] = fmaf(c[3][i], sc, fmaf(c[2][i], sc, fmaf(c[0][i] + c[1][i], sc, __uint_as_float(i == 3 ? 0u - old : 0u)))); e[i] = x && dq + (i & 1) < 8 * (i >> 1) ? 0.f : ex2(r4[i]); }
        stsm2t(uP2 + x * 1024 + L16, pack2(e[0], e[1]), pack2(e[2], e[3]), again);
      };
      auto put_s = [&](int x) {
#pragma unroll
        for (int i = 0; i < 4; i++) sts32f(uW + R_S + x * 1536 + (L16 & 48) * 4 + (L16 >> 6) * 4 + (i & 1) * 32 + (i >> 1) * 256, r4[i]);
      };
      auto load_q = [&](uint32_t (&q)[4], uint32_t off) { ldsm4(q, sb + R_Q + (L16 & 112) + (L16 & 128) * 2 + (L16 >> 8) * 128 + off); };
      mbar_spin(sb + B_C, nc & 1, it);
      TS(13);
      float4 o4;
      uint32_t id[4], old;
      {
        uint32_t b[24][4];
#pragma unroll
        for (int i = 0; i < 2 * PD1; i++) { lds128(b[i], ma + i * 512); __syncwarp(); }
        sched();
        zero(c);
#pragma unroll
        for (int i = 0; i < 12; i++) {
          mma4(4 * i, b[2 * i], b[2 * i + 1]);
          if (i < 11) sched();
          if (i + PD1 < 12) { const int k = i + PD1; const uint32_t a = (ma ^ (k >> 2 << 12)) + (k & 3) * 1024; lds128(b[2 * k], a); __syncwarp(); lds128(b[2 * k + 1], a + 512); sched(); }
          if (i == RJ) { lds128(id, sb + R_ID + L16); sched(); }
          if (i == RI) { old = bar_or(4, 0); o4 = lds128f(uW + R_RED + L16); sched(); }
        }
      }
      TS(0);
      {
        float e[4] = {o4.x, o4.y, o4.z, o4.w};
#pragma unroll
        for (int i = 0; i < 4; i++) { r4[i] = (((e[i] + c[0][i]) + c[1][i]) + c[2][i]) + c[3][i]; e[i] = 0.f; }
        mma_a(e, id, pack2(r4[0], r4[1]), pack2(r4[2], r4[3]));
        sched();
        if (VB) bar_arrive(7, 256);
        sched();
        asm volatile("{.reg .pred p; setp.eq.u32 p, %3, 0; @p st.relaxed.gpu.global.v2.b32 [%0], {%1,%2};}" :: "l"(adst),
                     "r"((__byte_perm(__float_as_uint(e[0]), __float_as_uint(e[1]), 0x7632) & ~1u) | tag), "r"(__byte_perm(__float_as_uint(e[2]), __float_as_uint(e[3]), 0x7632)), "r"(old) : "memory");
        sched();
      }
      const unsigned tpub = clk(), now = gtime(), due = get_due();
      if (__any_sync(0xffffffffu, old) && nc < NC_MAX) { bar_sync(3, 256); continue; }
      TS(2);
      const uint8_t* asrc = pinp(adst + ((warp == 7) * 1024 - (int)uA));
      fresh();
      uint32_t wo[32][4];
      bool xok;
      auto reload = [&]() {
        sched();
#pragma unroll
        for (int i = RE0 + RE1; i < NSW; i++) lds128(w[i], uW + R_WC + L16 + i * 2048);
        sched();
      };
      auto out_proj = [&]() {
        uint32_t b[4][4];
        float d[4][4];
        uint8_t* dst[2];
        const uint32_t da = pin(uP2 + (R_DST - R_P) + L16 / 2);
        sched();
        TS(7);
        bar_sync(6, 256);
#pragma unroll
        for (int i = 0; i < 4; i++) { ldsm4(b[i], sb + R_O + i * 512 + L16); __syncwarp(); }
        sched();
        auto put_b = [&](uint8_t* a, const float (&e)[4][4]) {
          stx128(a, (pack2(e[0][0] + e[2][0], e[0][1] + e[2][1]) & ~1u) | tag, pack2(e[0][2] + e[2][2], e[0][3] + e[2][3]),
                 pack2(e[1][0] + e[3][0], e[1][1] + e[3][1]), pack2(e[1][2] + e[3][2], e[1][3] + e[3][3]));
        };
        zero(c); zero(d);
#pragma unroll
        for (int i = 0; i < 32; i++) {
          mma_h(i < 16 ? c[i & 3] : d[i & 3], wo[i], b[(i >> 2) & 3], (i >> 1) & 1);
          if (i >= LW0 && NB1 + i - LW0 < 32) { load_wo(wo, (NB1 + i - LW0) ^ 1, ((NB1 + i - LW0) ^ 1) + 1); __syncwarp(); }
          if (i == DL0 || i == DL1) asm volatile("ld.shared.u64 %0, [%1];" : "=l"(dst[i > DL0]) : "r"(da + (i > DL0) * 1024) : "memory");
          if (i >= 16 && i < 16 + RE0) { lds128(w[i - 16], uW + R_WC + L16 + (i - 16) * 2048); __syncwarp(); }
          if (i >= RP1 && i < RP1 + RE1) { lds128(w[i - RP1 + RE0], uW + R_WC + L16 + (i - RP1 + RE0) * 2048); __syncwarp(); }
          if (i == 22) put_b(dst[0], c);
          if ((i & 1) && (i < 20 || i > 22)) sched();
        }
        put_b(dst[1], d);
        sched();
        TS(6);
      };
      if (warp < 6) {
        delay_until(tpub + DLY_A);
        const int it0 = it;
        bool redo;
#pragma unroll 1
        do {
          uint32_t q[4][4], y[4];
          float d[4][4];
          wait_time(due);
          TS(4);
          ldx(q, asrc);
          sched();
          load_k();
          uint32_t qx[4][4];
#pragma unroll
          for (int i = 0; i < 4; i++) load_q(qx[i], i * 512);
          sched();
          load_wo(wo, 0, NE4);
          sched();
          zero(c);
#pragma unroll
          for (int i = 0; i < 8; i++) mma_h(c[i & 3], kf[i], qx[i >> 1], i & 1);
          put_p(1, 0, 0); put_s(1);
          sched();
          load_wo(wo, NE4, NA4);
          sched();
          zero(c); zero(d);
#pragma unroll
          for (int i = 0; i < 8; i++) {
            if (i == 0) { y[0] = dif2v(q[0][0], q[0][2], q[1][0]); sched(); }
            if (i == 3) { y[1] = dif2v(q[1][2], q[2][0], q[2][2]); sched(); }
            if (i == 6) { y[2] = dif2v(q[3][0], q[3][2], tag); sched(); }
            mma_h(i % 6 < 2 ? c[2 + i % 6] : d[i - 2], kf[i], q[i >> 1], i & 1);
            if (i == 2 || i == 5 || i == 7) sched();
          }
          y[0] = or_and(or3(y[0], y[1], dif2v(q[0][0], q[2][0], tag)), y[2], it < SPIN_LIMIT);
#pragma unroll
          for (int i = 0; i < 4; i++) { c[0][i] = d[0][i] + d[1][i]; c[1][i] = d[2][i] + d[3][i]; }
          put_p(0, y[0], it - it0);
          TS(5);
          bar_sync_unless(5, it - it0);
          redo = __any_sync(0xffffffffu, y[0]);
          it += INC_A;
        } while (redo);
        it -= INC_A;
        put_s(0);
        bar_arrive(8, 256);
        load_wo(wo, NA4, NB1);
        out_proj();
        if (warp == 4) LOG(12, tb);
      } else {
        uint32_t qx[2][4], q[4][4];
        if (warp == 6) {
          const uint32_t t1 = (now & ~31u) + NS_M;
          LOG(10, now - due);
          if (elect()) stx32(&gx->T[h][j], ((int)(t1 - due) > 0 ? t1 + NS_PEN : due) | ((s + 1) & 31));
          __syncwarp();
        }
        auto score = [&](const uint32_t (&a0)[4], const uint32_t (&a1)[4]) {
          zero(c);
#pragma unroll
          for (int i = 0; i < 4; i++) mma_h(c[i], i < 2 ? a0 : a1, q[2 + (i >> 1)], i & 1);
        };
        auto put_m = [&](uint32_t a, uint32_t old, uint32_t again) {
#pragma unroll
          for (int i = 0; i < 2; i++) { r4[i] = fmaf(c[3][2 + i], sc, fmaf((c[0][i] + c[1][2 + i]) + c[2][i], sc, __uint_as_float(i ? 0u - old : 0u))); r4[2 + i] = fmaf(r4[i] * 0x1p122f, 0.f, ex2(r4[i])); }
          asm volatile("{.reg .pred p; setp.eq.u32 p, %3, 0; @p st.shared.v2.f32 [%0], {%1,%2};}" :: "r"(a), "f"(r4[2]), "f"(r4[3]), "r"(again) : "memory");
        };
        delay_until(tpub + DLY_A);
        const uint32_t sa = sb + R_S + 512 + w4 * 256 + (L16 >> 1);
        const int it0 = it;
        bool redo;
#pragma unroll 1
        do {
          wait_time(due);
          TS(4);
          ldx<4, 2048>(q, asrc);
          sched();
          load_q(qx[0], (w4 & 1) * 1024); load_q(qx[1], (w4 & 1) * 1024 + 512);
          load_wo(wo, 0, NA6);
          sched();
          score(q[0], q[1]);
          sched();
          const uint32_t y = or_and(or3(dif2v(q[0][0], q[0][2], tag), dif2v(q[1][0], q[1][2], tag), dif2v(q[2][0], q[2][2], tag)), dif2v(q[3][0], q[3][2], tag), it < SPIN_LIMIT);
          put_m(sa + 2560, y, it - it0);
          TS(5);
          bar_arrive_unless(5, it - it0);
          redo = __any_sync(0xffffffffu, y);
          it += INC_A;
        } while (redo);
        it -= INC_A;
        sts64f(sa, r4[0], r4[1]);
        score(qx[0], qx[1]);
        put_m(sa + 3584, 0, 0);
        sts64f(sa + 1536, r4[0], r4[1]);
        bar_arrive(8, 256);
        load_wo(wo, NA6, NB1);
        out_proj();
      }
      TS(8);
      if (s + 1 == NSEG) break;
      wait_x(s + 2, 2);
      TS(9);
      fresh();
      if (N1) project_qk(IC<32>{}, IC<32 + N1>{}, IC<1>{}, [](int) {});
      TS(10);
      xpos(6, 6);
      uint32_t fl = s + 1;
      if (warp == 5) { wait_time(due + NS_F); fl = ldx32(xa + 4096 + ((L16 >> 2) & 60)); }
      reload();
      TS(14);
      pin_mem();
      wait_x(s + 2, 1); wait_x(s + 2, 0);
      if (warp == 5) {
#pragma unroll 1
        while (__any_sync(0xffffffffu, fl != s + 1) && !(EXP & 4) && ++it < SPIN_LIMIT) fl = ldx32(xa + 4096 + ((L16 >> 2) & 60));
        wait_time(due + (NS_B + NS_K));
        if (!(EXP & 2) && elect()) issue_kqv(s + 1);
        __syncwarp();
      }
      if (PFD && warp == 6 && s + PFD < NSEG && elect())
        asm volatile("cp.async.bulk.prefetch.L2.global [%0], 2048;" :: "l"(xin + ((s + PFD) * SEG + ((role + 4 * (role >> 5)) & 31)) * DM) : "memory");
      __syncwarp();
      TS(11);
      LOG(warp, it);
      if (warp == 4) LOG(8, nc);
      bar_sync(0, 256);
      if (N1 < 16) project_qk(IC<32 + N1>{}, IC<48>{}, IC<!N1>{}, [](int) {});
      project_qk(IC<16>{}, IC<32>{}, IC<0>{}, [&](int n) { if ((n & 15) == XWPOS) { __syncwarp(); xok = mbar_test(sb + B_PK, s & 1); __syncwarp(); } });
      if (rare(!xok)) mbar_spin(sb + B_PK, s & 1, it);
      unpark();
      project_qk(IC<0>{}, IC<16>{}, IC<0>{}, [](int) {});
      TS(12);
      wg_wait<0>(); keep(aq);
      TS(1);
      fin_qk();
      TS(15);
    }
    s++;
  }
  if (it >= SPIN_LIMIT || nc >= NC_MAX) g_err = 2;
}

typedef CUresult (*EncodeFn)(CUtensorMap*, CUtensorMapDataType, cuuint32_t, void*, const cuuint64_t*, const cuuint64_t*, const cuuint32_t*,
                             const cuuint32_t*, CUtensorMapInterleave, CUtensorMapSwizzle, CUtensorMapL2promotion, CUtensorMapFloatOOBfill);
static void make_map(EncodeFn fn, CUtensorMap* m, const void* p, uint64_t cols, uint64_t rows, uint64_t pitch, uint32_t bc, uint32_t br, CUtensorMapSwizzle sw) {
  cuuint64_t dims[2] = {cols, rows}, strides[1] = {pitch * 2};
  cuuint32_t box[2] = {bc, br}, es[2] = {1, 1};
  fn(m, CU_TENSOR_MAP_DATA_TYPE_BFLOAT16, 2, const_cast<void*>(p), dims, strides, box, es, CU_TENSOR_MAP_INTERLEAVE_NONE, sw,
     CU_TENSOR_MAP_L2_PROMOTION_L2_256B, CU_TENSOR_MAP_FLOAT_OOB_FILL_NONE);
}

extern "C" void kernel_launch(void* const* d_in, const int* in_sizes, int n_in, void* d_out, int out_size) {
  const bf16* Ax = (const bf16*)d_in[0]; const bf16* mem0 = (const bf16*)d_in[1];
  const bf16* Wq = (const bf16*)d_in[2]; const bf16* Wk = (const bf16*)d_in[3]; const bf16* Wv = (const bf16*)d_in[4];
  const bf16* Wo = (const bf16*)d_in[5];
  const bf16* Bx = (const bf16*)d_in[7]; const bf16* wr = (const bf16*)d_in[8]; const bf16* wi = (const bf16*)d_in[9];
  bf16* out = (bf16*)d_out;

  void* fp = nullptr; cudaDriverEntryPointQueryResult qr;
  cudaGetDriverEntryPoint("cuTensorMapEncodeTiled", &fp, cudaEnableDefault, &qr);
  EncodeFn fn = (EncodeFn)fp;
  void *kqv, *ox, *xr;
  cudaGetSymbolAddress(&xr, g_xraw);
  cudaGetSymbolAddress(&kqv, g_kqv); cudaGetSymbolAddress(&ox, g_ox);
  const CUtensorMapSwizzle S128 = CU_TENSOR_MAP_SWIZZLE_128B, S64 = CU_TENSOR_MAP_SWIZZLE_64B;

  GemmMaps m3; RecMaps mr;
  make_map(fn, &m3.a, ox, HD, S_LEN, HD, 64, 128, S128);
  make_map(fn, &m3.b[0], Wo, DM, HD, DM, 64, 64, S128);
  m3.b[1] = m3.b[0]; m3.b[2] = m3.b[0];
  make_map(fn, &m3.c, out, DM, S_LEN, 2 * DM, 64, 64, S128);
  make_map(fn, &mr.wq, Wq, HD, DM, HD, 32, 256, S64);
  make_map(fn, &mr.wk, Wk, HD, DM, HD, 32, 256, S64);
  make_map(fn, &mr.wv, Wv, HD, DM, HD, 64, 256, S128);
  make_map(fn, &mr.wo, Wo, DM, HD, DM, 64, 128, S128);
  {
    cuuint64_t dims[3] = {64, S_LEN, 16}, strides[2] = {DM * 2, 128};
    cuuint32_t box[3] = {64, 32, 4}, es[3] = {1, 1, 1};
    fn(&mr.x, CU_TENSOR_MAP_DATA_TYPE_BFLOAT16, 3, const_cast<bf16*>(Ax), dims, strides, box, es, CU_TENSOR_MAP_INTERLEAVE_NONE, S128,
       CU_TENSOR_MAP_L2_PROMOTION_L2_256B, CU_TENSOR_MAP_FLOAT_OOB_FILL_NONE);
  }
  for (int i = 0; i < 3; i++) {
    cuuint64_t dims[3] = {128, 32, 512}, strides[2] = {256, 8192};
    cuuint32_t box[3] = {128, i == 0 ? 8u : i == 1 ? 2u : 16u, 4}, es[3] = {1, 1, 1};
    fn(i == 0 ? &mr.k : i == 1 ? &mr.q : &mr.v, CU_TENSOR_MAP_DATA_TYPE_BFLOAT16, 3, kqv, dims, strides, box, es, CU_TENSOR_MAP_INTERLEAVE_NONE,
       CU_TENSOR_MAP_SWIZZLE_NONE, CU_TENSOR_MAP_L2_PROMOTION_L2_256B, CU_TENSOR_MAP_FLOAT_OOB_FILL_NONE);
  }
  {
    cuuint64_t dims[3] = {64, 16, S_LEN}, strides[2] = {128, 2 * DM * 2};
    cuuint32_t box[3] = {64, 16, 2}, es[3] = {1, 1, 1};
    fn(&mr.fo, CU_TENSOR_MAP_DATA_TYPE_BFLOAT16, 3, out + DM, dims, strides, box, es, CU_TENSOR_MAP_INTERLEAVE_NONE, S128,
       CU_TENSOR_MAP_L2_PROMOTION_NONE, CU_TENSOR_MAP_FLOAT_OOB_FILL_NONE);
  }
  constexpr int SM3 = GST * 32768 + 256 + 1024;
  cudaFuncSetAttribute(gemm_kernel<128, GST>, cudaFuncAttributeMaxDynamicSharedMemorySize, SM3);
  cudaFuncSetAttribute(rec_kernel, cudaFuncAttributeMaxDynamicSharedMemorySize, R_TOTAL);

  cudaStream_t st = cudaStreamPerThread;
  Xchg* gx = reinterpret_cast<Xchg*>((reinterpret_cast<uintptr_t>(xr) + 0x1FFFFF) & ~(uintptr_t)0x1FFFFF);
  rec_kernel<<<132, 256, R_TOTAL, st>>>(mr, Ax, mem0, gx, Bx, wr, wi);
  gemm_kernel<128, GST><<<128, 384, SM3, st>>>(m3, 16, 8, 64, 8, reinterpret_cast<uint4*>(gx));
}
```
